```python
import torch

def _softmax(x, axis=-1):
    return torch.softmax(x, dim=axis)
def _gelu(x):
    return torch.nn.functional.gelu(x, approximate="tanh")
def _silu(x):
    return torch.nn.functional.silu(x)
def _sigmoid(x):
    return torch.sigmoid(x)
def _layernorm(x, axis=-1, eps=1e-5):
    m = x.mean(dim=axis, keepdim=True)
    v = x.var(dim=axis, keepdim=True, unbiased=False)
    return (x - m) / torch.sqrt(v + eps)
def _scatter_add(tgt, idx, src, axis=0):
    return tgt.clone().index_add_(axis, idx, src)
def _segment_sum(src, seg, n):
    out = torch.zeros((n,) + src.shape[1:], dtype=src.dtype)
    return out.index_add_(0, seg, src)
def _pad(x, pw):
    flat = tuple(v for pair in reversed(pw) for v in pair)
    return torch.nn.functional.pad(x, flat)

kernel_name = 'gated_mix__linear_kernel_hedgehog__ssm_conv_s4d__prompt'

def setup_inputs():

    _w = (lambda a: (lambda t: t.to(torch.bfloat16) if t.is_floating_point() else t)(torch.as_tensor(a)))
    def _A_setup():
        B, S, D, H = 1, 2048, 512, 32
        Dh = D // H
        return {
            "x": _w((lambda *s: torch.randn(*s, dtype=torch.bfloat16) * 0.05)(B, S, D)),
            "wqkv": _w((lambda *s: torch.randn(*s, dtype=torch.bfloat16) * 0.8)(D, 3 * D)),
            "w_phi": _w((lambda *s: torch.randn(*s, dtype=torch.bfloat16) * 0.8)(H, Dh, Dh) * (Dh ** -0.5)),
            "wo": _w((lambda *s: torch.randn(*s, dtype=torch.bfloat16) * 0.05)(D, D)),
        }
    _A_in = _A_setup()

    def _B_setup():
        Bsz, L, D, N = 1, 2048, 512, 128
        return {
            "u": _w((lambda *s: torch.randn(*s, dtype=torch.bfloat16) * 0.05)(Bsz, L, D)),
            "log_A_real": _w((lambda *s: torch.randn(*s, dtype=torch.bfloat16) * 6.4)(D, N) * 0.5),
            "A_imag": _w((lambda *s: torch.randn(*s, dtype=torch.bfloat16) * 0.05)(D, N) * 3.14),
            "C_real": _w((lambda *s: torch.randn(*s, dtype=torch.bfloat16) * 0.2)(D, N) / N ** 0.5),
            "C_imag": _w((lambda *s: torch.randn(*s, dtype=torch.bfloat16) * 0.2)(D, N) / N ** 0.5),
            "log_dt": _w((lambda *s: torch.randn(*s, dtype=torch.bfloat16) * 0.05)(D) * 0.5 - 4.0),
            "D_skip": _w((lambda *s: torch.randn(*s, dtype=torch.bfloat16) * 0.05)(D)),
        }
    _B_in = _B_setup()

    return {
        "A_x": _A_in["x"],
        "A_wqkv": _A_in["wqkv"],
        "A_w_phi": _A_in["w_phi"],
        "A_wo": _A_in["wo"],
        "B_u": _B_in["u"],
        "B_log_A_real": _B_in["log_A_real"],
        "B_A_imag": _B_in["A_imag"],
        "B_C_real": _B_in["C_real"],
        "B_C_imag": _B_in["C_imag"],
        "B_log_dt": _B_in["log_dt"],
        "B_D_skip": _B_in["D_skip"],
        "gate_w": _w((lambda *s: torch.randn(*s, dtype=torch.bfloat16) * 0.05)(512) * 16.0),
    }

def reference(A_x, A_wqkv, A_w_phi, A_wo, B_u, B_log_A_real, B_A_imag, B_C_real, B_C_imag, B_log_dt, B_D_skip, gate_w):
    def _A_ref(x, wqkv, w_phi, wo):
        B, S, D = x.shape
        H = 32; Dh = D // H
        qkv = (lambda x, *d: x.permute(*d))((x @ wqkv).reshape(B, S, 3, H, Dh), 2, 0, 3, 1, 4)
        q, k, v = qkv[0], qkv[1], qkv[2]
        pq = torch.einsum("bhsd,hdf->bhsf", q, w_phi)
        pk = torch.einsum("bhsd,hdf->bhsf", k, w_phi)
        phi_q = torch.concatenate([_softmax(pq, axis=-1), _softmax(-pq, axis=-1)], axis=-1)
        phi_k = torch.concatenate([_softmax(pk, axis=-1), _softmax(-pk, axis=-1)], axis=-1)
        kv = torch.einsum("bhsf,bhsd->bhfd", phi_k, v)
        z  = torch.einsum("bhsf->bhf", phi_k)
        num = torch.einsum("bhqf,bhfd->bhqd", phi_q, kv)
        den = torch.einsum("bhqf,bhf->bhq", phi_q, z)[..., None] + 1e-6
        o = num / den
        return (lambda x, *d: x.permute(*d))(o, 0, 2, 1, 3).reshape(B, S, D) @ wo

    def _B_ref(u, log_A_real, A_imag, C_real, C_imag, log_dt, D_skip):
        L = u.shape[1]
        dt = torch.exp(log_dt)
        A = -torch.exp(log_A_real) + 1j * A_imag
        C = (C_real + 1j * C_imag) * dt[:, None]
        pos = (lambda x, dt: x.to(dt))(torch.arange(L), log_dt.dtype)
        P = torch.exp((A * dt[:, None])[:, :, None] * pos[None, None, :])
        K = 2.0 * torch.einsum("dn,dnl->dl", C, P).real
        L2 = 2 * L
        u_t = (lambda x, *d: x.permute(*d))(u, 0, 2, 1)
        Kf = (lambda x, *a, **k: torch.fft.rfft(x.float(), *a, **k))(K, L2)
        Uf = (lambda x, *a, **k: torch.fft.rfft(x.float(), *a, **k))(u_t, L2)
        y = (lambda x, *a, **k: torch.fft.irfft(x, *a, **k).to(torch.bfloat16))(Uf * Kf[None, :, :], L2)[:, :, :L]
        y = (lambda x, *d: x.permute(*d))(y, 0, 2, 1)
        return y + u * D_skip[None, None, :]

    x = A_x
    g = _sigmoid((x * gate_w).sum(-1, keepdims=True))
    a = _A_ref(x, A_wqkv, A_w_phi, A_wo)
    b = _B_ref(x, B_log_A_real, B_A_imag, B_C_real, B_C_imag, B_log_dt, B_D_skip)
    return g * a + (1 - g) * b
```

```cpp
#include <cuda_runtime.h>
#include <cuda.h>
#include <cuda_bf16.h>
#include <stdint.h>

typedef __nv_bfloat16 bf16;

__device__ unsigned g_done[32];
__device__ unsigned g_cnt0[32];
__device__ unsigned g_kvcnt[8 * 32];
__device__ float4 g_kv[8 * 4 * 136];
__device__ uint4 g_o[16 * 8 * 32 * 32];
__device__ uint4 g_y[128 * 1024];
__device__ unsigned g_g[2048];
#define STAMP(n)

constexpr int SLOT = 40960;
constexpr int OFF_SP0 = 32768, OFF_SP1 = SLOT + 32768;
constexpr int OFF_P = 2 * SLOT, OFF_V = OFF_P + 32768, OFF_OUT = OFF_V + 32768;
constexpr int OFF_U = 4 * SLOT, U_STRIDE = 4096 + 256;
constexpr int OFF_K = OFF_U + 4 * U_STRIDE, K_STRIDE = 3840;
constexpr int OFF_BUF = OFF_K + 4 * K_STRIDE;
constexpr int OFF_WPHI = OFF_BUF + 4 * 8192;
constexpr int OFF_BAR = OFF_WPHI + 2048;
constexpr int SMEM_BYTES = OFF_BAR + 256;
constexpr int KW_D = 0, KW_2E = 536, KW_2O = 664, KW_3E = 792, KW_3O = 872;
constexpr int BAR_FULL = 0, BAR_WPHI = 4, BAR_WO = 5, BAR_UGO = 6, BAR_DONE = 7, OFF_CNT = 64;
constexpr int SPIN_LIMIT = 1 << 21;

__device__ __forceinline__ uint32_t s2u(const void* p) { return (uint32_t)__cvta_generic_to_shared(p); }
__device__ __forceinline__ void mbar_init(uint32_t b, int c) { asm volatile("mbarrier.init.shared::cta.b64 [%0],%1;" ::"r"(b), "r"(c) : "memory"); }
__device__ __forceinline__ void mbar_expect(uint32_t b, int bytes) { asm volatile("mbarrier.arrive.expect_tx.shared::cta.b64 _,[%0],%1;" ::"r"(b), "r"(bytes) : "memory"); }
__device__ __forceinline__ void mbar_arrive(uint32_t b) { asm volatile("mbarrier.arrive.shared::cta.b64 _,[%0];" ::"r"(b) : "memory"); }
__device__ __forceinline__ void mbar_wait(uint32_t b, int ph) {
    uint32_t ok; int n = 0;
    do {
        asm volatile("{.reg .pred p; mbarrier.try_wait.parity.shared::cta.b64 p,[%1],%2; selp.u32 %0,1,0,p;}" : "=r"(ok) : "r"(b), "r"(ph) : "memory");
        if (++n > SPIN_LIMIT) __trap();
    } while (!ok);
}
__device__ __forceinline__ void tma2d(uint32_t dst, const CUtensorMap* m, int c0, int c1, uint32_t bar) {
    asm volatile("cp.async.bulk.tensor.2d.shared::cluster.global.mbarrier::complete_tx::bytes [%0],[%1,{%3,%4}],[%2];" ::"r"(dst), "l"(m), "r"(bar), "r"(c0), "r"(c1) : "memory");
}
__device__ __forceinline__ void tma3d(uint32_t dst, const CUtensorMap* m, int c0, int c1, int c2, uint32_t bar) {
    asm volatile("cp.async.bulk.tensor.3d.shared::cluster.global.mbarrier::complete_tx::bytes [%0],[%1,{%3,%4,%5}],[%2];" ::"r"(dst), "l"(m), "r"(bar), "r"(c0), "r"(c1), "r"(c2) : "memory");
}
__device__ __forceinline__ void bulk_g2s(uint32_t dst, const void* src, int bytes, uint32_t bar) {
    asm volatile("cp.async.bulk.shared::cluster.global.mbarrier::complete_tx::bytes [%0],[%1],%2,[%3];" ::"r"(dst), "l"(src), "r"(bytes), "r"(bar) : "memory");
}
__device__ __forceinline__ uint64_t mkdesc(uint32_t addr, uint32_t lbo, uint32_t sbo) {
    return (uint64_t)((addr & 0x3FFFF) >> 4) | ((uint64_t)(lbo >> 4) << 16) | ((uint64_t)(sbo >> 4) << 32) | ((uint64_t)1 << 62);
}
__device__ __forceinline__ void wg_fence() { asm volatile("wgmma.fence.sync.aligned;" ::: "memory"); }
__device__ __forceinline__ void wg_commit() { asm volatile("wgmma.commit_group.sync.aligned;" ::: "memory"); }
template <int N> __device__ __forceinline__ void wg_wait() { asm volatile("wgmma.wait_group.sync.aligned %0;" ::"n"(N) : "memory"); }
template <int N> __device__ __forceinline__ void fence_regs(float* d) {
#pragma unroll
    for (int i = 0; i < N; i++) asm volatile("" : "+f"(d[i])::"memory");
}
#define R8(d, o) "+f"(d[o]), "+f"(d[o + 1]), "+f"(d[o + 2]), "+f"(d[o + 3]), "+f"(d[o + 4]), "+f"(d[o + 5]), "+f"(d[o + 6]), "+f"(d[o + 7])
__device__ __forceinline__ void wgmma192(float* d, uint64_t da, uint64_t db, int sc) {
    asm volatile("{.reg .pred p; setp.ne.b32 p,%98,0; wgmma.mma_async.sync.aligned.m64n192k16.f32.bf16.bf16 {"
                 "%0,%1,%2,%3,%4,%5,%6,%7,%8,%9,%10,%11,%12,%13,%14,%15,%16,%17,%18,%19,%20,%21,%22,%23,%24,%25,%26,%27,%28,%29,%30,%31,"
                 "%32,%33,%34,%35,%36,%37,%38,%39,%40,%41,%42,%43,%44,%45,%46,%47,%48,%49,%50,%51,%52,%53,%54,%55,%56,%57,%58,%59,%60,%61,%62,%63,"
                 "%64,%65,%66,%67,%68,%69,%70,%71,%72,%73,%74,%75,%76,%77,%78,%79,%80,%81,%82,%83,%84,%85,%86,%87,%88,%89,%90,%91,%92,%93,%94,%95},"
                 "%96,%97,p,1,1,0,1;}"
                 : R8(d, 0), R8(d, 8), R8(d, 16), R8(d, 24), R8(d, 32), R8(d, 40), R8(d, 48), R8(d, 56), R8(d, 64), R8(d, 72), R8(d, 80), R8(d, 88)
                 : "l"(da), "l"(db), "r"(sc));
}
__device__ __forceinline__ void wgmma64_tt(float* d, uint64_t da, uint64_t db, int sc) {
    asm volatile("{.reg .pred p; setp.ne.b32 p,%34,0; wgmma.mma_async.sync.aligned.m64n64k16.f32.bf16.bf16 {"
                 "%0,%1,%2,%3,%4,%5,%6,%7,%8,%9,%10,%11,%12,%13,%14,%15,%16,%17,%18,%19,%20,%21,%22,%23,%24,%25,%26,%27,%28,%29,%30,%31},"
                 "%32,%33,p,1,1,1,1;}"
                 : R8(d, 0), R8(d, 8), R8(d, 16), R8(d, 24)
                 : "l"(da), "l"(db), "r"(sc));
}
__device__ __forceinline__ void wgmma64_rs(float* d, const uint4& a, uint64_t db, int sc) {
    asm volatile("{.reg .pred p; setp.ne.b32 p,%37,0; wgmma.mma_async.sync.aligned.m64n64k16.f32.bf16.bf16 {"
                 "%0,%1,%2,%3,%4,%5,%6,%7,%8,%9,%10,%11,%12,%13,%14,%15,%16,%17,%18,%19,%20,%21,%22,%23,%24,%25,%26,%27,%28,%29,%30,%31},"
                 "{%32,%33,%34,%35},%36,p,1,1,1;}"
                 : R8(d, 0), R8(d, 8), R8(d, 16), R8(d, 24)
                 : "r"(a.x), "r"(a.y), "r"(a.z), "r"(a.w), "l"(db), "r"(sc));
}
__device__ __forceinline__ void mma16816(float* c, uint32_t a0, uint32_t a1, uint32_t a2, uint32_t a3, uint32_t b0, uint32_t b1) {
    asm("mma.sync.aligned.m16n8k16.row.col.f32.bf16.bf16.f32 {%0,%1,%2,%3},{%4,%5,%6,%7},{%8,%9},{%0,%1,%2,%3};"
        : "+f"(c[0]), "+f"(c[1]), "+f"(c[2]), "+f"(c[3]) : "r"(a0), "r"(a1), "r"(a2), "r"(a3), "r"(b0), "r"(b1));
}
__device__ __forceinline__ void ldsm4(uint32_t* r, uint32_t a) {
    asm volatile("ldmatrix.sync.aligned.m8n8.x4.shared.b16 {%0,%1,%2,%3},[%4];" : "=r"(r[0]), "=r"(r[1]), "=r"(r[2]), "=r"(r[3]) : "r"(a) : "memory");
}
__device__ __forceinline__ void ldsm4t(uint32_t* r, uint32_t a) {
    asm volatile("ldmatrix.sync.aligned.m8n8.x4.trans.shared.b16 {%0,%1,%2,%3},[%4];" : "=r"(r[0]), "=r"(r[1]), "=r"(r[2]), "=r"(r[3]) : "r"(a) : "memory");
}
__device__ __forceinline__ void stsm4(uint32_t a, uint32_t r0, uint32_t r1, uint32_t r2, uint32_t r3) {
    asm volatile("stmatrix.sync.aligned.m8n8.x4.shared.b16 [%0],{%1,%2,%3,%4};" ::"r"(a), "r"(r0), "r"(r1), "r"(r2), "r"(r3) : "memory");
}
__device__ __forceinline__ uint32_t lds32(uint32_t a) { uint32_t v; asm volatile("ld.shared.b32 %0,[%1];" : "=r"(v) : "r"(a) : "memory"); return v; }
__device__ __forceinline__ uint4 lds128(uint32_t a) { uint4 v; asm volatile("ld.shared.v4.b32 {%0,%1,%2,%3},[%4];" : "=r"(v.x), "=r"(v.y), "=r"(v.z), "=r"(v.w) : "r"(a) : "memory"); return v; }
__device__ __forceinline__ void sts16(uint32_t a, uint32_t v) { asm volatile("st.shared.b16 [%0],%1;" ::"r"(a), "h"((unsigned short)v) : "memory"); }
__device__ __forceinline__ void sts32(uint32_t a, uint32_t v) { asm volatile("st.shared.b32 [%0],%1;" ::"r"(a), "r"(v) : "memory"); }
__device__ __forceinline__ void sts64(uint32_t a, uint32_t x, uint32_t y) { asm volatile("st.shared.v2.b32 [%0],{%1,%2};" ::"r"(a), "r"(x), "r"(y) : "memory"); }
__device__ __forceinline__ void sts128(uint32_t a, uint32_t x, uint32_t y, uint32_t z, uint32_t w) { asm volatile("st.shared.v4.b32 [%0],{%1,%2,%3,%4};" ::"r"(a), "r"(x), "r"(y), "r"(z), "r"(w) : "memory"); }
__device__ __forceinline__ uint32_t pack2(float lo, float hi) { uint32_t d; asm("cvt.rn.bf16x2.f32 %0,%1,%2;" : "=r"(d) : "f"(hi), "f"(lo)); return d; }
__device__ __forceinline__ float bf_lo(uint32_t v) { return __uint_as_float(v << 16); }
__device__ __forceinline__ float bf_hi(uint32_t v) { return __uint_as_float(v & 0xffff0000u); }
__device__ __forceinline__ float bf_round(float v) { return bf_lo(pack2(v, 0.f)); }
__device__ __forceinline__ uint32_t hmax2(uint32_t a, uint32_t b) { uint32_t d; asm("max.bf16x2 %0,%1,%2;" : "=r"(d) : "r"(a), "r"(b)); return d; }
__device__ __forceinline__ uint32_t hmin2(uint32_t a, uint32_t b) { uint32_t d; asm("min.bf16x2 %0,%1,%2;" : "=r"(d) : "r"(a), "r"(b)); return d; }
__device__ __forceinline__ uint32_t hmul2(uint32_t a, uint32_t b) { uint32_t d; asm("mul.rn.bf16x2 %0,%1,%2;" : "=r"(d) : "r"(a), "r"(b)); return d; }
__device__ __forceinline__ float ex2(float x) { float y; asm("ex2.approx.ftz.f32 %0,%1;" : "=f"(y) : "f"(x)); return y; }
__device__ __forceinline__ float rcp(float x) { float y; asm("rcp.approx.ftz.f32 %0,%1;" : "=f"(y) : "f"(x)); return y; }
__device__ __forceinline__ unsigned ld_acq(const unsigned* p) { unsigned v; asm volatile("ld.acquire.gpu.global.u32 %0,[%1];" : "=r"(v) : "l"(p) : "memory"); return v; }
__device__ __forceinline__ unsigned ld_rlx(const unsigned* p) { unsigned v; asm volatile("ld.relaxed.gpu.global.u32 %0,[%1];" : "=r"(v) : "l"(p) : "memory"); return v; }
__device__ __forceinline__ uint2 ld_rlx64(const void* p) { uint2 v; asm volatile("ld.relaxed.gpu.global.v2.u32 {%0,%1},[%2];" : "=r"(v.x), "=r"(v.y) : "l"(p) : "memory"); return v; }
__device__ __forceinline__ uint4 ld_rlx128(const void* p) { uint4 v; asm volatile("ld.relaxed.gpu.global.v4.u32 {%0,%1,%2,%3},[%4];" : "=r"(v.x), "=r"(v.y), "=r"(v.z), "=r"(v.w) : "l"(p) : "memory"); return v; }
__device__ __forceinline__ void st_rlx128(void* p, uint4 v) { asm volatile("st.relaxed.gpu.global.v4.u32 [%0],{%1,%2,%3,%4};" ::"l"(p), "r"(v.x), "r"(v.y), "r"(v.z), "r"(v.w) : "memory"); }
__device__ __forceinline__ void red_rel(unsigned* p) { asm volatile("red.release.gpu.global.add.u32 [%0],1;" ::"l"(p) : "memory"); }
__device__ __forceinline__ void red_v4(float4* p, float a, float b, float c, float d) { asm volatile("red.global.v4.f32.add [%0],{%1,%2,%3,%4};" ::"l"(p), "f"(a), "f"(b), "f"(c), "f"(d) : "memory"); }
__device__ __forceinline__ void wait_counter(const unsigned* p, unsigned target) {
    int n = 0;
    while ((int)(ld_acq(p) - target) < 0) { if (++n > SPIN_LIMIT) __trap(); }
}
__device__ __forceinline__ void bar_named(int id, int n) { asm volatile("bar.sync %0,%1;" ::"r"(id), "r"(n) : "memory"); }
__device__ __forceinline__ bool nz4(const uint4& v) { return (v.x != 0) & (v.y != 0) & (v.z != 0) & (v.w != 0); }
__device__ __forceinline__ uint32_t nzw(uint32_t w) { return w == 0 ? 0x80000000u : w; }

struct cf { float re, im; };
__device__ __forceinline__ cf cmul(cf a, cf b) { cf r; r.re = a.re * b.re - a.im * b.im; r.im = a.re * b.im + a.im * b.re; return r; }
__device__ __forceinline__ cf cexp_p(float arl, float ait, float p) {
    float mag = ex2(arl * p);
    float t = ait * p;
    t = (t - rintf(t)) * 6.283185307179586f;
    cf r; r.re = mag * __cosf(t); r.im = mag * __sinf(t);
    return r;
}

__device__ __forceinline__ void hedgehog(const uint32_t* a, uint32_t wphi_addr, uint32_t* out) {
    uint32_t b[4];
    ldsm4t(b, wphi_addr);
    float c0[4] = {0.f, 0.f, 0.f, 0.f}, c1[4] = {0.f, 0.f, 0.f, 0.f};
    mma16816(c0, a[0], a[1], a[2], a[3], b[0], b[1]);
    mma16816(c1, a[0], a[1], a[2], a[3], b[2], b[3]);
    uint32_t R[4] = {pack2(c0[0], c0[2]), pack2(c0[1], c0[3]), pack2(c1[0], c1[2]), pack2(c1[1], c1[3])};
    uint32_t mx = hmax2(hmax2(R[0], R[1]), hmax2(R[2], R[3]));
    uint32_t mn = hmin2(hmin2(R[0], R[1]), hmin2(R[2], R[3]));
    mx = hmax2(mx, __shfl_xor_sync(~0u, mx, 1)); mn = hmin2(mn, __shfl_xor_sync(~0u, mn, 1));
    mx = hmax2(mx, __shfl_xor_sync(~0u, mx, 2)); mn = hmin2(mn, __shfl_xor_sync(~0u, mn, 2));
    const float L = 1.4426950408889634f;
    float mxl = -bf_lo(mx) * L, mxh = -bf_hi(mx) * L, mnl = bf_lo(mn) * L, mnh = bf_hi(mn) * L;
    float pl[4], ph[4], ml[4], mh[4];
#pragma unroll
    for (int i = 0; i < 4; i++) {
        float xl = bf_lo(R[i]), xh = bf_hi(R[i]);
        pl[i] = ex2(fmaf(xl, L, mxl)); ph[i] = ex2(fmaf(xh, L, mxh));
        ml[i] = ex2(fmaf(xl, -L, mnl)); mh[i] = ex2(fmaf(xh, -L, mnh));
    }
    float spl = (pl[0] + pl[1]) + (pl[2] + pl[3]), sph = (ph[0] + ph[1]) + (ph[2] + ph[3]);
    float sml = (ml[0] + ml[1]) + (ml[2] + ml[3]), smh = (mh[0] + mh[1]) + (mh[2] + mh[3]);
#pragma unroll
    for (int o = 1; o <= 2; o <<= 1) {
        spl += __shfl_xor_sync(~0u, spl, o); sph += __shfl_xor_sync(~0u, sph, o);
        sml += __shfl_xor_sync(~0u, sml, o); smh += __shfl_xor_sync(~0u, smh, o);
    }
    spl = rcp(spl); sph = rcp(sph); sml = rcp(sml); smh = rcp(smh);
    out[0] = pack2(pl[0] * spl, pl[1] * spl); out[1] = pack2(ph[0] * sph, ph[1] * sph);
    out[2] = pack2(pl[2] * spl, pl[3] * spl); out[3] = pack2(ph[2] * sph, ph[3] * sph);
    out[4] = pack2(ml[0] * sml, ml[1] * sml); out[5] = pack2(mh[0] * smh, mh[1] * smh);
    out[6] = pack2(ml[2] * sml, ml[3] * sml); out[7] = pack2(mh[2] * smh, mh[3] * smh);
}

__global__ void __launch_bounds__(384, 1)
fused_kernel(const __grid_constant__ CUtensorMap mx, const __grid_constant__ CUtensorMap mw, const __grid_constant__ CUtensorMap mwo,
             const bf16* __restrict__ x, const bf16* __restrict__ wphi, const bf16* __restrict__ logA, const bf16* __restrict__ Aim,
             const bf16* __restrict__ Cre, const bf16* __restrict__ Cim, const bf16* __restrict__ logdt, const bf16* __restrict__ Dskip,
             const bf16* __restrict__ gatew, bf16* __restrict__ out) {
    extern __shared__ __align__(1024) uint8_t smem[];
    const uint32_t sb = s2u(smem);
    const int tid = threadIdx.x, warp = __shfl_sync(~0u, tid >> 5, 0), lane = tid & 31;
    const int g = lane >> 2, q = lane & 3;
    const int bi = blockIdx.x, bi_i = bi & 15, bi_j = bi >> 4;
    const uint32_t bar = sb + OFF_BAR;

    if (tid == 0) {
        if (sb & 1023) __trap();
        for (int s = 0; s < 4; s++) { mbar_init(bar + 8 * (BAR_FULL + s), 1); sts32(bar + OFF_CNT + 4 * s, 0); }
        mbar_init(bar + 8 * BAR_WPHI, 1); mbar_init(bar + 8 * BAR_WO, 2); mbar_init(bar + 8 * BAR_UGO, 1); mbar_init(bar + 8 * BAR_DONE, 8);
        asm volatile("fence.mbarrier_init.release.cluster;" ::: "memory");
        asm volatile("fence.proxy.async.shared::cta;" ::: "memory");
        for (int s = 0; s < 4; s++) {
            mbar_expect(bar + 8 * (BAR_FULL + s), SLOT);
            tma2d(sb + s * SLOT, &mx, s * 64, bi_i * 128, bar + 8 * (BAR_FULL + s));
            tma3d(sb + s * SLOT + 16384, &mw, bi_j * 64, s * 64, 0, bar + 8 * (BAR_FULL + s));
        }
        mbar_expect(bar + 8 * BAR_WPHI, 2048);
        bulk_g2s(sb + OFF_WPHI, wphi + bi_j * 1024, 2048, bar + 8 * BAR_WPHI);
    }
    if (warp < 8) {
        uint4* op = g_o + ((bi_i * 8 + warp) * 32 + bi_j * 4) * 32 + lane;
#pragma unroll
        for (int hh = 0; hh < 4; hh++) op[hh * 32] = make_uint4(0, 0, 0, 0);
        if ((lane & 15) == 0) g_g[bi_i * 128 + bi_j * 16 + warp * 2 + (lane >> 4)] = 0u;
    } else {
        uint4* yp = g_y + bi * 1024 + (tid - 256);
#pragma unroll
        for (int v = 0; v < 8; v++) yp[v * 128] = make_uint4(0, 0, 0, 0);
        if (tid - 256 < 34) g_kv[bi_j * 544 + bi_i * 34 + (tid - 256)] = make_float4(0.f, 0.f, 0.f, 0.f);
    }
    const unsigned target = ((ld_rlx(g_done) >> 7) + 1u) << 7;
    __syncthreads();

    if (warp < 8) {
        const int wg = warp >> 2, w4 = warp & 3;
        if (tid == 32) red_rel(g_cnt0);
        float acc[96];
        const int grow = bi_j * 16 + warp * 2 + (lane >> 4);
        const uint32_t gx_a = grow * 128 + ((((lane & 15) >> 1) ^ (grow & 7)) << 4) + (lane & 1) * 8;
        float gsum = 0.f;
#pragma unroll
        for (int kb = 0; kb < 8; kb++) {
            const int s = kb & 3;
            const uint2 gw = __ldg((const uint2*)(gatew + kb * 64) + (lane & 15));
            mbar_wait(bar + 8 * (BAR_FULL + s), kb >> 2);
            if (kb == 0 && warp == 0) STAMP(0);
            const uint32_t st = sb + s * SLOT;
            wg_fence();
#pragma unroll
            for (int k = 0; k < 4; k++)
                wgmma192(acc, mkdesc(st + wg * 8192 + k * 32, 16, 1024), mkdesc(st + 16384 + k * 2048, 8192, 1024), (kb | k) != 0);
            wg_commit();
            {
                uint32_t x0, x1;
                asm volatile("ld.shared.v2.b32 {%0,%1},[%2];" : "=r"(x0), "=r"(x1) : "r"(st + gx_a) : "memory");
                const uint32_t p0 = hmul2(x0, gw.x), p1 = hmul2(x1, gw.y);
                gsum += (bf_lo(p0) + bf_hi(p0)) + (bf_lo(p1) + bf_hi(p1));
            }
            if (kb > 0 && kb < 7) {
                wg_wait<1>();
                __syncwarp();
                if (lane == 0) {
                    const int ps = (kb - 1) & 3;
                    unsigned old;
                    asm volatile("atom.acq_rel.cta.shared.add.u32 %0,[%1],1;" : "=r"(old) : "r"(bar + OFF_CNT + 4 * ps) : "memory");
                    if ((old & 7) == 7) {
                        if (kb < 5) {
                            mbar_expect(bar + 8 * (BAR_FULL + ps), SLOT);
                            tma2d(sb + ps * SLOT, &mx, (kb + 3) * 64, bi_i * 128, bar + 8 * (BAR_FULL + ps));
                            tma3d(sb + ps * SLOT + 16384, &mw, bi_j * 64, (kb + 3) * 64, 0, bar + 8 * (BAR_FULL + ps));
                            if (kb == 4) mbar_arrive(bar + 8 * BAR_UGO);
                        } else {
                            mbar_expect(bar + 8 * BAR_WO, 32768);
                            tma2d(sb + ps * SLOT, &mwo, bi_j * 64, ps * 256, bar + 8 * BAR_WO);
                        }
                    }
                }
                __syncwarp();
            }
        }
        if (lane == 0) wait_counter(g_cnt0, target);
        mbar_wait(bar + 8 * BAR_WPHI, 0);
        wg_wait<0>();
        fence_regs<96>(acc);
        __syncwarp();
        if (lane == 0) mbar_arrive(bar + 8 * BAR_DONE);
        if (warp == 0) STAMP(1);
        uint32_t qa[16], ka[16], va[16];
#pragma unroll
        for (int r = 0; r < 16; r++) {
            qa[r] = pack2(acc[2 * r], acc[2 * r + 1]);
            ka[r] = pack2(acc[32 + 2 * r], acc[32 + 2 * r + 1]);
            va[r] = pack2(acc[64 + 2 * r], acc[64 + 2 * r + 1]);
        }
        const uint32_t wphi_a = sb + OFF_WPHI + (lane & 15) * 32 + (lane >> 4) * 16;
        const int srow = wg * 64 + w4 * 16 + (lane & 15);
        const uint32_t srow_a = srow * 128;
        const int sx = srow & 7, shi = lane >> 4;
        {
            uint32_t ph[4][8];
#pragma unroll
            for (int hh = 0; hh < 4; hh++) hedgehog(ka + 4 * hh, wphi_a + hh * 512, ph[hh]);
            mbar_wait(bar + 8 * BAR_DONE, 0);
#pragma unroll
            for (int hh = 0; hh < 4; hh++) {
                const uint32_t pt = sb + OFF_P + (hh >> 1) * 16384 + srow_a, vt = sb + OFF_V + (hh >> 1) * 16384 + srow_a;
                stsm4(pt + (((4 * (hh & 1) + shi) ^ sx) << 4), ph[hh][0], ph[hh][1], ph[hh][2], ph[hh][3]);
                stsm4(pt + (((4 * (hh & 1) + 2 + shi) ^ sx) << 4), ph[hh][4], ph[hh][5], ph[hh][6], ph[hh][7]);
                stsm4(vt + (((2 * (hh & 1) + shi) ^ sx) << 4), va[4 * hh], va[4 * hh + 1], va[4 * hh + 2], va[4 * hh + 3]);
            }
            sts128(sb + OFF_V + shi * 16384 + srow_a + ((4 ^ sx) << 4), 0x3f803f80u, 0x3f803f80u, 0x3f803f80u, 0x3f803f80u);
        }
        asm volatile("fence.proxy.async.shared::cta;" ::: "memory");
        bar_named(1, 256);
        if (warp == 0) STAMP(2);
        {
            float d[32];
            wg_fence();
#pragma unroll
            for (int k = 0; k < 8; k++)
                wgmma64_tt(d, mkdesc(sb + OFF_V + wg * 16384 + k * 2048, 16, 1024), mkdesc(sb + OFF_P + wg * 16384 + k * 2048, 16, 1024), k != 0);
            wg_commit();
            wg_wait<0>();
            fence_regs<32>(d);
            float4* kvp = g_kv + (bi_j * 4 + wg * 2) * 136;
            if (w4 < 2) {
                float e[16];
#pragma unroll
                for (int r = 0; r < 16; r++) e[r] = w4 ? d[16 + r] : d[r];
                float4* p = kvp + w4 * 136 + lane;
#pragma unroll
                for (int ks = 0; ks < 2; ks++)
#pragma unroll
                    for (int nt = 0; nt < 2; nt++)
                        red_v4(p + (ks * 2 + nt) * 32, e[8 * ks + 2 * nt], e[8 * ks + 2 * nt + 1], e[8 * ks + 4 + 2 * nt], e[8 * ks + 4 + 2 * nt + 1]);
            } else if (w4 == 2 && lane < 4) {
#pragma unroll
                for (int hl = 0; hl < 2; hl++)
#pragma unroll
                    for (int ks = 0; ks < 2; ks++)
                        red_v4(kvp + hl * 136 + 128 + ks * 4 + lane, d[16 * hl + 8 * ks], d[16 * hl + 8 * ks + 1], d[16 * hl + 8 * ks + 4], d[16 * hl + 8 * ks + 5]);
            }
            __syncwarp();
            if (lane == 0) red_rel(g_kvcnt + bi_j * 32);
        }
        if (warp == 0) STAMP(3);
        {
#pragma unroll
            for (int o = 1; o < 16; o <<= 1) gsum += __shfl_xor_sync(~0u, gsum, o);
            const float gate = bf_round(1.0f / (1.0f + __expf(-bf_round(gsum))));
            if ((lane & 15) == 0) asm volatile("st.relaxed.gpu.global.u32 [%0],%1;" ::"l"(g_g + bi_i * 128 + grow), "r"(nzw(__float_as_uint(gate))) : "memory");
        }
        uint32_t pq[4][8];
#pragma unroll
        for (int hh = 0; hh < 4; hh++) hedgehog(qa + 4 * hh, wphi_a + hh * 512, pq[hh]);
        if (warp == 0) STAMP(4);
        if (lane == 0) wait_counter(g_kvcnt + bi_j * 32, target);
        __syncwarp();
        if (warp == 0) STAMP(5);
        uint4 own[4];
        uint4* og = g_o + (bi_i * 8 + warp) * 1024 + lane;
#pragma unroll
        for (int hh = 0; hh < 4; hh++) {
            const float4* kvp = g_kv + (bi_j * 4 + hh) * 136;
            float n0[4] = {0.f, 0.f, 0.f, 0.f}, n1[4] = {0.f, 0.f, 0.f, 0.f}, dn[4] = {0.f, 0.f, 0.f, 0.f};
#pragma unroll
            for (int ks = 0; ks < 2; ks++) {
                float4 f0 = __ldcg(kvp + (ks * 2) * 32 + lane), f1 = __ldcg(kvp + (ks * 2 + 1) * 32 + lane), fz = __ldcg(kvp + 128 + ks * 4 + q);
                const uint32_t* a = pq[hh] + 4 * ks;
                mma16816(n0, a[0], a[1], a[2], a[3], pack2(f0.x, f0.y), pack2(f0.z, f0.w));
                mma16816(n1, a[0], a[1], a[2], a[3], pack2(f1.x, f1.y), pack2(f1.z, f1.w));
                mma16816(dn, a[0], a[1], a[2], a[3], pack2(fz.x, fz.y), pack2(fz.z, fz.w));
            }
            const float r0 = 1.0f / (dn[0] + 1e-6f), r1 = 1.0f / (dn[2] + 1e-6f);
            own[hh] = make_uint4(nzw(pack2(n0[0] * r0, n0[1] * r0)), nzw(pack2(n0[2] * r1, n0[3] * r1)),
                                 nzw(pack2(n1[0] * r0, n1[1] * r0)), nzw(pack2(n1[2] * r1, n1[3] * r1)));
            st_rlx128(og + (bi_j * 4 + hh) * 32, own[hh]);
        }
        if (warp == 0) STAMP(6);
        float oc[32];
        mbar_wait(bar + 8 * BAR_WO, 0);
        auto wdesc = [&](int hg) { return mkdesc(sb + (hg >> 4) * SLOT + (hg & 15) * 2048, 16, 1024); };
        wg_fence();
#pragma unroll
        for (int hh = 0; hh < 4; hh++) wgmma64_rs(oc, own[hh], wdesc(bi_j * 4 + hh), hh != 0);
        wg_commit();
        const uint8_t* yb = (const uint8_t*)g_y + (size_t)(bi_j * 16 + (q >> 1)) * 16384 + (bi_i * 8 + warp) * 128 + g * 16 + (q & 1) * 8;
        const unsigned* gp = g_g + bi_i * 128 + warp * 16 + g;
        uint2 yv[8]; unsigned g0, g1;
        {
            uint4 fr[7][4];
#pragma unroll
            for (int s = 0; s < 4; s++) {
                const int js = (bi_j + 1 + s) & 7;
#pragma unroll
                for (int hh = 0; hh < 4; hh++) fr[s][hh] = ld_rlx128(og + (js * 4 + hh) * 32);
            }
#pragma unroll
            for (int s = 0; s < 7; s++) {
                const int js = (bi_j + 1 + s) & 7;
                int n = 0;
                while (!__all_sync(~0u, nz4(fr[s][0]) & nz4(fr[s][1]) & nz4(fr[s][2]) & nz4(fr[s][3]))) {
#pragma unroll
                    for (int hh = 0; hh < 4; hh++) fr[s][hh] = ld_rlx128(og + (js * 4 + hh) * 32);
                    if (++n > SPIN_LIMIT) __trap();
                }
                wg_fence();
#pragma unroll
                for (int hh = 0; hh < 4; hh++) wgmma64_rs(oc, fr[s][hh], wdesc(js * 4 + hh), 1);
                wg_commit();
                if (s < 4) wg_wait<1>();
                if (s < 3) {
                    const int jn = (bi_j + 5 + s) & 7;
#pragma unroll
                    for (int hh = 0; hh < 4; hh++) fr[s + 4][hh] = ld_rlx128(og + (jn * 4 + hh) * 32);
                } else if (s == 3) {
#pragma unroll
                    for (int nt = 0; nt < 8; nt++) yv[nt] = ld_rlx64(yb + nt * 32768);
                    g0 = ld_rlx(gp); g1 = ld_rlx(gp + 8);
                }
            }
            if (warp == 0) STAMP(7);
        }
        {
            int n = 0;
            while (true) {
                bool ok = (g0 != 0) & (g1 != 0);
#pragma unroll
                for (int nt = 0; nt < 8; nt++) ok = ok & (yv[nt].x != 0) & (yv[nt].y != 0);
                if (__all_sync(~0u, ok)) break;
#pragma unroll
                for (int nt = 0; nt < 8; nt++) yv[nt] = ld_rlx64(yb + nt * 32768);
                g0 = ld_rlx(gp); g1 = ld_rlx(gp + 8);
                if (++n > SPIN_LIMIT) __trap();
            }
            if (warp == 0) STAMP(8);
            wg_wait<0>();
            fence_regs<32>(oc);
            if (warp == 0) STAMP(9);
            const float ga = __uint_as_float(g0), gb = __uint_as_float(g1);
            const float ha = bf_round(1.0f - ga), hb = bf_round(1.0f - gb);
            uint32_t w[8][2];
#pragma unroll
            for (int nt = 0; nt < 8; nt++) {
                w[nt][0] = pack2(fmaf(ga, oc[4 * nt], ha * bf_lo(yv[nt].x)), fmaf(ga, oc[4 * nt + 1], ha * bf_hi(yv[nt].x)));
                w[nt][1] = pack2(fmaf(gb, oc[4 * nt + 2], hb * bf_lo(yv[nt].y)), fmaf(gb, oc[4 * nt + 3], hb * bf_hi(yv[nt].y)));
            }
            const uint32_t ob = sb + OFF_OUT + warp * 2048;
#pragma unroll
            for (int nt = 0; nt < 8; nt += 2)
                stsm4(ob + (lane & 15) * 128 + (((nt + shi) ^ (lane & 7)) << 4), w[nt][0], w[nt][1], w[nt + 1][0], w[nt + 1][1]);
            __syncwarp();
            bf16* op = out + (size_t)(bi_i * 128 + warp * 16) * 512 + bi_j * 64 + (lane & 7) * 8;
#pragma unroll
            for (int it = 0; it < 4; it++) {
                const int r = it * 4 + (lane >> 3);
                uint4 v = lds128(ob + r * 128 + (((lane & 7) ^ (r & 7)) << 4));
                *(uint4*)(op + r * 512) = v;
            }
        }
        if (warp == 0) STAMP(10);
    } else {
        const int w4 = warp - 8, ch = bi * 4 + w4, st = tid - 256;
        const uint32_t ub = sb + OFF_U + w4 * U_STRIDE + 256, kb_ = sb + OFF_K + w4 * K_STRIDE, buf = sb + OFF_BUF + w4 * 8192;
        const uint32_t spare = sb + (w4 < 2 ? OFF_SP0 : OFF_SP1) + (w4 & 1) * 4096;
        const uint2 pla = __ldg((const uint2*)(logA + ch * 128) + lane), pai = __ldg((const uint2*)(Aim + ch * 128) + lane);
        const uint2 pcr = __ldg((const uint2*)(Cre + ch * 128) + lane), pci = __ldg((const uint2*)(Cim + ch * 128) + lane);
        const float dt = bf_round(expf(__bfloat162float(logdt[ch])));
        const float dskip = __bfloat162float(Dskip[ch]);
#pragma unroll
        for (int v = 0; v < 8; v++) if (v * 32 + lane < 240) sts128(kb_ + (v * 32 + lane) * 16, 0, 0, 0, 0);
        if (lane < 16) sts128(ub - 256 + lane * 16, 0, 0, 0, 0);
        float kc[6][4];
#pragma unroll
        for (int t = 0; t < 6; t++) { kc[t][0] = kc[t][1] = kc[t][2] = kc[t][3] = 0.f; }
        uint2 ur[16];
#pragma unroll 1
        for (int c = 0; c < 4; c++) {
            const int sh = (c & 1) * 16;
            auto pick = [&](const uint2& v) { return __uint_as_float(((c & 2 ? v.y : v.x) >> sh) << 16); };
            const float ea = bf_round(expf(pick(pla)));
            const float arl = (-ea * dt) * 1.4426950408889634f, ait = (pick(pai) * dt) * 0.15915494309189535f;
            cf C2; C2.re = 2.0f * (pick(pcr) * dt); C2.im = 2.0f * (pick(pci) * dt);
            const cf z1 = cexp_p(arl, ait, 1.0f), z128 = cexp_p(arl, ait, 128.0f);
            cf z8 = cexp_p(arl, ait, 8.0f); z8.im = -z8.im;
            const uint32_t lp = buf + lane * 4;
            auto put = [&](int row, const cf& v) { sts32((lp ^ ((row & 7) << 4)) + row * 128, pack2(v.re, v.im)); };
            {
                const cf z16 = cmul(z8, z8);
                cf e; e.re = 1.f; e.im = 0.f;
                cf o = z8;
                put(0, e); put(1, o);
                e = z16; put(2, e);
#pragma unroll
                for (int b = 3; b < 16; b += 2) {
                    o = cmul(o, z16); put(b, o);
                    if (b + 1 < 16) { e = cmul(e, z16); put(b + 1, e); }
                }
            }
            cf h[8];
            h[0] = C2; put(16, h[0]);
            {
                const cf z2 = cmul(z1, z1);
                h[1] = cmul(h[0], z1);
#pragma unroll
                for (int r = 2; r < 8; r++) h[r] = cmul(h[r - 2], z2);
#pragma unroll
                for (int r = 1; r < 8; r++) put(16 + r, h[r]);
            }
#pragma unroll
            for (int r = 0; r < 8; r++) { h[r] = cmul(h[r], z128); put(24 + r, h[r]); }
#pragma unroll
            for (int al = 0; al < 2; al++)
#pragma unroll
                for (int r = 0; r < 4; r++) { h[2 * r] = cmul(h[2 * r], z128); put(32 + al * 4 + r, h[2 * r]); }
#pragma unroll
            for (int al = 0; al < 4; al++)
#pragma unroll
                for (int r = 0; r < 2; r++) { h[4 * r] = cmul(h[4 * r], z128); put(40 + al * 2 + r, h[4 * r]); }
#pragma unroll
            for (int al = 0; al < 9; al++) { h[0] = cmul(h[0], z128); put(48 + al, h[0]); }
            __syncwarp();
            if (c == 3) {
                mbar_wait(bar + 8 * BAR_UGO, 0);
                const bf16* xp = x + (size_t)st * 8 * 512 + bi * 4;
#pragma unroll
                for (int v = 0; v < 16; v++) ur[v] = __ldg((const uint2*)(xp + (size_t)((v >> 3) * 1024 + (v & 7)) * 512));
            }
            const int lr = lane & 7, lm = lane >> 3;
#pragma unroll
            for (int kp = 0; kp < 2; kp++) {
                uint32_t a0[4], a1[4];
                ldsm4(a0, buf + ((lm & 1) * 8 + lr) * 128 + (((4 * kp + (lm >> 1)) ^ lr) << 4));
                ldsm4(a1, buf + ((lm & 1) * 8 + lr) * 128 + (((4 * kp + 2 + (lm >> 1)) ^ lr) << 4));
#pragma unroll
                for (int t = 0; t < 6; t++) {
                    uint32_t b[4];
                    ldsm4(b, buf + (16 + 8 * t + lr) * 128 + (((4 * kp + lm) ^ lr) << 4));
                    mma16816(kc[t], a0[0], a0[1], a0[2], a0[3], b[0], b[1]);
                    mma16816(kc[t], a1[0], a1[1], a1[2], a1[3], b[2], b[3]);
                }
            }
            __syncwarp();
        }
        if (warp == 8) STAMP(16);
        if (lane == 0) kc[0][0] += dskip;
        const uint32_t k1024 = __shfl_sync(~0u, pack2(kc[4][0], 0.f), 0);
#pragma unroll
        for (int i = 0; i < 2; i++) {
            const int be = g + 8 * i;
#pragma unroll
            for (int t = 0; t < 2; t++) {
                const uint32_t a = kb_ + (KW_D + 8 + 128 * t + 8 * be + 2 * q) * 4;
                const uint32_t w = pack2(kc[t][2 * i + 1], kc[t][2 * i]);
                sts32(a + 4, w); sts16(a, w >> 16); sts16(a + 10, w);
            }
            {
                const int p = 256 + 128 * (q >> 1) + 8 * be + 4 * (q & 1);
                const uint32_t a = kb_ + (KW_D + 8 + p) * 4;
                const uint32_t w = pack2(kc[2][2 * i + 1], kc[2][2 * i]);
                const uint32_t aa = (w >> 16) | (w & 0xffff0000u);
                if (p != 256) { sts16(a - 4, aa); sts32(a, aa); } else sts16(a, aa);
                sts32(a + 4, aa); sts32(a + 8, w); sts16(a + 14, w);
            }
            {
                const int k = 64 + 16 * q + be;
                const uint32_t w = pack2(kc[3][2 * i], kc[3][2 * i + 1]);
                if (k != 64) {
                    const uint32_t a = kb_ + (KW_2E + k - 1 - 32) * 4;
                    sts16(a, w); sts16(a + 6, w);
                } else {
                    const uint32_t a = kb_ + (KW_D + 8 + 511) * 4, aa = (w << 16) | (w & 0xffffu);
                    sts16(a, w); sts32(a + 4, aa); sts32(a + 8, aa); sts32(a + 12, aa); sts16(a + 18, w);
                }
                const uint32_t a = kb_ + (KW_2O + k - 32) * 4;
                sts16(a, w >> 16); sts16(a + 6, w >> 16);
            }
#pragma unroll
            for (int b = 0; b < 2; b++) {
                const int k = 64 + 8 * (2 * q + b) + (be >> 1);
                const uint32_t w = pack2(kc[4][2 * i + b], 0.f);
                uint32_t a;
                if (be & 1) a = kb_ + (KW_3O + k - 48) * 4;
                else if (k != 64) a = kb_ + (KW_3E + k - 1 - 48) * 4;
                else a = kb_ + (KW_2E + 127 - 32) * 4;
                sts16(a, w);
                if (!((be & 1) && k == 127)) sts16(a + 6, w);
            }
        }
        if (lane == 0) sts16(kb_ + (KW_3E + 127 - 48) * 4, pack2(kc[5][0], 0.f));
#pragma unroll
        for (int hf = 0; hf < 2; hf++) {
            const int ci = st + 128 * hf;
            const uint32_t a = sb + OFF_U + 256 + ((ci ^ ((ci >> 3) & 1)) << 4);
            const uint2* r = ur + 8 * hf;
            sts128(a, __byte_perm(r[0].x, r[1].x, 0x5410), __byte_perm(r[2].x, r[3].x, 0x5410), __byte_perm(r[4].x, r[5].x, 0x5410), __byte_perm(r[6].x, r[7].x, 0x5410));
            sts128(a + U_STRIDE, __byte_perm(r[0].x, r[1].x, 0x7632), __byte_perm(r[2].x, r[3].x, 0x7632), __byte_perm(r[4].x, r[5].x, 0x7632), __byte_perm(r[6].x, r[7].x, 0x7632));
            sts128(a + 2 * U_STRIDE, __byte_perm(r[0].y, r[1].y, 0x5410), __byte_perm(r[2].y, r[3].y, 0x5410), __byte_perm(r[4].y, r[5].y, 0x5410), __byte_perm(r[6].y, r[7].y, 0x5410));
            sts128(a + 3 * U_STRIDE, __byte_perm(r[0].y, r[1].y, 0x7632), __byte_perm(r[2].y, r[3].y, 0x7632), __byte_perm(r[4].y, r[5].y, 0x7632), __byte_perm(r[6].y, r[7].y, 0x7632));
        }
        mbar_wait(bar + 8 * BAR_WO, 0);
        bar_named(2, 128);
        if (warp == 8) STAMP(17);
        float y[8][2][4];
#pragma unroll
        for (int c = 0; c < 8; c++)
#pragma unroll
            for (int h = 0; h < 2; h++) { y[c][h][0] = y[c][h][1] = y[c][h][2] = y[c][h][3] = 0.f; }
        {
            uint32_t Ev[16], Od[16];
            auto uaddr = [&](int rho, int par) { const int R0 = lane - rho; return ub + (((2 * R0 + par) ^ ((R0 >> 2) & 1)) << 4); };
            auto ldset = [&](uint32_t* r, uint32_t a) {
#pragma unroll
                for (int b = 0; b < 4; b++) ldsm4(r + 4 * b, a + b * 1024);
            };
            const uint32_t kd = kb_ + (KW_D + 8 + g - 2 * q) * 4;
            ldset(Ev, uaddr(0, 0)); ldset(Od, uaddr(1, 1));
            {
                const uint32_t b0 = lds32(kd + (512 + 8) * 4), b1 = lds32(kd + 512 * 4);
#pragma unroll
                for (int c = 2; c < 8; c++) mma16816(y[c][0], Od[2 * c - 4], Od[2 * c - 3], Ev[2 * c - 4], Ev[2 * c - 3], b0, b1);
                ldset(Od, uaddr(0, 1));
#pragma unroll
                for (int c = 2; c < 8; c++) mma16816(y[c][1], Ev[2 * c - 4], Ev[2 * c - 3], Od[2 * c - 4], Od[2 * c - 3], b0, b1);
            }
#pragma unroll 1
            for (int rho = 0; rho < 8; rho++) {
                uint32_t b0[4], b1[4];
#pragma unroll
                for (int ga = 0; ga < 4; ga++) { b0[ga] = lds32(kd + rho * 64 + ga * 512 + 32); b1[ga] = lds32(kd + rho * 64 + ga * 512); }
                const int ci = lane + 32 * rho;
                uint4 e4[4];
#pragma unroll
                for (int v = 0; v < 4; v++) { const int cc = ci - 3 + v; e4[v] = lds128(ub + ((cc ^ ((cc >> 3) & 1)) << 4)); }
#pragma unroll
                for (int ga = 0; ga < 4; ga++)
#pragma unroll
                    for (int c = 0; c < 8; c++) {
                        const int m = 2 * c - ga;
                        if (m + 1 < 0) continue;
                        mma16816(y[c][1], m >= 0 ? Ev[m] : 0u, Ev[m + 1], m >= 0 ? Od[m] : 0u, Od[m + 1], b0[ga], b1[ga]);
                    }
                ldset(Od, uaddr(rho + 1, 1));
                {
                    float S[29];
                    const uint32_t* ew = (const uint32_t*)e4;
                    S[3] = 0.f;
#pragma unroll
                    for (int k = 4; k <= 28; k++) S[k] = S[k - 1] + ((k & 1) ? bf_hi(ew[k >> 1]) : bf_lo(ew[k >> 1]));
                    auto win = [&](int lo, int hi, uint32_t a) {
                        sts128(a, pack2(S[hi] - S[lo - 1], S[hi + 1] - S[lo]), pack2(S[hi + 2] - S[lo + 1], S[hi + 3] - S[lo + 2]),
                               pack2(S[hi + 4] - S[lo + 3], S[hi + 5] - S[lo + 4]), pack2(S[hi + 6] - S[lo + 5], S[hi + 7] - S[lo + 6]));
                    };
                    const uint32_t sw = (ci ^ ((ci >> 3) & 1)) << 4;
                    if (rho < 6) { win(14, 18, buf + ci * 16); win(19, 21, buf + 3072 + ci * 16); }
                    if (rho < 4) { win(4, 12, buf + 6144 + sw); win(13, 19, spare + sw); win(20, 21, spare + 2048 + sw); }
                }
#pragma unroll
                for (int ga = 0; ga < 4; ga++)
#pragma unroll
                    for (int c = 0; c < 8; c++) {
                        const int m = 2 * c - ga;
                        if (m + 1 < 0) continue;
                        mma16816(y[c][0], m >= 0 ? Od[m] : 0u, Od[m + 1], m >= 0 ? Ev[m] : 0u, Ev[m + 1], b0[ga], b1[ga]);
                    }
                ldset(Ev, uaddr(rho + 1, 0));
            }
        }
        __syncwarp();
        if (warp == 8) STAMP(18);
#pragma unroll 1
        for (int ph = 0; ph < 2; ph++) {
            uint32_t B[24];
#pragma unroll
            for (int s2 = 0; s2 < 6; s2++) ldsm4t(B + 4 * s2, buf + ph * 3072 + s2 * 512 + lane * 16);
#pragma unroll
            for (int h = 0; h < 2; h++) {
                uint32_t A[10];
                const uint32_t ka = kb_ + (KW_2E + ph * 128 + 96 + 2 * g - 2 * q + h) * 4;
#pragma unroll
                for (int yy = 0; yy < 10; yy++) A[yy] = lds32(ka - yy * 32);
                auto AA = [&](int yv) { return (yv <= 0 && yv >= -9) ? A[-yv] : 0u; };
#pragma unroll
                for (int sg = 0; sg < 6; sg++)
#pragma unroll
                    for (int c = 2; c < 8; c++) {
                        const int s = 2 * c - 8 + sg;
                        if (s < 0) continue;
                        mma16816(y[c][h], AA(-2 * sg), AA(-2 * sg + 2), AA(-2 * sg - 1), AA(-2 * sg + 1), B[2 * s], B[2 * s + 1]);
                    }
            }
        }
        {
            const int ap = (lane & 15), hsel = lane >> 4;
            const uint32_t loff = ((2 * ap + hsel) ^ ((ap >> 2) & 1)) << 4;
#pragma unroll 1
            for (int ph = 0; ph < 2; ph++) {
                uint32_t B[4][4], A[8];
                const uint32_t wb = (ph ? spare : buf + 6144) + loff;
#pragma unroll
                for (int s = 0; s < 4; s++) ldsm4t(B[s], wb + s * 512);
                const uint32_t ka = kb_ + (KW_3E + ph * 80 + 16 + g - 2 * q) * 4;
#pragma unroll
                for (int yy = 0; yy < 8; yy++) A[yy] = lds32(ka + yy * 32);
#pragma unroll
                for (int s = 0; s < 4; s++)
#pragma unroll
                    for (int c = 4 + s; c < 8; c++) {
                        const int y0 = 2 * (c - s) - 8;
#pragma unroll
                        for (int h = 0; h < 2; h++)
                            mma16816(y[c][h], A[y0], A[y0 + 1], y0 > 0 ? A[y0 - 1] : 0u, A[y0], B[s][2 * h], B[s][2 * h + 1]);
                    }
            }
            const uint32_t idw = (g == 2 * q) ? k1024 : ((g == 2 * q + 1) ? (k1024 << 16) : 0u);
#pragma unroll
            for (int s = 0; s < 4; s++) {
                uint32_t B[4];
                ldsm4t(B, spare + 2048 + loff + s * 512);
                mma16816(y[4 + s][0], idw, 0u, 0u, idw, B[0], B[1]);
                mma16816(y[4 + s][1], idw, 0u, 0u, idw, B[2], B[3]);
            }
        }
        __syncwarp();
        if (warp == 8) STAMP(19);
#pragma unroll
        for (int c = 0; c < 8; c++)
#pragma unroll
            for (int i = 0; i < 2; i++)
                sts64(buf + ((16 * c + 8 * i + g) * 8 + 2 * q) * 4, pack2(y[c][0][2 * i], y[c][1][2 * i]), pack2(y[c][0][2 * i + 1], y[c][1][2 * i + 1]));
        bar_named(2, 128);
        uint4* yp = g_y + bi * 1024 + st;
#pragma unroll
        for (int v = 0; v < 8; v++) {
            const uint32_t a = sb + OFF_BUF + (st + 128 * v) * 4;
            const uint32_t w0 = lds32(a), w1 = lds32(a + 8192), w2 = lds32(a + 16384), w3 = lds32(a + 24576);
            st_rlx128(yp + v * 128, make_uint4(nzw(__byte_perm(w0, w1, 0x5410)), nzw(__byte_perm(w0, w1, 0x7632)),
                                               nzw(__byte_perm(w2, w3, 0x5410)), nzw(__byte_perm(w2, w3, 0x7632))));
        }
        if (warp == 8) STAMP(20);
    }
    __syncthreads();
    if (tid == 0) atomicAdd(g_done, 1u);
}

typedef CUresult (*EncFn)(CUtensorMap*, CUtensorMapDataType, cuuint32_t, void*, const cuuint64_t*, const cuuint64_t*, const cuuint32_t*,
                          const cuuint32_t*, CUtensorMapInterleave, CUtensorMapSwizzle, CUtensorMapL2promotion, CUtensorMapFloatOOBfill);

extern "C" void kernel_launch(void* const* d_in, const int* in_sizes, int n_in, void* d_out, int out_size) {
    static EncFn enc = nullptr;
    if (!enc) {
        cudaDriverEntryPointQueryResult qr;
        cudaGetDriverEntryPoint("cuTensorMapEncodeTiled", (void**)&enc, cudaEnableDefault, &qr);
        cudaFuncSetAttribute(fused_kernel, cudaFuncAttributeMaxDynamicSharedMemorySize, SMEM_BYTES);
    }
    CUtensorMap mx, mw, mwo;
    const cuuint32_t es[3] = {1, 1, 1};
    {
        cuuint64_t d[2] = {512, 2048}, s[1] = {1024}; cuuint32_t b[2] = {64, 128};
        enc(&mx, CU_TENSOR_MAP_DATA_TYPE_BFLOAT16, 2, d_in[0], d, s, b, es, CU_TENSOR_MAP_INTERLEAVE_NONE, CU_TENSOR_MAP_SWIZZLE_128B,
            CU_TENSOR_MAP_L2_PROMOTION_L2_128B, CU_TENSOR_MAP_FLOAT_OOB_FILL_NONE);
    }
    {
        cuuint64_t d[3] = {512, 512, 3}, s[2] = {3072, 1024}; cuuint32_t b[3] = {64, 64, 3};
        enc(&mw, CU_TENSOR_MAP_DATA_TYPE_BFLOAT16, 3, d_in[1], d, s, b, es, CU_TENSOR_MAP_INTERLEAVE_NONE, CU_TENSOR_MAP_SWIZZLE_128B,
            CU_TENSOR_MAP_L2_PROMOTION_L2_128B, CU_TENSOR_MAP_FLOAT_OOB_FILL_NONE);
    }
    {
        cuuint64_t d[2] = {512, 512}, s[1] = {1024}; cuuint32_t b[2] = {64, 256};
        enc(&mwo, CU_TENSOR_MAP_DATA_TYPE_BFLOAT16, 2, d_in[3], d, s, b, es, CU_TENSOR_MAP_INTERLEAVE_NONE, CU_TENSOR_MAP_SWIZZLE_128B,
            CU_TENSOR_MAP_L2_PROMOTION_L2_128B, CU_TENSOR_MAP_FLOAT_OOB_FILL_NONE);
    }
    fused_kernel<<<128, 384, SMEM_BYTES, cudaStreamPerThread>>>(
        mx, mw, mwo, (const bf16*)d_in[0], (const bf16*)d_in[2], (const bf16*)d_in[5], (const bf16*)d_in[6], (const bf16*)d_in[7],
        (const bf16*)d_in[8], (const bf16*)d_in[9], (const bf16*)d_in[10], (const bf16*)d_in[11], (bf16*)d_out);
}
```

```cpp
#include <cuda_runtime.h>
#include <cuda.h>
#include <cuda_bf16.h>
#include <stdint.h>

typedef __nv_bfloat16 bf16;

__device__ unsigned g_done[32];
__device__ unsigned g_xcnt[8 * 32];
__device__ uint4 g_xt[128 * 1024];
__device__ uint4 g_kvp[8 * 16 * 544];
__device__ uint4 g_kvf[8 * 4 * 68];
__device__ uint4 g_o[16 * 8 * 32 * 32];
__device__ uint4 g_y[128 * 1024];
__device__ unsigned g_g[1024 * 8];
#define STAMP(n)

constexpr int SLOT = 40960;
constexpr int OFF_SP0 = 32768, OFF_SP1 = SLOT + 32768;
constexpr int OFF_P = 2 * SLOT, OFF_V = OFF_P + 32768, OFF_OUT = OFF_V + 32768;
constexpr int OFF_U = 4 * SLOT, U_STRIDE = 4096 + 256;
constexpr int OFF_K = OFF_U + 4 * U_STRIDE, K_STRIDE = 3264;
constexpr int OFF_BUF = OFF_K + 4 * K_STRIDE, BUF_STRIDE = 8320;
constexpr int OFF_WPHI = OFF_BUF + 4 * BUF_STRIDE;
constexpr int OFF_GW = OFF_WPHI + 2048;
constexpr int OFF_BAR = OFF_GW + 1024;
constexpr int SMEM_BYTES = OFF_BAR + 128;
static_assert(SMEM_BYTES <= 232448 && OFF_BUF % 128 == 0, "smem");
constexpr int KW_D = 16, KW_2 = 560, KW_3 = 656;
constexpr int W5_OFF = 0, W3_OFF = 3088, W9_OFF = 6176;
constexpr int BAR_FULL = 0, BAR_WPHI = 4, BAR_WO = 5, BAR_XT = 6, BAR_DONE = 7, OFF_CNT = 64;
constexpr int SPIN_LIMIT = 1 << 21;

__device__ __forceinline__ uint32_t s2u(const void* p) { return (uint32_t)__cvta_generic_to_shared(p); }
__device__ __forceinline__ void mbar_init(uint32_t b, int c) { asm volatile("mbarrier.init.shared::cta.b64 [%0],%1;" ::"r"(b), "r"(c) : "memory"); }
__device__ __forceinline__ void mbar_expect(uint32_t b, int bytes) { asm volatile("mbarrier.arrive.expect_tx.shared::cta.b64 _,[%0],%1;" ::"r"(b), "r"(bytes) : "memory"); }
__device__ __forceinline__ void mbar_arrive(uint32_t b) { asm volatile("mbarrier.arrive.shared::cta.b64 _,[%0];" ::"r"(b) : "memory"); }
__device__ __forceinline__ bool mbar_try(uint32_t b, int ph) {
    uint32_t ok;
    asm volatile("{.reg .pred p; mbarrier.try_wait.parity.shared::cta.b64 p,[%1],%2; selp.u32 %0,1,0,p;}" : "=r"(ok) : "r"(b), "r"(ph) : "memory");
    return ok;
}
__device__ __forceinline__ void mbar_wait(uint32_t b, int ph) {
    if ((threadIdx.x & 31) == 0) { int n = 0; while (!mbar_try(b, ph)) { if (++n > SPIN_LIMIT) __trap(); } }
    __syncwarp();
}
__device__ __forceinline__ void mbar_wait_slow(uint32_t b, int ph) {
    if ((threadIdx.x & 31) == 0) { int n = 0; while (!mbar_try(b, ph)) { __nanosleep(100); if (++n > SPIN_LIMIT) __trap(); } }
    __syncwarp();
}
__device__ __forceinline__ void tma2d(uint32_t dst, const CUtensorMap* m, int c0, int c1, uint32_t bar) {
    asm volatile("cp.async.bulk.tensor.2d.shared::cluster.global.mbarrier::complete_tx::bytes [%0],[%1,{%3,%4}],[%2];" ::"r"(dst), "l"(m), "r"(bar), "r"(c0), "r"(c1) : "memory");
}
__device__ __forceinline__ void tma3d(uint32_t dst, const CUtensorMap* m, int c0, int c1, int c2, uint32_t bar) {
    asm volatile("cp.async.bulk.tensor.3d.shared::cluster.global.mbarrier::complete_tx::bytes [%0],[%1,{%3,%4,%5}],[%2];" ::"r"(dst), "l"(m), "r"(bar), "r"(c0), "r"(c1), "r"(c2) : "memory");
}
__device__ __forceinline__ void bulk_g2s(uint32_t dst, const void* src, int bytes, uint32_t bar) {
    asm volatile("cp.async.bulk.shared::cluster.global.mbarrier::complete_tx::bytes [%0],[%1],%2,[%3];" ::"r"(dst), "l"(src), "r"(bytes), "r"(bar) : "memory");
}
__device__ __forceinline__ uint64_t mkdesc(uint32_t addr, uint32_t lbo, uint32_t sbo) {
    return (uint64_t)((addr & 0x3FFFF) >> 4) | ((uint64_t)(lbo >> 4) << 16) | ((uint64_t)(sbo >> 4) << 32) | ((uint64_t)1 << 62);
}
__device__ __forceinline__ void wg_fence() { asm volatile("wgmma.fence.sync.aligned;" ::: "memory"); }
__device__ __forceinline__ void wg_commit() { asm volatile("wgmma.commit_group.sync.aligned;" ::: "memory"); }
template <int N> __device__ __forceinline__ void wg_wait() { asm volatile("wgmma.wait_group.sync.aligned %0;" ::"n"(N) : "memory"); }
template <int N> __device__ __forceinline__ void fence_regs(float* d) {
#pragma unroll
    for (int i = 0; i < N; i++) asm volatile("" : "+f"(d[i])::"memory");
}
#define R8(d, o) "+f"(d[o]), "+f"(d[o + 1]), "+f"(d[o + 2]), "+f"(d[o + 3]), "+f"(d[o + 4]), "+f"(d[o + 5]), "+f"(d[o + 6]), "+f"(d[o + 7])
__device__ __forceinline__ void wgmma192(float* d, uint64_t da, uint64_t db, int sc) {
    asm volatile("{.reg .pred p; setp.ne.b32 p,%98,0; wgmma.mma_async.sync.aligned.m64n192k16.f32.bf16.bf16 {"
                 "%0,%1,%2,%3,%4,%5,%6,%7,%8,%9,%10,%11,%12,%13,%14,%15,%16,%17,%18,%19,%20,%21,%22,%23,%24,%25,%26,%27,%28,%29,%30,%31,"
                 "%32,%33,%34,%35,%36,%37,%38,%39,%40,%41,%42,%43,%44,%45,%46,%47,%48,%49,%50,%51,%52,%53,%54,%55,%56,%57,%58,%59,%60,%61,%62,%63,"
                 "%64,%65,%66,%67,%68,%69,%70,%71,%72,%73,%74,%75,%76,%77,%78,%79,%80,%81,%82,%83,%84,%85,%86,%87,%88,%89,%90,%91,%92,%93,%94,%95},"
                 "%96,%97,p,1,1,0,1;}"
                 : R8(d, 0), R8(d, 8), R8(d, 16), R8(d, 24), R8(d, 32), R8(d, 40), R8(d, 48), R8(d, 56), R8(d, 64), R8(d, 72), R8(d, 80), R8(d, 88)
                 : "l"(da), "l"(db), "r"(sc));
}
__device__ __forceinline__ void wgmma64_tt(float* d, uint64_t da, uint64_t db, int sc) {
    asm volatile("{.reg .pred p; setp.ne.b32 p,%34,0; wgmma.mma_async.sync.aligned.m64n64k16.f32.bf16.bf16 {"
                 "%0,%1,%2,%3,%4,%5,%6,%7,%8,%9,%10,%11,%12,%13,%14,%15,%16,%17,%18,%19,%20,%21,%22,%23,%24,%25,%26,%27,%28,%29,%30,%31},"
                 "%32,%33,p,1,1,1,1;}"
                 : R8(d, 0), R8(d, 8), R8(d, 16), R8(d, 24)
                 : "l"(da), "l"(db), "r"(sc));
}
__device__ __forceinline__ void wgmma64_rs(float* d, const uint4& a, uint64_t db, int sc) {
    asm volatile("{.reg .pred p; setp.ne.b32 p,%37,0; wgmma.mma_async.sync.aligned.m64n64k16.f32.bf16.bf16 {"
                 "%0,%1,%2,%3,%4,%5,%6,%7,%8,%9,%10,%11,%12,%13,%14,%15,%16,%17,%18,%19,%20,%21,%22,%23,%24,%25,%26,%27,%28,%29,%30,%31},"
                 "{%32,%33,%34,%35},%36,p,1,1,1;}"
                 : R8(d, 0), R8(d, 8), R8(d, 16), R8(d, 24)
                 : "r"(a.x), "r"(a.y), "r"(a.z), "r"(a.w), "l"(db), "r"(sc));
}
__device__ __forceinline__ void mma16816(float* c, uint32_t a0, uint32_t a1, uint32_t a2, uint32_t a3, uint32_t b0, uint32_t b1) {
    asm("mma.sync.aligned.m16n8k16.row.col.f32.bf16.bf16.f32 {%0,%1,%2,%3},{%4,%5,%6,%7},{%8,%9},{%0,%1,%2,%3};"
        : "+f"(c[0]), "+f"(c[1]), "+f"(c[2]), "+f"(c[3]) : "r"(a0), "r"(a1), "r"(a2), "r"(a3), "r"(b0), "r"(b1));
}
__device__ __forceinline__ void ldsm4(uint32_t* r, uint32_t a) {
    asm volatile("ldmatrix.sync.aligned.m8n8.x4.shared.b16 {%0,%1,%2,%3},[%4];" : "=r"(r[0]), "=r"(r[1]), "=r"(r[2]), "=r"(r[3]) : "r"(a) : "memory");
}
__device__ __forceinline__ void ldsm4t(uint32_t* r, uint32_t a) {
    asm volatile("ldmatrix.sync.aligned.m8n8.x4.trans.shared.b16 {%0,%1,%2,%3},[%4];" : "=r"(r[0]), "=r"(r[1]), "=r"(r[2]), "=r"(r[3]) : "r"(a) : "memory");
}
__device__ __forceinline__ void stsm4(uint32_t a, uint32_t r0, uint32_t r1, uint32_t r2, uint32_t r3) {
    asm volatile("stmatrix.sync.aligned.m8n8.x4.shared.b16 [%0],{%1,%2,%3,%4};" ::"r"(a), "r"(r0), "r"(r1), "r"(r2), "r"(r3) : "memory");
}
__device__ __forceinline__ uint32_t lds32(uint32_t a) { uint32_t v; asm volatile("ld.shared.b32 %0,[%1];" : "=r"(v) : "r"(a) : "memory"); return v; }
__device__ __forceinline__ uint4 lds128(uint32_t a) { uint4 v; asm volatile("ld.shared.v4.b32 {%0,%1,%2,%3},[%4];" : "=r"(v.x), "=r"(v.y), "=r"(v.z), "=r"(v.w) : "r"(a) : "memory"); return v; }
__device__ __forceinline__ void sts16(uint32_t a, uint32_t v) { asm volatile("st.shared.b16 [%0],%1;" ::"r"(a), "h"((unsigned short)v) : "memory"); }
__device__ __forceinline__ void sts32(uint32_t a, uint32_t v) { asm volatile("st.shared.b32 [%0],%1;" ::"r"(a), "r"(v) : "memory"); }
__device__ __forceinline__ void sts64(uint32_t a, uint32_t x, uint32_t y) { asm volatile("st.shared.v2.b32 [%0],{%1,%2};" ::"r"(a), "r"(x), "r"(y) : "memory"); }
__device__ __forceinline__ void sts128(uint32_t a, uint32_t x, uint32_t y, uint32_t z, uint32_t w) { asm volatile("st.shared.v4.b32 [%0],{%1,%2,%3,%4};" ::"r"(a), "r"(x), "r"(y), "r"(z), "r"(w) : "memory"); }
__device__ __forceinline__ uint32_t pack2(float lo, float hi) { uint32_t d; asm("cvt.rn.bf16x2.f32 %0,%1,%2;" : "=r"(d) : "f"(hi), "f"(lo)); return d; }
__device__ __forceinline__ float bf_lo(uint32_t v) { return __uint_as_float(v << 16); }
__device__ __forceinline__ float bf_hi(uint32_t v) { return __uint_as_float(v & 0xffff0000u); }
__device__ __forceinline__ float bf_round(float v) { return bf_lo(pack2(v, 0.f)); }
__device__ __forceinline__ uint32_t hmax2(uint32_t a, uint32_t b) { uint32_t d; asm("max.bf16x2 %0,%1,%2;" : "=r"(d) : "r"(a), "r"(b)); return d; }
__device__ __forceinline__ uint32_t hmin2(uint32_t a, uint32_t b) { uint32_t d; asm("min.bf16x2 %0,%1,%2;" : "=r"(d) : "r"(a), "r"(b)); return d; }
__device__ __forceinline__ uint32_t hmul2(uint32_t a, uint32_t b) { uint32_t d; asm("mul.rn.bf16x2 %0,%1,%2;" : "=r"(d) : "r"(a), "r"(b)); return d; }
__device__ __forceinline__ float ex2(float x) { float y; asm("ex2.approx.ftz.f32 %0,%1;" : "=f"(y) : "f"(x)); return y; }
__device__ __forceinline__ float rcp(float x) { float y; asm("rcp.approx.ftz.f32 %0,%1;" : "=f"(y) : "f"(x)); return y; }
__device__ __forceinline__ unsigned ld_acq(const unsigned* p) { unsigned v; asm volatile("ld.acquire.gpu.global.u32 %0,[%1];" : "=r"(v) : "l"(p) : "memory"); return v; }
__device__ __forceinline__ unsigned ld_rlx(const unsigned* p) { unsigned v; asm volatile("ld.relaxed.gpu.global.u32 %0,[%1];" : "=r"(v) : "l"(p) : "memory"); return v; }
__device__ __forceinline__ uint2 ld_rlx64(const void* p) { uint2 v; asm volatile("{.reg .b64 t; ld.relaxed.gpu.global.b64 t,[%2]; mov.b64 {%0,%1},t;}" : "=r"(v.x), "=r"(v.y) : "l"(p) : "memory"); return v; }
__device__ __forceinline__ uint4 ld_rlx128(const void* p) {
    uint4 v;
    asm volatile("{.reg .b64 t,u; ld.relaxed.gpu.global.v2.b64 {t,u},[%4]; mov.b64 {%0,%1},t; mov.b64 {%2,%3},u;}" : "=r"(v.x), "=r"(v.y), "=r"(v.z), "=r"(v.w) : "l"(p) : "memory");
    return v;
}
__device__ __forceinline__ void st_rlx64(void* p, uint32_t x, uint32_t y) { asm volatile("{.reg .b64 t; mov.b64 t,{%1,%2}; st.relaxed.gpu.global.b64 [%0],t;}" ::"l"(p), "r"(x), "r"(y) : "memory"); }
__device__ __forceinline__ void st_rlx128(void* p, uint4 v) {
    asm volatile("{.reg .b64 t,u; mov.b64 t,{%1,%2}; mov.b64 u,{%3,%4}; st.relaxed.gpu.global.v2.b64 [%0],{t,u};}" ::"l"(p), "r"(v.x), "r"(v.y), "r"(v.z), "r"(v.w) : "memory");
}
__device__ __forceinline__ uint32_t tagw(uint32_t w, uint32_t tag) { return (w & ~1u) | tag; }
__device__ __forceinline__ uint4 tag4(uint32_t x, uint32_t y, uint32_t z, uint32_t w, uint32_t tag) { return make_uint4(tagw(x, tag), y, tagw(z, tag), w); }
__device__ __forceinline__ uint32_t bad4(const uint4& v, uint32_t tag) { return (v.x ^ tag) | (v.z ^ tag); }
__device__ __forceinline__ void bar_named(int id, int n) { asm volatile("bar.sync %0,%1;" ::"r"(id), "r"(n) : "memory"); }

struct cf { float re, im; };
__device__ __forceinline__ cf cmul(cf a, cf b) { cf r; r.re = a.re * b.re - a.im * b.im; r.im = a.re * b.im + a.im * b.re; return r; }
__device__ __forceinline__ cf cexp_p(float arl, float ait, float p) {
    float mag = ex2(arl * p);
    float t = ait * p;
    t = (t - rintf(t)) * 6.283185307179586f;
    cf r; r.re = mag * __cosf(t); r.im = mag * __sinf(t);
    return r;
}

template <int NH>
__device__ __forceinline__ void hedgehog(const uint32_t* a, uint32_t wphi_addr, uint32_t (*out)[8]) {
    uint32_t R[NH][4], mx[NH], mn[NH];
#pragma unroll
    for (int h = 0; h < NH; h++) {
        uint32_t b[4];
        ldsm4t(b, wphi_addr + h * 512);
        float c0[4] = {0.f, 0.f, 0.f, 0.f}, c1[4] = {0.f, 0.f, 0.f, 0.f};
        mma16816(c0, a[4 * h], a[4 * h + 1], a[4 * h + 2], a[4 * h + 3], b[0], b[1]);
        mma16816(c1, a[4 * h], a[4 * h + 1], a[4 * h + 2], a[4 * h + 3], b[2], b[3]);
        R[h][0] = pack2(c0[0], c0[2]); R[h][1] = pack2(c0[1], c0[3]); R[h][2] = pack2(c1[0], c1[2]); R[h][3] = pack2(c1[1], c1[3]);
        mx[h] = hmax2(hmax2(R[h][0], R[h][1]), hmax2(R[h][2], R[h][3]));
        mn[h] = hmin2(hmin2(R[h][0], R[h][1]), hmin2(R[h][2], R[h][3]));
    }
#pragma unroll
    for (int o = 1; o <= 2; o <<= 1)
#pragma unroll
        for (int h = 0; h < NH; h++) { mx[h] = hmax2(mx[h], __shfl_xor_sync(~0u, mx[h], o)); mn[h] = hmin2(mn[h], __shfl_xor_sync(~0u, mn[h], o)); }
    const float L = 1.4426950408889634f;
    float e[NH][4][4], sm[NH][4];
#pragma unroll
    for (int h = 0; h < NH; h++) {
        const float mxl = -bf_lo(mx[h]) * L, mxh = -bf_hi(mx[h]) * L, mnl = bf_lo(mn[h]) * L, mnh = bf_hi(mn[h]) * L;
#pragma unroll
        for (int i = 0; i < 4; i++) {
            const float xl = bf_lo(R[h][i]), xh = bf_hi(R[h][i]);
            e[h][0][i] = ex2(fmaf(xl, L, mxl)); e[h][1][i] = ex2(fmaf(xh, L, mxh));
            e[h][2][i] = ex2(fmaf(xl, -L, mnl)); e[h][3][i] = ex2(fmaf(xh, -L, mnh));
        }
#pragma unroll
        for (int k = 0; k < 4; k++) sm[h][k] = (e[h][k][0] + e[h][k][1]) + (e[h][k][2] + e[h][k][3]);
    }
#pragma unroll
    for (int o = 1; o <= 2; o <<= 1)
#pragma unroll
        for (int h = 0; h < NH; h++)
#pragma unroll
            for (int k = 0; k < 4; k++) sm[h][k] += __shfl_xor_sync(~0u, sm[h][k], o);
#pragma unroll
    for (int h = 0; h < NH; h++)
#pragma unroll
        for (int k = 0; k < 4; k++) {
            const float r = rcp(sm[h][k]);
            out[h][(k >> 1) * 4 + (k & 1)] = pack2(e[h][k][0] * r, e[h][k][1] * r);
            out[h][(k >> 1) * 4 + (k & 1) + 2] = pack2(e[h][k][2] * r, e[h][k][3] * r);
        }
}

__global__ void __launch_bounds__(384, 1)
fused_kernel(const __grid_constant__ CUtensorMap mx, const __grid_constant__ CUtensorMap mw, const __grid_constant__ CUtensorMap mwo,
             const bf16* __restrict__ wphi, const bf16* __restrict__ logA, const bf16* __restrict__ Aim,
             const bf16* __restrict__ Cre, const bf16* __restrict__ Cim, const bf16* __restrict__ logdt, const bf16* __restrict__ Dskip,
             const bf16* __restrict__ gatew, bf16* __restrict__ out) {
    extern __shared__ __align__(1024) uint8_t smem[];
    const uint32_t sb = s2u(smem);
    const int tid = threadIdx.x, warp = __shfl_sync(~0u, tid >> 5, 0), lane = tid & 31;
    const int g = lane >> 2, q = lane & 3;
    const int bi = blockIdx.x, bi_i = bi & 15, bi_j = bi >> 4;
    const uint32_t bar = sb + OFF_BAR;

    if (tid == 0) {
        for (int s = 0; s < 4; s++) mbar_init(bar + 8 * (BAR_FULL + s), 1);
        asm volatile("fence.mbarrier_init.release.cluster;" ::: "memory");
        for (int s = 0; s < 4; s++) {
            mbar_expect(bar + 8 * (BAR_FULL + s), SLOT);
            tma2d(sb + s * SLOT, &mx, ((s + bi_j) & 7) * 64, bi_i * 128, bar + 8 * (BAR_FULL + s));
            tma3d(sb + s * SLOT + 16384, &mw, bi_j * 64, ((s + bi_j) & 7) * 64, 0, bar + 8 * (BAR_FULL + s));
        }
        STAMP(11);
    } else if (tid == 32) {
        if (sb & 1023) __trap();
        for (int s = 0; s < 4; s++) sts32(bar + OFF_CNT + 4 * s, 0);
        mbar_init(bar + 8 * BAR_WPHI, 1); mbar_init(bar + 8 * BAR_WO, 2); mbar_init(bar + 8 * BAR_XT, 8); mbar_init(bar + 8 * BAR_DONE, 8);
        asm volatile("fence.mbarrier_init.release.cluster;" ::: "memory");
        mbar_expect(bar + 8 * BAR_WPHI, 3072);
        bulk_g2s(sb + OFF_GW, gatew, 1024, bar + 8 * BAR_WPHI);
        bulk_g2s(sb + OFF_WPHI, wphi + bi_j * 1024, 2048, bar + 8 * BAR_WPHI);
    }
    const unsigned epoch1 = (ld_rlx(g_done) >> 7) + 1u;
    const uint32_t tag = epoch1 & 1u;
    __syncthreads();

    if (warp < 8) {
        const int wg = warp >> 2, w4 = warp & 3;
        float acc[96];
        const int grow = bi_j * 16 + warp * 2 + (lane >> 4);
        const uint32_t gx_a = grow * 128 + ((((lane & 15) >> 1) ^ (grow & 7)) << 4) + (lane & 1) * 8;
        const int srow = warp * 16 + (lane & 15);
        const uint32_t srow_a = srow * 128;
        const int sx = srow & 7, shi = lane >> 4;
        float gsum = 0.f;
#pragma unroll
        for (int kb = 0; kb < 8; kb++) {
            const int s = kb & 3;
            mbar_wait(bar + 8 * (BAR_FULL + s), kb >> 2);
            if (kb == 0 && warp == 0) STAMP(0);
            const uint32_t st = sb + s * SLOT;
            wg_fence();
#pragma unroll
            for (int k = 0; k < 4; k++)
                wgmma192(acc, mkdesc(st + wg * 8192 + k * 32, 16, 1024), mkdesc(st + 16384 + k * 2048, 8192, 1024), (kb | k) != 0);
            wg_commit();
            if (kb == 0) {
                uint32_t* xt = (uint32_t*)g_xt + (bi_j * 16 + (g >> 2)) * 4096 + (bi_i * 16 + warp * 2) * 16 + (g & 3) * 4 + q;
#pragma unroll
                for (int cb = 0; cb < 8; cb += 2) {
                    uint32_t r[4];
                    ldsm4t(r, st + srow_a + (((cb + shi) ^ sx) << 4));
                    xt[cb * 8192] = r[0]; xt[cb * 8192 + 16] = r[1]; xt[cb * 8192 + 8192] = r[2]; xt[cb * 8192 + 8192 + 16] = r[3];
                }
                __syncwarp();
                if (lane == 0) mbar_arrive(bar + 8 * BAR_XT);
                mbar_wait(bar + 8 * BAR_WPHI, 0);
            }
            {
                uint32_t x0, x1, w0, w1;
                asm volatile("ld.shared.v2.b32 {%0,%1},[%2];" : "=r"(x0), "=r"(x1) : "r"(st + gx_a) : "memory");
                asm volatile("ld.shared.v2.b32 {%0,%1},[%2];" : "=r"(w0), "=r"(w1) : "r"(sb + OFF_GW + ((kb + bi_j) & 7) * 128 + (lane & 15) * 8) : "memory");
                const uint32_t p0 = hmul2(x0, w0), p1 = hmul2(x1, w1);
                gsum += (bf_lo(p0) + bf_hi(p0)) + (bf_lo(p1) + bf_hi(p1));
            }
            if (kb > 0 && kb < 7) {
                wg_wait<1>();
                __syncwarp();
                if (lane == 0) {
                    const int ps = (kb - 1) & 3;
                    unsigned old;
                    asm volatile("atom.acq_rel.cta.shared.add.u32 %0,[%1],1;" : "=r"(old) : "r"(bar + OFF_CNT + 4 * ps) : "memory");
                    if ((old & 7) == 7) {
                        if (kb < 5) {
                            mbar_expect(bar + 8 * (BAR_FULL + ps), SLOT);
                            tma2d(sb + ps * SLOT, &mx, ((kb + 3 + bi_j) & 7) * 64, bi_i * 128, bar + 8 * (BAR_FULL + ps));
                            tma3d(sb + ps * SLOT + 16384, &mw, bi_j * 64, ((kb + 3 + bi_j) & 7) * 64, 0, bar + 8 * (BAR_FULL + ps));
                        } else {
                            mbar_expect(bar + 8 * BAR_WO, 32768);
                            tma2d(sb + ps * SLOT, &mwo, bi_j * 64, ps * 256, bar + 8 * BAR_WO);
                        }
                    }
                }
                __syncwarp();
            }
        }
        wg_wait<0>();
        fence_regs<96>(acc);
        __syncwarp();
        if (lane == 0) mbar_arrive(bar + 8 * BAR_DONE);
        if (warp == 0) STAMP(1);
        uint32_t qa[16], ka[16], va[16];
#pragma unroll
        for (int r = 0; r < 16; r++) {
            qa[r] = pack2(acc[2 * r], acc[2 * r + 1]);
            ka[r] = pack2(acc[32 + 2 * r], acc[32 + 2 * r + 1]);
            va[r] = pack2(acc[64 + 2 * r], acc[64 + 2 * r + 1]);
        }
        const uint32_t wphi_a = sb + OFF_WPHI + (lane & 15) * 32 + (lane >> 4) * 16;
        {
            uint32_t ph[4][8];
            hedgehog<4>(ka, wphi_a, ph);
            mbar_wait(bar + 8 * BAR_DONE, 0);
#pragma unroll
            for (int hh = 0; hh < 4; hh++) {
                const uint32_t pt = sb + OFF_P + (hh >> 1) * 16384 + srow_a, vt = sb + OFF_V + (hh >> 1) * 16384 + srow_a;
                stsm4(pt + (((4 * (hh & 1) + shi) ^ sx) << 4), ph[hh][0], ph[hh][1], ph[hh][2], ph[hh][3]);
                stsm4(pt + (((4 * (hh & 1) + 2 + shi) ^ sx) << 4), ph[hh][4], ph[hh][5], ph[hh][6], ph[hh][7]);
                stsm4(vt + (((2 * (hh & 1) + shi) ^ sx) << 4), va[4 * hh], va[4 * hh + 1], va[4 * hh + 2], va[4 * hh + 3]);
            }
            sts128(sb + OFF_V + shi * 16384 + srow_a + ((4 ^ sx) << 4), 0x3f803f80u, 0x3f803f80u, 0x3f803f80u, 0x3f803f80u);
        }
        asm volatile("fence.proxy.async.shared::cta;" ::: "memory");
        bar_named(1, 256);
        if (warp == 0) STAMP(2);
        {
            float d[32];
            wg_fence();
#pragma unroll
            for (int k = 0; k < 8; k++)
                wgmma64_tt(d, mkdesc(sb + OFF_V + wg * 16384 + k * 2048, 16, 1024), mkdesc(sb + OFF_P + wg * 16384 + k * 2048, 16, 1024), k != 0);
            wg_commit();
            wg_wait<0>();
            fence_regs<32>(d);
            uint4* kvp = g_kvp + bi * 544 + wg * 272;
            if (w4 < 2) {
                uint32_t e[16];
#pragma unroll
                for (int r = 0; r < 16; r++) e[r] = __float_as_uint(w4 ? d[16 + r] : d[r]);
                uint4* p = kvp + w4 * 136 + lane;
#pragma unroll
                for (int ks = 0; ks < 2; ks++)
#pragma unroll
                    for (int nt = 0; nt < 2; nt++)
                        st_rlx128(p + (ks * 2 + nt) * 32, tag4(e[8 * ks + 2 * nt], e[8 * ks + 2 * nt + 1], e[8 * ks + 4 + 2 * nt], e[8 * ks + 4 + 2 * nt + 1], tag));
            } else if (w4 == 2 && lane < 4) {
#pragma unroll
                for (int hl = 0; hl < 2; hl++)
#pragma unroll
                    for (int ks = 0; ks < 2; ks++)
                        st_rlx128(kvp + hl * 136 + 128 + ks * 4 + lane, tag4(__float_as_uint(d[16 * hl + 8 * ks]), __float_as_uint(d[16 * hl + 8 * ks + 1]),
                                                                            __float_as_uint(d[16 * hl + 8 * ks + 4]), __float_as_uint(d[16 * hl + 8 * ks + 5]), tag));
            }
        }
        if (warp == 0) STAMP(3);
        uint32_t pq[4][8];
        hedgehog<2>(qa, wphi_a, pq);
        if (warp == 0) STAMP(12);
        if (warp < 4) {
            const uint4* src = g_kvp + (bi_j * 16 + (lane >> 3) * 4) * 544 + (bi_i >> 2) * 136 + ((lane >> 1) & 3) * 32 + (bi_i & 3) * 8 + warp * 2 + (lane & 1);
            uint4 v[4];
            int n = 0;
            while (true) {
#pragma unroll
                for (int s = 0; s < 4; s++) v[s] = ld_rlx128(src + s * 544);
                if (!__any_sync(~0u, (bad4(v[0], tag) | bad4(v[1], tag) | bad4(v[2], tag) | bad4(v[3], tag)) & 1)) break;
                if (++n > SPIN_LIMIT) __trap();
            }
            float f0 = (__uint_as_float(v[0].x) + __uint_as_float(v[1].x)) + (__uint_as_float(v[2].x) + __uint_as_float(v[3].x));
            float f1 = (__uint_as_float(v[0].y) + __uint_as_float(v[1].y)) + (__uint_as_float(v[2].y) + __uint_as_float(v[3].y));
            float f2 = (__uint_as_float(v[0].z) + __uint_as_float(v[1].z)) + (__uint_as_float(v[2].z) + __uint_as_float(v[3].z));
            float f3 = (__uint_as_float(v[0].w) + __uint_as_float(v[1].w)) + (__uint_as_float(v[2].w) + __uint_as_float(v[3].w));
#pragma unroll
            for (int o = 8; o <= 16; o <<= 1) {
                f0 += __shfl_xor_sync(~0u, f0, o); f1 += __shfl_xor_sync(~0u, f1, o);
                f2 += __shfl_xor_sync(~0u, f2, o); f3 += __shfl_xor_sync(~0u, f3, o);
            }
            if (lane < 8)
                st_rlx64((uint2*)(g_kvf + (bi_j * 4 + (bi_i >> 2)) * 68) + ((bi_i & 3) * 8 + warp * 2 + (lane & 1)) * 4 + (lane >> 1),
                         tagw(pack2(f0, f1), tag), pack2(f2, f3));
        } else if (warp == 4 && (bi_i & 1) == 0) {
            const int hd = bi_i >> 2, qq = (bi_i & 2) + ((lane >> 1) & 1), ks = lane & 1;
            const uint4* src = g_kvp + (bi_j * 16 + (lane >> 2)) * 544 + hd * 136 + 128 + ks * 4 + qq;
            uint4 v[2];
            int n = 0;
            while (true) {
                v[0] = ld_rlx128(src); v[1] = ld_rlx128(src + 8 * 544);
                if (!__any_sync(~0u, (bad4(v[0], tag) | bad4(v[1], tag)) & 1)) break;
                if (++n > SPIN_LIMIT) __trap();
            }
            float f0 = __uint_as_float(v[0].x) + __uint_as_float(v[1].x), f1 = __uint_as_float(v[0].y) + __uint_as_float(v[1].y);
            float f2 = __uint_as_float(v[0].z) + __uint_as_float(v[1].z), f3 = __uint_as_float(v[0].w) + __uint_as_float(v[1].w);
#pragma unroll
            for (int o = 4; o <= 16; o <<= 1) {
                f0 += __shfl_xor_sync(~0u, f0, o); f1 += __shfl_xor_sync(~0u, f1, o);
                f2 += __shfl_xor_sync(~0u, f2, o); f3 += __shfl_xor_sync(~0u, f3, o);
            }
            if (lane < 4) st_rlx64((uint2*)(g_kvf + (bi_j * 4 + hd) * 68 + 64 + qq) + ks, tagw(pack2(f0, f1), tag), pack2(f2, f3));
        }
        if (warp == 0) STAMP(13);
        {
#pragma unroll
            for (int o = 1; o < 16; o <<= 1) gsum += __shfl_xor_sync(~0u, gsum, o);
            const float gate = bf_round(1.0f / (1.0f + __expf(-bf_round(gsum))));
            const uint32_t gv = __shfl_sync(~0u, __float_as_uint(gate) | tag, (lane & 4) * 4);
            if (lane < 8) asm volatile("st.relaxed.gpu.global.u32 [%0],%1;" ::"l"(g_g + (bi_i * 64 + bi_j * 8 + warp) * 8 + lane), "r"(gv) : "memory");
        }
        hedgehog<2>(qa + 8, wphi_a + 1024, pq + 2);
        if (warp == 0) STAMP(4);
        uint4 own[4];
        uint4* og = g_o + (bi_i * 8 + warp) * 1024 + lane;
        {
            uint4 kf[4][3];
            const uint4* kp = g_kvf + bi_j * 272;
            int n = 0;
            while (true) {
                uint32_t bad = 0;
#pragma unroll
                for (int hh = 0; hh < 4; hh++) {
                    kf[hh][0] = ld_rlx128(kp + hh * 68 + lane * 2); kf[hh][1] = ld_rlx128(kp + hh * 68 + lane * 2 + 1); kf[hh][2] = ld_rlx128(kp + hh * 68 + 64 + q);
                }
#pragma unroll
                for (int hh = 0; hh < 4; hh++) bad |= bad4(kf[hh][0], tag) | bad4(kf[hh][1], tag) | bad4(kf[hh][2], tag);
                if (!__any_sync(~0u, bad & 1)) break;
                if (++n > SPIN_LIMIT) __trap();
            }
            if (warp == 0) STAMP(5);
#pragma unroll
            for (int hh = 0; hh < 4; hh++) {
                float n0[4] = {0.f, 0.f, 0.f, 0.f}, n1[4] = {0.f, 0.f, 0.f, 0.f}, dn[4] = {0.f, 0.f, 0.f, 0.f};
                const uint32_t* a = pq[hh];
                mma16816(dn, a[0], a[1], a[2], a[3], kf[hh][2].x, kf[hh][2].y);
                mma16816(n0, a[0], a[1], a[2], a[3], kf[hh][0].x, kf[hh][0].y);
                mma16816(n1, a[0], a[1], a[2], a[3], kf[hh][0].z, kf[hh][0].w);
                mma16816(dn, a[4], a[5], a[6], a[7], kf[hh][2].z, kf[hh][2].w);
                mma16816(n0, a[4], a[5], a[6], a[7], kf[hh][1].x, kf[hh][1].y);
                mma16816(n1, a[4], a[5], a[6], a[7], kf[hh][1].z, kf[hh][1].w);
                const float r0 = rcp(dn[0] + 1e-6f), r1 = rcp(dn[2] + 1e-6f);
                own[hh] = tag4(pack2(n0[0] * r0, n0[1] * r0), pack2(n0[2] * r1, n0[3] * r1), pack2(n1[0] * r0, n1[1] * r0), pack2(n1[2] * r1, n1[3] * r1), tag);
            }
#pragma unroll
            for (int hh = 0; hh < 4; hh++) st_rlx128(og + (bi_j * 4 + hh) * 32, own[hh]);
        }
        if (warp == 0) STAMP(6);
        float oc[32];
        mbar_wait(bar + 8 * BAR_WO, 0);
        auto wdesc = [&](int hg) { return mkdesc(sb + (hg >> 4) * SLOT + (hg & 15) * 2048, 16, 1024); };
        wg_fence();
#pragma unroll
        for (int hh = 0; hh < 4; hh++) wgmma64_rs(oc, own[hh], wdesc(bi_j * 4 + hh), hh != 0);
        wg_commit();
        const uint8_t* yb = (const uint8_t*)g_y + (size_t)(bi_j * 16 + (q >> 1)) * 16384 + (bi_i * 8 + warp) * 128 + g * 16 + (q & 1) * 8;
        const unsigned* gp = g_g + (bi_i * 64 + warp * 8 + (g >> 1)) * 8 + (g & 1) * 4;
        uint2 yv[8]; unsigned g0, g1;
        {
            uint4 fr[7][4];
            const unsigned* probe = (const unsigned*)(og - lane + (((bi_j + 1 + (lane & 7)) & 7) * 4 + 3) * 32 + 31) + 2;
            auto wait_src = [&](unsigned mask) {
                int n = 0;
                while (__ballot_sync(~0u, (ld_rlx(probe) ^ tag) & 1) & mask) { if (++n > SPIN_LIMIT) __trap(); }
            };
            wait_src(0x0fu);
#pragma unroll
            for (int s = 0; s < 4; s++)
#pragma unroll
                for (int hh = 0; hh < 4; hh++) fr[s][hh] = ld_rlx128(og + (((bi_j + 1 + s) & 7) * 4 + hh) * 32);
#pragma unroll
            for (int s = 0; s < 7; s++) {
                const int js = (bi_j + 1 + s) & 7;
                int n = 0;
                while (__any_sync(~0u, (bad4(fr[s][0], tag) | bad4(fr[s][1], tag) | bad4(fr[s][2], tag) | bad4(fr[s][3], tag)) & 1)) {
#pragma unroll
                    for (int hh = 0; hh < 4; hh++) fr[s][hh] = ld_rlx128(og + (js * 4 + hh) * 32);
                    if (++n > SPIN_LIMIT) __trap();
                }
                wg_fence();
#pragma unroll
                for (int hh = 0; hh < 4; hh++) wgmma64_rs(oc, fr[s][hh], wdesc(js * 4 + hh), 1);
                wg_commit();
                if (s == 0) {
                    wait_src(0x70u);
                    wg_wait<0>();
#pragma unroll
                    for (int s2 = 4; s2 < 7; s2++)
#pragma unroll
                        for (int hh = 0; hh < 4; hh++) fr[s2][hh] = ld_rlx128(og + (((bi_j + 1 + s2) & 7) * 4 + hh) * 32);
                    if (warp == 0) STAMP(14);
                }
                if (s == 3) {
                    wg_wait<1>();
#pragma unroll
                    for (int nt = 0; nt < 8; nt++) yv[nt] = ld_rlx64(yb + nt * 32768);
                    g0 = ld_rlx(gp); g1 = ld_rlx(gp + 32);
                }
            }
            if (warp == 0) STAMP(7);
        }
        {
            int n = 0;
            while (true) {
                uint32_t bad = (g0 ^ tag) | (g1 ^ tag);
#pragma unroll
                for (int nt = 0; nt < 8; nt++) bad |= yv[nt].x ^ tag;
                if (!__any_sync(~0u, bad & 1)) break;
#pragma unroll
                for (int nt = 0; nt < 8; nt++) yv[nt] = ld_rlx64(yb + nt * 32768);
                g0 = ld_rlx(gp); g1 = ld_rlx(gp + 32);
                if (++n > SPIN_LIMIT) __trap();
            }
            if (warp == 0) STAMP(8);
            wg_wait<0>();
            fence_regs<32>(oc);
            if (warp == 0) STAMP(9);
            const float ga = bf_hi(g0), gb = bf_hi(g1);
            const float ha = bf_round(1.0f - ga), hb = bf_round(1.0f - gb);
            uint32_t w[8][2];
#pragma unroll
            for (int nt = 0; nt < 8; nt++) {
                w[nt][0] = pack2(fmaf(ga, oc[4 * nt], ha * bf_lo(yv[nt].x)), fmaf(ga, oc[4 * nt + 1], ha * bf_hi(yv[nt].x)));
                w[nt][1] = pack2(fmaf(gb, oc[4 * nt + 2], hb * bf_lo(yv[nt].y)), fmaf(gb, oc[4 * nt + 3], hb * bf_hi(yv[nt].y)));
            }
            const uint32_t ob = sb + OFF_OUT + warp * 2048;
#pragma unroll
            for (int nt = 0; nt < 8; nt += 2)
                stsm4(ob + (lane & 15) * 128 + (((nt + shi) ^ (lane & 7)) << 4), w[nt][0], w[nt][1], w[nt + 1][0], w[nt + 1][1]);
            __syncwarp();
            bf16* op = out + (size_t)(bi_i * 128 + warp * 16) * 512 + bi_j * 64 + (lane & 7) * 8;
#pragma unroll
            for (int it = 0; it < 4; it++) {
                const int r = it * 4 + (lane >> 3);
                uint4 v = lds128(ob + r * 128 + (((lane & 7) ^ (r & 7)) << 4));
                *(uint4*)(op + r * 512) = v;
            }
        }
        if (warp == 0) STAMP(10);
    } else {
        const int w4 = warp - 8, ch = bi * 4 + w4, st = tid - 256;
        const uint32_t ub = sb + OFF_U + w4 * U_STRIDE + 256, kb_ = sb + OFF_K + w4 * K_STRIDE, buf = sb + OFF_BUF + w4 * BUF_STRIDE;
        const uint32_t spare = sb + (w4 < 2 ? OFF_SP0 : OFF_SP1) + (w4 & 1) * 4096;
        const uint2 pla = __ldg((const uint2*)(logA + ch * 128) + lane), pai = __ldg((const uint2*)(Aim + ch * 128) + lane);
        const uint2 pcr = __ldg((const uint2*)(Cre + ch * 128) + lane), pci = __ldg((const uint2*)(Cim + ch * 128) + lane);
        const float dt = bf_round(expf(__bfloat162float(logdt[ch])));
        const float dskip = __bfloat162float(Dskip[ch]);
#pragma unroll
        for (int v = 0; v < 7; v++) if (v * 32 + lane < K_STRIDE / 16) sts128(kb_ + (v * 32 + lane) * 16, 0, 0, 0, 0);
        if (lane < 16) sts128(ub - 256 + lane * 16, 0, 0, 0, 0);
        float kc[6][4];
#pragma unroll
        for (int t = 0; t < 6; t++) { kc[t][0] = kc[t][1] = kc[t][2] = kc[t][3] = 0.f; }
#pragma unroll 1
        for (int c = 0; c < 4; c++) {
            const int sh = (c & 1) * 16;
            auto pick = [&](const uint2& v) { return __uint_as_float(((c & 2 ? v.y : v.x) >> sh) << 16); };
            const float ea = bf_round(expf(pick(pla)));
            const float arl = (-ea * dt) * 1.4426950408889634f, ait = (pick(pai) * dt) * 0.15915494309189535f;
            cf C2; C2.re = 2.0f * (pick(pcr) * dt); C2.im = 2.0f * (pick(pci) * dt);
            const cf z1 = cexp_p(arl, ait, 1.0f), z128 = cexp_p(arl, ait, 128.0f);
            cf z8 = cexp_p(arl, ait, 8.0f); z8.im = -z8.im;
            const uint32_t lp = buf + lane * 4;
            auto put = [&](int row, const cf& v) { sts32((lp ^ ((row & 7) << 4)) + row * 128, pack2(v.re, v.im)); };
            {
                const cf z16 = cmul(z8, z8);
                cf e; e.re = 1.f; e.im = 0.f;
                cf o = z8;
                put(0, e); put(1, o);
                e = z16; put(2, e);
#pragma unroll
                for (int b = 3; b < 16; b += 2) {
                    o = cmul(o, z16); put(b, o);
                    if (b + 1 < 16) { e = cmul(e, z16); put(b + 1, e); }
                }
            }
            cf h[8];
            h[0] = C2; put(16, h[0]);
            {
                const cf z2 = cmul(z1, z1);
                h[1] = cmul(h[0], z1);
#pragma unroll
                for (int r = 2; r < 8; r++) h[r] = cmul(h[r - 2], z2);
#pragma unroll
                for (int r = 1; r < 8; r++) put(16 + r, h[r]);
            }
#pragma unroll
            for (int r = 0; r < 8; r++) { h[r] = cmul(h[r], z128); put(24 + r, h[r]); }
#pragma unroll
            for (int al = 0; al < 2; al++)
#pragma unroll
                for (int r = 0; r < 4; r++) { h[2 * r] = cmul(h[2 * r], z128); put(32 + al * 4 + r, h[2 * r]); }
#pragma unroll
            for (int al = 0; al < 4; al++)
#pragma unroll
                for (int r = 0; r < 2; r++) { h[4 * r] = cmul(h[4 * r], z128); put(40 + al * 2 + r, h[4 * r]); }
#pragma unroll
            for (int al = 0; al < 9; al++) { h[0] = cmul(h[0], z128); put(48 + al, h[0]); }
            __syncwarp();
            if (c == 2 && warp == 8) {
                mbar_wait_slow(bar + 8 * BAR_XT, 0);
                if (lane == 0) asm volatile("red.release.gpu.global.add.u32 [%0],8;" ::"l"(g_xcnt + bi_j * 32) : "memory");
                __syncwarp();
            }
            const int lr = lane & 7, lm = lane >> 3;
#pragma unroll
            for (int kp = 0; kp < 2; kp++) {
                uint32_t a0[4], a1[4];
                ldsm4(a0, buf + ((lm & 1) * 8 + lr) * 128 + (((4 * kp + (lm >> 1)) ^ lr) << 4));
                ldsm4(a1, buf + ((lm & 1) * 8 + lr) * 128 + (((4 * kp + 2 + (lm >> 1)) ^ lr) << 4));
#pragma unroll
                for (int t = 0; t < 6; t++) {
                    uint32_t b[4];
                    ldsm4(b, buf + (16 + 8 * t + lr) * 128 + (((4 * kp + lm) ^ lr) << 4));
                    mma16816(kc[t], a0[0], a0[1], a0[2], a0[3], b[0], b[1]);
                    mma16816(kc[t], a1[0], a1[1], a1[2], a1[3], b[2], b[3]);
                }
            }
            __syncwarp();
        }
        if (warp == 8) STAMP(16);
        if (lane == 0) {
            int n = 0;
            while ((int)(ld_acq(g_xcnt + bi_j * 32) - (epoch1 << 7)) < 0) { __nanosleep(100); if (++n > SPIN_LIMIT) __trap(); }
        }
        __syncwarp();
        uint4 ur[8];
#pragma unroll
        for (int v = 0; v < 8; v++) ur[v] = __ldcg(g_xt + bi * 1024 + st + 128 * v);
        if (lane == 0) kc[0][0] += dskip;
        const uint32_t k1024 = __shfl_sync(~0u, pack2(kc[4][0], 0.f), 0);
#pragma unroll
        for (int i = 0; i < 2; i++) {
            const int be = g + 8 * i;
#pragma unroll
            for (int t = 0; t < 2; t++) {
                const uint32_t a = kb_ + (KW_D + 128 * t + 8 * be + 2 * q) * 4;
                const uint32_t w = pack2(kc[t][2 * i + 1], kc[t][2 * i]);
                sts32(a + 4, w); sts16(a, w >> 16); sts16(a + 10, w);
            }
            {
                const int p = 256 + 128 * (q >> 1) + 8 * be + 4 * (q & 1);
                const uint32_t a = kb_ + (KW_D + p) * 4;
                const uint32_t w = pack2(kc[2][2 * i + 1], kc[2][2 * i]);
                const uint32_t aa = (w >> 16) | (w & 0xffff0000u);
                if (p != 256) { sts16(a - 4, aa); sts32(a, aa); } else sts16(a, aa);
                sts32(a + 4, aa); sts32(a + 8, w); sts16(a + 14, w);
            }
            {
                const int k = 64 + 16 * q + be;
                const uint32_t w = pack2(kc[3][2 * i], kc[3][2 * i + 1]);
                if (k != 64) sts16(kb_ + (KW_2 + ((k - 1) >> 1) - 24) * 4 + (k & 1) * 2, w);
                else {
                    const uint32_t a = kb_ + (KW_D + 511) * 4, aa = (w << 16) | (w & 0xffffu);
                    sts16(a, w); sts32(a + 4, aa); sts32(a + 8, aa); sts32(a + 12, aa); sts16(a + 18, w);
                }
                sts16(kb_ + (KW_2 + 48 + (k >> 1) - 24) * 4 + ((k & 1) ^ 1) * 2, w >> 16);
            }
#pragma unroll
            for (int b = 0; b < 2; b++) {
                const int k = 64 + 8 * (2 * q + b) + (be >> 1);
                const uint32_t w = pack2(kc[4][2 * i + b], 0.f);
                if (!(be & 1) && k == 64) sts16(kb_ + (KW_2 + 63 - 24) * 4, w);
                else {
                    const uint32_t a = kb_ + (KW_3 + ((be & 1) ? 80 + k : k - 1) - 48) * 4;
                    sts16(a, w);
                    if (!((be & 1) && k == 127)) sts16(a + 6, w);
                }
            }
        }
        if (lane == 0) sts16(kb_ + (KW_3 + 127 - 48) * 4, pack2(kc[5][0], 0.f));
        if (lane < 2) sts128(buf + lane * W3_OFF, 0, 0, 0, 0);
#pragma unroll
        for (int v = 0; v < 8; v++) {
            const int ci = (st >> 2) + 32 * v;
            sts128(sb + OFF_U + (st & 3) * U_STRIDE + 256 + ((ci ^ ((ci >> 3) & 1)) << 4), ur[v].x, ur[v].y, ur[v].z, ur[v].w);
        }
        mbar_wait_slow(bar + 8 * BAR_WO, 0);
        bar_named(2, 128);
        if (warp == 8) STAMP(17);
        float y[16][4];
#pragma unroll
        for (int nt = 0; nt < 16; nt++) { y[nt][0] = y[nt][1] = y[nt][2] = y[nt][3] = 0.f; }
        {
            uint32_t Bp[32];
            auto uaddr = [&](int rho) { const int R0 = (lane >> 4) * 8 + (lane & 7) - rho; return ub + (((2 * R0 + ((lane >> 3) & 1)) ^ ((R0 >> 2) & 1)) << 4); };
            const uint32_t kd = kb_ + (KW_D + g - 2 * q) * 4;
            {
                const uint32_t a = uaddr(0);
#pragma unroll
                for (int p = 0; p < 8; p++) ldsm4(Bp + 4 * p, a + p * 512);
            }
#pragma unroll 1
            for (int rho = 0; rho < 8; rho++) {
                uint32_t A[5][4];
#pragma unroll
                for (int ga = 0; ga < 5; ga++) {
                    const uint32_t a = kd + (ga < 4 ? rho : (rho & 1)) * 64 + ga * 512;
                    A[ga][0] = lds32(a); A[ga][1] = lds32(a + 32); A[ga][2] = lds32(a - 32); A[ga][3] = lds32(a);
                }
                const int ci = lane + 32 * rho;
                uint4 e4[4];
#pragma unroll
                for (int v = 0; v < 4; v++) { const int cc = ci - 3 + v; e4[v] = lds128(ub + ((cc ^ ((cc >> 3) & 1)) << 4)); }
                if (rho < 2) {
#pragma unroll
                    for (int nt = 4; nt < 16; nt++) mma16816(y[nt], A[4][0], A[4][1], A[4][2], A[4][3], Bp[2 * (nt - 4)], Bp[2 * (nt - 4) + 1]);
                }
#pragma unroll
                for (int ga = 0; ga < 3; ga++)
#pragma unroll
                    for (int nt = ga; nt < 16; nt++) mma16816(y[nt], A[ga][0], A[ga][1], A[ga][2], A[ga][3], Bp[2 * (nt - ga)], Bp[2 * (nt - ga) + 1]);
                {
                    float S[29];
                    const uint32_t* ew = (const uint32_t*)e4;
                    S[3] = 0.f;
#pragma unroll
                    for (int k = 4; k <= 28; k++) S[k] = S[k - 1] + ((k & 1) ? bf_hi(ew[k >> 1]) : bf_lo(ew[k >> 1]));
                    auto win = [&](int lo, int hi, uint32_t a, bool on) {
                        const uint32_t w0 = pack2(S[hi] - S[lo - 1], S[hi + 1] - S[lo]), w1 = pack2(S[hi + 2] - S[lo + 1], S[hi + 3] - S[lo + 2]);
                        const uint32_t w2 = pack2(S[hi + 4] - S[lo + 3], S[hi + 5] - S[lo + 4]), w3 = pack2(S[hi + 6] - S[lo + 5], S[hi + 7] - S[lo + 6]);
                        asm volatile("{.reg .pred p; setp.ne.b32 p,%5,0; @p st.shared.v4.b32 [%0],{%1,%2,%3,%4};}" ::"r"(a), "r"(w0), "r"(w1), "r"(w2), "r"(w3), "r"((int)on) : "memory");
                    };
                    const uint32_t sw = (ci ^ ((ci >> 3) & 1)) << 4;
                    win(14, 18, buf + W5_OFF + 16 + ci * 16, rho < 6); win(19, 21, buf + W3_OFF + 16 + ci * 16, rho < 6);
                    win(4, 12, buf + W9_OFF + sw, rho < 4); win(13, 19, spare + sw, rho < 4); win(20, 21, spare + 2048 + sw, rho < 4);
                }
                const uint32_t an = uaddr(rho + 1);
                ldsm4(Bp + 28, an + 7 * 512);
#pragma unroll
                for (int nt = 3; nt < 16; nt++) {
                    mma16816(y[nt], A[3][0], A[3][1], A[3][2], A[3][3], Bp[2 * (nt - 3)], Bp[2 * (nt - 3) + 1]);
                    if ((nt & 1) == 0) ldsm4(Bp + 2 * (nt - 4), an + ((nt - 4) >> 1) * 512);
                    if (nt == 15) ldsm4(Bp + 24, an + 6 * 512);
                }
            }
        }
        __syncwarp();
        if (warp == 8) STAMP(18);
#pragma unroll 1
        for (int ph = 0; ph < 2; ph++) {
            uint32_t B[5][2];
            const uint32_t ka = kb_ + (KW_2 + ph * 48 + 8 + g - q) * 4;
#pragma unroll
            for (int dd = 0; dd < 5; dd++) { B[dd][0] = lds32(ka + dd * 32); B[dd][1] = lds32(ka + dd * 32 - 16); }
            const uint32_t wa = buf + ph * W3_OFF + ((lane & 7) + ((lane >> 3) & 1) + (lane >> 4) * 8) * 16;
#pragma unroll
            for (int s = 0; s < 12; s++) {
                uint32_t A[4];
                ldsm4t(A, wa + s * 256);
#pragma unroll
                for (int dd = 0; dd < 5; dd++)
                    if (s + 4 + dd < 16) mma16816(y[s + 4 + dd], A[0], A[1], A[2], A[3], B[dd][0], B[dd][1]);
            }
        }
        {
            const int ap = (lane & 7) + (lane >> 4) * 8;
            const uint32_t loff = ((2 * ap + ((lane >> 3) & 1)) ^ ((ap >> 2) & 1)) << 4;
#pragma unroll 1
            for (int ph = 0; ph < 2; ph++) {
                uint32_t B[8][2];
                const uint32_t wb = (ph ? spare : buf + W9_OFF) + loff;
                const uint32_t ka = kb_ + (KW_3 + ph * 80 + 16 + g - 2 * q) * 4;
#pragma unroll
                for (int dd = 0; dd < 8; dd++) { B[dd][0] = lds32(ka + dd * 32); B[dd][1] = lds32(ka + dd * 32 - 32); }
#pragma unroll
                for (int s = 0; s < 4; s++) {
                    uint32_t A[4];
                    ldsm4t(A, wb + s * 512);
#pragma unroll
                    for (int dd = 0; dd < 8; dd++)
                        if (8 + 2 * s + dd < 16) mma16816(y[8 + 2 * s + dd], A[0], A[1], A[2], A[3], B[dd][0], B[dd][1]);
                }
            }
            const uint32_t idw = (g == 2 * q) ? k1024 : ((g == 2 * q + 1) ? (k1024 << 16) : 0u);
#pragma unroll
            for (int s = 0; s < 4; s++) {
                uint32_t A[4];
                ldsm4t(A, spare + 2048 + loff + s * 512);
                mma16816(y[8 + 2 * s], A[0], A[1], A[2], A[3], idw, 0u);
                mma16816(y[9 + 2 * s], A[0], A[1], A[2], A[3], 0u, idw);
            }
        }
        __syncwarp();
        if (warp == 8) STAMP(19);
#pragma unroll
        for (int nt = 0; nt < 16; nt++)
#pragma unroll
            for (int b = 0; b < 2; b++) sts32(buf + ((8 * nt + 2 * q + b) * 8 + g) * 4, pack2(y[nt][b], y[nt][2 + b]));
        bar_named(2, 128);
        uint4* yp = g_y + bi * 1024 + st;
#pragma unroll
        for (int v = 0; v < 8; v++) {
            const uint32_t a = sb + OFF_BUF + (st + 128 * v) * 4;
            const uint32_t w0 = lds32(a), w1 = lds32(a + BUF_STRIDE), w2 = lds32(a + 2 * BUF_STRIDE), w3 = lds32(a + 3 * BUF_STRIDE);
            st_rlx128(yp + v * 128, tag4(__byte_perm(w0, w1, 0x5410), __byte_perm(w0, w1, 0x7632), __byte_perm(w2, w3, 0x5410), __byte_perm(w2, w3, 0x7632), tag));
        }
        if (warp == 8) STAMP(20);
    }
    __syncthreads();
    if (tid == 0) atomicAdd(g_done, 1u);
}

typedef CUresult (*EncFn)(CUtensorMap*, CUtensorMapDataType, cuuint32_t, void*, const cuuint64_t*, const cuuint64_t*, const cuuint32_t*,
                          const cuuint32_t*, CUtensorMapInterleave, CUtensorMapSwizzle, CUtensorMapL2promotion, CUtensorMapFloatOOBfill);

extern "C" void kernel_launch(void* const* d_in, const int* in_sizes, int n_in, void* d_out, int out_size) {
    static EncFn enc = nullptr;
    if (!enc) {
        cudaDriverEntryPointQueryResult qr;
        cudaGetDriverEntryPoint("cuTensorMapEncodeTiled", (void**)&enc, cudaEnableDefault, &qr);
        cudaFuncSetAttribute(fused_kernel, cudaFuncAttributeMaxDynamicSharedMemorySize, SMEM_BYTES);
    }
    CUtensorMap mx, mw, mwo;
    const cuuint32_t es[3] = {1, 1, 1};
    {
        cuuint64_t d[2] = {512, 2048}, s[1] = {1024}; cuuint32_t b[2] = {64, 128};
        enc(&mx, CU_TENSOR_MAP_DATA_TYPE_BFLOAT16, 2, d_in[0], d, s, b, es, CU_TENSOR_MAP_INTERLEAVE_NONE, CU_TENSOR_MAP_SWIZZLE_128B,
            CU_TENSOR_MAP_L2_PROMOTION_L2_128B, CU_TENSOR_MAP_FLOAT_OOB_FILL_NONE);
    }
    {
        cuuint64_t d[3] = {512, 512, 3}, s[2] = {3072, 1024}; cuuint32_t b[3] = {64, 64, 3};
        enc(&mw, CU_TENSOR_MAP_DATA_TYPE_BFLOAT16, 3, d_in[1], d, s, b, es, CU_TENSOR_MAP_INTERLEAVE_NONE, CU_TENSOR_MAP_SWIZZLE_128B,
            CU_TENSOR_MAP_L2_PROMOTION_L2_128B, CU_TENSOR_MAP_FLOAT_OOB_FILL_NONE);
    }
    {
        cuuint64_t d[2] = {512, 512}, s[1] = {1024}; cuuint32_t b[2] = {64, 256};
        enc(&mwo, CU_TENSOR_MAP_DATA_TYPE_BFLOAT16, 2, d_in[3], d, s, b, es, CU_TENSOR_MAP_INTERLEAVE_NONE, CU_TENSOR_MAP_SWIZZLE_128B,
            CU_TENSOR_MAP_L2_PROMOTION_L2_128B, CU_TENSOR_MAP_FLOAT_OOB_FILL_NONE);
    }
    fused_kernel<<<128, 384, SMEM_BYTES, cudaStreamPerThread>>>(
        mx, mw, mwo, (const bf16*)d_in[2], (const bf16*)d_in[5], (const bf16*)d_in[6], (const bf16*)d_in[7],
        (const bf16*)d_in[8], (const bf16*)d_in[9], (const bf16*)d_in[10], (const bf16*)d_in[11], (bf16*)d_out);
}
```

```cpp
#include <cuda_runtime.h>
#include <cuda.h>
#include <cuda_bf16.h>
#include <stdint.h>

typedef __nv_bfloat16 bf16;

__device__ unsigned g_done[32];
__device__ unsigned g_xcnt[8 * 32];
__device__ uint4 g_xt[128 * 1024];
__device__ uint4 g_kvp[8 * 16 * 544];
__device__ uint4 g_kvf[8 * 4 * 68];
__device__ uint4 g_o[16 * 8 * 32 * 32];
__device__ uint4 g_y[128 * 1024];
__device__ unsigned g_g[1024 * 8];
#define STAMP(n)

constexpr int SLOT = 40960;
constexpr int OFF_SP0 = 32768, OFF_SP1 = SLOT + 32768;
constexpr int OFF_P = 2 * SLOT, OFF_V = OFF_P + 32768;
constexpr int OFF_U = 4 * SLOT, U_STRIDE = 4096 + 256;
constexpr int OFF_K = OFF_U + 4 * U_STRIDE, K_STRIDE = 3264;
constexpr int OFF_BUF = OFF_K + 4 * K_STRIDE, BUF_STRIDE = 8320;
constexpr int OFF_WPHI = OFF_BUF + 4 * BUF_STRIDE;
constexpr int OFF_GW = OFF_WPHI + 2048;
constexpr int OFF_BAR = OFF_GW + 1024;
constexpr int SMEM_BYTES = OFF_BAR + 128 + 128;
static_assert(SMEM_BYTES <= 232448 && OFF_BUF % 128 == 0, "smem");
constexpr int KW_D = 16, KW_2 = 560, KW_3 = 656;
constexpr int W5_OFF = 0, W3_OFF = 3088, W9_OFF = 6176;
constexpr int BAR_FULL = 0, BAR_WPHI = 4, BAR_WO = 5, BAR_XT = 6, BAR_DONE = 7, BAR_KG = 8, BAR_WO2 = 9, OFF_CNT = 96;
constexpr int SPIN_LIMIT = 1 << 17;

__device__ __forceinline__ uint32_t s2u(const void* p) { return (uint32_t)__cvta_generic_to_shared(p); }
__device__ __forceinline__ void mbar_init(uint32_t b, int c) { asm volatile("mbarrier.init.shared::cta.b64 [%0],%1;" ::"r"(b), "r"(c) : "memory"); }
__device__ __forceinline__ void mbar_expect(uint32_t b, int bytes) { asm volatile("mbarrier.arrive.expect_tx.shared::cta.b64 _,[%0],%1;" ::"r"(b), "r"(bytes) : "memory"); }
__device__ __forceinline__ void mbar_arrive(uint32_t b) { asm volatile("mbarrier.arrive.shared::cta.b64 _,[%0];" ::"r"(b) : "memory"); }
__device__ __forceinline__ bool mbar_try(uint32_t b, int ph) {
    uint32_t ok;
    asm volatile("{.reg .pred p; mbarrier.try_wait.parity.shared::cta.b64 p,[%1],%2; selp.u32 %0,1,0,p;}" : "=r"(ok) : "r"(b), "r"(ph) : "memory");
    return ok;
}
__device__ __forceinline__ void mbar_wait(uint32_t b, int ph) {
    if ((threadIdx.x & 31) == 0) { int n = 0; while (!mbar_try(b, ph)) { if (++n > SPIN_LIMIT) break; } }
    __syncwarp();
}
__device__ __forceinline__ void tma2d(uint32_t dst, const CUtensorMap* m, int c0, int c1, uint32_t bar) {
    asm volatile("cp.async.bulk.tensor.2d.shared::cluster.global.mbarrier::complete_tx::bytes [%0],[%1,{%3,%4}],[%2];" ::"r"(dst), "l"(m), "r"(bar), "r"(c0), "r"(c1) : "memory");
}
__device__ __forceinline__ void tma3d(uint32_t dst, const CUtensorMap* m, int c0, int c1, int c2, uint32_t bar) {
    asm volatile("cp.async.bulk.tensor.3d.shared::cluster.global.mbarrier::complete_tx::bytes [%0],[%1,{%3,%4,%5}],[%2];" ::"r"(dst), "l"(m), "r"(bar), "r"(c0), "r"(c1), "r"(c2) : "memory");
}
__device__ __forceinline__ void bulk_g2s(uint32_t dst, const void* src, int bytes, uint32_t bar) {
    asm volatile("cp.async.bulk.shared::cluster.global.mbarrier::complete_tx::bytes [%0],[%1],%2,[%3];" ::"r"(dst), "l"(src), "r"(bytes), "r"(bar) : "memory");
}
__device__ __forceinline__ uint64_t mkdesc(uint32_t addr, uint32_t lbo, uint32_t sbo) {
    return (uint64_t)((addr & 0x3FFFF) >> 4) | ((uint64_t)(lbo >> 4) << 16) | ((uint64_t)(sbo >> 4) << 32) | ((uint64_t)1 << 62);
}
__device__ __forceinline__ void wg_fence() { asm volatile("wgmma.fence.sync.aligned;" ::: "memory"); }
__device__ __forceinline__ void wg_commit() { asm volatile("wgmma.commit_group.sync.aligned;" ::: "memory"); }
template <int N> __device__ __forceinline__ void wg_wait() { asm volatile("wgmma.wait_group.sync.aligned %0;" ::"n"(N) : "memory"); }
template <int N> __device__ __forceinline__ void fence_regs(float* d) {
#pragma unroll
    for (int i = 0; i < N; i++) asm volatile("" : "+f"(d[i])::"memory");
}
#define R8(d, o) "+f"(d[o]), "+f"(d[o + 1]), "+f"(d[o + 2]), "+f"(d[o + 3]), "+f"(d[o + 4]), "+f"(d[o + 5]), "+f"(d[o + 6]), "+f"(d[o + 7])
__device__ __forceinline__ void wgmma192(float* d, uint64_t da, uint64_t db) {
    asm volatile("wgmma.mma_async.sync.aligned.m64n192k16.f32.bf16.bf16 {"
                 "%0,%1,%2,%3,%4,%5,%6,%7,%8,%9,%10,%11,%12,%13,%14,%15,%16,%17,%18,%19,%20,%21,%22,%23,%24,%25,%26,%27,%28,%29,%30,%31,"
                 "%32,%33,%34,%35,%36,%37,%38,%39,%40,%41,%42,%43,%44,%45,%46,%47,%48,%49,%50,%51,%52,%53,%54,%55,%56,%57,%58,%59,%60,%61,%62,%63,"
                 "%64,%65,%66,%67,%68,%69,%70,%71,%72,%73,%74,%75,%76,%77,%78,%79,%80,%81,%82,%83,%84,%85,%86,%87,%88,%89,%90,%91,%92,%93,%94,%95},"
                 "%96,%97,1,1,1,0,1;"
                 : R8(d, 0), R8(d, 8), R8(d, 16), R8(d, 24), R8(d, 32), R8(d, 40), R8(d, 48), R8(d, 56), R8(d, 64), R8(d, 72), R8(d, 80), R8(d, 88)
                 : "l"(da), "l"(db));
}
__device__ __forceinline__ void wgmma64_tt(float* d, uint64_t da, uint64_t db, int sc) {
    asm volatile("{.reg .pred p; setp.ne.b32 p,%34,0; wgmma.mma_async.sync.aligned.m64n64k16.f32.bf16.bf16 {"
                 "%0,%1,%2,%3,%4,%5,%6,%7,%8,%9,%10,%11,%12,%13,%14,%15,%16,%17,%18,%19,%20,%21,%22,%23,%24,%25,%26,%27,%28,%29,%30,%31},"
                 "%32,%33,p,1,1,1,1;}"
                 : R8(d, 0), R8(d, 8), R8(d, 16), R8(d, 24)
                 : "l"(da), "l"(db), "r"(sc));
}
__device__ __forceinline__ void wgmma128_rs(float* d, const uint4& a, uint64_t db, int sc) {
    asm volatile("{.reg .pred p; setp.ne.b32 p,%69,0; wgmma.mma_async.sync.aligned.m64n128k16.f32.bf16.bf16 {"
                 "%0,%1,%2,%3,%4,%5,%6,%7,%8,%9,%10,%11,%12,%13,%14,%15,%16,%17,%18,%19,%20,%21,%22,%23,%24,%25,%26,%27,%28,%29,%30,%31,"
                 "%32,%33,%34,%35,%36,%37,%38,%39,%40,%41,%42,%43,%44,%45,%46,%47,%48,%49,%50,%51,%52,%53,%54,%55,%56,%57,%58,%59,%60,%61,%62,%63},"
                 "{%64,%65,%66,%67},%68,p,1,1,1;}"
                 : R8(d, 0), R8(d, 8), R8(d, 16), R8(d, 24), R8(d, 32), R8(d, 40), R8(d, 48), R8(d, 56)
                 : "r"(a.x), "r"(a.y), "r"(a.z), "r"(a.w), "l"(db), "r"(sc));
}
__device__ __forceinline__ void mma16816v(float* c, uint32_t a0, uint32_t a1, uint32_t a2, uint32_t a3, uint32_t b0, uint32_t b1) {
    asm volatile("mma.sync.aligned.m16n8k16.row.col.f32.bf16.bf16.f32 {%0,%1,%2,%3},{%4,%5,%6,%7},{%8,%9},{%0,%1,%2,%3};"
        : "+f"(c[0]), "+f"(c[1]), "+f"(c[2]), "+f"(c[3]) : "r"(a0), "r"(a1), "r"(a2), "r"(a3), "r"(b0), "r"(b1));
}
__device__ __forceinline__ void mma16816(float* c, uint32_t a0, uint32_t a1, uint32_t a2, uint32_t a3, uint32_t b0, uint32_t b1) {
    asm("mma.sync.aligned.m16n8k16.row.col.f32.bf16.bf16.f32 {%0,%1,%2,%3},{%4,%5,%6,%7},{%8,%9},{%0,%1,%2,%3};"
        : "+f"(c[0]), "+f"(c[1]), "+f"(c[2]), "+f"(c[3]) : "r"(a0), "r"(a1), "r"(a2), "r"(a3), "r"(b0), "r"(b1));
}
__device__ __forceinline__ void ldsm4(uint32_t* r, uint32_t a) {
    asm volatile("ldmatrix.sync.aligned.m8n8.x4.shared.b16 {%0,%1,%2,%3},[%4];" : "=r"(r[0]), "=r"(r[1]), "=r"(r[2]), "=r"(r[3]) : "r"(a) : "memory");
}
__device__ __forceinline__ void ldsm4t(uint32_t* r, uint32_t a) {
    asm volatile("ldmatrix.sync.aligned.m8n8.x4.trans.shared.b16 {%0,%1,%2,%3},[%4];" : "=r"(r[0]), "=r"(r[1]), "=r"(r[2]), "=r"(r[3]) : "r"(a) : "memory");
}
__device__ __forceinline__ void stsm4(uint32_t a, uint32_t r0, uint32_t r1, uint32_t r2, uint32_t r3) {
    asm volatile("stmatrix.sync.aligned.m8n8.x4.shared.b16 [%0],{%1,%2,%3,%4};" ::"r"(a), "r"(r0), "r"(r1), "r"(r2), "r"(r3) : "memory");
}
__device__ __forceinline__ uint32_t lds32(uint32_t a) { uint32_t v; asm volatile("ld.shared.b32 %0,[%1];" : "=r"(v) : "r"(a) : "memory"); return v; }
__device__ __forceinline__ uint4 lds128(uint32_t a) { uint4 v; asm volatile("ld.shared.v4.b32 {%0,%1,%2,%3},[%4];" : "=r"(v.x), "=r"(v.y), "=r"(v.z), "=r"(v.w) : "r"(a) : "memory"); return v; }
__device__ __forceinline__ void sts16(uint32_t a, uint32_t v) { asm volatile("st.shared.b16 [%0],%1;" ::"r"(a), "h"((unsigned short)v) : "memory"); }
__device__ __forceinline__ void sts32(uint32_t a, uint32_t v) { asm volatile("st.shared.b32 [%0],%1;" ::"r"(a), "r"(v) : "memory"); }
__device__ __forceinline__ void sts64(uint32_t a, uint32_t x, uint32_t y) { asm volatile("st.shared.v2.b32 [%0],{%1,%2};" ::"r"(a), "r"(x), "r"(y) : "memory"); }
__device__ __forceinline__ void sts128(uint32_t a, uint32_t x, uint32_t y, uint32_t z, uint32_t w) { asm volatile("st.shared.v4.b32 [%0],{%1,%2,%3,%4};" ::"r"(a), "r"(x), "r"(y), "r"(z), "r"(w) : "memory"); }
__device__ __forceinline__ uint32_t pack2(float lo, float hi) { uint32_t d; asm("cvt.rn.bf16x2.f32 %0,%1,%2;" : "=r"(d) : "f"(hi), "f"(lo)); return d; }
__device__ __forceinline__ float bf_lo(uint32_t v) { return __uint_as_float(v << 16); }
__device__ __forceinline__ float bf_hi(uint32_t v) { return __uint_as_float(v & 0xffff0000u); }
__device__ __forceinline__ float bf_round(float v) { return bf_lo(pack2(v, 0.f)); }
__device__ __forceinline__ uint32_t hmax2(uint32_t a, uint32_t b) { uint32_t d; asm("max.bf16x2 %0,%1,%2;" : "=r"(d) : "r"(a), "r"(b)); return d; }
__device__ __forceinline__ uint32_t hmin2(uint32_t a, uint32_t b) { uint32_t d; asm("min.bf16x2 %0,%1,%2;" : "=r"(d) : "r"(a), "r"(b)); return d; }
__device__ __forceinline__ uint32_t hmul2(uint32_t a, uint32_t b) { uint32_t d; asm("mul.rn.bf16x2 %0,%1,%2;" : "=r"(d) : "r"(a), "r"(b)); return d; }
__device__ __forceinline__ float ex2(float x) { float y; asm("ex2.approx.ftz.f32 %0,%1;" : "=f"(y) : "f"(x)); return y; }
__device__ __forceinline__ float rcp(float x) { float y; asm("rcp.approx.ftz.f32 %0,%1;" : "=f"(y) : "f"(x)); return y; }
__device__ __forceinline__ unsigned ld_acq(const unsigned* p) { unsigned v; asm volatile("ld.acquire.gpu.global.u32 %0,[%1];" : "=r"(v) : "l"(p) : "memory"); return v; }
__device__ __forceinline__ unsigned ld_rlx(const unsigned* p) { unsigned v; asm volatile("ld.relaxed.gpu.global.u32 %0,[%1];" : "=r"(v) : "l"(p) : "memory"); return v; }
__device__ __forceinline__ uint2 ld_rlx64(const void* p) { uint2 v; asm volatile("{.reg .b64 t; ld.relaxed.gpu.global.b64 t,[%2]; mov.b64 {%0,%1},t;}" : "=r"(v.x), "=r"(v.y) : "l"(p) : "memory"); return v; }
__device__ __forceinline__ uint4 ld_rlx128(const void* p) {
    uint4 v;
    asm volatile("{.reg .b64 t,u; ld.relaxed.gpu.global.v2.b64 {t,u},[%4]; mov.b64 {%0,%1},t; mov.b64 {%2,%3},u;}" : "=r"(v.x), "=r"(v.y), "=r"(v.z), "=r"(v.w) : "l"(p) : "memory");
    return v;
}
__device__ __forceinline__ void st_rlx64(void* p, uint32_t x, uint32_t y) { asm volatile("{.reg .b64 t; mov.b64 t,{%1,%2}; st.relaxed.gpu.global.b64 [%0],t;}" ::"l"(p), "r"(x), "r"(y) : "memory"); }
__device__ __forceinline__ void st_rlx128(void* p, uint4 v) {
    asm volatile("{.reg .b64 t,u; mov.b64 t,{%1,%2}; mov.b64 u,{%3,%4}; st.relaxed.gpu.global.v2.b64 [%0],{t,u};}" ::"l"(p), "r"(v.x), "r"(v.y), "r"(v.z), "r"(v.w) : "memory");
}
__device__ __forceinline__ uint32_t tagw(uint32_t w, uint32_t tag) { return (w & ~1u) | tag; }
__device__ __forceinline__ uint4 tag4(uint32_t x, uint32_t y, uint32_t z, uint32_t w, uint32_t tag) { return make_uint4(tagw(x, tag), y, tagw(z, tag), w); }
__device__ __forceinline__ uint32_t bad4(const uint4& v, uint32_t tag) { return (v.x ^ tag) | (v.z ^ tag); }
__device__ __forceinline__ void bar_named(int id, int n) { asm volatile("bar.sync %0,%1;" ::"r"(id), "r"(n) : "memory"); }

struct cf { float re, im; };
__device__ __forceinline__ cf cmul(cf a, cf b) { cf r; r.re = a.re * b.re - a.im * b.im; r.im = a.re * b.im + a.im * b.re; return r; }
__device__ __forceinline__ cf cexp_p(float arl, float ait, float p) {
    float mag = ex2(arl * p);
    float t = ait * p;
    t = (t - rintf(t)) * 6.283185307179586f;
    cf r; r.re = mag * __cosf(t); r.im = mag * __sinf(t);
    return r;
}

template <int NH>
__device__ __forceinline__ void hedgehog(const uint32_t* a, uint32_t wphi_addr, uint32_t (*out)[8]) {
    uint32_t R[NH][4], mx[NH], mn[NH];
#pragma unroll
    for (int h = 0; h < NH; h++) {
        uint32_t b[4];
        ldsm4t(b, wphi_addr + h * 512);
        float c0[4] = {0.f, 0.f, 0.f, 0.f}, c1[4] = {0.f, 0.f, 0.f, 0.f};
        mma16816(c0, a[4 * h], a[4 * h + 1], a[4 * h + 2], a[4 * h + 3], b[0], b[1]);
        mma16816(c1, a[4 * h], a[4 * h + 1], a[4 * h + 2], a[4 * h + 3], b[2], b[3]);
        R[h][0] = pack2(c0[0], c0[2]); R[h][1] = pack2(c0[1], c0[3]); R[h][2] = pack2(c1[0], c1[2]); R[h][3] = pack2(c1[1], c1[3]);
        mx[h] = hmax2(hmax2(R[h][0], R[h][1]), hmax2(R[h][2], R[h][3]));
        mn[h] = hmin2(hmin2(R[h][0], R[h][1]), hmin2(R[h][2], R[h][3]));
    }
#pragma unroll
    for (int o = 1; o <= 2; o <<= 1)
#pragma unroll
        for (int h = 0; h < NH; h++) { mx[h] = hmax2(mx[h], __shfl_xor_sync(~0u, mx[h], o)); mn[h] = hmin2(mn[h], __shfl_xor_sync(~0u, mn[h], o)); }
    const float L = 1.4426950408889634f;
    float e[NH][4][4], sm[NH][4];
#pragma unroll
    for (int h = 0; h < NH; h++) {
        const float mxl = -bf_lo(mx[h]) * L, mxh = -bf_hi(mx[h]) * L, mnl = bf_lo(mn[h]) * L, mnh = bf_hi(mn[h]) * L;
#pragma unroll
        for (int i = 0; i < 4; i++) {
            const float xl = bf_lo(R[h][i]), xh = bf_hi(R[h][i]);
            e[h][0][i] = ex2(fmaf(xl, L, mxl)); e[h][1][i] = ex2(fmaf(xh, L, mxh));
            e[h][2][i] = ex2(fmaf(xl, -L, mnl)); e[h][3][i] = ex2(fmaf(xh, -L, mnh));
        }
#pragma unroll
        for (int k = 0; k < 4; k++) sm[h][k] = (e[h][k][0] + e[h][k][1]) + (e[h][k][2] + e[h][k][3]);
    }
#pragma unroll
    for (int o = 1; o <= 2; o <<= 1)
#pragma unroll
        for (int h = 0; h < NH; h++)
#pragma unroll
            for (int k = 0; k < 4; k++) sm[h][k] += __shfl_xor_sync(~0u, sm[h][k], o);
#pragma unroll
    for (int h = 0; h < NH; h++)
#pragma unroll
        for (int k = 0; k < 4; k++) {
            const float r = rcp(sm[h][k]);
            out[h][(k >> 1) * 4 + (k & 1)] = pack2(e[h][k][0] * r, e[h][k][1] * r);
            out[h][(k >> 1) * 4 + (k & 1) + 2] = pack2(e[h][k][2] * r, e[h][k][3] * r);
        }
}

__global__ void __launch_bounds__(384, 1)
fused_kernel(const __grid_constant__ CUtensorMap mx, const __grid_constant__ CUtensorMap mw, const __grid_constant__ CUtensorMap mwo,
             const bf16* __restrict__ wphi, const bf16* __restrict__ logA, const bf16* __restrict__ Aim,
             const bf16* __restrict__ Cre, const bf16* __restrict__ Cim, const bf16* __restrict__ logdt, const bf16* __restrict__ Dskip,
             const bf16* __restrict__ gatew, bf16* __restrict__ out) {
    extern __shared__ __align__(1024) uint8_t smem[];
    const uint32_t sb = s2u(smem);
    const int tid = threadIdx.x, warp = __shfl_sync(~0u, tid >> 5, 0), lane = tid & 31;
    const int g = lane >> 2, q = lane & 3, w4 = warp & 3;
    const int bi = blockIdx.x, bi_i = bi & 15, bi_j = bi >> 4;
    const uint32_t bar = sb + OFF_BAR;
    const int rot = (bi_j & 1) * 4;
    auto load_stage = [&](int kb) {
        const uint32_t b = bar + 8 * (BAR_FULL + (kb & 3)), d = sb + (kb & 3) * SLOT;
        const int kc = ((kb + rot) & 7) * 64;
        mbar_expect(b, SLOT);
        tma2d(d, &mx, kc, bi_i * 128, b);
        tma3d(d + 16384, &mw, bi_j * 64, kc, 0, b);
    };

    if (tid == 0) {
        for (int s = 0; s < 4; s++) mbar_init(bar + 8 * (BAR_FULL + s), 1);
        asm volatile("fence.mbarrier_init.release.cluster;" ::: "memory");
#pragma unroll 1
        for (int s = 0; s < 3; s++) load_stage(s);
        STAMP(11);
    } else if (tid == 32) {
        if (sb & 1023) __trap();
        for (int s = 0; s < 5; s++) sts32(bar + OFF_CNT + 4 * s, 0);
        mbar_init(bar + 8 * BAR_WPHI, 1); mbar_init(bar + 8 * BAR_WO, 2); mbar_init(bar + 8 * BAR_XT, 8); mbar_init(bar + 8 * BAR_DONE, 8);
        mbar_init(bar + 8 * BAR_KG, 8); mbar_init(bar + 8 * BAR_WO2, 1);
        asm volatile("fence.mbarrier_init.release.cluster;" ::: "memory");
        mbar_expect(bar + 8 * BAR_WPHI, 3072);
        bulk_g2s(sb + OFF_GW, gatew, 1024, bar + 8 * BAR_WPHI);
        bulk_g2s(sb + OFF_WPHI, wphi + bi_j * 1024, 2048, bar + 8 * BAR_WPHI);
    } else if (tid == 64) {
        asm volatile("prefetch.tensormap [%0];" ::"l"(&mw) : "memory");
    }
    const int ch = bi * 4 + w4;
    const int pidx = ch * 64 + lane * 2 + (warp < 8);
    const uint32_t pla = __ldg((const uint32_t*)logA + pidx), pai = __ldg((const uint32_t*)Aim + pidx);
    const uint32_t pcr = __ldg((const uint32_t*)Cre + pidx), pci = __ldg((const uint32_t*)Cim + pidx);
    const float ldt = __bfloat162float(logdt[ch]);
    const unsigned epoch1 = (ld_rlx(g_done) >> 7) + 1u;
    const uint32_t tag = epoch1 & 1u;
    const uint32_t kb_ = sb + OFF_K + w4 * K_STRIDE, buf = sb + OFF_BUF + w4 * BUF_STRIDE;
    if (warp >= 8) {
#pragma unroll
        for (int v = 0; v < 7; v++) if (v * 32 + lane < K_STRIDE / 16) sts128(kb_ + (v * 32 + lane) * 16, 0, 0, 0, 0);
    }
    __syncthreads();

    float kc[6][4];
#pragma unroll
    for (int t = 0; t < 6; t++) { kc[t][0] = kc[t][1] = kc[t][2] = kc[t][3] = 0.f; }
    {
        const float dt = bf_round(expf(ldt));
#pragma unroll 1
        for (int it = 0; it < 4; it++) {
            uint32_t stg = (warp < 8) ? sb + 3 * SLOT + warp * 7296 : buf;
            if (it < 2) {
                const int sh = (warp < 8 ? (warp >> 2) : it) * 16;
                auto pick = [&](uint32_t v) { return __uint_as_float((v >> sh) << 16); };
                const float ea = bf_round(expf(pick(pla)));
                const float arl = (-ea * dt) * 1.4426950408889634f, ait = (pick(pai) * dt) * 0.15915494309189535f;
                cf C2; C2.re = 2.0f * (pick(pcr) * dt); C2.im = 2.0f * (pick(pci) * dt);
                const cf z1 = cexp_p(arl, ait, 1.0f), z128 = cexp_p(arl, ait, 128.0f);
                cf z8 = cexp_p(arl, ait, 8.0f); z8.im = -z8.im;
                const uint32_t lp = stg + lane * 4;
                auto put = [&](int row, const cf& v) { sts32((lp ^ ((row & 7) << 4)) + row * 128, pack2(v.re, v.im)); };
                {
                    const cf z16 = cmul(z8, z8);
                    cf e; e.re = 1.f; e.im = 0.f;
                    cf o = z8;
                    put(0, e); put(1, o);
                    e = z16; put(2, e);
#pragma unroll
                    for (int b = 3; b < 16; b += 2) {
                        o = cmul(o, z16); put(b, o);
                        if (b + 1 < 16) { e = cmul(e, z16); put(b + 1, e); }
                    }
                }
                cf h[8];
                h[0] = C2; put(16, h[0]);
                {
                    const cf z2 = cmul(z1, z1);
                    h[1] = cmul(h[0], z1);
#pragma unroll
                    for (int r = 2; r < 8; r++) h[r] = cmul(h[r - 2], z2);
#pragma unroll
                    for (int r = 1; r < 8; r++) put(16 + r, h[r]);
                }
#pragma unroll
                for (int r = 0; r < 8; r++) { h[r] = cmul(h[r], z128); put(24 + r, h[r]); }
#pragma unroll
                for (int al = 0; al < 2; al++)
#pragma unroll
                    for (int r = 0; r < 4; r++) { h[2 * r] = cmul(h[2 * r], z128); put(32 + al * 4 + r, h[2 * r]); }
#pragma unroll
                for (int al = 0; al < 4; al++)
#pragma unroll
                    for (int r = 0; r < 2; r++) { h[4 * r] = cmul(h[4 * r], z128); put(40 + al * 2 + r, h[4 * r]); }
#pragma unroll
                for (int al = 0; al < 9; al++) { h[0] = cmul(h[0], z128); put(48 + al, h[0]); }
                __syncwarp();
                if (warp < 8) {
                    if (lane == 0) mbar_arrive(bar + 8 * BAR_KG);
                    break;
                }
            } else {
                if (it == 2) mbar_wait(bar + 8 * BAR_KG, 0);
                stg = sb + 3 * SLOT + (w4 + (it - 2) * 4) * 7296;
            }
            const int lr = lane & 7, lm = lane >> 3;
#pragma unroll
            for (int kp = 0; kp < 2; kp++) {
                uint32_t a0[4], a1[4];
                ldsm4(a0, stg + ((lm & 1) * 8 + lr) * 128 + (((4 * kp + (lm >> 1)) ^ lr) << 4));
                ldsm4(a1, stg + ((lm & 1) * 8 + lr) * 128 + (((4 * kp + 2 + (lm >> 1)) ^ lr) << 4));
#pragma unroll
                for (int t = 0; t < 6; t++) {
                    uint32_t b[4];
                    ldsm4(b, stg + (16 + 8 * t + lr) * 128 + (((4 * kp + lm) ^ lr) << 4));
                    mma16816(kc[t], a0[0], a0[1], a0[2], a0[3], b[0], b[1]);
                    mma16816(kc[t], a1[0], a1[1], a1[2], a1[3], b[2], b[3]);
                }
            }
            __syncwarp();
        }
    }

    if (warp < 8) {
        const int wg = warp >> 2;
        if (warp == 0) STAMP(21);
        float acc[96];
        const int grow = bi_j * 16 + warp * 2 + (lane >> 4);
        const uint32_t gx_a = grow * 128 + ((((lane & 15) >> 1) ^ (grow & 7)) << 4) + (lane & 1) * 8;
        const int srow = warp * 16 + (lane & 15);
        const uint32_t srow_a = srow * 128;
        const int sx = srow & 7, shi = lane >> 4;
        auto last_of_8 = [&](int c) {
            unsigned old;
            asm volatile("atom.acq_rel.cta.shared.add.u32 %0,[%1],1;" : "=r"(old) : "r"(bar + OFF_CNT + 4 * c) : "memory");
            return (old & 7) == 7;
        };
        float gsum = 0.f;
#pragma unroll
        for (int r = 0; r < 96; r++) acc[r] = 0.f;
        fence_regs<96>(acc);
        const uint64_t da0 = mkdesc(sb + wg * 8192, 16, 1024), db0 = mkdesc(sb + 16384, 8192, 1024);
        mbar_wait(bar + 8 * BAR_WPHI, 0);
#pragma unroll 1
        for (int kb = 0; kb < 8; kb++) {
            const int s = kb & 3;
            const uint64_t da = da0 + s * (SLOT >> 4), db = db0 + s * (SLOT >> 4);
            mbar_wait(bar + 8 * (BAR_FULL + s), kb >> 2);
            if (kb == 0 && warp == 0) STAMP(0);
            wg_fence();
#pragma unroll
            for (int k = 0; k < 4; k++) wgmma192(acc, da + 2 * k, db + 128 * k);
            wg_commit();
            wg_wait<1>();
            __syncwarp();
            if (lane == 0 && kb > 0 && kb < 7) {
                const int ps = (kb - 1) & 3;
                if (last_of_8(ps)) {
                    if (kb < 5) load_stage(kb + 3);
                    else {
                        mbar_expect(bar + 8 * BAR_WO, 32768);
                        tma2d(sb + ps * SLOT, &mwo, (bi_j & 3) * 128 + ps * 64, 0, bar + 8 * BAR_WO);
                    }
                }
            }
            __syncwarp();
            const uint32_t st = sb + s * SLOT;
            if (kb == (bi_j >> 1)) {
                uint32_t* xt = (uint32_t*)g_xt + ((kb + rot) * 16 + (g >> 2)) * 4096 + (bi_i * 16 + warp * 2) * 16 + (g & 3) * 4 + q;
#pragma unroll
                for (int cb = 0; cb < 8; cb += 2) {
                    uint32_t r[4];
                    ldsm4t(r, st + srow_a + (((cb + shi) ^ sx) << 4));
                    xt[cb * 8192] = r[0]; xt[cb * 8192 + 16] = r[1]; xt[cb * 8192 + 8192] = r[2]; xt[cb * 8192 + 8192 + 16] = r[3];
                }
                __syncwarp();
                if (lane == 0) mbar_arrive(bar + 8 * BAR_XT);
            }
            {
                uint32_t x0, x1, w0, w1;
                asm volatile("ld.shared.v2.b32 {%0,%1},[%2];" : "=r"(x0), "=r"(x1) : "r"(st + gx_a) : "memory");
                asm volatile("ld.shared.v2.b32 {%0,%1},[%2];" : "=r"(w0), "=r"(w1) : "r"(sb + OFF_GW + ((kb + rot) & 7) * 128 + (lane & 15) * 8) : "memory");
                const uint32_t p0 = hmul2(x0, w0), p1 = hmul2(x1, w1);
                gsum += (bf_lo(p0) + bf_hi(p0)) + (bf_lo(p1) + bf_hi(p1));
            }
        }
        wg_wait<0>();
        fence_regs<96>(acc);
        __syncwarp();
        if (lane == 0) mbar_arrive(bar + 8 * BAR_DONE);
        if (warp == 0) STAMP(1);
        uint32_t in[32], va[16];
#pragma unroll
        for (int r = 0; r < 16; r++) {
            in[r] = pack2(acc[32 + 2 * r], acc[32 + 2 * r + 1]);
            in[16 + r] = pack2(acc[2 * r], acc[2 * r + 1]);
            va[r] = pack2(acc[64 + 2 * r], acc[64 + 2 * r + 1]);
        }
        const uint32_t wphi_a = sb + OFF_WPHI + (lane & 15) * 32 + (lane >> 4) * 16;
        uint32_t pq[4][8];
#pragma unroll 1
        for (int it = 0; it < 4; it++) {
            hedgehog<2>(in, wphi_a + (it & 1) * 1024, pq + 2);
#pragma unroll
            for (int r = 0; r < 24; r++) in[r] = in[r + 8];
            if (it < 2) {
                if (it == 0) mbar_wait(bar + 8 * BAR_DONE, 0);
                const uint32_t pt = sb + OFF_P + it * 16384 + srow_a, vt = sb + OFF_V + it * 16384 + srow_a;
#pragma unroll
                for (int hl = 0; hl < 2; hl++) {
                    stsm4(pt + (((4 * hl + shi) ^ sx) << 4), pq[2 + hl][0], pq[2 + hl][1], pq[2 + hl][2], pq[2 + hl][3]);
                    stsm4(pt + (((4 * hl + 2 + shi) ^ sx) << 4), pq[2 + hl][4], pq[2 + hl][5], pq[2 + hl][6], pq[2 + hl][7]);
                    stsm4(vt + (((2 * hl + shi) ^ sx) << 4), va[4 * hl], va[4 * hl + 1], va[4 * hl + 2], va[4 * hl + 3]);
                }
                if (lane < 16) sts128(vt + ((4 ^ sx) << 4), 0x3f803f80u, 0x3f803f80u, 0x3f803f80u, 0x3f803f80u);
#pragma unroll
                for (int r = 0; r < 8; r++) va[r] = va[r + 8];
            }
            if (it == 1) {
                asm volatile("fence.proxy.async.shared::cta;" ::: "memory");
                bar_named(1, 256);
                if (warp == 0) STAMP(2);
                float d[32];
                const uint64_t dv = mkdesc(sb + OFF_V + wg * 16384, 16, 1024), dp = mkdesc(sb + OFF_P + wg * 16384, 16, 1024);
                wg_fence();
#pragma unroll
                for (int k = 0; k < 8; k++) wgmma64_tt(d, dv + 128 * k, dp + 128 * k, k != 0);
                wg_commit();
                wg_wait<0>();
                fence_regs<32>(d);
                uint4* kvp = g_kvp + bi * 544 + wg * 272;
                if (w4 < 2) {
                    uint32_t e[16];
#pragma unroll
                    for (int r = 0; r < 16; r++) e[r] = __float_as_uint(w4 ? d[16 + r] : d[r]);
                    uint4* p = kvp + w4 * 136 + lane;
#pragma unroll
                    for (int ks = 0; ks < 2; ks++)
#pragma unroll
                        for (int nt = 0; nt < 2; nt++)
                            st_rlx128(p + (ks * 2 + nt) * 32, tag4(e[8 * ks + 2 * nt], e[8 * ks + 2 * nt + 1], e[8 * ks + 4 + 2 * nt], e[8 * ks + 4 + 2 * nt + 1], tag));
                } else if (w4 == 2 && lane < 4) {
#pragma unroll
                    for (int hl = 0; hl < 2; hl++)
#pragma unroll
                        for (int ks = 0; ks < 2; ks++)
                            st_rlx128(kvp + hl * 136 + 128 + ks * 4 + lane, tag4(__float_as_uint(d[16 * hl + 8 * ks]), __float_as_uint(d[16 * hl + 8 * ks + 1]),
                                                                                __float_as_uint(d[16 * hl + 8 * ks + 4]), __float_as_uint(d[16 * hl + 8 * ks + 5]), tag));
                }
                __syncwarp();
                if (lane == 0 && last_of_8(4)) {
                    mbar_expect(bar + 8 * BAR_WO2, 65536);
                    tma2d(sb + 2 * SLOT, &mwo, (bi_j & 3) * 128, 256, bar + 8 * BAR_WO2);
                    tma2d(sb + 3 * SLOT, &mwo, (bi_j & 3) * 128 + 64, 256, bar + 8 * BAR_WO2);
                }
                __syncwarp();
                if (warp == 0) STAMP(3);
            }
            if (it == 2) {
#pragma unroll
                for (int r = 0; r < 8; r++) { pq[0][r] = pq[2][r]; pq[1][r] = pq[3][r]; }
                if (warp == 0) STAMP(12);
                if (warp < 4 || (warp == 4 && (bi_i & 1) == 0)) {
                    const bool zw = warp == 4;
                    const int qq = (bi_i & 2) + ((lane >> 1) & 1);
                    const uint4* src = g_kvp + bi_j * (16 * 544) + (bi_i >> 2) * 136 +
                                       (zw ? (lane >> 2) * (2 * 544) + 128 + (lane & 1) * 4 + qq
                                           : (lane >> 3) * (4 * 544) + ((lane >> 1) & 3) * 32 + (bi_i & 3) * 8 + warp * 2 + (lane & 1));
                    const int s23 = zw ? 0 : 2 * 544;
                    uint4 v[4];
                    int n = 0;
                    while (true) {
                        v[0] = ld_rlx128(src); v[1] = ld_rlx128(src + 544); v[2] = ld_rlx128(src + s23); v[3] = ld_rlx128(src + s23 + 544);
                        if (!__any_sync(~0u, (bad4(v[0], tag) | bad4(v[1], tag) | bad4(v[2], tag) | bad4(v[3], tag)) & 1)) break;
                        if (++n > SPIN_LIMIT) break;
                    }
                    float f[4];
                    f[0] = __uint_as_float(v[2].x) + __uint_as_float(v[3].x); f[1] = __uint_as_float(v[2].y) + __uint_as_float(v[3].y);
                    f[2] = __uint_as_float(v[2].z) + __uint_as_float(v[3].z); f[3] = __uint_as_float(v[2].w) + __uint_as_float(v[3].w);
                    float e0 = __uint_as_float(v[0].x) + __uint_as_float(v[1].x), e1 = __uint_as_float(v[0].y) + __uint_as_float(v[1].y);
                    float e2 = __uint_as_float(v[0].z) + __uint_as_float(v[1].z), e3 = __uint_as_float(v[0].w) + __uint_as_float(v[1].w);
                    if (zw) {
                        e0 = __shfl_xor_sync(~0u, f[0], 4); e1 = __shfl_xor_sync(~0u, f[1], 4);
                        e2 = __shfl_xor_sync(~0u, f[2], 4); e3 = __shfl_xor_sync(~0u, f[3], 4);
                    }
                    f[0] += e0; f[1] += e1; f[2] += e2; f[3] += e3;
#pragma unroll
                    for (int o = 8; o <= 16; o <<= 1)
#pragma unroll
                        for (int r = 0; r < 4; r++) f[r] += __shfl_xor_sync(~0u, f[r], o);
                    uint2* dst = (uint2*)(g_kvf + (bi_j * 4 + (bi_i >> 2)) * 68) +
                                 (zw ? (64 + qq) * 2 + (lane & 1) : ((bi_i & 3) * 8 + warp * 2 + (lane & 1)) * 4 + (lane >> 1));
                    if (lane < (zw ? 4 : 8)) st_rlx64(dst, tagw(pack2(f[0], f[1]), tag), pack2(f[2], f[3]));
                }
                if (warp == 0) STAMP(13);
#pragma unroll
                for (int o = 1; o < 16; o <<= 1) gsum += __shfl_xor_sync(~0u, gsum, o);
                const float gate = bf_round(rcp(1.0f + ex2(-1.4426950408889634f * bf_round(gsum))));
                const uint32_t gv = __shfl_sync(~0u, __float_as_uint(gate) | tag, (lane & 4) * 4);
                if (lane < 8) asm volatile("st.relaxed.gpu.global.u32 [%0],%1;" ::"l"(g_g + (bi_i * 64 + bi_j * 8 + warp) * 8 + lane), "r"(gv) : "memory");
            }
        }
        if (warp == 0) STAMP(4);
        {
            uint4 kf[4][3];
            const uint4* kp = g_kvf + bi_j * 272;
            int n = 0;
            while (true) {
                uint32_t bad = 0;
#pragma unroll
                for (int hh = 0; hh < 4; hh++) {
                    kf[hh][0] = ld_rlx128(kp + hh * 68 + lane * 2); kf[hh][1] = ld_rlx128(kp + hh * 68 + lane * 2 + 1); kf[hh][2] = ld_rlx128(kp + hh * 68 + 64 + q);
                }
#pragma unroll
                for (int hh = 0; hh < 4; hh++) bad |= bad4(kf[hh][0], tag) | bad4(kf[hh][1], tag) | bad4(kf[hh][2], tag);
                if (!__any_sync(~0u, bad & 1)) break;
                if (++n > SPIN_LIMIT) break;
            }
            if (warp == 0) STAMP(5);
            uint4 own[4];
#pragma unroll
            for (int hh = 0; hh < 4; hh++) {
                float n0[4] = {0.f, 0.f, 0.f, 0.f}, n1[4] = {0.f, 0.f, 0.f, 0.f}, dn[4] = {0.f, 0.f, 0.f, 0.f};
                const uint32_t* a = pq[hh];
                mma16816(dn, a[0], a[1], a[2], a[3], kf[hh][2].x, kf[hh][2].y);
                mma16816(n0, a[0], a[1], a[2], a[3], kf[hh][0].x, kf[hh][0].y);
                mma16816(n1, a[0], a[1], a[2], a[3], kf[hh][0].z, kf[hh][0].w);
                mma16816(dn, a[4], a[5], a[6], a[7], kf[hh][2].z, kf[hh][2].w);
                mma16816(n0, a[4], a[5], a[6], a[7], kf[hh][1].x, kf[hh][1].y);
                mma16816(n1, a[4], a[5], a[6], a[7], kf[hh][1].z, kf[hh][1].w);
                const float r0 = rcp(dn[0] + 1e-6f), r1 = rcp(dn[2] + 1e-6f);
                own[hh] = tag4(pack2(n0[0] * r0, n0[1] * r0), pack2(n0[2] * r1, n0[3] * r1), pack2(n1[0] * r0, n1[1] * r0), pack2(n1[2] * r1, n1[3] * r1), tag);
            }
            uint4* og = g_o + ((bi_i * 8 + warp) * 32 + bi_j * 4) * 32 + lane;
#pragma unroll
            for (int hh = 0; hh < 4; hh++) st_rlx128(og + hh * 32, own[hh]);
        }
        if (warp == 0) STAMP(6);
        float oc[64];
        const int slab = bi_i * 8 + (bi_j >> 2) * 4 + w4;
        const uint8_t* yb = (const uint8_t*)g_y + (size_t)((bi_j & 3) * 32 + wg * 16 + (q >> 1)) * 16384 + slab * 128 + g * 16 + (q & 1) * 8;
        const unsigned* gp = g_g + (slab * 8 + (g >> 1)) * 8 + (g & 1) * 4;
        uint2 yv[8]; unsigned g0, g1;
        {
            const uint4* osrc = g_o + (slab * 32 + wg * 16) * 32 + lane;
            uint4 fr[16];
            {
                const unsigned* probe = (const unsigned*)(osrc - lane + ((lane & 3) * 4 + 3) * 32 + 31) + 2;
                int n = 0;
                while (__any_sync(~0u, (ld_rlx(probe) ^ tag) & 1)) { if (++n > SPIN_LIMIT) break; }
            }
            if (warp == 0) STAMP(14);
#pragma unroll
            for (int k = 0; k < 16; k++) fr[k] = ld_rlx128(osrc + k * 32);
            mbar_wait(bar + 8 * (wg ? BAR_WO2 : BAR_WO), 0);
            const uint64_t dw = mkdesc(sb + wg * 2 * SLOT, SLOT, 1024);
#pragma unroll
            for (int s = 0; s < 4; s++) {
                int n = 0;
                while (__any_sync(~0u, (bad4(fr[4 * s], tag) | bad4(fr[4 * s + 1], tag) | bad4(fr[4 * s + 2], tag) | bad4(fr[4 * s + 3], tag)) & 1)) {
#pragma unroll
                    for (int hh = 0; hh < 4; hh++) fr[4 * s + hh] = ld_rlx128(osrc + (4 * s + hh) * 32);
                    if (++n > SPIN_LIMIT) break;
                }
                wg_fence();
#pragma unroll
                for (int hh = 0; hh < 4; hh++) wgmma128_rs(oc, fr[4 * s + hh], dw + 128 * (4 * s + hh), (s | hh) != 0);
                wg_commit();
            }
#pragma unroll
            for (int nt = 0; nt < 8; nt++) yv[nt] = ld_rlx64(yb + nt * 32768);
            g0 = ld_rlx(gp); g1 = ld_rlx(gp + 32);
            if (warp == 0) STAMP(7);
            wg_wait<0>();
            fence_regs<64>(oc);
        }
        {
            bar_named(3 + wg, 128);
            const uint32_t xw = sb + wg * 2 * SLOT + (tid & 127) * 16, xr = sb + (wg ^ 1) * 2 * SLOT + (tid & 127) * 16;
#pragma unroll
            for (int r = 0; r < 8; r++) {
                const float* o = oc + 4 * r;
                sts128(xw + r * 2048, __float_as_uint(wg ? o[0] : o[32]), __float_as_uint(wg ? o[1] : o[33]), __float_as_uint(wg ? o[2] : o[34]), __float_as_uint(wg ? o[3] : o[35]));
            }
#pragma unroll
            for (int r = 0; r < 32; r++) oc[r] = wg ? oc[32 + r] : oc[r];
            bar_named(1, 256);
            if (warp == 0) STAMP(8);
            int n = 0;
            while (true) {
                uint32_t bad = (g0 ^ tag) | (g1 ^ tag);
#pragma unroll
                for (int nt = 0; nt < 8; nt++) bad |= yv[nt].x ^ tag;
                if (!__any_sync(~0u, bad & 1)) break;
#pragma unroll
                for (int nt = 0; nt < 8; nt++) yv[nt] = ld_rlx64(yb + nt * 32768);
                g0 = ld_rlx(gp); g1 = ld_rlx(gp + 32);
                if (++n > SPIN_LIMIT) break;
            }
            if (warp == 0) STAMP(9);
            const float ga = bf_hi(g0), gb = bf_hi(g1);
            const float ha = bf_round(1.0f - ga), hb = bf_round(1.0f - gb);
            uint32_t w[8][2];
#pragma unroll
            for (int nt = 0; nt < 8; nt++) {
                const uint4 p = lds128(xr + nt * 2048);
                w[nt][0] = pack2(fmaf(ga, oc[4 * nt] + __uint_as_float(p.x), ha * bf_lo(yv[nt].x)), fmaf(ga, oc[4 * nt + 1] + __uint_as_float(p.y), ha * bf_hi(yv[nt].x)));
                w[nt][1] = pack2(fmaf(gb, oc[4 * nt + 2] + __uint_as_float(p.z), hb * bf_lo(yv[nt].y)), fmaf(gb, oc[4 * nt + 3] + __uint_as_float(p.w), hb * bf_hi(yv[nt].y)));
            }
            const uint32_t ob = sb + (2 + wg) * SLOT + 32768 + w4 * 2048;
#pragma unroll
            for (int nt = 0; nt < 8; nt += 2)
                stsm4(ob + (lane & 15) * 128 + (((nt + shi) ^ (lane & 7)) << 4), w[nt][0], w[nt][1], w[nt + 1][0], w[nt + 1][1]);
            __syncwarp();
            bf16* op = out + (size_t)(slab * 16) * 512 + (bi_j & 3) * 128 + wg * 64 + (lane & 7) * 8;
#pragma unroll
            for (int it = 0; it < 4; it++) {
                const int r = it * 4 + (lane >> 3);
                uint4 v = lds128(ob + r * 128 + (((lane & 7) ^ (r & 7)) << 4));
                *(uint4*)(op + r * 512) = v;
            }
        }
        if (warp == 0) STAMP(10);
    } else {
        const int st = tid - 256;
        const uint32_t ub = sb + OFF_U + w4 * U_STRIDE + 256;
        const uint32_t spare = sb + (w4 < 2 ? OFF_SP0 : OFF_SP1) + (w4 & 1) * 4096;
        asm volatile("fence.proxy.async.shared::cta;" ::: "memory");
        bar_named(2, 128);
        if (st == 0) load_stage(3);
        if (warp == 8) STAMP(16);
        if (lane == 0) kc[0][0] += __bfloat162float(Dskip[ch]);
        const uint32_t k1024 = __shfl_sync(~0u, pack2(kc[4][0], 0.f), 0);
#pragma unroll
        for (int i = 0; i < 2; i++) {
            const int be = g + 8 * i;
#pragma unroll
            for (int t = 0; t < 2; t++) {
                const uint32_t a = kb_ + (KW_D + 128 * t + 8 * be + 2 * q) * 4;
                const uint32_t w = pack2(kc[t][2 * i + 1], kc[t][2 * i]);
                sts32(a + 4, w); sts16(a, w >> 16); sts16(a + 10, w);
            }
            {
                const int p = 256 + 128 * (q >> 1) + 8 * be + 4 * (q & 1);
                const uint32_t a = kb_ + (KW_D + p) * 4;
                const uint32_t w = pack2(kc[2][2 * i + 1], kc[2][2 * i]);
                const uint32_t aa = (w >> 16) | (w & 0xffff0000u);
                if (p != 256) { sts16(a - 4, aa); sts32(a, aa); } else sts16(a, aa);
                sts32(a + 4, aa); sts32(a + 8, w); sts16(a + 14, w);
            }
            {
                const int k = 64 + 16 * q + be;
                const uint32_t w = pack2(kc[3][2 * i], kc[3][2 * i + 1]);
                if (k != 64) sts16(kb_ + (KW_2 + ((k - 1) >> 1) - 24) * 4 + (k & 1) * 2, w);
                else {
                    const uint32_t a = kb_ + (KW_D + 511) * 4, aa = (w << 16) | (w & 0xffffu);
                    sts16(a, w); sts32(a + 4, aa); sts32(a + 8, aa); sts32(a + 12, aa); sts16(a + 18, w);
                }
                sts16(kb_ + (KW_2 + 48 + (k >> 1) - 24) * 4 + ((k & 1) ^ 1) * 2, w >> 16);
            }
#pragma unroll
            for (int b = 0; b < 2; b++) {
                const int k = 64 + 8 * (2 * q + b) + (be >> 1);
                const uint32_t w = pack2(kc[4][2 * i + b], 0.f);
                if (!(be & 1) && k == 64) sts16(kb_ + (KW_2 + 63 - 24) * 4, w);
                else {
                    const uint32_t a = kb_ + (KW_3 + ((be & 1) ? 80 + k : k - 1) - 48) * 4;
                    sts16(a, w);
                    if (!((be & 1) && k == 127)) sts16(a + 6, w);
                }
            }
        }
        if (lane == 0) sts16(kb_ + (KW_3 + 127 - 48) * 4, pack2(kc[5][0], 0.f));
        if (lane < 2) sts128(buf + lane * W3_OFF, 0, 0, 0, 0);
        if (lane < 16) sts128(ub - 256 + lane * 16, 0, 0, 0, 0);
        if (warp == 8) {
            mbar_wait(bar + 8 * BAR_XT, 0);
            if (lane == 0) asm volatile("red.release.gpu.global.add.u32 [%0],8;" ::"l"(g_xcnt + ((bi_j >> 1) + rot) * 32) : "memory");
        }
        if (lane == 0) {
            int n = 0;
            while ((int)(ld_acq(g_xcnt + bi_j * 32) - (epoch1 << 7)) < 0) { __nanosleep(200); if (++n > SPIN_LIMIT) break; }
        }
        __syncwarp();
        if (warp == 8) STAMP(15);
        {
            uint4 ur[8];
#pragma unroll
            for (int v = 0; v < 8; v++) ur[v] = __ldcg(g_xt + bi * 1024 + st + 128 * v);
#pragma unroll
            for (int v = 0; v < 8; v++) {
                const int ci = (st >> 2) + 32 * v;
                sts128(sb + OFF_U + (st & 3) * U_STRIDE + 256 + ((ci ^ ((ci >> 3) & 1)) << 4), ur[v].x, ur[v].y, ur[v].z, ur[v].w);
            }
        }
        mbar_wait(bar + 8 * BAR_WO, 0);
        bar_named(2, 128);
        if (warp == 8) STAMP(17);
        float y[16][4];
#pragma unroll
        for (int nt = 0; nt < 16; nt++) { y[nt][0] = y[nt][1] = y[nt][2] = y[nt][3] = 0.f; }
        {
            uint32_t Bp[32];
            auto uaddr = [&](int rho) { const int R0 = (lane >> 4) * 8 + (lane & 7) - rho; return ub + (((2 * R0 + ((lane >> 3) & 1)) ^ ((R0 >> 2) & 1)) << 4); };
            const uint32_t kd = kb_ + (KW_D + g - 2 * q) * 4;
            {
                const uint32_t a = uaddr(0);
#pragma unroll
                for (int p = 0; p < 8; p++) ldsm4(Bp + 4 * p, a + p * 512);
            }
#pragma unroll 1
            for (int rho = 0; rho < 8; rho++) {
                uint32_t A[5][4];
#pragma unroll
                for (int ga = 0; ga < 5; ga++) {
                    const uint32_t a = kd + (ga < 4 ? rho : (rho & 1)) * 64 + ga * 512;
                    A[ga][0] = lds32(a); A[ga][1] = lds32(a + 32); A[ga][2] = lds32(a - 32); A[ga][3] = A[ga][0];
                }
                const int ci = lane + 32 * rho;
                uint4 e4[4];
#pragma unroll
                for (int v = 0; v < 4; v++) { const int cc = ci - 3 + v; e4[v] = lds128(ub + ((cc ^ ((cc >> 3) & 1)) << 4)); }
                float S[29];
                const uint32_t* ew = (const uint32_t*)e4;
                S[3] = 0.f;
#pragma unroll
                for (int k = 4; k <= 28; k++) S[k] = S[k - 1] + ((k & 1) ? bf_hi(ew[k >> 1]) : bf_lo(ew[k >> 1]));
                auto win = [&](int lo, int hi, uint32_t a, bool on) {
                    const uint32_t w0 = pack2(S[hi] - S[lo - 1], S[hi + 1] - S[lo]), w1 = pack2(S[hi + 2] - S[lo + 1], S[hi + 3] - S[lo + 2]);
                    const uint32_t w2 = pack2(S[hi + 4] - S[lo + 3], S[hi + 5] - S[lo + 4]), w3 = pack2(S[hi + 6] - S[lo + 5], S[hi + 7] - S[lo + 6]);
                    asm volatile("{.reg .pred p; setp.ne.b32 p,%5,0; @p st.shared.v4.b32 [%0],{%1,%2,%3,%4};}" ::"r"(a), "r"(w0), "r"(w1), "r"(w2), "r"(w3), "r"((int)on) : "memory");
                };
                const uint32_t sw = (ci ^ ((ci >> 3) & 1)) << 4;
#pragma unroll
                for (int nt = 0; nt < 16; nt++) mma16816v(y[nt], A[0][0], A[0][1], A[0][2], A[0][3], Bp[2 * nt], Bp[2 * nt + 1]);
                win(4, 12, buf + W9_OFF + sw, rho < 4);
#pragma unroll
                for (int nt = 1; nt < 16; nt++) mma16816v(y[nt], A[1][0], A[1][1], A[1][2], A[1][3], Bp[2 * (nt - 1)], Bp[2 * (nt - 1) + 1]);
                win(14, 18, buf + W5_OFF + 16 + ci * 16, rho < 6); win(13, 19, spare + sw, rho < 4);
                const uint32_t an = uaddr(rho + 1);
                ldsm4(Bp + 28, an + 7 * 512);
#pragma unroll
                for (int nt = 2; nt < 16; nt++) mma16816v(y[nt], A[2][0], A[2][1], A[2][2], A[2][3], Bp[2 * (nt - 2)], Bp[2 * (nt - 2) + 1]);
                win(19, 21, buf + W3_OFF + 16 + ci * 16, rho < 6); win(20, 21, spare + 2048 + sw, rho < 4);
                if (rho < 2) {
#pragma unroll
                    for (int nt = 4; nt < 16; nt++) mma16816v(y[nt], A[4][0], A[4][1], A[4][2], A[4][3], Bp[2 * (nt - 4)], Bp[2 * (nt - 4) + 1]);
                }
#pragma unroll
                for (int nt = 3; nt < 16; nt++) {
                    mma16816v(y[nt], A[3][0], A[3][1], A[3][2], A[3][3], Bp[2 * (nt - 3)], Bp[2 * (nt - 3) + 1]);
                    if ((nt & 1) == 0) ldsm4(Bp + 2 * (nt - 4), an + ((nt - 4) >> 1) * 512);
                    if (nt == 15) ldsm4(Bp + 24, an + 6 * 512);
                }
            }
        }
        __syncwarp();
        if (warp == 8) STAMP(18);
#pragma unroll 1
        for (int ph = 0; ph < 2; ph++) {
            uint32_t B[5][2];
            const uint32_t ka = kb_ + (KW_2 + ph * 48 + 8 + g - q) * 4;
#pragma unroll
            for (int dd = 0; dd < 5; dd++) { B[dd][0] = lds32(ka + dd * 32); B[dd][1] = lds32(ka + dd * 32 - 16); }
            const uint32_t wa = buf + ph * W3_OFF + ((lane & 7) + ((lane >> 3) & 1) + (lane >> 4) * 8) * 16;
#pragma unroll
            for (int s = 0; s < 12; s++) {
                uint32_t A[4];
                ldsm4t(A, wa + s * 256);
#pragma unroll
                for (int dd = 0; dd < 5; dd++)
                    if (s + 4 + dd < 16) mma16816(y[s + 4 + dd], A[0], A[1], A[2], A[3], B[dd][0], B[dd][1]);
            }
        }
        {
            const int ap = (lane & 7) + (lane >> 4) * 8;
            const uint32_t loff = ((2 * ap + ((lane >> 3) & 1)) ^ ((ap >> 2) & 1)) << 4;
#pragma unroll 1
            for (int ph = 0; ph < 2; ph++) {
                uint32_t B[8][2];
                const uint32_t wb = (ph ? spare : buf + W9_OFF) + loff;
                const uint32_t ka = kb_ + (KW_3 + ph * 80 + 16 + g - 2 * q) * 4;
#pragma unroll
                for (int dd = 0; dd < 8; dd++) { B[dd][0] = lds32(ka + dd * 32); B[dd][1] = lds32(ka + dd * 32 - 32); }
#pragma unroll
                for (int s = 0; s < 4; s++) {
                    uint32_t A[4];
                    ldsm4t(A, wb + s * 512);
#pragma unroll
                    for (int dd = 0; dd < 8; dd++)
                        if (8 + 2 * s + dd < 16) mma16816(y[8 + 2 * s + dd], A[0], A[1], A[2], A[3], B[dd][0], B[dd][1]);
                }
            }
            const uint32_t idw = (g == 2 * q) ? k1024 : ((g == 2 * q + 1) ? (k1024 << 16) : 0u);
#pragma unroll
            for (int s = 0; s < 4; s++) {
                uint32_t A[4];
                ldsm4t(A, spare + 2048 + loff + s * 512);
                mma16816(y[8 + 2 * s], A[0], A[1], A[2], A[3], idw, 0u);
                mma16816(y[9 + 2 * s], A[0], A[1], A[2], A[3], 0u, idw);
            }
        }
        __syncwarp();
        if (warp == 8) STAMP(19);
#pragma unroll
        for (int nt = 0; nt < 16; nt++)
#pragma unroll
            for (int b = 0; b < 2; b++) sts32(buf + ((8 * nt + 2 * q + b) * 8 + g) * 4, pack2(y[nt][b], y[nt][2 + b]));
        bar_named(2, 128);
        uint4* yp = g_y + bi * 1024 + st;
#pragma unroll
        for (int v = 0; v < 8; v++) {
            const uint32_t a = sb + OFF_BUF + (st + 128 * v) * 4;
            const uint32_t w0 = lds32(a), w1 = lds32(a + BUF_STRIDE), w2 = lds32(a + 2 * BUF_STRIDE), w3 = lds32(a + 3 * BUF_STRIDE);
            st_rlx128(yp + v * 128, tag4(__byte_perm(w0, w1, 0x5410), __byte_perm(w0, w1, 0x7632), __byte_perm(w2, w3, 0x5410), __byte_perm(w2, w3, 0x7632), tag));
        }
        if (warp == 8) STAMP(20);
    }
    __syncthreads();
    if (tid == 0) atomicAdd(g_done, 1u);
}

typedef CUresult (*EncFn)(CUtensorMap*, CUtensorMapDataType, cuuint32_t, void*, const cuuint64_t*, const cuuint64_t*, const cuuint32_t*,
                          const cuuint32_t*, CUtensorMapInterleave, CUtensorMapSwizzle, CUtensorMapL2promotion, CUtensorMapFloatOOBfill);

extern "C" void kernel_launch(void* const* d_in, const int* in_sizes, int n_in, void* d_out, int out_size) {
    static EncFn enc = nullptr;
    if (!enc) {
        cudaDriverEntryPointQueryResult qr;
        cudaGetDriverEntryPoint("cuTensorMapEncodeTiled", (void**)&enc, cudaEnableDefault, &qr);
        cudaFuncSetAttribute(fused_kernel, cudaFuncAttributeMaxDynamicSharedMemorySize, SMEM_BYTES);
    }
    CUtensorMap mx, mw, mwo;
    const cuuint32_t es[3] = {1, 1, 1};
    {
        cuuint64_t d[2] = {512, 2048}, s[1] = {1024}; cuuint32_t b[2] = {64, 128};
        enc(&mx, CU_TENSOR_MAP_DATA_TYPE_BFLOAT16, 2, d_in[0], d, s, b, es, CU_TENSOR_MAP_INTERLEAVE_NONE, CU_TENSOR_MAP_SWIZZLE_128B,
            CU_TENSOR_MAP_L2_PROMOTION_L2_128B, CU_TENSOR_MAP_FLOAT_OOB_FILL_NONE);
    }
    {
        cuuint64_t d[3] = {512, 512, 3}, s[2] = {3072, 1024}; cuuint32_t b[3] = {64, 64, 3};
        enc(&mw, CU_TENSOR_MAP_DATA_TYPE_BFLOAT16, 3, d_in[1], d, s, b, es, CU_TENSOR_MAP_INTERLEAVE_NONE, CU_TENSOR_MAP_SWIZZLE_128B,
            CU_TENSOR_MAP_L2_PROMOTION_L2_128B, CU_TENSOR_MAP_FLOAT_OOB_FILL_NONE);
    }
    {
        cuuint64_t d[2] = {512, 512}, s[1] = {1024}; cuuint32_t b[2] = {64, 256};
        enc(&mwo, CU_TENSOR_MAP_DATA_TYPE_BFLOAT16, 2, d_in[3], d, s, b, es, CU_TENSOR_MAP_INTERLEAVE_NONE, CU_TENSOR_MAP_SWIZZLE_128B,
            CU_TENSOR_MAP_L2_PROMOTION_L2_128B, CU_TENSOR_MAP_FLOAT_OOB_FILL_NONE);
    }
    fused_kernel<<<128, 384, SMEM_BYTES, cudaStreamPerThread>>>(
        mx, mw, mwo, (const bf16*)d_in[2], (const bf16*)d_in[5], (const bf16*)d_in[6], (const bf16*)d_in[7],
        (const bf16*)d_in[8], (const bf16*)d_in[9], (const bf16*)d_in[10], (const bf16*)d_in[11], (bf16*)d_out);
}
```

```cpp
#include <cuda_runtime.h>
#include <cuda.h>
#include <cuda_bf16.h>
#include <stdint.h>

typedef __nv_bfloat16 bf16;

__device__ unsigned g_done[32];
__device__ unsigned g_xcnt[8 * 32];
__device__ uint4 g_xt[128 * 1024];
__device__ uint4 g_kvp[8 * 16 * 544];
__device__ uint4 g_kvf[8 * 4 * 68];
__device__ uint4 g_o[16 * 8 * 32 * 32];
__device__ uint4 g_y[128 * 1024];
__device__ unsigned g_g[1024 * 8];
#define STAMP(n)

constexpr int SLOT = 40960;
constexpr int OFF_SP0 = 32768, OFF_SP1 = SLOT + 32768;
constexpr int OFF_P = 2 * SLOT, OFF_V = OFF_P + 32768;
constexpr int OFF_U = 4 * SLOT, U_STRIDE = 4096 + 256;
constexpr int OFF_K = OFF_U + 4 * U_STRIDE, K_STRIDE = 3264;
constexpr int OFF_BUF = OFF_K + 4 * K_STRIDE, BUF_STRIDE = 8320;
constexpr int OFF_WPHI = OFF_BUF + 4 * BUF_STRIDE;
constexpr int OFF_GW = OFF_WPHI + 2048;
constexpr int OFF_BAR = OFF_GW + 1024;
constexpr int SMEM_BYTES = OFF_BAR + 128 + 128;
static_assert(SMEM_BYTES <= 232448 && OFF_BUF % 128 == 0, "smem");
constexpr int KW_D = 16, KW_2 = 560, KW_3 = 656;
constexpr int W5_OFF = 0, W3_OFF = 3088, W9_OFF = 6176;
constexpr int BAR_FULL = 0, BAR_WPHI = 4, BAR_WO = 5, BAR_XT = 6, BAR_DONE = 7, BAR_KG = 8, BAR_WO2 = 9, BAR_KG2 = 10, OFF_CNT = 96;
constexpr int SPIN_LIMIT = 1 << 17;

__device__ __forceinline__ uint32_t s2u(const void* p) { return (uint32_t)__cvta_generic_to_shared(p); }
__device__ __forceinline__ void mbar_init(uint32_t b, int c) { asm volatile("mbarrier.init.shared::cta.b64 [%0],%1;" ::"r"(b), "r"(c) : "memory"); }
__device__ __forceinline__ void mbar_expect(uint32_t b, int bytes) { asm volatile("mbarrier.arrive.expect_tx.shared::cta.b64 _,[%0],%1;" ::"r"(b), "r"(bytes) : "memory"); }
__device__ __forceinline__ void mbar_arrive(uint32_t b) { asm volatile("mbarrier.arrive.shared::cta.b64 _,[%0];" ::"r"(b) : "memory"); }
__device__ __forceinline__ bool mbar_try(uint32_t b, int ph) {
    uint32_t ok;
    asm volatile("{.reg .pred p; mbarrier.try_wait.parity.shared::cta.b64 p,[%1],%2; selp.u32 %0,1,0,p;}" : "=r"(ok) : "r"(b), "r"(ph) : "memory");
    return ok;
}
__device__ __forceinline__ void mbar_wait(uint32_t b, int ph) {
    if ((threadIdx.x & 31) == 0) { int n = 0; while (!mbar_try(b, ph)) { if (++n > SPIN_LIMIT) break; } }
    __syncwarp();
}
__device__ __forceinline__ void tma2d(uint32_t dst, const CUtensorMap* m, int c0, int c1, uint32_t bar) {
    asm volatile("cp.async.bulk.tensor.2d.shared::cluster.global.mbarrier::complete_tx::bytes [%0],[%1,{%3,%4}],[%2];" ::"r"(dst), "l"(m), "r"(bar), "r"(c0), "r"(c1) : "memory");
}
__device__ __forceinline__ void tma3d(uint32_t dst, const CUtensorMap* m, int c0, int c1, int c2, uint32_t bar) {
    asm volatile("cp.async.bulk.tensor.3d.shared::cluster.global.mbarrier::complete_tx::bytes [%0],[%1,{%3,%4,%5}],[%2];" ::"r"(dst), "l"(m), "r"(bar), "r"(c0), "r"(c1), "r"(c2) : "memory");
}
__device__ __forceinline__ void bulk_g2s(uint32_t dst, const void* src, int bytes, uint32_t bar) {
    asm volatile("cp.async.bulk.shared::cluster.global.mbarrier::complete_tx::bytes [%0],[%1],%2,[%3];" ::"r"(dst), "l"(src), "r"(bytes), "r"(bar) : "memory");
}
__device__ __forceinline__ uint64_t mkdesc(uint32_t addr, uint32_t lbo, uint32_t sbo) {
    return (uint64_t)((addr & 0x3FFFF) >> 4) | ((uint64_t)(lbo >> 4) << 16) | ((uint64_t)(sbo >> 4) << 32) | ((uint64_t)1 << 62);
}
__device__ __forceinline__ void wg_fence() { asm volatile("wgmma.fence.sync.aligned;" ::: "memory"); }
__device__ __forceinline__ void wg_commit() { asm volatile("wgmma.commit_group.sync.aligned;" ::: "memory"); }
template <int N> __device__ __forceinline__ void wg_wait() { asm volatile("wgmma.wait_group.sync.aligned %0;" ::"n"(N) : "memory"); }
template <int N> __device__ __forceinline__ void fence_regs(float* d) {
#pragma unroll
    for (int i = 0; i < N; i++) asm volatile("" : "+f"(d[i])::"memory");
}
#define R8(d, o) "+f"(d[o]), "+f"(d[o + 1]), "+f"(d[o + 2]), "+f"(d[o + 3]), "+f"(d[o + 4]), "+f"(d[o + 5]), "+f"(d[o + 6]), "+f"(d[o + 7])
__device__ __forceinline__ void wgmma192(float* d, uint64_t da, uint64_t db) {
    asm volatile("wgmma.mma_async.sync.aligned.m64n192k16.f32.bf16.bf16 {"
                 "%0,%1,%2,%3,%4,%5,%6,%7,%8,%9,%10,%11,%12,%13,%14,%15,%16,%17,%18,%19,%20,%21,%22,%23,%24,%25,%26,%27,%28,%29,%30,%31,"
                 "%32,%33,%34,%35,%36,%37,%38,%39,%40,%41,%42,%43,%44,%45,%46,%47,%48,%49,%50,%51,%52,%53,%54,%55,%56,%57,%58,%59,%60,%61,%62,%63,"
                 "%64,%65,%66,%67,%68,%69,%70,%71,%72,%73,%74,%75,%76,%77,%78,%79,%80,%81,%82,%83,%84,%85,%86,%87,%88,%89,%90,%91,%92,%93,%94,%95},"
                 "%96,%97,1,1,1,0,1;"
                 : R8(d, 0), R8(d, 8), R8(d, 16), R8(d, 24), R8(d, 32), R8(d, 40), R8(d, 48), R8(d, 56), R8(d, 64), R8(d, 72), R8(d, 80), R8(d, 88)
                 : "l"(da), "l"(db));
}
__device__ __forceinline__ void wgmma64_tt(float* d, uint64_t da, uint64_t db, int sc) {
    asm volatile("{.reg .pred p; setp.ne.b32 p,%34,0; wgmma.mma_async.sync.aligned.m64n64k16.f32.bf16.bf16 {"
                 "%0,%1,%2,%3,%4,%5,%6,%7,%8,%9,%10,%11,%12,%13,%14,%15,%16,%17,%18,%19,%20,%21,%22,%23,%24,%25,%26,%27,%28,%29,%30,%31},"
                 "%32,%33,p,1,1,1,1;}"
                 : R8(d, 0), R8(d, 8), R8(d, 16), R8(d, 24)
                 : "l"(da), "l"(db), "r"(sc));
}
__device__ __forceinline__ void wgmma128_rs(float* d, const uint4& a, uint64_t db, int sc) {
    asm volatile("{.reg .pred p; setp.ne.b32 p,%69,0; wgmma.mma_async.sync.aligned.m64n128k16.f32.bf16.bf16 {"
                 "%0,%1,%2,%3,%4,%5,%6,%7,%8,%9,%10,%11,%12,%13,%14,%15,%16,%17,%18,%19,%20,%21,%22,%23,%24,%25,%26,%27,%28,%29,%30,%31,"
                 "%32,%33,%34,%35,%36,%37,%38,%39,%40,%41,%42,%43,%44,%45,%46,%47,%48,%49,%50,%51,%52,%53,%54,%55,%56,%57,%58,%59,%60,%61,%62,%63},"
                 "{%64,%65,%66,%67},%68,p,1,1,1;}"
                 : R8(d, 0), R8(d, 8), R8(d, 16), R8(d, 24), R8(d, 32), R8(d, 40), R8(d, 48), R8(d, 56)
                 : "r"(a.x), "r"(a.y), "r"(a.z), "r"(a.w), "l"(db), "r"(sc));
}
__device__ __forceinline__ void mma16816v(float* c, uint32_t a0, uint32_t a1, uint32_t a2, uint32_t a3, uint32_t b0, uint32_t b1) {
    asm volatile("mma.sync.aligned.m16n8k16.row.col.f32.bf16.bf16.f32 {%0,%1,%2,%3},{%4,%5,%6,%7},{%8,%9},{%0,%1,%2,%3};"
        : "+f"(c[0]), "+f"(c[1]), "+f"(c[2]), "+f"(c[3]) : "r"(a0), "r"(a1), "r"(a2), "r"(a3), "r"(b0), "r"(b1));
}
__device__ __forceinline__ void mma16816(float* c, uint32_t a0, uint32_t a1, uint32_t a2, uint32_t a3, uint32_t b0, uint32_t b1) {
    asm("mma.sync.aligned.m16n8k16.row.col.f32.bf16.bf16.f32 {%0,%1,%2,%3},{%4,%5,%6,%7},{%8,%9},{%0,%1,%2,%3};"
        : "+f"(c[0]), "+f"(c[1]), "+f"(c[2]), "+f"(c[3]) : "r"(a0), "r"(a1), "r"(a2), "r"(a3), "r"(b0), "r"(b1));
}
__device__ __forceinline__ void ldsm4(uint32_t* r, uint32_t a) {
    asm volatile("ldmatrix.sync.aligned.m8n8.x4.shared.b16 {%0,%1,%2,%3},[%4];" : "=r"(r[0]), "=r"(r[1]), "=r"(r[2]), "=r"(r[3]) : "r"(a) : "memory");
}
__device__ __forceinline__ void ldsm4t(uint32_t* r, uint32_t a) {
    asm volatile("ldmatrix.sync.aligned.m8n8.x4.trans.shared.b16 {%0,%1,%2,%3},[%4];" : "=r"(r[0]), "=r"(r[1]), "=r"(r[2]), "=r"(r[3]) : "r"(a) : "memory");
}
__device__ __forceinline__ void stsm4(uint32_t a, uint32_t r0, uint32_t r1, uint32_t r2, uint32_t r3) {
    asm volatile("stmatrix.sync.aligned.m8n8.x4.shared.b16 [%0],{%1,%2,%3,%4};" ::"r"(a), "r"(r0), "r"(r1), "r"(r2), "r"(r3) : "memory");
}
__device__ __forceinline__ uint32_t lds32(uint32_t a) { uint32_t v; asm volatile("ld.shared.b32 %0,[%1];" : "=r"(v) : "r"(a) : "memory"); return v; }
__device__ __forceinline__ uint4 lds128(uint32_t a) { uint4 v; asm volatile("ld.shared.v4.b32 {%0,%1,%2,%3},[%4];" : "=r"(v.x), "=r"(v.y), "=r"(v.z), "=r"(v.w) : "r"(a) : "memory"); return v; }
__device__ __forceinline__ void sts16(uint32_t a, uint32_t v) { asm volatile("st.shared.b16 [%0],%1;" ::"r"(a), "h"((unsigned short)v) : "memory"); }
__device__ __forceinline__ void sts32(uint32_t a, uint32_t v) { asm volatile("st.shared.b32 [%0],%1;" ::"r"(a), "r"(v) : "memory"); }
__device__ __forceinline__ void sts64(uint32_t a, uint32_t x, uint32_t y) { asm volatile("st.shared.v2.b32 [%0],{%1,%2};" ::"r"(a), "r"(x), "r"(y) : "memory"); }
__device__ __forceinline__ void sts128(uint32_t a, uint32_t x, uint32_t y, uint32_t z, uint32_t w) { asm volatile("st.shared.v4.b32 [%0],{%1,%2,%3,%4};" ::"r"(a), "r"(x), "r"(y), "r"(z), "r"(w) : "memory"); }
__device__ __forceinline__ uint32_t pack2(float lo, float hi) { uint32_t d; asm("cvt.rn.bf16x2.f32 %0,%1,%2;" : "=r"(d) : "f"(hi), "f"(lo)); return d; }
__device__ __forceinline__ uint32_t packi(float lo, float hi) { return __byte_perm(__float_as_uint(lo) + 0x8000u, __float_as_uint(hi) + 0x8000u, 0x7632); }
__device__ __forceinline__ float bf_lo(uint32_t v) { return __uint_as_float(v << 16); }
__device__ __forceinline__ float bf_hi(uint32_t v) { return __uint_as_float(v & 0xffff0000u); }
__device__ __forceinline__ float bf_round(float v) { return bf_lo(pack2(v, 0.f)); }
__device__ __forceinline__ uint32_t hmax2(uint32_t a, uint32_t b) { uint32_t d; asm("max.bf16x2 %0,%1,%2;" : "=r"(d) : "r"(a), "r"(b)); return d; }
__device__ __forceinline__ uint32_t hmin2(uint32_t a, uint32_t b) { uint32_t d; asm("min.bf16x2 %0,%1,%2;" : "=r"(d) : "r"(a), "r"(b)); return d; }
__device__ __forceinline__ uint32_t hmul2(uint32_t a, uint32_t b) { uint32_t d; asm("mul.rn.bf16x2 %0,%1,%2;" : "=r"(d) : "r"(a), "r"(b)); return d; }
__device__ __forceinline__ float ex2(float x) { float y; asm("ex2.approx.ftz.f32 %0,%1;" : "=f"(y) : "f"(x)); return y; }
__device__ __forceinline__ float rcp(float x) { float y; asm("rcp.approx.ftz.f32 %0,%1;" : "=f"(y) : "f"(x)); return y; }
__device__ __forceinline__ uint32_t ld_nc(const uint32_t* p) { uint32_t v; asm volatile("ld.global.nc.b32 %0,[%1];" : "=r"(v) : "l"(p)); return v; }
__device__ __forceinline__ unsigned ld_acq(const unsigned* p) { unsigned v; asm volatile("ld.acquire.gpu.global.u32 %0,[%1];" : "=r"(v) : "l"(p) : "memory"); return v; }
__device__ __forceinline__ unsigned ld_rlx(const unsigned* p) { unsigned v; asm volatile("ld.relaxed.gpu.global.u32 %0,[%1];" : "=r"(v) : "l"(p) : "memory"); return v; }
__device__ __forceinline__ uint2 ld_rlx64(const void* p) { uint2 v; asm volatile("{.reg .b64 t; ld.relaxed.gpu.global.b64 t,[%2]; mov.b64 {%0,%1},t;}" : "=r"(v.x), "=r"(v.y) : "l"(p) : "memory"); return v; }
__device__ __forceinline__ uint4 ld_rlx128(const void* p) {
    uint4 v;
    asm volatile("{.reg .b64 t,u; ld.relaxed.gpu.global.v2.b64 {t,u},[%4]; mov.b64 {%0,%1},t; mov.b64 {%2,%3},u;}" : "=r"(v.x), "=r"(v.y), "=r"(v.z), "=r"(v.w) : "l"(p) : "memory");
    return v;
}
__device__ __forceinline__ void st_rlx64(void* p, uint32_t x, uint32_t y) { asm volatile("{.reg .b64 t; mov.b64 t,{%1,%2}; st.relaxed.gpu.global.b64 [%0],t;}" ::"l"(p), "r"(x), "r"(y) : "memory"); }
__device__ __forceinline__ void st_rlx128(void* p, uint4 v) {
    asm volatile("{.reg .b64 t,u; mov.b64 t,{%1,%2}; mov.b64 u,{%3,%4}; st.relaxed.gpu.global.v2.b64 [%0],{t,u};}" ::"l"(p), "r"(v.x), "r"(v.y), "r"(v.z), "r"(v.w) : "memory");
}
__device__ __forceinline__ uint32_t tagw(uint32_t w, uint32_t tag) { return (w & ~1u) | tag; }
__device__ __forceinline__ uint4 tag4(uint32_t x, uint32_t y, uint32_t z, uint32_t w, uint32_t tag) { return make_uint4(tagw(x, tag), y, tagw(z, tag), w); }
__device__ __forceinline__ uint32_t bad4(const uint4& v, uint32_t tag) { return (v.x ^ tag) | (v.z ^ tag); }
__device__ __forceinline__ void bar_named(int id, int n) { asm volatile("bar.sync %0,%1;" ::"r"(id), "r"(n) : "memory"); }

struct cf { float re, im; };
__device__ __forceinline__ cf cmul(cf a, cf b) { cf r; r.re = a.re * b.re - a.im * b.im; r.im = a.re * b.im + a.im * b.re; return r; }
__device__ __forceinline__ cf cexp_p(float arl, float ait, float p) {
    float mag = ex2(arl * p);
    float t = ait * p;
    t = (t - rintf(t)) * 6.283185307179586f;
    cf r; r.re = mag * __cosf(t); r.im = mag * __sinf(t);
    return r;
}

__device__ __forceinline__ void hedgehog2(const uint32_t* a, uint32_t wphi_addr, uint32_t (*out)[8]) {
    float p[2][2][4], mx[2][2];
#pragma unroll
    for (int h = 0; h < 2; h++) {
        uint32_t b[4];
        ldsm4t(b, wphi_addr + h * 512);
        float c0[4] = {0.f, 0.f, 0.f, 0.f}, c1[4] = {0.f, 0.f, 0.f, 0.f};
        mma16816(c0, a[4 * h], a[4 * h + 1], a[4 * h + 2], a[4 * h + 3], b[0], b[1]);
        mma16816(c1, a[4 * h], a[4 * h + 1], a[4 * h + 2], a[4 * h + 3], b[2], b[3]);
#pragma unroll
        for (int k = 0; k < 2; k++) {
            p[h][k][0] = c0[2 * k]; p[h][k][1] = c0[2 * k + 1]; p[h][k][2] = c1[2 * k]; p[h][k][3] = c1[2 * k + 1];
            mx[h][k] = fmaxf(fmaxf(p[h][k][0], p[h][k][1]), fmaxf(p[h][k][2], p[h][k][3]));
        }
    }
#pragma unroll
    for (int o = 1; o <= 2; o <<= 1)
#pragma unroll
        for (int h = 0; h < 2; h++)
#pragma unroll
            for (int k = 0; k < 2; k++) mx[h][k] = fmaxf(mx[h][k], __shfl_xor_sync(~0u, mx[h][k], o));
    const float L = 1.4426950408889634f;
    float pmin = 1.f;
#pragma unroll
    for (int h = 0; h < 2; h++)
#pragma unroll
        for (int k = 0; k < 2; k++) {
            const float m = -mx[h][k] * L;
            const float e0 = ex2(fmaf(p[h][k][0], L, m)), e1 = ex2(fmaf(p[h][k][1], L, m)), e2 = ex2(fmaf(p[h][k][2], L, m)), e3 = ex2(fmaf(p[h][k][3], L, m));
            const float p01 = e0 * e1, p23 = e2 * e3, pp = p01 * p23, r = rcp(pp), r01 = r * p23, r23 = r * p01;
            pmin = fminf(pmin, pp);
            out[h][k] = packi(e0, e1); out[h][k + 2] = packi(e2, e3);
            out[h][4 + k] = pack2(r01 * e1, r01 * e0); out[h][4 + k + 2] = packi(r23 * e3, r23 * e2);
        }
    if (__any_sync(~0u, !(pmin > 1e-18f))) {
#pragma unroll
        for (int h = 0; h < 2; h++)
#pragma unroll
            for (int k = 0; k < 2; k++) {
                float m = fminf(fminf(p[h][k][0], p[h][k][1]), fminf(p[h][k][2], p[h][k][3]));
                m = fminf(m, __shfl_xor_sync(~0u, m, 1));
                m = fminf(m, __shfl_xor_sync(~0u, m, 2)) * L;
                out[h][4 + k] = pack2(ex2(fmaf(p[h][k][0], -L, m)), ex2(fmaf(p[h][k][1], -L, m)));
                out[h][4 + k + 2] = pack2(ex2(fmaf(p[h][k][2], -L, m)), ex2(fmaf(p[h][k][3], -L, m)));
            }
    }
}

__global__ void __launch_bounds__(384, 1)
fused_kernel(const __grid_constant__ CUtensorMap mx, const __grid_constant__ CUtensorMap mw, const __grid_constant__ CUtensorMap mwo,
             const bf16* __restrict__ wphi, const bf16* __restrict__ logA, const bf16* __restrict__ Aim,
             const bf16* __restrict__ Cre, const bf16* __restrict__ Cim, const bf16* __restrict__ logdt, const bf16* __restrict__ Dskip,
             const bf16* __restrict__ gatew, bf16* __restrict__ out) {
    extern __shared__ __align__(1024) uint8_t smem[];
    const uint32_t sb = s2u(smem);
    const int tid = threadIdx.x, warp = __shfl_sync(~0u, tid >> 5, 0), lane = tid & 31;
    const int g = lane >> 2, q = lane & 3, w4 = warp & 3;
    const int bi = blockIdx.x, bi_i = bi & 15, bi_j = bi >> 4;
    const uint32_t bar = sb + OFF_BAR;
    const int rot = (bi_j & 1) * 4;
    auto load_stage = [&](int kb) {
        const uint32_t b = bar + 8 * (BAR_FULL + (kb & 3)), d = sb + (kb & 3) * SLOT;
        const int kc = ((kb + rot) & 7) * 64;
        mbar_expect(b, SLOT);
        tma2d(d, &mx, kc, bi_i * 128, b);
        tma3d(d + 16384, &mw, bi_j * 64, kc, 0, b);
    };

    const int ch = bi * 4 + w4;
    const int pidx = ch * 64 + lane * 2 + (warp < 8);
    const uint32_t pla = ld_nc((const uint32_t*)logA + pidx), pai = ld_nc((const uint32_t*)Aim + pidx);
    const uint32_t pcr = ld_nc((const uint32_t*)Cre + pidx), pci = ld_nc((const uint32_t*)Cim + pidx);
    uint32_t pdt = ld_nc((const uint32_t*)logdt + (ch >> 1));
    const uint32_t pds = ld_nc((const uint32_t*)Dskip + (ch >> 1));
    const unsigned done0 = ld_rlx(g_done);
    if (tid == 0) {
        for (int s = 0; s < 4; s++) mbar_init(bar + 8 * (BAR_FULL + s), 1);
        asm volatile("fence.mbarrier_init.release.cluster;" ::: "memory");
#pragma unroll 1
        for (int s = 0; s < 3; s++) load_stage(s);
        STAMP(11);
    } else if (tid == 32) {
        if (sb & 1023) __trap();
        for (int s = 0; s < 5; s++) sts32(bar + OFF_CNT + 4 * s, 0);
        mbar_init(bar + 8 * BAR_WPHI, 1); mbar_init(bar + 8 * BAR_WO, 2); mbar_init(bar + 8 * BAR_XT, 8); mbar_init(bar + 8 * BAR_DONE, 8);
        mbar_init(bar + 8 * BAR_KG, 8); mbar_init(bar + 8 * BAR_WO2, 1); mbar_init(bar + 8 * BAR_KG2, 1);
        asm volatile("fence.mbarrier_init.release.cluster;" ::: "memory");
        mbar_expect(bar + 8 * BAR_WPHI, 3072);
        bulk_g2s(sb + OFF_GW, gatew, 1024, bar + 8 * BAR_WPHI);
        bulk_g2s(sb + OFF_WPHI, wphi + bi_j * 1024, 2048, bar + 8 * BAR_WPHI);
    } else if (tid == 64) {
        asm volatile("prefetch.tensormap [%0];" ::"l"(&mw) : "memory");
    }
    const uint32_t kb_ = sb + OFF_K + w4 * K_STRIDE, buf = sb + OFF_BUF + w4 * BUF_STRIDE;
    if (warp >= 8) {
#pragma unroll
        for (int v = 0; v < 7; v++) if (v * 32 + lane < K_STRIDE / 16) sts128(kb_ + (v * 32 + lane) * 16, 0, 0, 0, 0);
    }
    __syncthreads();
    asm volatile("" : "+r"(pdt));
    const unsigned epoch1 = (done0 >> 7) + 1u;
    const uint32_t tag = epoch1 & 1u;

    float kc[6][4];
#pragma unroll
    for (int t = 0; t < 6; t++) { kc[t][0] = kc[t][1] = kc[t][2] = kc[t][3] = 0.f; }
    {
        const float dt = bf_round(expf((ch & 1) ? bf_hi(pdt) : bf_lo(pdt)));
#pragma unroll 1
        for (int it = 0; it < 4; it++) {
            uint32_t stg = (warp < 8) ? sb + 3 * SLOT + warp * 7296 : buf;
            if (it == 0 || it == 3) {
                const int sh = (warp < 8 ? (warp >> 2) : (it & 1)) * 16;
                auto pick = [&](uint32_t v) { return __uint_as_float((v >> sh) << 16); };
                const float ea = bf_round(expf(pick(pla)));
                const float arl = (-ea * dt) * 1.4426950408889634f, ait = (pick(pai) * dt) * 0.15915494309189535f;
                cf C2; C2.re = 2.0f * (pick(pcr) * dt); C2.im = 2.0f * (pick(pci) * dt);
                const cf z1 = cexp_p(arl, ait, 1.0f), z128 = cexp_p(arl, ait, 128.0f);
                cf z8 = cexp_p(arl, ait, 8.0f); z8.im = -z8.im;
                const uint32_t lp = stg + lane * 4;
                auto put = [&](int row, const cf& v) { sts32((lp ^ ((row & 7) << 4)) + row * 128, pack2(v.re, v.im)); };
                {
                    const cf z16 = cmul(z8, z8);
                    cf e; e.re = 1.f; e.im = 0.f;
                    cf o = z8;
                    put(0, e); put(1, o);
                    e = z16; put(2, e);
#pragma unroll
                    for (int b = 3; b < 16; b += 2) {
                        o = cmul(o, z16); put(b, o);
                        if (b + 1 < 16) { e = cmul(e, z16); put(b + 1, e); }
                    }
                }
                cf h[8];
                h[0] = C2; put(16, h[0]);
                {
                    const cf z2 = cmul(z1, z1);
                    h[1] = cmul(h[0], z1);
#pragma unroll
                    for (int r = 2; r < 8; r++) h[r] = cmul(h[r - 2], z2);
#pragma unroll
                    for (int r = 1; r < 8; r++) put(16 + r, h[r]);
                }
#pragma unroll
                for (int r = 0; r < 8; r++) { h[r] = cmul(h[r], z128); put(24 + r, h[r]); }
#pragma unroll
                for (int al = 0; al < 2; al++)
#pragma unroll
                    for (int r = 0; r < 4; r++) { h[2 * r] = cmul(h[2 * r], z128); put(32 + al * 4 + r, h[2 * r]); }
#pragma unroll
                for (int al = 0; al < 4; al++)
#pragma unroll
                    for (int r = 0; r < 2; r++) { h[4 * r] = cmul(h[4 * r], z128); put(40 + al * 2 + r, h[4 * r]); }
#pragma unroll
                for (int al = 0; al < 9; al++) { h[0] = cmul(h[0], z128); put(48 + al, h[0]); }
                __syncwarp();
                if (warp < 8) {
                    if (lane == 0) mbar_arrive(bar + 8 * BAR_KG);
                    break;
                }
            } else {
                if (it == 1) mbar_wait(bar + 8 * BAR_KG, 0);
                stg = sb + 3 * SLOT + (w4 + (it - 1) * 4) * 7296;
            }
            const int lr = lane & 7, lm = lane >> 3;
#pragma unroll
            for (int kp = 0; kp < 2; kp++) {
                uint32_t a0[4], a1[4];
                ldsm4(a0, stg + ((lm & 1) * 8 + lr) * 128 + (((4 * kp + (lm >> 1)) ^ lr) << 4));
                ldsm4(a1, stg + ((lm & 1) * 8 + lr) * 128 + (((4 * kp + 2 + (lm >> 1)) ^ lr) << 4));
#pragma unroll
                for (int t = 0; t < 6; t++) {
                    uint32_t b[4];
                    ldsm4(b, stg + (16 + 8 * t + lr) * 128 + (((4 * kp + lm) ^ lr) << 4));
                    mma16816(kc[t], a0[0], a0[1], a0[2], a0[3], b[0], b[1]);
                    mma16816(kc[t], a1[0], a1[1], a1[2], a1[3], b[2], b[3]);
                }
            }
            __syncwarp();
            if (it == 2) {
                asm volatile("fence.proxy.async.shared::cta;" ::: "memory");
                bar_named(2, 128);
                if (tid == 256) { load_stage(3); mbar_arrive(bar + 8 * BAR_KG2); }
                if (warp == 8) STAMP(22);
            }
        }
    }

    if (warp < 8) {
        const int wg = warp >> 2;
        if (warp == 0) STAMP(21);
        float acc[96];
        const int grow = bi_j * 16 + warp * 2 + (lane >> 4);
        const uint32_t gx_a = grow * 128 + ((((lane & 15) >> 1) ^ (grow & 7)) << 4) + (lane & 1) * 8;
        const int srow = warp * 16 + (lane & 15);
        const uint32_t srow_a = srow * 128;
        const int sx = srow & 7, shi = lane >> 4;
        auto last_of_8 = [&](int c) {
            unsigned old;
            asm volatile("atom.acq_rel.cta.shared.add.u32 %0,[%1],1;" : "=r"(old) : "r"(bar + OFF_CNT + 4 * c) : "memory");
            return (old & 7) == 7;
        };
        float gsum = 0.f;
#pragma unroll
        for (int r = 0; r < 96; r++) acc[r] = 0.f;
        fence_regs<96>(acc);
        const uint64_t da0 = mkdesc(sb + wg * 8192, 16, 1024), db0 = mkdesc(sb + 16384, 8192, 1024);
        mbar_wait(bar + 8 * BAR_WPHI, 0);
        mbar_wait(bar + 8 * BAR_KG2, 0);
#pragma unroll 1
        for (int kb = 0; kb < 8; kb++) {
            const int s = kb & 3;
            const uint64_t da = da0 + s * (SLOT >> 4), db = db0 + s * (SLOT >> 4);
            mbar_wait(bar + 8 * (BAR_FULL + s), kb >> 2);
            if (kb == 0 && warp == 0) STAMP(0);
            wg_fence();
#pragma unroll
            for (int k = 0; k < 4; k++) wgmma192(acc, da + 2 * k, db + 128 * k);
            wg_commit();
            wg_wait<1>();
            __syncwarp();
            if (lane == 0 && kb > 0 && kb < 7) {
                const int ps = (kb - 1) & 3;
                if (last_of_8(ps)) {
                    if (kb < 5) load_stage(kb + 3);
                    else {
                        mbar_expect(bar + 8 * BAR_WO, 32768);
                        tma2d(sb + ps * SLOT, &mwo, (bi_j & 3) * 128 + ps * 64, 0, bar + 8 * BAR_WO);
                    }
                }
            }
            __syncwarp();
            const uint32_t st = sb + s * SLOT;
            if (kb == (bi_j >> 1)) {
                uint32_t* xt = (uint32_t*)g_xt + ((kb + rot) * 16 + (g >> 2)) * 4096 + (bi_i * 16 + warp * 2) * 16 + (g & 3) * 4 + q;
#pragma unroll
                for (int cb = 0; cb < 8; cb += 2) {
                    uint32_t r[4];
                    ldsm4t(r, st + srow_a + (((cb + shi) ^ sx) << 4));
                    xt[cb * 8192] = r[0]; xt[cb * 8192 + 16] = r[1]; xt[cb * 8192 + 8192] = r[2]; xt[cb * 8192 + 8192 + 16] = r[3];
                }
                __syncwarp();
                if (lane == 0) mbar_arrive(bar + 8 * BAR_XT);
            }
            {
                uint32_t x0, x1, w0, w1;
                asm volatile("ld.shared.v2.b32 {%0,%1},[%2];" : "=r"(x0), "=r"(x1) : "r"(st + gx_a) : "memory");
                asm volatile("ld.shared.v2.b32 {%0,%1},[%2];" : "=r"(w0), "=r"(w1) : "r"(sb + OFF_GW + ((kb + rot) & 7) * 128 + (lane & 15) * 8) : "memory");
                const uint32_t p0 = hmul2(x0, w0), p1 = hmul2(x1, w1);
                gsum += (bf_lo(p0) + bf_hi(p0)) + (bf_lo(p1) + bf_hi(p1));
            }
        }
        wg_wait<0>();
        fence_regs<96>(acc);
        __syncwarp();
        if (lane == 0) mbar_arrive(bar + 8 * BAR_DONE);
        if (warp == 0) STAMP(1);
        uint32_t in[32], va[16];
#pragma unroll
        for (int r = 0; r < 16; r++) {
            in[r] = pack2(acc[32 + 2 * r], acc[32 + 2 * r + 1]);
            in[16 + r] = packi(acc[2 * r], acc[2 * r + 1]);
            va[r] = packi(acc[64 + 2 * r], acc[64 + 2 * r + 1]);
        }
        const uint32_t wphi_a = sb + OFF_WPHI + (lane & 15) * 32 + (lane >> 4) * 16;
        uint32_t pq[4][8];
#pragma unroll 1
        for (int it = 0; it < 4; it++) {
            hedgehog2(in, wphi_a + (it & 1) * 1024, pq + 2);
#pragma unroll
            for (int r = 0; r < 24; r++) in[r] = in[r + 8];
            if (it < 2) {
#pragma unroll
                for (int hs = 0; hs < 4; hs++) {
                    float c[4] = {0.f, 0.f, 0.f, 0.f};
                    uint32_t* o = pq[2 + (hs >> 1)] + 4 * (hs & 1);
                    mma16816(c, o[0], o[1], o[2], o[3], 0x3f803f80u, 0x3f803f80u);
                    const float r0 = rcp(c[0]), r1 = rcp(c[2]);
                    const uint32_t s0 = packi(r0, r0), s1 = packi(r1, r1);
                    o[0] = hmul2(o[0], s0); o[1] = hmul2(o[1], s1); o[2] = hmul2(o[2], s0); o[3] = hmul2(o[3], s1);
                }
                if (it == 0) mbar_wait(bar + 8 * BAR_DONE, 0);
                const uint32_t pt = sb + OFF_P + it * 16384 + srow_a, vt = sb + OFF_V + it * 16384 + srow_a;
#pragma unroll
                for (int hl = 0; hl < 2; hl++) {
                    stsm4(pt + (((4 * hl + shi) ^ sx) << 4), pq[2 + hl][0], pq[2 + hl][1], pq[2 + hl][2], pq[2 + hl][3]);
                    stsm4(pt + (((4 * hl + 2 + shi) ^ sx) << 4), pq[2 + hl][4], pq[2 + hl][5], pq[2 + hl][6], pq[2 + hl][7]);
                    stsm4(vt + (((2 * hl + shi) ^ sx) << 4), va[4 * hl], va[4 * hl + 1], va[4 * hl + 2], va[4 * hl + 3]);
                }
                if (lane < 16) sts128(vt + ((4 ^ sx) << 4), 0x3f803f80u, 0x3f803f80u, 0x3f803f80u, 0x3f803f80u);
#pragma unroll
                for (int r = 0; r < 8; r++) va[r] = va[r + 8];
            }
            if (it == 1) {
                asm volatile("fence.proxy.async.shared::cta;" ::: "memory");
                bar_named(1, 256);
                if (warp == 0) STAMP(2);
                float d[32];
                const uint64_t dv = mkdesc(sb + OFF_V + wg * 16384, 16, 1024), dp = mkdesc(sb + OFF_P + wg * 16384, 16, 1024);
                wg_fence();
#pragma unroll
                for (int k = 0; k < 8; k++) wgmma64_tt(d, dv + 128 * k, dp + 128 * k, k != 0);
                wg_commit();
                wg_wait<0>();
                fence_regs<32>(d);
                uint4* kvp = g_kvp + bi * 544 + wg * 272;
                if (w4 < 2) {
                    uint32_t e[16];
#pragma unroll
                    for (int r = 0; r < 16; r++) e[r] = __float_as_uint(w4 ? d[16 + r] : d[r]);
                    uint4* p = kvp + w4 * 136 + lane;
#pragma unroll
                    for (int ks = 0; ks < 2; ks++)
#pragma unroll
                        for (int nt = 0; nt < 2; nt++)
                            st_rlx128(p + (ks * 2 + nt) * 32, tag4(e[8 * ks + 2 * nt], e[8 * ks + 2 * nt + 1], e[8 * ks + 4 + 2 * nt], e[8 * ks + 4 + 2 * nt + 1], tag));
                } else if (w4 == 2 && lane < 4) {
#pragma unroll
                    for (int hl = 0; hl < 2; hl++)
#pragma unroll
                        for (int ks = 0; ks < 2; ks++)
                            st_rlx128(kvp + hl * 136 + 128 + ks * 4 + lane, tag4(__float_as_uint(d[16 * hl + 8 * ks]), __float_as_uint(d[16 * hl + 8 * ks + 1]),
                                                                                __float_as_uint(d[16 * hl + 8 * ks + 4]), __float_as_uint(d[16 * hl + 8 * ks + 5]), tag));
                }
                if (warp == 0) STAMP(3);
            }
            if (it == 2) {
#pragma unroll
                for (int r = 0; r < 8; r++) { pq[0][r] = pq[2][r]; pq[1][r] = pq[3][r]; }
                if (warp == 0) STAMP(12);
                if (warp < 4 || (warp == 4 && (bi_i & 1) == 0)) {
                    const bool zw = warp == 4;
                    const int qq = (bi_i & 2) + ((lane >> 1) & 1);
                    const uint4* src = g_kvp + bi_j * (16 * 544) + (bi_i >> 2) * 136 +
                                       (zw ? (lane >> 2) * (2 * 544) + 128 + (lane & 1) * 4 + qq
                                           : (lane >> 3) * (4 * 544) + ((lane >> 1) & 3) * 32 + (bi_i & 3) * 8 + warp * 2 + (lane & 1));
                    const int s23 = zw ? 0 : 2 * 544;
                    uint4 v[4];
                    int n = 0;
                    while (true) {
                        v[0] = ld_rlx128(src); v[1] = ld_rlx128(src + 544); v[2] = ld_rlx128(src + s23); v[3] = ld_rlx128(src + s23 + 544);
                        if (!__any_sync(~0u, (bad4(v[0], tag) | bad4(v[1], tag) | bad4(v[2], tag) | bad4(v[3], tag)) & 1)) break;
                        if (++n > SPIN_LIMIT) break;
                    }
                    float f[4];
                    f[0] = __uint_as_float(v[2].x) + __uint_as_float(v[3].x); f[1] = __uint_as_float(v[2].y) + __uint_as_float(v[3].y);
                    f[2] = __uint_as_float(v[2].z) + __uint_as_float(v[3].z); f[3] = __uint_as_float(v[2].w) + __uint_as_float(v[3].w);
                    float e0 = __uint_as_float(v[0].x) + __uint_as_float(v[1].x), e1 = __uint_as_float(v[0].y) + __uint_as_float(v[1].y);
                    float e2 = __uint_as_float(v[0].z) + __uint_as_float(v[1].z), e3 = __uint_as_float(v[0].w) + __uint_as_float(v[1].w);
                    if (zw) {
                        e0 = __shfl_xor_sync(~0u, f[0], 4); e1 = __shfl_xor_sync(~0u, f[1], 4);
                        e2 = __shfl_xor_sync(~0u, f[2], 4); e3 = __shfl_xor_sync(~0u, f[3], 4);
                    }
                    f[0] += e0; f[1] += e1; f[2] += e2; f[3] += e3;
#pragma unroll
                    for (int o = 8; o <= 16; o <<= 1)
#pragma unroll
                        for (int r = 0; r < 4; r++) f[r] += __shfl_xor_sync(~0u, f[r], o);
                    uint2* dst = (uint2*)(g_kvf + (bi_j * 4 + (bi_i >> 2)) * 68) +
                                 (zw ? (64 + qq) * 2 + (lane & 1) : ((bi_i & 3) * 8 + warp * 2 + (lane & 1)) * 4 + (lane >> 1));
                    if (lane < (zw ? 4 : 8)) st_rlx64(dst, tagw(pack2(f[0], f[1]), tag), pack2(f[2], f[3]));
                }
                __syncwarp();
                if (lane == 0 && last_of_8(4)) {
                    mbar_expect(bar + 8 * BAR_WO2, 65536);
                    tma2d(sb + 2 * SLOT, &mwo, (bi_j & 3) * 128, 256, bar + 8 * BAR_WO2);
                    tma2d(sb + 3 * SLOT, &mwo, (bi_j & 3) * 128 + 64, 256, bar + 8 * BAR_WO2);
                }
                __syncwarp();
                if (warp == 0) STAMP(13);
#pragma unroll
                for (int o = 1; o < 16; o <<= 1) gsum += __shfl_xor_sync(~0u, gsum, o);
                const float gate = bf_round(rcp(1.0f + ex2(-1.4426950408889634f * bf_round(gsum))));
                const uint32_t gv = __shfl_sync(~0u, __float_as_uint(gate) | tag, (lane & 4) * 4);
                if (lane < 8) asm volatile("st.relaxed.gpu.global.u32 [%0],%1;" ::"l"(g_g + (bi_i * 64 + bi_j * 8 + warp) * 8 + lane), "r"(gv) : "memory");
            }
        }
        if (warp == 0) STAMP(4);
        {
            uint4 kf[4][3];
            const uint4* kp = g_kvf + bi_j * 272;
            int n = 0;
            while (true) {
                uint32_t bad = 0;
#pragma unroll
                for (int hh = 0; hh < 4; hh++) {
                    kf[hh][0] = ld_rlx128(kp + hh * 68 + lane * 2); kf[hh][1] = ld_rlx128(kp + hh * 68 + lane * 2 + 1); kf[hh][2] = ld_rlx128(kp + hh * 68 + 64 + q);
                }
#pragma unroll
                for (int hh = 0; hh < 4; hh++) bad |= bad4(kf[hh][0], tag) | bad4(kf[hh][1], tag) | bad4(kf[hh][2], tag);
                if (!__any_sync(~0u, bad & 1)) break;
                if (++n > SPIN_LIMIT) break;
            }
            if (warp == 0) STAMP(5);
            uint4 own[4];
#pragma unroll
            for (int hh = 0; hh < 4; hh++) {
                float c[6][4];
#pragma unroll
                for (int t = 0; t < 6; t++) { c[t][0] = c[t][1] = c[t][2] = c[t][3] = 0.f; }
                const uint32_t* a = pq[hh];
                const bool od = g & 1;
                mma16816(c[0], a[0], a[1], a[2], a[3], od ? 0x3f803f80u : kf[hh][2].x, od ? 0x3f803f80u : kf[hh][2].y);
                mma16816(c[1], a[4], a[5], a[6], a[7], od ? 0x3f803f80u : kf[hh][2].z, od ? 0x3f803f80u : kf[hh][2].w);
                mma16816(c[2], a[0], a[1], a[2], a[3], kf[hh][0].x, kf[hh][0].y);
                mma16816(c[3], a[0], a[1], a[2], a[3], kf[hh][0].z, kf[hh][0].w);
                mma16816(c[4], a[4], a[5], a[6], a[7], kf[hh][1].x, kf[hh][1].y);
                mma16816(c[5], a[4], a[5], a[6], a[7], kf[hh][1].z, kf[hh][1].w);
                uint32_t w[4];
#pragma unroll
                for (int k = 0; k < 2; k++) {
                    const float rho = c[0][2 * k + 1] * rcp(c[1][2 * k + 1]);
                    const float r = rcp(fmaf(c[0][2 * k + 1], 1e-6f, fmaf(rho, c[1][2 * k], c[0][2 * k]))), rr = r * rho;
                    w[k] = packi(fmaf(c[4][2 * k], rr, c[2][2 * k] * r), fmaf(c[4][2 * k + 1], rr, c[2][2 * k + 1] * r));
                    w[2 + k] = packi(fmaf(c[5][2 * k], rr, c[3][2 * k] * r), fmaf(c[5][2 * k + 1], rr, c[3][2 * k + 1] * r));
                }
                own[hh] = tag4(w[0], w[1], w[2], w[3], tag);
            }
            uint4* og = g_o + ((bi_i * 8 + warp) * 32 + bi_j * 4) * 32 + lane;
#pragma unroll
            for (int hh = 0; hh < 4; hh++) st_rlx128(og + hh * 32, own[hh]);
        }
        if (warp == 0) STAMP(6);
        float oc[64];
        const int slab = bi_i * 8 + (bi_j >> 2) * 4 + w4;
        const uint8_t* yb = (const uint8_t*)g_y + (size_t)((bi_j & 3) * 32 + wg * 16 + (q >> 1)) * 16384 + slab * 128 + g * 16 + (q & 1) * 8;
        const unsigned* gp = g_g + (slab * 8 + (g >> 1)) * 8 + (g & 1) * 4;
        uint2 yv[8]; unsigned g0, g1;
        {
            const uint4* osrc = g_o + (slab * 32 + wg * 16) * 32 + lane;
            uint4 fr[16];
            {
                const unsigned* probe = (const unsigned*)(osrc - lane + ((lane & 3) * 4 + 3) * 32 + 31) + 2;
                int n = 0;
                while (__any_sync(~0u, (ld_rlx(probe) ^ tag) & 1)) { if (++n > SPIN_LIMIT) break; }
            }
            if (warp == 0) STAMP(14);
#pragma unroll
            for (int k = 0; k < 16; k++) fr[k] = ld_rlx128(osrc + k * 32);
            mbar_wait(bar + 8 * (wg ? BAR_WO2 : BAR_WO), 0);
            const uint64_t dw = mkdesc(sb + wg * 2 * SLOT, SLOT, 1024);
#pragma unroll
            for (int s = 0; s < 4; s++) {
                int n = 0;
                while (__any_sync(~0u, (bad4(fr[4 * s], tag) | bad4(fr[4 * s + 1], tag) | bad4(fr[4 * s + 2], tag) | bad4(fr[4 * s + 3], tag)) & 1)) {
#pragma unroll
                    for (int hh = 0; hh < 4; hh++) fr[4 * s + hh] = ld_rlx128(osrc + (4 * s + hh) * 32);
                    if (++n > SPIN_LIMIT) break;
                }
                wg_fence();
#pragma unroll
                for (int hh = 0; hh < 4; hh++) wgmma128_rs(oc, fr[4 * s + hh], dw + 128 * (4 * s + hh), (s | hh) != 0);
                wg_commit();
            }
#pragma unroll
            for (int nt = 0; nt < 8; nt++) yv[nt] = ld_rlx64(yb + nt * 32768);
            g0 = ld_rlx(gp); g1 = ld_rlx(gp + 32);
            if (warp == 0) STAMP(7);
            wg_wait<0>();
            fence_regs<64>(oc);
        }
        {
            bar_named(3 + wg, 128);
            const uint32_t xw = sb + wg * 2 * SLOT + (tid & 127) * 16, xr = sb + (wg ^ 1) * 2 * SLOT + (tid & 127) * 16;
#pragma unroll
            for (int r = 0; r < 8; r++) {
                const float* o = oc + 4 * r;
                sts128(xw + r * 2048, __float_as_uint(wg ? o[0] : o[32]), __float_as_uint(wg ? o[1] : o[33]), __float_as_uint(wg ? o[2] : o[34]), __float_as_uint(wg ? o[3] : o[35]));
            }
#pragma unroll
            for (int r = 0; r < 32; r++) oc[r] = wg ? oc[32 + r] : oc[r];
            bar_named(1, 256);
            if (warp == 0) STAMP(8);
            int n = 0;
            while (true) {
                uint32_t bad = (g0 ^ tag) | (g1 ^ tag);
#pragma unroll
                for (int nt = 0; nt < 8; nt++) bad |= yv[nt].x ^ tag;
                if (!__any_sync(~0u, bad & 1)) break;
#pragma unroll
                for (int nt = 0; nt < 8; nt++) yv[nt] = ld_rlx64(yb + nt * 32768);
                g0 = ld_rlx(gp); g1 = ld_rlx(gp + 32);
                if (++n > SPIN_LIMIT) break;
            }
            if (warp == 0) STAMP(9);
            const float ga = bf_hi(g0), gb = bf_hi(g1);
            const float ha = bf_round(1.0f - ga), hb = bf_round(1.0f - gb);
            uint32_t w[8][2];
#pragma unroll
            for (int nt = 0; nt < 8; nt++) {
                const uint4 p = lds128(xr + nt * 2048);
                w[nt][0] = pack2(fmaf(ga, oc[4 * nt] + __uint_as_float(p.x), ha * bf_lo(yv[nt].x)), fmaf(ga, oc[4 * nt + 1] + __uint_as_float(p.y), ha * bf_hi(yv[nt].x)));
                w[nt][1] = pack2(fmaf(gb, oc[4 * nt + 2] + __uint_as_float(p.z), hb * bf_lo(yv[nt].y)), fmaf(gb, oc[4 * nt + 3] + __uint_as_float(p.w), hb * bf_hi(yv[nt].y)));
            }
            const uint32_t ob = sb + (2 + wg) * SLOT + 32768 + w4 * 2048;
#pragma unroll
            for (int nt = 0; nt < 8; nt += 2)
                stsm4(ob + (lane & 15) * 128 + (((nt + shi) ^ (lane & 7)) << 4), w[nt][0], w[nt][1], w[nt + 1][0], w[nt + 1][1]);
            __syncwarp();
            bf16* op = out + (size_t)(slab * 16) * 512 + (bi_j & 3) * 128 + wg * 64 + (lane & 7) * 8;
#pragma unroll
            for (int it = 0; it < 4; it++) {
                const int r = it * 4 + (lane >> 3);
                uint4 v = lds128(ob + r * 128 + (((lane & 7) ^ (r & 7)) << 4));
                *(uint4*)(op + r * 512) = v;
            }
        }
        if (warp == 0) STAMP(10);
    } else {
        const int st = tid - 256;
        const uint32_t ub = sb + OFF_U + w4 * U_STRIDE + 256;
        const uint32_t spare = sb + (w4 < 2 ? OFF_SP0 : OFF_SP1) + (w4 & 1) * 4096;
        if (warp == 8) STAMP(16);
        if (lane == 0) kc[0][0] += (ch & 1) ? bf_hi(pds) : bf_lo(pds);
        const uint32_t k1024 = __shfl_sync(~0u, pack2(kc[4][0], 0.f), 0);
#pragma unroll
        for (int i = 0; i < 2; i++) {
            const int be = g + 8 * i;
#pragma unroll
            for (int t = 0; t < 2; t++) {
                const uint32_t a = kb_ + (KW_D + 128 * t + 8 * be + 2 * q) * 4;
                const uint32_t w = pack2(kc[t][2 * i + 1], kc[t][2 * i]);
                sts32(a + 4, w); sts16(a, w >> 16); sts16(a + 10, w);
            }
            {
                const int p = 256 + 128 * (q >> 1) + 8 * be + 4 * (q & 1);
                const uint32_t a = kb_ + (KW_D + p) * 4;
                const uint32_t w = pack2(kc[2][2 * i + 1], kc[2][2 * i]);
                const uint32_t aa = (w >> 16) | (w & 0xffff0000u);
                if (p != 256) { sts16(a - 4, aa); sts32(a, aa); } else sts16(a, aa);
                sts32(a + 4, aa); sts32(a + 8, w); sts16(a + 14, w);
            }
            {
                const int k = 64 + 16 * q + be;
                const uint32_t w = pack2(kc[3][2 * i], kc[3][2 * i + 1]);
                if (k != 64) sts16(kb_ + (KW_2 + ((k - 1) >> 1) - 24) * 4 + (k & 1) * 2, w);
                else {
                    const uint32_t a = kb_ + (KW_D + 511) * 4, aa = (w << 16) | (w & 0xffffu);
                    sts16(a, w); sts32(a + 4, aa); sts32(a + 8, aa); sts32(a + 12, aa); sts16(a + 18, w);
                }
                sts16(kb_ + (KW_2 + 48 + (k >> 1) - 24) * 4 + ((k & 1) ^ 1) * 2, w >> 16);
            }
#pragma unroll
            for (int b = 0; b < 2; b++) {
                const int k = 64 + 8 * (2 * q + b) + (be >> 1);
                const uint32_t w = pack2(kc[4][2 * i + b], 0.f);
                if (!(be & 1) && k == 64) sts16(kb_ + (KW_2 + 63 - 24) * 4, w);
                else {
                    const uint32_t a = kb_ + (KW_3 + ((be & 1) ? 80 + k : k - 1) - 48) * 4;
                    sts16(a, w);
                    if (!((be & 1) && k == 127)) sts16(a + 6, w);
                }
            }
        }
        if (lane == 0) sts16(kb_ + (KW_3 + 127 - 48) * 4, pack2(kc[5][0], 0.f));
        if (lane < 2) sts128(buf + lane * W3_OFF, 0, 0, 0, 0);
        if (lane < 16) sts128(ub - 256 + lane * 16, 0, 0, 0, 0);
        if (warp == 8) {
            mbar_wait(bar + 8 * BAR_XT, 0);
            if (lane == 0) asm volatile("red.release.gpu.global.add.u32 [%0],8;" ::"l"(g_xcnt + ((bi_j >> 1) + rot) * 32) : "memory");
        }
        if (lane == 0) {
            int n = 0;
            while ((int)(ld_acq(g_xcnt + bi_j * 32) - (epoch1 << 7)) < 0) { __nanosleep(200); if (++n > SPIN_LIMIT) break; }
        }
        __syncwarp();
        if (warp == 8) STAMP(15);
        {
            uint4 ur[8];
#pragma unroll
            for (int v = 0; v < 8; v++) ur[v] = __ldcg(g_xt + bi * 1024 + st + 128 * v);
#pragma unroll
            for (int v = 0; v < 8; v++) {
                const int ci = (st >> 2) + 32 * v;
                sts128(sb + OFF_U + (st & 3) * U_STRIDE + 256 + ((ci ^ ((ci >> 3) & 1)) << 4), ur[v].x, ur[v].y, ur[v].z, ur[v].w);
            }
        }
        mbar_wait(bar + 8 * BAR_WO, 0);
        bar_named(2, 128);
        if (warp == 8) STAMP(17);
        float y[16][4];
#pragma unroll
        for (int nt = 0; nt < 16; nt++) { y[nt][0] = y[nt][1] = y[nt][2] = y[nt][3] = 0.f; }
        {
            uint32_t Bp[32];
            auto uaddr = [&](int rho) { const int R0 = (lane >> 4) * 8 + (lane & 7) - rho; return ub + (((2 * R0 + ((lane >> 3) & 1)) ^ ((R0 >> 2) & 1)) << 4); };
            const uint32_t kd = kb_ + (KW_D + g - 2 * q) * 4;
            {
                const uint32_t a = uaddr(0);
#pragma unroll
                for (int p = 0; p < 8; p++) ldsm4(Bp + 4 * p, a + p * 512);
            }
#pragma unroll 1
            for (int rho = 0; rho < 8; rho++) {
                uint32_t A[5][4];
#pragma unroll
                for (int ga = 0; ga < 5; ga++) {
                    const uint32_t a = kd + (ga < 4 ? rho : (rho & 1)) * 64 + ga * 512;
                    A[ga][0] = lds32(a); A[ga][1] = lds32(a + 32); A[ga][2] = lds32(a - 32); A[ga][3] = A[ga][0];
                }
                const int ci = lane + 32 * rho;
                uint4 e4[4];
#pragma unroll
                for (int v = 0; v < 4; v++) { const int cc = ci - 3 + v; e4[v] = lds128(ub + ((cc ^ ((cc >> 3) & 1)) << 4)); }
                float S[29];
                const uint32_t* ew = (const uint32_t*)e4;
                S[3] = 0.f;
#pragma unroll
                for (int k = 4; k <= 28; k++) S[k] = S[k - 1] + ((k & 1) ? bf_hi(ew[k >> 1]) : bf_lo(ew[k >> 1]));
                auto win = [&](int lo, int hi, uint32_t a, bool on) {
                    const uint32_t w0 = pack2(S[hi] - S[lo - 1], S[hi + 1] - S[lo]), w1 = pack2(S[hi + 2] - S[lo + 1], S[hi + 3] - S[lo + 2]);
                    const uint32_t w2 = pack2(S[hi + 4] - S[lo + 3], S[hi + 5] - S[lo + 4]), w3 = pack2(S[hi + 6] - S[lo + 5], S[hi + 7] - S[lo + 6]);
                    asm volatile("{.reg .pred p; setp.ne.b32 p,%5,0; @p st.shared.v4.b32 [%0],{%1,%2,%3,%4};}" ::"r"(a), "r"(w0), "r"(w1), "r"(w2), "r"(w3), "r"((int)on) : "memory");
                };
                const uint32_t sw = (ci ^ ((ci >> 3) & 1)) << 4;
#pragma unroll
                for (int nt = 0; nt < 16; nt++) mma16816v(y[nt], A[0][0], A[0][1], A[0][2], A[0][3], Bp[2 * nt], Bp[2 * nt + 1]);
                win(4, 12, buf + W9_OFF + sw, rho < 4);
#pragma unroll
                for (int nt = 1; nt < 16; nt++) mma16816v(y[nt], A[1][0], A[1][1], A[1][2], A[1][3], Bp[2 * (nt - 1)], Bp[2 * (nt - 1) + 1]);
                win(14, 18, buf + W5_OFF + 16 + ci * 16, rho < 6); win(13, 19, spare + sw, rho < 4);
                const uint32_t an = uaddr(rho + 1);
                ldsm4(Bp + 28, an + 7 * 512);
#pragma unroll
                for (int nt = 2; nt < 16; nt++) mma16816v(y[nt], A[2][0], A[2][1], A[2][2], A[2][3], Bp[2 * (nt - 2)], Bp[2 * (nt - 2) + 1]);
                win(19, 21, buf + W3_OFF + 16 + ci * 16, rho < 6); win(20, 21, spare + 2048 + sw, rho < 4);
                if (rho < 2) {
#pragma unroll
                    for (int nt = 4; nt < 16; nt++) mma16816v(y[nt], A[4][0], A[4][1], A[4][2], A[4][3], Bp[2 * (nt - 4)], Bp[2 * (nt - 4) + 1]);
                }
#pragma unroll
                for (int nt = 3; nt < 16; nt++) {
                    mma16816v(y[nt], A[3][0], A[3][1], A[3][2], A[3][3], Bp[2 * (nt - 3)], Bp[2 * (nt - 3) + 1]);
                    if ((nt & 1) == 0) ldsm4(Bp + 2 * (nt - 4), an + ((nt - 4) >> 1) * 512);
                    if (nt == 15) ldsm4(Bp + 24, an + 6 * 512);
                }
            }
        }
        __syncwarp();
        if (warp == 8) STAMP(18);
#pragma unroll 1
        for (int ph = 0; ph < 2; ph++) {
            uint32_t B[5][2];
            const uint32_t ka = kb_ + (KW_2 + ph * 48 + 8 + g - q) * 4;
#pragma unroll
            for (int dd = 0; dd < 5; dd++) { B[dd][0] = lds32(ka + dd * 32); B[dd][1] = lds32(ka + dd * 32 - 16); }
            const uint32_t wa = buf + ph * W3_OFF + ((lane & 7) + ((lane >> 3) & 1) + (lane >> 4) * 8) * 16;
#pragma unroll
            for (int s = 0; s < 12; s++) {
                uint32_t A[4];
                ldsm4t(A, wa + s * 256);
#pragma unroll
                for (int dd = 0; dd < 5; dd++)
                    if (s + 4 + dd < 16) mma16816(y[s + 4 + dd], A[0], A[1], A[2], A[3], B[dd][0], B[dd][1]);
            }
        }
        {
            const int ap = (lane & 7) + (lane >> 4) * 8;
            const uint32_t loff = ((2 * ap + ((lane >> 3) & 1)) ^ ((ap >> 2) & 1)) << 4;
#pragma unroll 1
            for (int ph = 0; ph < 2; ph++) {
                uint32_t B[8][2];
                const uint32_t wb = (ph ? spare : buf + W9_OFF) + loff;
                const uint32_t ka = kb_ + (KW_3 + ph * 80 + 16 + g - 2 * q) * 4;
#pragma unroll
                for (int dd = 0; dd < 8; dd++) { B[dd][0] = lds32(ka + dd * 32); B[dd][1] = lds32(ka + dd * 32 - 32); }
#pragma unroll
                for (int s = 0; s < 4; s++) {
                    uint32_t A[4];
                    ldsm4t(A, wb + s * 512);
#pragma unroll
                    for (int dd = 0; dd < 8; dd++)
                        if (8 + 2 * s + dd < 16) mma16816(y[8 + 2 * s + dd], A[0], A[1], A[2], A[3], B[dd][0], B[dd][1]);
                }
            }
            const uint32_t idw = (g == 2 * q) ? k1024 : ((g == 2 * q + 1) ? (k1024 << 16) : 0u);
#pragma unroll
            for (int s = 0; s < 4; s++) {
                uint32_t A[4];
                ldsm4t(A, spare + 2048 + loff + s * 512);
                mma16816(y[8 + 2 * s], A[0], A[1], A[2], A[3], idw, 0u);
                mma16816(y[9 + 2 * s], A[0], A[1], A[2], A[3], 0u, idw);
            }
        }
        __syncwarp();
        if (warp == 8) STAMP(19);
#pragma unroll
        for (int nt = 0; nt < 16; nt++)
#pragma unroll
            for (int b = 0; b < 2; b++) sts32(buf + ((8 * nt + 2 * q + b) * 8 + g) * 4, pack2(y[nt][b], y[nt][2 + b]));
        bar_named(2, 128);
        uint4* yp = g_y + bi * 1024 + st;
#pragma unroll
        for (int v = 0; v < 8; v++) {
            const uint32_t a = sb + OFF_BUF + (st + 128 * v) * 4;
            const uint32_t w0 = lds32(a), w1 = lds32(a + BUF_STRIDE), w2 = lds32(a + 2 * BUF_STRIDE), w3 = lds32(a + 3 * BUF_STRIDE);
            st_rlx128(yp + v * 128, tag4(__byte_perm(w0, w1, 0x5410), __byte_perm(w0, w1, 0x7632), __byte_perm(w2, w3, 0x5410), __byte_perm(w2, w3, 0x7632), tag));
        }
        if (warp == 8) STAMP(20);
    }
    __syncthreads();
    if (tid == 0) atomicAdd(g_done, 1u);
}

typedef CUresult (*EncFn)(CUtensorMap*, CUtensorMapDataType, cuuint32_t, void*, const cuuint64_t*, const cuuint64_t*, const cuuint32_t*,
                          const cuuint32_t*, CUtensorMapInterleave, CUtensorMapSwizzle, CUtensorMapL2promotion, CUtensorMapFloatOOBfill);

extern "C" void kernel_launch(void* const* d_in, const int* in_sizes, int n_in, void* d_out, int out_size) {
    static EncFn enc = nullptr;
    if (!enc) {
        cudaDriverEntryPointQueryResult qr;
        cudaGetDriverEntryPoint("cuTensorMapEncodeTiled", (void**)&enc, cudaEnableDefault, &qr);
        cudaFuncSetAttribute(fused_kernel, cudaFuncAttributeMaxDynamicSharedMemorySize, SMEM_BYTES);
    }
    CUtensorMap mx, mw, mwo;
    const cuuint32_t es[3] = {1, 1, 1};
    {
        cuuint64_t d[2] = {512, 2048}, s[1] = {1024}; cuuint32_t b[2] = {64, 128};
        enc(&mx, CU_TENSOR_MAP_DATA_TYPE_BFLOAT16, 2, d_in[0], d, s, b, es, CU_TENSOR_MAP_INTERLEAVE_NONE, CU_TENSOR_MAP_SWIZZLE_128B,
            CU_TENSOR_MAP_L2_PROMOTION_L2_128B, CU_TENSOR_MAP_FLOAT_OOB_FILL_NONE);
    }
    {
        cuuint64_t d[3] = {512, 512, 3}, s[2] = {3072, 1024}; cuuint32_t b[3] = {64, 64, 3};
        enc(&mw, CU_TENSOR_MAP_DATA_TYPE_BFLOAT16, 3, d_in[1], d, s, b, es, CU_TENSOR_MAP_INTERLEAVE_NONE, CU_TENSOR_MAP_SWIZZLE_128B,
            CU_TENSOR_MAP_L2_PROMOTION_L2_128B, CU_TENSOR_MAP_FLOAT_OOB_FILL_NONE);
    }
    {
        cuuint64_t d[2] = {512, 512}, s[1] = {1024}; cuuint32_t b[2] = {64, 256};
        enc(&mwo, CU_TENSOR_MAP_DATA_TYPE_BFLOAT16, 2, d_in[3], d, s, b, es, CU_TENSOR_MAP_INTERLEAVE_NONE, CU_TENSOR_MAP_SWIZZLE_128B,
            CU_TENSOR_MAP_L2_PROMOTION_L2_128B, CU_TENSOR_MAP_FLOAT_OOB_FILL_NONE);
    }
    fused_kernel<<<128, 384, SMEM_BYTES, cudaStreamPerThread>>>(
        mx, mw, mwo, (const bf16*)d_in[2], (const bf16*)d_in[5], (const bf16*)d_in[6], (const bf16*)d_in[7],
        (const bf16*)d_in[8], (const bf16*)d_in[9], (const bf16*)d_in[10], (const bf16*)d_in[11], (bf16*)d_out);
}
```

```cpp
#include <cuda_runtime.h>
#include <cuda.h>
#include <cuda_bf16.h>
#include <stdint.h>

typedef __nv_bfloat16 bf16;

struct Scratch {
    uint4 xt[128 * 1024];
    uint4 o[16 * 8 * 32 * 32];
    uint4 y[128 * 1024];
    uint4 kvp[8 * 16 * 544];
    uint4 kvf[8 * 4 * 68];
    unsigned g[1024 * 8];
    unsigned yflag[128 * 8];
    unsigned xcnt[8 * 32];
    unsigned done[32];
};
__device__ Scratch g_scr;
#define STAMP(n)

constexpr int SLOT = 40960;
constexpr int OFF_SP0 = 32768, OFF_SP1 = SLOT + 32768;
constexpr int OFF_P = 2 * SLOT, OFF_V = OFF_P + 32768;
constexpr int OFF_U = 4 * SLOT, U_STRIDE = 4096 + 256;
constexpr int OFF_K = OFF_U + 4 * U_STRIDE, K_STRIDE = 3264;
constexpr int OFF_BUF = OFF_K + 4 * K_STRIDE, BUF_STRIDE = 8320;
constexpr int OFF_WPHI = OFF_BUF + 4 * BUF_STRIDE;
constexpr int OFF_GW = OFF_WPHI + 2048;
constexpr int OFF_BAR = OFF_GW + 1024;
constexpr int SMEM_BYTES = OFF_BAR + 128 + 128;
static_assert(SMEM_BYTES <= 232448 && OFF_BUF % 128 == 0, "smem");
constexpr int KW_D = 16, KW_2 = 560, KW_3 = 656;
constexpr int W5_OFF = 0, W3_OFF = 3088, W9_OFF = 6176;
constexpr int BAR_FULL = 0, BAR_WPHI = 4, BAR_WO = 5, BAR_XT = 6, BAR_DONE = 7, BAR_KG = 8, BAR_WO2 = 9, BAR_KG2 = 10, OFF_CNT = 96;
constexpr int SPIN_LIMIT = 1 << 17;

__device__ __forceinline__ uint32_t s2u(const void* p) { return (uint32_t)__cvta_generic_to_shared(p); }
__device__ __forceinline__ void mbar_init(uint32_t b, int c) { asm volatile("mbarrier.init.shared::cta.b64 [%0],%1;" ::"r"(b), "r"(c) : "memory"); }
__device__ __forceinline__ void mbar_expect(uint32_t b, int bytes) { asm volatile("mbarrier.arrive.expect_tx.shared::cta.b64 _,[%0],%1;" ::"r"(b), "r"(bytes) : "memory"); }
__device__ __forceinline__ void mbar_arrive(uint32_t b) { asm volatile("mbarrier.arrive.shared::cta.b64 _,[%0];" ::"r"(b) : "memory"); }
__device__ __forceinline__ bool mbar_try(uint32_t b, int ph) {
    uint32_t ok;
    asm volatile("{.reg .pred p; mbarrier.try_wait.parity.shared::cta.b64 p,[%1],%2; selp.u32 %0,1,0,p;}" : "=r"(ok) : "r"(b), "r"(ph) : "memory");
    return ok;
}
__device__ __forceinline__ void mbar_wait(uint32_t b, int ph) {
    if ((threadIdx.x & 31) == 0) { int n = 0; while (!mbar_try(b, ph)) { if (++n > SPIN_LIMIT) break; } }
    __syncwarp();
}
__device__ __forceinline__ void tma2d(uint32_t dst, const CUtensorMap* m, int c0, int c1, uint32_t bar) {
    asm volatile("cp.async.bulk.tensor.2d.shared::cluster.global.mbarrier::complete_tx::bytes [%0],[%1,{%3,%4}],[%2];" ::"r"(dst), "l"(m), "r"(bar), "r"(c0), "r"(c1) : "memory");
}
__device__ __forceinline__ void tma3d(uint32_t dst, const CUtensorMap* m, int c0, int c1, int c2, uint32_t bar) {
    asm volatile("cp.async.bulk.tensor.3d.shared::cluster.global.mbarrier::complete_tx::bytes [%0],[%1,{%3,%4,%5}],[%2];" ::"r"(dst), "l"(m), "r"(bar), "r"(c0), "r"(c1), "r"(c2) : "memory");
}
__device__ __forceinline__ void bulk_g2s(uint32_t dst, const void* src, int bytes, uint32_t bar) {
    asm volatile("cp.async.bulk.shared::cluster.global.mbarrier::complete_tx::bytes [%0],[%1],%2,[%3];" ::"r"(dst), "l"(src), "r"(bytes), "r"(bar) : "memory");
}
__device__ __forceinline__ uint64_t mkdesc(uint32_t addr, uint32_t lbo, uint32_t sbo) {
    return (uint64_t)((addr & 0x3FFFF) >> 4) | ((uint64_t)(lbo >> 4) << 16) | ((uint64_t)(sbo >> 4) << 32) | ((uint64_t)1 << 62);
}
__device__ __forceinline__ void wg_fence() { asm volatile("wgmma.fence.sync.aligned;" ::: "memory"); }
__device__ __forceinline__ void wg_commit() { asm volatile("wgmma.commit_group.sync.aligned;" ::: "memory"); }
template <int N> __device__ __forceinline__ void wg_wait() { asm volatile("wgmma.wait_group.sync.aligned %0;" ::"n"(N) : "memory"); }
template <int N> __device__ __forceinline__ void fence_regs(float* d) {
#pragma unroll
    for (int i = 0; i < N; i++) asm volatile("" : "+f"(d[i])::"memory");
}
#define R8(d, o) "+f"(d[o]), "+f"(d[o + 1]), "+f"(d[o + 2]), "+f"(d[o + 3]), "+f"(d[o + 4]), "+f"(d[o + 5]), "+f"(d[o + 6]), "+f"(d[o + 7])
__device__ __forceinline__ void wgmma192(float* d, uint64_t da, uint64_t db) {
    asm volatile("wgmma.mma_async.sync.aligned.m64n192k16.f32.bf16.bf16 {"
                 "%0,%1,%2,%3,%4,%5,%6,%7,%8,%9,%10,%11,%12,%13,%14,%15,%16,%17,%18,%19,%20,%21,%22,%23,%24,%25,%26,%27,%28,%29,%30,%31,"
                 "%32,%33,%34,%35,%36,%37,%38,%39,%40,%41,%42,%43,%44,%45,%46,%47,%48,%49,%50,%51,%52,%53,%54,%55,%56,%57,%58,%59,%60,%61,%62,%63,"
                 "%64,%65,%66,%67,%68,%69,%70,%71,%72,%73,%74,%75,%76,%77,%78,%79,%80,%81,%82,%83,%84,%85,%86,%87,%88,%89,%90,%91,%92,%93,%94,%95},"
                 "%96,%97,1,1,1,0,1;"
                 : R8(d, 0), R8(d, 8), R8(d, 16), R8(d, 24), R8(d, 32), R8(d, 40), R8(d, 48), R8(d, 56), R8(d, 64), R8(d, 72), R8(d, 80), R8(d, 88)
                 : "l"(da), "l"(db));
}
__device__ __forceinline__ void wgmma64_tt(float* d, uint64_t da, uint64_t db, int sc) {
    asm volatile("{.reg .pred p; setp.ne.b32 p,%34,0; wgmma.mma_async.sync.aligned.m64n64k16.f32.bf16.bf16 {"
                 "%0,%1,%2,%3,%4,%5,%6,%7,%8,%9,%10,%11,%12,%13,%14,%15,%16,%17,%18,%19,%20,%21,%22,%23,%24,%25,%26,%27,%28,%29,%30,%31},"
                 "%32,%33,p,1,1,1,1;}"
                 : R8(d, 0), R8(d, 8), R8(d, 16), R8(d, 24)
                 : "l"(da), "l"(db), "r"(sc));
}
__device__ __forceinline__ void wgmma128_rs(float* d, const uint4& a, uint64_t db, int sc) {
    asm volatile("{.reg .pred p; setp.ne.b32 p,%69,0; wgmma.mma_async.sync.aligned.m64n128k16.f32.bf16.bf16 {"
                 "%0,%1,%2,%3,%4,%5,%6,%7,%8,%9,%10,%11,%12,%13,%14,%15,%16,%17,%18,%19,%20,%21,%22,%23,%24,%25,%26,%27,%28,%29,%30,%31,"
                 "%32,%33,%34,%35,%36,%37,%38,%39,%40,%41,%42,%43,%44,%45,%46,%47,%48,%49,%50,%51,%52,%53,%54,%55,%56,%57,%58,%59,%60,%61,%62,%63},"
                 "{%64,%65,%66,%67},%68,p,1,1,1;}"
                 : R8(d, 0), R8(d, 8), R8(d, 16), R8(d, 24), R8(d, 32), R8(d, 40), R8(d, 48), R8(d, 56)
                 : "r"(a.x), "r"(a.y), "r"(a.z), "r"(a.w), "l"(db), "r"(sc));
}
__device__ __forceinline__ void mma16816v(float* c, uint32_t a0, uint32_t a1, uint32_t a2, uint32_t a3, uint32_t b0, uint32_t b1) {
    asm volatile("mma.sync.aligned.m16n8k16.row.col.f32.bf16.bf16.f32 {%0,%1,%2,%3},{%4,%5,%6,%7},{%8,%9},{%0,%1,%2,%3};"
        : "+f"(c[0]), "+f"(c[1]), "+f"(c[2]), "+f"(c[3]) : "r"(a0), "r"(a1), "r"(a2), "r"(a3), "r"(b0), "r"(b1));
}
__device__ __forceinline__ void mma16816(float* c, uint32_t a0, uint32_t a1, uint32_t a2, uint32_t a3, uint32_t b0, uint32_t b1) {
    asm("mma.sync.aligned.m16n8k16.row.col.f32.bf16.bf16.f32 {%0,%1,%2,%3},{%4,%5,%6,%7},{%8,%9},{%0,%1,%2,%3};"
        : "+f"(c[0]), "+f"(c[1]), "+f"(c[2]), "+f"(c[3]) : "r"(a0), "r"(a1), "r"(a2), "r"(a3), "r"(b0), "r"(b1));
}
__device__ __forceinline__ void ldsm4(uint32_t* r, uint32_t a) {
    asm volatile("ldmatrix.sync.aligned.m8n8.x4.shared.b16 {%0,%1,%2,%3},[%4];" : "=r"(r[0]), "=r"(r[1]), "=r"(r[2]), "=r"(r[3]) : "r"(a) : "memory");
}
__device__ __forceinline__ void ldsm4t(uint32_t* r, uint32_t a) {
    asm volatile("ldmatrix.sync.aligned.m8n8.x4.trans.shared.b16 {%0,%1,%2,%3},[%4];" : "=r"(r[0]), "=r"(r[1]), "=r"(r[2]), "=r"(r[3]) : "r"(a) : "memory");
}
__device__ __forceinline__ void stsm4(uint32_t a, uint32_t r0, uint32_t r1, uint32_t r2, uint32_t r3) {
    asm volatile("stmatrix.sync.aligned.m8n8.x4.shared.b16 [%0],{%1,%2,%3,%4};" ::"r"(a), "r"(r0), "r"(r1), "r"(r2), "r"(r3) : "memory");
}
__device__ __forceinline__ uint32_t lds32(uint32_t a) { uint32_t v; asm volatile("ld.shared.b32 %0,[%1];" : "=r"(v) : "r"(a) : "memory"); return v; }
__device__ __forceinline__ uint4 lds128(uint32_t a) { uint4 v; asm volatile("ld.shared.v4.b32 {%0,%1,%2,%3},[%4];" : "=r"(v.x), "=r"(v.y), "=r"(v.z), "=r"(v.w) : "r"(a) : "memory"); return v; }
__device__ __forceinline__ void sts16(uint32_t a, uint32_t v) { asm volatile("st.shared.b16 [%0],%1;" ::"r"(a), "h"((unsigned short)v) : "memory"); }
__device__ __forceinline__ void sts32(uint32_t a, uint32_t v) { asm volatile("st.shared.b32 [%0],%1;" ::"r"(a), "r"(v) : "memory"); }
__device__ __forceinline__ void sts64(uint32_t a, uint32_t x, uint32_t y) { asm volatile("st.shared.v2.b32 [%0],{%1,%2};" ::"r"(a), "r"(x), "r"(y) : "memory"); }
__device__ __forceinline__ void sts128(uint32_t a, uint32_t x, uint32_t y, uint32_t z, uint32_t w) { asm volatile("st.shared.v4.b32 [%0],{%1,%2,%3,%4};" ::"r"(a), "r"(x), "r"(y), "r"(z), "r"(w) : "memory"); }
__device__ __forceinline__ uint32_t pack2(float lo, float hi) { uint32_t d; asm("cvt.rn.bf16x2.f32 %0,%1,%2;" : "=r"(d) : "f"(hi), "f"(lo)); return d; }
__device__ __forceinline__ uint32_t packi(float lo, float hi) { return __byte_perm(__float_as_uint(lo) + 0x8000u, __float_as_uint(hi) + 0x8000u, 0x7632); }
__device__ __forceinline__ float bf_lo(uint32_t v) { return __uint_as_float(v << 16); }
__device__ __forceinline__ float bf_hi(uint32_t v) { return __uint_as_float(v & 0xffff0000u); }
__device__ __forceinline__ float bf_round(float v) { return bf_lo(pack2(v, 0.f)); }
__device__ __forceinline__ uint32_t hmax2(uint32_t a, uint32_t b) { uint32_t d; asm("max.bf16x2 %0,%1,%2;" : "=r"(d) : "r"(a), "r"(b)); return d; }
__device__ __forceinline__ uint32_t hmin2(uint32_t a, uint32_t b) { uint32_t d; asm("min.bf16x2 %0,%1,%2;" : "=r"(d) : "r"(a), "r"(b)); return d; }
__device__ __forceinline__ uint32_t hmul2(uint32_t a, uint32_t b) { uint32_t d; asm("mul.rn.bf16x2 %0,%1,%2;" : "=r"(d) : "r"(a), "r"(b)); return d; }
__device__ __forceinline__ float ex2(float x) { float y; asm("ex2.approx.ftz.f32 %0,%1;" : "=f"(y) : "f"(x)); return y; }
__device__ __forceinline__ float rcp(float x) { float y; asm("rcp.approx.ftz.f32 %0,%1;" : "=f"(y) : "f"(x)); return y; }
__device__ __forceinline__ uint32_t ld_nc(const uint32_t* p) { uint32_t v; asm volatile("ld.global.nc.b32 %0,[%1];" : "=r"(v) : "l"(p)); return v; }
__device__ __forceinline__ unsigned ld_acq(const unsigned* p) { unsigned v; asm volatile("ld.acquire.gpu.global.u32 %0,[%1];" : "=r"(v) : "l"(p) : "memory"); return v; }
__device__ __forceinline__ unsigned ld_rlx(const unsigned* p) { unsigned v; asm volatile("ld.relaxed.gpu.global.u32 %0,[%1];" : "=r"(v) : "l"(p) : "memory"); return v; }
__device__ __forceinline__ uint2 ld_rlx64(const void* p) { uint2 v; asm volatile("{.reg .b64 t; ld.relaxed.gpu.global.b64 t,[%2]; mov.b64 {%0,%1},t;}" : "=r"(v.x), "=r"(v.y) : "l"(p) : "memory"); return v; }
__device__ __forceinline__ uint4 ld_rlx128(const void* p) {
    uint4 v;
    asm volatile("{.reg .b64 t,u; ld.relaxed.gpu.global.v2.b64 {t,u},[%4]; mov.b64 {%0,%1},t; mov.b64 {%2,%3},u;}" : "=r"(v.x), "=r"(v.y), "=r"(v.z), "=r"(v.w) : "l"(p) : "memory");
    return v;
}
__device__ __forceinline__ void st_rlx32(void* p, uint32_t x) { asm volatile("st.relaxed.gpu.global.u32 [%0],%1;" ::"l"(p), "r"(x) : "memory"); }
__device__ __forceinline__ void st_rlx64(void* p, uint32_t x, uint32_t y) { asm volatile("{.reg .b64 t; mov.b64 t,{%1,%2}; st.relaxed.gpu.global.b64 [%0],t;}" ::"l"(p), "r"(x), "r"(y) : "memory"); }
__device__ __forceinline__ void st_rlx128(void* p, uint4 v) {
    asm volatile("{.reg .b64 t,u; mov.b64 t,{%1,%2}; mov.b64 u,{%3,%4}; st.relaxed.gpu.global.v2.b64 [%0],{t,u};}" ::"l"(p), "r"(v.x), "r"(v.y), "r"(v.z), "r"(v.w) : "memory");
}
__device__ __forceinline__ uint32_t tagw(uint32_t w, uint32_t tag) { return (w & ~1u) | tag; }
__device__ __forceinline__ uint4 tag4(uint32_t x, uint32_t y, uint32_t z, uint32_t w, uint32_t tag) { return make_uint4(tagw(x, tag), y, tagw(z, tag), w); }
__device__ __forceinline__ uint32_t bad4(const uint4& v, uint32_t tag) { return (v.x ^ tag) | (v.z ^ tag); }
__device__ __forceinline__ void bar_named(int id, int n) { asm volatile("bar.sync %0,%1;" ::"r"(id), "r"(n) : "memory"); }

struct cf { float re, im; };
__device__ __forceinline__ cf cmul(cf a, cf b) { cf r; r.re = a.re * b.re - a.im * b.im; r.im = a.re * b.im + a.im * b.re; return r; }
__device__ __forceinline__ cf cexp_p(float arl, float ait, float p) {
    float mag = ex2(arl * p);
    float t = ait * p;
    t = (t - rintf(t)) * 6.283185307179586f;
    cf r; r.re = mag * __cosf(t); r.im = mag * __sinf(t);
    return r;
}

__device__ __forceinline__ void hedgehog2(const uint32_t* a, uint32_t wphi_addr, uint32_t (*out)[8]) {
    float p[2][2][4], mx[2][2];
#pragma unroll
    for (int h = 0; h < 2; h++) {
        uint32_t b[4];
        ldsm4t(b, wphi_addr + h * 512);
        float c0[4] = {0.f, 0.f, 0.f, 0.f}, c1[4] = {0.f, 0.f, 0.f, 0.f};
        mma16816(c0, a[4 * h], a[4 * h + 1], a[4 * h + 2], a[4 * h + 3], b[0], b[1]);
        mma16816(c1, a[4 * h], a[4 * h + 1], a[4 * h + 2], a[4 * h + 3], b[2], b[3]);
#pragma unroll
        for (int k = 0; k < 2; k++) {
            p[h][k][0] = c0[2 * k]; p[h][k][1] = c0[2 * k + 1]; p[h][k][2] = c1[2 * k]; p[h][k][3] = c1[2 * k + 1];
            mx[h][k] = fmaxf(fmaxf(p[h][k][0], p[h][k][1]), fmaxf(p[h][k][2], p[h][k][3]));
        }
    }
#pragma unroll
    for (int o = 1; o <= 2; o <<= 1)
#pragma unroll
        for (int h = 0; h < 2; h++)
#pragma unroll
            for (int k = 0; k < 2; k++) mx[h][k] = fmaxf(mx[h][k], __shfl_xor_sync(~0u, mx[h][k], o));
    const float L = 1.4426950408889634f;
    float pmin = 1.f;
#pragma unroll
    for (int h = 0; h < 2; h++)
#pragma unroll
        for (int k = 0; k < 2; k++) {
            const float m = -mx[h][k] * L;
            const float e0 = ex2(fmaf(p[h][k][0], L, m)), e1 = ex2(fmaf(p[h][k][1], L, m)), e2 = ex2(fmaf(p[h][k][2], L, m)), e3 = ex2(fmaf(p[h][k][3], L, m));
            const float p01 = e0 * e1, p23 = e2 * e3, pp = p01 * p23, r = rcp(pp), r01 = r * p23, r23 = r * p01;
            pmin = fminf(pmin, pp);
            out[h][k] = packi(e0, e1); out[h][k + 2] = packi(e2, e3);
            out[h][4 + k] = pack2(r01 * e1, r01 * e0); out[h][4 + k + 2] = packi(r23 * e3, r23 * e2);
        }
    if (__any_sync(~0u, !(pmin > 1e-18f))) {
#pragma unroll
        for (int h = 0; h < 2; h++)
#pragma unroll
            for (int k = 0; k < 2; k++) {
                float m = fminf(fminf(p[h][k][0], p[h][k][1]), fminf(p[h][k][2], p[h][k][3]));
                m = fminf(m, __shfl_xor_sync(~0u, m, 1));
                m = fminf(m, __shfl_xor_sync(~0u, m, 2)) * L;
                out[h][4 + k] = pack2(ex2(fmaf(p[h][k][0], -L, m)), ex2(fmaf(p[h][k][1], -L, m)));
                out[h][4 + k + 2] = pack2(ex2(fmaf(p[h][k][2], -L, m)), ex2(fmaf(p[h][k][3], -L, m)));
            }
    }
}

__global__ void __launch_bounds__(384, 1)
fused_kernel(Scratch* __restrict__ scr, const bf16* __restrict__ logA, const bf16* __restrict__ Aim, const bf16* __restrict__ Cre,
             const bf16* __restrict__ Cim, const bf16* __restrict__ logdt, const bf16* __restrict__ Dskip, const bf16* __restrict__ wphi,
             const bf16* __restrict__ gatew, bf16* __restrict__ out,
             const __grid_constant__ CUtensorMap mx, const __grid_constant__ CUtensorMap mw, const __grid_constant__ CUtensorMap mwo) {
    extern __shared__ __align__(1024) uint8_t smem[];
    const uint32_t sb = s2u(smem);
    const int tid = threadIdx.x, warp = __shfl_sync(~0u, tid >> 5, 0), lane = tid & 31;
    const int g = lane >> 2, q = lane & 3, w4 = warp & 3;
    const int bi = blockIdx.x, bi_i = bi & 15, bi_j = bi >> 4;
    const uint32_t bar = sb + OFF_BAR;
    const int rot = (bi_j & 1) * 4;
    auto load_stage = [&](int kb) {
        const uint32_t b = bar + 8 * (BAR_FULL + (kb & 3)), d = sb + (kb & 3) * SLOT;
        const int kc = ((kb + rot) & 7) * 64;
        mbar_expect(b, SLOT);
        tma2d(d, &mx, kc, bi_i * 128, b);
        tma3d(d + 16384, &mw, bi_j * 64, kc, 0, b);
    };

    const int ch = bi * 4 + w4;
    const int pidx = ch * 64 + lane * 2 + (warp < 8);
    const uint32_t pla = ld_nc((const uint32_t*)logA + pidx), pai = ld_nc((const uint32_t*)Aim + pidx);
    const uint32_t pcr = ld_nc((const uint32_t*)Cre + pidx), pci = ld_nc((const uint32_t*)Cim + pidx);
    uint32_t pdt = ld_nc((const uint32_t*)logdt + (ch >> 1));
    const uint32_t pds = ld_nc((const uint32_t*)Dskip + (ch >> 1));
    const unsigned done0 = ld_rlx(scr->done);
    if (tid == 0) {
        for (int s = 0; s < 4; s++) mbar_init(bar + 8 * (BAR_FULL + s), 1);
        asm volatile("fence.mbarrier_init.release.cluster;" ::: "memory");
#pragma unroll 1
        for (int s = 0; s < 3; s++) load_stage(s);
        STAMP(11);
    } else if (tid == 32) {
        if (sb & 1023) __trap();
        for (int s = 0; s < 5; s++) sts32(bar + OFF_CNT + 4 * s, 0);
        mbar_init(bar + 8 * BAR_WPHI, 1); mbar_init(bar + 8 * BAR_WO, 2); mbar_init(bar + 8 * BAR_XT, 8); mbar_init(bar + 8 * BAR_DONE, 8);
        mbar_init(bar + 8 * BAR_KG, 8); mbar_init(bar + 8 * BAR_WO2, 1); mbar_init(bar + 8 * BAR_KG2, 1);
        asm volatile("fence.mbarrier_init.release.cluster;" ::: "memory");
        mbar_expect(bar + 8 * BAR_WPHI, 3072);
        bulk_g2s(sb + OFF_GW, gatew, 1024, bar + 8 * BAR_WPHI);
        bulk_g2s(sb + OFF_WPHI, wphi + bi_j * 1024, 2048, bar + 8 * BAR_WPHI);
    } else if (tid == 64) {
        asm volatile("prefetch.tensormap [%0];" ::"l"(&mw) : "memory");
    }
    const uint32_t kb_ = sb + OFF_K + w4 * K_STRIDE, buf = sb + OFF_BUF + w4 * BUF_STRIDE;
    if (warp >= 8) {
#pragma unroll
        for (int v = 0; v < 7; v++) if (v * 32 + lane < K_STRIDE / 16) sts128(kb_ + (v * 32 + lane) * 16, 0, 0, 0, 0);
    }
    __syncthreads();
    asm volatile("" : "+r"(pdt));
    const unsigned epoch1 = (done0 >> 7) + 1u;
    const uint32_t tag = epoch1 & 1u;

    float kc[6][4];
#pragma unroll
    for (int t = 0; t < 6; t++) { kc[t][0] = kc[t][1] = kc[t][2] = kc[t][3] = 0.f; }
    {
        const float dt = bf_round(expf((ch & 1) ? bf_hi(pdt) : bf_lo(pdt)));
#pragma unroll 1
        for (int it = 0; it < 4; it++) {
            uint32_t stg = (warp < 8) ? sb + 3 * SLOT + warp * 7296 : buf;
            if (it == 0 || it == 3) {
                const int sh = (warp < 8 ? (warp >> 2) : (it & 1)) * 16;
                auto pick = [&](uint32_t v) { return __uint_as_float((v >> sh) << 16); };
                const float ea = bf_round(expf(pick(pla)));
                const float arl = (-ea * dt) * 1.4426950408889634f, ait = (pick(pai) * dt) * 0.15915494309189535f;
                cf C2; C2.re = 2.0f * (pick(pcr) * dt); C2.im = 2.0f * (pick(pci) * dt);
                const cf z1 = cexp_p(arl, ait, 1.0f), z128 = cexp_p(arl, ait, 128.0f);
                cf z8 = cexp_p(arl, ait, 8.0f); z8.im = -z8.im;
                const uint32_t lp = stg + lane * 4;
                auto put = [&](int row, const cf& v) { sts32((lp ^ ((row & 7) << 4)) + row * 128, pack2(v.re, v.im)); };
                {
                    const cf z16 = cmul(z8, z8);
                    cf e; e.re = 1.f; e.im = 0.f;
                    cf o = z8;
                    put(0, e); put(1, o);
                    e = z16; put(2, e);
#pragma unroll
                    for (int b = 3; b < 16; b += 2) {
                        o = cmul(o, z16); put(b, o);
                        if (b + 1 < 16) { e = cmul(e, z16); put(b + 1, e); }
                    }
                }
                cf h[8];
                h[0] = C2; put(16, h[0]);
                {
                    const cf z2 = cmul(z1, z1);
                    h[1] = cmul(h[0], z1);
#pragma unroll
                    for (int r = 2; r < 8; r++) h[r] = cmul(h[r - 2], z2);
#pragma unroll
                    for (int r = 1; r < 8; r++) put(16 + r, h[r]);
                }
#pragma unroll
                for (int r = 0; r < 8; r++) { h[r] = cmul(h[r], z128); put(24 + r, h[r]); }
#pragma unroll
                for (int al = 0; al < 2; al++)
#pragma unroll
                    for (int r = 0; r < 4; r++) { h[2 * r] = cmul(h[2 * r], z128); put(32 + al * 4 + r, h[2 * r]); }
#pragma unroll
                for (int al = 0; al < 4; al++)
#pragma unroll
                    for (int r = 0; r < 2; r++) { h[4 * r] = cmul(h[4 * r], z128); put(40 + al * 2 + r, h[4 * r]); }
#pragma unroll
                for (int al = 0; al < 9; al++) { h[0] = cmul(h[0], z128); put(48 + al, h[0]); }
                __syncwarp();
                if (warp < 8) {
                    if (lane == 0) mbar_arrive(bar + 8 * BAR_KG);
                    break;
                }
            } else {
                if (it == 1) mbar_wait(bar + 8 * BAR_KG, 0);
                stg = sb + 3 * SLOT + (w4 + (it - 1) * 4) * 7296;
            }
            const int lr = lane & 7, lm = lane >> 3;
#pragma unroll
            for (int kp = 0; kp < 2; kp++) {
                uint32_t a0[4], a1[4];
                ldsm4(a0, stg + ((lm & 1) * 8 + lr) * 128 + (((4 * kp + (lm >> 1)) ^ lr) << 4));
                ldsm4(a1, stg + ((lm & 1) * 8 + lr) * 128 + (((4 * kp + 2 + (lm >> 1)) ^ lr) << 4));
#pragma unroll
                for (int t = 0; t < 6; t++) {
                    uint32_t b[4];
                    ldsm4(b, stg + (16 + 8 * t + lr) * 128 + (((4 * kp + lm) ^ lr) << 4));
                    mma16816(kc[t], a0[0], a0[1], a0[2], a0[3], b[0], b[1]);
                    mma16816(kc[t], a1[0], a1[1], a1[2], a1[3], b[2], b[3]);
                }
            }
            __syncwarp();
            if (it == 2) {
                asm volatile("fence.proxy.async.shared::cta;" ::: "memory");
                bar_named(2, 128);
                if (tid == 256) { load_stage(3); mbar_arrive(bar + 8 * BAR_KG2); }
                if (warp == 8) STAMP(22);
            }
        }
    }

    if (warp < 8) {
        const int wg = warp >> 2;
        if (warp == 0) STAMP(21);
        float acc[96];
        const int grow = bi_j * 16 + warp * 2 + (lane >> 4);
        const uint32_t gx_a = grow * 128 + ((((lane & 15) >> 1) ^ (grow & 7)) << 4) + (lane & 1) * 8;
        const int srow = warp * 16 + (lane & 15);
        const uint32_t srow_a = srow * 128;
        const int sx = srow & 7, shi = lane >> 4;
        auto last_of_8 = [&](int c) {
            unsigned old;
            asm volatile("atom.acq_rel.cta.shared.add.u32 %0,[%1],1;" : "=r"(old) : "r"(bar + OFF_CNT + 4 * c) : "memory");
            return (old & 7) == 7;
        };
        const int qq = (bi_i & 2) + ((lane >> 1) & 1);
        const int kvf_n = warp < 4 ? 8 : ((warp == 4 && (bi_i & 1) == 0) ? 4 : 0);
        uint2* kvf_dst = (uint2*)(scr->kvf + (bi_j * 4 + (bi_i >> 2)) * 68) +
                         (warp == 4 ? (64 + qq) * 2 + (lane & 1) : ((bi_i & 3) * 8 + w4 * 2 + (lane & 1)) * 4 + (lane >> 1));
        float gsum = 0.f;
#pragma unroll
        for (int r = 0; r < 96; r++) acc[r] = 0.f;
        fence_regs<96>(acc);
        const uint64_t da0 = mkdesc(sb + wg * 8192, 16, 1024), db0 = mkdesc(sb + 16384, 8192, 1024);
        {
            const uint32_t old = tag ^ 1u;
            const uint4 z4 = make_uint4(old, 0, old, 0);
            uint4* kvp = scr->kvp + bi * 544 + wg * 272;
            if (w4 < 2) {
#pragma unroll
                for (int f = 0; f < 4; f++) st_rlx128(kvp + w4 * 136 + lane + f * 32, z4);
            } else if (w4 == 2 && lane < 4) {
#pragma unroll
                for (int f = 0; f < 4; f++) st_rlx128(kvp + (f >> 1) * 136 + 128 + (f & 1) * 4 + lane, z4);
            }
            if (lane < kvf_n) st_rlx64(kvf_dst, old, 0);
            if (lane >= 30) st_rlx128(scr->o + ((bi_i * 8 + warp) * 32 + bi_j * 4 + 3) * 32 + lane, z4);
            if (lane < 8) st_rlx32(scr->g + (bi_i * 64 + bi_j * 8 + warp) * 8 + lane, old);
        }
        mbar_wait(bar + 8 * BAR_WPHI, 0);
        mbar_wait(bar + 8 * BAR_KG2, 0);
#pragma unroll 1
        for (int kb = 0; kb < 8; kb++) {
            const int s = kb & 3;
            const uint64_t da = da0 + s * (SLOT >> 4), db = db0 + s * (SLOT >> 4);
            mbar_wait(bar + 8 * (BAR_FULL + s), kb >> 2);
            if (kb == 0 && warp == 0) STAMP(0);
            wg_fence();
#pragma unroll
            for (int k = 0; k < 4; k++) wgmma192(acc, da + 2 * k, db + 128 * k);
            wg_commit();
            wg_wait<1>();
            __syncwarp();
            if (lane == 0 && kb > 0 && kb < 7) {
                const int ps = (kb - 1) & 3;
                if (last_of_8(ps)) {
                    if (kb < 5) load_stage(kb + 3);
                    else {
                        mbar_expect(bar + 8 * BAR_WO, 32768);
                        tma2d(sb + ps * SLOT, &mwo, (bi_j & 3) * 128 + ps * 64, 0, bar + 8 * BAR_WO);
                    }
                }
            }
            __syncwarp();
            const uint32_t st = sb + s * SLOT;
            if (kb == (bi_j >> 1)) {
                uint32_t* xt = (uint32_t*)scr->xt + ((kb + rot) * 16 + (g >> 2)) * 4096 + (bi_i * 16 + warp * 2) * 16 + (g & 3) * 4 + q;
#pragma unroll
                for (int cb = 0; cb < 8; cb += 2) {
                    uint32_t r[4];
                    ldsm4t(r, st + srow_a + (((cb + shi) ^ sx) << 4));
                    xt[cb * 8192] = r[0]; xt[cb * 8192 + 16] = r[1]; xt[cb * 8192 + 8192] = r[2]; xt[cb * 8192 + 8192 + 16] = r[3];
                }
                __syncwarp();
                if (lane == 0) mbar_arrive(bar + 8 * BAR_XT);
            }
            {
                uint32_t x0, x1, w0, w1;
                asm volatile("ld.shared.v2.b32 {%0,%1},[%2];" : "=r"(x0), "=r"(x1) : "r"(st + gx_a) : "memory");
                asm volatile("ld.shared.v2.b32 {%0,%1},[%2];" : "=r"(w0), "=r"(w1) : "r"(sb + OFF_GW + ((kb + rot) & 7) * 128 + (lane & 15) * 8) : "memory");
                const uint32_t p0 = hmul2(x0, w0), p1 = hmul2(x1, w1);
                gsum += (bf_lo(p0) + bf_hi(p0)) + (bf_lo(p1) + bf_hi(p1));
            }
        }
        wg_wait<0>();
        fence_regs<96>(acc);
        __syncwarp();
        if (lane == 0) mbar_arrive(bar + 8 * BAR_DONE);
        if (warp == 0) STAMP(1);
        uint32_t in[32], va[16];
#pragma unroll
        for (int r = 0; r < 16; r++) {
            in[r] = pack2(acc[32 + 2 * r], acc[32 + 2 * r + 1]);
            in[16 + r] = packi(acc[2 * r], acc[2 * r + 1]);
            va[r] = packi(acc[64 + 2 * r], acc[64 + 2 * r + 1]);
        }
        const uint32_t wphi_a = sb + OFF_WPHI + (lane & 15) * 32 + (lane >> 4) * 16;
        uint32_t pq[4][8];
#pragma unroll 1
        for (int it = 0; it < 4; it++) {
            hedgehog2(in, wphi_a + (it & 1) * 1024, pq + 2);
#pragma unroll
            for (int r = 0; r < 24; r++) in[r] = in[r + 8];
            if (it < 2) {
#pragma unroll
                for (int hs = 0; hs < 4; hs++) {
                    float c[4] = {0.f, 0.f, 0.f, 0.f};
                    uint32_t* o = pq[2 + (hs >> 1)] + 4 * (hs & 1);
                    mma16816(c, o[0], o[1], o[2], o[3], 0x3f803f80u, 0x3f803f80u);
                    const float r0 = rcp(c[0]), r1 = rcp(c[2]);
                    const uint32_t s0 = packi(r0, r0), s1 = packi(r1, r1);
                    o[0] = hmul2(o[0], s0); o[1] = hmul2(o[1], s1); o[2] = hmul2(o[2], s0); o[3] = hmul2(o[3], s1);
                }
                if (it == 0) mbar_wait(bar + 8 * BAR_DONE, 0);
                const uint32_t pt = sb + OFF_P + it * 16384 + srow_a, vt = sb + OFF_V + it * 16384 + srow_a;
#pragma unroll
                for (int hl = 0; hl < 2; hl++) {
                    stsm4(pt + (((4 * hl + shi) ^ sx) << 4), pq[2 + hl][0], pq[2 + hl][1], pq[2 + hl][2], pq[2 + hl][3]);
                    stsm4(pt + (((4 * hl + 2 + shi) ^ sx) << 4), pq[2 + hl][4], pq[2 + hl][5], pq[2 + hl][6], pq[2 + hl][7]);
                    stsm4(vt + (((2 * hl + shi) ^ sx) << 4), va[4 * hl], va[4 * hl + 1], va[4 * hl + 2], va[4 * hl + 3]);
                }
                if (lane < 16) sts128(vt + ((4 ^ sx) << 4), 0x3f803f80u, 0x3f803f80u, 0x3f803f80u, 0x3f803f80u);
#pragma unroll
                for (int r = 0; r < 8; r++) va[r] = va[r + 8];
            }
            if (it == 1) {
                asm volatile("fence.proxy.async.shared::cta;" ::: "memory");
                bar_named(1, 256);
                if (warp == 0) STAMP(2);
                float d[32];
                const uint64_t dv = mkdesc(sb + OFF_V + wg * 16384, 16, 1024), dp = mkdesc(sb + OFF_P + wg * 16384, 16, 1024);
                wg_fence();
#pragma unroll
                for (int k = 0; k < 8; k++) wgmma64_tt(d, dv + 128 * k, dp + 128 * k, k != 0);
                wg_commit();
                wg_wait<0>();
                fence_regs<32>(d);
                uint4* kvp = scr->kvp + bi * 544 + wg * 272;
                if (w4 < 2) {
                    uint32_t e[16];
#pragma unroll
                    for (int r = 0; r < 16; r++) e[r] = __float_as_uint(w4 ? d[16 + r] : d[r]);
                    uint4* p = kvp + w4 * 136 + lane;
#pragma unroll
                    for (int ks = 0; ks < 2; ks++)
#pragma unroll
                        for (int nt = 0; nt < 2; nt++)
                            st_rlx128(p + (ks * 2 + nt) * 32, tag4(e[8 * ks + 2 * nt], e[8 * ks + 2 * nt + 1], e[8 * ks + 4 + 2 * nt], e[8 * ks + 4 + 2 * nt + 1], tag));
                } else if (w4 == 2 && lane < 4) {
#pragma unroll
                    for (int hl = 0; hl < 2; hl++)
#pragma unroll
                        for (int ks = 0; ks < 2; ks++)
                            st_rlx128(kvp + hl * 136 + 128 + ks * 4 + lane, tag4(__float_as_uint(d[16 * hl + 8 * ks]), __float_as_uint(d[16 * hl + 8 * ks + 1]),
                                                                                __float_as_uint(d[16 * hl + 8 * ks + 4]), __float_as_uint(d[16 * hl + 8 * ks + 5]), tag));
                }
                if (warp == 0) STAMP(3);
            }
            if (it == 2) {
#pragma unroll
                for (int r = 0; r < 8; r++) { pq[0][r] = pq[2][r]; pq[1][r] = pq[3][r]; }
                if (warp == 0) STAMP(12);
                if (kvf_n) {
                    const bool zw = warp == 4;
                    const uint4* src = scr->kvp + bi_j * (16 * 544) + (bi_i >> 2) * 136 +
                                       (zw ? (lane >> 2) * (2 * 544) + 128 + (lane & 1) * 4 + qq
                                           : (lane >> 3) * (4 * 544) + ((lane >> 1) & 3) * 32 + (bi_i & 3) * 8 + warp * 2 + (lane & 1));
                    const int s23 = zw ? 0 : 2 * 544;
                    uint4 v[4];
                    int n = 0;
                    while (true) {
                        v[0] = ld_rlx128(src); v[1] = ld_rlx128(src + 544); v[2] = ld_rlx128(src + s23); v[3] = ld_rlx128(src + s23 + 544);
                        if (!__any_sync(~0u, (bad4(v[0], tag) | bad4(v[1], tag) | bad4(v[2], tag) | bad4(v[3], tag)) & 1)) break;
                        if (++n > SPIN_LIMIT) break;
                    }
                    float f[4];
                    f[0] = __uint_as_float(v[2].x) + __uint_as_float(v[3].x); f[1] = __uint_as_float(v[2].y) + __uint_as_float(v[3].y);
                    f[2] = __uint_as_float(v[2].z) + __uint_as_float(v[3].z); f[3] = __uint_as_float(v[2].w) + __uint_as_float(v[3].w);
                    float e0 = __uint_as_float(v[0].x) + __uint_as_float(v[1].x), e1 = __uint_as_float(v[0].y) + __uint_as_float(v[1].y);
                    float e2 = __uint_as_float(v[0].z) + __uint_as_float(v[1].z), e3 = __uint_as_float(v[0].w) + __uint_as_float(v[1].w);
                    if (zw) {
                        e0 = __shfl_xor_sync(~0u, f[0], 4); e1 = __shfl_xor_sync(~0u, f[1], 4);
                        e2 = __shfl_xor_sync(~0u, f[2], 4); e3 = __shfl_xor_sync(~0u, f[3], 4);
                    }
                    f[0] += e0; f[1] += e1; f[2] += e2; f[3] += e3;
#pragma unroll
                    for (int o = 8; o <= 16; o <<= 1)
#pragma unroll
                        for (int r = 0; r < 4; r++) f[r] += __shfl_xor_sync(~0u, f[r], o);
                    if (lane < kvf_n) st_rlx64(kvf_dst, tagw(pack2(f[0], f[1]), tag), pack2(f[2], f[3]));
                }
                __syncwarp();
                if (lane == 0 && last_of_8(4)) {
                    mbar_expect(bar + 8 * BAR_WO2, 65536);
                    tma2d(sb + 2 * SLOT, &mwo, (bi_j & 3) * 128, 256, bar + 8 * BAR_WO2);
                    tma2d(sb + 3 * SLOT, &mwo, (bi_j & 3) * 128 + 64, 256, bar + 8 * BAR_WO2);
                }
                __syncwarp();
                if (warp == 0) STAMP(13);
#pragma unroll
                for (int o = 1; o < 16; o <<= 1) gsum += __shfl_xor_sync(~0u, gsum, o);
                const float gate = bf_round(rcp(1.0f + ex2(-1.4426950408889634f * bf_round(gsum))));
                const uint32_t gv = __shfl_sync(~0u, __float_as_uint(gate) | tag, (lane & 4) * 4);
                if (lane < 8) st_rlx32(scr->g + (bi_i * 64 + bi_j * 8 + warp) * 8 + lane, gv);
            }
        }
        if (warp == 0) STAMP(4);
        {
            uint4 kf[4][3];
            const uint4* kp = scr->kvf + bi_j * 272;
            int n = 0;
            while (true) {
                uint32_t bad = 0;
#pragma unroll
                for (int hh = 0; hh < 4; hh++) {
                    kf[hh][0] = ld_rlx128(kp + hh * 68 + lane * 2); kf[hh][1] = ld_rlx128(kp + hh * 68 + lane * 2 + 1); kf[hh][2] = ld_rlx128(kp + hh * 68 + 64 + q);
                }
#pragma unroll
                for (int hh = 0; hh < 4; hh++) bad |= bad4(kf[hh][0], tag) | bad4(kf[hh][1], tag) | bad4(kf[hh][2], tag);
                if (!__any_sync(~0u, bad & 1)) break;
                if (++n > SPIN_LIMIT) break;
            }
            if (warp == 0) STAMP(5);
            uint4 own[4];
#pragma unroll
            for (int hh = 0; hh < 4; hh++) {
                float c[6][4];
#pragma unroll
                for (int t = 0; t < 6; t++) { c[t][0] = c[t][1] = c[t][2] = c[t][3] = 0.f; }
                const uint32_t* a = pq[hh];
                const bool od = g & 1;
                mma16816(c[0], a[0], a[1], a[2], a[3], od ? 0x3f803f80u : kf[hh][2].x, od ? 0x3f803f80u : kf[hh][2].y);
                mma16816(c[1], a[4], a[5], a[6], a[7], od ? 0x3f803f80u : kf[hh][2].z, od ? 0x3f803f80u : kf[hh][2].w);
                mma16816(c[2], a[0], a[1], a[2], a[3], kf[hh][0].x, kf[hh][0].y);
                mma16816(c[3], a[0], a[1], a[2], a[3], kf[hh][0].z, kf[hh][0].w);
                mma16816(c[4], a[4], a[5], a[6], a[7], kf[hh][1].x, kf[hh][1].y);
                mma16816(c[5], a[4], a[5], a[6], a[7], kf[hh][1].z, kf[hh][1].w);
                uint32_t w[4];
#pragma unroll
                for (int k = 0; k < 2; k++) {
                    const float rho = c[0][2 * k + 1] * rcp(c[1][2 * k + 1]);
                    const float r = rcp(fmaf(c[0][2 * k + 1], 1e-6f, fmaf(rho, c[1][2 * k], c[0][2 * k]))), rr = r * rho;
                    w[k] = packi(fmaf(c[4][2 * k], rr, c[2][2 * k] * r), fmaf(c[4][2 * k + 1], rr, c[2][2 * k + 1] * r));
                    w[2 + k] = packi(fmaf(c[5][2 * k], rr, c[3][2 * k] * r), fmaf(c[5][2 * k + 1], rr, c[3][2 * k + 1] * r));
                }
                own[hh] = tag4(w[0], w[1], w[2], w[3], tag);
            }
            uint4* og = scr->o + ((bi_i * 8 + warp) * 32 + bi_j * 4) * 32 + lane;
#pragma unroll
            for (int hh = 0; hh < 4; hh++) st_rlx128(og + hh * 32, own[hh]);
        }
        if (warp == 0) STAMP(6);
        float oc[64];
        const int slab = bi_i * 8 + (bi_j >> 2) * 4 + w4;
        const uint8_t* yb = (const uint8_t*)scr->y + (size_t)((bi_j & 3) * 32 + wg * 16 + (q >> 1)) * 16384 + slab * 128 + g * 16 + (q & 1) * 8;
        const unsigned* gp = scr->g + (slab * 8 + (g >> 1)) * 8 + (g & 1) * 4;
        uint2 yv[8]; unsigned g0, g1;
        {
            const uint4* osrc = scr->o + (slab * 32 + wg * 16) * 32 + lane;
            uint4 fr[16];
            {
                const unsigned* probe = (const unsigned*)(osrc - lane + ((lane & 3) * 4 + 3) * 32 + 31) + 2;
                int n = 0;
                while (__any_sync(~0u, (ld_rlx(probe) ^ tag) & 1)) { if (++n > SPIN_LIMIT) break; }
            }
            if (warp == 0) STAMP(14);
#pragma unroll
            for (int k = 0; k < 16; k++) fr[k] = ld_rlx128(osrc + k * 32);
            mbar_wait(bar + 8 * (wg ? BAR_WO2 : BAR_WO), 0);
            const uint64_t dw = mkdesc(sb + wg * 2 * SLOT, SLOT, 1024);
#pragma unroll
            for (int s = 0; s < 4; s++) {
                int n = 0;
                while (__any_sync(~0u, (bad4(fr[4 * s], tag) | bad4(fr[4 * s + 1], tag) | bad4(fr[4 * s + 2], tag) | bad4(fr[4 * s + 3], tag)) & 1)) {
#pragma unroll
                    for (int hh = 0; hh < 4; hh++) fr[4 * s + hh] = ld_rlx128(osrc + (4 * s + hh) * 32);
                    if (++n > SPIN_LIMIT) break;
                }
                wg_fence();
#pragma unroll
                for (int hh = 0; hh < 4; hh++) wgmma128_rs(oc, fr[4 * s + hh], dw + 128 * (4 * s + hh), (s | hh) != 0);
                wg_commit();
            }
            if (warp == 0) STAMP(7);
            {
                const unsigned* probe = scr->yflag + ((bi_j & 3) * 32 + wg * 16 + (lane & 15)) * 8;
                int n = 0;
                while (__any_sync(~0u, (ld_rlx(probe) ^ tag) & 1)) { if (++n > SPIN_LIMIT) break; }
            }
#pragma unroll
            for (int nt = 0; nt < 8; nt++) yv[nt] = ld_rlx64(yb + nt * 32768);
            g0 = ld_rlx(gp); g1 = ld_rlx(gp + 32);
            if (warp == 0) STAMP(28);
            wg_wait<0>();
            fence_regs<64>(oc);
        }
        {
            bar_named(3 + wg, 128);
            const uint32_t xw = sb + wg * 2 * SLOT + (tid & 127) * 16, xr = sb + (wg ^ 1) * 2 * SLOT + (tid & 127) * 16;
#pragma unroll
            for (int r = 0; r < 8; r++) {
                const float* o = oc + 4 * r;
                sts128(xw + r * 2048, __float_as_uint(wg ? o[0] : o[32]), __float_as_uint(wg ? o[1] : o[33]), __float_as_uint(wg ? o[2] : o[34]), __float_as_uint(wg ? o[3] : o[35]));
            }
#pragma unroll
            for (int r = 0; r < 32; r++) oc[r] = wg ? oc[32 + r] : oc[r];
            bar_named(1, 256);
            if (warp == 0) STAMP(8);
            int n = 0;
            while (true) {
                uint32_t bad = (g0 ^ tag) | (g1 ^ tag);
#pragma unroll
                for (int nt = 0; nt < 8; nt++) bad |= yv[nt].x ^ tag;
                if (!__any_sync(~0u, bad & 1)) break;
#pragma unroll
                for (int nt = 0; nt < 8; nt++) yv[nt] = ld_rlx64(yb + nt * 32768);
                g0 = ld_rlx(gp); g1 = ld_rlx(gp + 32);
                if (++n > SPIN_LIMIT) break;
            }
            if (warp == 0) STAMP(9);
            const float ga = bf_hi(g0), gb = bf_hi(g1);
            const float ha = bf_round(1.0f - ga), hb = bf_round(1.0f - gb);
            uint32_t w[8][2];
#pragma unroll
            for (int nt = 0; nt < 8; nt++) {
                const uint4 p = lds128(xr + nt * 2048);
                w[nt][0] = pack2(fmaf(ga, oc[4 * nt] + __uint_as_float(p.x), ha * bf_lo(yv[nt].x)), fmaf(ga, oc[4 * nt + 1] + __uint_as_float(p.y), ha * bf_hi(yv[nt].x)));
                w[nt][1] = pack2(fmaf(gb, oc[4 * nt + 2] + __uint_as_float(p.z), hb * bf_lo(yv[nt].y)), fmaf(gb, oc[4 * nt + 3] + __uint_as_float(p.w), hb * bf_hi(yv[nt].y)));
            }
            const uint32_t ob = sb + (2 + wg) * SLOT + 32768 + w4 * 2048;
#pragma unroll
            for (int nt = 0; nt < 8; nt += 2)
                stsm4(ob + (lane & 15) * 128 + (((nt + shi) ^ (lane & 7)) << 4), w[nt][0], w[nt][1], w[nt + 1][0], w[nt + 1][1]);
            __syncwarp();
            bf16* op = out + (size_t)(slab * 16) * 512 + (bi_j & 3) * 128 + wg * 64 + (lane & 7) * 8;
#pragma unroll
            for (int it = 0; it < 4; it++) {
                const int r = it * 4 + (lane >> 3);
                uint4 v = lds128(ob + r * 128 + (((lane & 7) ^ (r & 7)) << 4));
                *(uint4*)(op + r * 512) = v;
            }
        }
        if (warp == 0) STAMP(10);
    } else {
        const int st = tid - 256;
        const uint32_t ub = sb + OFF_U + w4 * U_STRIDE + 256;
        const uint32_t spare = sb + (w4 < 2 ? OFF_SP0 : OFF_SP1) + (w4 & 1) * 4096;
        if (warp == 8) STAMP(16);
        if (st < 8) st_rlx32(scr->yflag + bi * 8 + st, tag ^ 1u);
        if (lane == 0) kc[0][0] += (ch & 1) ? bf_hi(pds) : bf_lo(pds);
        const uint32_t k1024 = __shfl_sync(~0u, pack2(kc[4][0], 0.f), 0);
#pragma unroll
        for (int i = 0; i < 2; i++) {
            const int be = g + 8 * i;
#pragma unroll
            for (int t = 0; t < 2; t++) {
                const uint32_t a = kb_ + (KW_D + 128 * t + 8 * be + 2 * q) * 4;
                const uint32_t w = pack2(kc[t][2 * i + 1], kc[t][2 * i]);
                sts32(a + 4, w); sts16(a, w >> 16); sts16(a + 10, w);
            }
            {
                const int p = 256 + 128 * (q >> 1) + 8 * be + 4 * (q & 1);
                const uint32_t a = kb_ + (KW_D + p) * 4;
                const uint32_t w = pack2(kc[2][2 * i + 1], kc[2][2 * i]);
                const uint32_t aa = (w >> 16) | (w & 0xffff0000u);
                if (p != 256) { sts16(a - 4, aa); sts32(a, aa); } else sts16(a, aa);
                sts32(a + 4, aa); sts32(a + 8, w); sts16(a + 14, w);
            }
            {
                const int k = 64 + 16 * q + be;
                const uint32_t w = pack2(kc[3][2 * i], kc[3][2 * i + 1]);
                if (k != 64) sts16(kb_ + (KW_2 + ((k - 1) >> 1) - 24) * 4 + (k & 1) * 2, w);
                else {
                    const uint32_t a = kb_ + (KW_D + 511) * 4, aa = (w << 16) | (w & 0xffffu);
                    sts16(a, w); sts32(a + 4, aa); sts32(a + 8, aa); sts32(a + 12, aa); sts16(a + 18, w);
                }
                sts16(kb_ + (KW_2 + 48 + (k >> 1) - 24) * 4 + ((k & 1) ^ 1) * 2, w >> 16);
            }
#pragma unroll
            for (int b = 0; b < 2; b++) {
                const int k = 64 + 8 * (2 * q + b) + (be >> 1);
                const uint32_t w = pack2(kc[4][2 * i + b], 0.f);
                if (!(be & 1) && k == 64) sts16(kb_ + (KW_2 + 63 - 24) * 4, w);
                else {
                    const uint32_t a = kb_ + (KW_3 + ((be & 1) ? 80 + k : k - 1) - 48) * 4;
                    sts16(a, w);
                    if (!((be & 1) && k == 127)) sts16(a + 6, w);
                }
            }
        }
        if (lane == 0) sts16(kb_ + (KW_3 + 127 - 48) * 4, pack2(kc[5][0], 0.f));
        if (lane < 2) sts128(buf + lane * W3_OFF, 0, 0, 0, 0);
        if (lane < 16) sts128(ub - 256 + lane * 16, 0, 0, 0, 0);
        if (warp == 8) {
            mbar_wait(bar + 8 * BAR_XT, 0);
            if (lane == 0) asm volatile("red.release.gpu.global.add.u32 [%0],8;" ::"l"(scr->xcnt + ((bi_j >> 1) + rot) * 32) : "memory");
        }
        if (lane == 0) {
            int n = 0;
            while ((int)(ld_acq(scr->xcnt + bi_j * 32) - (epoch1 << 7)) < 0) { __nanosleep(200); if (++n > SPIN_LIMIT) break; }
        }
        __syncwarp();
        if (warp == 8) STAMP(15);
        {
            uint4 ur[8];
#pragma unroll
            for (int v = 0; v < 8; v++) ur[v] = __ldcg(scr->xt + bi * 1024 + st + 128 * v);
#pragma unroll
            for (int v = 0; v < 8; v++) {
                const int ci = (st >> 2) + 32 * v;
                sts128(sb + OFF_U + (st & 3) * U_STRIDE + 256 + ((ci ^ ((ci >> 3) & 1)) << 4), ur[v].x, ur[v].y, ur[v].z, ur[v].w);
            }
        }
        mbar_wait(bar + 8 * BAR_WO, 0);
        bar_named(2, 128);
        if (warp == 8) STAMP(17);
        float y[16][4];
#pragma unroll
        for (int nt = 0; nt < 16; nt++) { y[nt][0] = y[nt][1] = y[nt][2] = y[nt][3] = 0.f; }
        {
            uint32_t Bp[32];
            auto uaddr = [&](int rho) { const int R0 = (lane >> 4) * 8 + (lane & 7) - rho; return ub + (((2 * R0 + ((lane >> 3) & 1)) ^ ((R0 >> 2) & 1)) << 4); };
            const uint32_t kd = kb_ + (KW_D + g - 2 * q) * 4;
            {
                const uint32_t a = uaddr(0);
#pragma unroll
                for (int p = 0; p < 8; p++) ldsm4(Bp + 4 * p, a + p * 512);
            }
#pragma unroll 1
            for (int rho = 0; rho < 8; rho++) {
                uint32_t A[5][4];
#pragma unroll
                for (int ga = 0; ga < 5; ga++) {
                    const uint32_t a = kd + (ga < 4 ? rho : (rho & 1)) * 64 + ga * 512;
                    A[ga][0] = lds32(a); A[ga][1] = lds32(a + 32); A[ga][2] = lds32(a - 32); A[ga][3] = A[ga][0];
                }
                const int ci = lane + 32 * rho;
                uint4 e4[4];
#pragma unroll
                for (int v = 0; v < 4; v++) { const int cc = ci - 3 + v; e4[v] = lds128(ub + ((cc ^ ((cc >> 3) & 1)) << 4)); }
                float S[29];
                const uint32_t* ew = (const uint32_t*)e4;
                S[3] = 0.f;
#pragma unroll
                for (int k = 4; k <= 28; k++) S[k] = S[k - 1] + ((k & 1) ? bf_hi(ew[k >> 1]) : bf_lo(ew[k >> 1]));
                auto win = [&](int lo, int hi, uint32_t a, bool on) {
                    const uint32_t w0 = pack2(S[hi] - S[lo - 1], S[hi + 1] - S[lo]), w1 = pack2(S[hi + 2] - S[lo + 1], S[hi + 3] - S[lo + 2]);
                    const uint32_t w2 = pack2(S[hi + 4] - S[lo + 3], S[hi + 5] - S[lo + 4]), w3 = pack2(S[hi + 6] - S[lo + 5], S[hi + 7] - S[lo + 6]);
                    asm volatile("{.reg .pred p; setp.ne.b32 p,%5,0; @p st.shared.v4.b32 [%0],{%1,%2,%3,%4};}" ::"r"(a), "r"(w0), "r"(w1), "r"(w2), "r"(w3), "r"((int)on) : "memory");
                };
                const uint32_t sw = (ci ^ ((ci >> 3) & 1)) << 4;
#pragma unroll
                for (int nt = 0; nt < 16; nt++) mma16816v(y[nt], A[0][0], A[0][1], A[0][2], A[0][3], Bp[2 * nt], Bp[2 * nt + 1]);
                win(4, 12, buf + W9_OFF + sw, rho < 4);
#pragma unroll
                for (int nt = 1; nt < 16; nt++) mma16816v(y[nt], A[1][0], A[1][1], A[1][2], A[1][3], Bp[2 * (nt - 1)], Bp[2 * (nt - 1) + 1]);
                win(14, 18, buf + W5_OFF + 16 + ci * 16, rho < 6); win(13, 19, spare + sw, rho < 4);
                const uint32_t an = uaddr(rho + 1);
                ldsm4(Bp + 28, an + 7 * 512);
#pragma unroll
                for (int nt = 2; nt < 16; nt++) mma16816v(y[nt], A[2][0], A[2][1], A[2][2], A[2][3], Bp[2 * (nt - 2)], Bp[2 * (nt - 2) + 1]);
                win(19, 21, buf + W3_OFF + 16 + ci * 16, rho < 6); win(20, 21, spare + 2048 + sw, rho < 4);
                if (rho < 2) {
#pragma unroll
                    for (int nt = 4; nt < 16; nt++) mma16816v(y[nt], A[4][0], A[4][1], A[4][2], A[4][3], Bp[2 * (nt - 4)], Bp[2 * (nt - 4) + 1]);
                }
#pragma unroll
                for (int nt = 3; nt < 16; nt++) {
                    mma16816v(y[nt], A[3][0], A[3][1], A[3][2], A[3][3], Bp[2 * (nt - 3)], Bp[2 * (nt - 3) + 1]);
                    if ((nt & 1) == 0) ldsm4(Bp + 2 * (nt - 4), an + ((nt - 4) >> 1) * 512);
                    if (nt == 15) ldsm4(Bp + 24, an + 6 * 512);
                }
            }
        }
        __syncwarp();
        if (warp == 8) STAMP(18);
#pragma unroll 1
        for (int ph = 0; ph < 2; ph++) {
            uint32_t B[5][2];
            const uint32_t ka = kb_ + (KW_2 + ph * 48 + 8 + g - q) * 4;
#pragma unroll
            for (int dd = 0; dd < 5; dd++) { B[dd][0] = lds32(ka + dd * 32); B[dd][1] = lds32(ka + dd * 32 - 16); }
            const uint32_t wa = buf + ph * W3_OFF + ((lane & 7) + ((lane >> 3) & 1) + (lane >> 4) * 8) * 16;
#pragma unroll
            for (int s = 0; s < 12; s++) {
                uint32_t A[4];
                ldsm4t(A, wa + s * 256);
#pragma unroll
                for (int dd = 0; dd < 5; dd++)
                    if (s + 4 + dd < 16) mma16816(y[s + 4 + dd], A[0], A[1], A[2], A[3], B[dd][0], B[dd][1]);
            }
        }
        {
            const int ap = (lane & 7) + (lane >> 4) * 8;
            const uint32_t loff = ((2 * ap + ((lane >> 3) & 1)) ^ ((ap >> 2) & 1)) << 4;
#pragma unroll 1
            for (int ph = 0; ph < 2; ph++) {
                uint32_t B[8][2];
                const uint32_t wb = (ph ? spare : buf + W9_OFF) + loff;
                const uint32_t ka = kb_ + (KW_3 + ph * 80 + 16 + g - 2 * q) * 4;
#pragma unroll
                for (int dd = 0; dd < 8; dd++) { B[dd][0] = lds32(ka + dd * 32); B[dd][1] = lds32(ka + dd * 32 - 32); }
#pragma unroll
                for (int s = 0; s < 4; s++) {
                    uint32_t A[4];
                    ldsm4t(A, wb + s * 512);
#pragma unroll
                    for (int dd = 0; dd < 8; dd++)
                        if (8 + 2 * s + dd < 16) mma16816(y[8 + 2 * s + dd], A[0], A[1], A[2], A[3], B[dd][0], B[dd][1]);
                }
            }
            const uint32_t idw = (g == 2 * q) ? k1024 : ((g == 2 * q + 1) ? (k1024 << 16) : 0u);
#pragma unroll
            for (int s = 0; s < 4; s++) {
                uint32_t A[4];
                ldsm4t(A, spare + 2048 + loff + s * 512);
                mma16816(y[8 + 2 * s], A[0], A[1], A[2], A[3], idw, 0u);
                mma16816(y[9 + 2 * s], A[0], A[1], A[2], A[3], 0u, idw);
            }
        }
        __syncwarp();
        if (warp == 8) STAMP(19);
#pragma unroll
        for (int nt = 0; nt < 16; nt++)
#pragma unroll
            for (int b = 0; b < 2; b++) sts32(buf + ((8 * nt + 2 * q + b) * 8 + g) * 4, pack2(y[nt][b], y[nt][2 + b]));
        bar_named(2, 128);
        uint4* yp = scr->y + bi * 1024 + st;
#pragma unroll
        for (int v = 0; v < 8; v++) {
            const uint32_t a = sb + OFF_BUF + (st + 128 * v) * 4;
            const uint32_t w0 = lds32(a), w1 = lds32(a + BUF_STRIDE), w2 = lds32(a + 2 * BUF_STRIDE), w3 = lds32(a + 3 * BUF_STRIDE);
            st_rlx128(yp + v * 128, tag4(__byte_perm(w0, w1, 0x5410), __byte_perm(w0, w1, 0x7632), __byte_perm(w2, w3, 0x5410), __byte_perm(w2, w3, 0x7632), tag));
        }
        if (st < 8) st_rlx32(scr->yflag + bi * 8 + st, tag);
        if (warp == 8) STAMP(20);
    }
    __syncthreads();
    if (tid == 0) atomicAdd(scr->done, 1u);
}

typedef CUresult (*EncFn)(CUtensorMap*, CUtensorMapDataType, cuuint32_t, void*, const cuuint64_t*, const cuuint64_t*, const cuuint32_t*,
                          const cuuint32_t*, CUtensorMapInterleave, CUtensorMapSwizzle, CUtensorMapL2promotion, CUtensorMapFloatOOBfill);

extern "C" void kernel_launch(void* const* d_in, const int* in_sizes, int n_in, void* d_out, int out_size) {
    static EncFn enc = nullptr;
    static Scratch* scr = nullptr;
    if (!enc) {
        cudaGetSymbolAddress((void**)&scr, g_scr);
        cudaDriverEntryPointQueryResult qr;
        cudaGetDriverEntryPoint("cuTensorMapEncodeTiled", (void**)&enc, cudaEnableDefault, &qr);
        cudaFuncSetAttribute(fused_kernel, cudaFuncAttributeMaxDynamicSharedMemorySize, SMEM_BYTES);
    }
    CUtensorMap mx, mw, mwo;
    const cuuint32_t es[3] = {1, 1, 1};
    {
        cuuint64_t d[2] = {512, 2048}, s[1] = {1024}; cuuint32_t b[2] = {64, 128};
        enc(&mx, CU_TENSOR_MAP_DATA_TYPE_BFLOAT16, 2, d_in[0], d, s, b, es, CU_TENSOR_MAP_INTERLEAVE_NONE, CU_TENSOR_MAP_SWIZZLE_128B,
            CU_TENSOR_MAP_L2_PROMOTION_L2_128B, CU_TENSOR_MAP_FLOAT_OOB_FILL_NONE);
    }
    {
        cuuint64_t d[3] = {512, 512, 3}, s[2] = {3072, 1024}; cuuint32_t b[3] = {64, 64, 3};
        enc(&mw, CU_TENSOR_MAP_DATA_TYPE_BFLOAT16, 3, d_in[1], d, s, b, es, CU_TENSOR_MAP_INTERLEAVE_NONE, CU_TENSOR_MAP_SWIZZLE_128B,
            CU_TENSOR_MAP_L2_PROMOTION_L2_128B, CU_TENSOR_MAP_FLOAT_OOB_FILL_NONE);
    }
    {
        cuuint64_t d[2] = {512, 512}, s[1] = {1024}; cuuint32_t b[2] = {64, 256};
        enc(&mwo, CU_TENSOR_MAP_DATA_TYPE_BFLOAT16, 2, d_in[3], d, s, b, es, CU_TENSOR_MAP_INTERLEAVE_NONE, CU_TENSOR_MAP_SWIZZLE_128B,
            CU_TENSOR_MAP_L2_PROMOTION_L2_128B, CU_TENSOR_MAP_FLOAT_OOB_FILL_NONE);
    }
    fused_kernel<<<128, 384, SMEM_BYTES, cudaStreamPerThread>>>(
        scr, (const bf16*)d_in[5], (const bf16*)d_in[6], (const bf16*)d_in[7], (const bf16*)d_in[8], (const bf16*)d_in[9],
        (const bf16*)d_in[10], (const bf16*)d_in[2], (const bf16*)d_in[11], (bf16*)d_out, mx, mw, mwo);
}
```

```cpp
#include <cuda_runtime.h>
#include <cuda.h>
#include <cuda_bf16.h>
#include <stdint.h>

typedef __nv_bfloat16 bf16;

struct Scratch {
    uint4 xt[128 * 1024];
    uint4 o[16 * 8 * 32 * 32];
    uint4 y[128 * 1024];
    uint4 kvp[8 * 16 * 544];
    uint4 kvf[8 * 4 * 68];
    unsigned g[1024 * 8];
    unsigned yflag[128 * 8];
    unsigned xcnt[8 * 32];
    unsigned done[32];
};
__device__ Scratch g_scr;
#define STAMP(n)

constexpr int SLOT = 40960;
constexpr int OFF_SP0 = 32768, OFF_SP1 = SLOT + 32768;
constexpr int OFF_P = 2 * SLOT, OFF_V = OFF_P + 32768;
constexpr int OFF_KT = OFF_V + 32768, KT_STRIDE = 3936, KT_E2 = 2688 + 240, KT_E2O = 496;
constexpr int OFF_U = 4 * SLOT, U_STRIDE = 41 * 128, U_PAD = 9 * 128;
constexpr int OFF_BUF = OFF_U + 4 * U_STRIDE, BUF_STRIDE = 8448;
constexpr int OFF_K3 = OFF_BUF + 4 * BUF_STRIDE, K3_STRIDE = 1136;
constexpr int OFF_WPHI = OFF_K3 + 4 * K3_STRIDE;
constexpr int OFF_GW = OFF_WPHI + 2048;
constexpr int OFF_KVF = OFF_GW + 1024;
constexpr int OFF_BAR = OFF_KVF + 4352;
constexpr int SMEM_BYTES = OFF_BAR + 128 + 128;
static_assert(SMEM_BYTES <= 232448 && OFF_BUF % 128 == 0 && OFF_KT + 4 * KT_STRIDE <= 4 * SLOT && 3 * SLOT + 7 * 7296 + 8192 <= OFF_BUF, "smem");
constexpr int W5_OFF = 0, W3_OFF = 3184, W9_OFF = 6368;
constexpr int BAR_FULL = 0, BAR_WPHI = 4, BAR_WO = 5, BAR_XT = 6, BAR_DONE = 7, BAR_WO2 = 8, BAR_KG = 9, OFF_CNT = 96;
constexpr int SPIN_LIMIT = 1 << 17;

__device__ __forceinline__ uint32_t s2u(const void* p) { return (uint32_t)__cvta_generic_to_shared(p); }
__device__ __forceinline__ void mbar_init(uint32_t b, int c) { asm volatile("mbarrier.init.shared::cta.b64 [%0],%1;" ::"r"(b), "r"(c) : "memory"); }
__device__ __forceinline__ void mbar_expect(uint32_t b, int bytes) { asm volatile("mbarrier.arrive.expect_tx.shared::cta.b64 _,[%0],%1;" ::"r"(b), "r"(bytes) : "memory"); }
__device__ __forceinline__ void mbar_arrive(uint32_t b) { asm volatile("mbarrier.arrive.shared::cta.b64 _,[%0];" ::"r"(b) : "memory"); }
__device__ __forceinline__ bool mbar_try(uint32_t b, int ph) {
    uint32_t ok;
    asm volatile("{.reg .pred p; mbarrier.try_wait.parity.shared::cta.b64 p,[%1],%2; selp.u32 %0,1,0,p;}" : "=r"(ok) : "r"(b), "r"(ph) : "memory");
    return ok;
}
__device__ __forceinline__ void mbar_wait(uint32_t b, int ph) {
    if ((threadIdx.x & 31) == 0) { int n = 0; while (!mbar_try(b, ph)) { if (++n > SPIN_LIMIT) break; } }
    __syncwarp();
}
__device__ __forceinline__ void tma2d(uint32_t dst, const CUtensorMap* m, int c0, int c1, uint32_t bar) {
    asm volatile("cp.async.bulk.tensor.2d.shared::cluster.global.mbarrier::complete_tx::bytes [%0],[%1,{%3,%4}],[%2];" ::"r"(dst), "l"(m), "r"(bar), "r"(c0), "r"(c1) : "memory");
}
__device__ __forceinline__ void tma3d(uint32_t dst, const CUtensorMap* m, int c0, int c1, int c2, uint32_t bar) {
    asm volatile("cp.async.bulk.tensor.3d.shared::cluster.global.mbarrier::complete_tx::bytes [%0],[%1,{%3,%4,%5}],[%2];" ::"r"(dst), "l"(m), "r"(bar), "r"(c0), "r"(c1), "r"(c2) : "memory");
}
__device__ __forceinline__ void bulk_g2s(uint32_t dst, const void* src, int bytes, uint32_t bar) {
    asm volatile("cp.async.bulk.shared::cluster.global.mbarrier::complete_tx::bytes [%0],[%1],%2,[%3];" ::"r"(dst), "l"(src), "r"(bytes), "r"(bar) : "memory");
}
__device__ __forceinline__ uint64_t mkdesc(uint32_t addr, uint32_t lbo, uint32_t sbo) {
    return (uint64_t)((addr & 0x3FFFF) >> 4) | ((uint64_t)(lbo >> 4) << 16) | ((uint64_t)(sbo >> 4) << 32) | ((uint64_t)1 << 62);
}
__device__ __forceinline__ void wg_fence() { asm volatile("wgmma.fence.sync.aligned;" ::: "memory"); }
__device__ __forceinline__ void wg_commit() { asm volatile("wgmma.commit_group.sync.aligned;" ::: "memory"); }
template <int N> __device__ __forceinline__ void wg_wait() { asm volatile("wgmma.wait_group.sync.aligned %0;" ::"n"(N) : "memory"); }
template <int N> __device__ __forceinline__ void fence_regs(float* d) {
#pragma unroll
    for (int i = 0; i < N; i++) asm volatile("" : "+f"(d[i])::"memory");
}
#define R8(d, o) "+f"(d[o]), "+f"(d[o + 1]), "+f"(d[o + 2]), "+f"(d[o + 3]), "+f"(d[o + 4]), "+f"(d[o + 5]), "+f"(d[o + 6]), "+f"(d[o + 7])
__device__ __forceinline__ void wgmma192(float* d, uint64_t da, uint64_t db) {
    asm volatile("wgmma.mma_async.sync.aligned.m64n192k16.f32.bf16.bf16 {"
                 "%0,%1,%2,%3,%4,%5,%6,%7,%8,%9,%10,%11,%12,%13,%14,%15,%16,%17,%18,%19,%20,%21,%22,%23,%24,%25,%26,%27,%28,%29,%30,%31,"
                 "%32,%33,%34,%35,%36,%37,%38,%39,%40,%41,%42,%43,%44,%45,%46,%47,%48,%49,%50,%51,%52,%53,%54,%55,%56,%57,%58,%59,%60,%61,%62,%63,"
                 "%64,%65,%66,%67,%68,%69,%70,%71,%72,%73,%74,%75,%76,%77,%78,%79,%80,%81,%82,%83,%84,%85,%86,%87,%88,%89,%90,%91,%92,%93,%94,%95},"
                 "%96,%97,1,1,1,0,1;"
                 : R8(d, 0), R8(d, 8), R8(d, 16), R8(d, 24), R8(d, 32), R8(d, 40), R8(d, 48), R8(d, 56), R8(d, 64), R8(d, 72), R8(d, 80), R8(d, 88)
                 : "l"(da), "l"(db));
}
__device__ __forceinline__ void wgmma64_tt(float* d, uint64_t da, uint64_t db, int sc) {
    asm volatile("{.reg .pred p; setp.ne.b32 p,%34,0; wgmma.mma_async.sync.aligned.m64n64k16.f32.bf16.bf16 {"
                 "%0,%1,%2,%3,%4,%5,%6,%7,%8,%9,%10,%11,%12,%13,%14,%15,%16,%17,%18,%19,%20,%21,%22,%23,%24,%25,%26,%27,%28,%29,%30,%31},"
                 "%32,%33,p,1,1,1,1;}"
                 : R8(d, 0), R8(d, 8), R8(d, 16), R8(d, 24)
                 : "l"(da), "l"(db), "r"(sc));
}
__device__ __forceinline__ void wgmma128_rs(float* d, const uint4& a, uint64_t db, int sc) {
    asm volatile("{.reg .pred p; setp.ne.b32 p,%69,0; wgmma.mma_async.sync.aligned.m64n128k16.f32.bf16.bf16 {"
                 "%0,%1,%2,%3,%4,%5,%6,%7,%8,%9,%10,%11,%12,%13,%14,%15,%16,%17,%18,%19,%20,%21,%22,%23,%24,%25,%26,%27,%28,%29,%30,%31,"
                 "%32,%33,%34,%35,%36,%37,%38,%39,%40,%41,%42,%43,%44,%45,%46,%47,%48,%49,%50,%51,%52,%53,%54,%55,%56,%57,%58,%59,%60,%61,%62,%63},"
                 "{%64,%65,%66,%67},%68,p,1,1,1;}"
                 : R8(d, 0), R8(d, 8), R8(d, 16), R8(d, 24), R8(d, 32), R8(d, 40), R8(d, 48), R8(d, 56)
                 : "r"(a.x), "r"(a.y), "r"(a.z), "r"(a.w), "l"(db), "r"(sc));
}
__device__ __forceinline__ void wgmma32_rs(float* d, const uint32_t* a, uint64_t db) {
    asm volatile("wgmma.mma_async.sync.aligned.m64n32k16.f32.bf16.bf16 {%0,%1,%2,%3,%4,%5,%6,%7,%8,%9,%10,%11,%12,%13,%14,%15},{%16,%17,%18,%19},%20,1,1,1,0;"
                 : R8(d, 0), R8(d, 8) : "r"(a[0]), "r"(a[1]), "r"(a[2]), "r"(a[3]), "l"(db));
}
__device__ __forceinline__ void wgmma24_rs(float* d, const uint32_t* a, uint64_t db) {
    asm volatile("wgmma.mma_async.sync.aligned.m64n24k16.f32.bf16.bf16 {%0,%1,%2,%3,%4,%5,%6,%7,%8,%9,%10,%11},{%12,%13,%14,%15},%16,1,1,1,0;"
                 : R8(d, 0), "+f"(d[8]), "+f"(d[9]), "+f"(d[10]), "+f"(d[11]) : "r"(a[0]), "r"(a[1]), "r"(a[2]), "r"(a[3]), "l"(db));
}
__device__ __forceinline__ void mma16816(float* c, uint32_t a0, uint32_t a1, uint32_t a2, uint32_t a3, uint32_t b0, uint32_t b1) {
    asm("mma.sync.aligned.m16n8k16.row.col.f32.bf16.bf16.f32 {%0,%1,%2,%3},{%4,%5,%6,%7},{%8,%9},{%0,%1,%2,%3};"
        : "+f"(c[0]), "+f"(c[1]), "+f"(c[2]), "+f"(c[3]) : "r"(a0), "r"(a1), "r"(a2), "r"(a3), "r"(b0), "r"(b1));
}
__device__ __forceinline__ void ldsm4(uint32_t* r, uint32_t a) {
    asm volatile("ldmatrix.sync.aligned.m8n8.x4.shared.b16 {%0,%1,%2,%3},[%4];" : "=r"(r[0]), "=r"(r[1]), "=r"(r[2]), "=r"(r[3]) : "r"(a) : "memory");
}
__device__ __forceinline__ void ldsm4t(uint32_t* r, uint32_t a) {
    asm volatile("ldmatrix.sync.aligned.m8n8.x4.trans.shared.b16 {%0,%1,%2,%3},[%4];" : "=r"(r[0]), "=r"(r[1]), "=r"(r[2]), "=r"(r[3]) : "r"(a) : "memory");
}
__device__ __forceinline__ void stsm4(uint32_t a, uint32_t r0, uint32_t r1, uint32_t r2, uint32_t r3) {
    asm volatile("stmatrix.sync.aligned.m8n8.x4.shared.b16 [%0],{%1,%2,%3,%4};" ::"r"(a), "r"(r0), "r"(r1), "r"(r2), "r"(r3) : "memory");
}
__device__ __forceinline__ uint32_t lds32(uint32_t a) { uint32_t v; asm volatile("ld.shared.b32 %0,[%1];" : "=r"(v) : "r"(a) : "memory"); return v; }
__device__ __forceinline__ uint4 lds128(uint32_t a) { uint4 v; asm volatile("ld.shared.v4.b32 {%0,%1,%2,%3},[%4];" : "=r"(v.x), "=r"(v.y), "=r"(v.z), "=r"(v.w) : "r"(a) : "memory"); return v; }
__device__ __forceinline__ void sts16(uint32_t a, uint32_t v) { asm volatile("st.shared.b16 [%0],%1;" ::"r"(a), "h"((unsigned short)v) : "memory"); }
__device__ __forceinline__ void sts32(uint32_t a, uint32_t v) { asm volatile("st.shared.b32 [%0],%1;" ::"r"(a), "r"(v) : "memory"); }
__device__ __forceinline__ void sts64(uint32_t a, uint32_t x, uint32_t y) { asm volatile("st.shared.v2.b32 [%0],{%1,%2};" ::"r"(a), "r"(x), "r"(y) : "memory"); }
__device__ __forceinline__ void sts128(uint32_t a, uint32_t x, uint32_t y, uint32_t z, uint32_t w) { asm volatile("st.shared.v4.b32 [%0],{%1,%2,%3,%4};" ::"r"(a), "r"(x), "r"(y), "r"(z), "r"(w) : "memory"); }
__device__ __forceinline__ uint32_t pack2(float lo, float hi) { uint32_t d; asm("cvt.rn.bf16x2.f32 %0,%1,%2;" : "=r"(d) : "f"(hi), "f"(lo)); return d; }
__device__ __forceinline__ float bf_lo(uint32_t v) { return __uint_as_float(v << 16); }
__device__ __forceinline__ float bf_hi(uint32_t v) { return __uint_as_float(v & 0xffff0000u); }
__device__ __forceinline__ float bf_round(float v) { return bf_lo(pack2(v, 0.f)); }
__device__ __forceinline__ uint32_t hmax2(uint32_t a, uint32_t b) { uint32_t d; asm("max.bf16x2 %0,%1,%2;" : "=r"(d) : "r"(a), "r"(b)); return d; }
__device__ __forceinline__ uint32_t hmin2(uint32_t a, uint32_t b) { uint32_t d; asm("min.bf16x2 %0,%1,%2;" : "=r"(d) : "r"(a), "r"(b)); return d; }
__device__ __forceinline__ uint32_t hmul2(uint32_t a, uint32_t b) { uint32_t d; asm("mul.rn.bf16x2 %0,%1,%2;" : "=r"(d) : "r"(a), "r"(b)); return d; }
__device__ __forceinline__ float ex2(float x) { float y; asm("ex2.approx.ftz.f32 %0,%1;" : "=f"(y) : "f"(x)); return y; }
__device__ __forceinline__ float rcp(float x) { float y; asm("rcp.approx.ftz.f32 %0,%1;" : "=f"(y) : "f"(x)); return y; }
__device__ __forceinline__ uint32_t ld_nc(const uint32_t* p) { uint32_t v; asm volatile("ld.global.nc.b32 %0,[%1];" : "=r"(v) : "l"(p)); return v; }
__device__ __forceinline__ uint2 ld_nc64(const uint2* p) { uint2 v; asm volatile("ld.global.nc.v2.b32 {%0,%1},[%2];" : "=r"(v.x), "=r"(v.y) : "l"(p)); return v; }
__device__ __forceinline__ unsigned ld_acq(const unsigned* p) { unsigned v; asm volatile("ld.acquire.gpu.global.u32 %0,[%1];" : "=r"(v) : "l"(p) : "memory"); return v; }
__device__ __forceinline__ unsigned ld_rlx(const unsigned* p) { unsigned v; asm volatile("ld.relaxed.gpu.global.u32 %0,[%1];" : "=r"(v) : "l"(p) : "memory"); return v; }
__device__ __forceinline__ uint2 ld_rlx64(const void* p) { uint2 v; asm volatile("{.reg .b64 t; ld.relaxed.gpu.global.b64 t,[%2]; mov.b64 {%0,%1},t;}" : "=r"(v.x), "=r"(v.y) : "l"(p) : "memory"); return v; }
__device__ __forceinline__ uint4 ld_rlx128(const void* p) {
    uint4 v;
    asm volatile("{.reg .b64 t,u; ld.relaxed.gpu.global.v2.b64 {t,u},[%4]; mov.b64 {%0,%1},t; mov.b64 {%2,%3},u;}" : "=r"(v.x), "=r"(v.y), "=r"(v.z), "=r"(v.w) : "l"(p) : "memory");
    return v;
}
__device__ __forceinline__ void st_rlx32(void* p, uint32_t x) { asm volatile("st.relaxed.gpu.global.u32 [%0],%1;" ::"l"(p), "r"(x) : "memory"); }
__device__ __forceinline__ void st_rlx64(void* p, uint32_t x, uint32_t y) { asm volatile("{.reg .b64 t; mov.b64 t,{%1,%2}; st.relaxed.gpu.global.b64 [%0],t;}" ::"l"(p), "r"(x), "r"(y) : "memory"); }
__device__ __forceinline__ void st_rlx128(void* p, uint4 v) {
    asm volatile("{.reg .b64 t,u; mov.b64 t,{%1,%2}; mov.b64 u,{%3,%4}; st.relaxed.gpu.global.v2.b64 [%0],{t,u};}" ::"l"(p), "r"(v.x), "r"(v.y), "r"(v.z), "r"(v.w) : "memory");
}
__device__ __forceinline__ uint32_t tagw(uint32_t w, uint32_t tag) { return (w & ~1u) | tag; }
__device__ __forceinline__ uint4 tag4(uint32_t x, uint32_t y, uint32_t z, uint32_t w, uint32_t tag) { return make_uint4(tagw(x, tag), y, tagw(z, tag), w); }
__device__ __forceinline__ uint32_t bad4(const uint4& v, uint32_t tag) { return (v.x ^ tag) | (v.z ^ tag); }
__device__ __forceinline__ void bar_named(int id, int n) { asm volatile("bar.sync %0,%1;" ::"r"(id), "r"(n) : "memory"); }

struct cf { float re, im; };
__device__ __forceinline__ cf cmul(cf a, cf b) { cf r; r.re = a.re * b.re - a.im * b.im; r.im = a.re * b.im + a.im * b.re; return r; }
__device__ __forceinline__ cf cexp_p(float arl, float ait, float p) {
    float mag = ex2(arl * p);
    float t = ait * p;
    t = (t - rintf(t)) * 6.283185307179586f;
    cf r; r.re = mag * __cosf(t); r.im = mag * __sinf(t);
    return r;
}

__device__ __forceinline__ void hedgehog2(const uint32_t* a, uint32_t wphi_addr, uint32_t (*out)[8]) {
    float p[2][2][4], mx[2][2];
#pragma unroll
    for (int h = 0; h < 2; h++) {
        uint32_t b[4];
        ldsm4t(b, wphi_addr + h * 512);
        float c0[4] = {0.f, 0.f, 0.f, 0.f}, c1[4] = {0.f, 0.f, 0.f, 0.f};
        mma16816(c0, a[4 * h], a[4 * h + 1], a[4 * h + 2], a[4 * h + 3], b[0], b[1]);
        mma16816(c1, a[4 * h], a[4 * h + 1], a[4 * h + 2], a[4 * h + 3], b[2], b[3]);
#pragma unroll
        for (int k = 0; k < 2; k++) {
            p[h][k][0] = c0[2 * k]; p[h][k][1] = c0[2 * k + 1]; p[h][k][2] = c1[2 * k]; p[h][k][3] = c1[2 * k + 1];
            mx[h][k] = fmaxf(fmaxf(p[h][k][0], p[h][k][1]), fmaxf(p[h][k][2], p[h][k][3]));
        }
    }
#pragma unroll
    for (int o = 1; o <= 2; o <<= 1)
#pragma unroll
        for (int h = 0; h < 2; h++)
#pragma unroll
            for (int k = 0; k < 2; k++) mx[h][k] = fmaxf(mx[h][k], __shfl_xor_sync(~0u, mx[h][k], o));
    const float L = 1.4426950408889634f;
    float pmin = 1.f;
#pragma unroll
    for (int h = 0; h < 2; h++)
#pragma unroll
        for (int k = 0; k < 2; k++) {
            const float m = -mx[h][k] * L;
            const float e0 = ex2(fmaf(p[h][k][0], L, m)), e1 = ex2(fmaf(p[h][k][1], L, m)), e2 = ex2(fmaf(p[h][k][2], L, m)), e3 = ex2(fmaf(p[h][k][3], L, m));
            const float p01 = e0 * e1, p23 = e2 * e3, pp = p01 * p23, r = rcp(pp), r01 = r * p23, r23 = r * p01;
            pmin = fminf(pmin, pp);
            out[h][k] = pack2(e0, e1); out[h][k + 2] = pack2(e2, e3);
            out[h][4 + k] = pack2(r01 * e1, r01 * e0); out[h][4 + k + 2] = pack2(r23 * e3, r23 * e2);
        }
    if (__any_sync(~0u, !(pmin > 1e-18f))) {
#pragma unroll
        for (int h = 0; h < 2; h++)
#pragma unroll
            for (int k = 0; k < 2; k++) {
                float m = fminf(fminf(p[h][k][0], p[h][k][1]), fminf(p[h][k][2], p[h][k][3]));
                m = fminf(m, __shfl_xor_sync(~0u, m, 1));
                m = fminf(m, __shfl_xor_sync(~0u, m, 2)) * L;
                out[h][4 + k] = pack2(ex2(fmaf(p[h][k][0], -L, m)), ex2(fmaf(p[h][k][1], -L, m)));
                out[h][4 + k + 2] = pack2(ex2(fmaf(p[h][k][2], -L, m)), ex2(fmaf(p[h][k][3], -L, m)));
            }
    }
}

__global__ void __launch_bounds__(384, 1)
fused_kernel(Scratch* __restrict__ scr, const bf16* __restrict__ logA, const bf16* __restrict__ Aim, const bf16* __restrict__ Cre,
             const bf16* __restrict__ Cim, const bf16* __restrict__ logdt, const bf16* __restrict__ Dskip, const bf16* __restrict__ wphi,
             const bf16* __restrict__ gatew, bf16* __restrict__ out,
             const __grid_constant__ CUtensorMap mx, const __grid_constant__ CUtensorMap mw, const __grid_constant__ CUtensorMap mwo) {
    extern __shared__ __align__(1024) uint8_t smem[];
    const uint32_t sb = s2u(smem);
    const int tid = threadIdx.x, warp = __shfl_sync(~0u, tid >> 5, 0), lane = tid & 31;
    const int g = lane >> 2, q = lane & 3, w4 = warp & 3;
    const int bi = blockIdx.x, bi_i = bi & 15, bi_j = bi >> 4;
    const uint32_t bar = sb + OFF_BAR;
    const int rot = (bi_j & 1) * 4;
    auto load_stage = [&](int kb) {
        const uint32_t b = bar + 8 * (BAR_FULL + (kb & 3)), d = sb + (kb & 3) * SLOT;
        const int kc = ((kb + rot) & 7) * 64;
        mbar_expect(b, SLOT);
        tma2d(d, &mx, kc, bi_i * 128, b);
        tma3d(d + 16384, &mw, bi_j * 64, kc, 0, b);
    };

    const int ch = bi * 4 + w4;
    const int pidx = ch * 64 + lane * 2 + (warp < 8);
    const uint32_t pla = ld_nc((const uint32_t*)logA + pidx), pai = ld_nc((const uint32_t*)Aim + pidx);
    const uint32_t pcr = ld_nc((const uint32_t*)Cre + pidx), pci = ld_nc((const uint32_t*)Cim + pidx);
    uint32_t pdt = ld_nc((const uint32_t*)logdt + (ch >> 1));
    const uint32_t pds = ld_nc((const uint32_t*)Dskip + (ch >> 1));
    const unsigned done0 = ld_rlx(scr->done);
    if (tid == 0) {
        for (int s = 0; s < 4; s++) mbar_init(bar + 8 * (BAR_FULL + s), 1);
        asm volatile("fence.mbarrier_init.release.cluster;" ::: "memory");
#pragma unroll 1
        for (int s = 0; s < 3; s++) load_stage(s);
        STAMP(11);
    } else if (tid == 32) {
        if (sb & 1023) __trap();
        for (int s = 0; s < 5; s++) sts32(bar + OFF_CNT + 4 * s, 0);
        mbar_init(bar + 8 * BAR_WPHI, 1); mbar_init(bar + 8 * BAR_WO, 2); mbar_init(bar + 8 * BAR_XT, 8); mbar_init(bar + 8 * BAR_DONE, 8);
        mbar_init(bar + 8 * BAR_WO2, 1); mbar_init(bar + 8 * BAR_KG, 8);
        asm volatile("fence.mbarrier_init.release.cluster;" ::: "memory");
        mbar_expect(bar + 8 * BAR_WPHI, 3072);
        bulk_g2s(sb + OFF_GW, gatew, 1024, bar + 8 * BAR_WPHI);
        bulk_g2s(sb + OFF_WPHI, wphi + bi_j * 1024, 2048, bar + 8 * BAR_WPHI);
    } else if (tid == 64) {
        asm volatile("prefetch.tensormap [%0];" ::"l"(&mw) : "memory");
    }
    const uint32_t buf = sb + OFF_BUF + w4 * BUF_STRIDE, k3 = sb + OFF_K3 + w4 * K3_STRIDE;
    if (warp >= 8) {
#pragma unroll
        for (int v = 0; v < 3; v++) if (v * 32 + lane < K3_STRIDE / 16) sts128(k3 + (v * 32 + lane) * 16, 0, 0, 0, 0);
    }
    __syncthreads();
    asm volatile("" : "+r"(pdt));
    const unsigned epoch1 = (done0 >> 7) + 1u;
    const uint32_t tag = epoch1 & 1u;

    const int st = tid - 256;
    float kc[6][4];
#pragma unroll
    for (int t = 0; t < 6; t++) { kc[t][0] = kc[t][1] = kc[t][2] = kc[t][3] = 0.f; }
    {
        const float dt = bf_round(expf((ch & 1) ? bf_hi(pdt) : bf_lo(pdt)));
        const uint32_t stg = (warp < 8) ? sb + 3 * SLOT + warp * 7296 : buf;
#pragma unroll 1
        for (int it = 0; it < 2; it++) {
            {
                const int sh = (warp < 8 ? (warp >> 2) : it) * 16;
                auto pick = [&](uint32_t v) { return __uint_as_float((v >> sh) << 16); };
                const float ea = bf_round(expf(pick(pla)));
                const float arl = (-ea * dt) * 1.4426950408889634f, ait = (pick(pai) * dt) * 0.15915494309189535f;
                cf C2; C2.re = 2.0f * (pick(pcr) * dt); C2.im = 2.0f * (pick(pci) * dt);
                const cf z1 = cexp_p(arl, ait, 1.0f), z128 = cexp_p(arl, ait, 128.0f);
                cf z8 = cexp_p(arl, ait, 8.0f); z8.im = -z8.im;
                const uint32_t lp = stg + lane * 4;
                auto put = [&](int row, const cf& v) { sts32((lp ^ ((row & 7) << 4)) + row * 128, pack2(v.re, v.im)); };
                {
                    const cf z16 = cmul(z8, z8);
                    cf e; e.re = 1.f; e.im = 0.f;
                    cf o = z8;
                    put(0, e); put(1, o);
                    e = z16; put(2, e);
#pragma unroll
                    for (int b = 3; b < 16; b += 2) {
                        o = cmul(o, z16); put(b, o);
                        if (b + 1 < 16) { e = cmul(e, z16); put(b + 1, e); }
                    }
                }
                cf h[8];
                h[0] = C2; put(16, h[0]);
                {
                    const cf z2 = cmul(z1, z1);
                    h[1] = cmul(h[0], z1);
#pragma unroll
                    for (int r = 2; r < 8; r++) h[r] = cmul(h[r - 2], z2);
#pragma unroll
                    for (int r = 1; r < 8; r++) put(16 + r, h[r]);
                }
#pragma unroll
                for (int r = 0; r < 8; r++) { h[r] = cmul(h[r], z128); put(24 + r, h[r]); }
#pragma unroll
                for (int al = 0; al < 2; al++)
#pragma unroll
                    for (int r = 0; r < 4; r++) { h[2 * r] = cmul(h[2 * r], z128); put(32 + al * 4 + r, h[2 * r]); }
#pragma unroll
                for (int al = 0; al < 4; al++)
#pragma unroll
                    for (int r = 0; r < 2; r++) { h[4 * r] = cmul(h[4 * r], z128); put(40 + al * 2 + r, h[4 * r]); }
#pragma unroll
                for (int al = 0; al < 9; al++) { h[0] = cmul(h[0], z128); put(48 + al, h[0]); }
                __syncwarp();
            }
            if (it == 1) {
                if (warp == 8) {
                    mbar_wait(bar + 8 * BAR_XT, 0);
                    if (lane == 0) asm volatile("red.release.gpu.global.add.u32 [%0],8;" ::"l"(scr->xcnt + ((bi_j >> 1) + rot) * 32) : "memory");
                }
                if (lane == 0) {
                    int n = 0;
                    while ((int)(ld_acq(scr->xcnt + bi_j * 32) - (epoch1 << 7)) < 0) { __nanosleep(200); if (++n > SPIN_LIMIT) break; }
                }
                __syncwarp();
                if (warp == 8) STAMP(15);
                uint4 ur[8];
#pragma unroll
                for (int v = 0; v < 8; v++) ur[v] = __ldcg(scr->xt + bi * 1024 + st + 128 * v);
#pragma unroll
                for (int v = 0; v < 3; v++) if (v * 32 + lane < U_PAD / 16) sts128(sb + OFF_U + w4 * U_STRIDE + (v * 32 + lane) * 16, 0, 0, 0, 0);
                if (st < 8) st_rlx32(scr->yflag + bi * 8 + st, tag ^ 1u);
#pragma unroll
                for (int v = 0; v < 8; v++) {
                    const uint32_t a = sb + OFF_U + (st & 3) * U_STRIDE + U_PAD + ((st >> 2) + 32 * v) * 16;
                    sts128(a ^ ((a >> 3) & 0x70), ur[v].x, ur[v].y, ur[v].z, ur[v].w);
                }
                if (warp == 8) STAMP(16);
                mbar_wait(bar + 8 * BAR_DONE, 0);
            }
            const int lr = lane & 7, lm = lane >> 3;
#pragma unroll
            for (int kp = 0; kp < 2; kp++) {
                uint32_t a0[4], a1[4];
                ldsm4(a0, stg + ((lm & 1) * 8 + lr) * 128 + (((4 * kp + (lm >> 1)) ^ lr) << 4));
                ldsm4(a1, stg + ((lm & 1) * 8 + lr) * 128 + (((4 * kp + 2 + (lm >> 1)) ^ lr) << 4));
#pragma unroll
                for (int t = 0; t < 6; t++) {
                    uint32_t b[4];
                    ldsm4(b, stg + (16 + 8 * t + lr) * 128 + (((4 * kp + lm) ^ lr) << 4));
                    mma16816(kc[t], a0[0], a0[1], a0[2], a0[3], b[0], b[1]);
                    mma16816(kc[t], a1[0], a1[1], a1[2], a1[3], b[2], b[3]);
                }
            }
            __syncwarp();
            if (it == 0) {
                if (warp < 8) {
#pragma unroll
                    for (int t = 0; t < 6; t++)
                        sts128(stg + (t * 32 + lane) * 16, __float_as_uint(kc[t][0]), __float_as_uint(kc[t][1]), __float_as_uint(kc[t][2]), __float_as_uint(kc[t][3]));
                    __syncwarp();
                    if (lane == 0) mbar_arrive(bar + 8 * BAR_KG);
                    break;
                }
                mbar_wait(bar + 8 * BAR_KG, 0);
#pragma unroll
                for (int t = 0; t < 12; t++) {
                    const uint4 v = lds128(sb + 3 * SLOT + (w4 + (t / 6) * 4) * 7296 + ((t % 6) * 32 + lane) * 16);
                    kc[t % 6][0] += __uint_as_float(v.x); kc[t % 6][1] += __uint_as_float(v.y); kc[t % 6][2] += __uint_as_float(v.z); kc[t % 6][3] += __uint_as_float(v.w);
                }
                asm volatile("fence.proxy.async.shared::cta;" ::: "memory");
                bar_named(2, 128);
                if (st == 0) load_stage(3);
                if (warp == 8) STAMP(22);
            }
        }
    }

    if (warp < 8) {
        const int wg = warp >> 2;
        if (warp == 0) STAMP(21);
        float acc[96];
        const int grow = bi_j * 16 + warp * 2 + (lane >> 4);
        const uint32_t gx_a = grow * 128 + ((((lane & 15) >> 1) ^ (grow & 7)) << 4) + (lane & 1) * 8;
        const int srow = warp * 16 + (lane & 15);
        const uint32_t srow_a = srow * 128;
        const int sx = srow & 7, shi = lane >> 4;
        auto last_of_8 = [&](int c) {
            unsigned old;
            asm volatile("atom.acq_rel.cta.shared.add.u32 %0,[%1],1;" : "=r"(old) : "r"(bar + OFF_CNT + 4 * c) : "memory");
            return (old & 7) == 7;
        };
        const int qq = (bi_i & 2) + ((lane >> 1) & 1);
        const int kvf_n = warp < 4 ? 8 : ((warp == 4 && (bi_i & 1) == 0) ? 4 : 0);
        uint2* kvf_dst = (uint2*)(scr->kvf + (bi_j * 4 + (bi_i >> 2)) * 68) +
                         (warp == 4 ? (64 + qq) * 2 + (lane & 1) : ((bi_i & 3) * 8 + w4 * 2 + (lane & 1)) * 4 + (lane >> 1));
        float gsum = 0.f;
#pragma unroll
        for (int r = 0; r < 96; r++) acc[r] = 0.f;
        fence_regs<96>(acc);
        const uint64_t da0 = mkdesc(sb + wg * 8192, 16, 1024), db0 = mkdesc(sb + 16384, 8192, 1024);
        {
            const uint32_t old = tag ^ 1u;
            const uint4 z4 = make_uint4(old, 0, old, 0);
            uint4* kvp = scr->kvp + bi * 544 + wg * 272;
            if (w4 < 2) {
#pragma unroll
                for (int f = 0; f < 4; f++) st_rlx128(kvp + w4 * 136 + lane + f * 32, z4);
            } else if (w4 == 2 && lane < 4) {
#pragma unroll
                for (int f = 0; f < 4; f++) st_rlx128(kvp + (f >> 1) * 136 + 128 + (f & 1) * 4 + lane, z4);
            }
            if (lane < kvf_n) st_rlx64(kvf_dst, old, 0);
            if (lane >= 30) st_rlx128(scr->o + ((bi_i * 8 + warp) * 32 + bi_j * 4 + 3) * 32 + lane, z4);
            if (lane < 8) st_rlx32(scr->g + (bi_i * 64 + bi_j * 8 + warp) * 8 + lane, old);
        }
        mbar_wait(bar + 8 * BAR_WPHI, 0);
#pragma unroll 1
        for (int kb = 0; kb < 8; kb++) {
            const int s = kb & 3;
            const uint64_t da = da0 + s * (SLOT >> 4), db = db0 + s * (SLOT >> 4);
            mbar_wait(bar + 8 * (BAR_FULL + s), kb >> 2);
            if (kb == 0 && warp == 0) STAMP(0);
            wg_fence();
#pragma unroll
            for (int k = 0; k < 4; k++) wgmma192(acc, da + 2 * k, db + 128 * k);
            wg_commit();
            wg_wait<1>();
            __syncwarp();
            if (lane == 0 && kb > 0 && kb < 7) {
                const int ps = (kb - 1) & 3;
                if (last_of_8(ps)) {
                    if (kb < 5) load_stage(kb + 3);
                    else {
                        mbar_expect(bar + 8 * BAR_WO, 32768);
                        tma2d(sb + ps * SLOT, &mwo, (bi_j & 3) * 128 + ps * 64, 0, bar + 8 * BAR_WO);
                    }
                }
            }
            __syncwarp();
            const uint32_t st = sb + s * SLOT;
            if (kb == (bi_j >> 1)) {
                uint32_t* xt = (uint32_t*)scr->xt + ((kb + rot) * 16 + (g >> 2)) * 4096 + (bi_i * 16 + warp * 2) * 16 + (g & 3) * 4 + q;
#pragma unroll
                for (int cb = 0; cb < 8; cb += 2) {
                    uint32_t r[4];
                    ldsm4t(r, st + srow_a + (((cb + shi) ^ sx) << 4));
                    xt[cb * 8192] = r[0]; xt[cb * 8192 + 16] = r[1]; xt[cb * 8192 + 8192] = r[2]; xt[cb * 8192 + 8192 + 16] = r[3];
                }
                __syncwarp();
                if (lane == 0) mbar_arrive(bar + 8 * BAR_XT);
            }
            {
                uint32_t x0, x1, w0, w1;
                asm volatile("ld.shared.v2.b32 {%0,%1},[%2];" : "=r"(x0), "=r"(x1) : "r"(st + gx_a) : "memory");
                asm volatile("ld.shared.v2.b32 {%0,%1},[%2];" : "=r"(w0), "=r"(w1) : "r"(sb + OFF_GW + ((kb + rot) & 7) * 128 + (lane & 15) * 8) : "memory");
                const uint32_t p0 = hmul2(x0, w0), p1 = hmul2(x1, w1);
                gsum += (bf_lo(p0) + bf_hi(p0)) + (bf_lo(p1) + bf_hi(p1));
            }
        }
        wg_wait<0>();
        fence_regs<96>(acc);
        __syncwarp();
        if (lane == 0) mbar_arrive(bar + 8 * BAR_DONE);
        if (warp == 0) STAMP(1);
        uint32_t in[32], va[16];
#pragma unroll
        for (int r = 0; r < 16; r++) {
            in[r] = pack2(acc[32 + 2 * r], acc[32 + 2 * r + 1]);
            in[16 + r] = pack2(acc[2 * r], acc[2 * r + 1]);
            va[r] = pack2(acc[64 + 2 * r], acc[64 + 2 * r + 1]);
        }
        const uint32_t wphi_a = sb + OFF_WPHI + (lane & 15) * 32 + (lane >> 4) * 16;
        uint32_t pq[4][8];
#pragma unroll 1
        for (int it = 0; it < 4; it++) {
            hedgehog2(in, wphi_a + (it & 1) * 1024, pq + 2);
#pragma unroll
            for (int r = 0; r < 24; r++) in[r] = in[r + 8];
            if (it < 2) {
#pragma unroll
                for (int hs = 0; hs < 4; hs++) {
                    float c[4] = {0.f, 0.f, 0.f, 0.f};
                    uint32_t* o = pq[2 + (hs >> 1)] + 4 * (hs & 1);
                    mma16816(c, o[0], o[1], o[2], o[3], 0x3f803f80u, 0x3f803f80u);
                    const float r0 = rcp(c[0]), r1 = rcp(c[2]);
                    const uint32_t s0 = pack2(r0, r0), s1 = pack2(r1, r1);
                    o[0] = hmul2(o[0], s0); o[1] = hmul2(o[1], s1); o[2] = hmul2(o[2], s0); o[3] = hmul2(o[3], s1);
                }
                if (it == 0) mbar_wait(bar + 8 * BAR_DONE, 0);
                const uint32_t pt = sb + OFF_P + it * 16384 + srow_a, vt = sb + OFF_V + it * 16384 + srow_a;
#pragma unroll
                for (int hl = 0; hl < 2; hl++) {
                    stsm4(pt + (((4 * hl + shi) ^ sx) << 4), pq[2 + hl][0], pq[2 + hl][1], pq[2 + hl][2], pq[2 + hl][3]);
                    stsm4(pt + (((4 * hl + 2 + shi) ^ sx) << 4), pq[2 + hl][4], pq[2 + hl][5], pq[2 + hl][6], pq[2 + hl][7]);
                    stsm4(vt + (((2 * hl + shi) ^ sx) << 4), va[4 * hl], va[4 * hl + 1], va[4 * hl + 2], va[4 * hl + 3]);
                }
                if (lane < 16) sts128(vt + ((4 ^ sx) << 4), 0x3f803f80u, 0x3f803f80u, 0x3f803f80u, 0x3f803f80u);
#pragma unroll
                for (int r = 0; r < 8; r++) va[r] = va[r + 8];
            }
            if (it == 1) {
                asm volatile("fence.proxy.async.shared::cta;" ::: "memory");
                bar_named(1, 256);
                if (warp == 0) STAMP(2);
                float d[32];
                const uint64_t dv = mkdesc(sb + OFF_V + wg * 16384, 16, 1024), dp = mkdesc(sb + OFF_P + wg * 16384, 16, 1024);
                wg_fence();
#pragma unroll
                for (int k = 0; k < 8; k++) wgmma64_tt(d, dv + 128 * k, dp + 128 * k, k != 0);
                wg_commit();
                wg_wait<0>();
                fence_regs<32>(d);
                uint4* kvp = scr->kvp + bi * 544 + wg * 272;
                if (w4 < 2) {
                    uint32_t e[16];
#pragma unroll
                    for (int r = 0; r < 16; r++) e[r] = __float_as_uint(w4 ? d[16 + r] : d[r]);
                    uint4* p = kvp + w4 * 136 + lane;
#pragma unroll
                    for (int ks = 0; ks < 2; ks++)
#pragma unroll
                        for (int nt = 0; nt < 2; nt++)
                            st_rlx128(p + (ks * 2 + nt) * 32, tag4(e[8 * ks + 2 * nt], e[8 * ks + 2 * nt + 1], e[8 * ks + 4 + 2 * nt], e[8 * ks + 4 + 2 * nt + 1], tag));
                } else if (w4 == 2 && lane < 4) {
#pragma unroll
                    for (int hl = 0; hl < 2; hl++)
#pragma unroll
                        for (int ks = 0; ks < 2; ks++)
                            st_rlx128(kvp + hl * 136 + 128 + ks * 4 + lane, tag4(__float_as_uint(d[16 * hl + 8 * ks]), __float_as_uint(d[16 * hl + 8 * ks + 1]),
                                                                                __float_as_uint(d[16 * hl + 8 * ks + 4]), __float_as_uint(d[16 * hl + 8 * ks + 5]), tag));
                }
                if (warp == 0) STAMP(3);
            }
            if (it == 2) {
#pragma unroll
                for (int r = 0; r < 8; r++) { pq[0][r] = pq[2][r]; pq[1][r] = pq[3][r]; }
                if (warp == 0) STAMP(12);
                if (kvf_n) {
                    const bool zw = warp == 4;
                    const uint4* src = scr->kvp + bi_j * (16 * 544) + (bi_i >> 2) * 136 +
                                       (zw ? (lane >> 2) * (2 * 544) + 128 + (lane & 1) * 4 + qq
                                           : (lane >> 3) * (4 * 544) + ((lane >> 1) & 3) * 32 + (bi_i & 3) * 8 + warp * 2 + (lane & 1));
                    const int s23 = zw ? 0 : 2 * 544;
                    uint4 v[4];
                    int n = 0;
                    while (true) {
                        v[0] = ld_rlx128(src); v[1] = ld_rlx128(src + 544); v[2] = ld_rlx128(src + s23); v[3] = ld_rlx128(src + s23 + 544);
                        if (!__any_sync(~0u, (bad4(v[0], tag) | bad4(v[1], tag) | bad4(v[2], tag) | bad4(v[3], tag)) & 1)) break;
                        if (++n > SPIN_LIMIT) break;
                    }
                    float f[4];
                    f[0] = __uint_as_float(v[2].x) + __uint_as_float(v[3].x); f[1] = __uint_as_float(v[2].y) + __uint_as_float(v[3].y);
                    f[2] = __uint_as_float(v[2].z) + __uint_as_float(v[3].z); f[3] = __uint_as_float(v[2].w) + __uint_as_float(v[3].w);
                    float e0 = __uint_as_float(v[0].x) + __uint_as_float(v[1].x), e1 = __uint_as_float(v[0].y) + __uint_as_float(v[1].y);
                    float e2 = __uint_as_float(v[0].z) + __uint_as_float(v[1].z), e3 = __uint_as_float(v[0].w) + __uint_as_float(v[1].w);
                    if (zw) {
                        e0 = __shfl_xor_sync(~0u, f[0], 4); e1 = __shfl_xor_sync(~0u, f[1], 4);
                        e2 = __shfl_xor_sync(~0u, f[2], 4); e3 = __shfl_xor_sync(~0u, f[3], 4);
                    }
                    f[0] += e0; f[1] += e1; f[2] += e2; f[3] += e3;
#pragma unroll
                    for (int o = 8; o <= 16; o <<= 1)
#pragma unroll
                        for (int r = 0; r < 4; r++) f[r] += __shfl_xor_sync(~0u, f[r], o);
                    if (lane < kvf_n) st_rlx64(kvf_dst, tagw(pack2(f[0], f[1]), tag), pack2(f[2], f[3]));
                }
                __syncwarp();
                if (lane == 0 && last_of_8(4)) {
                    mbar_expect(bar + 8 * BAR_WO2, 65536);
                    tma2d(sb + 2 * SLOT, &mwo, (bi_j & 3) * 128, 256, bar + 8 * BAR_WO2);
                    tma2d(sb + OFF_V, &mwo, (bi_j & 3) * 128 + 64, 256, bar + 8 * BAR_WO2);
                }
                __syncwarp();
                if (warp == 0) STAMP(13);
#pragma unroll
                for (int o = 1; o < 16; o <<= 1) gsum += __shfl_xor_sync(~0u, gsum, o);
                const float gate = bf_round(rcp(1.0f + ex2(-1.4426950408889634f * bf_round(gsum))));
                const uint32_t gv = __shfl_sync(~0u, __float_as_uint(gate) | tag, (lane & 4) * 4);
                if (lane < 8) st_rlx32(scr->g + (bi_i * 64 + bi_j * 8 + warp) * 8 + lane, gv);
            }
        }
        if (warp == 0) STAMP(4);
        {
            {
                const uint4* kp = scr->kvf + bi_j * 272 + tid;
                uint4 v0, v1;
                int n = 0;
                while (true) {
                    v0 = ld_rlx128(kp); v1 = ld_rlx128(kp + (tid < 16 ? 256 : 0));
                    if (!__any_sync(~0u, (bad4(v0, tag) | bad4(v1, tag)) & 1)) break;
                    if (++n > SPIN_LIMIT) break;
                }
                sts128(sb + OFF_KVF + tid * 16, v0.x, v0.y, v0.z, v0.w);
                if (tid < 16) sts128(sb + OFF_KVF + 4096 + tid * 16, v1.x, v1.y, v1.z, v1.w);
                bar_named(1, 256);
            }
            uint4 kf[4][3];
#pragma unroll
            for (int hh = 0; hh < 4; hh++) {
                const uint32_t a = sb + OFF_KVF + hh * 1088;
                kf[hh][0] = lds128(a + lane * 32); kf[hh][1] = lds128(a + lane * 32 + 16); kf[hh][2] = lds128(a + 1024 + q * 16);
            }
            if (warp == 0) STAMP(5);
            uint4 own[4];
#pragma unroll
            for (int hh = 0; hh < 4; hh++) {
                float c[6][4];
#pragma unroll
                for (int t = 0; t < 6; t++) { c[t][0] = c[t][1] = c[t][2] = c[t][3] = 0.f; }
                const uint32_t* a = pq[hh];
                const bool od = g & 1;
                mma16816(c[0], a[0], a[1], a[2], a[3], od ? 0x3f803f80u : kf[hh][2].x, od ? 0x3f803f80u : kf[hh][2].y);
                mma16816(c[1], a[4], a[5], a[6], a[7], od ? 0x3f803f80u : kf[hh][2].z, od ? 0x3f803f80u : kf[hh][2].w);
                mma16816(c[2], a[0], a[1], a[2], a[3], kf[hh][0].x, kf[hh][0].y);
                mma16816(c[3], a[0], a[1], a[2], a[3], kf[hh][0].z, kf[hh][0].w);
                mma16816(c[4], a[4], a[5], a[6], a[7], kf[hh][1].x, kf[hh][1].y);
                mma16816(c[5], a[4], a[5], a[6], a[7], kf[hh][1].z, kf[hh][1].w);
                uint32_t w[4];
#pragma unroll
                for (int k = 0; k < 2; k++) {
                    const float rho = c[0][2 * k + 1] * rcp(c[1][2 * k + 1]);
                    const float r = rcp(fmaf(c[0][2 * k + 1], 1e-6f, fmaf(rho, c[1][2 * k], c[0][2 * k]))), rr = r * rho;
                    w[k] = pack2(fmaf(c[4][2 * k], rr, c[2][2 * k] * r), fmaf(c[4][2 * k + 1], rr, c[2][2 * k + 1] * r));
                    w[2 + k] = pack2(fmaf(c[5][2 * k], rr, c[3][2 * k] * r), fmaf(c[5][2 * k + 1], rr, c[3][2 * k + 1] * r));
                }
                own[hh] = tag4(w[0], w[1], w[2], w[3], tag);
            }
            uint4* og = scr->o + ((bi_i * 8 + warp) * 32 + bi_j * 4) * 32 + lane;
#pragma unroll
            for (int hh = 0; hh < 4; hh++) st_rlx128(og + hh * 32, own[hh]);
        }
        if (warp == 0) STAMP(6);
        float oc[64];
        const int slab = bi_i * 8 + (bi_j >> 2) * 4 + w4;
        const uint8_t* yb = (const uint8_t*)scr->y + (size_t)((bi_j & 3) * 32 + wg * 16 + (q >> 1)) * 16384 + slab * 128 + g * 16 + (q & 1) * 8;
        const unsigned* gp = scr->g + (slab * 8 + (g >> 1)) * 8 + (g & 1) * 4;
        uint2 yv[8]; unsigned g0, g1;
        {
            const uint4* osrc = scr->o + (slab * 32 + wg * 16) * 32 + lane;
            uint4 fr[16];
            const unsigned* probe = (const unsigned*)(osrc - lane + ((lane & 3) * 4 + 3) * 32 + 31) + 2;
#pragma unroll
            for (int k = 0; k < 16; k++) fr[k] = ld_rlx128(osrc + k * 32);
            mbar_wait(bar + 8 * (wg ? BAR_WO2 : BAR_WO), 0);
            const uint64_t dw = mkdesc(sb + wg * 2 * SLOT, wg ? 32768 : SLOT, 1024);
            if (warp == 0) STAMP(14);
#pragma unroll
            for (int s = 0; s < 4; s++) {
                int n = 0;
                while (__any_sync(~0u, (bad4(fr[4 * s], tag) | bad4(fr[4 * s + 1], tag) | bad4(fr[4 * s + 2], tag) | bad4(fr[4 * s + 3], tag)) & 1)) {
                    while ((__ballot_sync(~0u, (ld_rlx(probe) ^ tag) & 1) >> s) & 1) { if (++n > SPIN_LIMIT) break; }
#pragma unroll
                    for (int k = 4 * s; k < 16; k++) if (bad4(fr[k], tag) & 1) fr[k] = ld_rlx128(osrc + k * 32);
                    if (++n > SPIN_LIMIT) break;
                }
                wg_fence();
#pragma unroll
                for (int hh = 0; hh < 4; hh++) wgmma128_rs(oc, fr[4 * s + hh], dw + 128 * (4 * s + hh), (s | hh) != 0);
                wg_commit();
                if (s == 1) {
                    wg_wait<1>();
#pragma unroll
                    for (int nt = 0; nt < 8; nt++) yv[nt] = ld_rlx64(yb + nt * 32768);
                    g0 = ld_rlx(gp); g1 = ld_rlx(gp + 32);
                }
            }
            if (warp == 0) STAMP(7);
            {
                const unsigned* yprobe = scr->yflag + ((bi_j & 3) * 32 + wg * 16 + (lane & 15)) * 8;
                int n = 0;
                while (true) {
                    uint32_t bad = (g0 ^ tag) | (g1 ^ tag);
#pragma unroll
                    for (int nt = 0; nt < 8; nt++) bad |= yv[nt].x ^ tag;
                    if (!__any_sync(~0u, bad & 1)) break;
                    while (__any_sync(~0u, (ld_rlx(yprobe) ^ tag) & 1)) { if (++n > SPIN_LIMIT) break; }
#pragma unroll
                    for (int nt = 0; nt < 8; nt++) yv[nt] = ld_rlx64(yb + nt * 32768);
                    g0 = ld_rlx(gp); g1 = ld_rlx(gp + 32);
                    if (++n > SPIN_LIMIT) break;
                }
            }
            if (warp == 0) STAMP(28);
            wg_wait<0>();
            fence_regs<64>(oc);
        }
        {
            bar_named(3 + wg, 128);
            const uint32_t xw = sb + wg * 2 * SLOT + (tid & 127) * 16, xr = sb + (wg ^ 1) * 2 * SLOT + (tid & 127) * 16;
#pragma unroll
            for (int r = 0; r < 8; r++) {
                const float* o = oc + 4 * r;
                sts128(xw + r * 2048, __float_as_uint(wg ? o[0] : o[32]), __float_as_uint(wg ? o[1] : o[33]), __float_as_uint(wg ? o[2] : o[34]), __float_as_uint(wg ? o[3] : o[35]));
            }
#pragma unroll
            for (int r = 0; r < 32; r++) oc[r] = wg ? oc[32 + r] : oc[r];
            bar_named(1, 256);
            if (warp == 0) STAMP(8);
            const float ga = bf_hi(g0), gb = bf_hi(g1);
            const float ha = bf_round(1.0f - ga), hb = bf_round(1.0f - gb);
            uint32_t w[8][2];
#pragma unroll
            for (int nt = 0; nt < 8; nt++) {
                const uint4 p = lds128(xr + nt * 2048);
                w[nt][0] = pack2(fmaf(ga, oc[4 * nt] + __uint_as_float(p.x), ha * bf_lo(yv[nt].x)), fmaf(ga, oc[4 * nt + 1] + __uint_as_float(p.y), ha * bf_hi(yv[nt].x)));
                w[nt][1] = pack2(fmaf(gb, oc[4 * nt + 2] + __uint_as_float(p.z), hb * bf_lo(yv[nt].y)), fmaf(gb, oc[4 * nt + 3] + __uint_as_float(p.w), hb * bf_hi(yv[nt].y)));
            }
            const uint32_t ob = sb + wg * 2 * SLOT + 16384 + w4 * 2048;
#pragma unroll
            for (int nt = 0; nt < 8; nt += 2)
                stsm4(ob + (lane & 15) * 128 + (((nt + shi) ^ (lane & 7)) << 4), w[nt][0], w[nt][1], w[nt + 1][0], w[nt + 1][1]);
            __syncwarp();
            bf16* op = out + (size_t)(slab * 16) * 512 + (bi_j & 3) * 128 + wg * 64 + (lane & 7) * 8;
#pragma unroll
            for (int it = 0; it < 4; it++) {
                const int r = it * 4 + (lane >> 3);
                uint4 v = lds128(ob + r * 128 + (((lane & 7) ^ (r & 7)) << 4));
                *(uint4*)(op + r * 512) = v;
            }
        }
        if (warp == 0) STAMP(10);
    } else {
        const uint32_t kt = sb + OFF_KT + w4 * KT_STRIDE;
        const uint32_t spare = sb + (w4 < 2 ? OFF_SP0 : OFF_SP1) + (w4 & 1) * 4096;
#pragma unroll
        for (int v = 0; v < 8; v++) if (v * 32 + lane < KT_STRIDE / 16) sts128(kt + (v * 32 + lane) * 16, 0, 0, 0, 0);
        if (lane < 14) sts128(buf + (lane >= 7 ? W3_OFF - 112 : 0) + lane * 16, 0, 0, 0, 0);
        __syncwarp();
        if (lane == 0) kc[0][0] += (ch & 1) ? bf_hi(pds) : bf_lo(pds);
#pragma unroll
        for (int i = 0; i < 2; i++) {
            const int be = g + 8 * i;
#pragma unroll
            for (int t = 0; t < 2; t++) {
                const uint32_t a = kt + (64 + 128 * t + 8 * be + 2 * q) * 4;
                const uint32_t w = pack2(kc[t][2 * i + 1], kc[t][2 * i]);
                sts32(a + 4, w); sts16(a, w >> 16); sts16(a + 10, w);
            }
            {
                const int p = 256 + 128 * (q >> 1) + 8 * be + 4 * (q & 1);
                const uint32_t a = kt + (64 + p) * 4;
                const uint32_t w = pack2(kc[2][2 * i + 1], kc[2][2 * i]);
                const uint32_t aa = (w >> 16) | (w & 0xffff0000u);
                if (p != 256) { sts16(a - 4, aa); sts32(a, aa); } else sts16(a, aa);
                sts32(a + 4, aa); sts32(a + 8, w); sts16(a + 14, w);
            }
            {
                const int k = 64 + 16 * q + be;
                const uint32_t w = pack2(kc[3][2 * i], kc[3][2 * i + 1]);
                if (k != 64) sts16(kt + KT_E2 + (k - 1) * 2, w);
                else {
                    const uint32_t a = kt + (64 + 511) * 4, aa = (w << 16) | (w & 0xffffu);
                    sts16(a, w); sts32(a + 4, aa); sts32(a + 8, aa); sts32(a + 12, aa); sts16(a + 18, w);
                }
                sts16(kt + KT_E2 + KT_E2O + k * 2, w >> 16);
            }
#pragma unroll
            for (int b = 0; b < 2; b++) {
                const int k = 64 + 8 * (2 * q + b) + (be >> 1);
                const uint32_t w = pack2(kc[4][2 * i + b], 0.f);
                const bool k1024 = !(be & 1) && k == 64;
                const uint32_t a = k3 + (k1024 ? 188 + 64 : ((be & 1) ? 94 + k : k - 1)) * 4 - 34 * 4;
                sts16(a, w);
                if (!((be & 1) && k == 127)) sts16(a + 6, w);
                if (k1024) sts16(kt + KT_E2 + 127 * 2, w);
            }
        }
        if (lane == 0) sts16(k3 + (127 - 34) * 4, pack2(kc[5][0], 0.f));
        asm volatile("fence.proxy.async.shared::cta;" ::: "memory");
        bar_named(2, 128);
        if (warp == 8) STAMP(17);
        float y[4][16];
#pragma unroll
        for (int c = 0; c < 4; c++) {
#pragma unroll
            for (int r = 0; r < 16; r++) y[c][r] = 0.f;
            fence_regs<16>(y[c]);
        }
        {
            uint32_t Q[2][4][4];
            uint32_t ka = sb + OFF_KT + (64 - 48 + 16 * w4 + g - 2 * q) * 4;
            uint64_t du = mkdesc(sb + OFF_U + U_PAD + 96, 16, 1024);
            auto ldq = [&](uint32_t (*qd)[4]) {
#pragma unroll
                for (int c = 0; c < 4; c++) {
                    qd[c][0] = lds32(ka + c * KT_STRIDE); qd[c][1] = lds32(ka + c * KT_STRIDE + 32); qd[c][2] = lds32(ka + c * KT_STRIDE - 32); qd[c][3] = qd[c][0];
                }
                ka += 64;
            };
            ldq(Q[0]);
#pragma unroll 1
            for (int it = 0; it < 19; it++) {
#pragma unroll
                for (int hb = 0; hb < 2; hb++) {
                    wg_fence();
#pragma unroll
                    for (int c = 0; c < 4; c++) wgmma32_rs(y[c], Q[hb][c], du + c * (U_STRIDE >> 4));
                    wg_commit();
                    du -= 2;
                    wg_wait<1>();
                    ldq(Q[hb ^ 1]);
                }
            }
        }
        if (warp == 8) STAMP(18);
        mbar_wait(bar + 8 * BAR_WO, 0);
        {
            const uint32_t u0 = sb + OFF_U + w4 * U_STRIDE + U_PAD + lane * 16;
#pragma unroll 1
            for (int rho = 0; rho < 6; rho++) {
                const int ci = lane + 32 * rho;
                uint4 e4[4];
#pragma unroll
                for (int v = 0; v < 4; v++) { const uint32_t a = u0 + rho * 512 + (v - 3) * 16; e4[v] = lds128(a ^ ((a >> 3) & 0x70)); }
                float S[29];
                const uint32_t* ew = (const uint32_t*)e4;
                S[3] = 0.f;
#pragma unroll
                for (int k = 4; k <= 28; k++) S[k] = S[k - 1] + ((k & 1) ? bf_hi(ew[k >> 1]) : bf_lo(ew[k >> 1]));
                auto win = [&](int lo, int hi, uint32_t a) {
                    sts128(a, pack2(S[hi] - S[lo - 1], S[hi + 1] - S[lo]), pack2(S[hi + 2] - S[lo + 1], S[hi + 3] - S[lo + 2]),
                           pack2(S[hi + 4] - S[lo + 3], S[hi + 5] - S[lo + 4]), pack2(S[hi + 6] - S[lo + 5], S[hi + 7] - S[lo + 6]));
                };
                win(14, 18, buf + W5_OFF + 112 + ci * 16); win(19, 21, buf + W3_OFF + 112 + ci * 16);
                if (rho < 4) {
                    const uint32_t sw = (ci ^ ((ci >> 3) & 1)) << 4;
                    win(4, 12, buf + W9_OFF + sw); win(13, 19, spare + sw); win(20, 21, spare + 2048 + sw);
                }
            }
        }
        bar_named(2, 128);
        if (warp == 8) STAMP(23);
        float z[4][12];
#pragma unroll
        for (int c = 0; c < 4; c++) {
#pragma unroll
            for (int r = 0; r < 12; r++) z[c][r] = 0.f;
            fence_regs<12>(z[c]);
        }
        {
            uint32_t Q[2][4][4];
            uint32_t wa = sb + OFF_BUF + (15 - (lane >> 4) * 8 - (lane & 7) + 2 * w4 + ((lane >> 3) & 1)) * 16;
            uint64_t de = (uint64_t)(((sb + OFF_KT + KT_E2 + 112) & 0x3FFFF) >> 4) | ((uint64_t)1 << 16) | ((uint64_t)8 << 32);
#pragma unroll
            for (int c = 0; c < 4; c++) ldsm4t(Q[0][c], wa + c * BUF_STRIDE);
#pragma unroll 1
            for (int s = 0; s < 12; s++) {
#pragma unroll
                for (int ph = 0; ph < 2; ph++) {
                    wg_fence();
#pragma unroll
                    for (int c = 0; c < 4; c++) wgmma24_rs(z[c], Q[ph][c], de + c * (KT_STRIDE >> 4) + ph * (KT_E2O >> 4));
                    wg_commit();
                    wg_wait<1>();
#pragma unroll
                    for (int c = 0; c < 4; c++) ldsm4t(Q[ph ^ 1][c], wa + c * BUF_STRIDE + (ph ? 256 : W3_OFF));
                }
                wa += 256; de -= 2;
            }
        }
        wg_wait<0>();
#pragma unroll
        for (int c = 0; c < 4; c++) {
            fence_regs<16>(y[c]); fence_regs<12>(z[c]);
#pragma unroll
            for (int r = 0; r < 12; r++) y[c][4 + r] += z[c][r];
        }
        if (warp == 8) STAMP(19);
        {
            const int ap = (lane & 7) + (lane >> 4) * 8;
            const uint32_t loff = ((2 * ap + ((lane >> 3) & 1)) ^ ((ap >> 2) & 1)) << 4;
#pragma unroll 1
            for (int ph = 0; ph < 3; ph++) {
                const uint32_t ka = sb + OFF_K3 + (ph * 94 + 4 * g + w4 - 2 * q - 34) * 4;
#pragma unroll
                for (int c = 0; c < 4; c++) {
                    const uint32_t wb = (ph ? sb + (c < 2 ? OFF_SP0 : OFF_SP1) + (c & 1) * 4096 + (ph - 1) * 2048 : sb + OFF_BUF + c * BUF_STRIDE + W9_OFF) + loff;
                    uint32_t B[4][2];
#pragma unroll
                    for (int d = 0; d < 4; d++) { B[d][0] = lds32(ka + c * K3_STRIDE + (48 + 16 * d) * 4); B[d][1] = lds32(ka + c * K3_STRIDE + (40 + 16 * d) * 4); }
#pragma unroll
                    for (int s = 0; s < 4; s++) {
                        uint32_t A[4];
                        ldsm4t(A, wb + s * 512);
                        if (s < 2) mma16816(y[c] + 8, A[0], A[1], A[2], A[3], B[1 - s][0], B[1 - s][1]);
                        mma16816(y[c] + 12, A[0], A[1], A[2], A[3], B[3 - s][0], B[3 - s][1]);
                    }
                }
            }
        }
        uint4* yp = scr->y + bi * 1024 + (8 * q + w4) * 8 + g;
#pragma unroll
        for (int j = 0; j < 4; j++)
#pragma unroll
            for (int b = 0; b < 2; b++)
                st_rlx128(yp + (32 * j + 4 * b) * 8, tag4(pack2(y[0][4 * j + b], y[1][4 * j + b]), pack2(y[0][4 * j + 2 + b], y[1][4 * j + 2 + b]),
                                                          pack2(y[2][4 * j + b], y[3][4 * j + b]), pack2(y[2][4 * j + 2 + b], y[3][4 * j + 2 + b]), tag));
        bar_named(2, 128);
        if (st < 8) st_rlx32(scr->yflag + bi * 8 + st, tag);
        if (warp == 8) STAMP(20);
    }
    __syncthreads();
    if (tid == 0) atomicAdd(scr->done, 1u);
}

typedef CUresult (*EncFn)(CUtensorMap*, CUtensorMapDataType, cuuint32_t, void*, const cuuint64_t*, const cuuint64_t*, const cuuint32_t*,
                          const cuuint32_t*, CUtensorMapInterleave, CUtensorMapSwizzle, CUtensorMapL2promotion, CUtensorMapFloatOOBfill);

extern "C" void kernel_launch(void* const* d_in, const int* in_sizes, int n_in, void* d_out, int out_size) {
    static EncFn enc = nullptr;
    static Scratch* scr = nullptr;
    if (!enc) {
        cudaGetSymbolAddress((void**)&scr, g_scr);
        cudaDriverEntryPointQueryResult qr;
        cudaGetDriverEntryPoint("cuTensorMapEncodeTiled", (void**)&enc, cudaEnableDefault, &qr);
        cudaFuncSetAttribute(fused_kernel, cudaFuncAttributeMaxDynamicSharedMemorySize, SMEM_BYTES);
    }
    CUtensorMap mx, mw, mwo;
    const cuuint32_t es[3] = {1, 1, 1};
    {
        cuuint64_t d[2] = {512, 2048}, s[1] = {1024}; cuuint32_t b[2] = {64, 128};
        enc(&mx, CU_TENSOR_MAP_DATA_TYPE_BFLOAT16, 2, d_in[0], d, s, b, es, CU_TENSOR_MAP_INTERLEAVE_NONE, CU_TENSOR_MAP_SWIZZLE_128B,
            CU_TENSOR_MAP_L2_PROMOTION_L2_128B, CU_TENSOR_MAP_FLOAT_OOB_FILL_NONE);
    }
    {
        cuuint64_t d[3] = {512, 512, 3}, s[2] = {3072, 1024}; cuuint32_t b[3] = {64, 64, 3};
        enc(&mw, CU_TENSOR_MAP_DATA_TYPE_BFLOAT16, 3, d_in[1], d, s, b, es, CU_TENSOR_MAP_INTERLEAVE_NONE, CU_TENSOR_MAP_SWIZZLE_128B,
            CU_TENSOR_MAP_L2_PROMOTION_L2_128B, CU_TENSOR_MAP_FLOAT_OOB_FILL_NONE);
    }
    {
        cuuint64_t d[2] = {512, 512}, s[1] = {1024}; cuuint32_t b[2] = {64, 256};
        enc(&mwo, CU_TENSOR_MAP_DATA_TYPE_BFLOAT16, 2, d_in[3], d, s, b, es, CU_TENSOR_MAP_INTERLEAVE_NONE, CU_TENSOR_MAP_SWIZZLE_128B,
            CU_TENSOR_MAP_L2_PROMOTION_L2_128B, CU_TENSOR_MAP_FLOAT_OOB_FILL_NONE);
    }
    fused_kernel<<<128, 384, SMEM_BYTES, cudaStreamPerThread>>>(
        scr, (const bf16*)d_in[5], (const bf16*)d_in[6], (const bf16*)d_in[7], (const bf16*)d_in[8], (const bf16*)d_in[9],
        (const bf16*)d_in[10], (const bf16*)d_in[2], (const bf16*)d_in[11], (bf16*)d_out, mx, mw, mwo);
}
```

```cpp
#include <cuda_runtime.h>
#include <cuda.h>
#include <cuda_bf16.h>
#include <stdint.h>

typedef __nv_bfloat16 bf16;

struct Scratch {
    uint4 xt[128 * 1024];
    uint4 o[16 * 8 * 32 * 32];
    uint4 y[128 * 1024];
    uint4 kvp[8 * 16 * 544];
    uint4 kvf[8 * 4 * 68];
    unsigned g[1024 * 8];
    unsigned yflag[128 * 8];
    unsigned xcnt[8 * 32];
    unsigned done[32];
};
__device__ Scratch g_scr;
#define STAMP(n)

constexpr int SLOT = 40960;
constexpr int OFF_SP0 = 32768, OFF_SP1 = SLOT + 32768;
constexpr int OFF_P = 2 * SLOT, OFF_V = OFF_P + 32768;
constexpr int OFF_KT = OFF_V + 32768, KT_STRIDE = 3824, KT_E2 = 2688, KT_E2O = 624;
constexpr int OFF_U = 4 * SLOT, U_STRIDE = 41 * 128, U_PAD = 9 * 128;
constexpr int OFF_BUF = OFF_U + 4 * U_STRIDE, BUF_STRIDE = 8448;
constexpr int OFF_K3 = OFF_BUF + 4 * BUF_STRIDE, K3_STRIDE = 1136;
constexpr int OFF_WPHI = OFF_K3 + 4 * K3_STRIDE;
constexpr int OFF_GW = OFF_WPHI + 2048;
constexpr int OFF_KVF = OFF_GW + 1024;
constexpr int OFF_BAR = OFF_KVF + 4352;
constexpr int SMEM_BYTES = OFF_BAR + 128 + 128;
static_assert(SMEM_BYTES <= 232448 && OFF_BUF % 128 == 0 && OFF_KT + 4 * KT_STRIDE <= 4 * SLOT && 3 * SLOT + 7 * 7296 + 8192 <= OFF_BUF, "smem");
constexpr int W5_OFF = 0, W3_OFF = 3184, W9_OFF = 6368;
constexpr int BAR_FULL = 0, BAR_WPHI = 4, BAR_WO = 5, BAR_XT = 6, BAR_DONE = 7, BAR_WO2 = 8, BAR_KG = 9, OFF_CNT = 96;
constexpr int SPIN_LIMIT = 1 << 17;

__device__ __forceinline__ uint32_t s2u(const void* p) { return (uint32_t)__cvta_generic_to_shared(p); }
__device__ __forceinline__ void mbar_init(uint32_t b, int c) { asm volatile("mbarrier.init.shared::cta.b64 [%0],%1;" ::"r"(b), "r"(c) : "memory"); }
__device__ __forceinline__ void mbar_expect(uint32_t b, int bytes) { asm volatile("mbarrier.arrive.expect_tx.shared::cta.b64 _,[%0],%1;" ::"r"(b), "r"(bytes) : "memory"); }
__device__ __forceinline__ void mbar_arrive(uint32_t b) { asm volatile("mbarrier.arrive.shared::cta.b64 _,[%0];" ::"r"(b) : "memory"); }
__device__ __forceinline__ bool mbar_try(uint32_t b, int ph) {
    uint32_t ok;
    asm volatile("{.reg .pred p; mbarrier.try_wait.parity.shared::cta.b64 p,[%1],%2; selp.u32 %0,1,0,p;}" : "=r"(ok) : "r"(b), "r"(ph) : "memory");
    return ok;
}
__device__ __forceinline__ void mbar_wait(uint32_t b, int ph) {
    if ((threadIdx.x & 31) == 0) { int n = 0; while (!mbar_try(b, ph)) { if (++n > SPIN_LIMIT) break; } }
    __syncwarp();
}
__device__ __forceinline__ void tma2d(uint32_t dst, const CUtensorMap* m, int c0, int c1, uint32_t bar) {
    asm volatile("cp.async.bulk.tensor.2d.shared::cluster.global.mbarrier::complete_tx::bytes [%0],[%1,{%3,%4}],[%2];" ::"r"(dst), "l"(m), "r"(bar), "r"(c0), "r"(c1) : "memory");
}
__device__ __forceinline__ void tma3d(uint32_t dst, const CUtensorMap* m, int c0, int c1, int c2, uint32_t bar) {
    asm volatile("cp.async.bulk.tensor.3d.shared::cluster.global.mbarrier::complete_tx::bytes [%0],[%1,{%3,%4,%5}],[%2];" ::"r"(dst), "l"(m), "r"(bar), "r"(c0), "r"(c1), "r"(c2) : "memory");
}
__device__ __forceinline__ void bulk_g2s(uint32_t dst, const void* src, int bytes, uint32_t bar) {
    asm volatile("cp.async.bulk.shared::cluster.global.mbarrier::complete_tx::bytes [%0],[%1],%2,[%3];" ::"r"(dst), "l"(src), "r"(bytes), "r"(bar) : "memory");
}
__device__ __forceinline__ uint64_t mkdesc(uint32_t addr, uint32_t lbo, uint32_t sbo) {
    return (uint64_t)((addr & 0x3FFFF) >> 4) | ((uint64_t)(lbo >> 4) << 16) | ((uint64_t)(sbo >> 4) << 32) | ((uint64_t)1 << 62);
}
__device__ __forceinline__ void wg_fence() { asm volatile("wgmma.fence.sync.aligned;" ::: "memory"); }
__device__ __forceinline__ void wg_commit() { asm volatile("wgmma.commit_group.sync.aligned;" ::: "memory"); }
template <int N> __device__ __forceinline__ void wg_wait() { asm volatile("wgmma.wait_group.sync.aligned %0;" ::"n"(N) : "memory"); }
template <int N> __device__ __forceinline__ void fence_regs(float* d) {
#pragma unroll
    for (int i = 0; i < N; i++) asm volatile("" : "+f"(d[i])::"memory");
}
#define R8(d, o) "+f"(d[o]), "+f"(d[o + 1]), "+f"(d[o + 2]), "+f"(d[o + 3]), "+f"(d[o + 4]), "+f"(d[o + 5]), "+f"(d[o + 6]), "+f"(d[o + 7])
__device__ __forceinline__ void wgmma192(float* d, uint64_t da, uint64_t db) {
    asm volatile("wgmma.mma_async.sync.aligned.m64n192k16.f32.bf16.bf16 {"
                 "%0,%1,%2,%3,%4,%5,%6,%7,%8,%9,%10,%11,%12,%13,%14,%15,%16,%17,%18,%19,%20,%21,%22,%23,%24,%25,%26,%27,%28,%29,%30,%31,"
                 "%32,%33,%34,%35,%36,%37,%38,%39,%40,%41,%42,%43,%44,%45,%46,%47,%48,%49,%50,%51,%52,%53,%54,%55,%56,%57,%58,%59,%60,%61,%62,%63,"
                 "%64,%65,%66,%67,%68,%69,%70,%71,%72,%73,%74,%75,%76,%77,%78,%79,%80,%81,%82,%83,%84,%85,%86,%87,%88,%89,%90,%91,%92,%93,%94,%95},"
                 "%96,%97,1,1,1,0,1;"
                 : R8(d, 0), R8(d, 8), R8(d, 16), R8(d, 24), R8(d, 32), R8(d, 40), R8(d, 48), R8(d, 56), R8(d, 64), R8(d, 72), R8(d, 80), R8(d, 88)
                 : "l"(da), "l"(db));
}
__device__ __forceinline__ void wgmma64_tt(float* d, uint64_t da, uint64_t db, int sc) {
    asm volatile("{.reg .pred p; setp.ne.b32 p,%34,0; wgmma.mma_async.sync.aligned.m64n64k16.f32.bf16.bf16 {"
                 "%0,%1,%2,%3,%4,%5,%6,%7,%8,%9,%10,%11,%12,%13,%14,%15,%16,%17,%18,%19,%20,%21,%22,%23,%24,%25,%26,%27,%28,%29,%30,%31},"
                 "%32,%33,p,1,1,1,1;}"
                 : R8(d, 0), R8(d, 8), R8(d, 16), R8(d, 24)
                 : "l"(da), "l"(db), "r"(sc));
}
__device__ __forceinline__ void wgmma128_rs(float* d, const uint4& a, uint64_t db, int sc) {
    asm volatile("{.reg .pred p; setp.ne.b32 p,%69,0; wgmma.mma_async.sync.aligned.m64n128k16.f32.bf16.bf16 {"
                 "%0,%1,%2,%3,%4,%5,%6,%7,%8,%9,%10,%11,%12,%13,%14,%15,%16,%17,%18,%19,%20,%21,%22,%23,%24,%25,%26,%27,%28,%29,%30,%31,"
                 "%32,%33,%34,%35,%36,%37,%38,%39,%40,%41,%42,%43,%44,%45,%46,%47,%48,%49,%50,%51,%52,%53,%54,%55,%56,%57,%58,%59,%60,%61,%62,%63},"
                 "{%64,%65,%66,%67},%68,p,1,1,1;}"
                 : R8(d, 0), R8(d, 8), R8(d, 16), R8(d, 24), R8(d, 32), R8(d, 40), R8(d, 48), R8(d, 56)
                 : "r"(a.x), "r"(a.y), "r"(a.z), "r"(a.w), "l"(db), "r"(sc));
}
__device__ __forceinline__ void wgmma32_rs(float* d, const uint32_t* a, uint64_t db) {
    asm volatile("wgmma.mma_async.sync.aligned.m64n32k16.f32.bf16.bf16 {%0,%1,%2,%3,%4,%5,%6,%7,%8,%9,%10,%11,%12,%13,%14,%15},{%16,%17,%18,%19},%20,1,1,1,0;"
                 : R8(d, 0), R8(d, 8) : "r"(a[0]), "r"(a[1]), "r"(a[2]), "r"(a[3]), "l"(db));
}
__device__ __forceinline__ void mma16816(float* c, uint32_t a0, uint32_t a1, uint32_t a2, uint32_t a3, uint32_t b0, uint32_t b1) {
    asm("mma.sync.aligned.m16n8k16.row.col.f32.bf16.bf16.f32 {%0,%1,%2,%3},{%4,%5,%6,%7},{%8,%9},{%0,%1,%2,%3};"
        : "+f"(c[0]), "+f"(c[1]), "+f"(c[2]), "+f"(c[3]) : "r"(a0), "r"(a1), "r"(a2), "r"(a3), "r"(b0), "r"(b1));
}
__device__ __forceinline__ void ldsm4(uint32_t* r, uint32_t a) {
    asm volatile("ldmatrix.sync.aligned.m8n8.x4.shared.b16 {%0,%1,%2,%3},[%4];" : "=r"(r[0]), "=r"(r[1]), "=r"(r[2]), "=r"(r[3]) : "r"(a) : "memory");
}
__device__ __forceinline__ void ldsm4t(uint32_t* r, uint32_t a) {
    asm volatile("ldmatrix.sync.aligned.m8n8.x4.trans.shared.b16 {%0,%1,%2,%3},[%4];" : "=r"(r[0]), "=r"(r[1]), "=r"(r[2]), "=r"(r[3]) : "r"(a) : "memory");
}
__device__ __forceinline__ void stsm4(uint32_t a, uint32_t r0, uint32_t r1, uint32_t r2, uint32_t r3) {
    asm volatile("stmatrix.sync.aligned.m8n8.x4.shared.b16 [%0],{%1,%2,%3,%4};" ::"r"(a), "r"(r0), "r"(r1), "r"(r2), "r"(r3) : "memory");
}
__device__ __forceinline__ uint32_t lds32(uint32_t a) { uint32_t v; asm volatile("ld.shared.b32 %0,[%1];" : "=r"(v) : "r"(a) : "memory"); return v; }
__device__ __forceinline__ uint4 lds128(uint32_t a) { uint4 v; asm volatile("ld.shared.v4.b32 {%0,%1,%2,%3},[%4];" : "=r"(v.x), "=r"(v.y), "=r"(v.z), "=r"(v.w) : "r"(a) : "memory"); return v; }
__device__ __forceinline__ void sts16(uint32_t a, uint32_t v) { asm volatile("st.shared.b16 [%0],%1;" ::"r"(a), "h"((unsigned short)v) : "memory"); }
__device__ __forceinline__ void sts32(uint32_t a, uint32_t v) { asm volatile("st.shared.b32 [%0],%1;" ::"r"(a), "r"(v) : "memory"); }
__device__ __forceinline__ void sts64(uint32_t a, uint32_t x, uint32_t y) { asm volatile("st.shared.v2.b32 [%0],{%1,%2};" ::"r"(a), "r"(x), "r"(y) : "memory"); }
__device__ __forceinline__ void sts128(uint32_t a, uint32_t x, uint32_t y, uint32_t z, uint32_t w) { asm volatile("st.shared.v4.b32 [%0],{%1,%2,%3,%4};" ::"r"(a), "r"(x), "r"(y), "r"(z), "r"(w) : "memory"); }
__device__ __forceinline__ uint32_t pack2(float lo, float hi) { uint32_t d; asm("cvt.rn.bf16x2.f32 %0,%1,%2;" : "=r"(d) : "f"(hi), "f"(lo)); return d; }
__device__ __forceinline__ float bf_lo(uint32_t v) { return __uint_as_float(v << 16); }
__device__ __forceinline__ float bf_hi(uint32_t v) { return __uint_as_float(v & 0xffff0000u); }
__device__ __forceinline__ float bf_round(float v) { return bf_lo(pack2(v, 0.f)); }
__device__ __forceinline__ uint32_t hmax2(uint32_t a, uint32_t b) { uint32_t d; asm("max.bf16x2 %0,%1,%2;" : "=r"(d) : "r"(a), "r"(b)); return d; }
__device__ __forceinline__ uint32_t hmin2(uint32_t a, uint32_t b) { uint32_t d; asm("min.bf16x2 %0,%1,%2;" : "=r"(d) : "r"(a), "r"(b)); return d; }
__device__ __forceinline__ uint32_t hmul2(uint32_t a, uint32_t b) { uint32_t d; asm("mul.rn.bf16x2 %0,%1,%2;" : "=r"(d) : "r"(a), "r"(b)); return d; }
__device__ __forceinline__ float ex2(float x) { float y; asm("ex2.approx.ftz.f32 %0,%1;" : "=f"(y) : "f"(x)); return y; }
__device__ __forceinline__ float rcp(float x) { float y; asm("rcp.approx.ftz.f32 %0,%1;" : "=f"(y) : "f"(x)); return y; }
__device__ __forceinline__ uint32_t ld_nc(const uint32_t* p) { uint32_t v; asm volatile("ld.global.nc.b32 %0,[%1];" : "=r"(v) : "l"(p)); return v; }
__device__ __forceinline__ uint2 ld_nc64(const uint2* p) { uint2 v; asm volatile("ld.global.nc.v2.b32 {%0,%1},[%2];" : "=r"(v.x), "=r"(v.y) : "l"(p)); return v; }
__device__ __forceinline__ unsigned ld_acq(const unsigned* p) { unsigned v; asm volatile("ld.acquire.gpu.global.u32 %0,[%1];" : "=r"(v) : "l"(p) : "memory"); return v; }
__device__ __forceinline__ unsigned ld_rlx(const unsigned* p) { unsigned v; asm volatile("ld.relaxed.gpu.global.u32 %0,[%1];" : "=r"(v) : "l"(p) : "memory"); return v; }
__device__ __forceinline__ uint2 ld_rlx64(const void* p) { uint2 v; asm volatile("{.reg .b64 t; ld.relaxed.gpu.global.b64 t,[%2]; mov.b64 {%0,%1},t;}" : "=r"(v.x), "=r"(v.y) : "l"(p) : "memory"); return v; }
__device__ __forceinline__ uint4 ld_rlx128(const void* p) {
    uint4 v;
    asm volatile("{.reg .b64 t,u; ld.relaxed.gpu.global.v2.b64 {t,u},[%4]; mov.b64 {%0,%1},t; mov.b64 {%2,%3},u;}" : "=r"(v.x), "=r"(v.y), "=r"(v.z), "=r"(v.w) : "l"(p) : "memory");
    return v;
}
__device__ __forceinline__ void st_rlx32(void* p, uint32_t x) { asm volatile("st.relaxed.gpu.global.u32 [%0],%1;" ::"l"(p), "r"(x) : "memory"); }
__device__ __forceinline__ void st_rlx64(void* p, uint32_t x, uint32_t y) { asm volatile("{.reg .b64 t; mov.b64 t,{%1,%2}; st.relaxed.gpu.global.b64 [%0],t;}" ::"l"(p), "r"(x), "r"(y) : "memory"); }
__device__ __forceinline__ void st_rlx128(void* p, uint4 v) {
    asm volatile("{.reg .b64 t,u; mov.b64 t,{%1,%2}; mov.b64 u,{%3,%4}; st.relaxed.gpu.global.v2.b64 [%0],{t,u};}" ::"l"(p), "r"(v.x), "r"(v.y), "r"(v.z), "r"(v.w) : "memory");
}
__device__ __forceinline__ uint32_t tagw(uint32_t w, uint32_t tag) { return (w & ~1u) | tag; }
__device__ __forceinline__ uint4 tag4(uint32_t x, uint32_t y, uint32_t z, uint32_t w, uint32_t tag) { return make_uint4(tagw(x, tag), y, tagw(z, tag), w); }
__device__ __forceinline__ uint32_t bad4(const uint4& v, uint32_t tag) { return (v.x ^ tag) | (v.z ^ tag); }
__device__ __forceinline__ void bar_named(int id, int n) { asm volatile("bar.sync %0,%1;" ::"r"(id), "r"(n) : "memory"); }

struct cf { float re, im; };
__device__ __forceinline__ cf cmul(cf a, cf b) { cf r; r.re = a.re * b.re - a.im * b.im; r.im = a.re * b.im + a.im * b.re; return r; }
__device__ __forceinline__ cf cexp_p(float arl, float ait, float p) {
    float mag = ex2(arl * p);
    float t = ait * p;
    t = (t - rintf(t)) * 6.283185307179586f;
    cf r; r.re = mag * __cosf(t); r.im = mag * __sinf(t);
    return r;
}

__device__ __forceinline__ void hedgehog2(const uint32_t* a, uint32_t wphi_addr, uint32_t (*out)[8]) {
    float p[2][2][4], mx[2][2];
#pragma unroll
    for (int h = 0; h < 2; h++) {
        uint32_t b[4];
        ldsm4t(b, wphi_addr + h * 512);
        float c0[4] = {0.f, 0.f, 0.f, 0.f}, c1[4] = {0.f, 0.f, 0.f, 0.f};
        mma16816(c0, a[4 * h], a[4 * h + 1], a[4 * h + 2], a[4 * h + 3], b[0], b[1]);
        mma16816(c1, a[4 * h], a[4 * h + 1], a[4 * h + 2], a[4 * h + 3], b[2], b[3]);
#pragma unroll
        for (int k = 0; k < 2; k++) {
            p[h][k][0] = c0[2 * k]; p[h][k][1] = c0[2 * k + 1]; p[h][k][2] = c1[2 * k]; p[h][k][3] = c1[2 * k + 1];
            mx[h][k] = fmaxf(fmaxf(p[h][k][0], p[h][k][1]), fmaxf(p[h][k][2], p[h][k][3]));
        }
    }
#pragma unroll
    for (int o = 1; o <= 2; o <<= 1)
#pragma unroll
        for (int h = 0; h < 2; h++)
#pragma unroll
            for (int k = 0; k < 2; k++) mx[h][k] = fmaxf(mx[h][k], __shfl_xor_sync(~0u, mx[h][k], o));
    const float L = 1.4426950408889634f;
    float pmin = 1.f;
#pragma unroll
    for (int h = 0; h < 2; h++)
#pragma unroll
        for (int k = 0; k < 2; k++) {
            const float m = -mx[h][k] * L;
            const float e0 = ex2(fmaf(p[h][k][0], L, m)), e1 = ex2(fmaf(p[h][k][1], L, m)), e2 = ex2(fmaf(p[h][k][2], L, m)), e3 = ex2(fmaf(p[h][k][3], L, m));
            const float p01 = e0 * e1, p23 = e2 * e3, pp = p01 * p23, r = rcp(pp), r01 = r * p23, r23 = r * p01;
            pmin = fminf(pmin, pp);
            out[h][k] = pack2(e0, e1); out[h][k + 2] = pack2(e2, e3);
            out[h][4 + k] = pack2(r01 * e1, r01 * e0); out[h][4 + k + 2] = pack2(r23 * e3, r23 * e2);
        }
    if (__any_sync(~0u, !(pmin > 1e-18f))) {
#pragma unroll
        for (int h = 0; h < 2; h++)
#pragma unroll
            for (int k = 0; k < 2; k++) {
                float m = fminf(fminf(p[h][k][0], p[h][k][1]), fminf(p[h][k][2], p[h][k][3]));
                m = fminf(m, __shfl_xor_sync(~0u, m, 1));
                m = fminf(m, __shfl_xor_sync(~0u, m, 2)) * L;
                out[h][4 + k] = pack2(ex2(fmaf(p[h][k][0], -L, m)), ex2(fmaf(p[h][k][1], -L, m)));
                out[h][4 + k + 2] = pack2(ex2(fmaf(p[h][k][2], -L, m)), ex2(fmaf(p[h][k][3], -L, m)));
            }
    }
}

__global__ void __launch_bounds__(384, 1)
fused_kernel(Scratch* __restrict__ scr, const bf16* __restrict__ logA, const bf16* __restrict__ Aim, const bf16* __restrict__ Cre,
             const bf16* __restrict__ Cim, const bf16* __restrict__ logdt, const bf16* __restrict__ Dskip, const bf16* __restrict__ wphi,
             const bf16* __restrict__ gatew, bf16* __restrict__ out,
             const __grid_constant__ CUtensorMap mx, const __grid_constant__ CUtensorMap mw, const __grid_constant__ CUtensorMap mwo) {
    extern __shared__ __align__(1024) uint8_t smem[];
    const uint32_t sb = s2u(smem);
    const int tid = threadIdx.x, warp = __shfl_sync(~0u, tid >> 5, 0), lane = tid & 31;
    const int g = lane >> 2, q = lane & 3, w4 = warp & 3;
    const int bi = blockIdx.x, bi_i = bi & 15, bi_j = bi >> 4;
    const uint32_t bar = sb + OFF_BAR;
    const int rot = (bi_j & 1) * 4;
    auto load_stage = [&](int kb) {
        const uint32_t b = bar + 8 * (BAR_FULL + (kb & 3)), d = sb + (kb & 3) * SLOT;
        const int kc = ((kb + rot) & 7) * 64;
        mbar_expect(b, SLOT);
        tma2d(d, &mx, kc, bi_i * 128, b);
        tma3d(d + 16384, &mw, bi_j * 64, kc, 0, b);
    };

    const int ch = bi * 4 + w4;
    const int pidx = ch * 64 + lane * 2 + (warp < 8);
    const uint32_t pla = ld_nc((const uint32_t*)logA + pidx), pai = ld_nc((const uint32_t*)Aim + pidx);
    const uint32_t pcr = ld_nc((const uint32_t*)Cre + pidx), pci = ld_nc((const uint32_t*)Cim + pidx);
    uint32_t pdt = ld_nc((const uint32_t*)logdt + (ch >> 1));
    const uint32_t pds = ld_nc((const uint32_t*)Dskip + (ch >> 1));
    const unsigned done0 = ld_rlx(scr->done);
    if (tid == 0) {
        for (int s = 0; s < 4; s++) mbar_init(bar + 8 * (BAR_FULL + s), 1);
        asm volatile("fence.mbarrier_init.release.cluster;" ::: "memory");
#pragma unroll 1
        for (int s = 0; s < 3; s++) load_stage(s);
        STAMP(11);
    } else if (tid == 32) {
        if (sb & 1023) __trap();
        for (int s = 0; s < 5; s++) sts32(bar + OFF_CNT + 4 * s, 0);
        mbar_init(bar + 8 * BAR_WPHI, 1); mbar_init(bar + 8 * BAR_WO, 2); mbar_init(bar + 8 * BAR_XT, 8); mbar_init(bar + 8 * BAR_DONE, 8);
        mbar_init(bar + 8 * BAR_WO2, 1); mbar_init(bar + 8 * BAR_KG, 8);
        asm volatile("fence.mbarrier_init.release.cluster;" ::: "memory");
        mbar_expect(bar + 8 * BAR_WPHI, 3072);
        bulk_g2s(sb + OFF_GW, gatew, 1024, bar + 8 * BAR_WPHI);
        bulk_g2s(sb + OFF_WPHI, wphi + bi_j * 1024, 2048, bar + 8 * BAR_WPHI);
    } else if (tid == 64) {
        asm volatile("prefetch.tensormap [%0];" ::"l"(&mw) : "memory");
    }
    const uint32_t buf = sb + OFF_BUF + w4 * BUF_STRIDE, k3 = sb + OFF_K3 + w4 * K3_STRIDE;
    if (warp >= 8) {
#pragma unroll
        for (int v = 0; v < 3; v++) if (v * 32 + lane < K3_STRIDE / 16) sts128(k3 + (v * 32 + lane) * 16, 0, 0, 0, 0);
    }
    __syncthreads();
    asm volatile("" : "+r"(pdt));
    const unsigned epoch1 = (done0 >> 7) + 1u;
    const uint32_t tag = epoch1 & 1u;

    const int st = tid - 256;
    float kc[6][4];
#pragma unroll
    for (int t = 0; t < 6; t++) { kc[t][0] = kc[t][1] = kc[t][2] = kc[t][3] = 0.f; }
    {
        const float dt = bf_round(expf((ch & 1) ? bf_hi(pdt) : bf_lo(pdt)));
        const uint32_t stg = (warp < 8) ? sb + 3 * SLOT + warp * 7296 : buf;
#pragma unroll 1
        for (int it = 0; it < 2; it++) {
            {
                const int sh = (warp < 8 ? (warp >> 2) : it) * 16;
                auto pick = [&](uint32_t v) { return __uint_as_float((v >> sh) << 16); };
                const float ea = bf_round(expf(pick(pla)));
                const float arl = (-ea * dt) * 1.4426950408889634f, ait = (pick(pai) * dt) * 0.15915494309189535f;
                cf C2; C2.re = 2.0f * (pick(pcr) * dt); C2.im = 2.0f * (pick(pci) * dt);
                const cf z1 = cexp_p(arl, ait, 1.0f), z128 = cexp_p(arl, ait, 128.0f);
                cf z8 = cexp_p(arl, ait, 8.0f); z8.im = -z8.im;
                const uint32_t lp = stg + lane * 4;
                auto put = [&](int row, const cf& v) { sts32((lp ^ ((row & 7) << 4)) + row * 128, pack2(v.re, v.im)); };
                {
                    const cf z16 = cmul(z8, z8);
                    cf e; e.re = 1.f; e.im = 0.f;
                    cf o = z8;
                    put(0, e); put(1, o);
                    e = z16; put(2, e);
#pragma unroll
                    for (int b = 3; b < 16; b += 2) {
                        o = cmul(o, z16); put(b, o);
                        if (b + 1 < 16) { e = cmul(e, z16); put(b + 1, e); }
                    }
                }
                cf h[8];
                h[0] = C2; put(16, h[0]);
                {
                    const cf z2 = cmul(z1, z1);
                    h[1] = cmul(h[0], z1);
#pragma unroll
                    for (int r = 2; r < 8; r++) h[r] = cmul(h[r - 2], z2);
#pragma unroll
                    for (int r = 1; r < 8; r++) put(16 + r, h[r]);
                }
#pragma unroll
                for (int r = 0; r < 8; r++) { h[r] = cmul(h[r], z128); put(24 + r, h[r]); }
#pragma unroll
                for (int al = 0; al < 2; al++)
#pragma unroll
                    for (int r = 0; r < 4; r++) { h[2 * r] = cmul(h[2 * r], z128); put(32 + al * 4 + r, h[2 * r]); }
#pragma unroll
                for (int al = 0; al < 4; al++)
#pragma unroll
                    for (int r = 0; r < 2; r++) { h[4 * r] = cmul(h[4 * r], z128); put(40 + al * 2 + r, h[4 * r]); }
#pragma unroll
                for (int al = 0; al < 9; al++) { h[0] = cmul(h[0], z128); put(48 + al, h[0]); }
                __syncwarp();
            }
            if (it == 1) {
                if (warp == 8) {
                    mbar_wait(bar + 8 * BAR_XT, 0);
                    if (lane == 0) asm volatile("red.release.gpu.global.add.u32 [%0],8;" ::"l"(scr->xcnt + ((bi_j >> 1) + rot) * 32) : "memory");
                }
                if (lane == 0) {
                    int n = 0;
                    while ((int)(ld_acq(scr->xcnt + bi_j * 32) - (epoch1 << 7)) < 0) { __nanosleep(200); if (++n > SPIN_LIMIT) break; }
                }
                __syncwarp();
                if (warp == 8) STAMP(15);
                uint4 ur[8];
#pragma unroll
                for (int v = 0; v < 8; v++) ur[v] = __ldcg(scr->xt + bi * 1024 + st + 128 * v);
#pragma unroll
                for (int v = 0; v < 3; v++) if (v * 32 + lane < U_PAD / 16) sts128(sb + OFF_U + w4 * U_STRIDE + (v * 32 + lane) * 16, 0, 0, 0, 0);
                if (st < 8) st_rlx32(scr->yflag + bi * 8 + st, tag ^ 1u);
#pragma unroll
                for (int v = 0; v < 8; v++) {
                    const uint32_t a = sb + OFF_U + (st & 3) * U_STRIDE + U_PAD + ((st >> 2) + 32 * v) * 16;
                    sts128(a ^ ((a >> 3) & 0x70), ur[v].x, ur[v].y, ur[v].z, ur[v].w);
                }
                if (warp == 8) STAMP(16);
                mbar_wait(bar + 8 * BAR_DONE, 0);
            }
            const int lr = lane & 7, lm = lane >> 3;
#pragma unroll
            for (int kp = 0; kp < 2; kp++) {
                uint32_t a0[4], a1[4];
                ldsm4(a0, stg + ((lm & 1) * 8 + lr) * 128 + (((4 * kp + (lm >> 1)) ^ lr) << 4));
                ldsm4(a1, stg + ((lm & 1) * 8 + lr) * 128 + (((4 * kp + 2 + (lm >> 1)) ^ lr) << 4));
#pragma unroll
                for (int t = 0; t < 6; t++) {
                    uint32_t b[4];
                    ldsm4(b, stg + (16 + 8 * t + lr) * 128 + (((4 * kp + lm) ^ lr) << 4));
                    mma16816(kc[t], a0[0], a0[1], a0[2], a0[3], b[0], b[1]);
                    mma16816(kc[t], a1[0], a1[1], a1[2], a1[3], b[2], b[3]);
                }
            }
            __syncwarp();
            if (it == 0) {
                if (warp < 8) {
#pragma unroll
                    for (int t = 0; t < 6; t++)
                        sts128(stg + (t * 32 + lane) * 16, __float_as_uint(kc[t][0]), __float_as_uint(kc[t][1]), __float_as_uint(kc[t][2]), __float_as_uint(kc[t][3]));
                    __syncwarp();
                    if (lane == 0) mbar_arrive(bar + 8 * BAR_KG);
                    break;
                }
                mbar_wait(bar + 8 * BAR_KG, 0);
#pragma unroll
                for (int t = 0; t < 12; t++) {
                    const uint4 v = lds128(sb + 3 * SLOT + (w4 + (t / 6) * 4) * 7296 + ((t % 6) * 32 + lane) * 16);
                    kc[t % 6][0] += __uint_as_float(v.x); kc[t % 6][1] += __uint_as_float(v.y); kc[t % 6][2] += __uint_as_float(v.z); kc[t % 6][3] += __uint_as_float(v.w);
                }
                asm volatile("fence.proxy.async.shared::cta;" ::: "memory");
                bar_named(2, 128);
                if (st == 0) load_stage(3);
                if (warp == 8) STAMP(22);
            }
        }
    }

    if (warp < 8) {
        const int wg = warp >> 2;
        if (warp == 0) STAMP(21);
        float acc[96];
        const int grow = bi_j * 16 + warp * 2 + (lane >> 4);
        const uint32_t gx_a = grow * 128 + ((((lane & 15) >> 1) ^ (grow & 7)) << 4) + (lane & 1) * 8;
        const int srow = warp * 16 + (lane & 15);
        const uint32_t srow_a = srow * 128;
        const int sx = srow & 7, shi = lane >> 4;
        auto last_of_8 = [&](int c) {
            unsigned old;
            asm volatile("atom.acq_rel.cta.shared.add.u32 %0,[%1],1;" : "=r"(old) : "r"(bar + OFF_CNT + 4 * c) : "memory");
            return (old & 7) == 7;
        };
        const int qq = (bi_i & 2) + ((lane >> 1) & 1);
        const int kvf_n = warp < 4 ? 8 : ((warp == 4 && (bi_i & 1) == 0) ? 4 : 0);
        uint2* kvf_dst = (uint2*)(scr->kvf + (bi_j * 4 + (bi_i >> 2)) * 68) +
                         (warp == 4 ? (64 + qq) * 2 + (lane & 1) : ((bi_i & 3) * 8 + w4 * 2 + (lane & 1)) * 4 + (lane >> 1));
        float gsum = 0.f;
#pragma unroll
        for (int r = 0; r < 96; r++) acc[r] = 0.f;
        fence_regs<96>(acc);
        const uint64_t da0 = mkdesc(sb + wg * 8192, 16, 1024), db0 = mkdesc(sb + 16384, 8192, 1024);
        {
            const uint32_t old = tag ^ 1u;
            const uint4 z4 = make_uint4(old, 0, old, 0);
            uint4* kvp = scr->kvp + bi * 544 + wg * 272;
            if (w4 < 2) {
#pragma unroll
                for (int f = 0; f < 4; f++) st_rlx128(kvp + w4 * 136 + lane + f * 32, z4);
            } else if (w4 == 2 && lane < 4) {
#pragma unroll
                for (int f = 0; f < 4; f++) st_rlx128(kvp + (f >> 1) * 136 + 128 + (f & 1) * 4 + lane, z4);
            }
            if (lane < kvf_n) st_rlx64(kvf_dst, old, 0);
            if (lane >= 30) st_rlx128(scr->o + ((bi_i * 8 + warp) * 32 + bi_j * 4 + 3) * 32 + lane, z4);
            if (lane < 8) st_rlx32(scr->g + (bi_i * 64 + bi_j * 8 + warp) * 8 + lane, old);
        }
        mbar_wait(bar + 8 * BAR_WPHI, 0);
#pragma unroll 1
        for (int kb = 0; kb < 8; kb++) {
            const int s = kb & 3;
            const uint64_t da = da0 + s * (SLOT >> 4), db = db0 + s * (SLOT >> 4);
            mbar_wait(bar + 8 * (BAR_FULL + s), kb >> 2);
            if (kb == 0 && warp == 0) STAMP(0);
            wg_fence();
#pragma unroll
            for (int k = 0; k < 4; k++) wgmma192(acc, da + 2 * k, db + 128 * k);
            wg_commit();
            wg_wait<1>();
            __syncwarp();
            if (lane == 0 && kb > 0 && kb < 7) {
                const int ps = (kb - 1) & 3;
                if (last_of_8(ps)) {
                    if (kb < 5) load_stage(kb + 3);
                    else {
                        mbar_expect(bar + 8 * BAR_WO, 32768);
                        tma2d(sb + ps * SLOT, &mwo, (bi_j & 3) * 128 + ps * 64, 0, bar + 8 * BAR_WO);
                    }
                }
            }
            __syncwarp();
            const uint32_t st = sb + s * SLOT;
            if (kb == (bi_j >> 1)) {
                uint32_t* xt = (uint32_t*)scr->xt + ((kb + rot) * 16 + (g >> 2)) * 4096 + (bi_i * 16 + warp * 2) * 16 + (g & 3) * 4 + q;
#pragma unroll
                for (int cb = 0; cb < 8; cb += 2) {
                    uint32_t r[4];
                    ldsm4t(r, st + srow_a + (((cb + shi) ^ sx) << 4));
                    xt[cb * 8192] = r[0]; xt[cb * 8192 + 16] = r[1]; xt[cb * 8192 + 8192] = r[2]; xt[cb * 8192 + 8192 + 16] = r[3];
                }
                __syncwarp();
                if (lane == 0) mbar_arrive(bar + 8 * BAR_XT);
            }
            {
                uint32_t x0, x1, w0, w1;
                asm volatile("ld.shared.v2.b32 {%0,%1},[%2];" : "=r"(x0), "=r"(x1) : "r"(st + gx_a) : "memory");
                asm volatile("ld.shared.v2.b32 {%0,%1},[%2];" : "=r"(w0), "=r"(w1) : "r"(sb + OFF_GW + ((kb + rot) & 7) * 128 + (lane & 15) * 8) : "memory");
                const uint32_t p0 = hmul2(x0, w0), p1 = hmul2(x1, w1);
                gsum += (bf_lo(p0) + bf_hi(p0)) + (bf_lo(p1) + bf_hi(p1));
            }
        }
        wg_wait<0>();
        fence_regs<96>(acc);
        __syncwarp();
        if (lane == 0) mbar_arrive(bar + 8 * BAR_DONE);
        if (warp == 0) STAMP(1);
        uint32_t in[32], va[16];
#pragma unroll
        for (int r = 0; r < 16; r++) {
            in[r] = pack2(acc[32 + 2 * r], acc[32 + 2 * r + 1]);
            in[16 + r] = pack2(acc[2 * r], acc[2 * r + 1]);
            va[r] = pack2(acc[64 + 2 * r], acc[64 + 2 * r + 1]);
        }
        const uint32_t wphi_a = sb + OFF_WPHI + (lane & 15) * 32 + (lane >> 4) * 16;
        uint32_t pq[4][8];
#pragma unroll 1
        for (int it = 0; it < 4; it++) {
            hedgehog2(in, wphi_a + (it & 1) * 1024, pq + 2);
#pragma unroll
            for (int r = 0; r < 24; r++) in[r] = in[r + 8];
            if (it < 2) {
#pragma unroll
                for (int hs = 0; hs < 4; hs++) {
                    float c[4] = {0.f, 0.f, 0.f, 0.f};
                    uint32_t* o = pq[2 + (hs >> 1)] + 4 * (hs & 1);
                    mma16816(c, o[0], o[1], o[2], o[3], 0x3f803f80u, 0x3f803f80u);
                    const float r0 = rcp(c[0]), r1 = rcp(c[2]);
                    const uint32_t s0 = pack2(r0, r0), s1 = pack2(r1, r1);
                    o[0] = hmul2(o[0], s0); o[1] = hmul2(o[1], s1); o[2] = hmul2(o[2], s0); o[3] = hmul2(o[3], s1);
                }
                if (it == 0) mbar_wait(bar + 8 * BAR_DONE, 0);
                const uint32_t pt = sb + OFF_P + it * 16384 + srow_a, vt = sb + OFF_V + it * 16384 + srow_a;
#pragma unroll
                for (int hl = 0; hl < 2; hl++) {
                    stsm4(pt + (((4 * hl + shi) ^ sx) << 4), pq[2 + hl][0], pq[2 + hl][1], pq[2 + hl][2], pq[2 + hl][3]);
                    stsm4(pt + (((4 * hl + 2 + shi) ^ sx) << 4), pq[2 + hl][4], pq[2 + hl][5], pq[2 + hl][6], pq[2 + hl][7]);
                    stsm4(vt + (((2 * hl + shi) ^ sx) << 4), va[4 * hl], va[4 * hl + 1], va[4 * hl + 2], va[4 * hl + 3]);
                }
                if (lane < 16) sts128(vt + ((4 ^ sx) << 4), 0x3f803f80u, 0x3f803f80u, 0x3f803f80u, 0x3f803f80u);
#pragma unroll
                for (int r = 0; r < 8; r++) va[r] = va[r + 8];
            }
            if (it == 1) {
                asm volatile("fence.proxy.async.shared::cta;" ::: "memory");
                bar_named(1, 256);
                if (warp == 0) STAMP(2);
                float d[32];
                const uint64_t dv = mkdesc(sb + OFF_V + wg * 16384, 16, 1024), dp = mkdesc(sb + OFF_P + wg * 16384, 16, 1024);
                wg_fence();
#pragma unroll
                for (int k = 0; k < 8; k++) wgmma64_tt(d, dv + 128 * k, dp + 128 * k, k != 0);
                wg_commit();
                wg_wait<0>();
                fence_regs<32>(d);
                uint4* kvp = scr->kvp + bi * 544 + wg * 272;
                if (w4 < 2) {
                    uint32_t e[16];
#pragma unroll
                    for (int r = 0; r < 16; r++) e[r] = __float_as_uint(w4 ? d[16 + r] : d[r]);
                    uint4* p = kvp + w4 * 136 + lane;
#pragma unroll
                    for (int ks = 0; ks < 2; ks++)
#pragma unroll
                        for (int nt = 0; nt < 2; nt++)
                            st_rlx128(p + (ks * 2 + nt) * 32, tag4(e[8 * ks + 2 * nt], e[8 * ks + 2 * nt + 1], e[8 * ks + 4 + 2 * nt], e[8 * ks + 4 + 2 * nt + 1], tag));
                } else if (w4 == 2 && lane < 4) {
#pragma unroll
                    for (int hl = 0; hl < 2; hl++)
#pragma unroll
                        for (int ks = 0; ks < 2; ks++)
                            st_rlx128(kvp + hl * 136 + 128 + ks * 4 + lane, tag4(__float_as_uint(d[16 * hl + 8 * ks]), __float_as_uint(d[16 * hl + 8 * ks + 1]),
                                                                                __float_as_uint(d[16 * hl + 8 * ks + 4]), __float_as_uint(d[16 * hl + 8 * ks + 5]), tag));
                }
                if (warp == 0) STAMP(3);
            }
            if (it == 2) {
#pragma unroll
                for (int r = 0; r < 8; r++) { pq[0][r] = pq[2][r]; pq[1][r] = pq[3][r]; }
                if (warp == 0) STAMP(12);
                if (kvf_n) {
                    const bool zw = warp == 4;
                    const uint4* src = scr->kvp + bi_j * (16 * 544) + (bi_i >> 2) * 136 +
                                       (zw ? (lane >> 2) * (2 * 544) + 128 + (lane & 1) * 4 + qq
                                           : (lane >> 3) * (4 * 544) + ((lane >> 1) & 3) * 32 + (bi_i & 3) * 8 + warp * 2 + (lane & 1));
                    const int s23 = zw ? 0 : 2 * 544;
                    uint4 v[4];
                    int n = 0;
                    while (true) {
                        v[0] = ld_rlx128(src); v[1] = ld_rlx128(src + 544); v[2] = ld_rlx128(src + s23); v[3] = ld_rlx128(src + s23 + 544);
                        if (!__any_sync(~0u, (bad4(v[0], tag) | bad4(v[1], tag) | bad4(v[2], tag) | bad4(v[3], tag)) & 1)) break;
                        if (++n > SPIN_LIMIT) break;
                    }
                    float f[4];
                    f[0] = __uint_as_float(v[2].x) + __uint_as_float(v[3].x); f[1] = __uint_as_float(v[2].y) + __uint_as_float(v[3].y);
                    f[2] = __uint_as_float(v[2].z) + __uint_as_float(v[3].z); f[3] = __uint_as_float(v[2].w) + __uint_as_float(v[3].w);
                    float e0 = __uint_as_float(v[0].x) + __uint_as_float(v[1].x), e1 = __uint_as_float(v[0].y) + __uint_as_float(v[1].y);
                    float e2 = __uint_as_float(v[0].z) + __uint_as_float(v[1].z), e3 = __uint_as_float(v[0].w) + __uint_as_float(v[1].w);
                    if (zw) {
                        e0 = __shfl_xor_sync(~0u, f[0], 4); e1 = __shfl_xor_sync(~0u, f[1], 4);
                        e2 = __shfl_xor_sync(~0u, f[2], 4); e3 = __shfl_xor_sync(~0u, f[3], 4);
                    }
                    f[0] += e0; f[1] += e1; f[2] += e2; f[3] += e3;
#pragma unroll
                    for (int o = 8; o <= 16; o <<= 1)
#pragma unroll
                        for (int r = 0; r < 4; r++) f[r] += __shfl_xor_sync(~0u, f[r], o);
                    if (lane < kvf_n) st_rlx64(kvf_dst, tagw(pack2(f[0], f[1]), tag), pack2(f[2], f[3]));
                }
                __syncwarp();
                if (lane == 0 && last_of_8(4)) {
                    mbar_expect(bar + 8 * BAR_WO2, 65536);
                    tma2d(sb + 2 * SLOT, &mwo, (bi_j & 3) * 128, 256, bar + 8 * BAR_WO2);
                    tma2d(sb + OFF_V, &mwo, (bi_j & 3) * 128 + 64, 256, bar + 8 * BAR_WO2);
                }
                __syncwarp();
                if (warp == 0) STAMP(13);
#pragma unroll
                for (int o = 1; o < 16; o <<= 1) gsum += __shfl_xor_sync(~0u, gsum, o);
                const float gate = bf_round(rcp(1.0f + ex2(-1.4426950408889634f * bf_round(gsum))));
                const uint32_t gv = __shfl_sync(~0u, __float_as_uint(gate) | tag, (lane & 4) * 4);
                if (lane < 8) st_rlx32(scr->g + (bi_i * 64 + bi_j * 8 + warp) * 8 + lane, gv);
            }
        }
        if (warp == 0) STAMP(4);
        {
            {
                const uint4* kp = scr->kvf + bi_j * 272 + tid;
                uint4 v0, v1;
                int n = 0;
                while (true) {
                    v0 = ld_rlx128(kp); v1 = ld_rlx128(kp + (tid < 16 ? 256 : 0));
                    if (!__any_sync(~0u, (bad4(v0, tag) | bad4(v1, tag)) & 1)) break;
                    if (++n > SPIN_LIMIT) break;
                }
                sts128(sb + OFF_KVF + tid * 16, v0.x, v0.y, v0.z, v0.w);
                if (tid < 16) sts128(sb + OFF_KVF + 4096 + tid * 16, v1.x, v1.y, v1.z, v1.w);
                bar_named(1, 256);
            }
            uint4 kf[4][3];
#pragma unroll
            for (int hh = 0; hh < 4; hh++) {
                const uint32_t a = sb + OFF_KVF + hh * 1088;
                kf[hh][0] = lds128(a + lane * 32); kf[hh][1] = lds128(a + lane * 32 + 16); kf[hh][2] = lds128(a + 1024 + q * 16);
            }
            if (warp == 0) STAMP(5);
            uint4 own[4];
#pragma unroll
            for (int hh = 0; hh < 4; hh++) {
                float c[6][4];
#pragma unroll
                for (int t = 0; t < 6; t++) { c[t][0] = c[t][1] = c[t][2] = c[t][3] = 0.f; }
                const uint32_t* a = pq[hh];
                const bool od = g & 1;
                mma16816(c[0], a[0], a[1], a[2], a[3], od ? 0x3f803f80u : kf[hh][2].x, od ? 0x3f803f80u : kf[hh][2].y);
                mma16816(c[1], a[4], a[5], a[6], a[7], od ? 0x3f803f80u : kf[hh][2].z, od ? 0x3f803f80u : kf[hh][2].w);
                mma16816(c[2], a[0], a[1], a[2], a[3], kf[hh][0].x, kf[hh][0].y);
                mma16816(c[3], a[0], a[1], a[2], a[3], kf[hh][0].z, kf[hh][0].w);
                mma16816(c[4], a[4], a[5], a[6], a[7], kf[hh][1].x, kf[hh][1].y);
                mma16816(c[5], a[4], a[5], a[6], a[7], kf[hh][1].z, kf[hh][1].w);
                uint32_t w[4];
#pragma unroll
                for (int k = 0; k < 2; k++) {
                    const float rho = c[0][2 * k + 1] * rcp(c[1][2 * k + 1]);
                    const float r = rcp(fmaf(c[0][2 * k + 1], 1e-6f, fmaf(rho, c[1][2 * k], c[0][2 * k]))), rr = r * rho;
                    w[k] = pack2(fmaf(c[4][2 * k], rr, c[2][2 * k] * r), fmaf(c[4][2 * k + 1], rr, c[2][2 * k + 1] * r));
                    w[2 + k] = pack2(fmaf(c[5][2 * k], rr, c[3][2 * k] * r), fmaf(c[5][2 * k + 1], rr, c[3][2 * k + 1] * r));
                }
                own[hh] = tag4(w[0], w[1], w[2], w[3], tag);
            }
            uint4* og = scr->o + ((bi_i * 8 + warp) * 32 + bi_j * 4) * 32 + lane;
#pragma unroll
            for (int hh = 0; hh < 4; hh++) st_rlx128(og + hh * 32, own[hh]);
        }
        if (warp == 0) STAMP(6);
        float oc[64];
        const int slab = bi_i * 8 + (bi_j >> 2) * 4 + w4;
        const uint8_t* yb = (const uint8_t*)scr->y + (size_t)((bi_j & 3) * 32 + wg * 16 + (q >> 1)) * 16384 + slab * 128 + g * 16 + (q & 1) * 8;
        const unsigned* gp = scr->g + (slab * 8 + (g >> 1)) * 8 + (g & 1) * 4;
        uint2 yv[8]; unsigned g0, g1;
        {
            const uint4* osrc = scr->o + (slab * 32 + wg * 16) * 32 + lane;
            uint4 fr[16];
            const unsigned* probe = (const unsigned*)(osrc - lane + ((lane & 3) * 4 + 3) * 32 + 31) + 2;
#pragma unroll
            for (int k = 0; k < 16; k++) fr[k] = ld_rlx128(osrc + k * 32);
            mbar_wait(bar + 8 * (wg ? BAR_WO2 : BAR_WO), 0);
            const uint64_t dw = mkdesc(sb + wg * 2 * SLOT, wg ? 32768 : SLOT, 1024);
            if (warp == 0) STAMP(14);
#pragma unroll
            for (int s = 0; s < 4; s++) {
                int n = 0;
                while (__any_sync(~0u, (bad4(fr[4 * s], tag) | bad4(fr[4 * s + 1], tag) | bad4(fr[4 * s + 2], tag) | bad4(fr[4 * s + 3], tag)) & 1)) {
                    while ((__ballot_sync(~0u, (ld_rlx(probe) ^ tag) & 1) >> s) & 1) { if (++n > SPIN_LIMIT) break; }
#pragma unroll
                    for (int k = 4 * s; k < 16; k++) if (bad4(fr[k], tag) & 1) fr[k] = ld_rlx128(osrc + k * 32);
                    if (++n > SPIN_LIMIT) break;
                }
                wg_fence();
#pragma unroll
                for (int hh = 0; hh < 4; hh++) wgmma128_rs(oc, fr[4 * s + hh], dw + 128 * (4 * s + hh), (s | hh) != 0);
                wg_commit();
                if (s == 1) {
                    wg_wait<1>();
#pragma unroll
                    for (int nt = 0; nt < 8; nt++) yv[nt] = ld_rlx64(yb + nt * 32768);
                    g0 = ld_rlx(gp); g1 = ld_rlx(gp + 32);
                }
            }
            if (warp == 0) STAMP(7);
            {
                const unsigned* yprobe = scr->yflag + ((bi_j & 3) * 32 + wg * 16 + (lane & 15)) * 8;
                int n = 0;
                while (true) {
                    uint32_t bad = (g0 ^ tag) | (g1 ^ tag);
#pragma unroll
                    for (int nt = 0; nt < 8; nt++) bad |= yv[nt].x ^ tag;
                    if (!__any_sync(~0u, bad & 1)) break;
                    while (__any_sync(~0u, (ld_rlx(yprobe) ^ tag) & 1)) { if (++n > SPIN_LIMIT) break; }
#pragma unroll
                    for (int nt = 0; nt < 8; nt++) yv[nt] = ld_rlx64(yb + nt * 32768);
                    g0 = ld_rlx(gp); g1 = ld_rlx(gp + 32);
                    if (++n > SPIN_LIMIT) break;
                }
            }
            if (warp == 0) STAMP(28);
            wg_wait<0>();
            fence_regs<64>(oc);
        }
        {
            bar_named(3 + wg, 128);
            const uint32_t xw = sb + wg * 2 * SLOT + (tid & 127) * 16, xr = sb + (wg ^ 1) * 2 * SLOT + (tid & 127) * 16;
#pragma unroll
            for (int r = 0; r < 8; r++) {
                const float* o = oc + 4 * r;
                sts128(xw + r * 2048, __float_as_uint(wg ? o[0] : o[32]), __float_as_uint(wg ? o[1] : o[33]), __float_as_uint(wg ? o[2] : o[34]), __float_as_uint(wg ? o[3] : o[35]));
            }
#pragma unroll
            for (int r = 0; r < 32; r++) oc[r] = wg ? oc[32 + r] : oc[r];
            bar_named(1, 256);
            if (warp == 0) STAMP(8);
            const float ga = bf_hi(g0), gb = bf_hi(g1);
            const float ha = bf_round(1.0f - ga), hb = bf_round(1.0f - gb);
            uint32_t w[8][2];
#pragma unroll
            for (int nt = 0; nt < 8; nt++) {
                const uint4 p = lds128(xr + nt * 2048);
                w[nt][0] = pack2(fmaf(ga, oc[4 * nt] + __uint_as_float(p.x), ha * bf_lo(yv[nt].x)), fmaf(ga, oc[4 * nt + 1] + __uint_as_float(p.y), ha * bf_hi(yv[nt].x)));
                w[nt][1] = pack2(fmaf(gb, oc[4 * nt + 2] + __uint_as_float(p.z), hb * bf_lo(yv[nt].y)), fmaf(gb, oc[4 * nt + 3] + __uint_as_float(p.w), hb * bf_hi(yv[nt].y)));
            }
            const uint32_t ob = sb + wg * 2 * SLOT + 16384 + w4 * 2048;
#pragma unroll
            for (int nt = 0; nt < 8; nt += 2)
                stsm4(ob + (lane & 15) * 128 + (((nt + shi) ^ (lane & 7)) << 4), w[nt][0], w[nt][1], w[nt + 1][0], w[nt + 1][1]);
            __syncwarp();
            bf16* op = out + (size_t)(slab * 16) * 512 + (bi_j & 3) * 128 + wg * 64 + (lane & 7) * 8;
#pragma unroll
            for (int it = 0; it < 4; it++) {
                const int r = it * 4 + (lane >> 3);
                uint4 v = lds128(ob + r * 128 + (((lane & 7) ^ (r & 7)) << 4));
                *(uint4*)(op + r * 512) = v;
            }
        }
        if (warp == 0) STAMP(10);
    } else {
        const uint32_t kt = sb + OFF_KT + w4 * KT_STRIDE;
        const uint32_t spare = sb + (w4 < 2 ? OFF_SP0 : OFF_SP1) + (w4 & 1) * 4096;
#pragma unroll
        for (int v = 0; v < 8; v++) if (v * 32 + lane < KT_STRIDE / 16) sts128(kt + (v * 32 + lane) * 16, 0, 0, 0, 0);
        if (lane < 14) sts128(buf + (lane >= 7 ? W3_OFF - 112 : 0) + lane * 16, 0, 0, 0, 0);
        __syncwarp();
        if (lane == 0) kc[0][0] += (ch & 1) ? bf_hi(pds) : bf_lo(pds);
#pragma unroll
        for (int i = 0; i < 2; i++) {
            const int be = g + 8 * i;
#pragma unroll
            for (int t = 0; t < 2; t++) {
                const uint32_t a = kt + (64 + 128 * t + 8 * be + 2 * q) * 4;
                const uint32_t w = pack2(kc[t][2 * i + 1], kc[t][2 * i]);
                sts32(a + 4, w); sts16(a, w >> 16); sts16(a + 10, w);
            }
            {
                const int p = 256 + 128 * (q >> 1) + 8 * be + 4 * (q & 1);
                const uint32_t a = kt + (64 + p) * 4;
                const uint32_t w = pack2(kc[2][2 * i + 1], kc[2][2 * i]);
                const uint32_t aa = (w >> 16) | (w & 0xffff0000u);
                if (p != 256) { sts16(a - 4, aa); sts32(a, aa); } else sts16(a, aa);
                sts32(a + 4, aa); sts32(a + 8, w); sts16(a + 14, w);
            }
            {
                const int k = 64 + 16 * q + be;
                const uint32_t w = pack2(kc[3][2 * i], kc[3][2 * i + 1]);
                if (k != 64) sts16(kt + KT_E2 + (k - 1) * 2, w);
                else {
                    const uint32_t a = kt + (64 + 511) * 4, aa = (w << 16) | (w & 0xffffu);
                    sts16(a, w); sts32(a + 4, aa); sts32(a + 8, aa); sts32(a + 12, aa); sts16(a + 18, w);
                }
                sts16(kt + KT_E2 + KT_E2O + k * 2, w >> 16);
            }
#pragma unroll
            for (int b = 0; b < 2; b++) {
                const int k = 64 + 8 * (2 * q + b) + (be >> 1);
                const uint32_t w = pack2(kc[4][2 * i + b], 0.f);
                const bool k1024 = !(be & 1) && k == 64;
                const uint32_t a = k3 + (k1024 ? 188 + 64 : ((be & 1) ? 94 + k : k - 1)) * 4 - 34 * 4;
                sts16(a, w);
                if (!((be & 1) && k == 127)) sts16(a + 6, w);
                if (k1024) sts16(kt + KT_E2 + 127 * 2, w);
            }
        }
        if (lane == 0) sts16(k3 + (127 - 34) * 4, pack2(kc[5][0], 0.f));
        asm volatile("fence.proxy.async.shared::cta;" ::: "memory");
        bar_named(2, 128);
        if (warp == 8) STAMP(17);
        float y[4][16];
#pragma unroll
        for (int c = 0; c < 4; c++) {
#pragma unroll
            for (int r = 0; r < 16; r++) y[c][r] = 0.f;
            fence_regs<16>(y[c]);
        }
        {
            uint32_t Q[2][4][4];
            uint32_t ka = sb + OFF_KT + (64 - 48 + 16 * w4 + g - 2 * q) * 4;
            uint64_t du = mkdesc(sb + OFF_U + U_PAD + 96, 16, 1024);
            auto ldq = [&](uint32_t (*qd)[4]) {
#pragma unroll
                for (int c = 0; c < 4; c++) {
                    qd[c][0] = lds32(ka + c * KT_STRIDE); qd[c][1] = lds32(ka + c * KT_STRIDE + 32); qd[c][2] = lds32(ka + c * KT_STRIDE - 32); qd[c][3] = qd[c][0];
                }
                ka += 64;
            };
            ldq(Q[0]);
#pragma unroll 1
            for (int it = 0; it < 19; it++) {
#pragma unroll
                for (int hb = 0; hb < 2; hb++) {
                    wg_fence();
#pragma unroll
                    for (int c = 0; c < 4; c++) wgmma32_rs(y[c], Q[hb][c], du + c * (U_STRIDE >> 4));
                    wg_commit();
                    du -= 2;
                    wg_wait<1>();
                    ldq(Q[hb ^ 1]);
                }
            }
        }
        if (warp == 8) STAMP(18);
        mbar_wait(bar + 8 * BAR_WO, 0);
        {
            const uint32_t u0 = sb + OFF_U + w4 * U_STRIDE + U_PAD + lane * 16;
#pragma unroll 1
            for (int rho = 0; rho < 6; rho++) {
                const int ci = lane + 32 * rho;
                uint4 e4[4];
#pragma unroll
                for (int v = 0; v < 4; v++) { const uint32_t a = u0 + rho * 512 + (v - 3) * 16; e4[v] = lds128(a ^ ((a >> 3) & 0x70)); }
                float S[29];
                const uint32_t* ew = (const uint32_t*)e4;
                S[3] = 0.f;
#pragma unroll
                for (int k = 4; k <= 28; k++) S[k] = S[k - 1] + ((k & 1) ? bf_hi(ew[k >> 1]) : bf_lo(ew[k >> 1]));
                auto win = [&](int lo, int hi, uint32_t a) {
                    sts128(a, pack2(S[hi] - S[lo - 1], S[hi + 1] - S[lo]), pack2(S[hi + 2] - S[lo + 1], S[hi + 3] - S[lo + 2]),
                           pack2(S[hi + 4] - S[lo + 3], S[hi + 5] - S[lo + 4]), pack2(S[hi + 6] - S[lo + 5], S[hi + 7] - S[lo + 6]));
                };
                win(14, 18, buf + W5_OFF + 112 + ci * 16); win(19, 21, buf + W3_OFF + 112 + ci * 16);
                if (rho < 4) {
                    const uint32_t sw = (ci ^ ((ci >> 3) & 1)) << 4;
                    win(4, 12, buf + W9_OFF + sw); win(13, 19, spare + sw); win(20, 21, spare + 2048 + sw);
                }
            }
        }
        bar_named(2, 128);
        if (warp == 8) STAMP(23);
        {
            uint32_t Q[2][4][4];
            uint32_t wa = sb + OFF_BUF + (15 - (lane >> 4) * 8 - (lane & 7) + 2 * w4 + ((lane >> 3) & 1)) * 16;
            uint64_t de = (uint64_t)(((sb + OFF_KT + KT_E2 - 16) & 0x3FFFF) >> 4) | ((uint64_t)1 << 16) | ((uint64_t)8 << 32);
#pragma unroll
            for (int c = 0; c < 4; c++) ldsm4t(Q[0][c], wa + c * BUF_STRIDE);
#pragma unroll 1
            for (int s = 0; s < 12; s++) {
#pragma unroll
                for (int ph = 0; ph < 2; ph++) {
                    wg_fence();
#pragma unroll
                    for (int c = 0; c < 4; c++) wgmma32_rs(y[c], Q[ph][c], de + c * (KT_STRIDE >> 4) + ph * (KT_E2O >> 4));
                    wg_commit();
                    wg_wait<1>();
#pragma unroll
                    for (int c = 0; c < 4; c++) ldsm4t(Q[ph ^ 1][c], wa + c * BUF_STRIDE + (ph ? 256 : W3_OFF));
                }
                wa += 256; de -= 2;
            }
        }
        wg_wait<0>();
#pragma unroll
        for (int c = 0; c < 4; c++) fence_regs<16>(y[c]);
        if (warp == 8) STAMP(19);
        {
            const int ap = (lane & 7) + (lane >> 4) * 8;
            const uint32_t loff = ((2 * ap + ((lane >> 3) & 1)) ^ ((ap >> 2) & 1)) << 4;
#pragma unroll 1
            for (int ph = 0; ph < 3; ph++) {
                const uint32_t ka = sb + OFF_K3 + (ph * 94 + 4 * g + w4 - 2 * q - 34) * 4;
#pragma unroll
                for (int c = 0; c < 4; c++) {
                    const uint32_t wb = (ph ? sb + (c < 2 ? OFF_SP0 : OFF_SP1) + (c & 1) * 4096 + (ph - 1) * 2048 : sb + OFF_BUF + c * BUF_STRIDE + W9_OFF) + loff;
                    uint32_t B[4][2];
#pragma unroll
                    for (int d = 0; d < 4; d++) { B[d][0] = lds32(ka + c * K3_STRIDE + (48 + 16 * d) * 4); B[d][1] = lds32(ka + c * K3_STRIDE + (40 + 16 * d) * 4); }
#pragma unroll
                    for (int s = 0; s < 4; s++) {
                        uint32_t A[4];
                        ldsm4t(A, wb + s * 512);
                        if (s < 2) mma16816(y[c] + 8, A[0], A[1], A[2], A[3], B[1 - s][0], B[1 - s][1]);
                        mma16816(y[c] + 12, A[0], A[1], A[2], A[3], B[3 - s][0], B[3 - s][1]);
                    }
                }
            }
        }
        uint4* yp = scr->y + bi * 1024 + (8 * q + w4) * 8 + g;
#pragma unroll
        for (int j = 0; j < 4; j++)
#pragma unroll
            for (int b = 0; b < 2; b++)
                st_rlx128(yp + (32 * j + 4 * b) * 8, tag4(pack2(y[0][4 * j + b], y[1][4 * j + b]), pack2(y[0][4 * j + 2 + b], y[1][4 * j + 2 + b]),
                                                          pack2(y[2][4 * j + b], y[3][4 * j + b]), pack2(y[2][4 * j + 2 + b], y[3][4 * j + 2 + b]), tag));
        bar_named(2, 128);
        if (st < 8) st_rlx32(scr->yflag + bi * 8 + st, tag);
        if (warp == 8) STAMP(20);
    }
    __syncthreads();
    if (tid == 0) atomicAdd(scr->done, 1u);
}

typedef CUresult (*EncFn)(CUtensorMap*, CUtensorMapDataType, cuuint32_t, void*, const cuuint64_t*, const cuuint64_t*, const cuuint32_t*,
                          const cuuint32_t*, CUtensorMapInterleave, CUtensorMapSwizzle, CUtensorMapL2promotion, CUtensorMapFloatOOBfill);

extern "C" void kernel_launch(void* const* d_in, const int* in_sizes, int n_in, void* d_out, int out_size) {
    static EncFn enc = nullptr;
    static Scratch* scr = nullptr;
    if (!enc) {
        cudaGetSymbolAddress((void**)&scr, g_scr);
        cudaDriverEntryPointQueryResult qr;
        cudaGetDriverEntryPoint("cuTensorMapEncodeTiled", (void**)&enc, cudaEnableDefault, &qr);
        cudaFuncSetAttribute(fused_kernel, cudaFuncAttributeMaxDynamicSharedMemorySize, SMEM_BYTES);
    }
    CUtensorMap mx, mw, mwo;
    const cuuint32_t es[3] = {1, 1, 1};
    {
        cuuint64_t d[2] = {512, 2048}, s[1] = {1024}; cuuint32_t b[2] = {64, 128};
        enc(&mx, CU_TENSOR_MAP_DATA_TYPE_BFLOAT16, 2, d_in[0], d, s, b, es, CU_TENSOR_MAP_INTERLEAVE_NONE, CU_TENSOR_MAP_SWIZZLE_128B,
            CU_TENSOR_MAP_L2_PROMOTION_L2_128B, CU_TENSOR_MAP_FLOAT_OOB_FILL_NONE);
    }
    {
        cuuint64_t d[3] = {512, 512, 3}, s[2] = {3072, 1024}; cuuint32_t b[3] = {64, 64, 3};
        enc(&mw, CU_TENSOR_MAP_DATA_TYPE_BFLOAT16, 3, d_in[1], d, s, b, es, CU_TENSOR_MAP_INTERLEAVE_NONE, CU_TENSOR_MAP_SWIZZLE_128B,
            CU_TENSOR_MAP_L2_PROMOTION_L2_128B, CU_TENSOR_MAP_FLOAT_OOB_FILL_NONE);
    }
    {
        cuuint64_t d[2] = {512, 512}, s[1] = {1024}; cuuint32_t b[2] = {64, 256};
        enc(&mwo, CU_TENSOR_MAP_DATA_TYPE_BFLOAT16, 2, d_in[3], d, s, b, es, CU_TENSOR_MAP_INTERLEAVE_NONE, CU_TENSOR_MAP_SWIZZLE_128B,
            CU_TENSOR_MAP_L2_PROMOTION_L2_128B, CU_TENSOR_MAP_FLOAT_OOB_FILL_NONE);
    }
    fused_kernel<<<128, 384, SMEM_BYTES, cudaStreamPerThread>>>(
        scr, (const bf16*)d_in[5], (const bf16*)d_in[6], (const bf16*)d_in[7], (const bf16*)d_in[8], (const bf16*)d_in[9],
        (const bf16*)d_in[10], (const bf16*)d_in[2], (const bf16*)d_in[11], (bf16*)d_out, mx, mw, mwo);
}
```

```cpp
#include <cuda_runtime.h>
#include <cuda.h>
#include <cuda_bf16.h>
#include <stdint.h>

typedef __nv_bfloat16 bf16;

struct Scratch {
    uint4 xt[128 * 1024];
    uint4 o[16 * 8 * 32 * 32];
    uint4 y[128 * 1024];
    uint4 kvp[8 * 16 * 544];
    uint4 kvf[8 * 4 * 68];
    unsigned g[1024 * 8];
    unsigned yflag[128 * 8];
    unsigned xcnt[8 * 32];
    unsigned done[32];
};
__device__ Scratch g_scr;
#define STAMP(n)

constexpr int SLOT = 40960;
constexpr int OFF_SP0 = 32768, OFF_SP1 = SLOT + 32768;
constexpr int OFF_P = 2 * SLOT, OFF_V = OFF_P + 32768;
constexpr int OFF_X = OFF_V + 32768;
constexpr int KT_BYTES = 3824, KT_E2 = 2688, KT_E2O = 624;
__host__ __device__ constexpr int kt_off(int c) { return (c < 2 ? OFF_SP0 : OFF_SP1) + (c & 1) * 4096; }
constexpr int OFF_U = 4 * SLOT, U_STRIDE = 41 * 128, U_PAD = 9 * 128;
constexpr int OFF_BUF = OFF_U + 4 * U_STRIDE, BUF_STRIDE = 8448;
constexpr int OFF_K3 = OFF_BUF + 4 * BUF_STRIDE, K3_STRIDE = 1136;
constexpr int OFF_WPHI = OFF_K3 + 4 * K3_STRIDE;
constexpr int OFF_GW = OFF_WPHI + 2048;
constexpr int OFF_KVF = OFF_GW + 1024;
constexpr int OFF_BAR = OFF_KVF + 4352;
constexpr int SMEM_BYTES = OFF_BAR + 128 + 128;
static_assert(SMEM_BYTES <= 232448 && OFF_BUF % 128 == 0, "smem");
constexpr int W5_OFF = 0, W3_OFF = 3184, W9_OFF = 6368;
constexpr int BAR_FULL = 0, BAR_WPHI = 4, BAR_WO = 5, BAR_XT = 6, BAR_DONE = 7, BAR_WO2 = 8, OFF_CNT = 96;
constexpr int SPIN_LIMIT = 1 << 17;

__device__ __forceinline__ uint32_t s2u(const void* p) { return (uint32_t)__cvta_generic_to_shared(p); }
__device__ __forceinline__ void mbar_init(uint32_t b, int c) { asm volatile("mbarrier.init.shared::cta.b64 [%0],%1;" ::"r"(b), "r"(c) : "memory"); }
__device__ __forceinline__ void mbar_expect(uint32_t b, int bytes) { asm volatile("mbarrier.arrive.expect_tx.shared::cta.b64 _,[%0],%1;" ::"r"(b), "r"(bytes) : "memory"); }
__device__ __forceinline__ void mbar_arrive(uint32_t b) { asm volatile("mbarrier.arrive.shared::cta.b64 _,[%0];" ::"r"(b) : "memory"); }
__device__ __forceinline__ bool mbar_try(uint32_t b, int ph) {
    uint32_t ok;
    asm volatile("{.reg .pred p; mbarrier.try_wait.parity.shared::cta.b64 p,[%1],%2; selp.u32 %0,1,0,p;}" : "=r"(ok) : "r"(b), "r"(ph) : "memory");
    return ok;
}
__device__ __forceinline__ void mbar_wait(uint32_t b, int ph) {
    if ((threadIdx.x & 31) == 0) {
        int n = 0;
#pragma unroll 1
        while (!mbar_try(b, ph)) { if (++n > SPIN_LIMIT) break; }
    }
    __syncwarp();
}
__device__ __forceinline__ void tma2d(uint32_t dst, const CUtensorMap* m, int c0, int c1, uint32_t bar) {
    asm volatile("cp.async.bulk.tensor.2d.shared::cluster.global.mbarrier::complete_tx::bytes [%0],[%1,{%3,%4}],[%2];" ::"r"(dst), "l"(m), "r"(bar), "r"(c0), "r"(c1) : "memory");
}
__device__ __forceinline__ void tma3d(uint32_t dst, const CUtensorMap* m, int c0, int c1, int c2, uint32_t bar) {
    asm volatile("cp.async.bulk.tensor.3d.shared::cluster.global.mbarrier::complete_tx::bytes [%0],[%1,{%3,%4,%5}],[%2];" ::"r"(dst), "l"(m), "r"(bar), "r"(c0), "r"(c1), "r"(c2) : "memory");
}
__device__ __forceinline__ void bulk_g2s(uint32_t dst, const void* src, int bytes, uint32_t bar) {
    asm volatile("cp.async.bulk.shared::cluster.global.mbarrier::complete_tx::bytes [%0],[%1],%2,[%3];" ::"r"(dst), "l"(src), "r"(bytes), "r"(bar) : "memory");
}
__device__ __forceinline__ uint64_t mkdesc(uint32_t addr, uint32_t lbo, uint32_t sbo) {
    return (uint64_t)((addr & 0x3FFFF) >> 4) | ((uint64_t)(lbo >> 4) << 16) | ((uint64_t)(sbo >> 4) << 32) | ((uint64_t)1 << 62);
}
__device__ __forceinline__ void wg_fence() { asm volatile("wgmma.fence.sync.aligned;" ::: "memory"); }
__device__ __forceinline__ void wg_commit() { asm volatile("wgmma.commit_group.sync.aligned;" ::: "memory"); }
template <int N> __device__ __forceinline__ void wg_wait() { asm volatile("wgmma.wait_group.sync.aligned %0;" ::"n"(N) : "memory"); }
template <int N> __device__ __forceinline__ void fence_regs(float* d) {
#pragma unroll
    for (int i = 0; i < N; i++) asm volatile("" : "+f"(d[i])::"memory");
}
#define R8(d, o) "+f"(d[o]), "+f"(d[o + 1]), "+f"(d[o + 2]), "+f"(d[o + 3]), "+f"(d[o + 4]), "+f"(d[o + 5]), "+f"(d[o + 6]), "+f"(d[o + 7])
__device__ __forceinline__ void wgmma192(float* d, uint64_t da, uint64_t db) {
    asm volatile("wgmma.mma_async.sync.aligned.m64n192k16.f32.bf16.bf16 {"
                 "%0,%1,%2,%3,%4,%5,%6,%7,%8,%9,%10,%11,%12,%13,%14,%15,%16,%17,%18,%19,%20,%21,%22,%23,%24,%25,%26,%27,%28,%29,%30,%31,"
                 "%32,%33,%34,%35,%36,%37,%38,%39,%40,%41,%42,%43,%44,%45,%46,%47,%48,%49,%50,%51,%52,%53,%54,%55,%56,%57,%58,%59,%60,%61,%62,%63,"
                 "%64,%65,%66,%67,%68,%69,%70,%71,%72,%73,%74,%75,%76,%77,%78,%79,%80,%81,%82,%83,%84,%85,%86,%87,%88,%89,%90,%91,%92,%93,%94,%95},"
                 "%96,%97,1,1,1,0,1;"
                 : R8(d, 0), R8(d, 8), R8(d, 16), R8(d, 24), R8(d, 32), R8(d, 40), R8(d, 48), R8(d, 56), R8(d, 64), R8(d, 72), R8(d, 80), R8(d, 88)
                 : "l"(da), "l"(db));
}
__device__ __forceinline__ void wgmma64_tt(float* d, uint64_t da, uint64_t db, int sc) {
    asm volatile("{.reg .pred p; setp.ne.b32 p,%34,0; wgmma.mma_async.sync.aligned.m64n64k16.f32.bf16.bf16 {"
                 "%0,%1,%2,%3,%4,%5,%6,%7,%8,%9,%10,%11,%12,%13,%14,%15,%16,%17,%18,%19,%20,%21,%22,%23,%24,%25,%26,%27,%28,%29,%30,%31},"
                 "%32,%33,p,1,1,1,1;}"
                 : R8(d, 0), R8(d, 8), R8(d, 16), R8(d, 24)
                 : "l"(da), "l"(db), "r"(sc));
}
__device__ __forceinline__ void wgmma128_rs(float* d, const uint4& a, uint64_t db, int sc) {
    asm volatile("{.reg .pred p; setp.ne.b32 p,%69,0; wgmma.mma_async.sync.aligned.m64n128k16.f32.bf16.bf16 {"
                 "%0,%1,%2,%3,%4,%5,%6,%7,%8,%9,%10,%11,%12,%13,%14,%15,%16,%17,%18,%19,%20,%21,%22,%23,%24,%25,%26,%27,%28,%29,%30,%31,"
                 "%32,%33,%34,%35,%36,%37,%38,%39,%40,%41,%42,%43,%44,%45,%46,%47,%48,%49,%50,%51,%52,%53,%54,%55,%56,%57,%58,%59,%60,%61,%62,%63},"
                 "{%64,%65,%66,%67},%68,p,1,1,1;}"
                 : R8(d, 0), R8(d, 8), R8(d, 16), R8(d, 24), R8(d, 32), R8(d, 40), R8(d, 48), R8(d, 56)
                 : "r"(a.x), "r"(a.y), "r"(a.z), "r"(a.w), "l"(db), "r"(sc));
}
__device__ __forceinline__ void wgmma32_rs(float* d, const uint32_t* a, uint64_t db) {
    asm volatile("wgmma.mma_async.sync.aligned.m64n32k16.f32.bf16.bf16 {%0,%1,%2,%3,%4,%5,%6,%7,%8,%9,%10,%11,%12,%13,%14,%15},{%16,%17,%18,%19},%20,1,1,1,0;"
                 : R8(d, 0), R8(d, 8) : "r"(a[0]), "r"(a[1]), "r"(a[2]), "r"(a[3]), "l"(db));
}
__device__ __forceinline__ void wgmma48_rs(float* d, uint32_t a0, uint32_t a1, uint32_t a2, uint32_t a3, uint64_t db) {
    asm volatile("wgmma.mma_async.sync.aligned.m64n48k16.f32.bf16.bf16 {%0,%1,%2,%3,%4,%5,%6,%7,%8,%9,%10,%11,%12,%13,%14,%15,%16,%17,%18,%19,%20,%21,%22,%23},{%24,%25,%26,%27},%28,1,1,1,0;"
                 : R8(d, 0), R8(d, 8), R8(d, 16) : "r"(a0), "r"(a1), "r"(a2), "r"(a3), "l"(db));
}
__device__ __forceinline__ void mma16816(float* c, uint32_t a0, uint32_t a1, uint32_t a2, uint32_t a3, uint32_t b0, uint32_t b1) {
    asm("mma.sync.aligned.m16n8k16.row.col.f32.bf16.bf16.f32 {%0,%1,%2,%3},{%4,%5,%6,%7},{%8,%9},{%0,%1,%2,%3};"
        : "+f"(c[0]), "+f"(c[1]), "+f"(c[2]), "+f"(c[3]) : "r"(a0), "r"(a1), "r"(a2), "r"(a3), "r"(b0), "r"(b1));
}
__device__ __forceinline__ void ldsm4(uint32_t* r, uint32_t a) {
    asm volatile("ldmatrix.sync.aligned.m8n8.x4.shared.b16 {%0,%1,%2,%3},[%4];" : "=r"(r[0]), "=r"(r[1]), "=r"(r[2]), "=r"(r[3]) : "r"(a) : "memory");
}
__device__ __forceinline__ void ldsm4t(uint32_t* r, uint32_t a) {
    asm volatile("ldmatrix.sync.aligned.m8n8.x4.trans.shared.b16 {%0,%1,%2,%3},[%4];" : "=r"(r[0]), "=r"(r[1]), "=r"(r[2]), "=r"(r[3]) : "r"(a) : "memory");
}
__device__ __forceinline__ void stsm4(uint32_t a, uint32_t r0, uint32_t r1, uint32_t r2, uint32_t r3) {
    asm volatile("stmatrix.sync.aligned.m8n8.x4.shared.b16 [%0],{%1,%2,%3,%4};" ::"r"(a), "r"(r0), "r"(r1), "r"(r2), "r"(r3) : "memory");
}
__device__ __forceinline__ uint32_t lds32(uint32_t a) { uint32_t v; asm volatile("ld.shared.b32 %0,[%1];" : "=r"(v) : "r"(a) : "memory"); return v; }
__device__ __forceinline__ uint4 lds128(uint32_t a) { uint4 v; asm volatile("ld.shared.v4.b32 {%0,%1,%2,%3},[%4];" : "=r"(v.x), "=r"(v.y), "=r"(v.z), "=r"(v.w) : "r"(a) : "memory"); return v; }
__device__ __forceinline__ void sts16(uint32_t a, uint32_t v) { asm volatile("st.shared.b16 [%0],%1;" ::"r"(a), "h"((unsigned short)v) : "memory"); }
__device__ __forceinline__ void sts32(uint32_t a, uint32_t v) { asm volatile("st.shared.b32 [%0],%1;" ::"r"(a), "r"(v) : "memory"); }
__device__ __forceinline__ void sts64(uint32_t a, uint32_t x, uint32_t y) { asm volatile("st.shared.v2.b32 [%0],{%1,%2};" ::"r"(a), "r"(x), "r"(y) : "memory"); }
__device__ __forceinline__ void sts128(uint32_t a, uint32_t x, uint32_t y, uint32_t z, uint32_t w) { asm volatile("st.shared.v4.b32 [%0],{%1,%2,%3,%4};" ::"r"(a), "r"(x), "r"(y), "r"(z), "r"(w) : "memory"); }
__device__ __forceinline__ uint32_t pack2(float lo, float hi) { uint32_t d; asm("cvt.rn.bf16x2.f32 %0,%1,%2;" : "=r"(d) : "f"(hi), "f"(lo)); return d; }
__device__ __forceinline__ float bf_lo(uint32_t v) { return __uint_as_float(v << 16); }
__device__ __forceinline__ float bf_hi(uint32_t v) { return __uint_as_float(v & 0xffff0000u); }
__device__ __forceinline__ float bf_round(float v) { return bf_lo(pack2(v, 0.f)); }
__device__ __forceinline__ uint32_t hmax2(uint32_t a, uint32_t b) { uint32_t d; asm("max.bf16x2 %0,%1,%2;" : "=r"(d) : "r"(a), "r"(b)); return d; }
__device__ __forceinline__ uint32_t hmin2(uint32_t a, uint32_t b) { uint32_t d; asm("min.bf16x2 %0,%1,%2;" : "=r"(d) : "r"(a), "r"(b)); return d; }
__device__ __forceinline__ uint32_t hmul2(uint32_t a, uint32_t b) { uint32_t d; asm("mul.rn.bf16x2 %0,%1,%2;" : "=r"(d) : "r"(a), "r"(b)); return d; }
__device__ __forceinline__ float ex2(float x) { float y; asm("ex2.approx.ftz.f32 %0,%1;" : "=f"(y) : "f"(x)); return y; }
__device__ __forceinline__ float rcp(float x) { float y; asm("rcp.approx.ftz.f32 %0,%1;" : "=f"(y) : "f"(x)); return y; }
__device__ __forceinline__ uint32_t ld_nc(const uint32_t* p) { uint32_t v; asm volatile("ld.global.nc.b32 %0,[%1];" : "=r"(v) : "l"(p)); return v; }
__device__ __forceinline__ uint2 ld_nc64(const uint2* p) { uint2 v; asm volatile("ld.global.nc.v2.b32 {%0,%1},[%2];" : "=r"(v.x), "=r"(v.y) : "l"(p)); return v; }
__device__ __forceinline__ unsigned ld_acq(const unsigned* p) { unsigned v; asm volatile("ld.acquire.gpu.global.u32 %0,[%1];" : "=r"(v) : "l"(p) : "memory"); return v; }
__device__ __forceinline__ unsigned ld_rlx(const unsigned* p) { unsigned v; asm volatile("ld.relaxed.gpu.global.u32 %0,[%1];" : "=r"(v) : "l"(p) : "memory"); return v; }
__device__ __forceinline__ uint2 ld_rlx64(const void* p) { uint2 v; asm volatile("{.reg .b64 t; ld.relaxed.gpu.global.b64 t,[%2]; mov.b64 {%0,%1},t;}" : "=r"(v.x), "=r"(v.y) : "l"(p) : "memory"); return v; }
__device__ __forceinline__ uint4 ld_rlx128(const void* p) {
    uint4 v;
    asm volatile("{.reg .b64 t,u; ld.relaxed.gpu.global.v2.b64 {t,u},[%4]; mov.b64 {%0,%1},t; mov.b64 {%2,%3},u;}" : "=r"(v.x), "=r"(v.y), "=r"(v.z), "=r"(v.w) : "l"(p) : "memory");
    return v;
}
__device__ __forceinline__ void st_rlx32(void* p, uint32_t x) { asm volatile("st.relaxed.gpu.global.u32 [%0],%1;" ::"l"(p), "r"(x) : "memory"); }
__device__ __forceinline__ void st_rlx64(void* p, uint32_t x, uint32_t y) { asm volatile("{.reg .b64 t; mov.b64 t,{%1,%2}; st.relaxed.gpu.global.b64 [%0],t;}" ::"l"(p), "r"(x), "r"(y) : "memory"); }
__device__ __forceinline__ void st_rlx128(void* p, uint4 v) {
    asm volatile("{.reg .b64 t,u; mov.b64 t,{%1,%2}; mov.b64 u,{%3,%4}; st.relaxed.gpu.global.v2.b64 [%0],{t,u};}" ::"l"(p), "r"(v.x), "r"(v.y), "r"(v.z), "r"(v.w) : "memory");
}
__device__ __forceinline__ uint32_t tagw(uint32_t w, uint32_t tag) { return (w & ~1u) | tag; }
__device__ __forceinline__ uint4 tag4(uint32_t x, uint32_t y, uint32_t z, uint32_t w, uint32_t tag) { return make_uint4(tagw(x, tag), y, tagw(z, tag), w); }
__device__ __forceinline__ uint32_t bad4(const uint4& v, uint32_t tag) { return (v.x ^ tag) | (v.z ^ tag); }
__device__ __forceinline__ void bar_named(int id, int n) { asm volatile("bar.sync %0,%1;" ::"r"(id), "r"(n) : "memory"); }

struct cf { float re, im; };
__device__ __forceinline__ cf cmul(cf a, cf b) { cf r; r.re = a.re * b.re - a.im * b.im; r.im = a.re * b.im + a.im * b.re; return r; }
__device__ __forceinline__ cf cexp_p(float arl, float ait, float p) {
    float mag = ex2(arl * p);
    float t = ait * p;
    t = (t - rintf(t)) * 6.283185307179586f;
    cf r; r.re = mag * __cosf(t); r.im = mag * __sinf(t);
    return r;
}

__device__ __forceinline__ void hedgehog2(const uint32_t* a, uint32_t wphi_addr, uint32_t (*out)[8]) {
    float p[2][2][4], mx[2][2];
#pragma unroll
    for (int h = 0; h < 2; h++) {
        uint32_t b[4];
        ldsm4t(b, wphi_addr + h * 512);
        float c0[4] = {0.f, 0.f, 0.f, 0.f}, c1[4] = {0.f, 0.f, 0.f, 0.f};
        mma16816(c0, a[4 * h], a[4 * h + 1], a[4 * h + 2], a[4 * h + 3], b[0], b[1]);
        mma16816(c1, a[4 * h], a[4 * h + 1], a[4 * h + 2], a[4 * h + 3], b[2], b[3]);
#pragma unroll
        for (int k = 0; k < 2; k++) {
            p[h][k][0] = c0[2 * k]; p[h][k][1] = c0[2 * k + 1]; p[h][k][2] = c1[2 * k]; p[h][k][3] = c1[2 * k + 1];
            mx[h][k] = fmaxf(fmaxf(p[h][k][0], p[h][k][1]), fmaxf(p[h][k][2], p[h][k][3]));
        }
    }
#pragma unroll
    for (int o = 1; o <= 2; o <<= 1)
#pragma unroll
        for (int h = 0; h < 2; h++)
#pragma unroll
            for (int k = 0; k < 2; k++) mx[h][k] = fmaxf(mx[h][k], __shfl_xor_sync(~0u, mx[h][k], o));
    const float L = 1.4426950408889634f;
    float pmin = 1.f;
#pragma unroll
    for (int h = 0; h < 2; h++)
#pragma unroll
        for (int k = 0; k < 2; k++) {
            const float m = -mx[h][k] * L;
            const float e0 = ex2(fmaf(p[h][k][0], L, m)), e1 = ex2(fmaf(p[h][k][1], L, m)), e2 = ex2(fmaf(p[h][k][2], L, m)), e3 = ex2(fmaf(p[h][k][3], L, m));
            const float p01 = e0 * e1, p23 = e2 * e3, pp = p01 * p23, r = rcp(pp), r01 = r * p23, r23 = r * p01;
            pmin = fminf(pmin, pp);
            out[h][k] = pack2(e0, e1); out[h][k + 2] = pack2(e2, e3);
            out[h][4 + k] = pack2(r01 * e1, r01 * e0); out[h][4 + k + 2] = pack2(r23 * e3, r23 * e2);
        }
    if (__builtin_expect(__any_sync(~0u, !(pmin > 1e-18f)), 0)) {
#pragma unroll
        for (int h = 0; h < 2; h++)
#pragma unroll
            for (int k = 0; k < 2; k++) {
                float m = fminf(fminf(p[h][k][0], p[h][k][1]), fminf(p[h][k][2], p[h][k][3]));
                m = fminf(m, __shfl_xor_sync(~0u, m, 1));
                m = fminf(m, __shfl_xor_sync(~0u, m, 2)) * L;
                out[h][4 + k] = pack2(ex2(fmaf(p[h][k][0], -L, m)), ex2(fmaf(p[h][k][1], -L, m)));
                out[h][4 + k + 2] = pack2(ex2(fmaf(p[h][k][2], -L, m)), ex2(fmaf(p[h][k][3], -L, m)));
            }
    }
}

__global__ void __launch_bounds__(384, 1)
fused_kernel(Scratch* __restrict__ scr, const bf16* __restrict__ logA, const bf16* __restrict__ Aim, const bf16* __restrict__ Cre,
             const bf16* __restrict__ Cim, const bf16* __restrict__ logdt, const bf16* __restrict__ Dskip, const bf16* __restrict__ wphi,
             const bf16* __restrict__ gatew, bf16* __restrict__ out,
             const __grid_constant__ CUtensorMap mx, const __grid_constant__ CUtensorMap mw, const __grid_constant__ CUtensorMap mwo) {
    extern __shared__ __align__(1024) uint8_t smem[];
    const uint32_t sb = s2u(smem);
    const int tid = threadIdx.x, warp = __shfl_sync(~0u, tid >> 5, 0), lane = tid & 31;
    const int g = lane >> 2, q = lane & 3, w4 = warp & 3;
    const int bi = blockIdx.x, bi_i = bi & 15, bi_j = bi >> 4;
    const uint32_t bar = sb + OFF_BAR;
    const int rot = (bi_j & 1) * 4;
    auto load_stage = [&](int kb) {
        const uint32_t b = bar + 8 * (BAR_FULL + (kb & 3)), d = sb + (kb & 3) * SLOT;
        const int kc = ((kb + rot) & 7) * 64;
        mbar_expect(b, SLOT);
        tma2d(d, &mx, kc, bi_i * 128, b);
        tma3d(d + 16384, &mw, bi_j * 64, kc, 0, b);
    };

    const int ch = bi * 4 + w4;
    uint2 pla, pai, pcr, pci; uint32_t pdt = 0, pds;
    if (warp >= 8) {
        pla = ld_nc64((const uint2*)logA + ch * 32 + lane); pai = ld_nc64((const uint2*)Aim + ch * 32 + lane);
        pcr = ld_nc64((const uint2*)Cre + ch * 32 + lane); pci = ld_nc64((const uint2*)Cim + ch * 32 + lane);
        pdt = ld_nc((const uint32_t*)logdt + (ch >> 1)); pds = ld_nc((const uint32_t*)Dskip + (ch >> 1));
    }
    const unsigned done0 = ld_rlx(scr->done);
    if (tid == 0) {
        for (int s = 0; s < 4; s++) mbar_init(bar + 8 * (BAR_FULL + s), 1);
        asm volatile("fence.mbarrier_init.release.cluster;" ::: "memory");
#pragma unroll 1
        for (int s = 0; s < 4; s++) load_stage(s);
        STAMP(11);
    } else if (tid == 32) {
        if (sb & 1023) __trap();
        for (int s = 0; s < 5; s++) sts32(bar + OFF_CNT + 4 * s, 0);
        mbar_init(bar + 8 * BAR_WPHI, 1); mbar_init(bar + 8 * BAR_WO, 2); mbar_init(bar + 8 * BAR_XT, 8); mbar_init(bar + 8 * BAR_DONE, 8);
        mbar_init(bar + 8 * BAR_WO2, 1);
        asm volatile("fence.mbarrier_init.release.cluster;" ::: "memory");
        mbar_expect(bar + 8 * BAR_WPHI, 3072);
        bulk_g2s(sb + OFF_GW, gatew, 1024, bar + 8 * BAR_WPHI);
        bulk_g2s(sb + OFF_WPHI, wphi + bi_j * 1024, 2048, bar + 8 * BAR_WPHI);
    } else if (tid == 64) {
        asm volatile("prefetch.tensormap [%0];" ::"l"(&mw) : "memory");
    }
    const uint32_t buf = sb + OFF_BUF + w4 * BUF_STRIDE, k3 = sb + OFF_K3 + w4 * K3_STRIDE;
    if (warp >= 8) {
#pragma unroll
        for (int v = 0; v < 3; v++) if (v * 32 + lane < K3_STRIDE / 16) sts128(k3 + (v * 32 + lane) * 16, 0, 0, 0, 0);
    }
    __syncthreads();
    asm volatile("" : "+r"(pdt));
    const unsigned epoch1 = (done0 >> 7) + 1u;
    const uint32_t tag = epoch1 & 1u;

    if (warp < 8) {
        const int wg = warp >> 2;
        if (warp == 0) STAMP(21);
        float acc[96];
        const int grow = bi_j * 16 + warp * 2 + (lane >> 4);
        const uint32_t gx_a = grow * 128 + ((((lane & 15) >> 1) ^ (grow & 7)) << 4) + (lane & 1) * 8;
        const int srow = warp * 16 + (lane & 15);
        const uint32_t srow_a = srow * 128;
        const int sx = srow & 7, shi = lane >> 4;
        auto last_of_8 = [&](int c) {
            unsigned old;
            asm volatile("atom.acq_rel.cta.shared.add.u32 %0,[%1],1;" : "=r"(old) : "r"(bar + OFF_CNT + 4 * c) : "memory");
            return (old & 7) == 7;
        };
        const int qq = (bi_i & 2) + ((lane >> 1) & 1);
        const int kvf_n = warp < 4 ? 8 : ((warp == 4 && (bi_i & 1) == 0) ? 4 : 0);
        uint2* kvf_dst = (uint2*)(scr->kvf + (bi_j * 4 + (bi_i >> 2)) * 68) +
                         (warp == 4 ? (64 + qq) * 2 + (lane & 1) : ((bi_i & 3) * 8 + w4 * 2 + (lane & 1)) * 4 + (lane >> 1));
        float gsum = 0.f;
#pragma unroll
        for (int r = 0; r < 96; r++) acc[r] = 0.f;
        fence_regs<96>(acc);
        const uint64_t da0 = mkdesc(sb + wg * 8192, 16, 1024), db0 = mkdesc(sb + 16384, 8192, 1024);
        {
            const uint32_t old = tag ^ 1u;
            const uint4 z4 = make_uint4(old, 0, old, 0);
            uint4* kvp = scr->kvp + bi * 544 + wg * 272;
            if (w4 < 2) {
#pragma unroll
                for (int f = 0; f < 4; f++) st_rlx128(kvp + w4 * 136 + lane + f * 32, z4);
            } else if (w4 == 2 && lane < 4) {
#pragma unroll
                for (int f = 0; f < 4; f++) st_rlx128(kvp + (f >> 1) * 136 + 128 + (f & 1) * 4 + lane, z4);
            }
            if (lane < kvf_n) st_rlx64(kvf_dst, old, 0);
            if (lane >= 30) st_rlx128(scr->o + ((bi_i * 8 + warp) * 32 + bi_j * 4 + 3) * 32 + lane, z4);
            if (lane < 8) st_rlx32(scr->g + (bi_i * 64 + bi_j * 8 + warp) * 8 + lane, old);
        }
        mbar_wait(bar + 8 * BAR_WPHI, 0);
#pragma unroll 1
        for (int kb = 0; kb < 8; kb++) {
            const int s = kb & 3;
            const uint64_t da = da0 + s * (SLOT >> 4), db = db0 + s * (SLOT >> 4);
            mbar_wait(bar + 8 * (BAR_FULL + s), kb >> 2);
            if (kb == 0 && warp == 0) STAMP(0);
            wg_fence();
#pragma unroll
            for (int k = 0; k < 4; k++) wgmma192(acc, da + 2 * k, db + 128 * k);
            wg_commit();
            wg_wait<1>();
            __syncwarp();
            if (lane == 0 && kb > 0 && kb < 7) {
                const int ps = (kb - 1) & 3;
                if (last_of_8(ps)) {
                    if (kb < 5) load_stage(kb + 3);
                    else {
                        mbar_expect(bar + 8 * BAR_WO, 32768);
                        tma2d(sb + ps * SLOT, &mwo, (bi_j & 3) * 128 + ps * 64, 0, bar + 8 * BAR_WO);
                    }
                }
            }
            __syncwarp();
            const uint32_t st = sb + s * SLOT;
            if (kb == (bi_j >> 1)) {
                uint32_t* xt = (uint32_t*)scr->xt + ((kb + rot) * 16 + (g >> 2)) * 4096 + (bi_i * 16 + warp * 2) * 16 + (g & 3) * 4 + q;
#pragma unroll
                for (int cb = 0; cb < 8; cb += 2) {
                    uint32_t r[4];
                    ldsm4t(r, st + srow_a + (((cb + shi) ^ sx) << 4));
                    xt[cb * 8192] = r[0]; xt[cb * 8192 + 16] = r[1]; xt[cb * 8192 + 8192] = r[2]; xt[cb * 8192 + 8192 + 16] = r[3];
                }
                __syncwarp();
                if (lane == 0) mbar_arrive(bar + 8 * BAR_XT);
            }
            {
                uint32_t x0, x1, w0, w1;
                asm volatile("ld.shared.v2.b32 {%0,%1},[%2];" : "=r"(x0), "=r"(x1) : "r"(st + gx_a) : "memory");
                asm volatile("ld.shared.v2.b32 {%0,%1},[%2];" : "=r"(w0), "=r"(w1) : "r"(sb + OFF_GW + ((kb + rot) & 7) * 128 + (lane & 15) * 8) : "memory");
                const uint32_t p0 = hmul2(x0, w0), p1 = hmul2(x1, w1);
                gsum += (bf_lo(p0) + bf_hi(p0)) + (bf_lo(p1) + bf_hi(p1));
            }
        }
        wg_wait<0>();
        fence_regs<96>(acc);
        __syncwarp();
        if (lane == 0) mbar_arrive(bar + 8 * BAR_DONE);
        if (warp == 0) STAMP(1);
        uint32_t in[32], va[16];
#pragma unroll
        for (int r = 0; r < 16; r++) {
            in[r] = pack2(acc[32 + 2 * r], acc[32 + 2 * r + 1]);
            in[16 + r] = pack2(acc[2 * r], acc[2 * r + 1]);
            va[r] = pack2(acc[64 + 2 * r], acc[64 + 2 * r + 1]);
        }
        const uint32_t wphi_a = sb + OFF_WPHI + (lane & 15) * 32 + (lane >> 4) * 16;
        uint32_t pq[4][8];
#pragma unroll 1
        for (int it = 0; it < 4; it++) {
            hedgehog2(in, wphi_a + (it & 1) * 1024, pq + 2);
#pragma unroll
            for (int r = 0; r < 24; r++) in[r] = in[r + 8];
            if (it < 2) {
#pragma unroll
                for (int hs = 0; hs < 4; hs++) {
                    float c[4] = {0.f, 0.f, 0.f, 0.f};
                    uint32_t* o = pq[2 + (hs >> 1)] + 4 * (hs & 1);
                    mma16816(c, o[0], o[1], o[2], o[3], 0x3f803f80u, 0x3f803f80u);
                    const float r0 = rcp(c[0]), r1 = rcp(c[2]);
                    const uint32_t s0 = pack2(r0, r0), s1 = pack2(r1, r1);
                    o[0] = hmul2(o[0], s0); o[1] = hmul2(o[1], s1); o[2] = hmul2(o[2], s0); o[3] = hmul2(o[3], s1);
                }
                if (it == 0) mbar_wait(bar + 8 * BAR_DONE, 0);
                const uint32_t pt = sb + OFF_P + it * 16384 + srow_a, vt = sb + OFF_V + it * 16384 + srow_a;
#pragma unroll
                for (int hl = 0; hl < 2; hl++) {
                    stsm4(pt + (((4 * hl + shi) ^ sx) << 4), pq[2 + hl][0], pq[2 + hl][1], pq[2 + hl][2], pq[2 + hl][3]);
                    stsm4(pt + (((4 * hl + 2 + shi) ^ sx) << 4), pq[2 + hl][4], pq[2 + hl][5], pq[2 + hl][6], pq[2 + hl][7]);
                    stsm4(vt + (((2 * hl + shi) ^ sx) << 4), va[4 * hl], va[4 * hl + 1], va[4 * hl + 2], va[4 * hl + 3]);
                }
                if (lane < 16) sts128(vt + ((4 ^ sx) << 4), 0x3f803f80u, 0x3f803f80u, 0x3f803f80u, 0x3f803f80u);
#pragma unroll
                for (int r = 0; r < 8; r++) va[r] = va[r + 8];
            }
            if (it == 1) {
                asm volatile("fence.proxy.async.shared::cta;" ::: "memory");
                bar_named(1, 256);
                if (warp == 0) STAMP(2);
                float d[32];
                const uint64_t dv = mkdesc(sb + OFF_V + wg * 16384, 16, 1024), dp = mkdesc(sb + OFF_P + wg * 16384, 16, 1024);
                wg_fence();
#pragma unroll
                for (int k = 0; k < 8; k++) wgmma64_tt(d, dv + 128 * k, dp + 128 * k, k != 0);
                wg_commit();
                wg_wait<0>();
                fence_regs<32>(d);
                uint4* kvp = scr->kvp + bi * 544 + wg * 272;
                if (w4 < 2) {
                    uint32_t e[16];
#pragma unroll
                    for (int r = 0; r < 16; r++) e[r] = __float_as_uint(w4 ? d[16 + r] : d[r]);
                    uint4* p = kvp + w4 * 136 + lane;
#pragma unroll
                    for (int ks = 0; ks < 2; ks++)
#pragma unroll
                        for (int nt = 0; nt < 2; nt++)
                            st_rlx128(p + (ks * 2 + nt) * 32, tag4(e[8 * ks + 2 * nt], e[8 * ks + 2 * nt + 1], e[8 * ks + 4 + 2 * nt], e[8 * ks + 4 + 2 * nt + 1], tag));
                } else if (w4 == 2 && lane < 4) {
#pragma unroll
                    for (int hl = 0; hl < 2; hl++)
#pragma unroll
                        for (int ks = 0; ks < 2; ks++)
                            st_rlx128(kvp + hl * 136 + 128 + ks * 4 + lane, tag4(__float_as_uint(d[16 * hl + 8 * ks]), __float_as_uint(d[16 * hl + 8 * ks + 1]),
                                                                                __float_as_uint(d[16 * hl + 8 * ks + 4]), __float_as_uint(d[16 * hl + 8 * ks + 5]), tag));
                }
                if (warp == 0) STAMP(3);
            }
            if (it == 2) {
#pragma unroll
                for (int r = 0; r < 8; r++) { pq[0][r] = pq[2][r]; pq[1][r] = pq[3][r]; }
                if (warp == 0) STAMP(12);
                if (kvf_n) {
                    const bool zw = warp == 4;
                    const uint4* src = scr->kvp + bi_j * (16 * 544) + (bi_i >> 2) * 136 +
                                       (zw ? (lane >> 2) * (2 * 544) + 128 + (lane & 1) * 4 + qq
                                           : (lane >> 3) * (4 * 544) + ((lane >> 1) & 3) * 32 + (bi_i & 3) * 8 + warp * 2 + (lane & 1));
                    const int s23 = zw ? 0 : 2 * 544;
                    uint4 v[4];
                    int n = 0;
#pragma unroll 1
                    while (true) {
                        v[0] = ld_rlx128(src); v[1] = ld_rlx128(src + 544); v[2] = ld_rlx128(src + s23); v[3] = ld_rlx128(src + s23 + 544);
                        if (!__any_sync(~0u, (bad4(v[0], tag) | bad4(v[1], tag) | bad4(v[2], tag) | bad4(v[3], tag)) & 1)) break;
                        if (++n > SPIN_LIMIT) break;
                    }
                    float f[4];
                    f[0] = __uint_as_float(v[2].x) + __uint_as_float(v[3].x); f[1] = __uint_as_float(v[2].y) + __uint_as_float(v[3].y);
                    f[2] = __uint_as_float(v[2].z) + __uint_as_float(v[3].z); f[3] = __uint_as_float(v[2].w) + __uint_as_float(v[3].w);
                    float e0 = __uint_as_float(v[0].x) + __uint_as_float(v[1].x), e1 = __uint_as_float(v[0].y) + __uint_as_float(v[1].y);
                    float e2 = __uint_as_float(v[0].z) + __uint_as_float(v[1].z), e3 = __uint_as_float(v[0].w) + __uint_as_float(v[1].w);
                    if (zw) {
                        e0 = __shfl_xor_sync(~0u, f[0], 4); e1 = __shfl_xor_sync(~0u, f[1], 4);
                        e2 = __shfl_xor_sync(~0u, f[2], 4); e3 = __shfl_xor_sync(~0u, f[3], 4);
                    }
                    f[0] += e0; f[1] += e1; f[2] += e2; f[3] += e3;
#pragma unroll
                    for (int o = 8; o <= 16; o <<= 1)
#pragma unroll
                        for (int r = 0; r < 4; r++) f[r] += __shfl_xor_sync(~0u, f[r], o);
                    if (lane < kvf_n) st_rlx64(kvf_dst, tagw(pack2(f[0], f[1]), tag), pack2(f[2], f[3]));
                }
                __syncwarp();
                if (lane == 0 && last_of_8(4)) {
                    mbar_expect(bar + 8 * BAR_WO2, 65536);
                    tma2d(sb + 2 * SLOT, &mwo, (bi_j & 3) * 128, 256, bar + 8 * BAR_WO2);
                    tma2d(sb + OFF_V, &mwo, (bi_j & 3) * 128 + 64, 256, bar + 8 * BAR_WO2);
                }
                __syncwarp();
                if (warp == 0) STAMP(13);
#pragma unroll
                for (int o = 1; o < 16; o <<= 1) gsum += __shfl_xor_sync(~0u, gsum, o);
                const float gate = bf_round(rcp(1.0f + ex2(-1.4426950408889634f * bf_round(gsum))));
                const uint32_t gv = __shfl_sync(~0u, __float_as_uint(gate) | tag, (lane & 4) * 4);
                if (lane < 8) st_rlx32(scr->g + (bi_i * 64 + bi_j * 8 + warp) * 8 + lane, gv);
            }
        }
        if (warp == 0) STAMP(4);
        {
            {
                const uint4* kp = scr->kvf + bi_j * 272 + tid;
                uint4 v0, v1;
                int n = 0;
#pragma unroll 1
                while (true) {
                    v0 = ld_rlx128(kp); v1 = ld_rlx128(kp + (tid < 16 ? 256 : 0));
                    if (!__any_sync(~0u, (bad4(v0, tag) | bad4(v1, tag)) & 1)) break;
                    if (++n > SPIN_LIMIT) break;
                }
                sts128(sb + OFF_KVF + tid * 16, v0.x, v0.y, v0.z, v0.w);
                if (tid < 16) sts128(sb + OFF_KVF + 4096 + tid * 16, v1.x, v1.y, v1.z, v1.w);
                bar_named(1, 256);
            }
            uint4 kf[4][3];
#pragma unroll
            for (int hh = 0; hh < 4; hh++) {
                const uint32_t a = sb + OFF_KVF + hh * 1088;
                kf[hh][0] = lds128(a + lane * 32); kf[hh][1] = lds128(a + lane * 32 + 16); kf[hh][2] = lds128(a + 1024 + q * 16);
            }
            if (warp == 0) STAMP(5);
            uint4 own[4];
#pragma unroll
            for (int hh = 0; hh < 4; hh++) {
                float c[6][4];
#pragma unroll
                for (int t = 0; t < 6; t++) { c[t][0] = c[t][1] = c[t][2] = c[t][3] = 0.f; }
                const uint32_t* a = pq[hh];
                const bool od = g & 1;
                mma16816(c[0], a[0], a[1], a[2], a[3], od ? 0x3f803f80u : kf[hh][2].x, od ? 0x3f803f80u : kf[hh][2].y);
                mma16816(c[1], a[4], a[5], a[6], a[7], od ? 0x3f803f80u : kf[hh][2].z, od ? 0x3f803f80u : kf[hh][2].w);
                mma16816(c[2], a[0], a[1], a[2], a[3], kf[hh][0].x, kf[hh][0].y);
                mma16816(c[3], a[0], a[1], a[2], a[3], kf[hh][0].z, kf[hh][0].w);
                mma16816(c[4], a[4], a[5], a[6], a[7], kf[hh][1].x, kf[hh][1].y);
                mma16816(c[5], a[4], a[5], a[6], a[7], kf[hh][1].z, kf[hh][1].w);
                uint32_t w[4];
#pragma unroll
                for (int k = 0; k < 2; k++) {
                    const float rho = c[0][2 * k + 1] * rcp(c[1][2 * k + 1]);
                    const float r = rcp(fmaf(c[0][2 * k + 1], 1e-6f, fmaf(rho, c[1][2 * k], c[0][2 * k]))), rr = r * rho;
                    w[k] = pack2(fmaf(c[4][2 * k], rr, c[2][2 * k] * r), fmaf(c[4][2 * k + 1], rr, c[2][2 * k + 1] * r));
                    w[2 + k] = pack2(fmaf(c[5][2 * k], rr, c[3][2 * k] * r), fmaf(c[5][2 * k + 1], rr, c[3][2 * k + 1] * r));
                }
                own[hh] = tag4(w[0], w[1], w[2], w[3], tag);
            }
            uint4* og = scr->o + ((bi_i * 8 + warp) * 32 + bi_j * 4) * 32 + lane;
#pragma unroll
            for (int hh = 0; hh < 4; hh++) st_rlx128(og + hh * 32, own[hh]);
        }
        if (warp == 0) STAMP(6);
        float oc[64];
        const int slab = bi_i * 8 + (bi_j >> 2) * 4 + w4;
        const uint8_t* yb = (const uint8_t*)scr->y + (size_t)((bi_j & 3) * 32 + wg * 16 + (q >> 1)) * 16384 + slab * 128 + g * 16 + (q & 1) * 8;
        const unsigned* gp = scr->g + (slab * 8 + (g >> 1)) * 8 + (g & 1) * 4;
        uint2 yv[8]; unsigned g0, g1;
        {
            const uint4* osrc = scr->o + (slab * 32 + wg * 16) * 32 + lane;
            uint4 fr[16];
            const unsigned* probe = (const unsigned*)(osrc - lane + ((lane & 3) * 4 + 3) * 32 + 31) + 2;
#pragma unroll
            for (int k = 0; k < 16; k++) fr[k] = ld_rlx128(osrc + k * 32);
            mbar_wait(bar + 8 * (wg ? BAR_WO2 : BAR_WO), 0);
            const uint64_t dw = mkdesc(sb + wg * 2 * SLOT, wg ? 32768 : SLOT, 1024);
            if (warp == 0) STAMP(14);
#pragma unroll
            for (int s = 0; s < 4; s++) {
                int n = 0;
#pragma unroll 1
                while (__builtin_expect(__any_sync(~0u, (bad4(fr[4 * s], tag) | bad4(fr[4 * s + 1], tag) | bad4(fr[4 * s + 2], tag) | bad4(fr[4 * s + 3], tag)) & 1), 0)) {
#pragma unroll 1
                    while ((__ballot_sync(~0u, (ld_rlx(probe) ^ tag) & 1) >> s) & 1) { if (++n > SPIN_LIMIT) break; }
#pragma unroll
                    for (int k = 4 * s; k < 16; k++) if (bad4(fr[k], tag) & 1) fr[k] = ld_rlx128(osrc + k * 32);
                    if (++n > SPIN_LIMIT) break;
                }
                wg_fence();
#pragma unroll
                for (int hh = 0; hh < 4; hh++) wgmma128_rs(oc, fr[4 * s + hh], dw + 128 * (4 * s + hh), (s | hh) != 0);
                wg_commit();
                if (s == 1) {
                    wg_wait<1>();
#pragma unroll
                    for (int nt = 0; nt < 8; nt++) yv[nt] = ld_rlx64(yb + nt * 32768);
                    g0 = ld_rlx(gp); g1 = ld_rlx(gp + 32);
                }
            }
            if (warp == 0) STAMP(7);
            {
                const unsigned* yprobe = scr->yflag + ((bi_j & 3) * 32 + wg * 16 + (lane & 15)) * 8;
                int n = 0;
#pragma unroll 1
                while (true) {
                    uint32_t bad = (g0 ^ tag) | (g1 ^ tag);
#pragma unroll
                    for (int nt = 0; nt < 8; nt++) bad |= yv[nt].x ^ tag;
                    if (!__any_sync(~0u, bad & 1)) break;
#pragma unroll 1
                    while (__any_sync(~0u, (ld_rlx(yprobe) ^ tag) & 1)) { if (++n > SPIN_LIMIT) break; }
#pragma unroll
                    for (int nt = 0; nt < 8; nt++) yv[nt] = ld_rlx64(yb + nt * 32768);
                    g0 = ld_rlx(gp); g1 = ld_rlx(gp + 32);
                    if (++n > SPIN_LIMIT) break;
                }
            }
            if (warp == 0) STAMP(28);
            wg_wait<0>();
            fence_regs<64>(oc);
        }
        {
            bar_named(3 + wg, 128);
            const uint32_t xw = sb + wg * 2 * SLOT + (tid & 127) * 16, xr = sb + (wg ^ 1) * 2 * SLOT + (tid & 127) * 16;
#pragma unroll
            for (int r = 0; r < 8; r++) {
                const float* o = oc + 4 * r;
                sts128(xw + r * 2048, __float_as_uint(wg ? o[0] : o[32]), __float_as_uint(wg ? o[1] : o[33]), __float_as_uint(wg ? o[2] : o[34]), __float_as_uint(wg ? o[3] : o[35]));
            }
#pragma unroll
            for (int r = 0; r < 32; r++) oc[r] = wg ? oc[32 + r] : oc[r];
            bar_named(1, 256);
            if (warp == 0) STAMP(8);
            const float ga = bf_hi(g0), gb = bf_hi(g1);
            const float ha = bf_round(1.0f - ga), hb = bf_round(1.0f - gb);
            uint32_t w[8][2];
#pragma unroll
            for (int nt = 0; nt < 8; nt++) {
                const uint4 p = lds128(xr + nt * 2048);
                w[nt][0] = pack2(fmaf(ga, oc[4 * nt] + __uint_as_float(p.x), ha * bf_lo(yv[nt].x)), fmaf(ga, oc[4 * nt + 1] + __uint_as_float(p.y), ha * bf_hi(yv[nt].x)));
                w[nt][1] = pack2(fmaf(gb, oc[4 * nt + 2] + __uint_as_float(p.z), hb * bf_lo(yv[nt].y)), fmaf(gb, oc[4 * nt + 3] + __uint_as_float(p.w), hb * bf_hi(yv[nt].y)));
            }
            const uint32_t ob = sb + wg * 2 * SLOT + 16384 + w4 * 2048;
#pragma unroll
            for (int nt = 0; nt < 8; nt += 2)
                stsm4(ob + (lane & 15) * 128 + (((nt + shi) ^ (lane & 7)) << 4), w[nt][0], w[nt][1], w[nt + 1][0], w[nt + 1][1]);
            __syncwarp();
            bf16* op = out + (size_t)(slab * 16) * 512 + (bi_j & 3) * 128 + wg * 64 + (lane & 7) * 8;
#pragma unroll
            for (int it = 0; it < 4; it++) {
                const int r = it * 4 + (lane >> 3);
                uint4 v = lds128(ob + r * 128 + (((lane & 7) ^ (r & 7)) << 4));
                *(uint4*)(op + r * 512) = v;
            }
        }
        if (warp == 0) STAMP(10);
    } else {
        const int st = tid - 256;
        float kc[24];
        const int brow = (buf >> 7) & 7;
#pragma unroll
        for (int t = 0; t < 24; t++) kc[t] = 0.f;
        fence_regs<24>(kc);
        {
            const float dt = bf_round(expf((ch & 1) ? bf_hi(pdt) : bf_lo(pdt)));
#pragma unroll 1
            for (int it = 0; it < 4; it++) {
                const int sh = (it & 1) * 16;
                auto pick = [&](const uint2& v) { return __uint_as_float(((it & 2 ? v.y : v.x) >> sh) << 16); };
                const float ea = bf_round(expf(pick(pla)));
                const float arl = (-ea * dt) * 1.4426950408889634f, ait = (pick(pai) * dt) * 0.15915494309189535f;
                cf C2; C2.re = 2.0f * (pick(pcr) * dt); C2.im = 2.0f * (pick(pci) * dt);
                const cf z1 = cexp_p(arl, ait, 1.0f), z128 = cexp_p(arl, ait, 128.0f);
                cf z8 = cexp_p(arl, ait, 8.0f); z8.im = -z8.im;
                const uint32_t lp = buf + lane * 4;
                auto put = [&](int row, const cf& v) { sts32((lp ^ (((row + brow) & 7) << 4)) + row * 128, pack2(v.re, v.im)); };
                {
                    const cf z16 = cmul(z8, z8);
                    cf e; e.re = 1.f; e.im = 0.f;
                    cf o = z8;
                    put(0, e); put(1, o);
                    e = z16; put(2, e);
#pragma unroll
                    for (int b = 3; b < 16; b += 2) {
                        o = cmul(o, z16); put(b, o);
                        if (b + 1 < 16) { e = cmul(e, z16); put(b + 1, e); }
                    }
                }
                cf h[8];
                h[0] = C2; put(16, h[0]);
                {
                    const cf z2 = cmul(z1, z1);
                    h[1] = cmul(h[0], z1);
#pragma unroll
                    for (int r = 2; r < 8; r++) h[r] = cmul(h[r - 2], z2);
#pragma unroll
                    for (int r = 1; r < 8; r++) put(16 + r, h[r]);
                }
#pragma unroll
                for (int r = 0; r < 8; r++) { h[r] = cmul(h[r], z128); put(24 + r, h[r]); }
#pragma unroll
                for (int al = 0; al < 2; al++)
#pragma unroll
                    for (int r = 0; r < 4; r++) { h[2 * r] = cmul(h[2 * r], z128); put(32 + al * 4 + r, h[2 * r]); }
#pragma unroll
                for (int al = 0; al < 4; al++)
#pragma unroll
                    for (int r = 0; r < 2; r++) { h[4 * r] = cmul(h[4 * r], z128); put(40 + al * 2 + r, h[4 * r]); }
#pragma unroll
                for (int al = 0; al < 9; al++) { h[0] = cmul(h[0], z128); put(48 + al, h[0]); }
                asm volatile("fence.proxy.async.shared::cta;" ::: "memory");
                bar_named(2, 128);
                uint32_t la[4][4];
#pragma unroll
                for (int ks = 0; ks < 4; ks++) ldsm4(la[ks], buf + (lane & 15) * 128 + (((2 * ks + (lane >> 4)) ^ ((lane + brow) & 7)) << 4));
                const uint64_t dh = mkdesc(sb + OFF_BUF + 2048, 16, 1024);
#pragma unroll
                for (int c = 0; c < 4; c++) {
                    uint32_t a[4][4];
#pragma unroll
                    for (int r = 0; r < 16; r++) a[r >> 2][r & 3] = (c == w4) ? la[r >> 2][r & 3] : 0u;
                    wg_fence();
#pragma unroll
                    for (int ks = 0; ks < 4; ks++) wgmma48_rs(kc, a[ks][0], a[ks][1], a[ks][2], a[ks][3], dh + c * (BUF_STRIDE >> 4) + 2 * ks);
                    wg_commit();
                }
                wg_wait<0>();
                fence_regs<24>(kc);
                bar_named(2, 128);
            }
        }
        if (warp == 8) STAMP(22);
        if (warp == 8) {
            mbar_wait(bar + 8 * BAR_XT, 0);
            if (lane == 0) asm volatile("red.release.gpu.global.add.u32 [%0],8;" ::"l"(scr->xcnt + ((bi_j >> 1) + rot) * 32) : "memory");
        }
        if (lane == 0) {
            int n = 0;
#pragma unroll 1
            while ((int)(ld_acq(scr->xcnt + bi_j * 32) - (epoch1 << 7)) < 0) { __nanosleep(200); if (++n > SPIN_LIMIT) break; }
        }
        __syncwarp();
        if (warp == 8) STAMP(15);
        uint4 ur[8];
#pragma unroll
        for (int v = 0; v < 8; v++) ur[v] = __ldcg(scr->xt + bi * 1024 + st + 128 * v);
#pragma unroll
        for (int v = 0; v < 3; v++) if (v * 32 + lane < U_PAD / 16) sts128(sb + OFF_U + w4 * U_STRIDE + (v * 32 + lane) * 16, 0, 0, 0, 0);
        if (st < 8) st_rlx32(scr->yflag + bi * 8 + st, tag ^ 1u);
#pragma unroll
        for (int v = 0; v < 8; v++) {
            const uint32_t a = sb + OFF_U + (st & 3) * U_STRIDE + U_PAD + ((st >> 2) + 32 * v) * 16;
            sts128(a ^ ((a >> 3) & 0x70), ur[v].x, ur[v].y, ur[v].z, ur[v].w);
        }
        if (warp == 8) STAMP(16);
        mbar_wait(bar + 8 * BAR_WO, 0);
        const uint32_t kt = sb + kt_off(w4);
#pragma unroll
        for (int v = 0; v < 8; v++) if (v * 32 + lane < KT_BYTES / 16) sts128(kt + (v * 32 + lane) * 16, 0, 0, 0, 0);
        if (lane < 14) sts128(buf + (lane >= 7 ? W3_OFF - 112 : 0) + lane * 16, 0, 0, 0, 0);
        __syncwarp();
        if (lane == 0) kc[4 * 0 + 0] += (ch & 1) ? bf_hi(pds) : bf_lo(pds);
#pragma unroll
        for (int i = 0; i < 2; i++) {
            const int be = g + 8 * i;
#pragma unroll
            for (int t = 0; t < 2; t++) {
                const uint32_t a = kt + (64 + 128 * t + 8 * be + 2 * q) * 4;
                const uint32_t w = pack2(kc[4 * t + 2 * i + 1], kc[4 * t + 2 * i]);
                sts32(a + 4, w); sts16(a, w >> 16); sts16(a + 10, w);
            }
            {
                const int p = 256 + 128 * (q >> 1) + 8 * be + 4 * (q & 1);
                const uint32_t a = kt + (64 + p) * 4;
                const uint32_t w = pack2(kc[4 * 2 + 2 * i + 1], kc[4 * 2 + 2 * i]);
                const uint32_t aa = (w >> 16) | (w & 0xffff0000u);
                if (p != 256) { sts16(a - 4, aa); sts32(a, aa); } else sts16(a, aa);
                sts32(a + 4, aa); sts32(a + 8, w); sts16(a + 14, w);
            }
            {
                const int k = 64 + 16 * q + be;
                const uint32_t w = pack2(kc[4 * 3 + 2 * i], kc[4 * 3 + 2 * i + 1]);
                if (k != 64) sts16(kt + KT_E2 + (k - 1) * 2, w);
                else {
                    const uint32_t a = kt + (64 + 511) * 4, aa = (w << 16) | (w & 0xffffu);
                    sts16(a, w); sts32(a + 4, aa); sts32(a + 8, aa); sts32(a + 12, aa); sts16(a + 18, w);
                }
                sts16(kt + KT_E2 + KT_E2O + k * 2, w >> 16);
            }
#pragma unroll
            for (int b = 0; b < 2; b++) {
                const int k = 64 + 8 * (2 * q + b) + (be >> 1);
                const uint32_t w = pack2(kc[4 * 4 + 2 * i + b], 0.f);
                const bool k1024 = !(be & 1) && k == 64;
                const uint32_t a = k3 + (k1024 ? 188 + 64 : ((be & 1) ? 94 + k : k - 1)) * 4 - 34 * 4;
                sts16(a, w);
                if (!((be & 1) && k == 127)) sts16(a + 6, w);
                if (k1024) sts16(kt + KT_E2 + 127 * 2, w);
            }
        }
        if (lane == 0) sts16(k3 + (127 - 34) * 4, pack2(kc[4 * 5 + 0], 0.f));
        asm volatile("fence.proxy.async.shared::cta;" ::: "memory");
        bar_named(2, 128);
        if (warp == 8) STAMP(17);
        mbar_wait(bar + 8 * BAR_DONE, 0);
        float y[4][16];
#pragma unroll
        for (int c = 0; c < 4; c++) {
#pragma unroll
            for (int r = 0; r < 16; r++) y[c][r] = 0.f;
            fence_regs<16>(y[c]);
        }
        {
            uint32_t Q[3][4][4];
            uint32_t ka = sb + (64 - 48 + 16 * w4 + g - 2 * q) * 4;
            uint64_t du = mkdesc(sb + OFF_U + U_PAD + 96, 16, 1024);
            auto ldq = [&](uint32_t (*qd)[4]) {
#pragma unroll
                for (int c = 0; c < 4; c++) {
                    qd[c][0] = lds32(ka + kt_off(c)); qd[c][1] = lds32(ka + kt_off(c) + 32); qd[c][2] = lds32(ka + kt_off(c) - 32); qd[c][3] = qd[c][0];
                }
                ka += 64;
            };
            auto step = [&](int b) {
                wg_fence();
#pragma unroll
                for (int c = 0; c < 4; c++) wgmma32_rs(y[c], Q[b][c], du + c * (U_STRIDE >> 4));
                wg_commit();
                du -= 2;
                wg_wait<1>();
                ldq(Q[(b + 2) % 3]);
            };
            ldq(Q[0]); ldq(Q[1]);
            const uint32_t u0 = sb + OFF_U + w4 * U_STRIDE + U_PAD + lane * 16;
#pragma unroll 1
            for (int rho = 0; rho < 6; rho++) {
                const int ci = lane + 32 * rho;
                const uint32_t sw = (ci ^ ((ci >> 3) & 1)) << 4;
                float S[17];
                auto prefix = [&](int v0, int o) {
                    uint4 e4[3];
#pragma unroll
                    for (int v = 0; v < 3; v++) { const uint32_t a = u0 + rho * 512 + (v0 + v - 3) * 16; e4[v] = lds128(a ^ ((a >> 3) & 0x70)); }
                    const uint32_t* ew = (const uint32_t*)e4;
                    S[0] = 0.f;
#pragma unroll
                    for (int k = 1; k <= 16; k++) { const int e = o + k - 8 * v0; S[k] = S[k - 1] + ((e & 1) ? bf_hi(ew[e >> 1]) : bf_lo(ew[e >> 1])); }
                };
                auto win = [&](int lo, int hi, uint32_t a, bool on) {
                    const uint32_t w0 = pack2(S[hi] - S[lo], S[hi + 1] - S[lo + 1]), w1 = pack2(S[hi + 2] - S[lo + 2], S[hi + 3] - S[lo + 3]);
                    const uint32_t w2 = pack2(S[hi + 4] - S[lo + 4], S[hi + 5] - S[lo + 5]), w3 = pack2(S[hi + 6] - S[lo + 6], S[hi + 7] - S[lo + 7]);
                    asm volatile("{.reg .pred p; setp.ne.b32 p,%5,0; @p st.shared.v4.b32 [%0],{%1,%2,%3,%4};}" ::"r"(a), "r"(w0), "r"(w1), "r"(w2), "r"(w3), "r"((int)on) : "memory");
                };
                step(0);
                prefix(0, 3);
                step(1);
                win(0, 9, buf + W9_OFF + sw, rho < 4);
                prefix(1, 12);
                step(2);
                win(1, 6, buf + W5_OFF + 112 + ci * 16, true);
                step(0);
                win(0, 7, sb + OFF_X + w4 * 4096 + sw, rho < 4);
                step(1);
                win(6, 9, buf + W3_OFF + 112 + ci * 16, true);
                step(2);
                win(7, 9, sb + OFF_X + w4 * 4096 + 2048 + sw, rho < 4);
            }
            step(0);
        }
        wg_wait<0>();
#pragma unroll
        for (int c = 0; c < 4; c++) fence_regs<16>(y[c]);
        if (warp == 8) STAMP(18);
        bar_named(2, 128);
        if (warp == 8) STAMP(23);
        {
            uint32_t Q[3][4][4];
            uint32_t wa = sb + OFF_BUF + (15 - (lane >> 4) * 8 - (lane & 7) + 2 * w4 + ((lane >> 3) & 1)) * 16;
            uint64_t de = (uint64_t)(((sb + KT_E2 - 16) & 0x3FFFF) >> 4) | ((uint64_t)1 << 16) | ((uint64_t)8 << 32);
#pragma unroll
            for (int c = 0; c < 4; c++) { ldsm4t(Q[0][c], wa + c * BUF_STRIDE); ldsm4t(Q[1][c], wa + c * BUF_STRIDE + W3_OFF); }
#pragma unroll 1
            for (int s = 0; s < 4; s++) {
#pragma unroll
                for (int b = 0; b < 6; b++) {
                    wg_fence();
#pragma unroll
                    for (int c = 0; c < 4; c++) wgmma32_rs(y[c], Q[b % 3][c], de + (kt_off(c) >> 4) + (b & 1) * (KT_E2O >> 4) - 2 * (b >> 1));
                    wg_commit();
                    wg_wait<1>();
#pragma unroll
                    for (int c = 0; c < 4; c++) ldsm4t(Q[(b + 2) % 3][c], wa + c * BUF_STRIDE + (b & 1) * W3_OFF + 256 * (1 + (b >> 1)));
                }
                wa += 768; de -= 6;
            }
        }
        wg_wait<0>();
#pragma unroll
        for (int c = 0; c < 4; c++) fence_regs<16>(y[c]);
        if (warp == 8) STAMP(19);
        {
            const int ap = (lane & 7) + (lane >> 4) * 8;
            const uint32_t loff = ((2 * ap + ((lane >> 3) & 1)) ^ ((ap >> 2) & 1)) << 4;
#pragma unroll 1
            for (int ph = 0; ph < 3; ph++) {
                const uint32_t ka = sb + OFF_K3 + (ph * 94 + 4 * g + w4 - 2 * q - 34) * 4;
#pragma unroll
                for (int c = 0; c < 4; c++) {
                    const uint32_t wb = (ph ? sb + OFF_X + c * 4096 + (ph - 1) * 2048 : sb + OFF_BUF + c * BUF_STRIDE + W9_OFF) + loff;
                    uint32_t B[4][2];
#pragma unroll
                    for (int d = 0; d < 4; d++) { B[d][0] = lds32(ka + c * K3_STRIDE + (48 + 16 * d) * 4); B[d][1] = lds32(ka + c * K3_STRIDE + (40 + 16 * d) * 4); }
#pragma unroll
                    for (int s = 0; s < 4; s++) {
                        uint32_t A[4];
                        ldsm4t(A, wb + s * 512);
                        if (s < 2) mma16816(y[c] + 8, A[0], A[1], A[2], A[3], B[1 - s][0], B[1 - s][1]);
                        mma16816(y[c] + 12, A[0], A[1], A[2], A[3], B[3 - s][0], B[3 - s][1]);
                    }
                }
            }
        }
        uint4* yp = scr->y + bi * 1024 + (8 * q + w4) * 8 + g;
#pragma unroll
        for (int j = 0; j < 4; j++)
#pragma unroll
            for (int b = 0; b < 2; b++)
                st_rlx128(yp + (32 * j + 4 * b) * 8, tag4(pack2(y[0][4 * j + b], y[1][4 * j + b]), pack2(y[0][4 * j + 2 + b], y[1][4 * j + 2 + b]),
                                                          pack2(y[2][4 * j + b], y[3][4 * j + b]), pack2(y[2][4 * j + 2 + b], y[3][4 * j + 2 + b]), tag));
        bar_named(2, 128);
        if (st < 8) st_rlx32(scr->yflag + bi * 8 + st, tag);
        if (warp == 8) STAMP(20);
    }
    __syncthreads();
    if (tid == 0) atomicAdd(scr->done, 1u);
}

typedef CUresult (*EncFn)(CUtensorMap*, CUtensorMapDataType, cuuint32_t, void*, const cuuint64_t*, const cuuint64_t*, const cuuint32_t*,
                          const cuuint32_t*, CUtensorMapInterleave, CUtensorMapSwizzle, CUtensorMapL2promotion, CUtensorMapFloatOOBfill);

extern "C" void kernel_launch(void* const* d_in, const int* in_sizes, int n_in, void* d_out, int out_size) {
    static EncFn enc = nullptr;
    static Scratch* scr = nullptr;
    if (!enc) {
        cudaGetSymbolAddress((void**)&scr, g_scr);
        cudaDriverEntryPointQueryResult qr;
        cudaGetDriverEntryPoint("cuTensorMapEncodeTiled", (void**)&enc, cudaEnableDefault, &qr);
        cudaFuncSetAttribute(fused_kernel, cudaFuncAttributeMaxDynamicSharedMemorySize, SMEM_BYTES);
    }
    CUtensorMap mx, mw, mwo;
    const cuuint32_t es[3] = {1, 1, 1};
    {
        cuuint64_t d[2] = {512, 2048}, s[1] = {1024}; cuuint32_t b[2] = {64, 128};
        enc(&mx, CU_TENSOR_MAP_DATA_TYPE_BFLOAT16, 2, d_in[0], d, s, b, es, CU_TENSOR_MAP_INTERLEAVE_NONE, CU_TENSOR_MAP_SWIZZLE_128B,
            CU_TENSOR_MAP_L2_PROMOTION_L2_128B, CU_TENSOR_MAP_FLOAT_OOB_FILL_NONE);
    }
    {
        cuuint64_t d[3] = {512, 512, 3}, s[2] = {3072, 1024}; cuuint32_t b[3] = {64, 64, 3};
        enc(&mw, CU_TENSOR_MAP_DATA_TYPE_BFLOAT16, 3, d_in[1], d, s, b, es, CU_TENSOR_MAP_INTERLEAVE_NONE, CU_TENSOR_MAP_SWIZZLE_128B,
            CU_TENSOR_MAP_L2_PROMOTION_L2_128B, CU_TENSOR_MAP_FLOAT_OOB_FILL_NONE);
    }
    {
        cuuint64_t d[2] = {512, 512}, s[1] = {1024}; cuuint32_t b[2] = {64, 256};
        enc(&mwo, CU_TENSOR_MAP_DATA_TYPE_BFLOAT16, 2, d_in[3], d, s, b, es, CU_TENSOR_MAP_INTERLEAVE_NONE, CU_TENSOR_MAP_SWIZZLE_128B,
            CU_TENSOR_MAP_L2_PROMOTION_L2_128B, CU_TENSOR_MAP_FLOAT_OOB_FILL_NONE);
    }
    fused_kernel<<<128, 384, SMEM_BYTES, cudaStreamPerThread>>>(
        scr, (const bf16*)d_in[5], (const bf16*)d_in[6], (const bf16*)d_in[7], (const bf16*)d_in[8], (const bf16*)d_in[9],
        (const bf16*)d_in[10], (const bf16*)d_in[2], (const bf16*)d_in[11], (bf16*)d_out, mx, mw, mwo);
}
```

```cpp
#include <cuda_runtime.h>
#include <cuda.h>
#include <cuda_bf16.h>
#include <stdint.h>

typedef __nv_bfloat16 bf16;

struct Scratch {
    uint4 xt[128 * 1024];
    uint4 o[16 * 8 * 32 * 32];
    uint4 y[128 * 1024];
    uint4 kvp[8 * 16 * 544];
    uint4 kvf[8 * 4 * 68];
    unsigned g[1024 * 8];
    unsigned yflag[128 * 8];
    unsigned xcnt[8 * 32];
    unsigned done[32];
};
__device__ Scratch g_scr;
#define STAMP(n)

constexpr int SLOT = 40960;
constexpr int OFF_SP0 = 32768, OFF_SP1 = SLOT + 32768;
constexpr int OFF_P = 2 * SLOT, OFF_V = OFF_P + 32768;
constexpr int OFF_X = OFF_V + 32768;
constexpr int KT_BYTES = 3824, KT_E2 = 2688, KT_E2O = 624;
__host__ __device__ constexpr int kt_off(int c) { return (c < 2 ? OFF_SP0 : OFF_SP1) + (c & 1) * 4096; }
constexpr int OFF_U = 4 * SLOT, U_STRIDE = 41 * 128, U_PAD = 9 * 128;
constexpr int OFF_BUF = OFF_U + 4 * U_STRIDE, BUF_STRIDE = 8448;
constexpr int OFF_K3 = OFF_BUF + 4 * BUF_STRIDE, K3_STRIDE = 1136;
constexpr int OFF_WPHI = OFF_K3 + 4 * K3_STRIDE;
constexpr int OFF_GW = OFF_WPHI + 2048;
constexpr int OFF_KVF = OFF_GW + 1024;
constexpr int OFF_BAR = OFF_KVF + 4352;
constexpr int SMEM_BYTES = OFF_BAR + 128 + 128;
static_assert(SMEM_BYTES <= 232448 && OFF_BUF % 128 == 0, "smem");
constexpr int W5_OFF = 0, W3_OFF = 3184, W9_OFF = 6368;
constexpr int BAR_FULL = 0, BAR_WPHI = 4, BAR_WO = 5, BAR_XT = 6, BAR_DONE = 7, BAR_WO2 = 8, OFF_CNT = 96;
#define KG_ROUNDS 4
constexpr int SPIN_LIMIT = 1 << 17;

__device__ __forceinline__ uint32_t s2u(const void* p) { return (uint32_t)__cvta_generic_to_shared(p); }
__device__ __forceinline__ void mbar_init(uint32_t b, int c) { asm volatile("mbarrier.init.shared::cta.b64 [%0],%1;" ::"r"(b), "r"(c) : "memory"); }
__device__ __forceinline__ void mbar_expect(uint32_t b, int bytes) { asm volatile("mbarrier.arrive.expect_tx.shared::cta.b64 _,[%0],%1;" ::"r"(b), "r"(bytes) : "memory"); }
__device__ __forceinline__ void mbar_arrive(uint32_t b) { asm volatile("mbarrier.arrive.shared::cta.b64 _,[%0];" ::"r"(b) : "memory"); }
__device__ __forceinline__ void mbar_wait(uint32_t b, int ph) {
    asm volatile("{\n.reg .pred p;\n.reg .u32 n;\nmov.u32 n,0;\nLW_%=:\nmbarrier.try_wait.parity.shared::cta.b64 p,[%0],%1;\n@p bra LD_%=;\n"
                 "add.u32 n,n,1;\nsetp.lt.u32 p,n,131072;\n@p bra LW_%=;\nLD_%=:\n}" ::"r"(b), "r"(ph) : "memory");
}
__device__ __forceinline__ void tma2d(uint32_t dst, const CUtensorMap* m, int c0, int c1, uint32_t bar) {
    asm volatile("cp.async.bulk.tensor.2d.shared::cluster.global.mbarrier::complete_tx::bytes [%0],[%1,{%3,%4}],[%2];" ::"r"(dst), "l"(m), "r"(bar), "r"(c0), "r"(c1) : "memory");
}
__device__ __forceinline__ void tma3d(uint32_t dst, const CUtensorMap* m, int c0, int c1, int c2, uint32_t bar) {
    asm volatile("cp.async.bulk.tensor.3d.shared::cluster.global.mbarrier::complete_tx::bytes [%0],[%1,{%3,%4,%5}],[%2];" ::"r"(dst), "l"(m), "r"(bar), "r"(c0), "r"(c1), "r"(c2) : "memory");
}
__device__ __forceinline__ void bulk_g2s(uint32_t dst, const void* src, int bytes, uint32_t bar) {
    asm volatile("cp.async.bulk.shared::cluster.global.mbarrier::complete_tx::bytes [%0],[%1],%2,[%3];" ::"r"(dst), "l"(src), "r"(bytes), "r"(bar) : "memory");
}
__device__ __forceinline__ uint64_t mkdesc(uint32_t addr, uint32_t lbo, uint32_t sbo) {
    return (uint64_t)((addr & 0x3FFFF) >> 4) | ((uint64_t)(lbo >> 4) << 16) | ((uint64_t)(sbo >> 4) << 32) | ((uint64_t)1 << 62);
}
__device__ __forceinline__ void wg_fence() { asm volatile("wgmma.fence.sync.aligned;" ::: "memory"); }
__device__ __forceinline__ void wg_commit() { asm volatile("wgmma.commit_group.sync.aligned;" ::: "memory"); }
template <int N> __device__ __forceinline__ void wg_wait() { asm volatile("wgmma.wait_group.sync.aligned %0;" ::"n"(N) : "memory"); }
template <int N> __device__ __forceinline__ void fence_regs(float* d) {
#pragma unroll
    for (int i = 0; i < N; i++) asm volatile("" : "+f"(d[i])::"memory");
}
#define R8(d, o) "+f"(d[o]), "+f"(d[o + 1]), "+f"(d[o + 2]), "+f"(d[o + 3]), "+f"(d[o + 4]), "+f"(d[o + 5]), "+f"(d[o + 6]), "+f"(d[o + 7])
__device__ __forceinline__ void wgmma192(float* d, uint64_t da, uint64_t db) {
    asm volatile("wgmma.mma_async.sync.aligned.m64n192k16.f32.bf16.bf16 {"
                 "%0,%1,%2,%3,%4,%5,%6,%7,%8,%9,%10,%11,%12,%13,%14,%15,%16,%17,%18,%19,%20,%21,%22,%23,%24,%25,%26,%27,%28,%29,%30,%31,"
                 "%32,%33,%34,%35,%36,%37,%38,%39,%40,%41,%42,%43,%44,%45,%46,%47,%48,%49,%50,%51,%52,%53,%54,%55,%56,%57,%58,%59,%60,%61,%62,%63,"
                 "%64,%65,%66,%67,%68,%69,%70,%71,%72,%73,%74,%75,%76,%77,%78,%79,%80,%81,%82,%83,%84,%85,%86,%87,%88,%89,%90,%91,%92,%93,%94,%95},"
                 "%96,%97,1,1,1,0,1;"
                 : R8(d, 0), R8(d, 8), R8(d, 16), R8(d, 24), R8(d, 32), R8(d, 40), R8(d, 48), R8(d, 56), R8(d, 64), R8(d, 72), R8(d, 80), R8(d, 88)
                 : "l"(da), "l"(db));
}
__device__ __forceinline__ void wgmma64_tt(float* d, uint64_t da, uint64_t db, int sc) {
    asm volatile("{.reg .pred p; setp.ne.b32 p,%34,0; wgmma.mma_async.sync.aligned.m64n64k16.f32.bf16.bf16 {"
                 "%0,%1,%2,%3,%4,%5,%6,%7,%8,%9,%10,%11,%12,%13,%14,%15,%16,%17,%18,%19,%20,%21,%22,%23,%24,%25,%26,%27,%28,%29,%30,%31},"
                 "%32,%33,p,1,1,1,1;}"
                 : R8(d, 0), R8(d, 8), R8(d, 16), R8(d, 24)
                 : "l"(da), "l"(db), "r"(sc));
}
__device__ __forceinline__ void wgmma128_rs(float* d, const uint4& a, uint64_t db, int sc) {
    asm volatile("{.reg .pred p; setp.ne.b32 p,%69,0; wgmma.mma_async.sync.aligned.m64n128k16.f32.bf16.bf16 {"
                 "%0,%1,%2,%3,%4,%5,%6,%7,%8,%9,%10,%11,%12,%13,%14,%15,%16,%17,%18,%19,%20,%21,%22,%23,%24,%25,%26,%27,%28,%29,%30,%31,"
                 "%32,%33,%34,%35,%36,%37,%38,%39,%40,%41,%42,%43,%44,%45,%46,%47,%48,%49,%50,%51,%52,%53,%54,%55,%56,%57,%58,%59,%60,%61,%62,%63},"
                 "{%64,%65,%66,%67},%68,p,1,1,1;}"
                 : R8(d, 0), R8(d, 8), R8(d, 16), R8(d, 24), R8(d, 32), R8(d, 40), R8(d, 48), R8(d, 56)
                 : "r"(a.x), "r"(a.y), "r"(a.z), "r"(a.w), "l"(db), "r"(sc));
}
__device__ __forceinline__ void wgmma32_rs(float* d, const uint32_t* a, uint64_t db) {
    asm volatile("wgmma.mma_async.sync.aligned.m64n32k16.f32.bf16.bf16 {%0,%1,%2,%3,%4,%5,%6,%7,%8,%9,%10,%11,%12,%13,%14,%15},{%16,%17,%18,%19},%20,1,1,1,0;"
                 : R8(d, 0), R8(d, 8) : "r"(a[0]), "r"(a[1]), "r"(a[2]), "r"(a[3]), "l"(db));
}
__device__ __forceinline__ void wgmma48_rs(float* d, uint32_t a0, uint32_t a1, uint32_t a2, uint32_t a3, uint64_t db) {
    asm volatile("wgmma.mma_async.sync.aligned.m64n48k16.f32.bf16.bf16 {%0,%1,%2,%3,%4,%5,%6,%7,%8,%9,%10,%11,%12,%13,%14,%15,%16,%17,%18,%19,%20,%21,%22,%23},{%24,%25,%26,%27},%28,1,1,1,0;"
                 : R8(d, 0), R8(d, 8), R8(d, 16) : "r"(a0), "r"(a1), "r"(a2), "r"(a3), "l"(db));
}
__device__ __forceinline__ void mma16816(float* c, uint32_t a0, uint32_t a1, uint32_t a2, uint32_t a3, uint32_t b0, uint32_t b1) {
    asm("mma.sync.aligned.m16n8k16.row.col.f32.bf16.bf16.f32 {%0,%1,%2,%3},{%4,%5,%6,%7},{%8,%9},{%0,%1,%2,%3};"
        : "+f"(c[0]), "+f"(c[1]), "+f"(c[2]), "+f"(c[3]) : "r"(a0), "r"(a1), "r"(a2), "r"(a3), "r"(b0), "r"(b1));
}
__device__ __forceinline__ void ldsm4(uint32_t* r, uint32_t a) {
    asm volatile("ldmatrix.sync.aligned.m8n8.x4.shared.b16 {%0,%1,%2,%3},[%4];" : "=r"(r[0]), "=r"(r[1]), "=r"(r[2]), "=r"(r[3]) : "r"(a) : "memory");
}
__device__ __forceinline__ void ldsm4t(uint32_t* r, uint32_t a) {
    asm volatile("ldmatrix.sync.aligned.m8n8.x4.trans.shared.b16 {%0,%1,%2,%3},[%4];" : "=r"(r[0]), "=r"(r[1]), "=r"(r[2]), "=r"(r[3]) : "r"(a) : "memory");
}
__device__ __forceinline__ void stsm4(uint32_t a, uint32_t r0, uint32_t r1, uint32_t r2, uint32_t r3) {
    asm volatile("stmatrix.sync.aligned.m8n8.x4.shared.b16 [%0],{%1,%2,%3,%4};" ::"r"(a), "r"(r0), "r"(r1), "r"(r2), "r"(r3) : "memory");
}
__device__ __forceinline__ uint32_t lds32(uint32_t a) { uint32_t v; asm volatile("ld.shared.b32 %0,[%1];" : "=r"(v) : "r"(a) : "memory"); return v; }
__device__ __forceinline__ uint4 lds128(uint32_t a) { uint4 v; asm volatile("ld.shared.v4.b32 {%0,%1,%2,%3},[%4];" : "=r"(v.x), "=r"(v.y), "=r"(v.z), "=r"(v.w) : "r"(a) : "memory"); return v; }
__device__ __forceinline__ void sts16(uint32_t a, uint32_t v) { asm volatile("st.shared.b16 [%0],%1;" ::"r"(a), "h"((unsigned short)v) : "memory"); }
__device__ __forceinline__ void sts32(uint32_t a, uint32_t v) { asm volatile("st.shared.b32 [%0],%1;" ::"r"(a), "r"(v) : "memory"); }
__device__ __forceinline__ void sts64(uint32_t a, uint32_t x, uint32_t y) { asm volatile("st.shared.v2.b32 [%0],{%1,%2};" ::"r"(a), "r"(x), "r"(y) : "memory"); }
__device__ __forceinline__ void sts128(uint32_t a, uint32_t x, uint32_t y, uint32_t z, uint32_t w) { asm volatile("st.shared.v4.b32 [%0],{%1,%2,%3,%4};" ::"r"(a), "r"(x), "r"(y), "r"(z), "r"(w) : "memory"); }
__device__ __forceinline__ uint32_t pack2(float lo, float hi) { uint32_t d; asm("cvt.rn.bf16x2.f32 %0,%1,%2;" : "=r"(d) : "f"(hi), "f"(lo)); return d; }
__device__ __forceinline__ float bf_lo(uint32_t v) { return __uint_as_float(v << 16); }
__device__ __forceinline__ float bf_hi(uint32_t v) { return __uint_as_float(v & 0xffff0000u); }
__device__ __forceinline__ float bf_round(float v) { return bf_lo(pack2(v, 0.f)); }
__device__ __forceinline__ uint32_t hmax2(uint32_t a, uint32_t b) { uint32_t d; asm("max.bf16x2 %0,%1,%2;" : "=r"(d) : "r"(a), "r"(b)); return d; }
__device__ __forceinline__ uint32_t hmin2(uint32_t a, uint32_t b) { uint32_t d; asm("min.bf16x2 %0,%1,%2;" : "=r"(d) : "r"(a), "r"(b)); return d; }
__device__ __forceinline__ uint32_t hmul2(uint32_t a, uint32_t b) { uint32_t d; asm("mul.rn.bf16x2 %0,%1,%2;" : "=r"(d) : "r"(a), "r"(b)); return d; }
__device__ __forceinline__ float ex2(float x) { float y; asm("ex2.approx.ftz.f32 %0,%1;" : "=f"(y) : "f"(x)); return y; }
__device__ __forceinline__ float rcp(float x) { float y; asm("rcp.approx.ftz.f32 %0,%1;" : "=f"(y) : "f"(x)); return y; }
__device__ __forceinline__ uint32_t ld_nc(const uint32_t* p) { uint32_t v; asm volatile("ld.global.nc.b32 %0,[%1];" : "=r"(v) : "l"(p)); return v; }
__device__ __forceinline__ uint2 ld_nc64(const uint2* p) { uint2 v; asm volatile("ld.global.nc.v2.b32 {%0,%1},[%2];" : "=r"(v.x), "=r"(v.y) : "l"(p)); return v; }
__device__ __forceinline__ unsigned ld_acq(const unsigned* p) { unsigned v; asm volatile("ld.acquire.gpu.global.u32 %0,[%1];" : "=r"(v) : "l"(p) : "memory"); return v; }
__device__ __forceinline__ unsigned ld_rlx(const unsigned* p) { unsigned v; asm volatile("ld.relaxed.gpu.global.u32 %0,[%1];" : "=r"(v) : "l"(p) : "memory"); return v; }
__device__ __forceinline__ uint2 ld_rlx64(const void* p) { uint2 v; asm volatile("{.reg .b64 t; ld.relaxed.gpu.global.b64 t,[%2]; mov.b64 {%0,%1},t;}" : "=r"(v.x), "=r"(v.y) : "l"(p) : "memory"); return v; }
__device__ __forceinline__ uint4 ld_rlx128(const void* p) {
    uint4 v;
    asm volatile("{.reg .b64 t,u; ld.relaxed.gpu.global.v2.b64 {t,u},[%4]; mov.b64 {%0,%1},t; mov.b64 {%2,%3},u;}" : "=r"(v.x), "=r"(v.y), "=r"(v.z), "=r"(v.w) : "l"(p) : "memory");
    return v;
}
__device__ __forceinline__ void st_rlx32(void* p, uint32_t x) { asm volatile("st.relaxed.gpu.global.u32 [%0],%1;" ::"l"(p), "r"(x) : "memory"); }
__device__ __forceinline__ void st_rlx64(void* p, uint32_t x, uint32_t y) { asm volatile("{.reg .b64 t; mov.b64 t,{%1,%2}; st.relaxed.gpu.global.b64 [%0],t;}" ::"l"(p), "r"(x), "r"(y) : "memory"); }
__device__ __forceinline__ void st_rlx128(void* p, uint4 v) {
    asm volatile("{.reg .b64 t,u; mov.b64 t,{%1,%2}; mov.b64 u,{%3,%4}; st.relaxed.gpu.global.v2.b64 [%0],{t,u};}" ::"l"(p), "r"(v.x), "r"(v.y), "r"(v.z), "r"(v.w) : "memory");
}
__device__ __forceinline__ uint32_t tagw(uint32_t w, uint32_t tag) { return (w & ~1u) | tag; }
__device__ __forceinline__ uint4 tag4(uint32_t x, uint32_t y, uint32_t z, uint32_t w, uint32_t tag) { return make_uint4(tagw(x, tag), y, tagw(z, tag), w); }
__device__ __forceinline__ uint32_t bad4(const uint4& v, uint32_t tag) { return (v.x ^ tag) | (v.z ^ tag); }
__device__ __forceinline__ void bar_named(int id, int n) { asm volatile("bar.sync %0,%1;" ::"r"(id), "r"(n) : "memory"); }

struct cf { float re, im; };
__device__ __forceinline__ cf cmul(cf a, cf b) { cf r; r.re = a.re * b.re - a.im * b.im; r.im = a.re * b.im + a.im * b.re; return r; }
__device__ __forceinline__ cf cexp_p(float arl, float ait, float p) {
    float mag = ex2(arl * p);
    float t = ait * p;
    t = (t - rintf(t)) * 6.283185307179586f;
    cf r; r.re = mag * __cosf(t); r.im = mag * __sinf(t);
    return r;
}

__device__ __forceinline__ void hedgehog2(const uint32_t* a, uint32_t wphi_addr, uint32_t (*out)[8]) {
    float p[2][2][4], mx[2][2];
#pragma unroll
    for (int h = 0; h < 2; h++) {
        uint32_t b[4];
        ldsm4t(b, wphi_addr + h * 512);
        float c0[4] = {0.f, 0.f, 0.f, 0.f}, c1[4] = {0.f, 0.f, 0.f, 0.f};
        mma16816(c0, a[4 * h], a[4 * h + 1], a[4 * h + 2], a[4 * h + 3], b[0], b[1]);
        mma16816(c1, a[4 * h], a[4 * h + 1], a[4 * h + 2], a[4 * h + 3], b[2], b[3]);
#pragma unroll
        for (int k = 0; k < 2; k++) {
            p[h][k][0] = c0[2 * k]; p[h][k][1] = c0[2 * k + 1]; p[h][k][2] = c1[2 * k]; p[h][k][3] = c1[2 * k + 1];
            mx[h][k] = fmaxf(fmaxf(p[h][k][0], p[h][k][1]), fmaxf(p[h][k][2], p[h][k][3]));
        }
    }
#pragma unroll
    for (int o = 1; o <= 2; o <<= 1)
#pragma unroll
        for (int h = 0; h < 2; h++)
#pragma unroll
            for (int k = 0; k < 2; k++) mx[h][k] = fmaxf(mx[h][k], __shfl_xor_sync(~0u, mx[h][k], o));
    const float L = 1.4426950408889634f;
    float pmin = 1.f;
#pragma unroll
    for (int h = 0; h < 2; h++)
#pragma unroll
        for (int k = 0; k < 2; k++) {
            const float m = -mx[h][k] * L;
            const float e0 = ex2(fmaf(p[h][k][0], L, m)), e1 = ex2(fmaf(p[h][k][1], L, m)), e2 = ex2(fmaf(p[h][k][2], L, m)), e3 = ex2(fmaf(p[h][k][3], L, m));
            const float p01 = e0 * e1, p23 = e2 * e3, pp = p01 * p23, r = rcp(pp), r01 = r * p23, r23 = r * p01;
            pmin = fminf(pmin, pp);
            out[h][k] = pack2(e0, e1); out[h][k + 2] = pack2(e2, e3);
            out[h][4 + k] = pack2(r01 * e1, r01 * e0); out[h][4 + k + 2] = pack2(r23 * e3, r23 * e2);
        }
    if (__builtin_expect(__any_sync(~0u, !(pmin > 1e-18f)), 0)) {
#pragma unroll
        for (int h = 0; h < 2; h++)
#pragma unroll
            for (int k = 0; k < 2; k++) {
                float m = fminf(fminf(p[h][k][0], p[h][k][1]), fminf(p[h][k][2], p[h][k][3]));
                m = fminf(m, __shfl_xor_sync(~0u, m, 1));
                m = fminf(m, __shfl_xor_sync(~0u, m, 2)) * L;
                out[h][4 + k] = pack2(ex2(fmaf(p[h][k][0], -L, m)), ex2(fmaf(p[h][k][1], -L, m)));
                out[h][4 + k + 2] = pack2(ex2(fmaf(p[h][k][2], -L, m)), ex2(fmaf(p[h][k][3], -L, m)));
            }
    }
}

__global__ void __launch_bounds__(384, 1)
fused_kernel(Scratch* __restrict__ scr, const bf16* __restrict__ logA, const bf16* __restrict__ Aim, const bf16* __restrict__ Cre,
             const bf16* __restrict__ Cim, const bf16* __restrict__ logdt, const bf16* __restrict__ Dskip, const bf16* __restrict__ wphi,
             const bf16* __restrict__ gatew, bf16* __restrict__ out,
             const __grid_constant__ CUtensorMap mx, const __grid_constant__ CUtensorMap mw, const __grid_constant__ CUtensorMap mwo) {
    extern __shared__ __align__(1024) uint8_t smem[];
    const uint32_t sb = s2u(smem);
    const int tid = threadIdx.x, warp = __shfl_sync(~0u, tid >> 5, 0), lane = tid & 31;
    const int g = lane >> 2, q = lane & 3, w4 = warp & 3;
    const int bi = blockIdx.x, bi_i = bi & 15, bi_j = bi >> 4;
    const uint32_t bar = sb + OFF_BAR;
    const int rot = (bi_j & 1) * 4;
    auto load_stage = [&](int kb) {
        const uint32_t b = bar + 8 * (BAR_FULL + (kb & 3)), d = sb + (kb & 3) * SLOT;
        const int kc = ((kb + rot) & 7) * 64;
        mbar_expect(b, SLOT);
        tma2d(d, &mx, kc, bi_i * 128, b);
        tma3d(d + 16384, &mw, bi_j * 64, kc, 0, b);
    };

    const int ch = bi * 4 + w4;
    uint2 pla, pai, pcr, pci; uint32_t pdt = 0, pds;
    if (warp >= 8) {
        pla = ld_nc64((const uint2*)logA + ch * 32 + lane); pai = ld_nc64((const uint2*)Aim + ch * 32 + lane);
        pcr = ld_nc64((const uint2*)Cre + ch * 32 + lane); pci = ld_nc64((const uint2*)Cim + ch * 32 + lane);
        pdt = ld_nc((const uint32_t*)logdt + (ch >> 1)); pds = ld_nc((const uint32_t*)Dskip + (ch >> 1));
    }
    unsigned done0 = ld_rlx(scr->done);
    if (tid == 0) {
        for (int s = 0; s < 4; s++) mbar_init(bar + 8 * (BAR_FULL + s), 1);
        asm volatile("fence.mbarrier_init.release.cluster;" ::: "memory");
#pragma unroll 1
        for (int s = 0; s < 4; s++) load_stage(s);
        STAMP(11);
    } else if (tid == 32) {
        if (sb & 1023) __trap();
        for (int s = 0; s < 5; s++) sts32(bar + OFF_CNT + 4 * s, 0);
        mbar_init(bar + 8 * BAR_WPHI, 1); mbar_init(bar + 8 * BAR_WO, 2); mbar_init(bar + 8 * BAR_XT, 8); mbar_init(bar + 8 * BAR_DONE, 8);
        mbar_init(bar + 8 * BAR_WO2, 1);
        asm volatile("fence.mbarrier_init.release.cluster;" ::: "memory");
        mbar_expect(bar + 8 * BAR_WPHI, 3072);
        bulk_g2s(sb + OFF_GW, gatew, 1024, bar + 8 * BAR_WPHI);
        bulk_g2s(sb + OFF_WPHI, wphi + bi_j * 1024, 2048, bar + 8 * BAR_WPHI);
    } else if (tid == 64) {
        asm volatile("prefetch.tensormap [%0];" ::"l"(&mw) : "memory");
    }
    const uint32_t buf = sb + OFF_BUF + w4 * BUF_STRIDE, k3 = sb + OFF_K3 + w4 * K3_STRIDE;
    if (warp >= 8) {
#pragma unroll
        for (int v = 0; v < 3; v++) if (v * 32 + lane < K3_STRIDE / 16) sts128(k3 + (v * 32 + lane) * 16, 0, 0, 0, 0);
    }
    __syncthreads();
    asm volatile("" : "+r"(pdt), "+r"(done0)::"memory");
    const unsigned epoch1 = (done0 >> 7) + 1u;
    const uint32_t tag = epoch1 & 1u;

    if (warp < 8) {
        const int wg = warp >> 2;
        if (warp == 0) STAMP(21);
        float acc[96];
        const int grow = bi_j * 16 + warp * 2 + (lane >> 4);
        const uint32_t gx_a = grow * 128 + ((((lane & 15) >> 1) ^ (grow & 7)) << 4) + (lane & 1) * 8;
        const int srow = warp * 16 + (lane & 15);
        const uint32_t srow_a = srow * 128;
        const int sx = srow & 7, shi = lane >> 4;
        auto last_of_8 = [&](int c) {
            unsigned old;
            asm volatile("atom.acq_rel.cta.shared.add.u32 %0,[%1],1;" : "=r"(old) : "r"(bar + OFF_CNT + 4 * c) : "memory");
            return (old & 7) == 7;
        };
        const int qq = (bi_i & 2) + ((lane >> 1) & 1);
        const int kvf_n = warp < 4 ? 8 : ((warp == 4 && (bi_i & 1) == 0) ? 4 : 0);
        uint2* kvf_dst = (uint2*)(scr->kvf + (bi_j * 4 + (bi_i >> 2)) * 68) +
                         (warp == 4 ? (64 + qq) * 2 + (lane & 1) : ((bi_i & 3) * 8 + w4 * 2 + (lane & 1)) * 4 + (lane >> 1));
        float gsum = 0.f;
#pragma unroll
        for (int r = 0; r < 96; r++) acc[r] = 0.f;
        fence_regs<96>(acc);
        const uint64_t da0 = mkdesc(sb + wg * 8192, 16, 1024), db0 = mkdesc(sb + 16384, 8192, 1024);
        {
            const uint32_t old = tag ^ 1u;
            const uint4 z4 = make_uint4(old, 0, old, 0);
            uint4* kvp = scr->kvp + bi * 544 + wg * 272;
            if (w4 < 2) {
#pragma unroll
                for (int f = 0; f < 4; f++) st_rlx128(kvp + w4 * 136 + lane + f * 32, z4);
            } else if (w4 == 2 && lane < 4) {
#pragma unroll
                for (int f = 0; f < 4; f++) st_rlx128(kvp + (f >> 1) * 136 + 128 + (f & 1) * 4 + lane, z4);
            }
            if (lane < kvf_n) st_rlx64(kvf_dst, old, 0);
            if (lane >= 30) st_rlx128(scr->o + ((bi_i * 8 + warp) * 32 + bi_j * 4 + 3) * 32 + lane, z4);
            if (lane < 8) st_rlx32(scr->g + (bi_i * 64 + bi_j * 8 + warp) * 8 + lane, old);
        }
        mbar_wait(bar + 8 * BAR_WPHI, 0);
#pragma unroll 1
        for (int kb = 0; kb < 8; kb++) {
            const int s = kb & 3;
            const uint64_t da = da0 + s * (SLOT >> 4), db = db0 + s * (SLOT >> 4);
            mbar_wait(bar + 8 * (BAR_FULL + s), kb >> 2);
            if (kb == 0 && warp == 0) STAMP(0);
            wg_fence();
#pragma unroll
            for (int k = 0; k < 4; k++) wgmma192(acc, da + 2 * k, db + 128 * k);
            wg_commit();
            wg_wait<1>();
            __syncwarp();
            if (lane == 0 && kb > 0 && kb < 7) {
                const int ps = (kb - 1) & 3;
                if (last_of_8(ps)) {
                    if (kb < 5) load_stage(kb + 3);
                    else {
                        mbar_expect(bar + 8 * BAR_WO, 32768);
                        tma2d(sb + ps * SLOT, &mwo, (bi_j & 3) * 128 + ps * 64, 0, bar + 8 * BAR_WO);
                    }
                }
            }
            __syncwarp();
            const uint32_t st = sb + s * SLOT;
            if (kb == (bi_j >> 1)) {
                uint32_t* xt = (uint32_t*)scr->xt + ((kb + rot) * 16 + (g >> 2)) * 4096 + (bi_i * 16 + warp * 2) * 16 + (g & 3) * 4 + q;
#pragma unroll
                for (int cb = 0; cb < 8; cb += 2) {
                    uint32_t r[4];
                    ldsm4t(r, st + srow_a + (((cb + shi) ^ sx) << 4));
                    xt[cb * 8192] = r[0]; xt[cb * 8192 + 16] = r[1]; xt[cb * 8192 + 8192] = r[2]; xt[cb * 8192 + 8192 + 16] = r[3];
                }
                __syncwarp();
                if (lane == 0) mbar_arrive(bar + 8 * BAR_XT);
            }
            {
                uint32_t x0, x1, w0, w1;
                asm volatile("ld.shared.v2.b32 {%0,%1},[%2];" : "=r"(x0), "=r"(x1) : "r"(st + gx_a) : "memory");
                asm volatile("ld.shared.v2.b32 {%0,%1},[%2];" : "=r"(w0), "=r"(w1) : "r"(sb + OFF_GW + ((kb + rot) & 7) * 128 + (lane & 15) * 8) : "memory");
                const uint32_t p0 = hmul2(x0, w0), p1 = hmul2(x1, w1);
                gsum += (bf_lo(p0) + bf_hi(p0)) + (bf_lo(p1) + bf_hi(p1));
            }
        }
        wg_wait<0>();
        fence_regs<96>(acc);
        __syncwarp();
        if (lane == 0) mbar_arrive(bar + 8 * BAR_DONE);
        if (warp == 0) STAMP(1);
        uint32_t in[32], va[16];
#pragma unroll
        for (int r = 0; r < 16; r++) {
            in[r] = pack2(acc[32 + 2 * r], acc[32 + 2 * r + 1]);
            in[16 + r] = pack2(acc[2 * r], acc[2 * r + 1]);
            va[r] = pack2(acc[64 + 2 * r], acc[64 + 2 * r + 1]);
        }
        const uint32_t wphi_a = sb + OFF_WPHI + (lane & 15) * 32 + (lane >> 4) * 16;
        uint32_t pq[4][8];
#pragma unroll 1
        for (int it = 0; it < 4; it++) {
            hedgehog2(in, wphi_a + (it & 1) * 1024, pq + 2);
#pragma unroll
            for (int r = 0; r < 24; r++) in[r] = in[r + 8];
            if (it < 2) {
#pragma unroll
                for (int hs = 0; hs < 4; hs++) {
                    float c[4] = {0.f, 0.f, 0.f, 0.f};
                    uint32_t* o = pq[2 + (hs >> 1)] + 4 * (hs & 1);
                    mma16816(c, o[0], o[1], o[2], o[3], 0x3f803f80u, 0x3f803f80u);
                    const float r0 = rcp(c[0]), r1 = rcp(c[2]);
                    const uint32_t s0 = pack2(r0, r0), s1 = pack2(r1, r1);
                    o[0] = hmul2(o[0], s0); o[1] = hmul2(o[1], s1); o[2] = hmul2(o[2], s0); o[3] = hmul2(o[3], s1);
                }
                if (it == 0) mbar_wait(bar + 8 * BAR_DONE, 0);
                const uint32_t pt = sb + OFF_P + it * 16384 + srow_a, vt = sb + OFF_V + it * 16384 + srow_a;
#pragma unroll
                for (int hl = 0; hl < 2; hl++) {
                    stsm4(pt + (((4 * hl + shi) ^ sx) << 4), pq[2 + hl][0], pq[2 + hl][1], pq[2 + hl][2], pq[2 + hl][3]);
                    stsm4(pt + (((4 * hl + 2 + shi) ^ sx) << 4), pq[2 + hl][4], pq[2 + hl][5], pq[2 + hl][6], pq[2 + hl][7]);
                    stsm4(vt + (((2 * hl + shi) ^ sx) << 4), va[4 * hl], va[4 * hl + 1], va[4 * hl + 2], va[4 * hl + 3]);
                }
                if (lane < 16) sts128(vt + ((4 ^ sx) << 4), 0x3f803f80u, 0x3f803f80u, 0x3f803f80u, 0x3f803f80u);
#pragma unroll
                for (int r = 0; r < 8; r++) va[r] = va[r + 8];
            }
            if (it == 1) {
                asm volatile("fence.proxy.async.shared::cta;" ::: "memory");
                bar_named(1, 256);
                if (warp == 0) STAMP(2);
                float d[32];
                const uint64_t dv = mkdesc(sb + OFF_V + wg * 16384, 16, 1024), dp = mkdesc(sb + OFF_P + wg * 16384, 16, 1024);
                wg_fence();
#pragma unroll
                for (int k = 0; k < 8; k++) wgmma64_tt(d, dv + 128 * k, dp + 128 * k, k != 0);
                wg_commit();
                wg_wait<0>();
                fence_regs<32>(d);
                uint4* kvp = scr->kvp + bi * 544 + wg * 272;
                if (w4 < 2) {
                    uint32_t e[16];
#pragma unroll
                    for (int r = 0; r < 16; r++) e[r] = __float_as_uint(w4 ? d[16 + r] : d[r]);
                    uint4* p = kvp + w4 * 136 + lane;
#pragma unroll
                    for (int ks = 0; ks < 2; ks++)
#pragma unroll
                        for (int nt = 0; nt < 2; nt++)
                            st_rlx128(p + (ks * 2 + nt) * 32, tag4(e[8 * ks + 2 * nt], e[8 * ks + 2 * nt + 1], e[8 * ks + 4 + 2 * nt], e[8 * ks + 4 + 2 * nt + 1], tag));
                } else if (w4 == 2 && lane < 4) {
#pragma unroll
                    for (int hl = 0; hl < 2; hl++)
#pragma unroll
                        for (int ks = 0; ks < 2; ks++)
                            st_rlx128(kvp + hl * 136 + 128 + ks * 4 + lane, tag4(__float_as_uint(d[16 * hl + 8 * ks]), __float_as_uint(d[16 * hl + 8 * ks + 1]),
                                                                                __float_as_uint(d[16 * hl + 8 * ks + 4]), __float_as_uint(d[16 * hl + 8 * ks + 5]), tag));
                }
                if (warp == 0) STAMP(3);
            }
            if (it == 2) {
#pragma unroll
                for (int r = 0; r < 8; r++) { pq[0][r] = pq[2][r]; pq[1][r] = pq[3][r]; }
                if (warp == 0) STAMP(12);
                if (kvf_n) {
                    const bool zw = warp == 4;
                    const uint4* src = scr->kvp + bi_j * (16 * 544) + (bi_i >> 2) * 136 +
                                       (zw ? (lane >> 2) * (2 * 544) + 128 + (lane & 1) * 4 + qq
                                           : (lane >> 3) * (4 * 544) + ((lane >> 1) & 3) * 32 + (bi_i & 3) * 8 + warp * 2 + (lane & 1));
                    const int s23 = zw ? 0 : 2 * 544;
                    uint4 v[4];
                    int n = 0;
#pragma unroll 1
                    while (true) {
                        v[0] = ld_rlx128(src); v[1] = ld_rlx128(src + 544); v[2] = ld_rlx128(src + s23); v[3] = ld_rlx128(src + s23 + 544);
                        if (!__any_sync(~0u, (bad4(v[0], tag) | bad4(v[1], tag) | bad4(v[2], tag) | bad4(v[3], tag)) & 1)) break;
                        if (++n > SPIN_LIMIT) break;
                    }
                    float f[4];
                    f[0] = __uint_as_float(v[2].x) + __uint_as_float(v[3].x); f[1] = __uint_as_float(v[2].y) + __uint_as_float(v[3].y);
                    f[2] = __uint_as_float(v[2].z) + __uint_as_float(v[3].z); f[3] = __uint_as_float(v[2].w) + __uint_as_float(v[3].w);
                    float e0 = __uint_as_float(v[0].x) + __uint_as_float(v[1].x), e1 = __uint_as_float(v[0].y) + __uint_as_float(v[1].y);
                    float e2 = __uint_as_float(v[0].z) + __uint_as_float(v[1].z), e3 = __uint_as_float(v[0].w) + __uint_as_float(v[1].w);
                    if (zw) {
                        e0 = __shfl_xor_sync(~0u, f[0], 4); e1 = __shfl_xor_sync(~0u, f[1], 4);
                        e2 = __shfl_xor_sync(~0u, f[2], 4); e3 = __shfl_xor_sync(~0u, f[3], 4);
                    }
                    f[0] += e0; f[1] += e1; f[2] += e2; f[3] += e3;
#pragma unroll
                    for (int o = 8; o <= 16; o <<= 1)
#pragma unroll
                        for (int r = 0; r < 4; r++) f[r] += __shfl_xor_sync(~0u, f[r], o);
                    if (lane < kvf_n) st_rlx64(kvf_dst, tagw(pack2(f[0], f[1]), tag), pack2(f[2], f[3]));
                }
                __syncwarp();
                if (lane == 0 && last_of_8(4)) {
                    mbar_expect(bar + 8 * BAR_WO2, 65536);
                    tma2d(sb + 2 * SLOT, &mwo, (bi_j & 3) * 128, 256, bar + 8 * BAR_WO2);
                    tma2d(sb + OFF_V, &mwo, (bi_j & 3) * 128 + 64, 256, bar + 8 * BAR_WO2);
                }
                __syncwarp();
                if (warp == 0) STAMP(13);
#pragma unroll
                for (int o = 1; o < 16; o <<= 1) gsum += __shfl_xor_sync(~0u, gsum, o);
                const float gate = bf_round(rcp(1.0f + ex2(-1.4426950408889634f * bf_round(gsum))));
                const uint32_t gv = __shfl_sync(~0u, __float_as_uint(gate) | tag, (lane & 4) * 4);
                if (lane < 8) st_rlx32(scr->g + (bi_i * 64 + bi_j * 8 + warp) * 8 + lane, gv);
            }
        }
        if (warp == 0) STAMP(4);
        {
            {
                const uint4* kp = scr->kvf + bi_j * 272 + tid;
                uint4 v0, v1;
                int n = 0;
#pragma unroll 1
                while (true) {
                    v0 = ld_rlx128(kp); v1 = ld_rlx128(kp + (tid < 16 ? 256 : 0));
                    if (!__any_sync(~0u, (bad4(v0, tag) | bad4(v1, tag)) & 1)) break;
                    if (++n > SPIN_LIMIT) break;
                }
                sts128(sb + OFF_KVF + tid * 16, v0.x, v0.y, v0.z, v0.w);
                if (tid < 16) sts128(sb + OFF_KVF + 4096 + tid * 16, v1.x, v1.y, v1.z, v1.w);
                bar_named(1, 256);
            }
            uint4 kf[4][3];
#pragma unroll
            for (int hh = 0; hh < 4; hh++) {
                const uint32_t a = sb + OFF_KVF + hh * 1088;
                kf[hh][0] = lds128(a + lane * 32); kf[hh][1] = lds128(a + lane * 32 + 16); kf[hh][2] = lds128(a + 1024 + q * 16);
            }
            if (warp == 0) STAMP(5);
            uint4 own[4];
#pragma unroll
            for (int hh = 0; hh < 4; hh++) {
                float c[6][4];
#pragma unroll
                for (int t = 0; t < 6; t++) { c[t][0] = c[t][1] = c[t][2] = c[t][3] = 0.f; }
                const uint32_t* a = pq[hh];
                const bool od = g & 1;
                mma16816(c[0], a[0], a[1], a[2], a[3], od ? 0x3f803f80u : kf[hh][2].x, od ? 0x3f803f80u : kf[hh][2].y);
                mma16816(c[1], a[4], a[5], a[6], a[7], od ? 0x3f803f80u : kf[hh][2].z, od ? 0x3f803f80u : kf[hh][2].w);
                mma16816(c[2], a[0], a[1], a[2], a[3], kf[hh][0].x, kf[hh][0].y);
                mma16816(c[3], a[0], a[1], a[2], a[3], kf[hh][0].z, kf[hh][0].w);
                mma16816(c[4], a[4], a[5], a[6], a[7], kf[hh][1].x, kf[hh][1].y);
                mma16816(c[5], a[4], a[5], a[6], a[7], kf[hh][1].z, kf[hh][1].w);
                uint32_t w[4];
#pragma unroll
                for (int k = 0; k < 2; k++) {
                    const float rho = c[0][2 * k + 1] * rcp(c[1][2 * k + 1]);
                    const float r = rcp(fmaf(c[0][2 * k + 1], 1e-6f, fmaf(rho, c[1][2 * k], c[0][2 * k]))), rr = r * rho;
                    w[k] = pack2(fmaf(c[4][2 * k], rr, c[2][2 * k] * r), fmaf(c[4][2 * k + 1], rr, c[2][2 * k + 1] * r));
                    w[2 + k] = pack2(fmaf(c[5][2 * k], rr, c[3][2 * k] * r), fmaf(c[5][2 * k + 1], rr, c[3][2 * k + 1] * r));
                }
                own[hh] = tag4(w[0], w[1], w[2], w[3], tag);
            }
            uint4* og = scr->o + ((bi_i * 8 + warp) * 32 + bi_j * 4) * 32 + lane;
#pragma unroll
            for (int hh = 0; hh < 4; hh++) st_rlx128(og + hh * 32, own[hh]);
        }
        if (warp == 0) STAMP(6);
        float oc[64];
        const int slab = bi_i * 8 + (bi_j >> 2) * 4 + w4;
        const uint8_t* yb = (const uint8_t*)scr->y + (size_t)((bi_j & 3) * 32 + wg * 16 + (q >> 1)) * 16384 + slab * 128 + g * 16 + (q & 1) * 8;
        const unsigned* gp = scr->g + (slab * 8 + (g >> 1)) * 8 + (g & 1) * 4;
        uint2 yv[8]; unsigned g0, g1;
        {
            const uint4* osrc = scr->o + (slab * 32 + wg * 16) * 32 + lane;
            uint4 fr[16];
            const unsigned* probe = (const unsigned*)(osrc - lane + ((lane & 3) * 4 + 3) * 32 + 31) + 2;
            {
                unsigned miss = ~0u;
                int n = 0;
#pragma unroll
                for (int s = 0; s < 4; s++) {
#pragma unroll 1
                    while ((miss >> s) & 1) { miss = __ballot_sync(~0u, (ld_rlx(probe) ^ tag) & 1); if (++n > SPIN_LIMIT) break; }
#pragma unroll
                    for (int k = 4 * s; k < 4 * s + 4; k++) fr[k] = ld_rlx128(osrc + k * 32);
                }
            }
            if (warp == 0) STAMP(14);
            mbar_wait(bar + 8 * (wg ? BAR_WO2 : BAR_WO), 0);
            const uint64_t dw = mkdesc(sb + wg * 2 * SLOT, wg ? 32768 : SLOT, 1024);
#pragma unroll
            for (int s = 0; s < 4; s++) {
                int n = 0;
#pragma unroll 1
                while (__builtin_expect(__any_sync(~0u, (bad4(fr[4 * s], tag) | bad4(fr[4 * s + 1], tag) | bad4(fr[4 * s + 2], tag) | bad4(fr[4 * s + 3], tag)) & 1), 0)) {
#pragma unroll
                    for (int k = 4 * s; k < 4 * s + 4; k++) fr[k] = ld_rlx128(osrc + k * 32);
                    if (++n > SPIN_LIMIT) break;
                }
                wg_fence();
#pragma unroll
                for (int hh = 0; hh < 4; hh++) wgmma128_rs(oc, fr[4 * s + hh], dw + 128 * (4 * s + hh), (s | hh) != 0);
                wg_commit();
                if (s == 1) {
                    wg_wait<1>();
#pragma unroll
                    for (int nt = 0; nt < 8; nt++) yv[nt] = ld_rlx64(yb + nt * 32768);
                    g0 = ld_rlx(gp); g1 = ld_rlx(gp + 32);
                }
            }
            if (warp == 0) STAMP(7);
            {
                const unsigned* yprobe = scr->yflag + ((bi_j & 3) * 32 + wg * 16 + (lane & 15)) * 8;
                int n = 0;
#pragma unroll 1
                while (true) {
                    uint32_t bad = (g0 ^ tag) | (g1 ^ tag);
#pragma unroll
                    for (int nt = 0; nt < 8; nt++) bad |= yv[nt].x ^ tag;
                    if (!__any_sync(~0u, bad & 1)) break;
#pragma unroll 1
                    while (__any_sync(~0u, (ld_rlx(yprobe) ^ tag) & 1)) { if (++n > SPIN_LIMIT) break; }
#pragma unroll
                    for (int nt = 0; nt < 8; nt++) yv[nt] = ld_rlx64(yb + nt * 32768);
                    g0 = ld_rlx(gp); g1 = ld_rlx(gp + 32);
                    if (++n > SPIN_LIMIT) break;
                }
            }
            if (warp == 0) STAMP(28);
            wg_wait<0>();
            fence_regs<64>(oc);
        }
        {
            bar_named(3 + wg, 128);
            const uint32_t xw = sb + wg * 2 * SLOT + (tid & 127) * 16, xr = sb + (wg ^ 1) * 2 * SLOT + (tid & 127) * 16;
#pragma unroll
            for (int r = 0; r < 8; r++) {
                const float* o = oc + 4 * r;
                sts128(xw + r * 2048, __float_as_uint(wg ? o[0] : o[32]), __float_as_uint(wg ? o[1] : o[33]), __float_as_uint(wg ? o[2] : o[34]), __float_as_uint(wg ? o[3] : o[35]));
            }
#pragma unroll
            for (int r = 0; r < 32; r++) oc[r] = wg ? oc[32 + r] : oc[r];
            bar_named(1, 256);
            if (warp == 0) STAMP(8);
            const float ga = bf_hi(g0), gb = bf_hi(g1);
            const float ha = bf_round(1.0f - ga), hb = bf_round(1.0f - gb);
            uint32_t w[8][2];
#pragma unroll
            for (int nt = 0; nt < 8; nt++) {
                const uint4 p = lds128(xr + nt * 2048);
                w[nt][0] = pack2(fmaf(ga, oc[4 * nt] + __uint_as_float(p.x), ha * bf_lo(yv[nt].x)), fmaf(ga, oc[4 * nt + 1] + __uint_as_float(p.y), ha * bf_hi(yv[nt].x)));
                w[nt][1] = pack2(fmaf(gb, oc[4 * nt + 2] + __uint_as_float(p.z), hb * bf_lo(yv[nt].y)), fmaf(gb, oc[4 * nt + 3] + __uint_as_float(p.w), hb * bf_hi(yv[nt].y)));
            }
            const uint32_t ob = sb + wg * 2 * SLOT + 16384 + w4 * 2048;
#pragma unroll
            for (int nt = 0; nt < 8; nt += 2)
                stsm4(ob + (lane & 15) * 128 + (((nt + shi) ^ (lane & 7)) << 4), w[nt][0], w[nt][1], w[nt + 1][0], w[nt + 1][1]);
            __syncwarp();
            bf16* op = out + (size_t)(slab * 16) * 512 + (bi_j & 3) * 128 + wg * 64 + (lane & 7) * 8;
#pragma unroll
            for (int it = 0; it < 4; it++) {
                const int r = it * 4 + (lane >> 3);
                uint4 v = lds128(ob + r * 128 + (((lane & 7) ^ (r & 7)) << 4));
                *(uint4*)(op + r * 512) = v;
            }
        }
        if (warp == 0) STAMP(10);
    } else {
        const int st = tid - 256;
        float kc[24];
        const int brow = (buf >> 7) & 7;
#pragma unroll
        for (int t = 0; t < 24; t++) kc[t] = 0.f;
        fence_regs<24>(kc);
        {
            const float dt = bf_round(expf((ch & 1) ? bf_hi(pdt) : bf_lo(pdt)));
#pragma unroll 1
            for (int it = 0; it < KG_ROUNDS; it++) {
                const int sh = (it & 1) * 16;
                auto pick = [&](const uint2& v) { return __uint_as_float(((it & 2 ? v.y : v.x) >> sh) << 16); };
                const float ea = bf_round(expf(pick(pla)));
                const float arl = (-ea * dt) * 1.4426950408889634f, ait = (pick(pai) * dt) * 0.15915494309189535f;
                cf C2; C2.re = 2.0f * (pick(pcr) * dt); C2.im = 2.0f * (pick(pci) * dt);
                const cf z1 = cexp_p(arl, ait, 1.0f), z128 = cexp_p(arl, ait, 128.0f);
                cf z8 = cexp_p(arl, ait, 8.0f); z8.im = -z8.im;
                const uint32_t lp = buf + lane * 4;
                auto put = [&](int row, const cf& v) { sts32((lp ^ (((row + brow) & 7) << 4)) + row * 128, pack2(v.re, v.im)); };
                {
                    const cf z16 = cmul(z8, z8);
                    cf e; e.re = 1.f; e.im = 0.f;
                    cf o = z8;
                    put(0, e); put(1, o);
                    e = z16; put(2, e);
#pragma unroll
                    for (int b = 3; b < 16; b += 2) {
                        o = cmul(o, z16); put(b, o);
                        if (b + 1 < 16) { e = cmul(e, z16); put(b + 1, e); }
                    }
                }
                cf h[8];
                h[0] = C2; put(16, h[0]);
                {
                    const cf z2 = cmul(z1, z1);
                    h[1] = cmul(h[0], z1);
#pragma unroll
                    for (int r = 2; r < 8; r++) h[r] = cmul(h[r - 2], z2);
#pragma unroll
                    for (int r = 1; r < 8; r++) put(16 + r, h[r]);
                }
#pragma unroll
                for (int r = 0; r < 8; r++) { h[r] = cmul(h[r], z128); put(24 + r, h[r]); }
#pragma unroll
                for (int al = 0; al < 2; al++)
#pragma unroll
                    for (int r = 0; r < 4; r++) { h[2 * r] = cmul(h[2 * r], z128); put(32 + al * 4 + r, h[2 * r]); }
#pragma unroll
                for (int al = 0; al < 4; al++)
#pragma unroll
                    for (int r = 0; r < 2; r++) { h[4 * r] = cmul(h[4 * r], z128); put(40 + al * 2 + r, h[4 * r]); }
#pragma unroll
                for (int al = 0; al < 9; al++) { h[0] = cmul(h[0], z128); put(48 + al, h[0]); }
                asm volatile("fence.proxy.async.shared::cta;" ::: "memory");
                bar_named(2, 128);
                uint32_t la[4][4];
#pragma unroll
                for (int ks = 0; ks < 4; ks++) ldsm4(la[ks], buf + (lane & 15) * 128 + (((2 * ks + (lane >> 4)) ^ ((lane + brow) & 7)) << 4));
                const uint64_t dh = mkdesc(sb + OFF_BUF + 2048, 16, 1024);
#pragma unroll
                for (int c = 0; c < 4; c++) {
                    uint32_t a[4][4];
#pragma unroll
                    for (int r = 0; r < 16; r++) a[r >> 2][r & 3] = (c == w4) ? la[r >> 2][r & 3] : 0u;
                    wg_fence();
#pragma unroll
                    for (int ks = 0; ks < 4; ks++) wgmma48_rs(kc, a[ks][0], a[ks][1], a[ks][2], a[ks][3], dh + c * (BUF_STRIDE >> 4) + 2 * ks);
                    wg_commit();
                }
                wg_wait<0>();
                fence_regs<24>(kc);
                bar_named(2, 128);
            }
        }
        if (warp == 8) STAMP(22);
        if (warp == 8) {
            mbar_wait(bar + 8 * BAR_XT, 0);
            if (lane == 0) asm volatile("red.release.gpu.global.add.u32 [%0],8;" ::"l"(scr->xcnt + ((bi_j >> 1) + rot) * 32) : "memory");
        }
        if (lane == 0) {
            int n = 0;
#pragma unroll 1
            while ((int)(ld_acq(scr->xcnt + bi_j * 32) - (epoch1 << 7)) < 0) { __nanosleep(200); if (++n > SPIN_LIMIT) break; }
        }
        __syncwarp();
        if (warp == 8) STAMP(15);
        uint4 ur[8];
#pragma unroll
        for (int v = 0; v < 8; v++) ur[v] = __ldcg(scr->xt + bi * 1024 + st + 128 * v);
#pragma unroll
        for (int v = 0; v < 3; v++) if (v * 32 + lane < U_PAD / 16) sts128(sb + OFF_U + w4 * U_STRIDE + (v * 32 + lane) * 16, 0, 0, 0, 0);
        if (st < 8) st_rlx32(scr->yflag + bi * 8 + st, tag ^ 1u);
#pragma unroll
        for (int v = 0; v < 8; v++) {
            const uint32_t a = sb + OFF_U + (st & 3) * U_STRIDE + U_PAD + ((st >> 2) + 32 * v) * 16;
            sts128(a ^ ((a >> 3) & 0x70), ur[v].x, ur[v].y, ur[v].z, ur[v].w);
        }
        if (warp == 8) STAMP(16);
        mbar_wait(bar + 8 * BAR_WO, 0);
        const uint32_t kt = sb + kt_off(w4);
#pragma unroll
        for (int v = 0; v < 8; v++) if (v * 32 + lane < KT_BYTES / 16) sts128(kt + (v * 32 + lane) * 16, 0, 0, 0, 0);
        if (lane < 14) sts128(buf + (lane >= 7 ? W3_OFF - 112 : 0) + lane * 16, 0, 0, 0, 0);
        __syncwarp();
        if (lane == 0) kc[4 * 0 + 0] += (ch & 1) ? bf_hi(pds) : bf_lo(pds);
#pragma unroll
        for (int i = 0; i < 2; i++) {
            const int be = g + 8 * i;
#pragma unroll
            for (int t = 0; t < 2; t++) {
                const uint32_t a = kt + (64 + 128 * t + 8 * be + 2 * q) * 4;
                const uint32_t w = pack2(kc[4 * t + 2 * i + 1], kc[4 * t + 2 * i]);
                sts32(a + 4, w); sts16(a, w >> 16); sts16(a + 10, w);
            }
            {
                const int p = 256 + 128 * (q >> 1) + 8 * be + 4 * (q & 1);
                const uint32_t a = kt + (64 + p) * 4;
                const uint32_t w = pack2(kc[4 * 2 + 2 * i + 1], kc[4 * 2 + 2 * i]);
                const uint32_t aa = (w >> 16) | (w & 0xffff0000u);
                if (p != 256) { sts16(a - 4, aa); sts32(a, aa); } else sts16(a, aa);
                sts32(a + 4, aa); sts32(a + 8, w); sts16(a + 14, w);
            }
            {
                const int k = 64 + 16 * q + be;
                const uint32_t w = pack2(kc[4 * 3 + 2 * i], kc[4 * 3 + 2 * i + 1]);
                if (k != 64) sts16(kt + KT_E2 + (k - 1) * 2, w);
                else {
                    const uint32_t a = kt + (64 + 511) * 4, aa = (w << 16) | (w & 0xffffu);
                    sts16(a, w); sts32(a + 4, aa); sts32(a + 8, aa); sts32(a + 12, aa); sts16(a + 18, w);
                }
                sts16(kt + KT_E2 + KT_E2O + k * 2, w >> 16);
            }
#pragma unroll
            for (int b = 0; b < 2; b++) {
                const int k = 64 + 8 * (2 * q + b) + (be >> 1);
                const uint32_t w = pack2(kc[4 * 4 + 2 * i + b], 0.f);
                const bool k1024 = !(be & 1) && k == 64;
                const uint32_t a = k3 + (k1024 ? 188 + 64 : ((be & 1) ? 94 + k : k - 1)) * 4 - 34 * 4;
                sts16(a, w);
                if (!((be & 1) && k == 127)) sts16(a + 6, w);
                if (k1024) sts16(kt + KT_E2 + 127 * 2, w);
            }
        }
        if (lane == 0) sts16(k3 + (127 - 34) * 4, pack2(kc[4 * 5 + 0], 0.f));
        asm volatile("fence.proxy.async.shared::cta;" ::: "memory");
        bar_named(2, 128);
        if (warp == 8) STAMP(17);
        mbar_wait(bar + 8 * BAR_DONE, 0);
        float y[4][16];
#pragma unroll
        for (int c = 0; c < 4; c++) {
#pragma unroll
            for (int r = 0; r < 16; r++) y[c][r] = 0.f;
            fence_regs<16>(y[c]);
        }
        {
            uint32_t Q[3][4][4];
            uint32_t ka = sb + (64 - 48 + 16 * w4 + g - 2 * q) * 4;
            uint64_t du = mkdesc(sb + OFF_U + U_PAD + 96, 16, 1024);
#pragma unroll 1
            for (int it = 0; it < 13; it++) {
#pragma unroll
                for (int b = 0; b < 3; b++) {
                    wg_wait<2>();
#pragma unroll
                    for (int c = 0; c < 4; c++) {
                        Q[b][c][0] = lds32(ka + kt_off(c) + b * 64); Q[b][c][1] = lds32(ka + kt_off(c) + b * 64 + 32);
                        Q[b][c][2] = lds32(ka + kt_off(c) + b * 64 - 32); Q[b][c][3] = Q[b][c][0];
                    }
                    if (b == 0 || it < 12) {
                        wg_fence();
#pragma unroll
                        for (int c = 0; c < 4; c++) wgmma32_rs(y[c], Q[b][c], du + c * (U_STRIDE >> 4) - 2 * b);
                        wg_commit();
                    }
                }
                ka += 192; du -= 6;
            }
        }
        if (warp == 8) STAMP(24);
        {
            const uint32_t u0 = sb + OFF_U + w4 * U_STRIDE + U_PAD + lane * 16;
#pragma unroll 1
            for (int r2 = 0; r2 < 3; r2++) {
#pragma unroll
                for (int hf = 0; hf < 2; hf++) {
                    const int rho = 2 * r2 + hf, ci = lane + 32 * rho;
                    uint4 e4[4];
#pragma unroll
                    for (int v = 0; v < 4; v++) { const uint32_t a = u0 + rho * 512 + (v - 3) * 16; e4[v] = lds128(a ^ ((a >> 3) & 0x70)); }
                    float S[29];
                    const uint32_t* ew = (const uint32_t*)e4;
                    S[3] = 0.f;
#pragma unroll
                    for (int k = 4; k <= 28; k++) S[k] = S[k - 1] + ((k & 1) ? bf_hi(ew[k >> 1]) : bf_lo(ew[k >> 1]));
                    auto win = [&](int lo, int hi, uint32_t a, bool on) {
                        const uint32_t w0 = pack2(S[hi] - S[lo - 1], S[hi + 1] - S[lo]), w1 = pack2(S[hi + 2] - S[lo + 1], S[hi + 3] - S[lo + 2]);
                        const uint32_t w2 = pack2(S[hi + 4] - S[lo + 3], S[hi + 5] - S[lo + 4]), w3 = pack2(S[hi + 6] - S[lo + 5], S[hi + 7] - S[lo + 6]);
                        asm volatile("{.reg .pred p; setp.ne.b32 p,%5,0; @p st.shared.v4.b32 [%0],{%1,%2,%3,%4};}" ::"r"(a), "r"(w0), "r"(w1), "r"(w2), "r"(w3), "r"((int)on) : "memory");
                    };
                    const uint32_t sw = (ci ^ ((ci >> 3) & 1)) << 4;
                    win(14, 18, buf + W5_OFF + 112 + ci * 16, true); win(19, 21, buf + W3_OFF + 112 + ci * 16, true);
                    win(4, 12, buf + W9_OFF + sw, r2 < 2); win(13, 19, sb + OFF_X + w4 * 4096 + sw, r2 < 2); win(20, 21, sb + OFF_X + w4 * 4096 + 2048 + sw, r2 < 2);
                }
            }
        }
        wg_wait<0>();
#pragma unroll
        for (int c = 0; c < 4; c++) fence_regs<16>(y[c]);
        if (warp == 8) STAMP(18);
        bar_named(2, 128);
        if (warp == 8) STAMP(23);
        {
            uint32_t Q[3][4][4];
            uint32_t wa = sb + OFF_BUF + (15 - (lane >> 4) * 8 - (lane & 7) + 2 * w4 + ((lane >> 3) & 1)) * 16;
            uint64_t de = (uint64_t)(((sb + KT_E2 - 16) & 0x3FFFF) >> 4) | ((uint64_t)1 << 16) | ((uint64_t)8 << 32);
#pragma unroll 1
            for (int s = 0; s < 4; s++) {
#pragma unroll
                for (int b = 0; b < 6; b++) {
                    wg_wait<2>();
#pragma unroll
                    for (int c = 0; c < 4; c++) ldsm4t(Q[b % 3][c], wa + c * BUF_STRIDE + (b & 1) * W3_OFF + 256 * (b >> 1));
                    wg_fence();
#pragma unroll
                    for (int c = 0; c < 4; c++) wgmma32_rs(y[c], Q[b % 3][c], de + (kt_off(c) >> 4) + (b & 1) * (KT_E2O >> 4) - 2 * (b >> 1));
                    wg_commit();
                }
                wa += 768; de -= 6;
            }
        }
        wg_wait<0>();
#pragma unroll
        for (int c = 0; c < 4; c++) fence_regs<16>(y[c]);
        if (warp == 8) STAMP(19);
        {
            const int ap = (lane & 7) + (lane >> 4) * 8;
            const uint32_t loff = ((2 * ap + ((lane >> 3) & 1)) ^ ((ap >> 2) & 1)) << 4;
#pragma unroll 1
            for (int ph = 0; ph < 3; ph++) {
                const uint32_t ka = sb + OFF_K3 + (ph * 94 + 4 * g + w4 - 2 * q - 34) * 4;
#pragma unroll
                for (int c = 0; c < 4; c++) {
                    const uint32_t wb = (ph ? sb + OFF_X + c * 4096 + (ph - 1) * 2048 : sb + OFF_BUF + c * BUF_STRIDE + W9_OFF) + loff;
                    uint32_t B[4][2];
#pragma unroll
                    for (int d = 0; d < 4; d++) { B[d][0] = lds32(ka + c * K3_STRIDE + (48 + 16 * d) * 4); B[d][1] = lds32(ka + c * K3_STRIDE + (40 + 16 * d) * 4); }
#pragma unroll
                    for (int s = 0; s < 4; s++) {
                        uint32_t A[4];
                        ldsm4t(A, wb + s * 512);
                        if (s < 2) mma16816(y[c] + 8, A[0], A[1], A[2], A[3], B[1 - s][0], B[1 - s][1]);
                        mma16816(y[c] + 12, A[0], A[1], A[2], A[3], B[3 - s][0], B[3 - s][1]);
                    }
                }
            }
        }
        uint4* yp = scr->y + bi * 1024 + (8 * q + w4) * 8 + g;
#pragma unroll
        for (int j = 0; j < 4; j++)
#pragma unroll
            for (int b = 0; b < 2; b++)
                st_rlx128(yp + (32 * j + 4 * b) * 8, tag4(pack2(y[0][4 * j + b], y[1][4 * j + b]), pack2(y[0][4 * j + 2 + b], y[1][4 * j + 2 + b]),
                                                          pack2(y[2][4 * j + b], y[3][4 * j + b]), pack2(y[2][4 * j + 2 + b], y[3][4 * j + 2 + b]), tag));
        bar_named(2, 128);
        if (st < 8) st_rlx32(scr->yflag + bi * 8 + st, tag);
        if (warp == 8) STAMP(20);
    }
    __syncthreads();
    if (tid == 0) atomicAdd(scr->done, 1u);
}

typedef CUresult (*EncFn)(CUtensorMap*, CUtensorMapDataType, cuuint32_t, void*, const cuuint64_t*, const cuuint64_t*, const cuuint32_t*,
                          const cuuint32_t*, CUtensorMapInterleave, CUtensorMapSwizzle, CUtensorMapL2promotion, CUtensorMapFloatOOBfill);

extern "C" void kernel_launch(void* const* d_in, const int* in_sizes, int n_in, void* d_out, int out_size) {
    static EncFn enc = nullptr;
    static Scratch* scr = nullptr;
    if (!enc) {
        cudaGetSymbolAddress((void**)&scr, g_scr);
        cudaDriverEntryPointQueryResult qr;
        cudaGetDriverEntryPoint("cuTensorMapEncodeTiled", (void**)&enc, cudaEnableDefault, &qr);
        cudaFuncSetAttribute(fused_kernel, cudaFuncAttributeMaxDynamicSharedMemorySize, SMEM_BYTES);
    }
    CUtensorMap mx, mw, mwo;
    const cuuint32_t es[3] = {1, 1, 1};
    {
        cuuint64_t d[2] = {512, 2048}, s[1] = {1024}; cuuint32_t b[2] = {64, 128};
        enc(&mx, CU_TENSOR_MAP_DATA_TYPE_BFLOAT16, 2, d_in[0], d, s, b, es, CU_TENSOR_MAP_INTERLEAVE_NONE, CU_TENSOR_MAP_SWIZZLE_128B,
            CU_TENSOR_MAP_L2_PROMOTION_L2_128B, CU_TENSOR_MAP_FLOAT_OOB_FILL_NONE);
    }
    {
        cuuint64_t d[3] = {512, 512, 3}, s[2] = {3072, 1024}; cuuint32_t b[3] = {64, 64, 3};
        enc(&mw, CU_TENSOR_MAP_DATA_TYPE_BFLOAT16, 3, d_in[1], d, s, b, es, CU_TENSOR_MAP_INTERLEAVE_NONE, CU_TENSOR_MAP_SWIZZLE_128B,
            CU_TENSOR_MAP_L2_PROMOTION_L2_128B, CU_TENSOR_MAP_FLOAT_OOB_FILL_NONE);
    }
    {
        cuuint64_t d[2] = {512, 512}, s[1] = {1024}; cuuint32_t b[2] = {64, 256};
        enc(&mwo, CU_TENSOR_MAP_DATA_TYPE_BFLOAT16, 2, d_in[3], d, s, b, es, CU_TENSOR_MAP_INTERLEAVE_NONE, CU_TENSOR_MAP_SWIZZLE_128B,
            CU_TENSOR_MAP_L2_PROMOTION_L2_128B, CU_TENSOR_MAP_FLOAT_OOB_FILL_NONE);
    }
    fused_kernel<<<128, 384, SMEM_BYTES, cudaStreamPerThread>>>(
        scr, (const bf16*)d_in[5], (const bf16*)d_in[6], (const bf16*)d_in[7], (const bf16*)d_in[8], (const bf16*)d_in[9],
        (const bf16*)d_in[10], (const bf16*)d_in[2], (const bf16*)d_in[11], (bf16*)d_out, mx, mw, mwo);
}
```

```cpp
#include <cuda_runtime.h>
#include <cuda.h>
#include <cuda_bf16.h>
#include <stdint.h>

typedef __nv_bfloat16 bf16;

struct Scratch {
    uint4 xt[128 * 1024];
    uint4 o[16 * 8 * 32 * 32];
    uint4 y[128 * 1024];
    uint4 kvp[8 * 16 * 544];
    uint4 kvf[8 * 4 * 68];
    unsigned g[1024 * 8];
    unsigned yflag[128 * 8];
    unsigned xcnt[8 * 32];
    unsigned done[32];
};
__device__ Scratch g_scr;
#define STAMP(n)

constexpr int SLOT = 40960;
constexpr int OFF_SP0 = 32768, OFF_SP1 = SLOT + 32768;
constexpr int OFF_P = 2 * SLOT, OFF_V = OFF_P + 32768;
constexpr int OFF_X = OFF_V + 32768;
constexpr int KT_BYTES = 3824, KT_E2 = 2688, KT_E2O = 624;
__host__ __device__ constexpr int kt_off(int c) { return (c < 2 ? OFF_SP0 : OFF_SP1) + (c & 1) * 4096; }
constexpr int OFF_U = 4 * SLOT, U_STRIDE = 41 * 128, U_PAD = 9 * 128;
constexpr int OFF_BUF = OFF_U + 4 * U_STRIDE, BUF_STRIDE = 8448;
constexpr int OFF_K3 = OFF_BUF + 4 * BUF_STRIDE, K3_STRIDE = 1136;
constexpr int OFF_WPHI = OFF_K3 + 4 * K3_STRIDE;
constexpr int OFF_GW = OFF_WPHI + 2048;
constexpr int OFF_KVF = OFF_GW + 1024;
constexpr int OFF_BAR = OFF_KVF + 4352;
constexpr int SMEM_BYTES = OFF_BAR + 128 + 128;
static_assert(SMEM_BYTES <= 232448 && OFF_BUF % 128 == 0, "smem");
constexpr int W5_OFF = 0, W3_OFF = 3184, W9_OFF = 6368;
constexpr int BAR_FULL = 0, BAR_WPHI = 4, BAR_WO = 5, BAR_XT = 6, BAR_DONE = 7, BAR_WO2 = 8, OFF_CNT = 96;
#define KG_ROUNDS 4
constexpr int SPIN_LIMIT = 1 << 17;

__device__ __forceinline__ uint32_t s2u(const void* p) { return (uint32_t)__cvta_generic_to_shared(p); }
__device__ __forceinline__ void mbar_init(uint32_t b, int c) { asm volatile("mbarrier.init.shared::cta.b64 [%0],%1;" ::"r"(b), "r"(c) : "memory"); }
__device__ __forceinline__ void mbar_expect(uint32_t b, int bytes) { asm volatile("mbarrier.arrive.expect_tx.shared::cta.b64 _,[%0],%1;" ::"r"(b), "r"(bytes) : "memory"); }
__device__ __forceinline__ void mbar_arrive(uint32_t b) { asm volatile("mbarrier.arrive.shared::cta.b64 _,[%0];" ::"r"(b) : "memory"); }
__device__ __forceinline__ void mbar_wait(uint32_t b, int ph) {
    asm volatile("{\n.reg .pred p;\n.reg .u32 n;\nmov.u32 n,0;\nLW_%=:\nmbarrier.try_wait.parity.shared::cta.b64 p,[%0],%1;\n@p bra LD_%=;\n"
                 "add.u32 n,n,1;\nsetp.lt.u32 p,n,131072;\n@p bra LW_%=;\nLD_%=:\n}" ::"r"(b), "r"(ph) : "memory");
}
__device__ __forceinline__ void tma2d(uint32_t dst, const CUtensorMap* m, int c0, int c1, uint32_t bar) {
    asm volatile("cp.async.bulk.tensor.2d.shared::cluster.global.mbarrier::complete_tx::bytes [%0],[%1,{%3,%4}],[%2];" ::"r"(dst), "l"(m), "r"(bar), "r"(c0), "r"(c1) : "memory");
}
__device__ __forceinline__ void tma3d(uint32_t dst, const CUtensorMap* m, int c0, int c1, int c2, uint32_t bar) {
    asm volatile("cp.async.bulk.tensor.3d.shared::cluster.global.mbarrier::complete_tx::bytes [%0],[%1,{%3,%4,%5}],[%2];" ::"r"(dst), "l"(m), "r"(bar), "r"(c0), "r"(c1), "r"(c2) : "memory");
}
__device__ __forceinline__ void bulk_g2s(uint32_t dst, const void* src, int bytes, uint32_t bar) {
    asm volatile("cp.async.bulk.shared::cluster.global.mbarrier::complete_tx::bytes [%0],[%1],%2,[%3];" ::"r"(dst), "l"(src), "r"(bytes), "r"(bar) : "memory");
}
__device__ __forceinline__ uint64_t mkdesc(uint32_t addr, uint32_t lbo, uint32_t sbo) {
    return (uint64_t)((addr & 0x3FFFF) >> 4) | ((uint64_t)(lbo >> 4) << 16) | ((uint64_t)(sbo >> 4) << 32) | ((uint64_t)1 << 62);
}
__device__ __forceinline__ void wg_fence() { asm volatile("wgmma.fence.sync.aligned;" ::: "memory"); }
__device__ __forceinline__ void wg_commit() { asm volatile("wgmma.commit_group.sync.aligned;" ::: "memory"); }
template <int N> __device__ __forceinline__ void wg_wait() { asm volatile("wgmma.wait_group.sync.aligned %0;" ::"n"(N) : "memory"); }
template <int N> __device__ __forceinline__ void fence_regs(float* d) {
#pragma unroll
    for (int i = 0; i < N; i++) asm volatile("" : "+f"(d[i])::"memory");
}
#define R8(d, o) "+f"(d[o]), "+f"(d[o + 1]), "+f"(d[o + 2]), "+f"(d[o + 3]), "+f"(d[o + 4]), "+f"(d[o + 5]), "+f"(d[o + 6]), "+f"(d[o + 7])
__device__ __forceinline__ void wgmma192(float* d, uint64_t da, uint64_t db) {
    asm volatile("wgmma.mma_async.sync.aligned.m64n192k16.f32.bf16.bf16 {"
                 "%0,%1,%2,%3,%4,%5,%6,%7,%8,%9,%10,%11,%12,%13,%14,%15,%16,%17,%18,%19,%20,%21,%22,%23,%24,%25,%26,%27,%28,%29,%30,%31,"
                 "%32,%33,%34,%35,%36,%37,%38,%39,%40,%41,%42,%43,%44,%45,%46,%47,%48,%49,%50,%51,%52,%53,%54,%55,%56,%57,%58,%59,%60,%61,%62,%63,"
                 "%64,%65,%66,%67,%68,%69,%70,%71,%72,%73,%74,%75,%76,%77,%78,%79,%80,%81,%82,%83,%84,%85,%86,%87,%88,%89,%90,%91,%92,%93,%94,%95},"
                 "%96,%97,1,1,1,0,1;"
                 : R8(d, 0), R8(d, 8), R8(d, 16), R8(d, 24), R8(d, 32), R8(d, 40), R8(d, 48), R8(d, 56), R8(d, 64), R8(d, 72), R8(d, 80), R8(d, 88)
                 : "l"(da), "l"(db));
}
__device__ __forceinline__ void wgmma64_tt(float* d, uint64_t da, uint64_t db, int sc) {
    asm volatile("{.reg .pred p; setp.ne.b32 p,%34,0; wgmma.mma_async.sync.aligned.m64n64k16.f32.bf16.bf16 {"
                 "%0,%1,%2,%3,%4,%5,%6,%7,%8,%9,%10,%11,%12,%13,%14,%15,%16,%17,%18,%19,%20,%21,%22,%23,%24,%25,%26,%27,%28,%29,%30,%31},"
                 "%32,%33,p,1,1,1,1;}"
                 : R8(d, 0), R8(d, 8), R8(d, 16), R8(d, 24)
                 : "l"(da), "l"(db), "r"(sc));
}
__device__ __forceinline__ void wgmma128_rs(float* d, const uint4& a, uint64_t db, int sc) {
    asm volatile("{.reg .pred p; setp.ne.b32 p,%69,0; wgmma.mma_async.sync.aligned.m64n128k16.f32.bf16.bf16 {"
                 "%0,%1,%2,%3,%4,%5,%6,%7,%8,%9,%10,%11,%12,%13,%14,%15,%16,%17,%18,%19,%20,%21,%22,%23,%24,%25,%26,%27,%28,%29,%30,%31,"
                 "%32,%33,%34,%35,%36,%37,%38,%39,%40,%41,%42,%43,%44,%45,%46,%47,%48,%49,%50,%51,%52,%53,%54,%55,%56,%57,%58,%59,%60,%61,%62,%63},"
                 "{%64,%65,%66,%67},%68,p,1,1,1;}"
                 : R8(d, 0), R8(d, 8), R8(d, 16), R8(d, 24), R8(d, 32), R8(d, 40), R8(d, 48), R8(d, 56)
                 : "r"(a.x), "r"(a.y), "r"(a.z), "r"(a.w), "l"(db), "r"(sc));
}
__device__ __forceinline__ void wgmma32_rs(float* d, const uint32_t* a, uint64_t db) {
    asm volatile("wgmma.mma_async.sync.aligned.m64n32k16.f32.bf16.bf16 {%0,%1,%2,%3,%4,%5,%6,%7,%8,%9,%10,%11,%12,%13,%14,%15},{%16,%17,%18,%19},%20,1,1,1,0;"
                 : R8(d, 0), R8(d, 8) : "r"(a[0]), "r"(a[1]), "r"(a[2]), "r"(a[3]), "l"(db));
}
__device__ __forceinline__ void wgmma48_rs(float* d, uint32_t a0, uint32_t a1, uint32_t a2, uint32_t a3, uint64_t db) {
    asm volatile("wgmma.mma_async.sync.aligned.m64n48k16.f32.bf16.bf16 {%0,%1,%2,%3,%4,%5,%6,%7,%8,%9,%10,%11,%12,%13,%14,%15,%16,%17,%18,%19,%20,%21,%22,%23},{%24,%25,%26,%27},%28,1,1,1,0;"
                 : R8(d, 0), R8(d, 8), R8(d, 16) : "r"(a0), "r"(a1), "r"(a2), "r"(a3), "l"(db));
}
__device__ __forceinline__ void mma16816(float* c, uint32_t a0, uint32_t a1, uint32_t a2, uint32_t a3, uint32_t b0, uint32_t b1) {
    asm("mma.sync.aligned.m16n8k16.row.col.f32.bf16.bf16.f32 {%0,%1,%2,%3},{%4,%5,%6,%7},{%8,%9},{%0,%1,%2,%3};"
        : "+f"(c[0]), "+f"(c[1]), "+f"(c[2]), "+f"(c[3]) : "r"(a0), "r"(a1), "r"(a2), "r"(a3), "r"(b0), "r"(b1));
}
__device__ __forceinline__ void ldsm4(uint32_t* r, uint32_t a) {
    asm volatile("ldmatrix.sync.aligned.m8n8.x4.shared.b16 {%0,%1,%2,%3},[%4];" : "=r"(r[0]), "=r"(r[1]), "=r"(r[2]), "=r"(r[3]) : "r"(a) : "memory");
}
__device__ __forceinline__ void ldsm4t(uint32_t* r, uint32_t a) {
    asm volatile("ldmatrix.sync.aligned.m8n8.x4.trans.shared.b16 {%0,%1,%2,%3},[%4];" : "=r"(r[0]), "=r"(r[1]), "=r"(r[2]), "=r"(r[3]) : "r"(a) : "memory");
}
__device__ __forceinline__ void stsm4(uint32_t a, uint32_t r0, uint32_t r1, uint32_t r2, uint32_t r3) {
    asm volatile("stmatrix.sync.aligned.m8n8.x4.shared.b16 [%0],{%1,%2,%3,%4};" ::"r"(a), "r"(r0), "r"(r1), "r"(r2), "r"(r3) : "memory");
}
__device__ __forceinline__ uint32_t lds32(uint32_t a) { uint32_t v; asm volatile("ld.shared.b32 %0,[%1];" : "=r"(v) : "r"(a) : "memory"); return v; }
__device__ __forceinline__ uint4 lds128(uint32_t a) { uint4 v; asm volatile("ld.shared.v4.b32 {%0,%1,%2,%3},[%4];" : "=r"(v.x), "=r"(v.y), "=r"(v.z), "=r"(v.w) : "r"(a) : "memory"); return v; }
__device__ __forceinline__ void sts16(uint32_t a, uint32_t v) { asm volatile("st.shared.b16 [%0],%1;" ::"r"(a), "h"((unsigned short)v) : "memory"); }
__device__ __forceinline__ void sts32(uint32_t a, uint32_t v) { asm volatile("st.shared.b32 [%0],%1;" ::"r"(a), "r"(v) : "memory"); }
__device__ __forceinline__ void sts64(uint32_t a, uint32_t x, uint32_t y) { asm volatile("st.shared.v2.b32 [%0],{%1,%2};" ::"r"(a), "r"(x), "r"(y) : "memory"); }
__device__ __forceinline__ void sts128(uint32_t a, uint32_t x, uint32_t y, uint32_t z, uint32_t w) { asm volatile("st.shared.v4.b32 [%0],{%1,%2,%3,%4};" ::"r"(a), "r"(x), "r"(y), "r"(z), "r"(w) : "memory"); }
__device__ __forceinline__ uint32_t pack2(float lo, float hi) { uint32_t d; asm("cvt.rn.bf16x2.f32 %0,%1,%2;" : "=r"(d) : "f"(hi), "f"(lo)); return d; }
__device__ __forceinline__ float bf_lo(uint32_t v) { return __uint_as_float(v << 16); }
__device__ __forceinline__ float bf_hi(uint32_t v) { return __uint_as_float(v & 0xffff0000u); }
__device__ __forceinline__ float bf_round(float v) { return bf_lo(pack2(v, 0.f)); }
__device__ __forceinline__ uint32_t hmax2(uint32_t a, uint32_t b) { uint32_t d; asm("max.bf16x2 %0,%1,%2;" : "=r"(d) : "r"(a), "r"(b)); return d; }
__device__ __forceinline__ uint32_t hmin2(uint32_t a, uint32_t b) { uint32_t d; asm("min.bf16x2 %0,%1,%2;" : "=r"(d) : "r"(a), "r"(b)); return d; }
__device__ __forceinline__ uint32_t hmul2(uint32_t a, uint32_t b) { uint32_t d; asm("mul.rn.bf16x2 %0,%1,%2;" : "=r"(d) : "r"(a), "r"(b)); return d; }
__device__ __forceinline__ float ex2(float x) { float y; asm("ex2.approx.ftz.f32 %0,%1;" : "=f"(y) : "f"(x)); return y; }
__device__ __forceinline__ float rcp(float x) { float y; asm("rcp.approx.ftz.f32 %0,%1;" : "=f"(y) : "f"(x)); return y; }
__device__ __forceinline__ uint32_t ld_nc(const uint32_t* p) { uint32_t v; asm volatile("ld.global.nc.b32 %0,[%1];" : "=r"(v) : "l"(p)); return v; }
__device__ __forceinline__ uint2 ld_nc64(const uint2* p) { uint2 v; asm volatile("ld.global.nc.v2.b32 {%0,%1},[%2];" : "=r"(v.x), "=r"(v.y) : "l"(p)); return v; }
__device__ __forceinline__ unsigned ld_acq(const unsigned* p) { unsigned v; asm volatile("ld.acquire.gpu.global.u32 %0,[%1];" : "=r"(v) : "l"(p) : "memory"); return v; }
__device__ __forceinline__ unsigned ld_rlx(const unsigned* p) { unsigned v; asm volatile("ld.relaxed.gpu.global.u32 %0,[%1];" : "=r"(v) : "l"(p) : "memory"); return v; }
__device__ __forceinline__ uint2 ld_rlx64(const void* p) { uint2 v; asm volatile("{.reg .b64 t; ld.relaxed.gpu.global.b64 t,[%2]; mov.b64 {%0,%1},t;}" : "=r"(v.x), "=r"(v.y) : "l"(p) : "memory"); return v; }
__device__ __forceinline__ uint4 ld_rlx128(const void* p) {
    uint4 v;
    asm volatile("{.reg .b64 t,u; ld.relaxed.gpu.global.v2.b64 {t,u},[%4]; mov.b64 {%0,%1},t; mov.b64 {%2,%3},u;}" : "=r"(v.x), "=r"(v.y), "=r"(v.z), "=r"(v.w) : "l"(p) : "memory");
    return v;
}
__device__ __forceinline__ void st_rlx32(void* p, uint32_t x) { asm volatile("st.relaxed.gpu.global.u32 [%0],%1;" ::"l"(p), "r"(x) : "memory"); }
__device__ __forceinline__ void st_rlx64(void* p, uint32_t x, uint32_t y) { asm volatile("{.reg .b64 t; mov.b64 t,{%1,%2}; st.relaxed.gpu.global.b64 [%0],t;}" ::"l"(p), "r"(x), "r"(y) : "memory"); }
__device__ __forceinline__ void st_rlx128(void* p, uint4 v) {
    asm volatile("{.reg .b64 t,u; mov.b64 t,{%1,%2}; mov.b64 u,{%3,%4}; st.relaxed.gpu.global.v2.b64 [%0],{t,u};}" ::"l"(p), "r"(v.x), "r"(v.y), "r"(v.z), "r"(v.w) : "memory");
}
__device__ __forceinline__ uint32_t tagw(uint32_t w, uint32_t tag) { return (w & ~1u) | tag; }
__device__ __forceinline__ uint4 tag4(uint32_t x, uint32_t y, uint32_t z, uint32_t w, uint32_t tag) { return make_uint4(tagw(x, tag), y, tagw(z, tag), w); }
__device__ __forceinline__ uint32_t bad4(const uint4& v, uint32_t tag) { return (v.x ^ tag) | (v.z ^ tag); }
__device__ __forceinline__ void bar_named(int id, int n) { asm volatile("bar.sync %0,%1;" ::"r"(id), "r"(n) : "memory"); }

struct cf { float re, im; };
__device__ __forceinline__ cf cmul(cf a, cf b) { cf r; r.re = a.re * b.re - a.im * b.im; r.im = a.re * b.im + a.im * b.re; return r; }
__device__ __forceinline__ cf cexp_p(float arl, float ait, float p) {
    float mag = ex2(arl * p);
    float t = ait * p;
    t = (t - rintf(t)) * 6.283185307179586f;
    cf r; r.re = mag * __cosf(t); r.im = mag * __sinf(t);
    return r;
}

__device__ __forceinline__ void hedgehog2(const uint32_t* a, uint32_t wphi_addr, uint32_t (*out)[8]) {
    float p[2][2][4], mx[2][2];
#pragma unroll
    for (int h = 0; h < 2; h++) {
        uint32_t b[4];
        ldsm4t(b, wphi_addr + h * 512);
        float c0[4] = {0.f, 0.f, 0.f, 0.f}, c1[4] = {0.f, 0.f, 0.f, 0.f};
        mma16816(c0, a[4 * h], a[4 * h + 1], a[4 * h + 2], a[4 * h + 3], b[0], b[1]);
        mma16816(c1, a[4 * h], a[4 * h + 1], a[4 * h + 2], a[4 * h + 3], b[2], b[3]);
#pragma unroll
        for (int k = 0; k < 2; k++) {
            p[h][k][0] = c0[2 * k]; p[h][k][1] = c0[2 * k + 1]; p[h][k][2] = c1[2 * k]; p[h][k][3] = c1[2 * k + 1];
            mx[h][k] = fmaxf(fmaxf(p[h][k][0], p[h][k][1]), fmaxf(p[h][k][2], p[h][k][3]));
        }
    }
#pragma unroll
    for (int o = 1; o <= 2; o <<= 1)
#pragma unroll
        for (int h = 0; h < 2; h++)
#pragma unroll
            for (int k = 0; k < 2; k++) mx[h][k] = fmaxf(mx[h][k], __shfl_xor_sync(~0u, mx[h][k], o));
    const float L = 1.4426950408889634f;
    float pmin = 1.f;
#pragma unroll
    for (int h = 0; h < 2; h++)
#pragma unroll
        for (int k = 0; k < 2; k++) {
            const float m = -mx[h][k] * L;
            const float e0 = ex2(fmaf(p[h][k][0], L, m)), e1 = ex2(fmaf(p[h][k][1], L, m)), e2 = ex2(fmaf(p[h][k][2], L, m)), e3 = ex2(fmaf(p[h][k][3], L, m));
            const float p01 = e0 * e1, p23 = e2 * e3, pp = p01 * p23, r = rcp(pp), r01 = r * p23, r23 = r * p01;
            pmin = fminf(pmin, pp);
            out[h][k] = pack2(e0, e1); out[h][k + 2] = pack2(e2, e3);
            out[h][4 + k] = pack2(r01 * e1, r01 * e0); out[h][4 + k + 2] = pack2(r23 * e3, r23 * e2);
        }
    if (__builtin_expect(__any_sync(~0u, !(pmin > 1e-18f)), 0)) {
#pragma unroll
        for (int h = 0; h < 2; h++)
#pragma unroll
            for (int k = 0; k < 2; k++) {
                float m = fminf(fminf(p[h][k][0], p[h][k][1]), fminf(p[h][k][2], p[h][k][3]));
                m = fminf(m, __shfl_xor_sync(~0u, m, 1));
                m = fminf(m, __shfl_xor_sync(~0u, m, 2)) * L;
                out[h][4 + k] = pack2(ex2(fmaf(p[h][k][0], -L, m)), ex2(fmaf(p[h][k][1], -L, m)));
                out[h][4 + k + 2] = pack2(ex2(fmaf(p[h][k][2], -L, m)), ex2(fmaf(p[h][k][3], -L, m)));
            }
    }
}

__global__ void __launch_bounds__(384, 1)
fused_kernel(Scratch* __restrict__ scr, const bf16* __restrict__ logA, const bf16* __restrict__ Aim, const bf16* __restrict__ Cre,
             const bf16* __restrict__ Cim, const bf16* __restrict__ logdt, const bf16* __restrict__ Dskip, const bf16* __restrict__ wphi,
             const bf16* __restrict__ gatew, bf16* __restrict__ out,
             const __grid_constant__ CUtensorMap mx, const __grid_constant__ CUtensorMap mw, const __grid_constant__ CUtensorMap mwo) {
    extern __shared__ __align__(1024) uint8_t smem[];
    const uint32_t sb = s2u(smem);
    const int tid = threadIdx.x, warp = __shfl_sync(~0u, tid >> 5, 0), lane = tid & 31;
    const int g = lane >> 2, q = lane & 3, w4 = warp & 3;
    const int bi = blockIdx.x, bi_i = bi & 15, bi_j = bi >> 4;
    const uint32_t bar = sb + OFF_BAR;
    const int rot = (bi_j & 1) * 4;
    auto load_stage = [&](int kb) {
        const uint32_t b = bar + 8 * (BAR_FULL + (kb & 3)), d = sb + (kb & 3) * SLOT;
        const int kc = ((kb + rot) & 7) * 64;
        mbar_expect(b, SLOT);
        tma2d(d, &mx, kc, bi_i * 128, b);
        tma3d(d + 16384, &mw, bi_j * 64, kc, 0, b);
    };

    const int ch = bi * 4 + w4;
    uint2 pla, pai, pcr, pci; uint32_t pdt = 0, pds;
    if (warp >= 8) {
        pla = ld_nc64((const uint2*)logA + ch * 32 + lane); pai = ld_nc64((const uint2*)Aim + ch * 32 + lane);
        pcr = ld_nc64((const uint2*)Cre + ch * 32 + lane); pci = ld_nc64((const uint2*)Cim + ch * 32 + lane);
        pdt = ld_nc((const uint32_t*)logdt + (ch >> 1)); pds = ld_nc((const uint32_t*)Dskip + (ch >> 1));
    }
    unsigned done0 = ld_rlx(scr->done);
    if (tid == 0) {
        for (int s = 0; s < 4; s++) mbar_init(bar + 8 * (BAR_FULL + s), 1);
        asm volatile("fence.mbarrier_init.release.cluster;" ::: "memory");
#pragma unroll 1
        for (int s = 0; s < 4; s++) load_stage(s);
        STAMP(11);
    } else if (tid == 32) {
        if (sb & 1023) __trap();
        for (int s = 0; s < 5; s++) sts32(bar + OFF_CNT + 4 * s, 0);
        mbar_init(bar + 8 * BAR_WPHI, 1); mbar_init(bar + 8 * BAR_WO, 2); mbar_init(bar + 8 * BAR_XT, 8); mbar_init(bar + 8 * BAR_DONE, 8);
        mbar_init(bar + 8 * BAR_WO2, 1);
        asm volatile("fence.mbarrier_init.release.cluster;" ::: "memory");
        mbar_expect(bar + 8 * BAR_WPHI, 3072);
        bulk_g2s(sb + OFF_GW, gatew, 1024, bar + 8 * BAR_WPHI);
        bulk_g2s(sb + OFF_WPHI, wphi + bi_j * 1024, 2048, bar + 8 * BAR_WPHI);
    } else if (tid == 64) {
        asm volatile("prefetch.tensormap [%0];" ::"l"(&mw) : "memory");
    }
    const uint32_t buf = sb + OFF_BUF + w4 * BUF_STRIDE, k3 = sb + OFF_K3 + w4 * K3_STRIDE;
    if (warp >= 8) {
#pragma unroll
        for (int v = 0; v < 3; v++) if (v * 32 + lane < K3_STRIDE / 16) sts128(k3 + (v * 32 + lane) * 16, 0, 0, 0, 0);
    }
    __syncthreads();
    asm volatile("" : "+r"(pdt), "+r"(done0)::"memory");
    const unsigned epoch1 = (done0 >> 7) + 1u;
    const uint32_t tag = epoch1 & 1u;

    if (warp < 8) {
        const int wg = warp >> 2;
        if (warp == 0) STAMP(21);
        float acc[96];
        const int grow = bi_j * 16 + warp * 2 + (lane >> 4);
        const uint32_t gx_a = grow * 128 + ((((lane & 15) >> 1) ^ (grow & 7)) << 4) + (lane & 1) * 8;
        const int srow = warp * 16 + (lane & 15);
        const uint32_t srow_a = srow * 128;
        const int sx = srow & 7, shi = lane >> 4;
        auto last_of_8 = [&](int c) {
            unsigned old;
            asm volatile("atom.acq_rel.cta.shared.add.u32 %0,[%1],1;" : "=r"(old) : "r"(bar + OFF_CNT + 4 * c) : "memory");
            return (old & 7) == 7;
        };
        const int qq = (bi_i & 2) + ((lane >> 1) & 1);
        const int kvf_n = warp < 4 ? 8 : ((warp == 4 && (bi_i & 1) == 0) ? 4 : 0);
        uint2* kvf_dst = (uint2*)(scr->kvf + (bi_j * 4 + (bi_i >> 2)) * 68) +
                         (warp == 4 ? (64 + qq) * 2 + (lane & 1) : ((bi_i & 3) * 8 + w4 * 2 + (lane & 1)) * 4 + (lane >> 1));
        float gsum = 0.f;
#pragma unroll
        for (int r = 0; r < 96; r++) acc[r] = 0.f;
        fence_regs<96>(acc);
        const uint64_t da0 = mkdesc(sb + wg * 8192, 16, 1024), db0 = mkdesc(sb + 16384, 8192, 1024);
        {
            const uint32_t old = tag ^ 1u;
            const uint4 z4 = make_uint4(old, 0, old, 0);
            uint4* kvp = scr->kvp + bi * 544 + wg * 272;
            if (w4 < 2) {
#pragma unroll
                for (int f = 0; f < 4; f++) st_rlx128(kvp + w4 * 136 + lane + f * 32, z4);
            } else if (w4 == 2 && lane < 4) {
#pragma unroll
                for (int f = 0; f < 4; f++) st_rlx128(kvp + (f >> 1) * 136 + 128 + (f & 1) * 4 + lane, z4);
            }
            if (lane < kvf_n) st_rlx64(kvf_dst, old, 0);
            if (lane >= 30) st_rlx128(scr->o + ((bi_i * 8 + warp) * 32 + bi_j * 4 + 3) * 32 + lane, z4);
            if (lane < 8) st_rlx32(scr->g + (bi_i * 64 + bi_j * 8 + warp) * 8 + lane, old);
        }
        mbar_wait(bar + 8 * BAR_WPHI, 0);
#pragma unroll 1
        for (int kb = 0; kb < 8; kb++) {
            const int s = kb & 3;
            const uint64_t da = da0 + s * (SLOT >> 4), db = db0 + s * (SLOT >> 4);
            mbar_wait(bar + 8 * (BAR_FULL + s), kb >> 2);
            if (kb == 0 && warp == 0) STAMP(0);
            wg_fence();
#pragma unroll
            for (int k = 0; k < 4; k++) wgmma192(acc, da + 2 * k, db + 128 * k);
            wg_commit();
            wg_wait<1>();
            __syncwarp();
            if (lane == 0 && kb > 0 && kb < 7) {
                const int ps = (kb - 1) & 3;
                if (last_of_8(ps)) {
                    if (kb < 5) load_stage(kb + 3);
                    else {
                        mbar_expect(bar + 8 * BAR_WO, 32768);
                        tma2d(sb + ps * SLOT, &mwo, (bi_j & 3) * 128 + ps * 64, 0, bar + 8 * BAR_WO);
                    }
                }
            }
            __syncwarp();
            const uint32_t st = sb + s * SLOT;
            if (kb == (bi_j >> 1)) {
                uint32_t* xt = (uint32_t*)scr->xt + ((kb + rot) * 16 + (g >> 2)) * 4096 + (bi_i * 16 + warp * 2) * 16 + (g & 3) * 4 + q;
#pragma unroll
                for (int cb = 0; cb < 8; cb += 2) {
                    uint32_t r[4];
                    ldsm4t(r, st + srow_a + (((cb + shi) ^ sx) << 4));
                    xt[cb * 8192] = r[0]; xt[cb * 8192 + 16] = r[1]; xt[cb * 8192 + 8192] = r[2]; xt[cb * 8192 + 8192 + 16] = r[3];
                }
                __syncwarp();
                if (lane == 0) mbar_arrive(bar + 8 * BAR_XT);
            }
            {
                uint32_t x0, x1, w0, w1;
                asm volatile("ld.shared.v2.b32 {%0,%1},[%2];" : "=r"(x0), "=r"(x1) : "r"(st + gx_a) : "memory");
                asm volatile("ld.shared.v2.b32 {%0,%1},[%2];" : "=r"(w0), "=r"(w1) : "r"(sb + OFF_GW + ((kb + rot) & 7) * 128 + (lane & 15) * 8) : "memory");
                const uint32_t p0 = hmul2(x0, w0), p1 = hmul2(x1, w1);
                gsum += (bf_lo(p0) + bf_hi(p0)) + (bf_lo(p1) + bf_hi(p1));
            }
        }
        wg_wait<0>();
        fence_regs<96>(acc);
        __syncwarp();
        if (lane == 0) mbar_arrive(bar + 8 * BAR_DONE);
        if (warp == 0) STAMP(1);
        uint32_t in[32], va[16];
#pragma unroll
        for (int r = 0; r < 16; r++) {
            in[r] = pack2(acc[32 + 2 * r], acc[32 + 2 * r + 1]);
            in[16 + r] = pack2(acc[2 * r], acc[2 * r + 1]);
            va[r] = pack2(acc[64 + 2 * r], acc[64 + 2 * r + 1]);
        }
        const uint32_t wphi_a = sb + OFF_WPHI + (lane & 15) * 32 + (lane >> 4) * 16;
        uint32_t pq[4][8];
#pragma unroll 1
        for (int it = 0; it < 4; it++) {
            hedgehog2(in, wphi_a + (it & 1) * 1024, pq + 2);
#pragma unroll
            for (int r = 0; r < 24; r++) in[r] = in[r + 8];
            if (it < 2) {
#pragma unroll
                for (int hs = 0; hs < 4; hs++) {
                    float c[4] = {0.f, 0.f, 0.f, 0.f};
                    uint32_t* o = pq[2 + (hs >> 1)] + 4 * (hs & 1);
                    mma16816(c, o[0], o[1], o[2], o[3], 0x3f803f80u, 0x3f803f80u);
                    const float r0 = rcp(c[0]), r1 = rcp(c[2]);
                    const uint32_t s0 = pack2(r0, r0), s1 = pack2(r1, r1);
                    o[0] = hmul2(o[0], s0); o[1] = hmul2(o[1], s1); o[2] = hmul2(o[2], s0); o[3] = hmul2(o[3], s1);
                }
                if (it == 0) mbar_wait(bar + 8 * BAR_DONE, 0);
                const uint32_t pt = sb + OFF_P + it * 16384 + srow_a, vt = sb + OFF_V + it * 16384 + srow_a;
#pragma unroll
                for (int hl = 0; hl < 2; hl++) {
                    stsm4(pt + (((4 * hl + shi) ^ sx) << 4), pq[2 + hl][0], pq[2 + hl][1], pq[2 + hl][2], pq[2 + hl][3]);
                    stsm4(pt + (((4 * hl + 2 + shi) ^ sx) << 4), pq[2 + hl][4], pq[2 + hl][5], pq[2 + hl][6], pq[2 + hl][7]);
                    stsm4(vt + (((2 * hl + shi) ^ sx) << 4), va[4 * hl], va[4 * hl + 1], va[4 * hl + 2], va[4 * hl + 3]);
                }
                if (lane < 16) sts128(vt + ((4 ^ sx) << 4), 0x3f803f80u, 0x3f803f80u, 0x3f803f80u, 0x3f803f80u);
#pragma unroll
                for (int r = 0; r < 8; r++) va[r] = va[r + 8];
            }
            if (it == 1) {
                asm volatile("fence.proxy.async.shared::cta;" ::: "memory");
                bar_named(1, 256);
                if (warp == 0) STAMP(2);
                float d[32];
                const uint64_t dv = mkdesc(sb + OFF_V + wg * 16384, 16, 1024), dp = mkdesc(sb + OFF_P + wg * 16384, 16, 1024);
                wg_fence();
#pragma unroll
                for (int k = 0; k < 8; k++) wgmma64_tt(d, dv + 128 * k, dp + 128 * k, k != 0);
                wg_commit();
                wg_wait<0>();
                fence_regs<32>(d);
                uint4* kvp = scr->kvp + bi * 544 + wg * 272;
                if (w4 < 2) {
                    uint32_t e[16];
#pragma unroll
                    for (int r = 0; r < 16; r++) e[r] = __float_as_uint(w4 ? d[16 + r] : d[r]);
                    uint4* p = kvp + w4 * 136 + lane;
#pragma unroll
                    for (int ks = 0; ks < 2; ks++)
#pragma unroll
                        for (int nt = 0; nt < 2; nt++)
                            st_rlx128(p + (ks * 2 + nt) * 32, tag4(e[8 * ks + 2 * nt], e[8 * ks + 2 * nt + 1], e[8 * ks + 4 + 2 * nt], e[8 * ks + 4 + 2 * nt + 1], tag));
                } else if (w4 == 2 && lane < 4) {
#pragma unroll
                    for (int hl = 0; hl < 2; hl++)
#pragma unroll
                        for (int ks = 0; ks < 2; ks++)
                            st_rlx128(kvp + hl * 136 + 128 + ks * 4 + lane, tag4(__float_as_uint(d[16 * hl + 8 * ks]), __float_as_uint(d[16 * hl + 8 * ks + 1]),
                                                                                __float_as_uint(d[16 * hl + 8 * ks + 4]), __float_as_uint(d[16 * hl + 8 * ks + 5]), tag));
                }
                if (warp == 0) STAMP(3);
            }
            if (it == 2) {
#pragma unroll
                for (int r = 0; r < 8; r++) { pq[0][r] = pq[2][r]; pq[1][r] = pq[3][r]; }
                if (warp == 0) STAMP(12);
                if (kvf_n) {
                    const bool zw = warp == 4;
                    const uint4* src = scr->kvp + bi_j * (16 * 544) + (bi_i >> 2) * 136 +
                                       (zw ? (lane >> 2) * (2 * 544) + 128 + (lane & 1) * 4 + qq
                                           : (lane >> 3) * (4 * 544) + ((lane >> 1) & 3) * 32 + (bi_i & 3) * 8 + warp * 2 + (lane & 1));
                    const int s23 = zw ? 0 : 2 * 544;
                    uint4 v[4];
                    int n = 0;
#pragma unroll 1
                    while (true) {
                        v[0] = ld_rlx128(src); v[1] = ld_rlx128(src + 544); v[2] = ld_rlx128(src + s23); v[3] = ld_rlx128(src + s23 + 544);
                        if (!__any_sync(~0u, (bad4(v[0], tag) | bad4(v[1], tag) | bad4(v[2], tag) | bad4(v[3], tag)) & 1)) break;
                        if (++n > SPIN_LIMIT) break;
                    }
                    float f[4];
                    f[0] = __uint_as_float(v[2].x) + __uint_as_float(v[3].x); f[1] = __uint_as_float(v[2].y) + __uint_as_float(v[3].y);
                    f[2] = __uint_as_float(v[2].z) + __uint_as_float(v[3].z); f[3] = __uint_as_float(v[2].w) + __uint_as_float(v[3].w);
                    float e0 = __uint_as_float(v[0].x) + __uint_as_float(v[1].x), e1 = __uint_as_float(v[0].y) + __uint_as_float(v[1].y);
                    float e2 = __uint_as_float(v[0].z) + __uint_as_float(v[1].z), e3 = __uint_as_float(v[0].w) + __uint_as_float(v[1].w);
                    if (zw) {
                        e0 = __shfl_xor_sync(~0u, f[0], 4); e1 = __shfl_xor_sync(~0u, f[1], 4);
                        e2 = __shfl_xor_sync(~0u, f[2], 4); e3 = __shfl_xor_sync(~0u, f[3], 4);
                    }
                    f[0] += e0; f[1] += e1; f[2] += e2; f[3] += e3;
#pragma unroll
                    for (int o = 8; o <= 16; o <<= 1)
#pragma unroll
                        for (int r = 0; r < 4; r++) f[r] += __shfl_xor_sync(~0u, f[r], o);
                    if (lane < kvf_n) st_rlx64(kvf_dst, tagw(pack2(f[0], f[1]), tag), pack2(f[2], f[3]));
                }
                __syncwarp();
                if (lane == 0 && last_of_8(4)) {
                    mbar_expect(bar + 8 * BAR_WO2, 65536);
                    tma2d(sb + 2 * SLOT, &mwo, (bi_j & 3) * 128, 256, bar + 8 * BAR_WO2);
                    tma2d(sb + OFF_V, &mwo, (bi_j & 3) * 128 + 64, 256, bar + 8 * BAR_WO2);
                }
                __syncwarp();
                if (warp == 0) STAMP(13);
#pragma unroll
                for (int o = 1; o < 16; o <<= 1) gsum += __shfl_xor_sync(~0u, gsum, o);
                const float gate = bf_round(rcp(1.0f + ex2(-1.4426950408889634f * bf_round(gsum))));
                const uint32_t gv = __shfl_sync(~0u, __float_as_uint(gate) | tag, (lane & 4) * 4);
                if (lane < 8) st_rlx32(scr->g + (bi_i * 64 + bi_j * 8 + warp) * 8 + lane, gv);
            }
        }
        if (warp == 0) STAMP(4);
        {
            {
                const uint4* kp = scr->kvf + bi_j * 272 + tid;
                uint4 v0, v1;
                int n = 0;
#pragma unroll 1
                while (true) {
                    v0 = ld_rlx128(kp); v1 = ld_rlx128(kp + (tid < 16 ? 256 : 0));
                    if (!__any_sync(~0u, (bad4(v0, tag) | bad4(v1, tag)) & 1)) break;
                    if (++n > SPIN_LIMIT) break;
                }
                sts128(sb + OFF_KVF + tid * 16, v0.x, v0.y, v0.z, v0.w);
                if (tid < 16) sts128(sb + OFF_KVF + 4096 + tid * 16, v1.x, v1.y, v1.z, v1.w);
                bar_named(1, 256);
            }
            uint4 kf[4][3];
#pragma unroll
            for (int hh = 0; hh < 4; hh++) {
                const uint32_t a = sb + OFF_KVF + hh * 1088;
                kf[hh][0] = lds128(a + lane * 32); kf[hh][1] = lds128(a + lane * 32 + 16); kf[hh][2] = lds128(a + 1024 + q * 16);
            }
            if (warp == 0) STAMP(5);
            uint4 own[4];
#pragma unroll
            for (int hh = 0; hh < 4; hh++) {
                float c[6][4];
#pragma unroll
                for (int t = 0; t < 6; t++) { c[t][0] = c[t][1] = c[t][2] = c[t][3] = 0.f; }
                const uint32_t* a = pq[hh];
                const bool od = g & 1;
                mma16816(c[0], a[0], a[1], a[2], a[3], od ? 0x3f803f80u : kf[hh][2].x, od ? 0x3f803f80u : kf[hh][2].y);
                mma16816(c[1], a[4], a[5], a[6], a[7], od ? 0x3f803f80u : kf[hh][2].z, od ? 0x3f803f80u : kf[hh][2].w);
                mma16816(c[2], a[0], a[1], a[2], a[3], kf[hh][0].x, kf[hh][0].y);
                mma16816(c[3], a[0], a[1], a[2], a[3], kf[hh][0].z, kf[hh][0].w);
                mma16816(c[4], a[4], a[5], a[6], a[7], kf[hh][1].x, kf[hh][1].y);
                mma16816(c[5], a[4], a[5], a[6], a[7], kf[hh][1].z, kf[hh][1].w);
                uint32_t w[4];
#pragma unroll
                for (int k = 0; k < 2; k++) {
                    const float rho = c[0][2 * k + 1] * rcp(c[1][2 * k + 1]);
                    const float r = rcp(fmaf(c[0][2 * k + 1], 1e-6f, fmaf(rho, c[1][2 * k], c[0][2 * k]))), rr = r * rho;
                    w[k] = pack2(fmaf(c[4][2 * k], rr, c[2][2 * k] * r), fmaf(c[4][2 * k + 1], rr, c[2][2 * k + 1] * r));
                    w[2 + k] = pack2(fmaf(c[5][2 * k], rr, c[3][2 * k] * r), fmaf(c[5][2 * k + 1], rr, c[3][2 * k + 1] * r));
                }
                own[hh] = tag4(w[0], w[1], w[2], w[3], tag);
            }
            uint4* og = scr->o + ((bi_i * 8 + warp) * 32 + bi_j * 4) * 32 + lane;
#pragma unroll
            for (int hh = 0; hh < 4; hh++) st_rlx128(og + hh * 32, own[hh]);
        }
        if (warp == 0) STAMP(6);
        float oc[64];
        const int slab = bi_i * 8 + (bi_j >> 2) * 4 + w4;
        const uint8_t* yb = (const uint8_t*)scr->y + (size_t)((bi_j & 3) * 32 + wg * 16 + (q >> 1)) * 16384 + slab * 128 + g * 16 + (q & 1) * 8;
        const unsigned* gp = scr->g + (slab * 8 + (g >> 1)) * 8 + (g & 1) * 4;
        uint2 yv[8]; unsigned g0, g1;
        {
            const uint4* osrc = scr->o + (slab * 32 + wg * 16) * 32 + lane;
            uint4 fr[16];
            const unsigned* probe = (const unsigned*)(osrc - lane + ((lane & 3) * 4 + 3) * 32 + 31) + 2;
            {
                unsigned miss = ~0u;
                int n = 0;
#pragma unroll
                for (int s = 0; s < 4; s++) {
#pragma unroll 1
                    while ((miss >> s) & 1) { miss = __ballot_sync(~0u, (ld_rlx(probe) ^ tag) & 1); if (++n > SPIN_LIMIT) break; }
#pragma unroll
                    for (int k = 4 * s; k < 4 * s + 4; k++) fr[k] = ld_rlx128(osrc + k * 32);
                }
            }
            if (warp == 0) STAMP(14);
            mbar_wait(bar + 8 * (wg ? BAR_WO2 : BAR_WO), 0);
            const uint64_t dw = mkdesc(sb + wg * 2 * SLOT, wg ? 32768 : SLOT, 1024);
#pragma unroll
            for (int s = 0; s < 4; s++) {
                int n = 0;
#pragma unroll 1
                while (__builtin_expect(__any_sync(~0u, (bad4(fr[4 * s], tag) | bad4(fr[4 * s + 1], tag) | bad4(fr[4 * s + 2], tag) | bad4(fr[4 * s + 3], tag)) & 1), 0)) {
#pragma unroll
                    for (int k = 4 * s; k < 4 * s + 4; k++) fr[k] = ld_rlx128(osrc + k * 32);
                    if (++n > SPIN_LIMIT) break;
                }
                wg_fence();
#pragma unroll
                for (int hh = 0; hh < 4; hh++) wgmma128_rs(oc, fr[4 * s + hh], dw + 128 * (4 * s + hh), (s | hh) != 0);
                wg_commit();
                if (s == 1) {
                    wg_wait<1>();
#pragma unroll
                    for (int nt = 0; nt < 8; nt++) yv[nt] = ld_rlx64(yb + nt * 32768);
                    g0 = ld_rlx(gp); g1 = ld_rlx(gp + 32);
                }
            }
            if (warp == 0) STAMP(7);
            {
                const unsigned* yprobe = scr->yflag + ((bi_j & 3) * 32 + wg * 16 + (lane & 15)) * 8;
                int n = 0;
#pragma unroll 1
                while (true) {
                    uint32_t bad = (g0 ^ tag) | (g1 ^ tag);
#pragma unroll
                    for (int nt = 0; nt < 8; nt++) bad |= yv[nt].x ^ tag;
                    if (!__any_sync(~0u, bad & 1)) break;
#pragma unroll 1
                    while (__any_sync(~0u, (ld_rlx(yprobe) ^ tag) & 1)) { if (++n > SPIN_LIMIT) break; }
#pragma unroll
                    for (int nt = 0; nt < 8; nt++) yv[nt] = ld_rlx64(yb + nt * 32768);
                    g0 = ld_rlx(gp); g1 = ld_rlx(gp + 32);
                    if (++n > SPIN_LIMIT) break;
                }
            }
            if (warp == 0) STAMP(28);
            wg_wait<0>();
            fence_regs<64>(oc);
        }
        {
            bar_named(3 + wg, 128);
            const uint32_t xw = sb + wg * 2 * SLOT + (tid & 127) * 16, xr = sb + (wg ^ 1) * 2 * SLOT + (tid & 127) * 16;
#pragma unroll
            for (int r = 0; r < 8; r++) {
                const float* o = oc + 4 * r;
                sts128(xw + r * 2048, __float_as_uint(wg ? o[0] : o[32]), __float_as_uint(wg ? o[1] : o[33]), __float_as_uint(wg ? o[2] : o[34]), __float_as_uint(wg ? o[3] : o[35]));
            }
#pragma unroll
            for (int r = 0; r < 32; r++) oc[r] = wg ? oc[32 + r] : oc[r];
            bar_named(1, 256);
            if (warp == 0) STAMP(8);
            const float ga = bf_hi(g0), gb = bf_hi(g1);
            const float ha = bf_round(1.0f - ga), hb = bf_round(1.0f - gb);
            uint32_t w[8][2];
#pragma unroll
            for (int nt = 0; nt < 8; nt++) {
                const uint4 p = lds128(xr + nt * 2048);
                w[nt][0] = pack2(fmaf(ga, oc[4 * nt] + __uint_as_float(p.x), ha * bf_lo(yv[nt].x)), fmaf(ga, oc[4 * nt + 1] + __uint_as_float(p.y), ha * bf_hi(yv[nt].x)));
                w[nt][1] = pack2(fmaf(gb, oc[4 * nt + 2] + __uint_as_float(p.z), hb * bf_lo(yv[nt].y)), fmaf(gb, oc[4 * nt + 3] + __uint_as_float(p.w), hb * bf_hi(yv[nt].y)));
            }
            const uint32_t ob = sb + wg * 2 * SLOT + 16384 + w4 * 2048;
#pragma unroll
            for (int nt = 0; nt < 8; nt += 2)
                stsm4(ob + (lane & 15) * 128 + (((nt + shi) ^ (lane & 7)) << 4), w[nt][0], w[nt][1], w[nt + 1][0], w[nt + 1][1]);
            __syncwarp();
            bf16* op = out + (size_t)(slab * 16) * 512 + (bi_j & 3) * 128 + wg * 64 + (lane & 7) * 8;
#pragma unroll
            for (int it = 0; it < 4; it++) {
                const int r = it * 4 + (lane >> 3);
                uint4 v = lds128(ob + r * 128 + (((lane & 7) ^ (r & 7)) << 4));
                *(uint4*)(op + r * 512) = v;
            }
        }
        if (warp == 0) STAMP(10);
    } else {
        const int st = tid - 256;
        float kc[24];
        const int brow = (buf >> 7) & 7;
#pragma unroll
        for (int t = 0; t < 24; t++) kc[t] = 0.f;
        fence_regs<24>(kc);
        {
            const float dt = bf_round(expf((ch & 1) ? bf_hi(pdt) : bf_lo(pdt)));
#pragma unroll 1
            for (int it = 0; it < KG_ROUNDS; it++) {
                const int sh = (it & 1) * 16;
                auto pick = [&](const uint2& v) { return __uint_as_float(((it & 2 ? v.y : v.x) >> sh) << 16); };
                const float ea = bf_round(expf(pick(pla)));
                const float arl = (-ea * dt) * 1.4426950408889634f, ait = (pick(pai) * dt) * 0.15915494309189535f;
                cf C2; C2.re = 2.0f * (pick(pcr) * dt); C2.im = 2.0f * (pick(pci) * dt);
                const cf z1 = cexp_p(arl, ait, 1.0f), z128 = cexp_p(arl, ait, 128.0f);
                cf z8 = cexp_p(arl, ait, 8.0f); z8.im = -z8.im;
                const uint32_t lp = buf + lane * 4;
                auto put = [&](int row, const cf& v) { sts32((lp ^ (((row + brow) & 7) << 4)) + row * 128, pack2(v.re, v.im)); };
                {
                    const cf z16 = cmul(z8, z8);
                    cf e; e.re = 1.f; e.im = 0.f;
                    cf o = z8;
                    put(0, e); put(1, o);
                    e = z16; put(2, e);
#pragma unroll
                    for (int b = 3; b < 16; b += 2) {
                        o = cmul(o, z16); put(b, o);
                        if (b + 1 < 16) { e = cmul(e, z16); put(b + 1, e); }
                    }
                }
                cf h[8];
                h[0] = C2; put(16, h[0]);
                {
                    const cf z2 = cmul(z1, z1);
                    h[1] = cmul(h[0], z1);
#pragma unroll
                    for (int r = 2; r < 8; r++) h[r] = cmul(h[r - 2], z2);
#pragma unroll
                    for (int r = 1; r < 8; r++) put(16 + r, h[r]);
                }
#pragma unroll
                for (int r = 0; r < 8; r++) { h[r] = cmul(h[r], z128); put(24 + r, h[r]); }
#pragma unroll
                for (int al = 0; al < 2; al++)
#pragma unroll
                    for (int r = 0; r < 4; r++) { h[2 * r] = cmul(h[2 * r], z128); put(32 + al * 4 + r, h[2 * r]); }
#pragma unroll
                for (int al = 0; al < 4; al++)
#pragma unroll
                    for (int r = 0; r < 2; r++) { h[4 * r] = cmul(h[4 * r], z128); put(40 + al * 2 + r, h[4 * r]); }
#pragma unroll
                for (int al = 0; al < 9; al++) { h[0] = cmul(h[0], z128); put(48 + al, h[0]); }
                asm volatile("fence.proxy.async.shared::cta;" ::: "memory");
                bar_named(2, 128);
                uint32_t la[4][4];
#pragma unroll
                for (int ks = 0; ks < 4; ks++) ldsm4(la[ks], buf + (lane & 15) * 128 + (((2 * ks + (lane >> 4)) ^ ((lane + brow) & 7)) << 4));
                const uint64_t dh = mkdesc(sb + OFF_BUF + 2048, 16, 1024);
#pragma unroll
                for (int c = 0; c < 4; c++) {
                    uint32_t a[4][4];
#pragma unroll
                    for (int r = 0; r < 16; r++) a[r >> 2][r & 3] = (c == w4) ? la[r >> 2][r & 3] : 0u;
                    wg_fence();
#pragma unroll
                    for (int ks = 0; ks < 4; ks++) wgmma48_rs(kc, a[ks][0], a[ks][1], a[ks][2], a[ks][3], dh + c * (BUF_STRIDE >> 4) + 2 * ks);
                    wg_commit();
                }
                wg_wait<0>();
                fence_regs<24>(kc);
                bar_named(2, 128);
            }
        }
        if (warp == 8) STAMP(22);
        if (warp == 8) {
            mbar_wait(bar + 8 * BAR_XT, 0);
            if (lane == 0) asm volatile("red.release.gpu.global.add.u32 [%0],8;" ::"l"(scr->xcnt + ((bi_j >> 1) + rot) * 32) : "memory");
        }
        if (lane == 0) {
            int n = 0;
#pragma unroll 1
            while ((int)(ld_acq(scr->xcnt + bi_j * 32) - (epoch1 << 7)) < 0) { __nanosleep(200); if (++n > SPIN_LIMIT) break; }
        }
        __syncwarp();
        if (warp == 8) STAMP(15);
        uint4 ur[8];
#pragma unroll
        for (int v = 0; v < 8; v++) ur[v] = __ldcg(scr->xt + bi * 1024 + st + 128 * v);
#pragma unroll
        for (int v = 0; v < 3; v++) if (v * 32 + lane < U_PAD / 16) sts128(sb + OFF_U + w4 * U_STRIDE + (v * 32 + lane) * 16, 0, 0, 0, 0);
        if (st < 8) st_rlx32(scr->yflag + bi * 8 + st, tag ^ 1u);
#pragma unroll
        for (int v = 0; v < 8; v++) {
            const uint32_t a = sb + OFF_U + (st & 3) * U_STRIDE + U_PAD + ((st >> 2) + 32 * v) * 16;
            sts128(a ^ ((a >> 3) & 0x70), ur[v].x, ur[v].y, ur[v].z, ur[v].w);
        }
        if (warp == 8) STAMP(16);
        bar_named(2, 128);
        if (lane < 14) sts128(buf + (lane >= 7 ? W3_OFF - 112 : 0) + lane * 16, 0, 0, 0, 0);
        {
            const uint32_t u0 = sb + OFF_U + w4 * U_STRIDE + U_PAD + lane * 16;
#pragma unroll 1
            for (int r2 = 0; r2 < 3; r2++) {
#pragma unroll
                for (int hf = 0; hf < 2; hf++) {
                    const int rho = 2 * r2 + hf, ci = lane + 32 * rho;
                    uint4 e4[4];
#pragma unroll
                    for (int v = 1; v < 4; v++) { const uint32_t a = u0 + rho * 512 + (v - 3) * 16; e4[v] = lds128(a ^ ((a >> 3) & 0x70)); }
                    float S[29];
                    const uint32_t* ew = (const uint32_t*)e4;
                    S[13] = 0.f;
#pragma unroll
                    for (int k = 14; k <= 28; k++) S[k] = S[k - 1] + ((k & 1) ? bf_hi(ew[k >> 1]) : bf_lo(ew[k >> 1]));
                    auto win = [&](int lo, int hi, uint32_t a) {
                        sts128(a, pack2(S[hi] - S[lo - 1], S[hi + 1] - S[lo]), pack2(S[hi + 2] - S[lo + 1], S[hi + 3] - S[lo + 2]),
                               pack2(S[hi + 4] - S[lo + 3], S[hi + 5] - S[lo + 4]), pack2(S[hi + 6] - S[lo + 5], S[hi + 7] - S[lo + 6]));
                    };
                    win(14, 18, buf + W5_OFF + 112 + ci * 16); win(19, 21, buf + W3_OFF + 112 + ci * 16);
                }
            }
        }
        if (warp == 8) STAMP(24);
        mbar_wait(bar + 8 * BAR_WO, 0);
        const uint32_t kt = sb + kt_off(w4);
#pragma unroll
        for (int v = 0; v < 8; v++) if (v * 32 + lane < KT_BYTES / 16) sts128(kt + (v * 32 + lane) * 16, 0, 0, 0, 0);
        __syncwarp();
        if (lane == 0) kc[4 * 0 + 0] += (ch & 1) ? bf_hi(pds) : bf_lo(pds);
#pragma unroll
        for (int i = 0; i < 2; i++) {
            const int be = g + 8 * i;
#pragma unroll
            for (int t = 0; t < 2; t++) {
                const uint32_t a = kt + (64 + 128 * t + 8 * be + 2 * q) * 4;
                const uint32_t w = pack2(kc[4 * t + 2 * i + 1], kc[4 * t + 2 * i]);
                sts32(a + 4, w); sts16(a, w >> 16); sts16(a + 10, w);
            }
            {
                const int p = 256 + 128 * (q >> 1) + 8 * be + 4 * (q & 1);
                const uint32_t a = kt + (64 + p) * 4;
                const uint32_t w = pack2(kc[4 * 2 + 2 * i + 1], kc[4 * 2 + 2 * i]);
                const uint32_t aa = (w >> 16) | (w & 0xffff0000u);
                if (p != 256) { sts16(a - 4, aa); sts32(a, aa); } else sts16(a, aa);
                sts32(a + 4, aa); sts32(a + 8, w); sts16(a + 14, w);
            }
            {
                const int k = 64 + 16 * q + be;
                const uint32_t w = pack2(kc[4 * 3 + 2 * i], kc[4 * 3 + 2 * i + 1]);
                if (k != 64) sts16(kt + KT_E2 + (k - 1) * 2, w);
                else {
                    const uint32_t a = kt + (64 + 511) * 4, aa = (w << 16) | (w & 0xffffu);
                    sts16(a, w); sts32(a + 4, aa); sts32(a + 8, aa); sts32(a + 12, aa); sts16(a + 18, w);
                }
                sts16(kt + KT_E2 + KT_E2O + k * 2, w >> 16);
            }
#pragma unroll
            for (int b = 0; b < 2; b++) {
                const int k = 64 + 8 * (2 * q + b) + (be >> 1);
                const uint32_t w = pack2(kc[4 * 4 + 2 * i + b], 0.f);
                const bool k1024 = !(be & 1) && k == 64;
                const uint32_t a = k3 + (k1024 ? 188 + 64 : ((be & 1) ? 94 + k : k - 1)) * 4 - 34 * 4;
                sts16(a, w);
                if (!((be & 1) && k == 127)) sts16(a + 6, w);
                if (k1024) sts16(kt + KT_E2 + 127 * 2, w);
            }
        }
        if (lane == 0) sts16(k3 + (127 - 34) * 4, pack2(kc[4 * 5 + 0], 0.f));
        asm volatile("fence.proxy.async.shared::cta;" ::: "memory");
        bar_named(2, 128);
        if (warp == 8) STAMP(17);
        mbar_wait(bar + 8 * BAR_DONE, 0);
        uint32_t yw[2][16];
#pragma unroll 1
        for (int p = 0; p < 2; p++) {
            uint32_t sp = sb, ln = lane;
            asm volatile("" : "+r"(sp), "+r"(ln));
            const int g = ln >> 2, q = ln & 3;
            float y[2][16];
#pragma unroll
            for (int c = 0; c < 2; c++) {
#pragma unroll
                for (int r = 0; r < 16; r++) y[c][r] = 0.f;
                fence_regs<16>(y[c]);
            }
            const uint32_t ktp = sp + OFF_SP0 + p * SLOT;
            {
                uint32_t Q[3][4][4];
                uint32_t ka = ktp + (64 - 48 + 16 * w4 + g - 2 * q) * 4;
                uint64_t dd = mkdesc(sp + OFF_U + 2 * p * U_STRIDE + U_PAD + 96, 16, 1024);
                int s1 = U_STRIDE >> 4, s2 = -2, sg = -4;
#pragma unroll 1
                for (int it = 0; it < 10; it++) {
                    if (it == 6) {
                        ka = sp + OFF_BUF + 2 * p * BUF_STRIDE + (15 - (ln >> 4) * 8 - (ln & 7) + 2 * w4 + ((ln >> 3) & 1)) * 16;
                        dd = (uint64_t)(((ktp + KT_E2 - 16) & 0x3FFFF) >> 4) | ((uint64_t)1 << 16) | ((uint64_t)8 << 32);
                        s1 = 256; s2 = KT_E2O >> 4; sg = -2;
                    }
#pragma unroll
                    for (int b = 0; b < 3; b++) {
                        wg_wait<2>();
                        if (it < 6) {
#pragma unroll
                            for (int c = 0; c < 4; c++) {
                                const uint32_t a = ka + (c & 1) * 4096 + (2 * b + (c >> 1)) * 64;
                                Q[b][c][0] = lds32(a); Q[b][c][1] = lds32(a + 32); Q[b][c][2] = lds32(a - 32); Q[b][c][3] = Q[b][c][0];
                            }
                        } else {
#pragma unroll
                            for (int c = 0; c < 4; c++) ldsm4t(Q[b][c], ka + (c & 1) * BUF_STRIDE + (c >> 1) * W3_OFF + 256 * b);
                        }
                        wg_fence();
                        wgmma32_rs(y[0], Q[b][0], dd); wgmma32_rs(y[1], Q[b][1], dd + s1);
                        wgmma32_rs(y[0], Q[b][2], dd + s2); wgmma32_rs(y[1], Q[b][3], dd + s1 + s2);
                        wg_commit();
                        dd += sg;
                    }
                    ka += it < 6 ? 384 : 768;
                }
            }
            wg_wait<0>();
            fence_regs<16>(y[0]); fence_regs<16>(y[1]);
            if (warp == 8) STAMP(18 + p);
            if (p == 0) {
                {
                    const uint32_t u0 = sp + OFF_U + w4 * U_STRIDE + U_PAD + ln * 16;
#pragma unroll 1
                    for (int r2 = 0; r2 < 2; r2++) {
#pragma unroll
                        for (int hf = 0; hf < 2; hf++) {
                            const int rho = 2 * r2 + hf, ci = ln + 32 * rho;
                            uint4 e4[4];
#pragma unroll
                            for (int v = 0; v < 4; v++) { const uint32_t a = u0 + rho * 512 + (v - 3) * 16; e4[v] = lds128(a ^ ((a >> 3) & 0x70)); }
                            float S[29];
                            const uint32_t* ew = (const uint32_t*)e4;
                            S[3] = 0.f;
#pragma unroll
                            for (int k = 4; k <= 28; k++) S[k] = S[k - 1] + ((k & 1) ? bf_hi(ew[k >> 1]) : bf_lo(ew[k >> 1]));
                            auto win = [&](int lo, int hi, uint32_t a) {
                                sts128(a, pack2(S[hi] - S[lo - 1], S[hi + 1] - S[lo]), pack2(S[hi + 2] - S[lo + 1], S[hi + 3] - S[lo + 2]),
                                       pack2(S[hi + 4] - S[lo + 3], S[hi + 5] - S[lo + 4]), pack2(S[hi + 6] - S[lo + 5], S[hi + 7] - S[lo + 6]));
                            };
                            const uint32_t sw = (ci ^ ((ci >> 3) & 1)) << 4;
                            win(4, 12, sp + OFF_BUF + w4 * BUF_STRIDE + W9_OFF + sw); win(13, 19, sp + OFF_X + w4 * 4096 + sw); win(20, 21, sp + OFF_X + w4 * 4096 + 2048 + sw);
                        }
                    }
                }
                bar_named(2, 128);
                if (warp == 8) STAMP(23);
            }
            {
                const int ap = (ln & 7) + (ln >> 4) * 8;
                const uint32_t loff = ((2 * ap + ((ln >> 3) & 1)) ^ ((ap >> 2) & 1)) << 4;
#pragma unroll
                for (int ph = 0; ph < 3; ph++) {
                    const uint32_t ka = sp + OFF_K3 + 2 * p * K3_STRIDE + (ph * 94 + 4 * g + w4 - 2 * q - 34) * 4;
#pragma unroll
                    for (int c = 0; c < 2; c++) {
                        const uint32_t wb = (ph ? sp + OFF_X + (2 * p + c) * 4096 + (ph - 1) * 2048 : sp + OFF_BUF + (2 * p + c) * BUF_STRIDE + W9_OFF) + loff;
                        uint32_t B[4][2];
#pragma unroll
                        for (int d = 0; d < (ph < 2 ? 4 : 2); d++) { B[d][0] = lds32(ka + c * K3_STRIDE + (48 + 16 * d) * 4); B[d][1] = lds32(ka + c * K3_STRIDE + (40 + 16 * d) * 4); }
#pragma unroll
                        for (int s = 0; s < 4; s++) {
                            uint32_t A[4];
                            ldsm4t(A, wb + s * 512);
                            if (s < 2) mma16816(y[c] + 8, A[0], A[1], A[2], A[3], B[1 - s][0], B[1 - s][1]);
                            if (ph < 2 || s >= 2) mma16816(y[c] + 12, A[0], A[1], A[2], A[3], B[3 - s][0], B[3 - s][1]);
                        }
                    }
                }
            }
#pragma unroll
            for (int c = 0; c < 2; c++) {
                const uint32_t a = ktp + c * 4096 + (64 + 16 * (33 + w4) + g - 2 * q) * 4;
                const uint32_t a0 = lds32(a), a1 = lds32(a + 32), a2 = lds32(a - 32);
                uint32_t B[8];
#pragma unroll
                for (int hf = 0; hf < 2; hf++) {
                    const uint32_t ua = sp + OFF_U + (2 * p + c) * U_STRIDE + U_PAD + (16 * hf + (ln >> 4) * 8 + (ln & 7) - 9) * 128 + (6 + ((ln >> 3) & 1)) * 16;
                    ldsm4(B + 4 * hf, ua ^ ((ua >> 3) & 0x70));
                }
#pragma unroll
                for (int j = 1; j < 4; j++) mma16816(y[c] + 4 * j, a0, a1, a2, a0, B[2 * j], B[2 * j + 1]);
            }
#pragma unroll
            for (int r = 0; r < 16; r++) { yw[0][r] = yw[1][r]; yw[1][r] = pack2(y[0][r], y[1][r]); }
        }
        uint4* yp = scr->y + bi * 1024 + (8 * q + w4) * 8 + g;
#pragma unroll
        for (int j = 0; j < 4; j++)
#pragma unroll
            for (int b = 0; b < 2; b++)
                st_rlx128(yp + (32 * j + 4 * b) * 8, tag4(yw[0][4 * j + b], yw[0][4 * j + 2 + b], yw[1][4 * j + b], yw[1][4 * j + 2 + b], tag));
        bar_named(2, 128);
        if (st < 8) st_rlx32(scr->yflag + bi * 8 + st, tag);
        if (warp == 8) STAMP(20);
    }
    __syncthreads();
    if (tid == 0) atomicAdd(scr->done, 1u);
}

typedef CUresult (*EncFn)(CUtensorMap*, CUtensorMapDataType, cuuint32_t, void*, const cuuint64_t*, const cuuint64_t*, const cuuint32_t*,
                          const cuuint32_t*, CUtensorMapInterleave, CUtensorMapSwizzle, CUtensorMapL2promotion, CUtensorMapFloatOOBfill);

extern "C" void kernel_launch(void* const* d_in, const int* in_sizes, int n_in, void* d_out, int out_size) {
    static EncFn enc = nullptr;
    static Scratch* scr = nullptr;
    if (!enc) {
        cudaGetSymbolAddress((void**)&scr, g_scr);
        cudaDriverEntryPointQueryResult qr;
        cudaGetDriverEntryPoint("cuTensorMapEncodeTiled", (void**)&enc, cudaEnableDefault, &qr);
        cudaFuncSetAttribute(fused_kernel, cudaFuncAttributeMaxDynamicSharedMemorySize, SMEM_BYTES);
    }
    CUtensorMap mx, mw, mwo;
    const cuuint32_t es[3] = {1, 1, 1};
    {
        cuuint64_t d[2] = {512, 2048}, s[1] = {1024}; cuuint32_t b[2] = {64, 128};
        enc(&mx, CU_TENSOR_MAP_DATA_TYPE_BFLOAT16, 2, d_in[0], d, s, b, es, CU_TENSOR_MAP_INTERLEAVE_NONE, CU_TENSOR_MAP_SWIZZLE_128B,
            CU_TENSOR_MAP_L2_PROMOTION_L2_128B, CU_TENSOR_MAP_FLOAT_OOB_FILL_NONE);
    }
    {
        cuuint64_t d[3] = {512, 512, 3}, s[2] = {3072, 1024}; cuuint32_t b[3] = {64, 64, 3};
        enc(&mw, CU_TENSOR_MAP_DATA_TYPE_BFLOAT16, 3, d_in[1], d, s, b, es, CU_TENSOR_MAP_INTERLEAVE_NONE, CU_TENSOR_MAP_SWIZZLE_128B,
            CU_TENSOR_MAP_L2_PROMOTION_L2_128B, CU_TENSOR_MAP_FLOAT_OOB_FILL_NONE);
    }
    {
        cuuint64_t d[2] = {512, 512}, s[1] = {1024}; cuuint32_t b[2] = {64, 256};
        enc(&mwo, CU_TENSOR_MAP_DATA_TYPE_BFLOAT16, 2, d_in[3], d, s, b, es, CU_TENSOR_MAP_INTERLEAVE_NONE, CU_TENSOR_MAP_SWIZZLE_128B,
            CU_TENSOR_MAP_L2_PROMOTION_L2_128B, CU_TENSOR_MAP_FLOAT_OOB_FILL_NONE);
    }
    fused_kernel<<<128, 384, SMEM_BYTES, cudaStreamPerThread>>>(
        scr, (const bf16*)d_in[5], (const bf16*)d_in[6], (const bf16*)d_in[7], (const bf16*)d_in[8], (const bf16*)d_in[9],
        (const bf16*)d_in[10], (const bf16*)d_in[2], (const bf16*)d_in[11], (bf16*)d_out, mx, mw, mwo);
}
```

```cpp
#include <cuda_runtime.h>
#include <cuda.h>
#include <cuda_bf16.h>
#include <stdint.h>

typedef __nv_bfloat16 bf16;

struct Scratch {
    uint4 xt[128 * 1024];
    uint4 o[16 * 8 * 32 * 32];
    uint4 y[128 * 1024];
    uint4 kvp[8 * 16 * 544];
    uint4 kvf[8 * 4 * 68];
    unsigned g[1024 * 8];
    unsigned yflag[128 * 8];
    unsigned xcnt[8 * 32];
    unsigned done[32];
};
__device__ Scratch g_scr;
#define STAMP(n)

constexpr int SLOT = 40960;
constexpr int OFF_SP0 = 32768, OFF_SP1 = SLOT + 32768;
constexpr int OFF_P = 2 * SLOT, OFF_V = OFF_P + 32768;
constexpr int OFF_X = OFF_V + 32768;
constexpr int KT_BYTES = 3824, KT_E2 = 2688, KT_E2O = 624;
__host__ __device__ constexpr int kt_off(int c) { return (c < 2 ? OFF_SP0 : OFF_SP1) + (c & 1) * 4096; }
constexpr int OFF_U = 4 * SLOT, U_STRIDE = 41 * 128, U_PAD = 9 * 128;
constexpr int OFF_BUF = OFF_U + 4 * U_STRIDE, BUF_STRIDE = 8448;
constexpr int OFF_K3 = OFF_BUF + 4 * BUF_STRIDE, K3_STRIDE = 1136;
constexpr int OFF_WPHI = OFF_K3 + 4 * K3_STRIDE;
constexpr int OFF_GW = OFF_WPHI + 2048;
constexpr int OFF_KVF = OFF_GW + 1024;
constexpr int OFF_BAR = OFF_KVF + 4352;
constexpr int SMEM_BYTES = OFF_BAR + 128 + 128;
static_assert(SMEM_BYTES <= 232448 && OFF_BUF % 128 == 0, "smem");
constexpr int W5_OFF = 0, W3_OFF = 3184, W9_OFF = 6368;
constexpr int BAR_FULL = 0, BAR_WPHI = 4, BAR_WO = 5, BAR_XT = 6, BAR_DONE = 7, BAR_WO2 = 8, OFF_CNT = 96;
#define KG_ROUNDS 4
constexpr int SPIN_LIMIT = 1 << 17;

__device__ __forceinline__ uint32_t s2u(const void* p) { return (uint32_t)__cvta_generic_to_shared(p); }
__device__ __forceinline__ void mbar_init(uint32_t b, int c) { asm volatile("mbarrier.init.shared::cta.b64 [%0],%1;" ::"r"(b), "r"(c) : "memory"); }
__device__ __forceinline__ void mbar_expect(uint32_t b, int bytes) { asm volatile("mbarrier.arrive.expect_tx.shared::cta.b64 _,[%0],%1;" ::"r"(b), "r"(bytes) : "memory"); }
__device__ __forceinline__ void mbar_arrive(uint32_t b) { asm volatile("mbarrier.arrive.shared::cta.b64 _,[%0];" ::"r"(b) : "memory"); }
__device__ __forceinline__ void mbar_wait(uint32_t b, int ph) {
    asm volatile("{\n.reg .pred p;\n.reg .u32 n;\nmov.u32 n,0;\nLW_%=:\nmbarrier.try_wait.parity.shared::cta.b64 p,[%0],%1;\n@p bra LD_%=;\n"
                 "add.u32 n,n,1;\nsetp.lt.u32 p,n,131072;\n@p bra LW_%=;\nLD_%=:\n}" ::"r"(b), "r"(ph) : "memory");
}
__device__ __forceinline__ void tma2d(uint32_t dst, const CUtensorMap* m, int c0, int c1, uint32_t bar) {
    asm volatile("cp.async.bulk.tensor.2d.shared::cluster.global.mbarrier::complete_tx::bytes [%0],[%1,{%3,%4}],[%2];" ::"r"(dst), "l"(m), "r"(bar), "r"(c0), "r"(c1) : "memory");
}
__device__ __forceinline__ void tma3d(uint32_t dst, const CUtensorMap* m, int c0, int c1, int c2, uint32_t bar) {
    asm volatile("cp.async.bulk.tensor.3d.shared::cluster.global.mbarrier::complete_tx::bytes [%0],[%1,{%3,%4,%5}],[%2];" ::"r"(dst), "l"(m), "r"(bar), "r"(c0), "r"(c1), "r"(c2) : "memory");
}
__device__ __forceinline__ void bulk_g2s(uint32_t dst, const void* src, int bytes, uint32_t bar) {
    asm volatile("cp.async.bulk.shared::cluster.global.mbarrier::complete_tx::bytes [%0],[%1],%2,[%3];" ::"r"(dst), "l"(src), "r"(bytes), "r"(bar) : "memory");
}
__device__ __forceinline__ uint64_t mkdesc(uint32_t addr, uint32_t lbo, uint32_t sbo) {
    return (uint64_t)((addr & 0x3FFFF) >> 4) | ((uint64_t)(lbo >> 4) << 16) | ((uint64_t)(sbo >> 4) << 32) | ((uint64_t)1 << 62);
}
__device__ __forceinline__ void wg_fence() { asm volatile("wgmma.fence.sync.aligned;" ::: "memory"); }
__device__ __forceinline__ void wg_commit() { asm volatile("wgmma.commit_group.sync.aligned;" ::: "memory"); }
template <int N> __device__ __forceinline__ void wg_wait() { asm volatile("wgmma.wait_group.sync.aligned %0;" ::"n"(N) : "memory"); }
template <int N> __device__ __forceinline__ void fence_regs(float* d) {
#pragma unroll
    for (int i = 0; i < N; i++) asm volatile("" : "+f"(d[i])::"memory");
}
#define R8(d, o) "+f"(d[o]), "+f"(d[o + 1]), "+f"(d[o + 2]), "+f"(d[o + 3]), "+f"(d[o + 4]), "+f"(d[o + 5]), "+f"(d[o + 6]), "+f"(d[o + 7])
__device__ __forceinline__ void wgmma192(float* d, uint64_t da, uint64_t db) {
    asm volatile("wgmma.mma_async.sync.aligned.m64n192k16.f32.bf16.bf16 {"
                 "%0,%1,%2,%3,%4,%5,%6,%7,%8,%9,%10,%11,%12,%13,%14,%15,%16,%17,%18,%19,%20,%21,%22,%23,%24,%25,%26,%27,%28,%29,%30,%31,"
                 "%32,%33,%34,%35,%36,%37,%38,%39,%40,%41,%42,%43,%44,%45,%46,%47,%48,%49,%50,%51,%52,%53,%54,%55,%56,%57,%58,%59,%60,%61,%62,%63,"
                 "%64,%65,%66,%67,%68,%69,%70,%71,%72,%73,%74,%75,%76,%77,%78,%79,%80,%81,%82,%83,%84,%85,%86,%87,%88,%89,%90,%91,%92,%93,%94,%95},"
                 "%96,%97,1,1,1,0,1;"
                 : R8(d, 0), R8(d, 8), R8(d, 16), R8(d, 24), R8(d, 32), R8(d, 40), R8(d, 48), R8(d, 56), R8(d, 64), R8(d, 72), R8(d, 80), R8(d, 88)
                 : "l"(da), "l"(db));
}
__device__ __forceinline__ void wgmma64_tt(float* d, uint64_t da, uint64_t db, int sc) {
    asm volatile("{.reg .pred p; setp.ne.b32 p,%34,0; wgmma.mma_async.sync.aligned.m64n64k16.f32.bf16.bf16 {"
                 "%0,%1,%2,%3,%4,%5,%6,%7,%8,%9,%10,%11,%12,%13,%14,%15,%16,%17,%18,%19,%20,%21,%22,%23,%24,%25,%26,%27,%28,%29,%30,%31},"
                 "%32,%33,p,1,1,1,1;}"
                 : R8(d, 0), R8(d, 8), R8(d, 16), R8(d, 24)
                 : "l"(da), "l"(db), "r"(sc));
}
__device__ __forceinline__ void wgmma128_rs(float* d, const uint4& a, uint64_t db, int sc) {
    asm volatile("{.reg .pred p; setp.ne.b32 p,%69,0; wgmma.mma_async.sync.aligned.m64n128k16.f32.bf16.bf16 {"
                 "%0,%1,%2,%3,%4,%5,%6,%7,%8,%9,%10,%11,%12,%13,%14,%15,%16,%17,%18,%19,%20,%21,%22,%23,%24,%25,%26,%27,%28,%29,%30,%31,"
                 "%32,%33,%34,%35,%36,%37,%38,%39,%40,%41,%42,%43,%44,%45,%46,%47,%48,%49,%50,%51,%52,%53,%54,%55,%56,%57,%58,%59,%60,%61,%62,%63},"
                 "{%64,%65,%66,%67},%68,p,1,1,1;}"
                 : R8(d, 0), R8(d, 8), R8(d, 16), R8(d, 24), R8(d, 32), R8(d, 40), R8(d, 48), R8(d, 56)
                 : "r"(a.x), "r"(a.y), "r"(a.z), "r"(a.w), "l"(db), "r"(sc));
}
__device__ __forceinline__ void wgmma32_rs(float* d, const uint32_t* a, uint64_t db) {
    asm volatile("wgmma.mma_async.sync.aligned.m64n32k16.f32.bf16.bf16 {%0,%1,%2,%3,%4,%5,%6,%7,%8,%9,%10,%11,%12,%13,%14,%15},{%16,%17,%18,%19},%20,1,1,1,0;"
                 : R8(d, 0), R8(d, 8) : "r"(a[0]), "r"(a[1]), "r"(a[2]), "r"(a[3]), "l"(db));
}
__device__ __forceinline__ void wgmma48_rs(float* d, uint32_t a0, uint32_t a1, uint32_t a2, uint32_t a3, uint64_t db) {
    asm volatile("wgmma.mma_async.sync.aligned.m64n48k16.f32.bf16.bf16 {%0,%1,%2,%3,%4,%5,%6,%7,%8,%9,%10,%11,%12,%13,%14,%15,%16,%17,%18,%19,%20,%21,%22,%23},{%24,%25,%26,%27},%28,1,1,1,0;"
                 : R8(d, 0), R8(d, 8), R8(d, 16) : "r"(a0), "r"(a1), "r"(a2), "r"(a3), "l"(db));
}
__device__ __forceinline__ void mma16816(float* c, uint32_t a0, uint32_t a1, uint32_t a2, uint32_t a3, uint32_t b0, uint32_t b1) {
    asm("mma.sync.aligned.m16n8k16.row.col.f32.bf16.bf16.f32 {%0,%1,%2,%3},{%4,%5,%6,%7},{%8,%9},{%0,%1,%2,%3};"
        : "+f"(c[0]), "+f"(c[1]), "+f"(c[2]), "+f"(c[3]) : "r"(a0), "r"(a1), "r"(a2), "r"(a3), "r"(b0), "r"(b1));
}
__device__ __forceinline__ void ldsm4(uint32_t* r, uint32_t a) {
    asm volatile("ldmatrix.sync.aligned.m8n8.x4.shared.b16 {%0,%1,%2,%3},[%4];" : "=r"(r[0]), "=r"(r[1]), "=r"(r[2]), "=r"(r[3]) : "r"(a) : "memory");
}
__device__ __forceinline__ void ldsm4t(uint32_t* r, uint32_t a) {
    asm volatile("ldmatrix.sync.aligned.m8n8.x4.trans.shared.b16 {%0,%1,%2,%3},[%4];" : "=r"(r[0]), "=r"(r[1]), "=r"(r[2]), "=r"(r[3]) : "r"(a) : "memory");
}
__device__ __forceinline__ void stsm4(uint32_t a, uint32_t r0, uint32_t r1, uint32_t r2, uint32_t r3) {
    asm volatile("stmatrix.sync.aligned.m8n8.x4.shared.b16 [%0],{%1,%2,%3,%4};" ::"r"(a), "r"(r0), "r"(r1), "r"(r2), "r"(r3) : "memory");
}
__device__ __forceinline__ uint32_t lds32(uint32_t a) { uint32_t v; asm volatile("ld.shared.b32 %0,[%1];" : "=r"(v) : "r"(a) : "memory"); return v; }
__device__ __forceinline__ uint4 lds128(uint32_t a) { uint4 v; asm volatile("ld.shared.v4.b32 {%0,%1,%2,%3},[%4];" : "=r"(v.x), "=r"(v.y), "=r"(v.z), "=r"(v.w) : "r"(a) : "memory"); return v; }
__device__ __forceinline__ void sts16(uint32_t a, uint32_t v) { asm volatile("st.shared.b16 [%0],%1;" ::"r"(a), "h"((unsigned short)v) : "memory"); }
__device__ __forceinline__ void sts32(uint32_t a, uint32_t v) { asm volatile("st.shared.b32 [%0],%1;" ::"r"(a), "r"(v) : "memory"); }
__device__ __forceinline__ void sts64(uint32_t a, uint32_t x, uint32_t y) { asm volatile("st.shared.v2.b32 [%0],{%1,%2};" ::"r"(a), "r"(x), "r"(y) : "memory"); }
__device__ __forceinline__ void sts128(uint32_t a, uint32_t x, uint32_t y, uint32_t z, uint32_t w) { asm volatile("st.shared.v4.b32 [%0],{%1,%2,%3,%4};" ::"r"(a), "r"(x), "r"(y), "r"(z), "r"(w) : "memory"); }
__device__ __forceinline__ uint32_t pack2(float lo, float hi) { uint32_t d; asm("cvt.rn.bf16x2.f32 %0,%1,%2;" : "=r"(d) : "f"(hi), "f"(lo)); return d; }
__device__ __forceinline__ float bf_lo(uint32_t v) { return __uint_as_float(v << 16); }
__device__ __forceinline__ float bf_hi(uint32_t v) { return __uint_as_float(v & 0xffff0000u); }
__device__ __forceinline__ float bf_round(float v) { return bf_lo(pack2(v, 0.f)); }
__device__ __forceinline__ uint32_t hmax2(uint32_t a, uint32_t b) { uint32_t d; asm("max.bf16x2 %0,%1,%2;" : "=r"(d) : "r"(a), "r"(b)); return d; }
__device__ __forceinline__ uint32_t hmin2(uint32_t a, uint32_t b) { uint32_t d; asm("min.bf16x2 %0,%1,%2;" : "=r"(d) : "r"(a), "r"(b)); return d; }
__device__ __forceinline__ uint32_t hmul2(uint32_t a, uint32_t b) { uint32_t d; asm("mul.rn.bf16x2 %0,%1,%2;" : "=r"(d) : "r"(a), "r"(b)); return d; }
__device__ __forceinline__ float ex2(float x) { float y; asm("ex2.approx.ftz.f32 %0,%1;" : "=f"(y) : "f"(x)); return y; }
__device__ __forceinline__ float rcp(float x) { float y; asm("rcp.approx.ftz.f32 %0,%1;" : "=f"(y) : "f"(x)); return y; }
__device__ __forceinline__ uint32_t ld_nc(const uint32_t* p) { uint32_t v; asm volatile("ld.global.nc.b32 %0,[%1];" : "=r"(v) : "l"(p)); return v; }
__device__ __forceinline__ uint2 ld_nc64(const uint2* p) { uint2 v; asm volatile("ld.global.nc.v2.b32 {%0,%1},[%2];" : "=r"(v.x), "=r"(v.y) : "l"(p)); return v; }
__device__ __forceinline__ unsigned ld_acq(const unsigned* p) { unsigned v; asm volatile("ld.acquire.gpu.global.u32 %0,[%1];" : "=r"(v) : "l"(p) : "memory"); return v; }
__device__ __forceinline__ unsigned ld_rlx(const unsigned* p) { unsigned v; asm volatile("ld.relaxed.gpu.global.u32 %0,[%1];" : "=r"(v) : "l"(p) : "memory"); return v; }
__device__ __forceinline__ uint2 ld_rlx64(const void* p) { uint2 v; asm volatile("{.reg .b64 t; ld.relaxed.gpu.global.b64 t,[%2]; mov.b64 {%0,%1},t;}" : "=r"(v.x), "=r"(v.y) : "l"(p) : "memory"); return v; }
__device__ __forceinline__ uint4 ld_rlx128(const void* p) {
    uint4 v;
    asm volatile("{.reg .b64 t,u; ld.relaxed.gpu.global.v2.b64 {t,u},[%4]; mov.b64 {%0,%1},t; mov.b64 {%2,%3},u;}" : "=r"(v.x), "=r"(v.y), "=r"(v.z), "=r"(v.w) : "l"(p) : "memory");
    return v;
}
__device__ __forceinline__ void st_rlx32(void* p, uint32_t x) { asm volatile("st.relaxed.gpu.global.u32 [%0],%1;" ::"l"(p), "r"(x) : "memory"); }
__device__ __forceinline__ void st_rlx64(void* p, uint32_t x, uint32_t y) { asm volatile("{.reg .b64 t; mov.b64 t,{%1,%2}; st.relaxed.gpu.global.b64 [%0],t;}" ::"l"(p), "r"(x), "r"(y) : "memory"); }
__device__ __forceinline__ void st_rlx128(void* p, uint4 v) {
    asm volatile("{.reg .b64 t,u; mov.b64 t,{%1,%2}; mov.b64 u,{%3,%4}; st.relaxed.gpu.global.v2.b64 [%0],{t,u};}" ::"l"(p), "r"(v.x), "r"(v.y), "r"(v.z), "r"(v.w) : "memory");
}
__device__ __forceinline__ uint32_t tagw(uint32_t w, uint32_t tag) { return (w & ~1u) | tag; }
__device__ __forceinline__ uint4 tag4(uint32_t x, uint32_t y, uint32_t z, uint32_t w, uint32_t tag) { return make_uint4(tagw(x, tag), y, tagw(z, tag), w); }
__device__ __forceinline__ uint32_t bad4(const uint4& v, uint32_t tag) { return (v.x ^ tag) | (v.z ^ tag); }
__device__ __forceinline__ void bar_named(int id, int n) { asm volatile("bar.sync %0,%1;" ::"r"(id), "r"(n) : "memory"); }

struct cf { float re, im; };
__device__ __forceinline__ cf cmul(cf a, cf b) { cf r; r.re = a.re * b.re - a.im * b.im; r.im = a.re * b.im + a.im * b.re; return r; }
__device__ __forceinline__ cf cexp_p(float arl, float ait, float p) {
    float mag = ex2(arl * p);
    float t = ait * p;
    t = (t - rintf(t)) * 6.283185307179586f;
    cf r; r.re = mag * __cosf(t); r.im = mag * __sinf(t);
    return r;
}

__device__ __forceinline__ void hedgehog2(const uint32_t* a, uint32_t wphi_addr, uint32_t (*out)[8]) {
    float p[2][2][4], mx[2][2];
#pragma unroll
    for (int h = 0; h < 2; h++) {
        uint32_t b[4];
        ldsm4t(b, wphi_addr + h * 512);
        float c0[4] = {0.f, 0.f, 0.f, 0.f}, c1[4] = {0.f, 0.f, 0.f, 0.f};
        mma16816(c0, a[4 * h], a[4 * h + 1], a[4 * h + 2], a[4 * h + 3], b[0], b[1]);
        mma16816(c1, a[4 * h], a[4 * h + 1], a[4 * h + 2], a[4 * h + 3], b[2], b[3]);
#pragma unroll
        for (int k = 0; k < 2; k++) {
            p[h][k][0] = c0[2 * k]; p[h][k][1] = c0[2 * k + 1]; p[h][k][2] = c1[2 * k]; p[h][k][3] = c1[2 * k + 1];
            mx[h][k] = fmaxf(fmaxf(p[h][k][0], p[h][k][1]), fmaxf(p[h][k][2], p[h][k][3]));
        }
    }
#pragma unroll
    for (int o = 1; o <= 2; o <<= 1)
#pragma unroll
        for (int h = 0; h < 2; h++)
#pragma unroll
            for (int k = 0; k < 2; k++) mx[h][k] = fmaxf(mx[h][k], __shfl_xor_sync(~0u, mx[h][k], o));
    const float L = 1.4426950408889634f;
    float pmin = 1.f;
#pragma unroll
    for (int h = 0; h < 2; h++)
#pragma unroll
        for (int k = 0; k < 2; k++) {
            const float m = -mx[h][k] * L;
            const float e0 = ex2(fmaf(p[h][k][0], L, m)), e1 = ex2(fmaf(p[h][k][1], L, m)), e2 = ex2(fmaf(p[h][k][2], L, m)), e3 = ex2(fmaf(p[h][k][3], L, m));
            const float p01 = e0 * e1, p23 = e2 * e3, pp = p01 * p23, r = rcp(pp), r01 = r * p23, r23 = r * p01;
            pmin = fminf(pmin, pp);
            out[h][k] = pack2(e0, e1); out[h][k + 2] = pack2(e2, e3);
            out[h][4 + k] = pack2(r01 * e1, r01 * e0); out[h][4 + k + 2] = pack2(r23 * e3, r23 * e2);
        }
    if (__builtin_expect(__any_sync(~0u, !(pmin > 1e-18f)), 0)) {
#pragma unroll
        for (int h = 0; h < 2; h++)
#pragma unroll
            for (int k = 0; k < 2; k++) {
                float m = fminf(fminf(p[h][k][0], p[h][k][1]), fminf(p[h][k][2], p[h][k][3]));
                m = fminf(m, __shfl_xor_sync(~0u, m, 1));
                m = fminf(m, __shfl_xor_sync(~0u, m, 2)) * L;
                out[h][4 + k] = pack2(ex2(fmaf(p[h][k][0], -L, m)), ex2(fmaf(p[h][k][1], -L, m)));
                out[h][4 + k + 2] = pack2(ex2(fmaf(p[h][k][2], -L, m)), ex2(fmaf(p[h][k][3], -L, m)));
            }
    }
}

__global__ void __launch_bounds__(384, 1)
fused_kernel(Scratch* __restrict__ scr, const bf16* __restrict__ logA, const bf16* __restrict__ Aim, const bf16* __restrict__ Cre,
             const bf16* __restrict__ Cim, const bf16* __restrict__ logdt, const bf16* __restrict__ Dskip, const bf16* __restrict__ wphi,
             const bf16* __restrict__ gatew, bf16* __restrict__ out,
             const __grid_constant__ CUtensorMap mx, const __grid_constant__ CUtensorMap mw, const __grid_constant__ CUtensorMap mwo) {
    extern __shared__ __align__(1024) uint8_t smem[];
    const uint32_t sb = s2u(smem);
    const int tid = threadIdx.x, warp = __shfl_sync(~0u, tid >> 5, 0), lane = tid & 31;
    const int g = lane >> 2, q = lane & 3, w4 = warp & 3;
    const int bi = blockIdx.x, bi_i = bi & 15, bi_j = bi >> 4;
    const uint32_t bar = sb + OFF_BAR;
    const int rot = (bi_j & 1) * 4;
    auto load_stage = [&](int kb) {
        const uint32_t b = bar + 8 * (BAR_FULL + (kb & 3)), d = sb + (kb & 3) * SLOT;
        const int kc = ((kb + rot) & 7) * 64;
        mbar_expect(b, SLOT);
        tma2d(d, &mx, kc, bi_i * 128, b);
        tma3d(d + 16384, &mw, bi_j * 64, kc, 0, b);
    };

    const int ch = bi * 4 + w4;
    uint2 pla, pai, pcr, pci; uint32_t pdt = 0, pds;
    if (warp >= 8) {
        pla = ld_nc64((const uint2*)logA + ch * 32 + lane); pai = ld_nc64((const uint2*)Aim + ch * 32 + lane);
        pcr = ld_nc64((const uint2*)Cre + ch * 32 + lane); pci = ld_nc64((const uint2*)Cim + ch * 32 + lane);
        pdt = ld_nc((const uint32_t*)logdt + (ch >> 1)); pds = ld_nc((const uint32_t*)Dskip + (ch >> 1));
    }
    unsigned done0 = ld_rlx(scr->done);
    if (tid == 0) {
        for (int s = 0; s < 4; s++) mbar_init(bar + 8 * (BAR_FULL + s), 1);
        asm volatile("fence.mbarrier_init.release.cluster;" ::: "memory");
#pragma unroll 1
        for (int s = 0; s < 4; s++) load_stage(s);
        STAMP(11);
    } else if (tid == 32) {
        if (sb & 1023) __trap();
        for (int s = 0; s < 5; s++) sts32(bar + OFF_CNT + 4 * s, 0);
        mbar_init(bar + 8 * BAR_WPHI, 1); mbar_init(bar + 8 * BAR_WO, 2); mbar_init(bar + 8 * BAR_XT, 8); mbar_init(bar + 8 * BAR_DONE, 8);
        mbar_init(bar + 8 * BAR_WO2, 1);
        asm volatile("fence.mbarrier_init.release.cluster;" ::: "memory");
        mbar_expect(bar + 8 * BAR_WPHI, 3072);
        bulk_g2s(sb + OFF_GW, gatew, 1024, bar + 8 * BAR_WPHI);
        bulk_g2s(sb + OFF_WPHI, wphi + bi_j * 1024, 2048, bar + 8 * BAR_WPHI);
    } else if (tid == 64) {
        asm volatile("prefetch.tensormap [%0];" ::"l"(&mw) : "memory");
    }
    const uint32_t buf = sb + OFF_BUF + w4 * BUF_STRIDE, k3 = sb + OFF_K3 + w4 * K3_STRIDE;
    if (warp >= 8) {
#pragma unroll
        for (int v = 0; v < 3; v++) if (v * 32 + lane < K3_STRIDE / 16) sts128(k3 + (v * 32 + lane) * 16, 0, 0, 0, 0);
    }
    __syncthreads();
    asm volatile("" : "+r"(pdt), "+r"(done0)::"memory");
    const unsigned epoch1 = (done0 >> 7) + 1u;
    const uint32_t tag = epoch1 & 1u;

    if (warp < 8) {
        const int wg = warp >> 2;
        if (warp == 0) STAMP(21);
        float acc[96];
        const int grow = bi_j * 16 + warp * 2 + (lane >> 4);
        const uint32_t gx_a = grow * 128 + ((((lane & 15) >> 1) ^ (grow & 7)) << 4) + (lane & 1) * 8;
        const int srow = warp * 16 + (lane & 15);
        const uint32_t srow_a = srow * 128;
        const int sx = srow & 7, shi = lane >> 4;
        auto last_of_8 = [&](int c) {
            unsigned old;
            asm volatile("atom.acq_rel.cta.shared.add.u32 %0,[%1],1;" : "=r"(old) : "r"(bar + OFF_CNT + 4 * c) : "memory");
            return (old & 7) == 7;
        };
        const int qq = (bi_i & 2) + ((lane >> 1) & 1);
        const int kvf_n = warp < 4 ? 8 : ((warp == 4 && (bi_i & 1) == 0) ? 4 : 0);
        uint2* kvf_dst = (uint2*)(scr->kvf + (bi_j * 4 + (bi_i >> 2)) * 68) +
                         (warp == 4 ? (64 + qq) * 2 + (lane & 1) : ((bi_i & 3) * 8 + w4 * 2 + (lane & 1)) * 4 + (lane >> 1));
        float gsum = 0.f;
#pragma unroll
        for (int r = 0; r < 96; r++) acc[r] = 0.f;
        fence_regs<96>(acc);
        const uint64_t da0 = mkdesc(sb + wg * 8192, 16, 1024), db0 = mkdesc(sb + 16384, 8192, 1024);
        {
            const uint32_t old = tag ^ 1u;
            const uint4 z4 = make_uint4(old, 0, old, 0);
            uint4* kvp = scr->kvp + bi * 544 + wg * 272;
            if (w4 < 2) {
#pragma unroll
                for (int f = 0; f < 4; f++) st_rlx128(kvp + w4 * 136 + lane + f * 32, z4);
            } else if (w4 == 2 && lane < 4) {
#pragma unroll
                for (int f = 0; f < 4; f++) st_rlx128(kvp + (f >> 1) * 136 + 128 + (f & 1) * 4 + lane, z4);
            }
            if (lane < kvf_n) st_rlx64(kvf_dst, old, 0);
            if (lane >= 30) st_rlx128(scr->o + ((bi_i * 8 + warp) * 32 + bi_j * 4 + 3) * 32 + lane, z4);
            if (lane < 8) st_rlx32(scr->g + (bi_i * 64 + bi_j * 8 + warp) * 8 + lane, old);
        }
        mbar_wait(bar + 8 * BAR_WPHI, 0);
#pragma unroll 1
        for (int kb = 0; kb < 8; kb++) {
            const int s = kb & 3;
            const uint64_t da = da0 + s * (SLOT >> 4), db = db0 + s * (SLOT >> 4);
            mbar_wait(bar + 8 * (BAR_FULL + s), kb >> 2);
            if (kb == 0 && warp == 0) STAMP(0);
            wg_fence();
#pragma unroll
            for (int k = 0; k < 4; k++) wgmma192(acc, da + 2 * k, db + 128 * k);
            wg_commit();
            wg_wait<1>();
            __syncwarp();
            if (lane == 0 && kb > 0 && kb < 7) {
                const int ps = (kb - 1) & 3;
                if (last_of_8(ps)) {
                    if (kb < 5) load_stage(kb + 3);
                    else {
                        mbar_expect(bar + 8 * BAR_WO, 32768);
                        tma2d(sb + ps * SLOT, &mwo, (bi_j & 3) * 128 + ps * 64, 0, bar + 8 * BAR_WO);
                    }
                }
            }
            __syncwarp();
            const uint32_t st = sb + s * SLOT;
            if (kb == (bi_j >> 1)) {
                uint32_t* xt = (uint32_t*)scr->xt + ((kb + rot) * 16 + (g >> 2)) * 4096 + (bi_i * 16 + warp * 2) * 16 + (g & 3) * 4 + q;
#pragma unroll
                for (int cb = 0; cb < 8; cb += 2) {
                    uint32_t r[4];
                    ldsm4t(r, st + srow_a + (((cb + shi) ^ sx) << 4));
                    xt[cb * 8192] = r[0]; xt[cb * 8192 + 16] = r[1]; xt[cb * 8192 + 8192] = r[2]; xt[cb * 8192 + 8192 + 16] = r[3];
                }
                __syncwarp();
                if (lane == 0) mbar_arrive(bar + 8 * BAR_XT);
            }
            {
                uint32_t x0, x1, w0, w1;
                asm volatile("ld.shared.v2.b32 {%0,%1},[%2];" : "=r"(x0), "=r"(x1) : "r"(st + gx_a) : "memory");
                asm volatile("ld.shared.v2.b32 {%0,%1},[%2];" : "=r"(w0), "=r"(w1) : "r"(sb + OFF_GW + ((kb + rot) & 7) * 128 + (lane & 15) * 8) : "memory");
                const uint32_t p0 = hmul2(x0, w0), p1 = hmul2(x1, w1);
                gsum += (bf_lo(p0) + bf_hi(p0)) + (bf_lo(p1) + bf_hi(p1));
            }
        }
        wg_wait<0>();
        fence_regs<96>(acc);
        __syncwarp();
        if (lane == 0) mbar_arrive(bar + 8 * BAR_DONE);
        if (warp == 0) STAMP(1);
        uint32_t in[32], va[16];
#pragma unroll
        for (int r = 0; r < 16; r++) {
            in[r] = pack2(acc[32 + 2 * r], acc[32 + 2 * r + 1]);
            in[16 + r] = pack2(acc[2 * r], acc[2 * r + 1]);
            va[r] = pack2(acc[64 + 2 * r], acc[64 + 2 * r + 1]);
        }
        const uint32_t wphi_a = sb + OFF_WPHI + (lane & 15) * 32 + (lane >> 4) * 16;
        uint32_t pq[4][8];
#pragma unroll 1
        for (int it = 0; it < 4; it++) {
            hedgehog2(in, wphi_a + (it & 1) * 1024, pq + 2);
#pragma unroll
            for (int r = 0; r < 24; r++) in[r] = in[r + 8];
            if (it < 2) {
#pragma unroll
                for (int hs = 0; hs < 4; hs++) {
                    float c[4] = {0.f, 0.f, 0.f, 0.f};
                    uint32_t* o = pq[2 + (hs >> 1)] + 4 * (hs & 1);
                    mma16816(c, o[0], o[1], o[2], o[3], 0x3f803f80u, 0x3f803f80u);
                    const float r0 = rcp(c[0]), r1 = rcp(c[2]);
                    const uint32_t s0 = pack2(r0, r0), s1 = pack2(r1, r1);
                    o[0] = hmul2(o[0], s0); o[1] = hmul2(o[1], s1); o[2] = hmul2(o[2], s0); o[3] = hmul2(o[3], s1);
                }
                if (it == 0) mbar_wait(bar + 8 * BAR_DONE, 0);
                const uint32_t pt = sb + OFF_P + it * 16384 + srow_a, vt = sb + OFF_V + it * 16384 + srow_a;
#pragma unroll
                for (int hl = 0; hl < 2; hl++) {
                    stsm4(pt + (((4 * hl + shi) ^ sx) << 4), pq[2 + hl][0], pq[2 + hl][1], pq[2 + hl][2], pq[2 + hl][3]);
                    stsm4(pt + (((4 * hl + 2 + shi) ^ sx) << 4), pq[2 + hl][4], pq[2 + hl][5], pq[2 + hl][6], pq[2 + hl][7]);
                    stsm4(vt + (((2 * hl + shi) ^ sx) << 4), va[4 * hl], va[4 * hl + 1], va[4 * hl + 2], va[4 * hl + 3]);
                }
                if (lane < 16) sts128(vt + ((4 ^ sx) << 4), 0x3f803f80u, 0x3f803f80u, 0x3f803f80u, 0x3f803f80u);
#pragma unroll
                for (int r = 0; r < 8; r++) va[r] = va[r + 8];
            }
            if (it == 1) {
                asm volatile("fence.proxy.async.shared::cta;" ::: "memory");
                bar_named(1, 256);
                if (warp == 0) STAMP(2);
                float d[32];
                const uint64_t dv = mkdesc(sb + OFF_V + wg * 16384, 16, 1024), dp = mkdesc(sb + OFF_P + wg * 16384, 16, 1024);
                wg_fence();
#pragma unroll
                for (int k = 0; k < 8; k++) wgmma64_tt(d, dv + 128 * k, dp + 128 * k, k != 0);
                wg_commit();
                wg_wait<0>();
                fence_regs<32>(d);
                uint4* kvp = scr->kvp + bi * 544 + wg * 272;
                if (w4 < 2) {
                    uint32_t e[16];
#pragma unroll
                    for (int r = 0; r < 16; r++) e[r] = __float_as_uint(w4 ? d[16 + r] : d[r]);
                    uint4* p = kvp + w4 * 136 + lane;
#pragma unroll
                    for (int ks = 0; ks < 2; ks++)
#pragma unroll
                        for (int nt = 0; nt < 2; nt++)
                            st_rlx128(p + (ks * 2 + nt) * 32, tag4(e[8 * ks + 2 * nt], e[8 * ks + 2 * nt + 1], e[8 * ks + 4 + 2 * nt], e[8 * ks + 4 + 2 * nt + 1], tag));
                } else if (w4 == 2 && lane < 4) {
#pragma unroll
                    for (int hl = 0; hl < 2; hl++)
#pragma unroll
                        for (int ks = 0; ks < 2; ks++)
                            st_rlx128(kvp + hl * 136 + 128 + ks * 4 + lane, tag4(__float_as_uint(d[16 * hl + 8 * ks]), __float_as_uint(d[16 * hl + 8 * ks + 1]),
                                                                                __float_as_uint(d[16 * hl + 8 * ks + 4]), __float_as_uint(d[16 * hl + 8 * ks + 5]), tag));
                }
                if (warp == 0) STAMP(3);
            }
            if (it == 2) {
#pragma unroll
                for (int r = 0; r < 8; r++) { pq[0][r] = pq[2][r]; pq[1][r] = pq[3][r]; }
                if (warp == 0) STAMP(12);
                if (kvf_n) {
                    const bool zw = warp == 4;
                    const uint4* src = scr->kvp + bi_j * (16 * 544) + (bi_i >> 2) * 136 +
                                       (zw ? (lane >> 2) * (2 * 544) + 128 + (lane & 1) * 4 + qq
                                           : (lane >> 3) * (4 * 544) + ((lane >> 1) & 3) * 32 + (bi_i & 3) * 8 + warp * 2 + (lane & 1));
                    const int s23 = zw ? 0 : 2 * 544;
                    uint4 v[4];
                    int n = 0;
#pragma unroll 1
                    while (true) {
                        v[0] = ld_rlx128(src); v[1] = ld_rlx128(src + 544); v[2] = ld_rlx128(src + s23); v[3] = ld_rlx128(src + s23 + 544);
                        if (!__any_sync(~0u, (bad4(v[0], tag) | bad4(v[1], tag) | bad4(v[2], tag) | bad4(v[3], tag)) & 1)) break;
                        if (++n > SPIN_LIMIT) break;
                    }
                    float f[4];
                    f[0] = __uint_as_float(v[2].x) + __uint_as_float(v[3].x); f[1] = __uint_as_float(v[2].y) + __uint_as_float(v[3].y);
                    f[2] = __uint_as_float(v[2].z) + __uint_as_float(v[3].z); f[3] = __uint_as_float(v[2].w) + __uint_as_float(v[3].w);
                    float e0 = __uint_as_float(v[0].x) + __uint_as_float(v[1].x), e1 = __uint_as_float(v[0].y) + __uint_as_float(v[1].y);
                    float e2 = __uint_as_float(v[0].z) + __uint_as_float(v[1].z), e3 = __uint_as_float(v[0].w) + __uint_as_float(v[1].w);
                    if (zw) {
                        e0 = __shfl_xor_sync(~0u, f[0], 4); e1 = __shfl_xor_sync(~0u, f[1], 4);
                        e2 = __shfl_xor_sync(~0u, f[2], 4); e3 = __shfl_xor_sync(~0u, f[3], 4);
                    }
                    f[0] += e0; f[1] += e1; f[2] += e2; f[3] += e3;
#pragma unroll
                    for (int o = 8; o <= 16; o <<= 1)
#pragma unroll
                        for (int r = 0; r < 4; r++) f[r] += __shfl_xor_sync(~0u, f[r], o);
                    if (lane < kvf_n) st_rlx64(kvf_dst, tagw(pack2(f[0], f[1]), tag), pack2(f[2], f[3]));
                }
                __syncwarp();
                if (lane == 0 && last_of_8(4)) {
                    mbar_expect(bar + 8 * BAR_WO2, 65536);
                    tma2d(sb + 2 * SLOT, &mwo, (bi_j & 3) * 128, 256, bar + 8 * BAR_WO2);
                    tma2d(sb + OFF_V, &mwo, (bi_j & 3) * 128 + 64, 256, bar + 8 * BAR_WO2);
                }
                __syncwarp();
                if (warp == 0) STAMP(13);
#pragma unroll
                for (int o = 1; o < 16; o <<= 1) gsum += __shfl_xor_sync(~0u, gsum, o);
                const float gate = bf_round(rcp(1.0f + ex2(-1.4426950408889634f * bf_round(gsum))));
                const uint32_t gv = __shfl_sync(~0u, __float_as_uint(gate) | tag, (lane & 4) * 4);
                if (lane < 8) st_rlx32(scr->g + (bi_i * 64 + bi_j * 8 + warp) * 8 + lane, gv);
            }
        }
        if (warp == 0) STAMP(4);
        {
            {
                const uint4* kp = scr->kvf + bi_j * 272 + tid;
                uint4 v0, v1;
                int n = 0;
#pragma unroll 1
                while (true) {
                    v0 = ld_rlx128(kp); v1 = ld_rlx128(kp + (tid < 16 ? 256 : 0));
                    if (!__any_sync(~0u, (bad4(v0, tag) | bad4(v1, tag)) & 1)) break;
                    if (++n > SPIN_LIMIT) break;
                }
                sts128(sb + OFF_KVF + tid * 16, v0.x, v0.y, v0.z, v0.w);
                if (tid < 16) sts128(sb + OFF_KVF + 4096 + tid * 16, v1.x, v1.y, v1.z, v1.w);
                bar_named(1, 256);
            }
            uint4 kf[4][3];
#pragma unroll
            for (int hh = 0; hh < 4; hh++) {
                const uint32_t a = sb + OFF_KVF + hh * 1088;
                kf[hh][0] = lds128(a + lane * 32); kf[hh][1] = lds128(a + lane * 32 + 16); kf[hh][2] = lds128(a + 1024 + q * 16);
            }
            if (warp == 0) STAMP(5);
            uint4 own[4];
#pragma unroll
            for (int hh = 0; hh < 4; hh++) {
                float c[6][4];
#pragma unroll
                for (int t = 0; t < 6; t++) { c[t][0] = c[t][1] = c[t][2] = c[t][3] = 0.f; }
                const uint32_t* a = pq[hh];
                const bool od = g & 1;
                mma16816(c[0], a[0], a[1], a[2], a[3], od ? 0x3f803f80u : kf[hh][2].x, od ? 0x3f803f80u : kf[hh][2].y);
                mma16816(c[1], a[4], a[5], a[6], a[7], od ? 0x3f803f80u : kf[hh][2].z, od ? 0x3f803f80u : kf[hh][2].w);
                mma16816(c[2], a[0], a[1], a[2], a[3], kf[hh][0].x, kf[hh][0].y);
                mma16816(c[3], a[0], a[1], a[2], a[3], kf[hh][0].z, kf[hh][0].w);
                mma16816(c[4], a[4], a[5], a[6], a[7], kf[hh][1].x, kf[hh][1].y);
                mma16816(c[5], a[4], a[5], a[6], a[7], kf[hh][1].z, kf[hh][1].w);
                uint32_t w[4];
#pragma unroll
                for (int k = 0; k < 2; k++) {
                    const float rho = c[0][2 * k + 1] * rcp(c[1][2 * k + 1]);
                    const float r = rcp(fmaf(c[0][2 * k + 1], 1e-6f, fmaf(rho, c[1][2 * k], c[0][2 * k]))), rr = r * rho;
                    w[k] = pack2(fmaf(c[4][2 * k], rr, c[2][2 * k] * r), fmaf(c[4][2 * k + 1], rr, c[2][2 * k + 1] * r));
                    w[2 + k] = pack2(fmaf(c[5][2 * k], rr, c[3][2 * k] * r), fmaf(c[5][2 * k + 1], rr, c[3][2 * k + 1] * r));
                }
                own[hh] = tag4(w[0], w[1], w[2], w[3], tag);
            }
            uint4* og = scr->o + ((bi_i * 8 + warp) * 32 + bi_j * 4) * 32 + lane;
#pragma unroll
            for (int hh = 0; hh < 4; hh++) st_rlx128(og + hh * 32, own[hh]);
        }
        if (warp == 0) STAMP(6);
        float oc[64];
        const int slab = bi_i * 8 + (bi_j >> 2) * 4 + w4;
        const uint8_t* yb = (const uint8_t*)scr->y + (size_t)((bi_j & 3) * 32 + wg * 16 + (q >> 1)) * 16384 + slab * 128 + g * 16 + (q & 1) * 8;
        const unsigned* gp = scr->g + (slab * 8 + (g >> 1)) * 8 + (g & 1) * 4;
        uint2 yv[8]; unsigned g0, g1;
        {
            const uint4* osrc = scr->o + (slab * 32 + wg * 16) * 32 + lane;
            uint4 fr[16];
            const unsigned* probe = (const unsigned*)(osrc - lane + ((lane & 3) * 4 + 3) * 32 + 31) + 2;
            {
                unsigned miss = ~0u;
                int n = 0;
#pragma unroll
                for (int s = 0; s < 4; s++) {
#pragma unroll 1
                    while ((miss >> s) & 1) { miss = __ballot_sync(~0u, (ld_rlx(probe) ^ tag) & 1); if (++n > SPIN_LIMIT) break; }
#pragma unroll
                    for (int k = 4 * s; k < 4 * s + 4; k++) fr[k] = ld_rlx128(osrc + k * 32);
                }
            }
            if (warp == 0) STAMP(14);
            mbar_wait(bar + 8 * (wg ? BAR_WO2 : BAR_WO), 0);
            const uint64_t dw = mkdesc(sb + wg * 2 * SLOT, wg ? 32768 : SLOT, 1024);
#pragma unroll
            for (int s = 0; s < 4; s++) {
                int n = 0;
#pragma unroll 1
                while (__builtin_expect(__any_sync(~0u, (bad4(fr[4 * s], tag) | bad4(fr[4 * s + 1], tag) | bad4(fr[4 * s + 2], tag) | bad4(fr[4 * s + 3], tag)) & 1), 0)) {
#pragma unroll
                    for (int k = 4 * s; k < 4 * s + 4; k++) fr[k] = ld_rlx128(osrc + k * 32);
                    if (++n > SPIN_LIMIT) break;
                }
                wg_fence();
#pragma unroll
                for (int hh = 0; hh < 4; hh++) wgmma128_rs(oc, fr[4 * s + hh], dw + 128 * (4 * s + hh), (s | hh) != 0);
                wg_commit();
                if (s == 1) {
                    wg_wait<1>();
#pragma unroll
                    for (int nt = 0; nt < 8; nt++) yv[nt] = ld_rlx64(yb + nt * 32768);
                    g0 = ld_rlx(gp); g1 = ld_rlx(gp + 32);
                }
            }
            if (warp == 0) STAMP(7);
            {
                const unsigned* yprobe = scr->yflag + ((bi_j & 3) * 32 + wg * 16 + (lane & 15)) * 8;
                int n = 0;
#pragma unroll 1
                while (true) {
                    uint32_t bad = (g0 ^ tag) | (g1 ^ tag);
#pragma unroll
                    for (int nt = 0; nt < 8; nt++) bad |= yv[nt].x ^ tag;
                    if (!__any_sync(~0u, bad & 1)) break;
#pragma unroll 1
                    while (__any_sync(~0u, (ld_rlx(yprobe) ^ tag) & 1)) { if (++n > SPIN_LIMIT) break; }
#pragma unroll
                    for (int nt = 0; nt < 8; nt++) yv[nt] = ld_rlx64(yb + nt * 32768);
                    g0 = ld_rlx(gp); g1 = ld_rlx(gp + 32);
                    if (++n > SPIN_LIMIT) break;
                }
            }
            if (warp == 0) STAMP(28);
            wg_wait<0>();
            fence_regs<64>(oc);
        }
        {
            bar_named(3 + wg, 128);
            const uint32_t xw = sb + wg * 2 * SLOT + (tid & 127) * 16, xr = sb + (wg ^ 1) * 2 * SLOT + (tid & 127) * 16;
#pragma unroll
            for (int r = 0; r < 8; r++) {
                const float* o = oc + 4 * r;
                sts128(xw + r * 2048, __float_as_uint(wg ? o[0] : o[32]), __float_as_uint(wg ? o[1] : o[33]), __float_as_uint(wg ? o[2] : o[34]), __float_as_uint(wg ? o[3] : o[35]));
            }
#pragma unroll
            for (int r = 0; r < 32; r++) oc[r] = wg ? oc[32 + r] : oc[r];
            bar_named(1, 256);
            if (warp == 0) STAMP(8);
            const float ga = bf_hi(g0), gb = bf_hi(g1);
            const float ha = bf_round(1.0f - ga), hb = bf_round(1.0f - gb);
            uint32_t w[8][2];
#pragma unroll
            for (int nt = 0; nt < 8; nt++) {
                const uint4 p = lds128(xr + nt * 2048);
                w[nt][0] = pack2(fmaf(ga, oc[4 * nt] + __uint_as_float(p.x), ha * bf_lo(yv[nt].x)), fmaf(ga, oc[4 * nt + 1] + __uint_as_float(p.y), ha * bf_hi(yv[nt].x)));
                w[nt][1] = pack2(fmaf(gb, oc[4 * nt + 2] + __uint_as_float(p.z), hb * bf_lo(yv[nt].y)), fmaf(gb, oc[4 * nt + 3] + __uint_as_float(p.w), hb * bf_hi(yv[nt].y)));
            }
            const uint32_t ob = sb + wg * 2 * SLOT + 16384 + w4 * 2048;
#pragma unroll
            for (int nt = 0; nt < 8; nt += 2)
                stsm4(ob + (lane & 15) * 128 + (((nt + shi) ^ (lane & 7)) << 4), w[nt][0], w[nt][1], w[nt + 1][0], w[nt + 1][1]);
            __syncwarp();
            bf16* op = out + (size_t)(slab * 16) * 512 + (bi_j & 3) * 128 + wg * 64 + (lane & 7) * 8;
#pragma unroll
            for (int it = 0; it < 4; it++) {
                const int r = it * 4 + (lane >> 3);
                uint4 v = lds128(ob + r * 128 + (((lane & 7) ^ (r & 7)) << 4));
                *(uint4*)(op + r * 512) = v;
            }
        }
        if (warp == 0) STAMP(10);
    } else {
        const int st = tid - 256;
        float kc[24];
        const int brow = (buf >> 7) & 7;
#pragma unroll
        for (int t = 0; t < 24; t++) kc[t] = 0.f;
        fence_regs<24>(kc);
        {
            const float dt = bf_round(expf((ch & 1) ? bf_hi(pdt) : bf_lo(pdt)));
#pragma unroll 1
            for (int it = 0; it < KG_ROUNDS; it++) {
                const int sh = (it & 1) * 16;
                auto pick = [&](const uint2& v) { return __uint_as_float(((it & 2 ? v.y : v.x) >> sh) << 16); };
                const float ea = bf_round(expf(pick(pla)));
                const float arl = (-ea * dt) * 1.4426950408889634f, ait = (pick(pai) * dt) * 0.15915494309189535f;
                cf C2; C2.re = 2.0f * (pick(pcr) * dt); C2.im = 2.0f * (pick(pci) * dt);
                const cf z1 = cexp_p(arl, ait, 1.0f), z128 = cexp_p(arl, ait, 128.0f);
                cf z8 = cexp_p(arl, ait, 8.0f); z8.im = -z8.im;
                const uint32_t lp = buf + lane * 4;
                auto put = [&](int row, const cf& v) { sts32((lp ^ (((row + brow) & 7) << 4)) + row * 128, pack2(v.re, v.im)); };
                {
                    const cf z16 = cmul(z8, z8);
                    cf e; e.re = 1.f; e.im = 0.f;
                    cf o = z8;
                    put(0, e); put(1, o);
                    e = z16; put(2, e);
#pragma unroll
                    for (int b = 3; b < 16; b += 2) {
                        o = cmul(o, z16); put(b, o);
                        if (b + 1 < 16) { e = cmul(e, z16); put(b + 1, e); }
                    }
                }
                cf h[8];
                h[0] = C2; put(16, h[0]);
                {
                    const cf z2 = cmul(z1, z1);
                    h[1] = cmul(h[0], z1);
#pragma unroll
                    for (int r = 2; r < 8; r++) h[r] = cmul(h[r - 2], z2);
#pragma unroll
                    for (int r = 1; r < 8; r++) put(16 + r, h[r]);
                }
#pragma unroll
                for (int r = 0; r < 8; r++) { h[r] = cmul(h[r], z128); put(24 + r, h[r]); }
#pragma unroll
                for (int al = 0; al < 2; al++)
#pragma unroll
                    for (int r = 0; r < 4; r++) { h[2 * r] = cmul(h[2 * r], z128); put(32 + al * 4 + r, h[2 * r]); }
#pragma unroll
                for (int al = 0; al < 4; al++)
#pragma unroll
                    for (int r = 0; r < 2; r++) { h[4 * r] = cmul(h[4 * r], z128); put(40 + al * 2 + r, h[4 * r]); }
#pragma unroll
                for (int al = 0; al < 9; al++) { h[0] = cmul(h[0], z128); put(48 + al, h[0]); }
                asm volatile("fence.proxy.async.shared::cta;" ::: "memory");
                bar_named(2, 128);
                uint32_t la[4][4];
#pragma unroll
                for (int ks = 0; ks < 4; ks++) ldsm4(la[ks], buf + (lane & 15) * 128 + (((2 * ks + (lane >> 4)) ^ ((lane + brow) & 7)) << 4));
                const uint64_t dh = mkdesc(sb + OFF_BUF + 2048, 16, 1024);
#pragma unroll
                for (int c = 0; c < 4; c++) {
                    uint32_t a[4][4];
#pragma unroll
                    for (int r = 0; r < 16; r++) a[r >> 2][r & 3] = (c == w4) ? la[r >> 2][r & 3] : 0u;
                    wg_fence();
#pragma unroll
                    for (int ks = 0; ks < 4; ks++) wgmma48_rs(kc, a[ks][0], a[ks][1], a[ks][2], a[ks][3], dh + c * (BUF_STRIDE >> 4) + 2 * ks);
                    wg_commit();
                }
                wg_wait<0>();
                fence_regs<24>(kc);
                bar_named(2, 128);
            }
        }
        if (warp == 8) STAMP(22);
        if (warp == 8) {
            mbar_wait(bar + 8 * BAR_XT, 0);
            if (lane == 0) asm volatile("red.release.gpu.global.add.u32 [%0],8;" ::"l"(scr->xcnt + ((bi_j >> 1) + rot) * 32) : "memory");
        }
        if (lane == 0) {
            int n = 0;
#pragma unroll 1
            while ((int)(ld_acq(scr->xcnt + bi_j * 32) - (epoch1 << 7)) < 0) { __nanosleep(200); if (++n > SPIN_LIMIT) break; }
        }
        __syncwarp();
        if (warp == 8) STAMP(15);
        uint4 ur[8];
#pragma unroll
        for (int v = 0; v < 8; v++) ur[v] = __ldcg(scr->xt + bi * 1024 + st + 128 * v);
#pragma unroll
        for (int v = 0; v < 3; v++) if (v * 32 + lane < U_PAD / 16) sts128(sb + OFF_U + w4 * U_STRIDE + (v * 32 + lane) * 16, 0, 0, 0, 0);
        if (st < 8) st_rlx32(scr->yflag + bi * 8 + st, tag ^ 1u);
#pragma unroll
        for (int v = 0; v < 8; v++) {
            const uint32_t a = sb + OFF_U + (st & 3) * U_STRIDE + U_PAD + ((st >> 2) + 32 * v) * 16;
            sts128(a ^ ((a >> 3) & 0x70), ur[v].x, ur[v].y, ur[v].z, ur[v].w);
        }
        if (warp == 8) STAMP(16);
        bar_named(2, 128);
        if (lane < 14) sts128(buf + (lane >= 7 ? W3_OFF - 112 : 0) + lane * 16, 0, 0, 0, 0);
        {
            const uint32_t u0 = sb + OFF_U + w4 * U_STRIDE + U_PAD + lane * 16;
#pragma unroll 1
            for (int r2 = 0; r2 < 3; r2++) {
#pragma unroll
                for (int hf = 0; hf < 2; hf++) {
                    const int rho = 2 * r2 + hf, ci = lane + 32 * rho;
                    uint4 e4[4];
#pragma unroll
                    for (int v = 1; v < 4; v++) { const uint32_t a = u0 + rho * 512 + (v - 3) * 16; e4[v] = lds128(a ^ ((a >> 3) & 0x70)); }
                    float S[29];
                    const uint32_t* ew = (const uint32_t*)e4;
                    S[13] = 0.f;
#pragma unroll
                    for (int k = 14; k <= 28; k++) S[k] = S[k - 1] + ((k & 1) ? bf_hi(ew[k >> 1]) : bf_lo(ew[k >> 1]));
                    auto win = [&](int lo, int hi, uint32_t a) {
                        sts128(a, pack2(S[hi] - S[lo - 1], S[hi + 1] - S[lo]), pack2(S[hi + 2] - S[lo + 1], S[hi + 3] - S[lo + 2]),
                               pack2(S[hi + 4] - S[lo + 3], S[hi + 5] - S[lo + 4]), pack2(S[hi + 6] - S[lo + 5], S[hi + 7] - S[lo + 6]));
                    };
                    win(14, 18, buf + W5_OFF + 112 + ci * 16); win(19, 21, buf + W3_OFF + 112 + ci * 16);
                }
            }
        }
        if (warp == 8) STAMP(24);
        mbar_wait(bar + 8 * BAR_WO, 0);
        const uint32_t kt = sb + kt_off(w4);
#pragma unroll
        for (int v = 0; v < 8; v++) if (v * 32 + lane < KT_BYTES / 16) sts128(kt + (v * 32 + lane) * 16, 0, 0, 0, 0);
        __syncwarp();
        if (lane == 0) kc[4 * 0 + 0] += (ch & 1) ? bf_hi(pds) : bf_lo(pds);
#pragma unroll
        for (int i = 0; i < 2; i++) {
            const int be = g + 8 * i;
#pragma unroll
            for (int t = 0; t < 2; t++) {
                const uint32_t a = kt + (64 + 128 * t + 8 * be + 2 * q) * 4;
                const uint32_t w = pack2(kc[4 * t + 2 * i + 1], kc[4 * t + 2 * i]);
                sts32(a + 4, w); sts16(a, w >> 16); sts16(a + 10, w);
            }
            {
                const int p = 256 + 128 * (q >> 1) + 8 * be + 4 * (q & 1);
                const uint32_t a = kt + (64 + p) * 4;
                const uint32_t w = pack2(kc[4 * 2 + 2 * i + 1], kc[4 * 2 + 2 * i]);
                const uint32_t aa = (w >> 16) | (w & 0xffff0000u);
                if (p != 256) { sts16(a - 4, aa); sts32(a, aa); } else sts16(a, aa);
                sts32(a + 4, aa); sts32(a + 8, w); sts16(a + 14, w);
            }
            {
                const int k = 64 + 16 * q + be;
                const uint32_t w = pack2(kc[4 * 3 + 2 * i], kc[4 * 3 + 2 * i + 1]);
                if (k != 64) sts16(kt + KT_E2 + (k - 1) * 2, w);
                else {
                    const uint32_t a = kt + (64 + 511) * 4, aa = (w << 16) | (w & 0xffffu);
                    sts16(a, w); sts32(a + 4, aa); sts32(a + 8, aa); sts32(a + 12, aa); sts16(a + 18, w);
                }
                sts16(kt + KT_E2 + KT_E2O + k * 2, w >> 16);
            }
#pragma unroll
            for (int b = 0; b < 2; b++) {
                const int k = 64 + 8 * (2 * q + b) + (be >> 1);
                const uint32_t w = pack2(kc[4 * 4 + 2 * i + b], 0.f);
                const bool k1024 = !(be & 1) && k == 64;
                const uint32_t a = k3 + (k1024 ? 188 + 64 : ((be & 1) ? 94 + k : k - 1)) * 4 - 34 * 4;
                sts16(a, w);
                if (!((be & 1) && k == 127)) sts16(a + 6, w);
                if (k1024) sts16(kt + KT_E2 + 127 * 2, w);
            }
        }
        if (lane == 0) sts16(k3 + (127 - 34) * 4, pack2(kc[4 * 5 + 0], 0.f));
        asm volatile("fence.proxy.async.shared::cta;" ::: "memory");
        bar_named(2, 128);
        if (warp == 8) STAMP(17);
        mbar_wait(bar + 8 * BAR_DONE, 0);
        uint32_t yw[2][16];
#pragma unroll 1
        for (int p = 0; p < 2; p++) {
            uint32_t sp = sb, ln = lane;
            asm volatile("" : "+r"(sp), "+r"(ln));
            const int g = ln >> 2, q = ln & 3;
            float y[2][16];
#pragma unroll
            for (int c = 0; c < 2; c++) {
#pragma unroll
                for (int r = 0; r < 16; r++) y[c][r] = 0.f;
                fence_regs<16>(y[c]);
            }
            const uint32_t ktp = sp + OFF_SP0 + p * SLOT;
            {
                uint32_t Q[3][4][4];
                uint32_t ka = ktp + (64 - 48 + 16 * w4 + g - 2 * q) * 4;
                const uint32_t wa = sp + OFF_BUF + 2 * p * BUF_STRIDE + (15 - (ln >> 4) * 8 - (ln & 7) + 2 * w4 + ((ln >> 3) & 1)) * 16;
                uint64_t dd = mkdesc(sp + OFF_U + 2 * p * U_STRIDE + U_PAD + 96, 16, 1024);
                int s1 = U_STRIDE >> 4, s2 = -2, sg = -4;
                auto ldq = [&](uint32_t (*qd)[4], bool direct) {
                    if (direct) {
#pragma unroll
                        for (int c = 0; c < 2; c++) {
                            const uint32_t a = ka + c * 4096;
                            qd[c][0] = lds32(a); qd[c][1] = lds32(a + 32); qd[c][2] = lds32(a - 32); qd[c][3] = qd[c][0];
                            qd[c + 2][0] = lds32(a + 64); qd[c + 2][1] = lds32(a + 96); qd[c + 2][2] = qd[c][1]; qd[c + 2][3] = qd[c + 2][0];
                        }
                        ka += 128;
                    } else {
#pragma unroll
                        for (int c = 0; c < 4; c++) ldsm4t(qd[c], ka + (c & 1) * BUF_STRIDE + (c >> 1) * W3_OFF);
                        ka += 256;
                    }
                };
                ldq(Q[0], true);
#pragma unroll 1
                for (int it = 0; it < 10; it++) {
                    if (it == 6) {
                        dd = (uint64_t)(((ktp + KT_E2 - 16) & 0x3FFFF) >> 4) | ((uint64_t)1 << 16) | ((uint64_t)8 << 32);
                        s1 = 256; s2 = KT_E2O >> 4; sg = -2;
                    }
#pragma unroll
                    for (int b = 0; b < 3; b++) {
                        wg_wait<1>();
                        if (b == 2 && it == 5) ka = wa;
                        ldq(Q[(b + 1) % 3], b == 2 ? it < 5 : it < 6);
                        wg_fence();
                        wgmma32_rs(y[0], Q[b][0], dd); wgmma32_rs(y[1], Q[b][1], dd + s1);
                        wgmma32_rs(y[0], Q[b][2], dd + s2); wgmma32_rs(y[1], Q[b][3], dd + s1 + s2);
                        wg_commit();
                        dd += sg;
                    }
                }
            }
            wg_wait<0>();
            fence_regs<16>(y[0]); fence_regs<16>(y[1]);
            if (warp == 8) STAMP(18 + p);
            if (p == 0) {
                {
                    const uint32_t u0 = sp + OFF_U + w4 * U_STRIDE + U_PAD + ln * 16;
#pragma unroll 1
                    for (int r2 = 0; r2 < 2; r2++) {
#pragma unroll
                        for (int hf = 0; hf < 2; hf++) {
                            const int rho = 2 * r2 + hf, ci = ln + 32 * rho;
                            uint4 e4[4];
#pragma unroll
                            for (int v = 0; v < 4; v++) { const uint32_t a = u0 + rho * 512 + (v - 3) * 16; e4[v] = lds128(a ^ ((a >> 3) & 0x70)); }
                            float S[29];
                            const uint32_t* ew = (const uint32_t*)e4;
                            S[3] = 0.f;
#pragma unroll
                            for (int k = 4; k <= 28; k++) S[k] = S[k - 1] + ((k & 1) ? bf_hi(ew[k >> 1]) : bf_lo(ew[k >> 1]));
                            auto win = [&](int lo, int hi, uint32_t a) {
                                sts128(a, pack2(S[hi] - S[lo - 1], S[hi + 1] - S[lo]), pack2(S[hi + 2] - S[lo + 1], S[hi + 3] - S[lo + 2]),
                                       pack2(S[hi + 4] - S[lo + 3], S[hi + 5] - S[lo + 4]), pack2(S[hi + 6] - S[lo + 5], S[hi + 7] - S[lo + 6]));
                            };
                            const uint32_t sw = (ci ^ ((ci >> 3) & 1)) << 4;
                            win(4, 12, sp + OFF_BUF + w4 * BUF_STRIDE + W9_OFF + sw); win(13, 19, sp + OFF_X + w4 * 4096 + sw); win(20, 21, sp + OFF_X + w4 * 4096 + 2048 + sw);
                        }
                    }
                }
                bar_named(2, 128);
                if (warp == 8) STAMP(23);
            }
            {
                const int ap = (ln & 7) + (ln >> 4) * 8;
                const uint32_t loff = ((2 * ap + ((ln >> 3) & 1)) ^ ((ap >> 2) & 1)) << 4;
#pragma unroll
                for (int ph = 0; ph < 3; ph++) {
                    const uint32_t ka = sp + OFF_K3 + 2 * p * K3_STRIDE + (ph * 94 + 4 * g + w4 - 2 * q - 34) * 4;
#pragma unroll
                    for (int c = 0; c < 2; c++) {
                        const uint32_t wb = (ph ? sp + OFF_X + (2 * p + c) * 4096 + (ph - 1) * 2048 : sp + OFF_BUF + (2 * p + c) * BUF_STRIDE + W9_OFF) + loff;
                        uint32_t B[4][2];
#pragma unroll
                        for (int d = 0; d < (ph < 2 ? 4 : 2); d++) { B[d][0] = lds32(ka + c * K3_STRIDE + (48 + 16 * d) * 4); B[d][1] = lds32(ka + c * K3_STRIDE + (40 + 16 * d) * 4); }
#pragma unroll
                        for (int s = 0; s < 4; s++) {
                            uint32_t A[4];
                            ldsm4t(A, wb + s * 512);
                            if (s < 2) mma16816(y[c] + 8, A[0], A[1], A[2], A[3], B[1 - s][0], B[1 - s][1]);
                            if (ph < 2 || s >= 2) mma16816(y[c] + 12, A[0], A[1], A[2], A[3], B[3 - s][0], B[3 - s][1]);
                        }
                    }
                }
            }
#pragma unroll
            for (int c = 0; c < 2; c++) {
                const uint32_t a = ktp + c * 4096 + (64 + 16 * (33 + w4) + g - 2 * q) * 4;
                const uint32_t a0 = lds32(a), a1 = lds32(a + 32), a2 = lds32(a - 32);
                uint32_t B[8];
#pragma unroll
                for (int hf = 0; hf < 2; hf++) {
                    const uint32_t ua = sp + OFF_U + (2 * p + c) * U_STRIDE + U_PAD + (16 * hf + (ln >> 4) * 8 + (ln & 7) - 9) * 128 + (6 + ((ln >> 3) & 1)) * 16;
                    ldsm4(B + 4 * hf, ua ^ ((ua >> 3) & 0x70));
                }
#pragma unroll
                for (int j = 1; j < 4; j++) mma16816(y[c] + 4 * j, a0, a1, a2, a0, B[2 * j], B[2 * j + 1]);
            }
#pragma unroll
            for (int r = 0; r < 16; r++) { yw[0][r] = yw[1][r]; yw[1][r] = pack2(y[0][r], y[1][r]); }
        }
        uint4* yp = scr->y + bi * 1024 + (8 * q + w4) * 8 + g;
#pragma unroll
        for (int j = 0; j < 4; j++)
#pragma unroll
            for (int b = 0; b < 2; b++)
                st_rlx128(yp + (32 * j + 4 * b) * 8, tag4(yw[0][4 * j + b], yw[0][4 * j + 2 + b], yw[1][4 * j + b], yw[1][4 * j + 2 + b], tag));
        bar_named(2, 128);
        if (st < 8) st_rlx32(scr->yflag + bi * 8 + st, tag);
        if (warp == 8) STAMP(20);
    }
    __syncthreads();
    if (tid == 0) atomicAdd(scr->done, 1u);
}

typedef CUresult (*EncFn)(CUtensorMap*, CUtensorMapDataType, cuuint32_t, void*, const cuuint64_t*, const cuuint64_t*, const cuuint32_t*,
                          const cuuint32_t*, CUtensorMapInterleave, CUtensorMapSwizzle, CUtensorMapL2promotion, CUtensorMapFloatOOBfill);

extern "C" void kernel_launch(void* const* d_in, const int* in_sizes, int n_in, void* d_out, int out_size) {
    static EncFn enc = nullptr;
    static Scratch* scr = nullptr;
    if (!enc) {
        cudaGetSymbolAddress((void**)&scr, g_scr);
        cudaDriverEntryPointQueryResult qr;
        cudaGetDriverEntryPoint("cuTensorMapEncodeTiled", (void**)&enc, cudaEnableDefault, &qr);
        cudaFuncSetAttribute(fused_kernel, cudaFuncAttributeMaxDynamicSharedMemorySize, SMEM_BYTES);
    }
    CUtensorMap mx, mw, mwo;
    const cuuint32_t es[3] = {1, 1, 1};
    {
        cuuint64_t d[2] = {512, 2048}, s[1] = {1024}; cuuint32_t b[2] = {64, 128};
        enc(&mx, CU_TENSOR_MAP_DATA_TYPE_BFLOAT16, 2, d_in[0], d, s, b, es, CU_TENSOR_MAP_INTERLEAVE_NONE, CU_TENSOR_MAP_SWIZZLE_128B,
            CU_TENSOR_MAP_L2_PROMOTION_L2_128B, CU_TENSOR_MAP_FLOAT_OOB_FILL_NONE);
    }
    {
        cuuint64_t d[3] = {512, 512, 3}, s[2] = {3072, 1024}; cuuint32_t b[3] = {64, 64, 3};
        enc(&mw, CU_TENSOR_MAP_DATA_TYPE_BFLOAT16, 3, d_in[1], d, s, b, es, CU_TENSOR_MAP_INTERLEAVE_NONE, CU_TENSOR_MAP_SWIZZLE_128B,
            CU_TENSOR_MAP_L2_PROMOTION_L2_128B, CU_TENSOR_MAP_FLOAT_OOB_FILL_NONE);
    }
    {
        cuuint64_t d[2] = {512, 512}, s[1] = {1024}; cuuint32_t b[2] = {64, 256};
        enc(&mwo, CU_TENSOR_MAP_DATA_TYPE_BFLOAT16, 2, d_in[3], d, s, b, es, CU_TENSOR_MAP_INTERLEAVE_NONE, CU_TENSOR_MAP_SWIZZLE_128B,
            CU_TENSOR_MAP_L2_PROMOTION_L2_128B, CU_TENSOR_MAP_FLOAT_OOB_FILL_NONE);
    }
    fused_kernel<<<128, 384, SMEM_BYTES, cudaStreamPerThread>>>(
        scr, (const bf16*)d_in[5], (const bf16*)d_in[6], (const bf16*)d_in[7], (const bf16*)d_in[8], (const bf16*)d_in[9],
        (const bf16*)d_in[10], (const bf16*)d_in[2], (const bf16*)d_in[11], (bf16*)d_out, mx, mw, mwo);
}
```

```cpp
#include <cuda_runtime.h>
#include <cuda.h>
#include <cuda_bf16.h>
#include <stdint.h>

typedef __nv_bfloat16 bf16;

struct Scratch {
    uint4 xt[128 * 1024];
    uint4 o[16 * 8 * 32 * 32];
    uint4 y[128 * 1024];
    uint4 kvp[8 * 16 * 544];
    uint4 kvf[8 * 4 * 68];
    unsigned g[1024 * 8];
    unsigned yflag[128 * 8];
    unsigned xcnt[8 * 32];
    unsigned done[32];
};
__device__ Scratch g_scr;
#define STAMP(n)

constexpr int SLOT = 40960;
constexpr int OFF_SP0 = 32768, OFF_SP1 = SLOT + 32768;
constexpr int OFF_P = 2 * SLOT, OFF_V = OFF_P + 32768;
constexpr int OFF_X = OFF_V + 32768;
constexpr int KT_BYTES = 3264, KW_D = 16, KW_2 = 560, KW_3 = 656;
constexpr int OFF_U = 4 * SLOT, U_STRIDE = 4096 + 256 + 32;
constexpr int OFF_BUF = OFF_U + 4 * U_STRIDE, BUF_STRIDE = 8320;
constexpr int OFF_K3 = OFF_BUF + 4 * BUF_STRIDE, K3_STRIDE = 0;
constexpr int OFF_WPHI = OFF_K3 + 4 * K3_STRIDE;
constexpr int OFF_GW = OFF_WPHI + 2048;
constexpr int OFF_KVF = OFF_GW + 1024;
constexpr int OFF_BAR = OFF_KVF + 4352;
constexpr int SMEM_BYTES = OFF_BAR + 128 + 128;
static_assert(SMEM_BYTES <= 232448 && OFF_BUF % 128 == 0, "smem");
constexpr int W5_OFF = 0, W3_OFF = 3088, W9_OFF = 6176;
constexpr int BAR_FULL = 0, BAR_WPHI = 4, BAR_WO = 5, BAR_XT = 6, BAR_DONE = 7, BAR_WO2 = 8, BAR_GO = 9, OFF_CNT = 96;
#define KG_ROUNDS 4
constexpr int SPIN_LIMIT = 1 << 17;

__device__ __forceinline__ uint32_t s2u(const void* p) { return (uint32_t)__cvta_generic_to_shared(p); }
__device__ __forceinline__ void mbar_init(uint32_t b, int c) { asm volatile("mbarrier.init.shared::cta.b64 [%0],%1;" ::"r"(b), "r"(c) : "memory"); }
__device__ __forceinline__ void mbar_expect(uint32_t b, int bytes) { asm volatile("mbarrier.arrive.expect_tx.shared::cta.b64 _,[%0],%1;" ::"r"(b), "r"(bytes) : "memory"); }
__device__ __forceinline__ void mbar_arrive(uint32_t b) { asm volatile("mbarrier.arrive.shared::cta.b64 _,[%0];" ::"r"(b) : "memory"); }
__device__ __forceinline__ void mbar_wait(uint32_t b, int ph) {
    asm volatile("{\n.reg .pred p;\n.reg .u32 n;\nmov.u32 n,0;\nLW_%=:\nmbarrier.try_wait.parity.shared::cta.b64 p,[%0],%1;\n@p bra LD_%=;\n"
                 "add.u32 n,n,1;\nsetp.lt.u32 p,n,131072;\n@p bra LW_%=;\nLD_%=:\n}" ::"r"(b), "r"(ph) : "memory");
}
__device__ __forceinline__ void tma2d(uint32_t dst, const CUtensorMap* m, int c0, int c1, uint32_t bar) {
    asm volatile("cp.async.bulk.tensor.2d.shared::cluster.global.mbarrier::complete_tx::bytes [%0],[%1,{%3,%4}],[%2];" ::"r"(dst), "l"(m), "r"(bar), "r"(c0), "r"(c1) : "memory");
}
__device__ __forceinline__ void tma3d(uint32_t dst, const CUtensorMap* m, int c0, int c1, int c2, uint32_t bar) {
    asm volatile("cp.async.bulk.tensor.3d.shared::cluster.global.mbarrier::complete_tx::bytes [%0],[%1,{%3,%4,%5}],[%2];" ::"r"(dst), "l"(m), "r"(bar), "r"(c0), "r"(c1), "r"(c2) : "memory");
}
__device__ __forceinline__ void bulk_g2s(uint32_t dst, const void* src, int bytes, uint32_t bar) {
    asm volatile("cp.async.bulk.shared::cluster.global.mbarrier::complete_tx::bytes [%0],[%1],%2,[%3];" ::"r"(dst), "l"(src), "r"(bytes), "r"(bar) : "memory");
}
__device__ __forceinline__ uint64_t mkdesc(uint32_t addr, uint32_t lbo, uint32_t sbo) {
    return (uint64_t)((addr & 0x3FFFF) >> 4) | ((uint64_t)(lbo >> 4) << 16) | ((uint64_t)(sbo >> 4) << 32) | ((uint64_t)1 << 62);
}
__device__ __forceinline__ void wg_fence() { asm volatile("wgmma.fence.sync.aligned;" ::: "memory"); }
__device__ __forceinline__ void wg_commit() { asm volatile("wgmma.commit_group.sync.aligned;" ::: "memory"); }
template <int N> __device__ __forceinline__ void wg_wait() { asm volatile("wgmma.wait_group.sync.aligned %0;" ::"n"(N) : "memory"); }
template <int N> __device__ __forceinline__ void fence_regs(float* d) {
#pragma unroll
    for (int i = 0; i < N; i++) asm volatile("" : "+f"(d[i])::"memory");
}
#define R8(d, o) "+f"(d[o]), "+f"(d[o + 1]), "+f"(d[o + 2]), "+f"(d[o + 3]), "+f"(d[o + 4]), "+f"(d[o + 5]), "+f"(d[o + 6]), "+f"(d[o + 7])
__device__ __forceinline__ void wgmma192(float* d, uint64_t da, uint64_t db) {
    asm volatile("wgmma.mma_async.sync.aligned.m64n192k16.f32.bf16.bf16 {"
                 "%0,%1,%2,%3,%4,%5,%6,%7,%8,%9,%10,%11,%12,%13,%14,%15,%16,%17,%18,%19,%20,%21,%22,%23,%24,%25,%26,%27,%28,%29,%30,%31,"
                 "%32,%33,%34,%35,%36,%37,%38,%39,%40,%41,%42,%43,%44,%45,%46,%47,%48,%49,%50,%51,%52,%53,%54,%55,%56,%57,%58,%59,%60,%61,%62,%63,"
                 "%64,%65,%66,%67,%68,%69,%70,%71,%72,%73,%74,%75,%76,%77,%78,%79,%80,%81,%82,%83,%84,%85,%86,%87,%88,%89,%90,%91,%92,%93,%94,%95},"
                 "%96,%97,1,1,1,0,1;"
                 : R8(d, 0), R8(d, 8), R8(d, 16), R8(d, 24), R8(d, 32), R8(d, 40), R8(d, 48), R8(d, 56), R8(d, 64), R8(d, 72), R8(d, 80), R8(d, 88)
                 : "l"(da), "l"(db));
}
__device__ __forceinline__ void wgmma64_tt(float* d, uint64_t da, uint64_t db, int sc) {
    asm volatile("{.reg .pred p; setp.ne.b32 p,%34,0; wgmma.mma_async.sync.aligned.m64n64k16.f32.bf16.bf16 {"
                 "%0,%1,%2,%3,%4,%5,%6,%7,%8,%9,%10,%11,%12,%13,%14,%15,%16,%17,%18,%19,%20,%21,%22,%23,%24,%25,%26,%27,%28,%29,%30,%31},"
                 "%32,%33,p,1,1,1,1;}"
                 : R8(d, 0), R8(d, 8), R8(d, 16), R8(d, 24)
                 : "l"(da), "l"(db), "r"(sc));
}
__device__ __forceinline__ void wgmma128_rs(float* d, const uint4& a, uint64_t db, int sc) {
    asm volatile("{.reg .pred p; setp.ne.b32 p,%69,0; wgmma.mma_async.sync.aligned.m64n128k16.f32.bf16.bf16 {"
                 "%0,%1,%2,%3,%4,%5,%6,%7,%8,%9,%10,%11,%12,%13,%14,%15,%16,%17,%18,%19,%20,%21,%22,%23,%24,%25,%26,%27,%28,%29,%30,%31,"
                 "%32,%33,%34,%35,%36,%37,%38,%39,%40,%41,%42,%43,%44,%45,%46,%47,%48,%49,%50,%51,%52,%53,%54,%55,%56,%57,%58,%59,%60,%61,%62,%63},"
                 "{%64,%65,%66,%67},%68,p,1,1,1;}"
                 : R8(d, 0), R8(d, 8), R8(d, 16), R8(d, 24), R8(d, 32), R8(d, 40), R8(d, 48), R8(d, 56)
                 : "r"(a.x), "r"(a.y), "r"(a.z), "r"(a.w), "l"(db), "r"(sc));
}
__device__ __forceinline__ void wgmma48_rs(float* d, uint32_t a0, uint32_t a1, uint32_t a2, uint32_t a3, uint64_t db) {
    asm volatile("wgmma.mma_async.sync.aligned.m64n48k16.f32.bf16.bf16 {%0,%1,%2,%3,%4,%5,%6,%7,%8,%9,%10,%11,%12,%13,%14,%15,%16,%17,%18,%19,%20,%21,%22,%23},{%24,%25,%26,%27},%28,1,1,1,0;"
                 : R8(d, 0), R8(d, 8), R8(d, 16) : "r"(a0), "r"(a1), "r"(a2), "r"(a3), "l"(db));
}
__device__ __forceinline__ void mma16816(float* c, uint32_t a0, uint32_t a1, uint32_t a2, uint32_t a3, uint32_t b0, uint32_t b1) {
    asm("mma.sync.aligned.m16n8k16.row.col.f32.bf16.bf16.f32 {%0,%1,%2,%3},{%4,%5,%6,%7},{%8,%9},{%0,%1,%2,%3};"
        : "+f"(c[0]), "+f"(c[1]), "+f"(c[2]), "+f"(c[3]) : "r"(a0), "r"(a1), "r"(a2), "r"(a3), "r"(b0), "r"(b1));
}
__device__ __forceinline__ void ldsm4(uint32_t* r, uint32_t a) {
    asm volatile("ldmatrix.sync.aligned.m8n8.x4.shared.b16 {%0,%1,%2,%3},[%4];" : "=r"(r[0]), "=r"(r[1]), "=r"(r[2]), "=r"(r[3]) : "r"(a) : "memory");
}
__device__ __forceinline__ void ldsm4t(uint32_t* r, uint32_t a) {
    asm volatile("ldmatrix.sync.aligned.m8n8.x4.trans.shared.b16 {%0,%1,%2,%3},[%4];" : "=r"(r[0]), "=r"(r[1]), "=r"(r[2]), "=r"(r[3]) : "r"(a) : "memory");
}
__device__ __forceinline__ void stsm4(uint32_t a, uint32_t r0, uint32_t r1, uint32_t r2, uint32_t r3) {
    asm volatile("stmatrix.sync.aligned.m8n8.x4.shared.b16 [%0],{%1,%2,%3,%4};" ::"r"(a), "r"(r0), "r"(r1), "r"(r2), "r"(r3) : "memory");
}
__device__ __forceinline__ uint32_t lds32(uint32_t a) { uint32_t v; asm volatile("ld.shared.b32 %0,[%1];" : "=r"(v) : "r"(a) : "memory"); return v; }
__device__ __forceinline__ uint4 lds128(uint32_t a) { uint4 v; asm volatile("ld.shared.v4.b32 {%0,%1,%2,%3},[%4];" : "=r"(v.x), "=r"(v.y), "=r"(v.z), "=r"(v.w) : "r"(a) : "memory"); return v; }
__device__ __forceinline__ void sts16(uint32_t a, uint32_t v) { asm volatile("st.shared.b16 [%0],%1;" ::"r"(a), "h"((unsigned short)v) : "memory"); }
__device__ __forceinline__ void sts32(uint32_t a, uint32_t v) { asm volatile("st.shared.b32 [%0],%1;" ::"r"(a), "r"(v) : "memory"); }
__device__ __forceinline__ void sts64(uint32_t a, uint32_t x, uint32_t y) { asm volatile("st.shared.v2.b32 [%0],{%1,%2};" ::"r"(a), "r"(x), "r"(y) : "memory"); }
__device__ __forceinline__ void sts128(uint32_t a, uint32_t x, uint32_t y, uint32_t z, uint32_t w) { asm volatile("st.shared.v4.b32 [%0],{%1,%2,%3,%4};" ::"r"(a), "r"(x), "r"(y), "r"(z), "r"(w) : "memory"); }
__device__ __forceinline__ uint32_t pack2(float lo, float hi) { uint32_t d; asm("cvt.rn.bf16x2.f32 %0,%1,%2;" : "=r"(d) : "f"(hi), "f"(lo)); return d; }
__device__ __forceinline__ float bf_lo(uint32_t v) { return __uint_as_float(v << 16); }
__device__ __forceinline__ float bf_hi(uint32_t v) { return __uint_as_float(v & 0xffff0000u); }
__device__ __forceinline__ float bf_round(float v) { return bf_lo(pack2(v, 0.f)); }
__device__ __forceinline__ uint32_t hmax2(uint32_t a, uint32_t b) { uint32_t d; asm("max.bf16x2 %0,%1,%2;" : "=r"(d) : "r"(a), "r"(b)); return d; }
__device__ __forceinline__ uint32_t hmin2(uint32_t a, uint32_t b) { uint32_t d; asm("min.bf16x2 %0,%1,%2;" : "=r"(d) : "r"(a), "r"(b)); return d; }
__device__ __forceinline__ uint32_t hmul2(uint32_t a, uint32_t b) { uint32_t d; asm("mul.rn.bf16x2 %0,%1,%2;" : "=r"(d) : "r"(a), "r"(b)); return d; }
__device__ __forceinline__ float ex2(float x) { float y; asm("ex2.approx.ftz.f32 %0,%1;" : "=f"(y) : "f"(x)); return y; }
__device__ __forceinline__ float rcp(float x) { float y; asm("rcp.approx.ftz.f32 %0,%1;" : "=f"(y) : "f"(x)); return y; }
__device__ __forceinline__ uint32_t ld_nc(const uint32_t* p) { uint32_t v; asm volatile("ld.global.nc.b32 %0,[%1];" : "=r"(v) : "l"(p)); return v; }
__device__ __forceinline__ uint2 ld_nc64(const uint2* p) { uint2 v; asm volatile("ld.global.nc.v2.b32 {%0,%1},[%2];" : "=r"(v.x), "=r"(v.y) : "l"(p)); return v; }
__device__ __forceinline__ unsigned ld_acq(const unsigned* p) { unsigned v; asm volatile("ld.acquire.gpu.global.u32 %0,[%1];" : "=r"(v) : "l"(p) : "memory"); return v; }
__device__ __forceinline__ unsigned ld_rlx(const unsigned* p) { unsigned v; asm volatile("ld.relaxed.gpu.global.u32 %0,[%1];" : "=r"(v) : "l"(p) : "memory"); return v; }
__device__ __forceinline__ uint2 ld_rlx64(const void* p) { uint2 v; asm volatile("{.reg .b64 t; ld.relaxed.gpu.global.b64 t,[%2]; mov.b64 {%0,%1},t;}" : "=r"(v.x), "=r"(v.y) : "l"(p) : "memory"); return v; }
__device__ __forceinline__ uint4 ld_rlx128(const void* p) {
    uint4 v;
    asm volatile("{.reg .b64 t,u; ld.relaxed.gpu.global.v2.b64 {t,u},[%4]; mov.b64 {%0,%1},t; mov.b64 {%2,%3},u;}" : "=r"(v.x), "=r"(v.y), "=r"(v.z), "=r"(v.w) : "l"(p) : "memory");
    return v;
}
__device__ __forceinline__ void st_rlx32(void* p, uint32_t x) { asm volatile("st.relaxed.gpu.global.u32 [%0],%1;" ::"l"(p), "r"(x) : "memory"); }
__device__ __forceinline__ void st_rlx64(void* p, uint32_t x, uint32_t y) { asm volatile("{.reg .b64 t; mov.b64 t,{%1,%2}; st.relaxed.gpu.global.b64 [%0],t;}" ::"l"(p), "r"(x), "r"(y) : "memory"); }
__device__ __forceinline__ void st_rlx128(void* p, uint4 v) {
    asm volatile("{.reg .b64 t,u; mov.b64 t,{%1,%2}; mov.b64 u,{%3,%4}; st.relaxed.gpu.global.v2.b64 [%0],{t,u};}" ::"l"(p), "r"(v.x), "r"(v.y), "r"(v.z), "r"(v.w) : "memory");
}
__device__ __forceinline__ uint32_t tagw(uint32_t w, uint32_t tag) { return (w & ~1u) | tag; }
__device__ __forceinline__ uint4 tag4(uint32_t x, uint32_t y, uint32_t z, uint32_t w, uint32_t tag) { return make_uint4(tagw(x, tag), y, tagw(z, tag), w); }
__device__ __forceinline__ uint32_t bad4(const uint4& v, uint32_t tag) { return (v.x ^ tag) | (v.z ^ tag); }
__device__ __forceinline__ void bar_named(int id, int n) { asm volatile("bar.sync %0,%1;" ::"r"(id), "r"(n) : "memory"); }

struct cf { float re, im; };
__device__ __forceinline__ cf cmul(cf a, cf b) { cf r; r.re = a.re * b.re - a.im * b.im; r.im = a.re * b.im + a.im * b.re; return r; }
__device__ __forceinline__ cf cexp_p(float arl, float ait, float p) {
    float mag = ex2(arl * p);
    float t = ait * p;
    t = (t - rintf(t)) * 6.283185307179586f;
    cf r; r.re = mag * __cosf(t); r.im = mag * __sinf(t);
    return r;
}

__device__ __forceinline__ void hedgehog2(const uint32_t* a, uint32_t wphi_addr, uint32_t (*out)[8]) {
    float p[2][2][4], mx[2][2];
#pragma unroll
    for (int h = 0; h < 2; h++) {
        uint32_t b[4];
        ldsm4t(b, wphi_addr + h * 512);
        float c0[4] = {0.f, 0.f, 0.f, 0.f}, c1[4] = {0.f, 0.f, 0.f, 0.f};
        mma16816(c0, a[4 * h], a[4 * h + 1], a[4 * h + 2], a[4 * h + 3], b[0], b[1]);
        mma16816(c1, a[4 * h], a[4 * h + 1], a[4 * h + 2], a[4 * h + 3], b[2], b[3]);
#pragma unroll
        for (int k = 0; k < 2; k++) {
            p[h][k][0] = c0[2 * k]; p[h][k][1] = c0[2 * k + 1]; p[h][k][2] = c1[2 * k]; p[h][k][3] = c1[2 * k + 1];
            mx[h][k] = fmaxf(fmaxf(p[h][k][0], p[h][k][1]), fmaxf(p[h][k][2], p[h][k][3]));
        }
    }
#pragma unroll
    for (int o = 1; o <= 2; o <<= 1)
#pragma unroll
        for (int h = 0; h < 2; h++)
#pragma unroll
            for (int k = 0; k < 2; k++) mx[h][k] = fmaxf(mx[h][k], __shfl_xor_sync(~0u, mx[h][k], o));
    const float L = 1.4426950408889634f;
    float pmin = 1.f;
#pragma unroll
    for (int h = 0; h < 2; h++)
#pragma unroll
        for (int k = 0; k < 2; k++) {
            const float m = -mx[h][k] * L;
            const float e0 = ex2(fmaf(p[h][k][0], L, m)), e1 = ex2(fmaf(p[h][k][1], L, m)), e2 = ex2(fmaf(p[h][k][2], L, m)), e3 = ex2(fmaf(p[h][k][3], L, m));
            const float p01 = e0 * e1, p23 = e2 * e3, pp = p01 * p23, r = rcp(pp), r01 = r * p23, r23 = r * p01;
            pmin = fminf(pmin, pp);
            out[h][k] = pack2(e0, e1); out[h][k + 2] = pack2(e2, e3);
            out[h][4 + k] = pack2(r01 * e1, r01 * e0); out[h][4 + k + 2] = pack2(r23 * e3, r23 * e2);
        }
    if (__builtin_expect(__any_sync(~0u, !(pmin > 1e-18f)), 0)) {
#pragma unroll
        for (int h = 0; h < 2; h++)
#pragma unroll
            for (int k = 0; k < 2; k++) {
                float m = fminf(fminf(p[h][k][0], p[h][k][1]), fminf(p[h][k][2], p[h][k][3]));
                m = fminf(m, __shfl_xor_sync(~0u, m, 1));
                m = fminf(m, __shfl_xor_sync(~0u, m, 2)) * L;
                out[h][4 + k] = pack2(ex2(fmaf(p[h][k][0], -L, m)), ex2(fmaf(p[h][k][1], -L, m)));
                out[h][4 + k + 2] = pack2(ex2(fmaf(p[h][k][2], -L, m)), ex2(fmaf(p[h][k][3], -L, m)));
            }
    }
}

__global__ void __launch_bounds__(384, 1)
fused_kernel(Scratch* __restrict__ scr, const bf16* __restrict__ logA, const bf16* __restrict__ Aim, const bf16* __restrict__ Cre,
             const bf16* __restrict__ Cim, const bf16* __restrict__ logdt, const bf16* __restrict__ Dskip, const bf16* __restrict__ wphi,
             const bf16* __restrict__ gatew, bf16* __restrict__ out,
             const __grid_constant__ CUtensorMap mx, const __grid_constant__ CUtensorMap mw, const __grid_constant__ CUtensorMap mwo) {
    extern __shared__ __align__(1024) uint8_t smem[];
    const uint32_t sb = s2u(smem);
    const int tid = threadIdx.x, warp = __shfl_sync(~0u, tid >> 5, 0), lane = tid & 31;
    const int g = lane >> 2, q = lane & 3, w4 = warp & 3;
    const int bi = blockIdx.x, bi_i = bi & 15, bi_j = bi >> 4;
    const uint32_t bar = sb + OFF_BAR;
    const int rot = (bi_j & 1) * 4;
    auto load_stage = [&](int kb) {
        const uint32_t b = bar + 8 * (BAR_FULL + (kb & 3)), d = sb + (kb & 3) * SLOT;
        const int kc = ((kb + rot) & 7) * 64;
        mbar_expect(b, SLOT);
        tma2d(d, &mx, kc, bi_i * 128, b);
        tma3d(d + 16384, &mw, bi_j * 64, kc, 0, b);
    };

    const int ch = bi * 4 + w4;
    uint2 pla, pai, pcr, pci; uint32_t pdt = 0, pds;
    if (warp >= 8) {
        pla = ld_nc64((const uint2*)logA + ch * 32 + lane); pai = ld_nc64((const uint2*)Aim + ch * 32 + lane);
        pcr = ld_nc64((const uint2*)Cre + ch * 32 + lane); pci = ld_nc64((const uint2*)Cim + ch * 32 + lane);
        pdt = ld_nc((const uint32_t*)logdt + (ch >> 1)); pds = ld_nc((const uint32_t*)Dskip + (ch >> 1));
    }
    unsigned done0 = ld_rlx(scr->done);
    if (tid == 0) {
        for (int s = 0; s < 4; s++) mbar_init(bar + 8 * (BAR_FULL + s), 1);
        asm volatile("fence.mbarrier_init.release.cluster;" ::: "memory");
#pragma unroll 1
        for (int s = 0; s < 4; s++) load_stage(s);
        STAMP(11);
    } else if (tid == 32) {
        if (sb & 1023) __trap();
        for (int s = 0; s < 5; s++) sts32(bar + OFF_CNT + 4 * s, 0);
        mbar_init(bar + 8 * BAR_WPHI, 1); mbar_init(bar + 8 * BAR_WO, 2); mbar_init(bar + 8 * BAR_XT, 8); mbar_init(bar + 8 * BAR_DONE, 8);
        mbar_init(bar + 8 * BAR_WO2, 1); mbar_init(bar + 8 * BAR_GO, 1);
        asm volatile("fence.mbarrier_init.release.cluster;" ::: "memory");
        mbar_expect(bar + 8 * BAR_WPHI, 3072);
        bulk_g2s(sb + OFF_GW, gatew, 1024, bar + 8 * BAR_WPHI);
        bulk_g2s(sb + OFF_WPHI, wphi + bi_j * 1024, 2048, bar + 8 * BAR_WPHI);
    } else if (tid == 64) {
        asm volatile("prefetch.tensormap [%0];" ::"l"(&mw) : "memory");
    }
    const uint32_t buf = sb + OFF_BUF + w4 * BUF_STRIDE;
    __syncthreads();
    asm volatile("" : "+r"(pdt), "+r"(done0)::"memory");
    const unsigned epoch1 = (done0 >> 7) + 1u;
    const uint32_t tag = epoch1 & 1u;

    if (warp < 8) {
        const int wg = warp >> 2;
        if (warp == 0) STAMP(21);
        float acc[96];
        const int grow = bi_j * 16 + warp * 2 + (lane >> 4);
        const uint32_t gx_a = grow * 128 + ((((lane & 15) >> 1) ^ (grow & 7)) << 4) + (lane & 1) * 8;
        const int srow = warp * 16 + (lane & 15);
        const uint32_t srow_a = srow * 128;
        const int sx = srow & 7, shi = lane >> 4;
        auto last_of_8 = [&](int c) {
            unsigned old;
            asm volatile("atom.acq_rel.cta.shared.add.u32 %0,[%1],1;" : "=r"(old) : "r"(bar + OFF_CNT + 4 * c) : "memory");
            return (old & 7) == 7;
        };
        const int qq = (bi_i & 2) + ((lane >> 1) & 1);
        const int kvf_n = warp < 4 ? 8 : ((warp == 4 && (bi_i & 1) == 0) ? 4 : 0);
        uint2* kvf_dst = (uint2*)(scr->kvf + (bi_j * 4 + (bi_i >> 2)) * 68) +
                         (warp == 4 ? (64 + qq) * 2 + (lane & 1) : ((bi_i & 3) * 8 + w4 * 2 + (lane & 1)) * 4 + (lane >> 1));
        float gsum = 0.f;
#pragma unroll
        for (int r = 0; r < 96; r++) acc[r] = 0.f;
        fence_regs<96>(acc);
        const uint64_t da0 = mkdesc(sb + wg * 8192, 16, 1024), db0 = mkdesc(sb + 16384, 8192, 1024);
        {
            const uint32_t old = tag ^ 1u;
            const uint4 z4 = make_uint4(old, 0, old, 0);
            uint4* kvp = scr->kvp + bi * 544 + wg * 272;
            if (w4 < 2) {
#pragma unroll
                for (int f = 0; f < 4; f++) st_rlx128(kvp + w4 * 136 + lane + f * 32, z4);
            } else if (w4 == 2 && lane < 4) {
#pragma unroll
                for (int f = 0; f < 4; f++) st_rlx128(kvp + (f >> 1) * 136 + 128 + (f & 1) * 4 + lane, z4);
            }
            if (lane < kvf_n) st_rlx64(kvf_dst, old, 0);
            if (lane >= 30) st_rlx128(scr->o + ((bi_i * 8 + warp) * 32 + bi_j * 4 + 3) * 32 + lane, z4);
            if (lane < 8) st_rlx32(scr->g + (bi_i * 64 + bi_j * 8 + warp) * 8 + lane, old);
        }
        mbar_wait(bar + 8 * BAR_WPHI, 0);
#pragma unroll 1
        for (int kb = 0; kb < 8; kb++) {
            const int s = kb & 3;
            const uint64_t da = da0 + s * (SLOT >> 4), db = db0 + s * (SLOT >> 4);
            mbar_wait(bar + 8 * (BAR_FULL + s), kb >> 2);
            if (kb == 0 && warp == 0) STAMP(0);
            wg_fence();
#pragma unroll
            for (int k = 0; k < 4; k++) wgmma192(acc, da + 2 * k, db + 128 * k);
            wg_commit();
            wg_wait<1>();
            __syncwarp();
            if (lane == 0 && kb > 0 && kb < 7) {
                const int ps = (kb - 1) & 3;
                if (last_of_8(ps)) {
                    if (kb < 5) load_stage(kb + 3);
                    else {
                        mbar_expect(bar + 8 * BAR_WO, 32768);
                        tma2d(sb + ps * SLOT, &mwo, (bi_j & 3) * 128 + ps * 64, 0, bar + 8 * BAR_WO);
                    }
                }
            }
            __syncwarp();
            const uint32_t st = sb + s * SLOT;
            if (kb == (bi_j >> 1)) {
                uint32_t* xt = (uint32_t*)scr->xt + ((kb + rot) * 16 + (g >> 2)) * 4096 + (bi_i * 16 + warp * 2) * 16 + (g & 3) * 4 + q;
#pragma unroll
                for (int cb = 0; cb < 8; cb += 2) {
                    uint32_t r[4];
                    ldsm4t(r, st + srow_a + (((cb + shi) ^ sx) << 4));
                    xt[cb * 8192] = r[0]; xt[cb * 8192 + 16] = r[1]; xt[cb * 8192 + 8192] = r[2]; xt[cb * 8192 + 8192 + 16] = r[3];
                }
                __syncwarp();
                if (lane == 0) mbar_arrive(bar + 8 * BAR_XT);
            }
            {
                uint32_t x0, x1, w0, w1;
                asm volatile("ld.shared.v2.b32 {%0,%1},[%2];" : "=r"(x0), "=r"(x1) : "r"(st + gx_a) : "memory");
                asm volatile("ld.shared.v2.b32 {%0,%1},[%2];" : "=r"(w0), "=r"(w1) : "r"(sb + OFF_GW + ((kb + rot) & 7) * 128 + (lane & 15) * 8) : "memory");
                const uint32_t p0 = hmul2(x0, w0), p1 = hmul2(x1, w1);
                gsum += (bf_lo(p0) + bf_hi(p0)) + (bf_lo(p1) + bf_hi(p1));
            }
        }
        wg_wait<0>();
        fence_regs<96>(acc);
        __syncwarp();
        if (lane == 0) mbar_arrive(bar + 8 * BAR_DONE);
        if (warp == 0) STAMP(1);
        uint32_t in[32], va[16];
#pragma unroll
        for (int r = 0; r < 16; r++) {
            in[r] = pack2(acc[32 + 2 * r], acc[32 + 2 * r + 1]);
            in[16 + r] = pack2(acc[2 * r], acc[2 * r + 1]);
            va[r] = pack2(acc[64 + 2 * r], acc[64 + 2 * r + 1]);
        }
        const uint32_t wphi_a = sb + OFF_WPHI + (lane & 15) * 32 + (lane >> 4) * 16;
        uint32_t pq[4][8];
#pragma unroll 1
        for (int it = 0; it < 4; it++) {
            hedgehog2(in, wphi_a + (it & 1) * 1024, pq + 2);
#pragma unroll
            for (int r = 0; r < 24; r++) in[r] = in[r + 8];
            if (it < 2) {
#pragma unroll
                for (int hs = 0; hs < 4; hs++) {
                    float c[4] = {0.f, 0.f, 0.f, 0.f};
                    uint32_t* o = pq[2 + (hs >> 1)] + 4 * (hs & 1);
                    mma16816(c, o[0], o[1], o[2], o[3], 0x3f803f80u, 0x3f803f80u);
                    const float r0 = rcp(c[0]), r1 = rcp(c[2]);
                    const uint32_t s0 = pack2(r0, r0), s1 = pack2(r1, r1);
                    o[0] = hmul2(o[0], s0); o[1] = hmul2(o[1], s1); o[2] = hmul2(o[2], s0); o[3] = hmul2(o[3], s1);
                }
                if (it == 0) mbar_wait(bar + 8 * BAR_DONE, 0);
                const uint32_t pt = sb + OFF_P + it * 16384 + srow_a, vt = sb + OFF_V + it * 16384 + srow_a;
#pragma unroll
                for (int hl = 0; hl < 2; hl++) {
                    stsm4(pt + (((4 * hl + shi) ^ sx) << 4), pq[2 + hl][0], pq[2 + hl][1], pq[2 + hl][2], pq[2 + hl][3]);
                    stsm4(pt + (((4 * hl + 2 + shi) ^ sx) << 4), pq[2 + hl][4], pq[2 + hl][5], pq[2 + hl][6], pq[2 + hl][7]);
                    stsm4(vt + (((2 * hl + shi) ^ sx) << 4), va[4 * hl], va[4 * hl + 1], va[4 * hl + 2], va[4 * hl + 3]);
                }
                if (lane < 16) sts128(vt + ((4 ^ sx) << 4), 0x3f803f80u, 0x3f803f80u, 0x3f803f80u, 0x3f803f80u);
#pragma unroll
                for (int r = 0; r < 8; r++) va[r] = va[r + 8];
            }
            if (it == 1) {
                asm volatile("fence.proxy.async.shared::cta;" ::: "memory");
                bar_named(1, 256);
                if (warp == 0) STAMP(2);
                if (tid == 0) mbar_arrive(bar + 8 * BAR_GO);
                float d[32];
                const uint64_t dv = mkdesc(sb + OFF_V + wg * 16384, 16, 1024), dp = mkdesc(sb + OFF_P + wg * 16384, 16, 1024);
                wg_fence();
#pragma unroll
                for (int k = 0; k < 8; k++) wgmma64_tt(d, dv + 128 * k, dp + 128 * k, k != 0);
                wg_commit();
                wg_wait<0>();
                fence_regs<32>(d);
                uint4* kvp = scr->kvp + bi * 544 + wg * 272;
                if (w4 < 2) {
                    uint32_t e[16];
#pragma unroll
                    for (int r = 0; r < 16; r++) e[r] = __float_as_uint(w4 ? d[16 + r] : d[r]);
                    uint4* p = kvp + w4 * 136 + lane;
#pragma unroll
                    for (int ks = 0; ks < 2; ks++)
#pragma unroll
                        for (int nt = 0; nt < 2; nt++)
                            st_rlx128(p + (ks * 2 + nt) * 32, tag4(e[8 * ks + 2 * nt], e[8 * ks + 2 * nt + 1], e[8 * ks + 4 + 2 * nt], e[8 * ks + 4 + 2 * nt + 1], tag));
                } else if (w4 == 2 && lane < 4) {
#pragma unroll
                    for (int hl = 0; hl < 2; hl++)
#pragma unroll
                        for (int ks = 0; ks < 2; ks++)
                            st_rlx128(kvp + hl * 136 + 128 + ks * 4 + lane, tag4(__float_as_uint(d[16 * hl + 8 * ks]), __float_as_uint(d[16 * hl + 8 * ks + 1]),
                                                                                __float_as_uint(d[16 * hl + 8 * ks + 4]), __float_as_uint(d[16 * hl + 8 * ks + 5]), tag));
                }
                if (warp == 0) STAMP(3);
            }
            if (it == 2) {
#pragma unroll
                for (int r = 0; r < 8; r++) { pq[0][r] = pq[2][r]; pq[1][r] = pq[3][r]; }
                if (warp == 0) STAMP(12);
                if (kvf_n) {
                    const bool zw = warp == 4;
                    const uint4* src = scr->kvp + bi_j * (16 * 544) + (bi_i >> 2) * 136 +
                                       (zw ? (lane >> 2) * (2 * 544) + 128 + (lane & 1) * 4 + qq
                                           : (lane >> 3) * (4 * 544) + ((lane >> 1) & 3) * 32 + (bi_i & 3) * 8 + warp * 2 + (lane & 1));
                    const int s23 = zw ? 0 : 2 * 544;
                    uint4 v[4];
                    int n = 0;
#pragma unroll 1
                    while (true) {
                        v[0] = ld_rlx128(src); v[1] = ld_rlx128(src + 544); v[2] = ld_rlx128(src + s23); v[3] = ld_rlx128(src + s23 + 544);
                        if (!__any_sync(~0u, (bad4(v[0], tag) | bad4(v[1], tag) | bad4(v[2], tag) | bad4(v[3], tag)) & 1)) break;
                        if (++n > SPIN_LIMIT) break;
                    }
                    float f[4];
                    f[0] = __uint_as_float(v[2].x) + __uint_as_float(v[3].x); f[1] = __uint_as_float(v[2].y) + __uint_as_float(v[3].y);
                    f[2] = __uint_as_float(v[2].z) + __uint_as_float(v[3].z); f[3] = __uint_as_float(v[2].w) + __uint_as_float(v[3].w);
                    float e0 = __uint_as_float(v[0].x) + __uint_as_float(v[1].x), e1 = __uint_as_float(v[0].y) + __uint_as_float(v[1].y);
                    float e2 = __uint_as_float(v[0].z) + __uint_as_float(v[1].z), e3 = __uint_as_float(v[0].w) + __uint_as_float(v[1].w);
                    if (zw) {
                        e0 = __shfl_xor_sync(~0u, f[0], 4); e1 = __shfl_xor_sync(~0u, f[1], 4);
                        e2 = __shfl_xor_sync(~0u, f[2], 4); e3 = __shfl_xor_sync(~0u, f[3], 4);
                    }
                    f[0] += e0; f[1] += e1; f[2] += e2; f[3] += e3;
#pragma unroll
                    for (int o = 8; o <= 16; o <<= 1)
#pragma unroll
                        for (int r = 0; r < 4; r++) f[r] += __shfl_xor_sync(~0u, f[r], o);
                    if (lane < kvf_n) st_rlx64(kvf_dst, tagw(pack2(f[0], f[1]), tag), pack2(f[2], f[3]));
                }
                __syncwarp();
                if (lane == 0 && last_of_8(4)) {
                    mbar_expect(bar + 8 * BAR_WO2, 65536);
                    tma2d(sb + 2 * SLOT, &mwo, (bi_j & 3) * 128, 256, bar + 8 * BAR_WO2);
                    tma2d(sb + OFF_V, &mwo, (bi_j & 3) * 128 + 64, 256, bar + 8 * BAR_WO2);
                }
                __syncwarp();
                if (warp == 0) STAMP(13);
#pragma unroll
                for (int o = 1; o < 16; o <<= 1) gsum += __shfl_xor_sync(~0u, gsum, o);
                const float gate = bf_round(rcp(1.0f + ex2(-1.4426950408889634f * bf_round(gsum))));
                const uint32_t gv = __shfl_sync(~0u, __float_as_uint(gate) | tag, (lane & 4) * 4);
                if (lane < 8) st_rlx32(scr->g + (bi_i * 64 + bi_j * 8 + warp) * 8 + lane, gv);
            }
        }
        if (warp == 0) STAMP(4);
        {
            {
                const uint4* kp = scr->kvf + bi_j * 272 + tid;
                uint4 v0, v1;
                int n = 0;
#pragma unroll 1
                while (true) {
                    v0 = ld_rlx128(kp); v1 = ld_rlx128(kp + (tid < 16 ? 256 : 0));
                    if (!__any_sync(~0u, (bad4(v0, tag) | bad4(v1, tag)) & 1)) break;
                    if (++n > SPIN_LIMIT) break;
                }
                sts128(sb + OFF_KVF + tid * 16, v0.x, v0.y, v0.z, v0.w);
                if (tid < 16) sts128(sb + OFF_KVF + 4096 + tid * 16, v1.x, v1.y, v1.z, v1.w);
                bar_named(1, 256);
            }
            uint4 kf[4][3];
#pragma unroll
            for (int hh = 0; hh < 4; hh++) {
                const uint32_t a = sb + OFF_KVF + hh * 1088;
                kf[hh][0] = lds128(a + lane * 32); kf[hh][1] = lds128(a + lane * 32 + 16); kf[hh][2] = lds128(a + 1024 + q * 16);
            }
            if (warp == 0) STAMP(5);
            uint4 own[4];
#pragma unroll
            for (int hh = 0; hh < 4; hh++) {
                float c[6][4];
#pragma unroll
                for (int t = 0; t < 6; t++) { c[t][0] = c[t][1] = c[t][2] = c[t][3] = 0.f; }
                const uint32_t* a = pq[hh];
                const bool od = g & 1;
                mma16816(c[0], a[0], a[1], a[2], a[3], od ? 0x3f803f80u : kf[hh][2].x, od ? 0x3f803f80u : kf[hh][2].y);
                mma16816(c[1], a[4], a[5], a[6], a[7], od ? 0x3f803f80u : kf[hh][2].z, od ? 0x3f803f80u : kf[hh][2].w);
                mma16816(c[2], a[0], a[1], a[2], a[3], kf[hh][0].x, kf[hh][0].y);
                mma16816(c[3], a[0], a[1], a[2], a[3], kf[hh][0].z, kf[hh][0].w);
                mma16816(c[4], a[4], a[5], a[6], a[7], kf[hh][1].x, kf[hh][1].y);
                mma16816(c[5], a[4], a[5], a[6], a[7], kf[hh][1].z, kf[hh][1].w);
                uint32_t w[4];
#pragma unroll
                for (int k = 0; k < 2; k++) {
                    const float rho = c[0][2 * k + 1] * rcp(c[1][2 * k + 1]);
                    const float r = rcp(fmaf(c[0][2 * k + 1], 1e-6f, fmaf(rho, c[1][2 * k], c[0][2 * k]))), rr = r * rho;
                    w[k] = pack2(fmaf(c[4][2 * k], rr, c[2][2 * k] * r), fmaf(c[4][2 * k + 1], rr, c[2][2 * k + 1] * r));
                    w[2 + k] = pack2(fmaf(c[5][2 * k], rr, c[3][2 * k] * r), fmaf(c[5][2 * k + 1], rr, c[3][2 * k + 1] * r));
                }
                own[hh] = tag4(w[0], w[1], w[2], w[3], tag);
            }
            uint4* og = scr->o + ((bi_i * 8 + warp) * 32 + bi_j * 4) * 32 + lane;
#pragma unroll
            for (int hh = 0; hh < 4; hh++) st_rlx128(og + hh * 32, own[hh]);
        }
        if (warp == 0) STAMP(6);
        float oc[64];
        const int slab = bi_i * 8 + (bi_j >> 2) * 4 + w4;
        const uint8_t* yb = (const uint8_t*)scr->y + (size_t)((bi_j & 3) * 32 + wg * 16 + (q >> 1)) * 16384 + slab * 128 + g * 16 + (q & 1) * 8;
        const unsigned* gp = scr->g + (slab * 8 + (g >> 1)) * 8 + (g & 1) * 4;
        uint2 yv[8]; unsigned g0, g1;
        {
            const uint4* osrc = scr->o + (slab * 32 + wg * 16) * 32 + lane;
            uint4 fr[16];
            const unsigned* probe = (const unsigned*)(osrc - lane + ((lane & 3) * 4 + 3) * 32 + 31) + 2;
            {
                unsigned miss = ~0u;
                int n = 0;
#pragma unroll
                for (int s = 0; s < 4; s++) {
#pragma unroll 1
                    while ((miss >> s) & 1) { miss = __ballot_sync(~0u, (ld_rlx(probe) ^ tag) & 1); if (++n > SPIN_LIMIT) break; }
#pragma unroll
                    for (int k = 4 * s; k < 4 * s + 4; k++) fr[k] = ld_rlx128(osrc + k * 32);
                }
            }
            if (warp == 0) STAMP(14);
            mbar_wait(bar + 8 * (wg ? BAR_WO2 : BAR_WO), 0);
            const uint64_t dw = mkdesc(sb + wg * 2 * SLOT, wg ? 32768 : SLOT, 1024);
#pragma unroll
            for (int s = 0; s < 4; s++) {
                int n = 0;
#pragma unroll 1
                while (__builtin_expect(__any_sync(~0u, (bad4(fr[4 * s], tag) | bad4(fr[4 * s + 1], tag) | bad4(fr[4 * s + 2], tag) | bad4(fr[4 * s + 3], tag)) & 1), 0)) {
#pragma unroll
                    for (int k = 4 * s; k < 4 * s + 4; k++) fr[k] = ld_rlx128(osrc + k * 32);
                    if (++n > SPIN_LIMIT) break;
                }
                wg_fence();
#pragma unroll
                for (int hh = 0; hh < 4; hh++) wgmma128_rs(oc, fr[4 * s + hh], dw + 128 * (4 * s + hh), (s | hh) != 0);
                wg_commit();
                if (s == 1) {
                    wg_wait<1>();
#pragma unroll
                    for (int nt = 0; nt < 8; nt++) yv[nt] = ld_rlx64(yb + nt * 32768);
                    g0 = ld_rlx(gp); g1 = ld_rlx(gp + 32);
                }
            }
            if (warp == 0) STAMP(7);
            {
                const unsigned* yprobe = scr->yflag + ((bi_j & 3) * 32 + wg * 16 + (lane & 15)) * 8;
                int n = 0;
#pragma unroll 1
                while (true) {
                    uint32_t bad = (g0 ^ tag) | (g1 ^ tag);
#pragma unroll
                    for (int nt = 0; nt < 8; nt++) bad |= yv[nt].x ^ tag;
                    if (!__any_sync(~0u, bad & 1)) break;
#pragma unroll 1
                    while (__any_sync(~0u, (ld_rlx(yprobe) ^ tag) & 1)) { if (++n > SPIN_LIMIT) break; }
#pragma unroll
                    for (int nt = 0; nt < 8; nt++) yv[nt] = ld_rlx64(yb + nt * 32768);
                    g0 = ld_rlx(gp); g1 = ld_rlx(gp + 32);
                    if (++n > SPIN_LIMIT) break;
                }
            }
            if (warp == 0) STAMP(28);
            wg_wait<0>();
            fence_regs<64>(oc);
        }
        {
            bar_named(3 + wg, 128);
            const uint32_t xw = sb + wg * 2 * SLOT + (tid & 127) * 16, xr = sb + (wg ^ 1) * 2 * SLOT + (tid & 127) * 16;
#pragma unroll
            for (int r = 0; r < 8; r++) {
                const float* o = oc + 4 * r;
                sts128(xw + r * 2048, __float_as_uint(wg ? o[0] : o[32]), __float_as_uint(wg ? o[1] : o[33]), __float_as_uint(wg ? o[2] : o[34]), __float_as_uint(wg ? o[3] : o[35]));
            }
#pragma unroll
            for (int r = 0; r < 32; r++) oc[r] = wg ? oc[32 + r] : oc[r];
            bar_named(1, 256);
            if (warp == 0) STAMP(8);
            const float ga = bf_hi(g0), gb = bf_hi(g1);
            const float ha = bf_round(1.0f - ga), hb = bf_round(1.0f - gb);
            uint32_t w[8][2];
#pragma unroll
            for (int nt = 0; nt < 8; nt++) {
                const uint4 p = lds128(xr + nt * 2048);
                w[nt][0] = pack2(fmaf(ga, oc[4 * nt] + __uint_as_float(p.x), ha * bf_lo(yv[nt].x)), fmaf(ga, oc[4 * nt + 1] + __uint_as_float(p.y), ha * bf_hi(yv[nt].x)));
                w[nt][1] = pack2(fmaf(gb, oc[4 * nt + 2] + __uint_as_float(p.z), hb * bf_lo(yv[nt].y)), fmaf(gb, oc[4 * nt + 3] + __uint_as_float(p.w), hb * bf_hi(yv[nt].y)));
            }
            const uint32_t ob = sb + wg * 2 * SLOT + 16384 + w4 * 2048;
#pragma unroll
            for (int nt = 0; nt < 8; nt += 2)
                stsm4(ob + (lane & 15) * 128 + (((nt + shi) ^ (lane & 7)) << 4), w[nt][0], w[nt][1], w[nt + 1][0], w[nt + 1][1]);
            __syncwarp();
            bf16* op = out + (size_t)(slab * 16) * 512 + (bi_j & 3) * 128 + wg * 64 + (lane & 7) * 8;
#pragma unroll
            for (int it = 0; it < 4; it++) {
                const int r = it * 4 + (lane >> 3);
                uint4 v = lds128(ob + r * 128 + (((lane & 7) ^ (r & 7)) << 4));
                *(uint4*)(op + r * 512) = v;
            }
        }
        if (warp == 0) STAMP(10);
    } else {
        const int st = tid - 256;
        float kc[24];
        const int brow = (buf >> 7) & 7;
#pragma unroll
        for (int t = 0; t < 24; t++) kc[t] = 0.f;
        fence_regs<24>(kc);
        {
            const float dt = bf_round(expf((ch & 1) ? bf_hi(pdt) : bf_lo(pdt)));
#pragma unroll 1
            for (int it = 0; it < KG_ROUNDS; it++) {
                const int sh = (it & 1) * 16;
                auto pick = [&](const uint2& v) { return __uint_as_float(((it & 2 ? v.y : v.x) >> sh) << 16); };
                const float ea = bf_round(expf(pick(pla)));
                const float arl = (-ea * dt) * 1.4426950408889634f, ait = (pick(pai) * dt) * 0.15915494309189535f;
                cf C2; C2.re = 2.0f * (pick(pcr) * dt); C2.im = 2.0f * (pick(pci) * dt);
                const cf z1 = cexp_p(arl, ait, 1.0f), z128 = cexp_p(arl, ait, 128.0f);
                cf z8 = cexp_p(arl, ait, 8.0f); z8.im = -z8.im;
                const uint32_t lp = buf + lane * 4;
                auto put = [&](int row, const cf& v) { sts32((lp ^ (((row + brow) & 7) << 4)) + row * 128, pack2(v.re, v.im)); };
                {
                    const cf z16 = cmul(z8, z8);
                    cf e; e.re = 1.f; e.im = 0.f;
                    cf o = z8;
                    put(0, e); put(1, o);
                    e = z16; put(2, e);
#pragma unroll
                    for (int b = 3; b < 16; b += 2) {
                        o = cmul(o, z16); put(b, o);
                        if (b + 1 < 16) { e = cmul(e, z16); put(b + 1, e); }
                    }
                }
                cf h[8];
                h[0] = C2; put(16, h[0]);
                {
                    const cf z2 = cmul(z1, z1);
                    h[1] = cmul(h[0], z1);
#pragma unroll
                    for (int r = 2; r < 8; r++) h[r] = cmul(h[r - 2], z2);
#pragma unroll
                    for (int r = 1; r < 8; r++) put(16 + r, h[r]);
                }
#pragma unroll
                for (int r = 0; r < 8; r++) { h[r] = cmul(h[r], z128); put(24 + r, h[r]); }
#pragma unroll
                for (int al = 0; al < 2; al++)
#pragma unroll
                    for (int r = 0; r < 4; r++) { h[2 * r] = cmul(h[2 * r], z128); put(32 + al * 4 + r, h[2 * r]); }
#pragma unroll
                for (int al = 0; al < 4; al++)
#pragma unroll
                    for (int r = 0; r < 2; r++) { h[4 * r] = cmul(h[4 * r], z128); put(40 + al * 2 + r, h[4 * r]); }
#pragma unroll
                for (int al = 0; al < 9; al++) { h[0] = cmul(h[0], z128); put(48 + al, h[0]); }
                asm volatile("fence.proxy.async.shared::cta;" ::: "memory");
                bar_named(2, 128);
                uint32_t la[4][4];
#pragma unroll
                for (int ks = 0; ks < 4; ks++) ldsm4(la[ks], buf + (lane & 15) * 128 + (((2 * ks + (lane >> 4)) ^ ((lane + brow) & 7)) << 4));
                const uint64_t dh = mkdesc(sb + OFF_BUF + 2048, 16, 1024);
#pragma unroll
                for (int c = 0; c < 4; c++) {
                    uint32_t a[4][4];
#pragma unroll
                    for (int r = 0; r < 16; r++) a[r >> 2][r & 3] = (c == w4) ? la[r >> 2][r & 3] : 0u;
                    wg_fence();
#pragma unroll
                    for (int ks = 0; ks < 4; ks++) wgmma48_rs(kc, a[ks][0], a[ks][1], a[ks][2], a[ks][3], dh + c * (BUF_STRIDE >> 4) + 2 * ks);
                    wg_commit();
                }
                wg_wait<0>();
                fence_regs<24>(kc);
                bar_named(2, 128);
            }
        }
        if (warp == 8) STAMP(22);
        if (warp == 8) {
            mbar_wait(bar + 8 * BAR_XT, 0);
            if (lane == 0) asm volatile("red.release.gpu.global.add.u32 [%0],8;" ::"l"(scr->xcnt + ((bi_j >> 1) + rot) * 32) : "memory");
        }
        if (lane == 0) {
            int n = 0;
#pragma unroll 1
            while ((int)(ld_acq(scr->xcnt + bi_j * 32) - (epoch1 << 7)) < 0) { __nanosleep(200); if (++n > SPIN_LIMIT) break; }
        }
        __syncwarp();
        if (warp == 8) STAMP(15);
        uint4 ur[8];
#pragma unroll
        for (int v = 0; v < 8; v++) ur[v] = __ldcg(scr->xt + bi * 1024 + st + 128 * v);
        const uint32_t ub = sb + OFF_U + w4 * U_STRIDE + 256;
        if (lane < 16) sts128(ub - 256 + lane * 16, 0, 0, 0, 0);
        if (st < 8) st_rlx32(scr->yflag + bi * 8 + st, tag ^ 1u);
#pragma unroll
        for (int v = 0; v < 8; v++) {
            const int ci = (st >> 2) + 32 * v;
            sts128(sb + OFF_U + (st & 3) * U_STRIDE + 256 + ((ci ^ ((ci >> 3) & 1)) << 4), ur[v].x, ur[v].y, ur[v].z, ur[v].w);
        }
        if (warp == 8) STAMP(16);
        bar_named(2, 128);
        if (lane < 2) sts128(buf + lane * W3_OFF, 0, 0, 0, 0);
        {
#pragma unroll 1
            for (int r2 = 0; r2 < 3; r2++) {
#pragma unroll
                for (int hf = 0; hf < 2; hf++) {
                    const int ci = lane + 32 * (2 * r2 + hf);
                    uint4 e4[4];
#pragma unroll
                    for (int v = 0; v < 4; v++) { const int cc = ci - 3 + v; e4[v] = lds128(ub + ((cc ^ ((cc >> 3) & 1)) << 4)); }
                    float S[29];
                    const uint32_t* ew = (const uint32_t*)e4;
                    S[3] = 0.f;
#pragma unroll
                    for (int k = 4; k <= 28; k++) S[k] = S[k - 1] + ((k & 1) ? bf_hi(ew[k >> 1]) : bf_lo(ew[k >> 1]));
                    auto win = [&](int lo, int hi, uint32_t a, bool on) {
                        const uint32_t w0 = pack2(S[hi] - S[lo - 1], S[hi + 1] - S[lo]), w1 = pack2(S[hi + 2] - S[lo + 1], S[hi + 3] - S[lo + 2]);
                        const uint32_t w2 = pack2(S[hi + 4] - S[lo + 3], S[hi + 5] - S[lo + 4]), w3 = pack2(S[hi + 6] - S[lo + 5], S[hi + 7] - S[lo + 6]);
                        asm volatile("{.reg .pred p; setp.ne.b32 p,%5,0; @p st.shared.v4.b32 [%0],{%1,%2,%3,%4};}" ::"r"(a), "r"(w0), "r"(w1), "r"(w2), "r"(w3), "r"((int)on) : "memory");
                    };
                    const uint32_t sw = (ci ^ ((ci >> 3) & 1)) << 4;
                    win(14, 18, buf + W5_OFF + 16 + ci * 16, true); win(19, 21, buf + W3_OFF + 16 + ci * 16, true); win(4, 12, buf + W9_OFF + sw, r2 < 2);
                }
            }
        }
        if (warp == 8) STAMP(24);
        mbar_wait(bar + 8 * BAR_WO, 0);
        const uint32_t kb_ = sb + (w4 < 2 ? OFF_SP0 : OFF_SP1) + (w4 & 1) * 4096, spare = sb + OFF_X + w4 * 4096;
#pragma unroll
        for (int v = 0; v < 7; v++) if (v * 32 + lane < KT_BYTES / 16) sts128(kb_ + (v * 32 + lane) * 16, 0, 0, 0, 0);
        __syncwarp();
        if (lane == 0) kc[4 * 0 + 0] += ((ch & 1) ? bf_hi(pds) : bf_lo(pds));
        const uint32_t k1024 = __shfl_sync(~0u, pack2(kc[4 * 4 + 0], 0.f), 0);
#pragma unroll
        for (int i = 0; i < 2; i++) {
            const int be = g + 8 * i;
#pragma unroll
            for (int t = 0; t < 2; t++) {
                const uint32_t a = kb_ + (KW_D + 128 * t + 8 * be + 2 * q) * 4;
                const uint32_t w = pack2(kc[4 * t + 2 * i + 1], kc[4 * t + 2 * i]);
                sts32(a + 4, w); sts16(a, w >> 16); sts16(a + 10, w);
            }
            {
                const int p = 256 + 128 * (q >> 1) + 8 * be + 4 * (q & 1);
                const uint32_t a = kb_ + (KW_D + p) * 4;
                const uint32_t w = pack2(kc[4 * 2 + 2 * i + 1], kc[4 * 2 + 2 * i]);
                const uint32_t aa = (w >> 16) | (w & 0xffff0000u);
                if (p != 256) { sts16(a - 4, aa); sts32(a, aa); } else sts16(a, aa);
                sts32(a + 4, aa); sts32(a + 8, w); sts16(a + 14, w);
            }
            {
                const int k = 64 + 16 * q + be;
                const uint32_t w = pack2(kc[4 * 3 + 2 * i], kc[4 * 3 + 2 * i + 1]);
                if (k != 64) sts16(kb_ + (KW_2 + ((k - 1) >> 1) - 24) * 4 + (k & 1) * 2, w);
                else {
                    const uint32_t a = kb_ + (KW_D + 511) * 4, aa = (w << 16) | (w & 0xffffu);
                    sts16(a, w); sts32(a + 4, aa); sts32(a + 8, aa); sts32(a + 12, aa); sts16(a + 18, w);
                }
                sts16(kb_ + (KW_2 + 48 + (k >> 1) - 24) * 4 + ((k & 1) ^ 1) * 2, w >> 16);
            }
#pragma unroll
            for (int b = 0; b < 2; b++) {
                const int k = 64 + 8 * (2 * q + b) + (be >> 1);
                const uint32_t w = pack2(kc[4 * 4 + 2 * i + b], 0.f);
                if (!(be & 1) && k == 64) sts16(kb_ + (KW_2 + 63 - 24) * 4, w);
                else {
                    const uint32_t a = kb_ + (KW_3 + ((be & 1) ? 80 + k : k - 1) - 48) * 4;
                    sts16(a, w);
                    if (!((be & 1) && k == 127)) sts16(a + 6, w);
                }
            }
        }
        if (lane == 0) sts16(kb_ + (KW_3 + 127 - 48) * 4, pack2(kc[4 * 5 + 0], 0.f));
        if (warp == 8) STAMP(17);
        mbar_wait(bar + 8 * BAR_DONE, 0);
        {
#pragma unroll 1
            for (int r2 = 0; r2 < 2; r2++) {
#pragma unroll
                for (int hf = 0; hf < 2; hf++) {
                    const int ci = lane + 32 * (2 * r2 + hf);
                    uint4 e4[4];
#pragma unroll
                    for (int v = 1; v < 4; v++) { const int cc = ci - 3 + v; e4[v] = lds128(ub + ((cc ^ ((cc >> 3) & 1)) << 4)); }
                    float S[29];
                    const uint32_t* ew = (const uint32_t*)e4;
                    S[12] = 0.f;
#pragma unroll
                    for (int k = 13; k <= 28; k++) S[k] = S[k - 1] + ((k & 1) ? bf_hi(ew[k >> 1]) : bf_lo(ew[k >> 1]));
                    auto win = [&](int lo, int hi, uint32_t a, bool on) {
                        const uint32_t w0 = pack2(S[hi] - S[lo - 1], S[hi + 1] - S[lo]), w1 = pack2(S[hi + 2] - S[lo + 1], S[hi + 3] - S[lo + 2]);
                        const uint32_t w2 = pack2(S[hi + 4] - S[lo + 3], S[hi + 5] - S[lo + 4]), w3 = pack2(S[hi + 6] - S[lo + 5], S[hi + 7] - S[lo + 6]);
                        asm volatile("{.reg .pred p; setp.ne.b32 p,%5,0; @p st.shared.v4.b32 [%0],{%1,%2,%3,%4};}" ::"r"(a), "r"(w0), "r"(w1), "r"(w2), "r"(w3), "r"((int)on) : "memory");
                    };
                    const uint32_t sw = (ci ^ ((ci >> 3) & 1)) << 4;
                    win(13, 19, spare + sw, true); win(20, 21, spare + 2048 + sw, true);
                }
            }
        }
        __syncwarp();
        if (warp == 8) STAMP(23);
        float y[16][4];
#pragma unroll
        for (int nt = 0; nt < 16; nt++) { y[nt][0] = y[nt][1] = y[nt][2] = y[nt][3] = 0.f; }
        {
            uint32_t Bp[32], A[5][3], An[5][3];
            auto uaddr = [&](int rho) { const int R0 = (lane >> 4) * 8 + (lane & 7) - rho; return ub + (((2 * R0 + ((lane >> 3) & 1)) ^ ((R0 >> 2) & 1)) << 4); };
            const uint32_t kd = kb_ + (KW_D + g - 2 * q) * 4;
            auto lda = [&](int rho) {
#pragma unroll
                for (int ga = 0; ga < 5; ga++) {
                    const uint32_t a = kd + (ga < 4 ? rho : (rho & 1)) * 64 + ga * 512;
                    An[ga][0] = lds32(a); An[ga][1] = lds32(a + 32); An[ga][2] = lds32(a - 32);
                }
            };
            lda(0);
            {
                const uint32_t a = uaddr(0);
#pragma unroll
                for (int p = 0; p < 8; p++) ldsm4(Bp + 4 * p, a + p * 512);
            }
#pragma unroll 1
            for (int rho = 0; rho < 8; rho++) {
#pragma unroll
                for (int r = 0; r < 15; r++) A[r / 3][r % 3] = An[r / 3][r % 3];
                lda(rho + 1);
                if (rho < 2) {
#pragma unroll
                    for (int nt = 4; nt < 16; nt++) mma16816(y[nt], A[4][0], A[4][1], A[4][2], A[4][0], Bp[2 * (nt - 4)], Bp[2 * (nt - 4) + 1]);
                }
#pragma unroll
                for (int ga = 0; ga < 3; ga++)
#pragma unroll
                    for (int nt = 15; nt >= ga; nt--) mma16816(y[nt], A[ga][0], A[ga][1], A[ga][2], A[ga][0], Bp[2 * (nt - ga)], Bp[2 * (nt - ga) + 1]);
                const uint32_t an = uaddr(rho + 1);
                ldsm4(Bp + 28, an + 7 * 512);
#pragma unroll
                for (int nt = 15; nt >= 3; nt--) {
                    mma16816(y[nt], A[3][0], A[3][1], A[3][2], A[3][0], Bp[2 * (nt - 3)], Bp[2 * (nt - 3) + 1]);
                    if (nt & 1) ldsm4(Bp + 2 * (nt - 3), an + ((nt - 3) >> 1) * 512);
                }
            }
        }
        if (warp == 8) STAMP(18);
#pragma unroll 1
        for (int ph = 0; ph < 2; ph++) {
            uint32_t B[5][2];
            const uint32_t ka = kb_ + (KW_2 + ph * 48 + 8 + g - q) * 4;
#pragma unroll
            for (int dd = 0; dd < 5; dd++) { B[dd][0] = lds32(ka + dd * 32); B[dd][1] = lds32(ka + dd * 32 - 16); }
            const uint32_t wa = buf + ph * W3_OFF + ((lane & 7) + ((lane >> 3) & 1) + (lane >> 4) * 8) * 16;
#pragma unroll
            for (int s = 0; s < 12; s++) {
                uint32_t A[4];
                ldsm4t(A, wa + s * 256);
#pragma unroll
                for (int dd = 0; dd < 5; dd++)
                    if (s + 4 + dd < 16) mma16816(y[s + 4 + dd], A[0], A[1], A[2], A[3], B[dd][0], B[dd][1]);
            }
        }
        {
            const int ap = (lane & 7) + (lane >> 4) * 8;
            const uint32_t loff = ((2 * ap + ((lane >> 3) & 1)) ^ ((ap >> 2) & 1)) << 4;
#pragma unroll 1
            for (int ph = 0; ph < 2; ph++) {
                uint32_t B[8][2];
                const uint32_t wb = (ph ? spare : buf + W9_OFF) + loff;
                const uint32_t ka = kb_ + (KW_3 + ph * 80 + 16 + g - 2 * q) * 4;
#pragma unroll
                for (int dd = 0; dd < 8; dd++) { B[dd][0] = lds32(ka + dd * 32); B[dd][1] = lds32(ka + dd * 32 - 32); }
#pragma unroll
                for (int s = 0; s < 4; s++) {
                    uint32_t A[4];
                    ldsm4t(A, wb + s * 512);
#pragma unroll
                    for (int dd = 0; dd < 8; dd++)
                        if (8 + 2 * s + dd < 16) mma16816(y[8 + 2 * s + dd], A[0], A[1], A[2], A[3], B[dd][0], B[dd][1]);
                }
            }
            const uint32_t idw = (g == 2 * q) ? k1024 : ((g == 2 * q + 1) ? (k1024 << 16) : 0u);
#pragma unroll
            for (int s = 0; s < 4; s++) {
                uint32_t A[4];
                ldsm4t(A, spare + 2048 + loff + s * 512);
                mma16816(y[8 + 2 * s], A[0], A[1], A[2], A[3], idw, 0u);
                mma16816(y[9 + 2 * s], A[0], A[1], A[2], A[3], 0u, idw);
            }
        }
        __syncwarp();
        if (warp == 8) STAMP(19);
#pragma unroll
        for (int nt = 0; nt < 16; nt++)
#pragma unroll
            for (int b = 0; b < 2; b++) sts32(buf + ((8 * nt + 2 * q + b) * 8 + g) * 4, pack2(y[nt][b], y[nt][2 + b]));
        bar_named(2, 128);
        uint4* yp = scr->y + bi * 1024 + st;
#pragma unroll
        for (int v = 0; v < 8; v++) {
            const uint32_t a = sb + OFF_BUF + (st + 128 * v) * 4;
            const uint32_t w0 = lds32(a), w1 = lds32(a + BUF_STRIDE), w2 = lds32(a + 2 * BUF_STRIDE), w3 = lds32(a + 3 * BUF_STRIDE);
            st_rlx128(yp + v * 128, tag4(__byte_perm(w0, w1, 0x5410), __byte_perm(w0, w1, 0x7632), __byte_perm(w2, w3, 0x5410), __byte_perm(w2, w3, 0x7632), tag));
        }
        if (st < 8) st_rlx32(scr->yflag + bi * 8 + st, tag);
        if (warp == 8) STAMP(20);
    }
    __syncthreads();
    if (tid == 0) atomicAdd(scr->done, 1u);
}

typedef CUresult (*EncFn)(CUtensorMap*, CUtensorMapDataType, cuuint32_t, void*, const cuuint64_t*, const cuuint64_t*, const cuuint32_t*,
                          const cuuint32_t*, CUtensorMapInterleave, CUtensorMapSwizzle, CUtensorMapL2promotion, CUtensorMapFloatOOBfill);

extern "C" void kernel_launch(void* const* d_in, const int* in_sizes, int n_in, void* d_out, int out_size) {
    static EncFn enc = nullptr;
    static Scratch* scr = nullptr;
    if (!enc) {
        cudaGetSymbolAddress((void**)&scr, g_scr);
        cudaDriverEntryPointQueryResult qr;
        cudaGetDriverEntryPoint("cuTensorMapEncodeTiled", (void**)&enc, cudaEnableDefault, &qr);
        cudaFuncSetAttribute(fused_kernel, cudaFuncAttributeMaxDynamicSharedMemorySize, SMEM_BYTES);
    }
    CUtensorMap mx, mw, mwo;
    const cuuint32_t es[3] = {1, 1, 1};
    {
        cuuint64_t d[2] = {512, 2048}, s[1] = {1024}; cuuint32_t b[2] = {64, 128};
        enc(&mx, CU_TENSOR_MAP_DATA_TYPE_BFLOAT16, 2, d_in[0], d, s, b, es, CU_TENSOR_MAP_INTERLEAVE_NONE, CU_TENSOR_MAP_SWIZZLE_128B,
            CU_TENSOR_MAP_L2_PROMOTION_L2_128B, CU_TENSOR_MAP_FLOAT_OOB_FILL_NONE);
    }
    {
        cuuint64_t d[3] = {512, 512, 3}, s[2] = {3072, 1024}; cuuint32_t b[3] = {64, 64, 3};
        enc(&mw, CU_TENSOR_MAP_DATA_TYPE_BFLOAT16, 3, d_in[1], d, s, b, es, CU_TENSOR_MAP_INTERLEAVE_NONE, CU_TENSOR_MAP_SWIZZLE_128B,
            CU_TENSOR_MAP_L2_PROMOTION_L2_128B, CU_TENSOR_MAP_FLOAT_OOB_FILL_NONE);
    }
    {
        cuuint64_t d[2] = {512, 512}, s[1] = {1024}; cuuint32_t b[2] = {64, 256};
        enc(&mwo, CU_TENSOR_MAP_DATA_TYPE_BFLOAT16, 2, d_in[3], d, s, b, es, CU_TENSOR_MAP_INTERLEAVE_NONE, CU_TENSOR_MAP_SWIZZLE_128B,
            CU_TENSOR_MAP_L2_PROMOTION_L2_128B, CU_TENSOR_MAP_FLOAT_OOB_FILL_NONE);
    }
    fused_kernel<<<128, 384, SMEM_BYTES, cudaStreamPerThread>>>(
        scr, (const bf16*)d_in[5], (const bf16*)d_in[6], (const bf16*)d_in[7], (const bf16*)d_in[8], (const bf16*)d_in[9],
        (const bf16*)d_in[10], (const bf16*)d_in[2], (const bf16*)d_in[11], (bf16*)d_out, mx, mw, mwo);
}
```

```cpp
#include <cuda_runtime.h>
#include <cuda.h>
#include <cuda_bf16.h>
#include <stdint.h>

typedef __nv_bfloat16 bf16;

struct Scratch {
    uint4 xt[128 * 1024];
    uint4 o[16 * 8 * 32 * 32];
    uint4 y[128 * 1024];
    uint4 kvp[8 * 16 * 544];
    uint4 kvf[8 * 4 * 68];
    unsigned g[1024 * 8];
    unsigned yflag[128 * 8];
    unsigned xcnt[8 * 32];
    unsigned done[32];
};
__device__ Scratch g_scr;
#define STAMP(n)

constexpr int SLOT = 40960;
constexpr int OFF_SP0 = 32768, OFF_SP1 = SLOT + 32768;
constexpr int OFF_P = 2 * SLOT, OFF_V = OFF_P + 32768;
constexpr int OFF_KVF = OFF_V + 32768;
constexpr int KT_BYTES = 3264, KW_D = 16, KW_2 = 560, KW_3 = 656;
constexpr int OFF_U = 4 * SLOT, U_STRIDE = 4096 + 256 + 32;
constexpr int OFF_BUF = OFF_U + 4 * U_STRIDE, BUF_STRIDE = 8320;
constexpr int OFF_K = OFF_BUF + 4 * BUF_STRIDE;
constexpr int OFF_WPHI = OFF_K + 4 * KT_BYTES;
constexpr int OFF_GW = OFF_WPHI + 2048;
constexpr int OFF_BAR = OFF_GW + 1024;
constexpr int SMEM_BYTES = OFF_BAR + 128 + 128;
static_assert(SMEM_BYTES <= 232448 && OFF_BUF % 128 == 0, "smem");
constexpr int W5_OFF = 0, W3_OFF = 3088, W9_OFF = 6176;
constexpr int BAR_FULL = 0, BAR_WPHI = 4, BAR_WO = 5, BAR_XT = 6, BAR_DONE = 7, BAR_WO2 = 8, BAR_GO = 9, BAR_KG = 10, OFF_CNT = 96;
#define KG_ROUNDS 4
constexpr int SPIN_LIMIT = 1 << 17;

__device__ __forceinline__ uint32_t s2u(const void* p) { return (uint32_t)__cvta_generic_to_shared(p); }
__device__ __forceinline__ void mbar_init(uint32_t b, int c) { asm volatile("mbarrier.init.shared::cta.b64 [%0],%1;" ::"r"(b), "r"(c) : "memory"); }
__device__ __forceinline__ void mbar_expect(uint32_t b, int bytes) { asm volatile("mbarrier.arrive.expect_tx.shared::cta.b64 _,[%0],%1;" ::"r"(b), "r"(bytes) : "memory"); }
__device__ __forceinline__ void mbar_arrive(uint32_t b) { asm volatile("mbarrier.arrive.shared::cta.b64 _,[%0];" ::"r"(b) : "memory"); }
__device__ __forceinline__ void mbar_wait(uint32_t b, int ph) {
    asm volatile("{\n.reg .pred p;\n.reg .u32 n;\nmov.u32 n,0;\nLW_%=:\nmbarrier.try_wait.parity.shared::cta.b64 p,[%0],%1;\n@p bra LD_%=;\n"
                 "add.u32 n,n,1;\nsetp.lt.u32 p,n,131072;\n@p bra LW_%=;\nLD_%=:\n}" ::"r"(b), "r"(ph) : "memory");
}
__device__ __forceinline__ void tma2d(uint32_t dst, const CUtensorMap* m, int c0, int c1, uint32_t bar) {
    asm volatile("cp.async.bulk.tensor.2d.shared::cluster.global.mbarrier::complete_tx::bytes [%0],[%1,{%3,%4}],[%2];" ::"r"(dst), "l"(m), "r"(bar), "r"(c0), "r"(c1) : "memory");
}
__device__ __forceinline__ void tma3d(uint32_t dst, const CUtensorMap* m, int c0, int c1, int c2, uint32_t bar) {
    asm volatile("cp.async.bulk.tensor.3d.shared::cluster.global.mbarrier::complete_tx::bytes [%0],[%1,{%3,%4,%5}],[%2];" ::"r"(dst), "l"(m), "r"(bar), "r"(c0), "r"(c1), "r"(c2) : "memory");
}
__device__ __forceinline__ void bulk_g2s(uint32_t dst, const void* src, int bytes, uint32_t bar) {
    asm volatile("cp.async.bulk.shared::cluster.global.mbarrier::complete_tx::bytes [%0],[%1],%2,[%3];" ::"r"(dst), "l"(src), "r"(bytes), "r"(bar) : "memory");
}
__device__ __forceinline__ uint64_t mkdesc(uint32_t addr, uint32_t lbo, uint32_t sbo) {
    return (uint64_t)((addr & 0x3FFFF) >> 4) | ((uint64_t)(lbo >> 4) << 16) | ((uint64_t)(sbo >> 4) << 32) | ((uint64_t)1 << 62);
}
__device__ __forceinline__ void wg_fence() { asm volatile("wgmma.fence.sync.aligned;" ::: "memory"); }
__device__ __forceinline__ void wg_commit() { asm volatile("wgmma.commit_group.sync.aligned;" ::: "memory"); }
template <int N> __device__ __forceinline__ void wg_wait() { asm volatile("wgmma.wait_group.sync.aligned %0;" ::"n"(N) : "memory"); }
template <int N> __device__ __forceinline__ void fence_regs(float* d) {
#pragma unroll
    for (int i = 0; i < N; i++) asm volatile("" : "+f"(d[i])::"memory");
}
#define R8(d, o) "+f"(d[o]), "+f"(d[o + 1]), "+f"(d[o + 2]), "+f"(d[o + 3]), "+f"(d[o + 4]), "+f"(d[o + 5]), "+f"(d[o + 6]), "+f"(d[o + 7])
__device__ __forceinline__ void wgmma192(float* d, uint64_t da, uint64_t db) {
    asm volatile("wgmma.mma_async.sync.aligned.m64n192k16.f32.bf16.bf16 {"
                 "%0,%1,%2,%3,%4,%5,%6,%7,%8,%9,%10,%11,%12,%13,%14,%15,%16,%17,%18,%19,%20,%21,%22,%23,%24,%25,%26,%27,%28,%29,%30,%31,"
                 "%32,%33,%34,%35,%36,%37,%38,%39,%40,%41,%42,%43,%44,%45,%46,%47,%48,%49,%50,%51,%52,%53,%54,%55,%56,%57,%58,%59,%60,%61,%62,%63,"
                 "%64,%65,%66,%67,%68,%69,%70,%71,%72,%73,%74,%75,%76,%77,%78,%79,%80,%81,%82,%83,%84,%85,%86,%87,%88,%89,%90,%91,%92,%93,%94,%95},"
                 "%96,%97,1,1,1,0,1;"
                 : R8(d, 0), R8(d, 8), R8(d, 16), R8(d, 24), R8(d, 32), R8(d, 40), R8(d, 48), R8(d, 56), R8(d, 64), R8(d, 72), R8(d, 80), R8(d, 88)
                 : "l"(da), "l"(db));
}
__device__ __forceinline__ void wgmma64_tt(float* d, uint64_t da, uint64_t db, int sc) {
    asm volatile("{.reg .pred p; setp.ne.b32 p,%34,0; wgmma.mma_async.sync.aligned.m64n64k16.f32.bf16.bf16 {"
                 "%0,%1,%2,%3,%4,%5,%6,%7,%8,%9,%10,%11,%12,%13,%14,%15,%16,%17,%18,%19,%20,%21,%22,%23,%24,%25,%26,%27,%28,%29,%30,%31},"
                 "%32,%33,p,1,1,1,1;}"
                 : R8(d, 0), R8(d, 8), R8(d, 16), R8(d, 24)
                 : "l"(da), "l"(db), "r"(sc));
}
__device__ __forceinline__ void wgmma128_rs(float* d, const uint4& a, uint64_t db, int sc) {
    asm volatile("{.reg .pred p; setp.ne.b32 p,%69,0; wgmma.mma_async.sync.aligned.m64n128k16.f32.bf16.bf16 {"
                 "%0,%1,%2,%3,%4,%5,%6,%7,%8,%9,%10,%11,%12,%13,%14,%15,%16,%17,%18,%19,%20,%21,%22,%23,%24,%25,%26,%27,%28,%29,%30,%31,"
                 "%32,%33,%34,%35,%36,%37,%38,%39,%40,%41,%42,%43,%44,%45,%46,%47,%48,%49,%50,%51,%52,%53,%54,%55,%56,%57,%58,%59,%60,%61,%62,%63},"
                 "{%64,%65,%66,%67},%68,p,1,1,1;}"
                 : R8(d, 0), R8(d, 8), R8(d, 16), R8(d, 24), R8(d, 32), R8(d, 40), R8(d, 48), R8(d, 56)
                 : "r"(a.x), "r"(a.y), "r"(a.z), "r"(a.w), "l"(db), "r"(sc));
}
__device__ __forceinline__ void mma16816(float* c, uint32_t a0, uint32_t a1, uint32_t a2, uint32_t a3, uint32_t b0, uint32_t b1) {
    asm("mma.sync.aligned.m16n8k16.row.col.f32.bf16.bf16.f32 {%0,%1,%2,%3},{%4,%5,%6,%7},{%8,%9},{%0,%1,%2,%3};"
        : "+f"(c[0]), "+f"(c[1]), "+f"(c[2]), "+f"(c[3]) : "r"(a0), "r"(a1), "r"(a2), "r"(a3), "r"(b0), "r"(b1));
}
__device__ __forceinline__ void ldsm4(uint32_t* r, uint32_t a) {
    asm volatile("ldmatrix.sync.aligned.m8n8.x4.shared.b16 {%0,%1,%2,%3},[%4];" : "=r"(r[0]), "=r"(r[1]), "=r"(r[2]), "=r"(r[3]) : "r"(a) : "memory");
}
__device__ __forceinline__ void ldsm4t(uint32_t* r, uint32_t a) {
    asm volatile("ldmatrix.sync.aligned.m8n8.x4.trans.shared.b16 {%0,%1,%2,%3},[%4];" : "=r"(r[0]), "=r"(r[1]), "=r"(r[2]), "=r"(r[3]) : "r"(a) : "memory");
}
__device__ __forceinline__ void stsm4(uint32_t a, uint32_t r0, uint32_t r1, uint32_t r2, uint32_t r3) {
    asm volatile("stmatrix.sync.aligned.m8n8.x4.shared.b16 [%0],{%1,%2,%3,%4};" ::"r"(a), "r"(r0), "r"(r1), "r"(r2), "r"(r3) : "memory");
}
__device__ __forceinline__ uint32_t lds32(uint32_t a) { uint32_t v; asm volatile("ld.shared.b32 %0,[%1];" : "=r"(v) : "r"(a) : "memory"); return v; }
__device__ __forceinline__ uint4 lds128(uint32_t a) { uint4 v; asm volatile("ld.shared.v4.b32 {%0,%1,%2,%3},[%4];" : "=r"(v.x), "=r"(v.y), "=r"(v.z), "=r"(v.w) : "r"(a) : "memory"); return v; }
__device__ __forceinline__ void sts16(uint32_t a, uint32_t v) { asm volatile("st.shared.b16 [%0],%1;" ::"r"(a), "h"((unsigned short)v) : "memory"); }
__device__ __forceinline__ void sts32(uint32_t a, uint32_t v) { asm volatile("st.shared.b32 [%0],%1;" ::"r"(a), "r"(v) : "memory"); }
__device__ __forceinline__ void sts64(uint32_t a, uint32_t x, uint32_t y) { asm volatile("st.shared.v2.b32 [%0],{%1,%2};" ::"r"(a), "r"(x), "r"(y) : "memory"); }
__device__ __forceinline__ void sts128(uint32_t a, uint32_t x, uint32_t y, uint32_t z, uint32_t w) { asm volatile("st.shared.v4.b32 [%0],{%1,%2,%3,%4};" ::"r"(a), "r"(x), "r"(y), "r"(z), "r"(w) : "memory"); }
__device__ __forceinline__ uint32_t pack2(float lo, float hi) { uint32_t d; asm("cvt.rn.bf16x2.f32 %0,%1,%2;" : "=r"(d) : "f"(hi), "f"(lo)); return d; }
__device__ __forceinline__ float bf_lo(uint32_t v) { return __uint_as_float(v << 16); }
__device__ __forceinline__ float bf_hi(uint32_t v) { return __uint_as_float(v & 0xffff0000u); }
__device__ __forceinline__ float bf_round(float v) { return bf_lo(pack2(v, 0.f)); }
__device__ __forceinline__ uint32_t hmax2(uint32_t a, uint32_t b) { uint32_t d; asm("max.bf16x2 %0,%1,%2;" : "=r"(d) : "r"(a), "r"(b)); return d; }
__device__ __forceinline__ uint32_t hmin2(uint32_t a, uint32_t b) { uint32_t d; asm("min.bf16x2 %0,%1,%2;" : "=r"(d) : "r"(a), "r"(b)); return d; }
__device__ __forceinline__ uint32_t hmul2(uint32_t a, uint32_t b) { uint32_t d; asm("mul.rn.bf16x2 %0,%1,%2;" : "=r"(d) : "r"(a), "r"(b)); return d; }
__device__ __forceinline__ float ex2(float x) { float y; asm("ex2.approx.ftz.f32 %0,%1;" : "=f"(y) : "f"(x)); return y; }
__device__ __forceinline__ float rcp(float x) { float y; asm("rcp.approx.ftz.f32 %0,%1;" : "=f"(y) : "f"(x)); return y; }
__device__ __forceinline__ uint32_t ld_nc(const uint32_t* p) { uint32_t v; asm volatile("ld.global.nc.b32 %0,[%1];" : "=r"(v) : "l"(p)); return v; }
__device__ __forceinline__ uint2 ld_nc64(const uint2* p) { uint2 v; asm volatile("ld.global.nc.v2.b32 {%0,%1},[%2];" : "=r"(v.x), "=r"(v.y) : "l"(p)); return v; }
__device__ __forceinline__ unsigned ld_acq(const unsigned* p) { unsigned v; asm volatile("ld.acquire.gpu.global.u32 %0,[%1];" : "=r"(v) : "l"(p) : "memory"); return v; }
__device__ __forceinline__ unsigned ld_rlx(const unsigned* p) { unsigned v; asm volatile("ld.relaxed.gpu.global.u32 %0,[%1];" : "=r"(v) : "l"(p) : "memory"); return v; }
__device__ __forceinline__ uint2 ld_rlx64(const void* p) { uint2 v; asm volatile("{.reg .b64 t; ld.relaxed.gpu.global.b64 t,[%2]; mov.b64 {%0,%1},t;}" : "=r"(v.x), "=r"(v.y) : "l"(p) : "memory"); return v; }
__device__ __forceinline__ uint4 ld_rlx128(const void* p) {
    uint4 v;
    asm volatile("{.reg .b64 t,u; ld.relaxed.gpu.global.v2.b64 {t,u},[%4]; mov.b64 {%0,%1},t; mov.b64 {%2,%3},u;}" : "=r"(v.x), "=r"(v.y), "=r"(v.z), "=r"(v.w) : "l"(p) : "memory");
    return v;
}
__device__ __forceinline__ void st_rlx32(void* p, uint32_t x) { asm volatile("st.relaxed.gpu.global.u32 [%0],%1;" ::"l"(p), "r"(x) : "memory"); }
__device__ __forceinline__ void st_rlx64(void* p, uint32_t x, uint32_t y) { asm volatile("{.reg .b64 t; mov.b64 t,{%1,%2}; st.relaxed.gpu.global.b64 [%0],t;}" ::"l"(p), "r"(x), "r"(y) : "memory"); }
__device__ __forceinline__ void st_rlx128(void* p, uint4 v) {
    asm volatile("{.reg .b64 t,u; mov.b64 t,{%1,%2}; mov.b64 u,{%3,%4}; st.relaxed.gpu.global.v2.b64 [%0],{t,u};}" ::"l"(p), "r"(v.x), "r"(v.y), "r"(v.z), "r"(v.w) : "memory");
}
__device__ __forceinline__ uint32_t tagw(uint32_t w, uint32_t tag) { return (w & ~1u) | tag; }
__device__ __forceinline__ uint4 tag4(uint32_t x, uint32_t y, uint32_t z, uint32_t w, uint32_t tag) { return make_uint4(tagw(x, tag), y, tagw(z, tag), w); }
__device__ __forceinline__ uint32_t bad4(const uint4& v, uint32_t tag) { return (v.x ^ tag) | (v.z ^ tag); }
__device__ __forceinline__ void bar_named(int id, int n) { asm volatile("bar.sync %0,%1;" ::"r"(id), "r"(n) : "memory"); }

struct cf { float re, im; };
__device__ __forceinline__ cf cmul(cf a, cf b) { cf r; r.re = a.re * b.re - a.im * b.im; r.im = a.re * b.im + a.im * b.re; return r; }
__device__ __forceinline__ cf cexp_p(float arl, float ait, float p) {
    float mag = ex2(arl * p);
    float t = ait * p;
    t = (t - rintf(t)) * 6.283185307179586f;
    cf r; r.re = mag * __cosf(t); r.im = mag * __sinf(t);
    return r;
}

__device__ __forceinline__ void hedgehog2(const uint32_t* a, uint32_t wphi_addr, uint32_t (*out)[8]) {
    float p[2][2][4], mx[2][2];
#pragma unroll
    for (int h = 0; h < 2; h++) {
        uint32_t b[4];
        ldsm4t(b, wphi_addr + h * 512);
        float c0[4] = {0.f, 0.f, 0.f, 0.f}, c1[4] = {0.f, 0.f, 0.f, 0.f};
        mma16816(c0, a[4 * h], a[4 * h + 1], a[4 * h + 2], a[4 * h + 3], b[0], b[1]);
        mma16816(c1, a[4 * h], a[4 * h + 1], a[4 * h + 2], a[4 * h + 3], b[2], b[3]);
#pragma unroll
        for (int k = 0; k < 2; k++) {
            p[h][k][0] = c0[2 * k]; p[h][k][1] = c0[2 * k + 1]; p[h][k][2] = c1[2 * k]; p[h][k][3] = c1[2 * k + 1];
            mx[h][k] = fmaxf(fmaxf(p[h][k][0], p[h][k][1]), fmaxf(p[h][k][2], p[h][k][3]));
        }
    }
#pragma unroll
    for (int o = 1; o <= 2; o <<= 1)
#pragma unroll
        for (int h = 0; h < 2; h++)
#pragma unroll
            for (int k = 0; k < 2; k++) mx[h][k] = fmaxf(mx[h][k], __shfl_xor_sync(~0u, mx[h][k], o));
    const float L = 1.4426950408889634f;
    float pmin = 1.f;
#pragma unroll
    for (int h = 0; h < 2; h++)
#pragma unroll
        for (int k = 0; k < 2; k++) {
            const float m = -mx[h][k] * L;
            const float e0 = ex2(fmaf(p[h][k][0], L, m)), e1 = ex2(fmaf(p[h][k][1], L, m)), e2 = ex2(fmaf(p[h][k][2], L, m)), e3 = ex2(fmaf(p[h][k][3], L, m));
            const float p01 = e0 * e1, p23 = e2 * e3, pp = p01 * p23, r = rcp(pp), r01 = r * p23, r23 = r * p01;
            pmin = fminf(pmin, pp);
            out[h][k] = pack2(e0, e1); out[h][k + 2] = pack2(e2, e3);
            out[h][4 + k] = pack2(r01 * e1, r01 * e0); out[h][4 + k + 2] = pack2(r23 * e3, r23 * e2);
        }
    if (__builtin_expect(__any_sync(~0u, !(pmin > 1e-18f)), 0)) {
#pragma unroll
        for (int h = 0; h < 2; h++)
#pragma unroll
            for (int k = 0; k < 2; k++) {
                float m = fminf(fminf(p[h][k][0], p[h][k][1]), fminf(p[h][k][2], p[h][k][3]));
                m = fminf(m, __shfl_xor_sync(~0u, m, 1));
                m = fminf(m, __shfl_xor_sync(~0u, m, 2)) * L;
                out[h][4 + k] = pack2(ex2(fmaf(p[h][k][0], -L, m)), ex2(fmaf(p[h][k][1], -L, m)));
                out[h][4 + k + 2] = pack2(ex2(fmaf(p[h][k][2], -L, m)), ex2(fmaf(p[h][k][3], -L, m)));
            }
    }
}

__global__ void __launch_bounds__(384, 1)
fused_kernel(Scratch* __restrict__ scr, const bf16* __restrict__ logA, const bf16* __restrict__ Aim, const bf16* __restrict__ Cre,
             const bf16* __restrict__ Cim, const bf16* __restrict__ logdt, const bf16* __restrict__ Dskip, const bf16* __restrict__ wphi,
             const bf16* __restrict__ gatew, bf16* __restrict__ out,
             const __grid_constant__ CUtensorMap mx, const __grid_constant__ CUtensorMap mw, const __grid_constant__ CUtensorMap mwo) {
    extern __shared__ __align__(1024) uint8_t smem[];
    const uint32_t sb = s2u(smem);
    const int tid = threadIdx.x, warp = __shfl_sync(~0u, tid >> 5, 0), lane = tid & 31;
    const int g = lane >> 2, q = lane & 3, w4 = warp & 3;
    const int bi = blockIdx.x, bi_i = bi & 15, bi_j = bi >> 4;
    const uint32_t bar = sb + OFF_BAR;
    const int rot = (bi_j & 1) * 4;
    auto load_stage = [&](int kb) {
        const uint32_t b = bar + 8 * (BAR_FULL + (kb & 3)), d = sb + (kb & 3) * SLOT;
        const int kc = ((kb + rot) & 7) * 64;
        mbar_expect(b, SLOT);
        tma2d(d, &mx, kc, bi_i * 128, b);
        tma3d(d + 16384, &mw, bi_j * 64, kc, 0, b);
    };

    const int ch = bi * 4 + w4;
    const int pidx = ch * 64 + lane * 2 + (warp < 8);
    const uint32_t pla = ld_nc((const uint32_t*)logA + pidx), pai = ld_nc((const uint32_t*)Aim + pidx);
    const uint32_t pcr = ld_nc((const uint32_t*)Cre + pidx), pci = ld_nc((const uint32_t*)Cim + pidx);
    uint32_t pdt = ld_nc((const uint32_t*)logdt + (ch >> 1));
    const uint32_t pds = ld_nc((const uint32_t*)Dskip + (ch >> 1));
    unsigned done0 = ld_rlx(scr->done);
    if (tid == 0) {
        for (int s = 0; s < 4; s++) mbar_init(bar + 8 * (BAR_FULL + s), 1);
        asm volatile("fence.mbarrier_init.release.cluster;" ::: "memory");
#pragma unroll 1
        for (int s = 0; s < 3; s++) load_stage(s);
        STAMP(11);
    } else if (tid == 32) {
        if (sb & 1023) __trap();
        for (int s = 0; s < 5; s++) sts32(bar + OFF_CNT + 4 * s, 0);
        mbar_init(bar + 8 * BAR_WPHI, 1); mbar_init(bar + 8 * BAR_WO, 2); mbar_init(bar + 8 * BAR_XT, 8); mbar_init(bar + 8 * BAR_DONE, 8);
        mbar_init(bar + 8 * BAR_WO2, 1); mbar_init(bar + 8 * BAR_GO, 1); mbar_init(bar + 8 * BAR_KG, 8);
        asm volatile("fence.mbarrier_init.release.cluster;" ::: "memory");
        mbar_expect(bar + 8 * BAR_WPHI, 3072);
        bulk_g2s(sb + OFF_GW, gatew, 1024, bar + 8 * BAR_WPHI);
        bulk_g2s(sb + OFF_WPHI, wphi + bi_j * 1024, 2048, bar + 8 * BAR_WPHI);
    } else if (tid == 64) {
        asm volatile("prefetch.tensormap [%0];" ::"l"(&mw) : "memory");
    }
    const uint32_t buf = sb + OFF_BUF + w4 * BUF_STRIDE, kb_ = sb + OFF_K + w4 * KT_BYTES;
    if (warp >= 8) {
#pragma unroll
        for (int v = 0; v < 7; v++) if (v * 32 + lane < KT_BYTES / 16) sts128(kb_ + (v * 32 + lane) * 16, 0, 0, 0, 0);
    }
    __syncthreads();
    asm volatile("" : "+r"(pdt), "+r"(done0)::"memory");
    const unsigned epoch1 = (done0 >> 7) + 1u;
    const uint32_t tag = epoch1 & 1u;

    const int st = tid - 256;
    const uint32_t ub = sb + OFF_U + w4 * U_STRIDE + 256, spare = sb + (w4 < 2 ? OFF_SP0 : OFF_SP1) + (w4 & 1) * 4096;
    float kc[24];
#pragma unroll
    for (int t = 0; t < 24; t++) kc[t] = 0.f;
    {
        const float dt = bf_round(expf((ch & 1) ? bf_hi(pdt) : bf_lo(pdt)));
        const uint32_t stg = (warp < 8) ? sb + 3 * SLOT + warp * 7296 : buf;
#pragma unroll 1
        for (int it = 0; it < 2; it++) {
            {
                const int sh = (warp < 8 ? (warp >> 2) : it) * 16;
                auto pick = [&](uint32_t v) { return __uint_as_float((v >> sh) << 16); };
                const float ea = bf_round(expf(pick(pla)));
                const float arl = (-ea * dt) * 1.4426950408889634f, ait = (pick(pai) * dt) * 0.15915494309189535f;
                cf C2; C2.re = 2.0f * (pick(pcr) * dt); C2.im = 2.0f * (pick(pci) * dt);
                const cf z1 = cexp_p(arl, ait, 1.0f), z128 = cexp_p(arl, ait, 128.0f);
                cf z8 = cexp_p(arl, ait, 8.0f); z8.im = -z8.im;
                const uint32_t lp = stg + lane * 4;
                auto put = [&](int row, const cf& v) { sts32((lp ^ ((row & 7) << 4)) + row * 128, pack2(v.re, v.im)); };
                {
                    const cf z16 = cmul(z8, z8);
                    cf e; e.re = 1.f; e.im = 0.f;
                    cf o = z8;
                    put(0, e); put(1, o);
                    e = z16; put(2, e);
#pragma unroll
                    for (int b = 3; b < 16; b += 2) {
                        o = cmul(o, z16); put(b, o);
                        if (b + 1 < 16) { e = cmul(e, z16); put(b + 1, e); }
                    }
                }
                cf h[8];
                h[0] = C2; put(16, h[0]);
                {
                    const cf z2 = cmul(z1, z1);
                    h[1] = cmul(h[0], z1);
#pragma unroll
                    for (int r = 2; r < 8; r++) h[r] = cmul(h[r - 2], z2);
#pragma unroll
                    for (int r = 1; r < 8; r++) put(16 + r, h[r]);
                }
#pragma unroll
                for (int r = 0; r < 8; r++) { h[r] = cmul(h[r], z128); put(24 + r, h[r]); }
#pragma unroll
                for (int al = 0; al < 2; al++)
#pragma unroll
                    for (int r = 0; r < 4; r++) { h[2 * r] = cmul(h[2 * r], z128); put(32 + al * 4 + r, h[2 * r]); }
#pragma unroll
                for (int al = 0; al < 4; al++)
#pragma unroll
                    for (int r = 0; r < 2; r++) { h[4 * r] = cmul(h[4 * r], z128); put(40 + al * 2 + r, h[4 * r]); }
#pragma unroll
                for (int al = 0; al < 9; al++) { h[0] = cmul(h[0], z128); put(48 + al, h[0]); }
                __syncwarp();
            }
            const int lr = lane & 7, lm = lane >> 3;
#pragma unroll
            for (int kp = 0; kp < 2; kp++) {
                uint32_t a0[4], a1[4];
                ldsm4(a0, stg + ((lm & 1) * 8 + lr) * 128 + (((4 * kp + (lm >> 1)) ^ lr) << 4));
                ldsm4(a1, stg + ((lm & 1) * 8 + lr) * 128 + (((4 * kp + 2 + (lm >> 1)) ^ lr) << 4));
#pragma unroll
                for (int t = 0; t < 6; t++) {
                    uint32_t b[4];
                    ldsm4(b, stg + (16 + 8 * t + lr) * 128 + (((4 * kp + lm) ^ lr) << 4));
                    mma16816(kc + 4 * t, a0[0], a0[1], a0[2], a0[3], b[0], b[1]);
                    mma16816(kc + 4 * t, a1[0], a1[1], a1[2], a1[3], b[2], b[3]);
                }
            }
            __syncwarp();
            if (it == 0) {
                if (warp < 8) {
#pragma unroll
                    for (int t = 0; t < 6; t++)
                        sts128(stg + (t * 32 + lane) * 16, __float_as_uint(kc[4 * t]), __float_as_uint(kc[4 * t + 1]), __float_as_uint(kc[4 * t + 2]), __float_as_uint(kc[4 * t + 3]));
                    __syncwarp();
                    if (lane == 0) mbar_arrive(bar + 8 * BAR_KG);
                    break;
                }
                mbar_wait(bar + 8 * BAR_KG, 0);
#pragma unroll
                for (int t = 0; t < 12; t++) {
                    const uint4 v = lds128(sb + 3 * SLOT + (w4 + (t / 6) * 4) * 7296 + ((t % 6) * 32 + lane) * 16);
                    kc[4 * (t % 6)] += __uint_as_float(v.x); kc[4 * (t % 6) + 1] += __uint_as_float(v.y); kc[4 * (t % 6) + 2] += __uint_as_float(v.z); kc[4 * (t % 6) + 3] += __uint_as_float(v.w);
                }
                asm volatile("fence.proxy.async.shared::cta;" ::: "memory");
                bar_named(2, 128);
                if (st == 0) load_stage(3);
                if (warp == 8) STAMP(22);
            }
        }
    }

    if (warp < 8) {
        const int wg = warp >> 2;
        if (warp == 0) STAMP(21);
        float acc[96];
        const int grow = bi_j * 16 + warp * 2 + (lane >> 4);
        const uint32_t gx_a = grow * 128 + ((((lane & 15) >> 1) ^ (grow & 7)) << 4) + (lane & 1) * 8;
        const int srow = warp * 16 + (lane & 15);
        const uint32_t srow_a = srow * 128;
        const int sx = srow & 7, shi = lane >> 4;
        auto last_of_8 = [&](int c) {
            unsigned old;
            asm volatile("atom.acq_rel.cta.shared.add.u32 %0,[%1],1;" : "=r"(old) : "r"(bar + OFF_CNT + 4 * c) : "memory");
            return (old & 7) == 7;
        };
        const int qq = (bi_i & 2) + ((lane >> 1) & 1);
        const int kvf_n = warp < 4 ? 8 : ((warp == 4 && (bi_i & 1) == 0) ? 4 : 0);
        uint2* kvf_dst = (uint2*)(scr->kvf + (bi_j * 4 + (bi_i >> 2)) * 68) +
                         (warp == 4 ? (64 + qq) * 2 + (lane & 1) : ((bi_i & 3) * 8 + w4 * 2 + (lane & 1)) * 4 + (lane >> 1));
        float gsum = 0.f;
#pragma unroll
        for (int r = 0; r < 96; r++) acc[r] = 0.f;
        fence_regs<96>(acc);
        const uint64_t da0 = mkdesc(sb + wg * 8192, 16, 1024), db0 = mkdesc(sb + 16384, 8192, 1024);
        {
            const uint32_t old = tag ^ 1u;
            const uint4 z4 = make_uint4(old, 0, old, 0);
            uint4* kvp = scr->kvp + bi * 544 + wg * 272;
            if (w4 < 2) {
#pragma unroll
                for (int f = 0; f < 4; f++) st_rlx128(kvp + w4 * 136 + lane + f * 32, z4);
            } else if (w4 == 2 && lane < 4) {
#pragma unroll
                for (int f = 0; f < 4; f++) st_rlx128(kvp + (f >> 1) * 136 + 128 + (f & 1) * 4 + lane, z4);
            }
            if (lane < kvf_n) st_rlx64(kvf_dst, old, 0);
            if (lane >= 30) st_rlx128(scr->o + ((bi_i * 8 + warp) * 32 + bi_j * 4 + 3) * 32 + lane, z4);
            if (lane < 8) st_rlx32(scr->g + (bi_i * 64 + bi_j * 8 + warp) * 8 + lane, old);
        }
        mbar_wait(bar + 8 * BAR_WPHI, 0);
#pragma unroll 1
        for (int kb = 0; kb < 8; kb++) {
            const int s = kb & 3;
            const uint64_t da = da0 + s * (SLOT >> 4), db = db0 + s * (SLOT >> 4);
            mbar_wait(bar + 8 * (BAR_FULL + s), kb >> 2);
            if (kb == 0 && warp == 0) STAMP(0);
            wg_fence();
#pragma unroll
            for (int k = 0; k < 4; k++) wgmma192(acc, da + 2 * k, db + 128 * k);
            wg_commit();
            wg_wait<1>();
            __syncwarp();
            if (lane == 0 && kb > 0 && kb < 7) {
                const int ps = (kb - 1) & 3;
                if (last_of_8(ps)) {
                    if (kb < 5) load_stage(kb + 3);
                    else {
                        mbar_expect(bar + 8 * BAR_WO, 32768);
                        tma2d(sb + ps * SLOT, &mwo, (bi_j & 3) * 128 + ps * 64, 0, bar + 8 * BAR_WO);
                    }
                }
            }
            __syncwarp();
            const uint32_t st = sb + s * SLOT;
            if (kb == (bi_j >> 1)) {
                uint32_t* xt = (uint32_t*)scr->xt + ((kb + rot) * 16 + (g >> 2)) * 4096 + (bi_i * 16 + warp * 2) * 16 + (g & 3) * 4 + q;
#pragma unroll
                for (int cb = 0; cb < 8; cb += 2) {
                    uint32_t r[4];
                    ldsm4t(r, st + srow_a + (((cb + shi) ^ sx) << 4));
                    xt[cb * 8192] = r[0]; xt[cb * 8192 + 16] = r[1]; xt[cb * 8192 + 8192] = r[2]; xt[cb * 8192 + 8192 + 16] = r[3];
                }
                __syncwarp();
                if (lane == 0) mbar_arrive(bar + 8 * BAR_XT);
            }
            {
                uint32_t x0, x1, w0, w1;
                asm volatile("ld.shared.v2.b32 {%0,%1},[%2];" : "=r"(x0), "=r"(x1) : "r"(st + gx_a) : "memory");
                asm volatile("ld.shared.v2.b32 {%0,%1},[%2];" : "=r"(w0), "=r"(w1) : "r"(sb + OFF_GW + ((kb + rot) & 7) * 128 + (lane & 15) * 8) : "memory");
                const uint32_t p0 = hmul2(x0, w0), p1 = hmul2(x1, w1);
                gsum += (bf_lo(p0) + bf_hi(p0)) + (bf_lo(p1) + bf_hi(p1));
            }
        }
        wg_wait<0>();
        fence_regs<96>(acc);
        __syncwarp();
        if (lane == 0) mbar_arrive(bar + 8 * BAR_DONE);
        if (warp == 0) STAMP(1);
        uint32_t in[32], va[16];
#pragma unroll
        for (int r = 0; r < 16; r++) {
            in[r] = pack2(acc[32 + 2 * r], acc[32 + 2 * r + 1]);
            in[16 + r] = pack2(acc[2 * r], acc[2 * r + 1]);
            va[r] = pack2(acc[64 + 2 * r], acc[64 + 2 * r + 1]);
        }
        const uint32_t wphi_a = sb + OFF_WPHI + (lane & 15) * 32 + (lane >> 4) * 16;
        uint32_t pq[4][8];
#pragma unroll 1
        for (int it = 0; it < 4; it++) {
            hedgehog2(in, wphi_a + (it & 1) * 1024, pq + 2);
#pragma unroll
            for (int r = 0; r < 24; r++) in[r] = in[r + 8];
            if (it < 2) {
#pragma unroll
                for (int hs = 0; hs < 4; hs++) {
                    float c[4] = {0.f, 0.f, 0.f, 0.f};
                    uint32_t* o = pq[2 + (hs >> 1)] + 4 * (hs & 1);
                    mma16816(c, o[0], o[1], o[2], o[3], 0x3f803f80u, 0x3f803f80u);
                    const float r0 = rcp(c[0]), r1 = rcp(c[2]);
                    const uint32_t s0 = pack2(r0, r0), s1 = pack2(r1, r1);
                    o[0] = hmul2(o[0], s0); o[1] = hmul2(o[1], s1); o[2] = hmul2(o[2], s0); o[3] = hmul2(o[3], s1);
                }
                if (it == 0) mbar_wait(bar + 8 * BAR_DONE, 0);
                const uint32_t pt = sb + OFF_P + it * 16384 + srow_a, vt = sb + OFF_V + it * 16384 + srow_a;
#pragma unroll
                for (int hl = 0; hl < 2; hl++) {
                    stsm4(pt + (((4 * hl + shi) ^ sx) << 4), pq[2 + hl][0], pq[2 + hl][1], pq[2 + hl][2], pq[2 + hl][3]);
                    stsm4(pt + (((4 * hl + 2 + shi) ^ sx) << 4), pq[2 + hl][4], pq[2 + hl][5], pq[2 + hl][6], pq[2 + hl][7]);
                    stsm4(vt + (((2 * hl + shi) ^ sx) << 4), va[4 * hl], va[4 * hl + 1], va[4 * hl + 2], va[4 * hl + 3]);
                }
                if (lane < 16) sts128(vt + ((4 ^ sx) << 4), 0x3f803f80u, 0x3f803f80u, 0x3f803f80u, 0x3f803f80u);
#pragma unroll
                for (int r = 0; r < 8; r++) va[r] = va[r + 8];
            }
            if (it == 1) {
                asm volatile("fence.proxy.async.shared::cta;" ::: "memory");
                bar_named(1, 256);
                if (warp == 0) STAMP(2);
                if (tid == 0) mbar_arrive(bar + 8 * BAR_GO);
                float d[32];
                const uint64_t dv = mkdesc(sb + OFF_V + wg * 16384, 16, 1024), dp = mkdesc(sb + OFF_P + wg * 16384, 16, 1024);
                wg_fence();
#pragma unroll
                for (int k = 0; k < 8; k++) wgmma64_tt(d, dv + 128 * k, dp + 128 * k, k != 0);
                wg_commit();
                wg_wait<0>();
                fence_regs<32>(d);
                uint4* kvp = scr->kvp + bi * 544 + wg * 272;
                if (w4 < 2) {
                    uint32_t e[16];
#pragma unroll
                    for (int r = 0; r < 16; r++) e[r] = __float_as_uint(w4 ? d[16 + r] : d[r]);
                    uint4* p = kvp + w4 * 136 + lane;
#pragma unroll
                    for (int ks = 0; ks < 2; ks++)
#pragma unroll
                        for (int nt = 0; nt < 2; nt++)
                            st_rlx128(p + (ks * 2 + nt) * 32, tag4(e[8 * ks + 2 * nt], e[8 * ks + 2 * nt + 1], e[8 * ks + 4 + 2 * nt], e[8 * ks + 4 + 2 * nt + 1], tag));
                } else if (w4 == 2 && lane < 4) {
#pragma unroll
                    for (int hl = 0; hl < 2; hl++)
#pragma unroll
                        for (int ks = 0; ks < 2; ks++)
                            st_rlx128(kvp + hl * 136 + 128 + ks * 4 + lane, tag4(__float_as_uint(d[16 * hl + 8 * ks]), __float_as_uint(d[16 * hl + 8 * ks + 1]),
                                                                                __float_as_uint(d[16 * hl + 8 * ks + 4]), __float_as_uint(d[16 * hl + 8 * ks + 5]), tag));
                }
                if (warp == 0) STAMP(3);
            }
            if (it == 2) {
#pragma unroll
                for (int r = 0; r < 8; r++) { pq[0][r] = pq[2][r]; pq[1][r] = pq[3][r]; }
                if (warp == 0) STAMP(12);
                if (kvf_n) {
                    const bool zw = warp == 4;
                    const uint4* src = scr->kvp + bi_j * (16 * 544) + (bi_i >> 2) * 136 +
                                       (zw ? (lane >> 2) * (2 * 544) + 128 + (lane & 1) * 4 + qq
                                           : (lane >> 3) * (4 * 544) + ((lane >> 1) & 3) * 32 + (bi_i & 3) * 8 + warp * 2 + (lane & 1));
                    const int s23 = zw ? 0 : 2 * 544;
                    uint4 v[4];
                    int n = 0;
#pragma unroll 1
                    while (true) {
                        v[0] = ld_rlx128(src); v[1] = ld_rlx128(src + 544); v[2] = ld_rlx128(src + s23); v[3] = ld_rlx128(src + s23 + 544);
                        if (!__any_sync(~0u, (bad4(v[0], tag) | bad4(v[1], tag) | bad4(v[2], tag) | bad4(v[3], tag)) & 1)) break;
                        if (++n > SPIN_LIMIT) break;
                    }
                    float f[4];
                    f[0] = __uint_as_float(v[2].x) + __uint_as_float(v[3].x); f[1] = __uint_as_float(v[2].y) + __uint_as_float(v[3].y);
                    f[2] = __uint_as_float(v[2].z) + __uint_as_float(v[3].z); f[3] = __uint_as_float(v[2].w) + __uint_as_float(v[3].w);
                    float e0 = __uint_as_float(v[0].x) + __uint_as_float(v[1].x), e1 = __uint_as_float(v[0].y) + __uint_as_float(v[1].y);
                    float e2 = __uint_as_float(v[0].z) + __uint_as_float(v[1].z), e3 = __uint_as_float(v[0].w) + __uint_as_float(v[1].w);
                    if (zw) {
                        e0 = __shfl_xor_sync(~0u, f[0], 4); e1 = __shfl_xor_sync(~0u, f[1], 4);
                        e2 = __shfl_xor_sync(~0u, f[2], 4); e3 = __shfl_xor_sync(~0u, f[3], 4);
                    }
                    f[0] += e0; f[1] += e1; f[2] += e2; f[3] += e3;
#pragma unroll
                    for (int o = 8; o <= 16; o <<= 1)
#pragma unroll
                        for (int r = 0; r < 4; r++) f[r] += __shfl_xor_sync(~0u, f[r], o);
                    if (lane < kvf_n) st_rlx64(kvf_dst, tagw(pack2(f[0], f[1]), tag), pack2(f[2], f[3]));
                }
                __syncwarp();
                if (lane == 0 && last_of_8(4)) {
                    mbar_expect(bar + 8 * BAR_WO2, 65536);
                    tma2d(sb + 2 * SLOT, &mwo, (bi_j & 3) * 128, 256, bar + 8 * BAR_WO2);
                    tma2d(sb + OFF_V, &mwo, (bi_j & 3) * 128 + 64, 256, bar + 8 * BAR_WO2);
                }
                __syncwarp();
                if (warp == 0) STAMP(13);
#pragma unroll
                for (int o = 1; o < 16; o <<= 1) gsum += __shfl_xor_sync(~0u, gsum, o);
                const float gate = bf_round(rcp(1.0f + ex2(-1.4426950408889634f * bf_round(gsum))));
                const uint32_t gv = __shfl_sync(~0u, __float_as_uint(gate) | tag, (lane & 4) * 4);
                if (lane < 8) st_rlx32(scr->g + (bi_i * 64 + bi_j * 8 + warp) * 8 + lane, gv);
            }
        }
        if (warp == 0) STAMP(4);
        {
            {
                const uint4* kp = scr->kvf + bi_j * 272 + tid;
                uint4 v0, v1;
                int n = 0;
#pragma unroll 1
                while (true) {
                    v0 = ld_rlx128(kp); v1 = ld_rlx128(kp + (tid < 16 ? 256 : 0));
                    if (!__any_sync(~0u, (bad4(v0, tag) | bad4(v1, tag)) & 1)) break;
                    if (++n > SPIN_LIMIT) break;
                }
                sts128(sb + OFF_KVF + tid * 16, v0.x, v0.y, v0.z, v0.w);
                if (tid < 16) sts128(sb + OFF_KVF + 4096 + tid * 16, v1.x, v1.y, v1.z, v1.w);
                bar_named(1, 256);
            }
            uint4 kf[4][3];
#pragma unroll
            for (int hh = 0; hh < 4; hh++) {
                const uint32_t a = sb + OFF_KVF + hh * 1088;
                kf[hh][0] = lds128(a + lane * 32); kf[hh][1] = lds128(a + lane * 32 + 16); kf[hh][2] = lds128(a + 1024 + q * 16);
            }
            if (warp == 0) STAMP(5);
            uint4 own[4];
#pragma unroll
            for (int hh = 0; hh < 4; hh++) {
                float c[6][4];
#pragma unroll
                for (int t = 0; t < 6; t++) { c[t][0] = c[t][1] = c[t][2] = c[t][3] = 0.f; }
                const uint32_t* a = pq[hh];
                const bool od = g & 1;
                mma16816(c[0], a[0], a[1], a[2], a[3], od ? 0x3f803f80u : kf[hh][2].x, od ? 0x3f803f80u : kf[hh][2].y);
                mma16816(c[1], a[4], a[5], a[6], a[7], od ? 0x3f803f80u : kf[hh][2].z, od ? 0x3f803f80u : kf[hh][2].w);
                mma16816(c[2], a[0], a[1], a[2], a[3], kf[hh][0].x, kf[hh][0].y);
                mma16816(c[3], a[0], a[1], a[2], a[3], kf[hh][0].z, kf[hh][0].w);
                mma16816(c[4], a[4], a[5], a[6], a[7], kf[hh][1].x, kf[hh][1].y);
                mma16816(c[5], a[4], a[5], a[6], a[7], kf[hh][1].z, kf[hh][1].w);
                uint32_t w[4];
#pragma unroll
                for (int k = 0; k < 2; k++) {
                    const float rho = c[0][2 * k + 1] * rcp(c[1][2 * k + 1]);
                    const float r = rcp(fmaf(c[0][2 * k + 1], 1e-6f, fmaf(rho, c[1][2 * k], c[0][2 * k]))), rr = r * rho;
                    w[k] = pack2(fmaf(c[4][2 * k], rr, c[2][2 * k] * r), fmaf(c[4][2 * k + 1], rr, c[2][2 * k + 1] * r));
                    w[2 + k] = pack2(fmaf(c[5][2 * k], rr, c[3][2 * k] * r), fmaf(c[5][2 * k + 1], rr, c[3][2 * k + 1] * r));
                }
                own[hh] = tag4(w[0], w[1], w[2], w[3], tag);
            }
            uint4* og = scr->o + ((bi_i * 8 + warp) * 32 + bi_j * 4) * 32 + lane;
#pragma unroll
            for (int hh = 0; hh < 4; hh++) st_rlx128(og + hh * 32, own[hh]);
        }
        if (warp == 0) STAMP(6);
        float oc[64];
        const int slab = bi_i * 8 + (bi_j >> 2) * 4 + w4;
        const uint8_t* yb = (const uint8_t*)scr->y + (size_t)((bi_j & 3) * 32 + wg * 16 + (q >> 1)) * 16384 + slab * 128 + g * 16 + (q & 1) * 8;
        const unsigned* gp = scr->g + (slab * 8 + (g >> 1)) * 8 + (g & 1) * 4;
        uint2 yv[8]; unsigned g0, g1;
        {
            const uint4* osrc = scr->o + (slab * 32 + wg * 16) * 32 + lane;
            uint4 fr[16];
            const unsigned* probe = (const unsigned*)(osrc - lane + ((lane & 3) * 4 + 3) * 32 + 31) + 2;
            {
                unsigned miss = ~0u;
                int n = 0;
#pragma unroll
                for (int s = 0; s < 4; s++) {
#pragma unroll 1
                    while ((miss >> s) & 1) { miss = __ballot_sync(~0u, (ld_rlx(probe) ^ tag) & 1); if (++n > SPIN_LIMIT) break; }
#pragma unroll
                    for (int k = 4 * s; k < 4 * s + 4; k++) fr[k] = ld_rlx128(osrc + k * 32);
                }
            }
            if (warp == 0) STAMP(14);
            mbar_wait(bar + 8 * (wg ? BAR_WO2 : BAR_WO), 0);
            const uint64_t dw = mkdesc(sb + wg * 2 * SLOT, wg ? 32768 : SLOT, 1024);
#pragma unroll
            for (int s = 0; s < 4; s++) {
                int n = 0;
#pragma unroll 1
                while (__builtin_expect(__any_sync(~0u, (bad4(fr[4 * s], tag) | bad4(fr[4 * s + 1], tag) | bad4(fr[4 * s + 2], tag) | bad4(fr[4 * s + 3], tag)) & 1), 0)) {
#pragma unroll
                    for (int k = 4 * s; k < 4 * s + 4; k++) fr[k] = ld_rlx128(osrc + k * 32);
                    if (++n > SPIN_LIMIT) break;
                }
                wg_fence();
#pragma unroll
                for (int hh = 0; hh < 4; hh++) wgmma128_rs(oc, fr[4 * s + hh], dw + 128 * (4 * s + hh), (s | hh) != 0);
                wg_commit();
                if (s == 1) {
                    wg_wait<1>();
#pragma unroll
                    for (int nt = 0; nt < 8; nt++) yv[nt] = ld_rlx64(yb + nt * 32768);
                    g0 = ld_rlx(gp); g1 = ld_rlx(gp + 32);
                }
            }
            if (warp == 0) STAMP(7);
            {
                const unsigned* yprobe = scr->yflag + ((bi_j & 3) * 32 + wg * 16 + (lane & 15)) * 8;
                int n = 0;
#pragma unroll 1
                while (true) {
                    uint32_t bad = (g0 ^ tag) | (g1 ^ tag);
#pragma unroll
                    for (int nt = 0; nt < 8; nt++) bad |= yv[nt].x ^ tag;
                    if (!__any_sync(~0u, bad & 1)) break;
#pragma unroll 1
                    while (__any_sync(~0u, (ld_rlx(yprobe) ^ tag) & 1)) { if (++n > SPIN_LIMIT) break; }
#pragma unroll
                    for (int nt = 0; nt < 8; nt++) yv[nt] = ld_rlx64(yb + nt * 32768);
                    g0 = ld_rlx(gp); g1 = ld_rlx(gp + 32);
                    if (++n > SPIN_LIMIT) break;
                }
            }
            if (warp == 0) STAMP(28);
            wg_wait<0>();
            fence_regs<64>(oc);
        }
        {
            bar_named(3 + wg, 128);
            const uint32_t xw = sb + wg * 2 * SLOT + (tid & 127) * 16, xr = sb + (wg ^ 1) * 2 * SLOT + (tid & 127) * 16;
#pragma unroll
            for (int r = 0; r < 8; r++) {
                const float* o = oc + 4 * r;
                sts128(xw + r * 2048, __float_as_uint(wg ? o[0] : o[32]), __float_as_uint(wg ? o[1] : o[33]), __float_as_uint(wg ? o[2] : o[34]), __float_as_uint(wg ? o[3] : o[35]));
            }
#pragma unroll
            for (int r = 0; r < 32; r++) oc[r] = wg ? oc[32 + r] : oc[r];
            bar_named(1, 256);
            if (warp == 0) STAMP(8);
            const float ga = bf_hi(g0), gb = bf_hi(g1);
            const float ha = bf_round(1.0f - ga), hb = bf_round(1.0f - gb);
            uint32_t w[8][2];
#pragma unroll
            for (int nt = 0; nt < 8; nt++) {
                const uint4 p = lds128(xr + nt * 2048);
                w[nt][0] = pack2(fmaf(ga, oc[4 * nt] + __uint_as_float(p.x), ha * bf_lo(yv[nt].x)), fmaf(ga, oc[4 * nt + 1] + __uint_as_float(p.y), ha * bf_hi(yv[nt].x)));
                w[nt][1] = pack2(fmaf(gb, oc[4 * nt + 2] + __uint_as_float(p.z), hb * bf_lo(yv[nt].y)), fmaf(gb, oc[4 * nt + 3] + __uint_as_float(p.w), hb * bf_hi(yv[nt].y)));
            }
            const uint32_t ob = sb + wg * 2 * SLOT + 16384 + w4 * 2048;
#pragma unroll
            for (int nt = 0; nt < 8; nt += 2)
                stsm4(ob + (lane & 15) * 128 + (((nt + shi) ^ (lane & 7)) << 4), w[nt][0], w[nt][1], w[nt + 1][0], w[nt + 1][1]);
            __syncwarp();
            bf16* op = out + (size_t)(slab * 16) * 512 + (bi_j & 3) * 128 + wg * 64 + (lane & 7) * 8;
#pragma unroll
            for (int it = 0; it < 4; it++) {
                const int r = it * 4 + (lane >> 3);
                uint4 v = lds128(ob + r * 128 + (((lane & 7) ^ (r & 7)) << 4));
                *(uint4*)(op + r * 512) = v;
            }
        }
        if (warp == 0) STAMP(10);
    } else {
        if (lane == 0) kc[4 * 0 + 0] += ((ch & 1) ? bf_hi(pds) : bf_lo(pds));
        const uint32_t k1024 = __shfl_sync(~0u, pack2(kc[4 * 4 + 0], 0.f), 0);
#pragma unroll
        for (int i = 0; i < 2; i++) {
            const int be = g + 8 * i;
#pragma unroll
            for (int t = 0; t < 2; t++) {
                const uint32_t a = kb_ + (KW_D + 128 * t + 8 * be + 2 * q) * 4;
                const uint32_t w = pack2(kc[4 * t + 2 * i + 1], kc[4 * t + 2 * i]);
                sts32(a + 4, w); sts16(a, w >> 16); sts16(a + 10, w);
            }
            {
                const int p = 256 + 128 * (q >> 1) + 8 * be + 4 * (q & 1);
                const uint32_t a = kb_ + (KW_D + p) * 4;
                const uint32_t w = pack2(kc[4 * 2 + 2 * i + 1], kc[4 * 2 + 2 * i]);
                const uint32_t aa = (w >> 16) | (w & 0xffff0000u);
                if (p != 256) { sts16(a - 4, aa); sts32(a, aa); } else sts16(a, aa);
                sts32(a + 4, aa); sts32(a + 8, w); sts16(a + 14, w);
            }
            {
                const int k = 64 + 16 * q + be;
                const uint32_t w = pack2(kc[4 * 3 + 2 * i], kc[4 * 3 + 2 * i + 1]);
                if (k != 64) sts16(kb_ + (KW_2 + ((k - 1) >> 1) - 24) * 4 + (k & 1) * 2, w);
                else {
                    const uint32_t a = kb_ + (KW_D + 511) * 4, aa = (w << 16) | (w & 0xffffu);
                    sts16(a, w); sts32(a + 4, aa); sts32(a + 8, aa); sts32(a + 12, aa); sts16(a + 18, w);
                }
                sts16(kb_ + (KW_2 + 48 + (k >> 1) - 24) * 4 + ((k & 1) ^ 1) * 2, w >> 16);
            }
#pragma unroll
            for (int b = 0; b < 2; b++) {
                const int k = 64 + 8 * (2 * q + b) + (be >> 1);
                const uint32_t w = pack2(kc[4 * 4 + 2 * i + b], 0.f);
                if (!(be & 1) && k == 64) sts16(kb_ + (KW_2 + 63 - 24) * 4, w);
                else {
                    const uint32_t a = kb_ + (KW_3 + ((be & 1) ? 80 + k : k - 1) - 48) * 4;
                    sts16(a, w);
                    if (!((be & 1) && k == 127)) sts16(a + 6, w);
                }
            }
        }
        if (lane == 0) sts16(kb_ + (KW_3 + 127 - 48) * 4, pack2(kc[4 * 5 + 0], 0.f));
        if (warp == 8) STAMP(17);
        if (warp == 8) STAMP(25);
        if (warp == 8) {
            mbar_wait(bar + 8 * BAR_XT, 0);
            if (lane == 0) asm volatile("red.release.gpu.global.add.u32 [%0],8;" ::"l"(scr->xcnt + ((bi_j >> 1) + rot) * 32) : "memory");
        }
        if (lane == 0) {
            int n = 0;
#pragma unroll 1
            while ((int)(ld_acq(scr->xcnt + bi_j * 32) - (epoch1 << 7)) < 0) { __nanosleep(200); if (++n > SPIN_LIMIT) break; }
        }
        __syncwarp();
        if (warp == 8) STAMP(15);
        uint4 ur[8];
#pragma unroll
        for (int v = 0; v < 8; v++) ur[v] = __ldcg(scr->xt + bi * 1024 + st + 128 * v);
        if (lane < 16) sts128(ub - 256 + lane * 16, 0, 0, 0, 0);
        if (st < 8) st_rlx32(scr->yflag + bi * 8 + st, tag ^ 1u);
#pragma unroll
        for (int v = 0; v < 8; v++) {
            const int ci = (st >> 2) + 32 * v;
            sts128(sb + OFF_U + (st & 3) * U_STRIDE + 256 + ((ci ^ ((ci >> 3) & 1)) << 4), ur[v].x, ur[v].y, ur[v].z, ur[v].w);
        }
        if (warp == 8) STAMP(16);
mbar_wait(bar + 8 * BAR_WO, 0);
        bar_named(2, 128);
        if (lane < 2) sts128(buf + lane * W3_OFF, 0, 0, 0, 0);
        {
#pragma unroll 1
            for (int r2 = 0; r2 < 3; r2++) {
#pragma unroll
                for (int hf = 0; hf < 2; hf++) {
                    const int ci = lane + 32 * (2 * r2 + hf);
                    uint4 e4[4];
#pragma unroll
                    for (int v = 0; v < 4; v++) { const int cc = ci - 3 + v; e4[v] = lds128(ub + ((cc ^ ((cc >> 3) & 1)) << 4)); }
                    float S[29];
                    const uint32_t* ew = (const uint32_t*)e4;
                    S[3] = 0.f;
#pragma unroll
                    for (int k = 4; k <= 28; k++) S[k] = S[k - 1] + ((k & 1) ? bf_hi(ew[k >> 1]) : bf_lo(ew[k >> 1]));
                    auto win = [&](int lo, int hi, uint32_t a, bool on) {
                        const uint32_t w0 = pack2(S[hi] - S[lo - 1], S[hi + 1] - S[lo]), w1 = pack2(S[hi + 2] - S[lo + 1], S[hi + 3] - S[lo + 2]);
                        const uint32_t w2 = pack2(S[hi + 4] - S[lo + 3], S[hi + 5] - S[lo + 4]), w3 = pack2(S[hi + 6] - S[lo + 5], S[hi + 7] - S[lo + 6]);
                        asm volatile("{.reg .pred p; setp.ne.b32 p,%5,0; @p st.shared.v4.b32 [%0],{%1,%2,%3,%4};}" ::"r"(a), "r"(w0), "r"(w1), "r"(w2), "r"(w3), "r"((int)on) : "memory");
                    };
                    const uint32_t sw = (ci ^ ((ci >> 3) & 1)) << 4;
                    win(14, 18, buf + W5_OFF + 16 + ci * 16, true); win(19, 21, buf + W3_OFF + 16 + ci * 16, true);
                    win(4, 12, buf + W9_OFF + sw, r2 < 2); win(13, 19, spare + sw, r2 < 2); win(20, 21, spare + 2048 + sw, r2 < 2);
                }
            }
        }
if (warp == 8) STAMP(24);
        __syncwarp();
        mbar_wait(bar + 8 * BAR_GO, 0);
        if (warp == 8) STAMP(23);
        float y[16][4];
#pragma unroll
        for (int nt = 0; nt < 16; nt++) { y[nt][0] = y[nt][1] = y[nt][2] = y[nt][3] = 0.f; }
        {
            uint32_t Bp[32], A[5][3], An[5][3];
            auto uaddr = [&](int rho) { const int R0 = (lane >> 4) * 8 + (lane & 7) - rho; return ub + (((2 * R0 + ((lane >> 3) & 1)) ^ ((R0 >> 2) & 1)) << 4); };
            const uint32_t kd = kb_ + (KW_D + g - 2 * q) * 4;
            auto lda = [&](int rho) {
#pragma unroll
                for (int ga = 0; ga < 5; ga++) {
                    const uint32_t a = kd + (ga < 4 ? rho : (rho & 1)) * 64 + ga * 512;
                    An[ga][0] = lds32(a); An[ga][1] = lds32(a + 32); An[ga][2] = lds32(a - 32);
                }
            };
            lda(0);
            {
                const uint32_t a = uaddr(0);
#pragma unroll
                for (int p = 0; p < 8; p++) ldsm4(Bp + 4 * p, a + p * 512);
            }
#pragma unroll 1
            for (int rho = 0; rho < 8; rho++) {
#pragma unroll
                for (int r = 0; r < 15; r++) A[r / 3][r % 3] = An[r / 3][r % 3];
                lda(rho + 1);
                if (rho < 2) {
#pragma unroll
                    for (int nt = 4; nt < 16; nt++) mma16816(y[nt], A[4][0], A[4][1], A[4][2], A[4][0], Bp[2 * (nt - 4)], Bp[2 * (nt - 4) + 1]);
                }
#pragma unroll
                for (int ga = 0; ga < 3; ga++)
#pragma unroll
                    for (int nt = 15; nt >= ga; nt--) mma16816(y[nt], A[ga][0], A[ga][1], A[ga][2], A[ga][0], Bp[2 * (nt - ga)], Bp[2 * (nt - ga) + 1]);
                const uint32_t an = uaddr(rho + 1);
                ldsm4(Bp + 28, an + 7 * 512);
#pragma unroll
                for (int nt = 15; nt >= 3; nt--) {
                    mma16816(y[nt], A[3][0], A[3][1], A[3][2], A[3][0], Bp[2 * (nt - 3)], Bp[2 * (nt - 3) + 1]);
                    if (nt & 1) ldsm4(Bp + 2 * (nt - 3), an + ((nt - 3) >> 1) * 512);
                }
            }
        }
        if (warp == 8) STAMP(18);
#pragma unroll 1
        for (int ph = 0; ph < 2; ph++) {
            uint32_t B[5][2];
            const uint32_t ka = kb_ + (KW_2 + ph * 48 + 8 + g - q) * 4;
#pragma unroll
            for (int dd = 0; dd < 5; dd++) { B[dd][0] = lds32(ka + dd * 32); B[dd][1] = lds32(ka + dd * 32 - 16); }
            const uint32_t wa = buf + ph * W3_OFF + ((lane & 7) + ((lane >> 3) & 1) + (lane >> 4) * 8) * 16;
#pragma unroll
            for (int s = 0; s < 12; s++) {
                uint32_t A[4];
                ldsm4t(A, wa + s * 256);
#pragma unroll
                for (int dd = 0; dd < 5; dd++)
                    if (s + 4 + dd < 16) mma16816(y[s + 4 + dd], A[0], A[1], A[2], A[3], B[dd][0], B[dd][1]);
            }
        }
        {
            const int ap = (lane & 7) + (lane >> 4) * 8;
            const uint32_t loff = ((2 * ap + ((lane >> 3) & 1)) ^ ((ap >> 2) & 1)) << 4;
#pragma unroll 1
            for (int ph = 0; ph < 2; ph++) {
                uint32_t B[8][2];
                const uint32_t wb = (ph ? spare : buf + W9_OFF) + loff;
                const uint32_t ka = kb_ + (KW_3 + ph * 80 + 16 + g - 2 * q) * 4;
#pragma unroll
                for (int dd = 0; dd < 8; dd++) { B[dd][0] = lds32(ka + dd * 32); B[dd][1] = lds32(ka + dd * 32 - 32); }
#pragma unroll
                for (int s = 0; s < 4; s++) {
                    uint32_t A[4];
                    ldsm4t(A, wb + s * 512);
#pragma unroll
                    for (int dd = 0; dd < 8; dd++)
                        if (8 + 2 * s + dd < 16) mma16816(y[8 + 2 * s + dd], A[0], A[1], A[2], A[3], B[dd][0], B[dd][1]);
                }
            }
            const uint32_t idw = (g == 2 * q) ? k1024 : ((g == 2 * q + 1) ? (k1024 << 16) : 0u);
#pragma unroll
            for (int s = 0; s < 4; s++) {
                uint32_t A[4];
                ldsm4t(A, spare + 2048 + loff + s * 512);
                mma16816(y[8 + 2 * s], A[0], A[1], A[2], A[3], idw, 0u);
                mma16816(y[9 + 2 * s], A[0], A[1], A[2], A[3], 0u, idw);
            }
        }
        __syncwarp();
        if (warp == 8) STAMP(19);
#pragma unroll
        for (int nt = 0; nt < 16; nt++)
#pragma unroll
            for (int b = 0; b < 2; b++) sts32(buf + ((8 * nt + 2 * q + b) * 8 + g) * 4, pack2(y[nt][b], y[nt][2 + b]));
        bar_named(2, 128);
        uint4* yp = scr->y + bi * 1024 + st;
#pragma unroll
        for (int v = 0; v < 8; v++) {
            const uint32_t a = sb + OFF_BUF + (st + 128 * v) * 4;
            const uint32_t w0 = lds32(a), w1 = lds32(a + BUF_STRIDE), w2 = lds32(a + 2 * BUF_STRIDE), w3 = lds32(a + 3 * BUF_STRIDE);
            st_rlx128(yp + v * 128, tag4(__byte_perm(w0, w1, 0x5410), __byte_perm(w0, w1, 0x7632), __byte_perm(w2, w3, 0x5410), __byte_perm(w2, w3, 0x7632), tag));
        }
        if (st < 8) st_rlx32(scr->yflag + bi * 8 + st, tag);
        if (warp == 8) STAMP(20);
    }
    __syncthreads();
    if (tid == 0) atomicAdd(scr->done, 1u);
}

typedef CUresult (*EncFn)(CUtensorMap*, CUtensorMapDataType, cuuint32_t, void*, const cuuint64_t*, const cuuint64_t*, const cuuint32_t*,
                          const cuuint32_t*, CUtensorMapInterleave, CUtensorMapSwizzle, CUtensorMapL2promotion, CUtensorMapFloatOOBfill);

extern "C" void kernel_launch(void* const* d_in, const int* in_sizes, int n_in, void* d_out, int out_size) {
    static EncFn enc = nullptr;
    static Scratch* scr = nullptr;
    if (!enc) {
        cudaGetSymbolAddress((void**)&scr, g_scr);
        cudaDriverEntryPointQueryResult qr;
        cudaGetDriverEntryPoint("cuTensorMapEncodeTiled", (void**)&enc, cudaEnableDefault, &qr);
        cudaFuncSetAttribute(fused_kernel, cudaFuncAttributeMaxDynamicSharedMemorySize, SMEM_BYTES);
    }
    CUtensorMap mx, mw, mwo;
    const cuuint32_t es[3] = {1, 1, 1};
    {
        cuuint64_t d[2] = {512, 2048}, s[1] = {1024}; cuuint32_t b[2] = {64, 128};
        enc(&mx, CU_TENSOR_MAP_DATA_TYPE_BFLOAT16, 2, d_in[0], d, s, b, es, CU_TENSOR_MAP_INTERLEAVE_NONE, CU_TENSOR_MAP_SWIZZLE_128B,
            CU_TENSOR_MAP_L2_PROMOTION_L2_128B, CU_TENSOR_MAP_FLOAT_OOB_FILL_NONE);
    }
    {
        cuuint64_t d[3] = {512, 512, 3}, s[2] = {3072, 1024}; cuuint32_t b[3] = {64, 64, 3};
        enc(&mw, CU_TENSOR_MAP_DATA_TYPE_BFLOAT16, 3, d_in[1], d, s, b, es, CU_TENSOR_MAP_INTERLEAVE_NONE, CU_TENSOR_MAP_SWIZZLE_128B,
            CU_TENSOR_MAP_L2_PROMOTION_L2_128B, CU_TENSOR_MAP_FLOAT_OOB_FILL_NONE);
    }
    {
        cuuint64_t d[2] = {512, 512}, s[1] = {1024}; cuuint32_t b[2] = {64, 256};
        enc(&mwo, CU_TENSOR_MAP_DATA_TYPE_BFLOAT16, 2, d_in[3], d, s, b, es, CU_TENSOR_MAP_INTERLEAVE_NONE, CU_TENSOR_MAP_SWIZZLE_128B,
            CU_TENSOR_MAP_L2_PROMOTION_L2_128B, CU_TENSOR_MAP_FLOAT_OOB_FILL_NONE);
    }
    fused_kernel<<<128, 384, SMEM_BYTES, cudaStreamPerThread>>>(
        scr, (const bf16*)d_in[5], (const bf16*)d_in[6], (const bf16*)d_in[7], (const bf16*)d_in[8], (const bf16*)d_in[9],
        (const bf16*)d_in[10], (const bf16*)d_in[2], (const bf16*)d_in[11], (bf16*)d_out, mx, mw, mwo);
}
```

```cpp
#include <cuda_runtime.h>
#include <cuda.h>
#include <cuda_bf16.h>
#include <stdint.h>

typedef __nv_bfloat16 bf16;

struct Scratch {
    uint4 xt[128 * 1024];
    uint4 o[16 * 8 * 32 * 32];
    uint4 y[128 * 1024];
    uint4 kvp[8 * 16 * 544];
    uint4 kvf[8 * 4 * 68];
    unsigned g[1024 * 8];
    unsigned yflag[128 * 8];
    unsigned xcnt[8 * 32];
    unsigned done[32];
};
__device__ Scratch g_scr;
#define STAMP(n)

constexpr int SLOT = 40960;
constexpr int OFF_SP0 = 32768, OFF_SP1 = SLOT + 32768;
constexpr int OFF_P = 2 * SLOT, OFF_V = OFF_P + 32768;
constexpr int OFF_KVF = OFF_V + 32768;
constexpr int KT_BYTES = 3264, KW_D = 16, KW_2 = 560, KW_3 = 656;
constexpr int OFF_U = 4 * SLOT, U_STRIDE = 4096 + 256 + 32;
constexpr int OFF_BUF = OFF_U + 4 * U_STRIDE, BUF_STRIDE = 8320;
constexpr int OFF_K = OFF_BUF + 4 * BUF_STRIDE;
constexpr int OFF_WPHI = OFF_K + 4 * KT_BYTES;
constexpr int OFF_GW = OFF_WPHI + 2048;
constexpr int OFF_BAR = OFF_GW + 1024;
constexpr int SMEM_BYTES = OFF_BAR + 256 + 256;
static_assert(SMEM_BYTES <= 232448 && OFF_BUF % 128 == 0, "smem");
constexpr int W5_OFF = 0, W3_OFF = 3088, W9_OFF = 6176;
constexpr int BAR_FULL = 0, BAR_EMPTY = 4, BAR_WPHI = 8, BAR_WO = 9, BAR_WO2 = 10, BAR_XT = 11, BAR_DONE = 12, BAR_KG = 13, BAR_SP = 14,
              BAR_PUB = 15, BAR_KVF = 16, BAR_UR = 17, BAR_WR = 18, BAR_PREP = 19, BAR_SP2 = 20, OFF_CNT = 192;
constexpr int SPIN_LIMIT = 1 << 17;

__device__ __forceinline__ uint32_t s2u(const void* p) { return (uint32_t)__cvta_generic_to_shared(p); }
__device__ __forceinline__ void mbar_init(uint32_t b, int c) { asm volatile("mbarrier.init.shared::cta.b64 [%0],%1;" ::"r"(b), "r"(c) : "memory"); }
__device__ __forceinline__ void mbar_expect(uint32_t b, int bytes) { asm volatile("mbarrier.arrive.expect_tx.shared::cta.b64 _,[%0],%1;" ::"r"(b), "r"(bytes) : "memory"); }
__device__ __forceinline__ void mbar_arrive(uint32_t b) { asm volatile("mbarrier.arrive.shared::cta.b64 _,[%0];" ::"r"(b) : "memory"); }
__device__ __forceinline__ void mbar_wait(uint32_t b, int ph) {
    asm volatile("{\n.reg .pred p;\n.reg .u32 n;\nmov.u32 n,0;\nLW_%=:\nmbarrier.try_wait.parity.shared::cta.b64 p,[%0],%1;\n@p bra LD_%=;\n"
                 "add.u32 n,n,1;\nsetp.lt.u32 p,n,131072;\n@p bra LW_%=;\nLD_%=:\n}" ::"r"(b), "r"(ph) : "memory");
}
__device__ __forceinline__ void tma2d(uint32_t dst, const CUtensorMap* m, int c0, int c1, uint32_t bar) {
    asm volatile("cp.async.bulk.tensor.2d.shared::cluster.global.mbarrier::complete_tx::bytes [%0],[%1,{%3,%4}],[%2];" ::"r"(dst), "l"(m), "r"(bar), "r"(c0), "r"(c1) : "memory");
}
__device__ __forceinline__ void tma3d(uint32_t dst, const CUtensorMap* m, int c0, int c1, int c2, uint32_t bar) {
    asm volatile("cp.async.bulk.tensor.3d.shared::cluster.global.mbarrier::complete_tx::bytes [%0],[%1,{%3,%4,%5}],[%2];" ::"r"(dst), "l"(m), "r"(bar), "r"(c0), "r"(c1), "r"(c2) : "memory");
}
__device__ __forceinline__ void bulk_g2s(uint32_t dst, const void* src, int bytes, uint32_t bar) {
    asm volatile("cp.async.bulk.shared::cluster.global.mbarrier::complete_tx::bytes [%0],[%1],%2,[%3];" ::"r"(dst), "l"(src), "r"(bytes), "r"(bar) : "memory");
}
__device__ __forceinline__ uint64_t mkdesc(uint32_t addr, uint32_t lbo, uint32_t sbo) {
    return (uint64_t)((addr & 0x3FFFF) >> 4) | ((uint64_t)(lbo >> 4) << 16) | ((uint64_t)(sbo >> 4) << 32) | ((uint64_t)1 << 62);
}
__device__ __forceinline__ void wg_fence() { asm volatile("wgmma.fence.sync.aligned;" ::: "memory"); }
__device__ __forceinline__ void wg_commit() { asm volatile("wgmma.commit_group.sync.aligned;" ::: "memory"); }
template <int N> __device__ __forceinline__ void wg_wait() { asm volatile("wgmma.wait_group.sync.aligned %0;" ::"n"(N) : "memory"); }
template <int N> __device__ __forceinline__ void fence_regs(float* d) {
#pragma unroll
    for (int i = 0; i < N; i++) asm volatile("" : "+f"(d[i])::"memory");
}
#define R8(d, o) "+f"(d[o]), "+f"(d[o + 1]), "+f"(d[o + 2]), "+f"(d[o + 3]), "+f"(d[o + 4]), "+f"(d[o + 5]), "+f"(d[o + 6]), "+f"(d[o + 7])
__device__ __forceinline__ void wgmma192(float* d, uint64_t da, uint64_t db) {
    asm volatile("wgmma.mma_async.sync.aligned.m64n192k16.f32.bf16.bf16 {"
                 "%0,%1,%2,%3,%4,%5,%6,%7,%8,%9,%10,%11,%12,%13,%14,%15,%16,%17,%18,%19,%20,%21,%22,%23,%24,%25,%26,%27,%28,%29,%30,%31,"
                 "%32,%33,%34,%35,%36,%37,%38,%39,%40,%41,%42,%43,%44,%45,%46,%47,%48,%49,%50,%51,%52,%53,%54,%55,%56,%57,%58,%59,%60,%61,%62,%63,"
                 "%64,%65,%66,%67,%68,%69,%70,%71,%72,%73,%74,%75,%76,%77,%78,%79,%80,%81,%82,%83,%84,%85,%86,%87,%88,%89,%90,%91,%92,%93,%94,%95},"
                 "%96,%97,1,1,1,0,1;"
                 : R8(d, 0), R8(d, 8), R8(d, 16), R8(d, 24), R8(d, 32), R8(d, 40), R8(d, 48), R8(d, 56), R8(d, 64), R8(d, 72), R8(d, 80), R8(d, 88)
                 : "l"(da), "l"(db));
}
__device__ __forceinline__ void wgmma64_tt(float* d, uint64_t da, uint64_t db, int sc) {
    asm volatile("{.reg .pred p; setp.ne.b32 p,%34,0; wgmma.mma_async.sync.aligned.m64n64k16.f32.bf16.bf16 {"
                 "%0,%1,%2,%3,%4,%5,%6,%7,%8,%9,%10,%11,%12,%13,%14,%15,%16,%17,%18,%19,%20,%21,%22,%23,%24,%25,%26,%27,%28,%29,%30,%31},"
                 "%32,%33,p,1,1,1,1;}"
                 : R8(d, 0), R8(d, 8), R8(d, 16), R8(d, 24)
                 : "l"(da), "l"(db), "r"(sc));
}
__device__ __forceinline__ void wgmma128_rs(float* d, const uint4& a, uint64_t db, int sc) {
    asm volatile("{.reg .pred p; setp.ne.b32 p,%69,0; wgmma.mma_async.sync.aligned.m64n128k16.f32.bf16.bf16 {"
                 "%0,%1,%2,%3,%4,%5,%6,%7,%8,%9,%10,%11,%12,%13,%14,%15,%16,%17,%18,%19,%20,%21,%22,%23,%24,%25,%26,%27,%28,%29,%30,%31,"
                 "%32,%33,%34,%35,%36,%37,%38,%39,%40,%41,%42,%43,%44,%45,%46,%47,%48,%49,%50,%51,%52,%53,%54,%55,%56,%57,%58,%59,%60,%61,%62,%63},"
                 "{%64,%65,%66,%67},%68,p,1,1,1;}"
                 : R8(d, 0), R8(d, 8), R8(d, 16), R8(d, 24), R8(d, 32), R8(d, 40), R8(d, 48), R8(d, 56)
                 : "r"(a.x), "r"(a.y), "r"(a.z), "r"(a.w), "l"(db), "r"(sc));
}
__device__ __forceinline__ void mma16816(float* c, uint32_t a0, uint32_t a1, uint32_t a2, uint32_t a3, uint32_t b0, uint32_t b1) {
    asm("mma.sync.aligned.m16n8k16.row.col.f32.bf16.bf16.f32 {%0,%1,%2,%3},{%4,%5,%6,%7},{%8,%9},{%0,%1,%2,%3};"
        : "+f"(c[0]), "+f"(c[1]), "+f"(c[2]), "+f"(c[3]) : "r"(a0), "r"(a1), "r"(a2), "r"(a3), "r"(b0), "r"(b1));
}
__device__ __forceinline__ void ldsm4(uint32_t* r, uint32_t a) {
    asm volatile("ldmatrix.sync.aligned.m8n8.x4.shared.b16 {%0,%1,%2,%3},[%4];" : "=r"(r[0]), "=r"(r[1]), "=r"(r[2]), "=r"(r[3]) : "r"(a) : "memory");
}
__device__ __forceinline__ void ldsm4t(uint32_t* r, uint32_t a) {
    asm volatile("ldmatrix.sync.aligned.m8n8.x4.trans.shared.b16 {%0,%1,%2,%3},[%4];" : "=r"(r[0]), "=r"(r[1]), "=r"(r[2]), "=r"(r[3]) : "r"(a) : "memory");
}
__device__ __forceinline__ void stsm4(uint32_t a, uint32_t r0, uint32_t r1, uint32_t r2, uint32_t r3) {
    asm volatile("stmatrix.sync.aligned.m8n8.x4.shared.b16 [%0],{%1,%2,%3,%4};" ::"r"(a), "r"(r0), "r"(r1), "r"(r2), "r"(r3) : "memory");
}
__device__ __forceinline__ uint32_t lds32(uint32_t a) { uint32_t v; asm volatile("ld.shared.b32 %0,[%1];" : "=r"(v) : "r"(a) : "memory"); return v; }
__device__ __forceinline__ uint4 lds128(uint32_t a) { uint4 v; asm volatile("ld.shared.v4.b32 {%0,%1,%2,%3},[%4];" : "=r"(v.x), "=r"(v.y), "=r"(v.z), "=r"(v.w) : "r"(a) : "memory"); return v; }
__device__ __forceinline__ void sts16(uint32_t a, uint32_t v) { asm volatile("st.shared.b16 [%0],%1;" ::"r"(a), "h"((unsigned short)v) : "memory"); }
__device__ __forceinline__ void sts32(uint32_t a, uint32_t v) { asm volatile("st.shared.b32 [%0],%1;" ::"r"(a), "r"(v) : "memory"); }
__device__ __forceinline__ void sts64(uint32_t a, uint32_t x, uint32_t y) { asm volatile("st.shared.v2.b32 [%0],{%1,%2};" ::"r"(a), "r"(x), "r"(y) : "memory"); }
__device__ __forceinline__ void sts128(uint32_t a, uint32_t x, uint32_t y, uint32_t z, uint32_t w) { asm volatile("st.shared.v4.b32 [%0],{%1,%2,%3,%4};" ::"r"(a), "r"(x), "r"(y), "r"(z), "r"(w) : "memory"); }
__device__ __forceinline__ uint32_t pack2(float lo, float hi) { uint32_t d; asm("cvt.rn.bf16x2.f32 %0,%1,%2;" : "=r"(d) : "f"(hi), "f"(lo)); return d; }
__device__ __forceinline__ float bf_lo(uint32_t v) { return __uint_as_float(v << 16); }
__device__ __forceinline__ float bf_hi(uint32_t v) { return __uint_as_float(v & 0xffff0000u); }
__device__ __forceinline__ float bf_round(float v) { return bf_lo(pack2(v, 0.f)); }
__device__ __forceinline__ uint32_t hmax2(uint32_t a, uint32_t b) { uint32_t d; asm("max.bf16x2 %0,%1,%2;" : "=r"(d) : "r"(a), "r"(b)); return d; }
__device__ __forceinline__ uint32_t hmin2(uint32_t a, uint32_t b) { uint32_t d; asm("min.bf16x2 %0,%1,%2;" : "=r"(d) : "r"(a), "r"(b)); return d; }
__device__ __forceinline__ uint32_t hmul2(uint32_t a, uint32_t b) { uint32_t d; asm("mul.rn.bf16x2 %0,%1,%2;" : "=r"(d) : "r"(a), "r"(b)); return d; }
__device__ __forceinline__ float ex2(float x) { float y; asm("ex2.approx.ftz.f32 %0,%1;" : "=f"(y) : "f"(x)); return y; }
__device__ __forceinline__ float rcp(float x) { float y; asm("rcp.approx.ftz.f32 %0,%1;" : "=f"(y) : "f"(x)); return y; }
__device__ __forceinline__ uint32_t ld_nc(const uint32_t* p) { uint32_t v; asm volatile("ld.global.nc.b32 %0,[%1];" : "=r"(v) : "l"(p)); return v; }
__device__ __forceinline__ uint2 ld_nc64(const uint2* p) { uint2 v; asm volatile("ld.global.nc.v2.b32 {%0,%1},[%2];" : "=r"(v.x), "=r"(v.y) : "l"(p)); return v; }
__device__ __forceinline__ unsigned ld_acq(const unsigned* p) { unsigned v; asm volatile("ld.acquire.gpu.global.u32 %0,[%1];" : "=r"(v) : "l"(p) : "memory"); return v; }
__device__ __forceinline__ unsigned ld_rlx(const unsigned* p) { unsigned v; asm volatile("ld.relaxed.gpu.global.u32 %0,[%1];" : "=r"(v) : "l"(p) : "memory"); return v; }
__device__ __forceinline__ uint2 ld_rlx64(const void* p) { uint2 v; asm volatile("{.reg .b64 t; ld.relaxed.gpu.global.b64 t,[%2]; mov.b64 {%0,%1},t;}" : "=r"(v.x), "=r"(v.y) : "l"(p) : "memory"); return v; }
__device__ __forceinline__ uint4 ld_rlx128(const void* p) {
    uint4 v;
    asm volatile("{.reg .b64 t,u; ld.relaxed.gpu.global.v2.b64 {t,u},[%4]; mov.b64 {%0,%1},t; mov.b64 {%2,%3},u;}" : "=r"(v.x), "=r"(v.y), "=r"(v.z), "=r"(v.w) : "l"(p) : "memory");
    return v;
}
__device__ __forceinline__ void st_rlx32(void* p, uint32_t x) { asm volatile("st.relaxed.gpu.global.u32 [%0],%1;" ::"l"(p), "r"(x) : "memory"); }
__device__ __forceinline__ void st_rlx64(void* p, uint32_t x, uint32_t y) { asm volatile("{.reg .b64 t; mov.b64 t,{%1,%2}; st.relaxed.gpu.global.b64 [%0],t;}" ::"l"(p), "r"(x), "r"(y) : "memory"); }
__device__ __forceinline__ void st_rlx128(void* p, uint4 v) {
    asm volatile("{.reg .b64 t,u; mov.b64 t,{%1,%2}; mov.b64 u,{%3,%4}; st.relaxed.gpu.global.v2.b64 [%0],{t,u};}" ::"l"(p), "r"(v.x), "r"(v.y), "r"(v.z), "r"(v.w) : "memory");
}
__device__ __forceinline__ uint32_t tagw(uint32_t w, uint32_t tag) { return (w & ~1u) | tag; }
__device__ __forceinline__ uint4 tag4(uint32_t x, uint32_t y, uint32_t z, uint32_t w, uint32_t tag) { return make_uint4(tagw(x, tag), y, tagw(z, tag), w); }
__device__ __forceinline__ uint32_t bad4(const uint4& v, uint32_t tag) { return (v.x ^ tag) | (v.z ^ tag); }
__device__ __forceinline__ void bar_named(int id, int n) { asm volatile("bar.sync %0,%1;" ::"r"(id), "r"(n) : "memory"); }

struct cf { float re, im; };
__device__ __forceinline__ cf cmul(cf a, cf b) { cf r; r.re = a.re * b.re - a.im * b.im; r.im = a.re * b.im + a.im * b.re; return r; }
__device__ __forceinline__ cf cexp_p(float arl, float ait, float p) {
    float mag = ex2(arl * p);
    float t = ait * p;
    t = (t - rintf(t)) * 6.283185307179586f;
    cf r; r.re = mag * __cosf(t); r.im = mag * __sinf(t);
    return r;
}

__device__ __forceinline__ void hedgehog2(const uint32_t* a, uint32_t wphi_addr, uint32_t (*out)[8]) {
    float p[2][2][4], mx[2][2];
#pragma unroll
    for (int h = 0; h < 2; h++) {
        uint32_t b[4];
        ldsm4t(b, wphi_addr + h * 512);
        float c0[4] = {0.f, 0.f, 0.f, 0.f}, c1[4] = {0.f, 0.f, 0.f, 0.f};
        mma16816(c0, a[4 * h], a[4 * h + 1], a[4 * h + 2], a[4 * h + 3], b[0], b[1]);
        mma16816(c1, a[4 * h], a[4 * h + 1], a[4 * h + 2], a[4 * h + 3], b[2], b[3]);
#pragma unroll
        for (int k = 0; k < 2; k++) {
            p[h][k][0] = c0[2 * k]; p[h][k][1] = c0[2 * k + 1]; p[h][k][2] = c1[2 * k]; p[h][k][3] = c1[2 * k + 1];
            mx[h][k] = fmaxf(fmaxf(p[h][k][0], p[h][k][1]), fmaxf(p[h][k][2], p[h][k][3]));
        }
    }
#pragma unroll
    for (int o = 1; o <= 2; o <<= 1)
#pragma unroll
        for (int h = 0; h < 2; h++)
#pragma unroll
            for (int k = 0; k < 2; k++) mx[h][k] = fmaxf(mx[h][k], __shfl_xor_sync(~0u, mx[h][k], o));
    const float L = 1.4426950408889634f;
    float pmin = 1.f;
#pragma unroll
    for (int h = 0; h < 2; h++)
#pragma unroll
        for (int k = 0; k < 2; k++) {
            const float m = -mx[h][k] * L;
            const float e0 = ex2(fmaf(p[h][k][0], L, m)), e1 = ex2(fmaf(p[h][k][1], L, m)), e2 = ex2(fmaf(p[h][k][2], L, m)), e3 = ex2(fmaf(p[h][k][3], L, m));
            const float p01 = e0 * e1, p23 = e2 * e3, pp = p01 * p23, r = rcp(pp), r01 = r * p23, r23 = r * p01;
            pmin = fminf(pmin, pp);
            out[h][k] = pack2(e0, e1); out[h][k + 2] = pack2(e2, e3);
            out[h][4 + k] = pack2(r01 * e1, r01 * e0); out[h][4 + k + 2] = pack2(r23 * e3, r23 * e2);
        }
    if (__builtin_expect(__any_sync(~0u, !(pmin > 1e-18f)), 0)) {
#pragma unroll
        for (int h = 0; h < 2; h++)
#pragma unroll
            for (int k = 0; k < 2; k++) {
                float m = fminf(fminf(p[h][k][0], p[h][k][1]), fminf(p[h][k][2], p[h][k][3]));
                m = fminf(m, __shfl_xor_sync(~0u, m, 1));
                m = fminf(m, __shfl_xor_sync(~0u, m, 2)) * L;
                out[h][4 + k] = pack2(ex2(fmaf(p[h][k][0], -L, m)), ex2(fmaf(p[h][k][1], -L, m)));
                out[h][4 + k + 2] = pack2(ex2(fmaf(p[h][k][2], -L, m)), ex2(fmaf(p[h][k][3], -L, m)));
            }
    }
}

__global__ void __launch_bounds__(512, 1)
fused_kernel(Scratch* __restrict__ scr, const bf16* __restrict__ logA, const bf16* __restrict__ Aim, const bf16* __restrict__ Cre,
             const bf16* __restrict__ Cim, const bf16* __restrict__ logdt, const bf16* __restrict__ Dskip, const bf16* __restrict__ wphi,
             const bf16* __restrict__ gatew, bf16* __restrict__ out,
             const __grid_constant__ CUtensorMap mx, const __grid_constant__ CUtensorMap mw, const __grid_constant__ CUtensorMap mwo) {
    extern __shared__ __align__(1024) uint8_t smem[];
    const uint32_t sb = s2u(smem);
    const int tid = threadIdx.x, warp = __shfl_sync(~0u, tid >> 5, 0), lane = tid & 31;
    const int g = lane >> 2, q = lane & 3, w4 = warp & 3;
    const int bi = blockIdx.x, bi_i = bi & 15, bi_j = bi >> 4;
    const uint32_t bar = sb + OFF_BAR;
    const int rot = (bi_j & 3) * 2, xkb = bi_j >> 2;
    auto load_stage = [&](int kb) {
        const uint32_t b = bar + 8 * (BAR_FULL + (kb & 3)), d = sb + (kb & 3) * SLOT;
        const int kc = ((kb + rot) & 7) * 64;
        mbar_expect(b, SLOT);
        tma2d(d, &mx, kc, bi_i * 128, b);
        tma3d(d + 16384, &mw, bi_j * 64, kc, 0, b);
    };

    const int ch = bi * 4 + w4;
    const int pidx = ch * 64 + lane * 2 + (warp >> 3);
    const uint32_t pla = ld_nc((const uint32_t*)logA + pidx), pai = ld_nc((const uint32_t*)Aim + pidx);
    const uint32_t pcr = ld_nc((const uint32_t*)Cre + pidx), pci = ld_nc((const uint32_t*)Cim + pidx);
    uint32_t pdt = ld_nc((const uint32_t*)logdt + (ch >> 1));
    const uint32_t pds = ld_nc((const uint32_t*)Dskip + (ch >> 1));
    unsigned done0 = ld_rlx(scr->done);
    if (tid == 0) {
        for (int s = 0; s < 4; s++) mbar_init(bar + 8 * (BAR_FULL + s), 1);
        asm volatile("fence.mbarrier_init.release.cluster;" ::: "memory");
        load_stage(0); load_stage(1);
        STAMP(11);
    } else if (tid == 32) {
        if (sb & 1023) __trap();
        sts32(bar + OFF_CNT, 0);
        for (int s = 0; s < 4; s++) mbar_init(bar + 8 * (BAR_EMPTY + s), 8);
        mbar_init(bar + 8 * BAR_WPHI, 1); mbar_init(bar + 8 * BAR_WO, 2); mbar_init(bar + 8 * BAR_WO2, 1); mbar_init(bar + 8 * BAR_XT, 4);
        mbar_init(bar + 8 * BAR_DONE, 9); mbar_init(bar + 8 * BAR_KG, 12); mbar_init(bar + 8 * BAR_SP, 1); mbar_init(bar + 8 * BAR_PUB, 8);
        mbar_init(bar + 8 * BAR_KVF, 4); mbar_init(bar + 8 * BAR_UR, 4); mbar_init(bar + 8 * BAR_WR, 4); mbar_init(bar + 8 * BAR_PREP, 4); mbar_init(bar + 8 * BAR_SP2, 1);
        asm volatile("fence.mbarrier_init.release.cluster;" ::: "memory");
        mbar_expect(bar + 8 * BAR_WPHI, 3072);
        bulk_g2s(sb + OFF_GW, gatew, 1024, bar + 8 * BAR_WPHI);
        bulk_g2s(sb + OFF_WPHI, wphi + bi_j * 1024, 2048, bar + 8 * BAR_WPHI);
    } else if (tid == 64) {
        asm volatile("prefetch.tensormap [%0];" ::"l"(&mw) : "memory");
    }
    const uint32_t buf = sb + OFF_BUF + w4 * BUF_STRIDE, kb_ = sb + OFF_K + w4 * KT_BYTES;
    if ((warp >> 2) == 2) {
#pragma unroll
        for (int v = 0; v < 7; v++) if (v * 32 + lane < KT_BYTES / 16) sts128(kb_ + (v * 32 + lane) * 16, 0, 0, 0, 0);
    }
    __syncthreads();
    asm volatile("" : "+r"(pdt), "+r"(done0)::"memory");
    const unsigned epoch1 = (done0 >> 7) + 1u;
    const uint32_t tag = epoch1 & 1u;

    const int st = tid & 127;
    const uint32_t ub = sb + OFF_U + w4 * U_STRIDE + 256, spare = sb + (w4 < 2 ? OFF_SP0 : OFF_SP1) + (w4 & 1) * 4096;
    auto stg_of = [&](int w) { return w < 8 ? sb + 3 * SLOT + w * 7296 : sb + 2 * SLOT + (w & 3) * 7296; };
    float kc[24];
#pragma unroll
    for (int t = 0; t < 24; t++) kc[t] = 0.f;
    {
        const float dt = bf_round(expf((ch & 1) ? bf_hi(pdt) : bf_lo(pdt)));
        const uint32_t stg = (warp >> 2) == 2 ? buf : stg_of(warp);
        const int sh = ((warp >> 2) & 1) * 16;
        auto pick = [&](uint32_t v) { return __uint_as_float((v >> sh) << 16); };
        const float ea = bf_round(expf(pick(pla)));
        const float arl = (-ea * dt) * 1.4426950408889634f, ait = (pick(pai) * dt) * 0.15915494309189535f;
        cf C2; C2.re = 2.0f * (pick(pcr) * dt); C2.im = 2.0f * (pick(pci) * dt);
        const cf z1 = cexp_p(arl, ait, 1.0f), z128 = cexp_p(arl, ait, 128.0f);
        cf z8 = cexp_p(arl, ait, 8.0f); z8.im = -z8.im;
        const uint32_t lp = stg + lane * 4;
        auto put = [&](int row, const cf& v) { sts32((lp ^ ((row & 7) << 4)) + row * 128, pack2(v.re, v.im)); };
        {
            const cf z16 = cmul(z8, z8);
            cf e; e.re = 1.f; e.im = 0.f;
            cf o = z8;
            put(0, e); put(1, o);
            e = z16; put(2, e);
#pragma unroll
            for (int b = 3; b < 16; b += 2) {
                o = cmul(o, z16); put(b, o);
                if (b + 1 < 16) { e = cmul(e, z16); put(b + 1, e); }
            }
        }
        cf h[8];
        h[0] = C2; put(16, h[0]);
        {
            const cf z2 = cmul(z1, z1);
            h[1] = cmul(h[0], z1);
#pragma unroll
            for (int r = 2; r < 8; r++) h[r] = cmul(h[r - 2], z2);
#pragma unroll
            for (int r = 1; r < 8; r++) put(16 + r, h[r]);
        }
#pragma unroll
        for (int r = 0; r < 8; r++) { h[r] = cmul(h[r], z128); put(24 + r, h[r]); }
#pragma unroll
        for (int al = 0; al < 2; al++)
#pragma unroll
            for (int r = 0; r < 4; r++) { h[2 * r] = cmul(h[2 * r], z128); put(32 + al * 4 + r, h[2 * r]); }
#pragma unroll
        for (int al = 0; al < 4; al++)
#pragma unroll
            for (int r = 0; r < 2; r++) { h[4 * r] = cmul(h[4 * r], z128); put(40 + al * 2 + r, h[4 * r]); }
#pragma unroll
        for (int al = 0; al < 9; al++) { h[0] = cmul(h[0], z128); put(48 + al, h[0]); }
        __syncwarp();
        const int lr = lane & 7, lm = lane >> 3;
#pragma unroll
        for (int kp = 0; kp < 2; kp++) {
            uint32_t a0[4], a1[4];
            ldsm4(a0, stg + ((lm & 1) * 8 + lr) * 128 + (((4 * kp + (lm >> 1)) ^ lr) << 4));
            ldsm4(a1, stg + ((lm & 1) * 8 + lr) * 128 + (((4 * kp + 2 + (lm >> 1)) ^ lr) << 4));
#pragma unroll
            for (int t = 0; t < 6; t++) {
                uint32_t b[4];
                ldsm4(b, stg + (16 + 8 * t + lr) * 128 + (((4 * kp + lm) ^ lr) << 4));
                mma16816(kc + 4 * t, a0[0], a0[1], a0[2], a0[3], b[0], b[1]);
                mma16816(kc + 4 * t, a1[0], a1[1], a1[2], a1[3], b[2], b[3]);
            }
        }
        __syncwarp();
        if ((warp >> 2) != 2) {
#pragma unroll
            for (int t = 0; t < 6; t++)
                sts128(stg + (t * 32 + lane) * 16, __float_as_uint(kc[4 * t]), __float_as_uint(kc[4 * t + 1]), __float_as_uint(kc[4 * t + 2]), __float_as_uint(kc[4 * t + 3]));
            __syncwarp();
            if (lane == 0) mbar_arrive(bar + 8 * BAR_KG);
        }
    }

    if (warp < 8) {
        asm volatile("setmaxnreg.inc.sync.aligned.u32 160;");
        const int wg = warp >> 2;
        if (warp == 0) STAMP(21);
        float acc[96];
        const int srow = warp * 16 + (lane & 15);
        const uint32_t srow_a = srow * 128;
        const int sx = srow & 7, shi = lane >> 4;
#pragma unroll
        for (int r = 0; r < 96; r++) acc[r] = 0.f;
        fence_regs<96>(acc);
        const uint64_t da0 = mkdesc(sb + wg * 8192, 16, 1024), db0 = mkdesc(sb + 16384, 8192, 1024);
#pragma unroll 1
        for (int kb = 0; kb < 8; kb++) {
            const int s = kb & 3;
            const uint64_t da = da0 + s * (SLOT >> 4), db = db0 + s * (SLOT >> 4);
            if (warp == 0) STAMP(40 + kb);
            mbar_wait(bar + 8 * (BAR_FULL + s), kb >> 2);
            if (warp == 0) STAMP(32 + kb);
            wg_fence();
#pragma unroll
            for (int k = 0; k < 4; k++) wgmma192(acc, da + 2 * k, db + 128 * k);
            wg_commit();
            wg_wait<1>();
            if (lane == 0 && kb > 0) mbar_arrive(bar + 8 * (BAR_EMPTY + ((kb - 1) & 3)));
        }
        mbar_wait(bar + 8 * BAR_WPHI, 0);
        wg_wait<0>();
        fence_regs<96>(acc);
        if (lane == 0) mbar_arrive(bar + 8 * BAR_DONE);
        if (warp == 0) STAMP(1);
        uint32_t in[32], va[16];
#pragma unroll
        for (int r = 0; r < 16; r++) {
            in[r] = pack2(acc[32 + 2 * r], acc[32 + 2 * r + 1]);
            in[16 + r] = pack2(acc[2 * r], acc[2 * r + 1]);
            va[r] = pack2(acc[64 + 2 * r], acc[64 + 2 * r + 1]);
        }
        const uint32_t wphi_a = sb + OFF_WPHI + (lane & 15) * 32 + (lane >> 4) * 16;
        uint32_t pq[4][8];
#pragma unroll 1
        for (int it = 0; it < 4; it++) {
            hedgehog2(in, wphi_a + (it & 1) * 1024, pq + 2);
#pragma unroll
            for (int r = 0; r < 24; r++) in[r] = in[r + 8];
            if (it < 2) {
#pragma unroll
                for (int hs = 0; hs < 4; hs++) {
                    float c[4] = {0.f, 0.f, 0.f, 0.f};
                    uint32_t* o = pq[2 + (hs >> 1)] + 4 * (hs & 1);
                    mma16816(c, o[0], o[1], o[2], o[3], 0x3f803f80u, 0x3f803f80u);
                    const float r0 = rcp(c[0]), r1 = rcp(c[2]);
                    const uint32_t s0 = pack2(r0, r0), s1 = pack2(r1, r1);
                    o[0] = hmul2(o[0], s0); o[1] = hmul2(o[1], s1); o[2] = hmul2(o[2], s0); o[3] = hmul2(o[3], s1);
                }
                if (it == 0) mbar_wait(bar + 8 * BAR_DONE, 0);
                const uint32_t pt = sb + OFF_P + it * 16384 + srow_a, vt = sb + OFF_V + it * 16384 + srow_a;
#pragma unroll
                for (int hl = 0; hl < 2; hl++) {
                    stsm4(pt + (((4 * hl + shi) ^ sx) << 4), pq[2 + hl][0], pq[2 + hl][1], pq[2 + hl][2], pq[2 + hl][3]);
                    stsm4(pt + (((4 * hl + 2 + shi) ^ sx) << 4), pq[2 + hl][4], pq[2 + hl][5], pq[2 + hl][6], pq[2 + hl][7]);
                    stsm4(vt + (((2 * hl + shi) ^ sx) << 4), va[4 * hl], va[4 * hl + 1], va[4 * hl + 2], va[4 * hl + 3]);
                }
                if (lane < 16) sts128(vt + ((4 ^ sx) << 4), 0x3f803f80u, 0x3f803f80u, 0x3f803f80u, 0x3f803f80u);
#pragma unroll
                for (int r = 0; r < 8; r++) va[r] = va[r + 8];
            }
            if (it == 1) {
                asm volatile("fence.proxy.async.shared::cta;" ::: "memory");
                bar_named(1, 256);
                if (warp == 0) STAMP(2);
                float d[32];
                const uint64_t dv = mkdesc(sb + OFF_V + wg * 16384, 16, 1024), dp = mkdesc(sb + OFF_P + wg * 16384, 16, 1024);
                wg_fence();
#pragma unroll
                for (int k = 0; k < 8; k++) wgmma64_tt(d, dv + 128 * k, dp + 128 * k, k != 0);
                wg_commit();
                wg_wait<0>();
                fence_regs<32>(d);
                mbar_wait(bar + 8 * BAR_PREP, 0);
                uint4* kvp = scr->kvp + bi * 544 + wg * 272;
                if (w4 < 2) {
                    uint32_t e[16];
#pragma unroll
                    for (int r = 0; r < 16; r++) e[r] = __float_as_uint(w4 ? d[16 + r] : d[r]);
                    uint4* p = kvp + w4 * 136 + lane;
#pragma unroll
                    for (int ks = 0; ks < 2; ks++)
#pragma unroll
                        for (int nt = 0; nt < 2; nt++)
                            st_rlx128(p + (ks * 2 + nt) * 32, tag4(e[8 * ks + 2 * nt], e[8 * ks + 2 * nt + 1], e[8 * ks + 4 + 2 * nt], e[8 * ks + 4 + 2 * nt + 1], tag));
                } else if (w4 == 2 && lane < 4) {
#pragma unroll
                    for (int hl = 0; hl < 2; hl++)
#pragma unroll
                        for (int ks = 0; ks < 2; ks++)
                            st_rlx128(kvp + hl * 136 + 128 + ks * 4 + lane, tag4(__float_as_uint(d[16 * hl + 8 * ks]), __float_as_uint(d[16 * hl + 8 * ks + 1]),
                                                                                __float_as_uint(d[16 * hl + 8 * ks + 4]), __float_as_uint(d[16 * hl + 8 * ks + 5]), tag));
                }
                __syncwarp();
                if (lane == 0) mbar_arrive(bar + 8 * BAR_PUB);
                if (warp == 0) STAMP(3);
            }
            if (it == 2) {
#pragma unroll
                for (int r = 0; r < 8; r++) { pq[0][r] = pq[2][r]; pq[1][r] = pq[3][r]; }
            }
        }
        if (warp == 0) STAMP(4);
        {
            mbar_wait(bar + 8 * BAR_KVF, 0);
            uint4 kf[4][3];
#pragma unroll
            for (int hh = 0; hh < 4; hh++) {
                const uint32_t a = sb + OFF_KVF + hh * 1088;
                kf[hh][0] = lds128(a + lane * 32); kf[hh][1] = lds128(a + lane * 32 + 16); kf[hh][2] = lds128(a + 1024 + q * 16);
            }
            if (warp == 0) STAMP(5);
            uint4 own[4];
#pragma unroll
            for (int hh = 0; hh < 4; hh++) {
                float c[6][4];
#pragma unroll
                for (int t = 0; t < 6; t++) { c[t][0] = c[t][1] = c[t][2] = c[t][3] = 0.f; }
                const uint32_t* a = pq[hh];
                const bool od = g & 1;
                mma16816(c[0], a[0], a[1], a[2], a[3], od ? 0x3f803f80u : kf[hh][2].x, od ? 0x3f803f80u : kf[hh][2].y);
                mma16816(c[1], a[4], a[5], a[6], a[7], od ? 0x3f803f80u : kf[hh][2].z, od ? 0x3f803f80u : kf[hh][2].w);
                mma16816(c[2], a[0], a[1], a[2], a[3], kf[hh][0].x, kf[hh][0].y);
                mma16816(c[3], a[0], a[1], a[2], a[3], kf[hh][0].z, kf[hh][0].w);
                mma16816(c[4], a[4], a[5], a[6], a[7], kf[hh][1].x, kf[hh][1].y);
                mma16816(c[5], a[4], a[5], a[6], a[7], kf[hh][1].z, kf[hh][1].w);
                uint32_t w[4];
#pragma unroll
                for (int k = 0; k < 2; k++) {
                    const float rho = c[0][2 * k + 1] * rcp(c[1][2 * k + 1]);
                    const float r = rcp(fmaf(c[0][2 * k + 1], 1e-6f, fmaf(rho, c[1][2 * k], c[0][2 * k]))), rr = r * rho;
                    w[k] = pack2(fmaf(c[4][2 * k], rr, c[2][2 * k] * r), fmaf(c[4][2 * k + 1], rr, c[2][2 * k + 1] * r));
                    w[2 + k] = pack2(fmaf(c[5][2 * k], rr, c[3][2 * k] * r), fmaf(c[5][2 * k + 1], rr, c[3][2 * k + 1] * r));
                }
                own[hh] = tag4(w[0], w[1], w[2], w[3], tag);
            }
            uint4* og = scr->o + ((bi_i * 8 + warp) * 32 + bi_j * 4) * 32 + lane;
#pragma unroll
            for (int hh = 0; hh < 4; hh++) st_rlx128(og + hh * 32, own[hh]);
        }
        if (warp == 0) STAMP(6);
        float oc[64];
        const int slab = bi_i * 8 + (bi_j >> 2) * 4 + w4;
        const uint8_t* yb = (const uint8_t*)scr->y + (size_t)((bi_j & 3) * 32 + wg * 16 + (q >> 1)) * 16384 + slab * 128 + g * 16 + (q & 1) * 8;
        const unsigned* gp = scr->g + (slab * 8 + (g >> 1)) * 8 + (g & 1) * 4;
        uint2 yv[8]; unsigned g0, g1;
        {
            const uint4* osrc = scr->o + (slab * 32 + wg * 16) * 32 + lane;
            uint4 fr[16];
            const unsigned* probe = (const unsigned*)(osrc - lane + ((lane & 3) * 4 + 3) * 32 + 31) + 2;
            {
                unsigned miss = ~0u;
                int n = 0;
#pragma unroll
                for (int s = 0; s < 4; s++) {
#pragma unroll 1
                    while ((miss >> s) & 1) { miss = __ballot_sync(~0u, (ld_rlx(probe) ^ tag) & 1); if (++n > SPIN_LIMIT) break; }
#pragma unroll
                    for (int k = 4 * s; k < 4 * s + 4; k++) fr[k] = ld_rlx128(osrc + k * 32);
                }
            }
            if (warp == 0) STAMP(14);
            mbar_wait(bar + 8 * (wg ? BAR_WO2 : BAR_WO), 0);
            const uint64_t dw = mkdesc(sb + wg * 2 * SLOT, wg ? 32768 : SLOT, 1024);
#pragma unroll
            for (int s = 0; s < 4; s++) {
                int n = 0;
#pragma unroll 1
                while (__builtin_expect(__any_sync(~0u, (bad4(fr[4 * s], tag) | bad4(fr[4 * s + 1], tag) | bad4(fr[4 * s + 2], tag) | bad4(fr[4 * s + 3], tag)) & 1), 0)) {
#pragma unroll
                    for (int k = 4 * s; k < 4 * s + 4; k++) fr[k] = ld_rlx128(osrc + k * 32);
                    if (++n > SPIN_LIMIT) break;
                }
                wg_fence();
#pragma unroll
                for (int hh = 0; hh < 4; hh++) wgmma128_rs(oc, fr[4 * s + hh], dw + 128 * (4 * s + hh), (s | hh) != 0);
                wg_commit();
                if (s == 1) {
                    wg_wait<1>();
#pragma unroll
                    for (int nt = 0; nt < 8; nt++) yv[nt] = ld_rlx64(yb + nt * 32768);
                    g0 = ld_rlx(gp); g1 = ld_rlx(gp + 32);
                }
            }
            if (warp == 0) STAMP(7);
            {
                const unsigned* yprobe = scr->yflag + ((bi_j & 3) * 32 + wg * 16 + (lane & 15)) * 8;
                int n = 0;
#pragma unroll 1
                while (true) {
                    uint32_t bad = (g0 ^ tag) | (g1 ^ tag);
#pragma unroll
                    for (int nt = 0; nt < 8; nt++) bad |= yv[nt].x ^ tag;
                    if (!__any_sync(~0u, bad & 1)) break;
#pragma unroll 1
                    while (__any_sync(~0u, (ld_rlx(yprobe) ^ tag) & 1)) { if (++n > SPIN_LIMIT) break; }
#pragma unroll
                    for (int nt = 0; nt < 8; nt++) yv[nt] = ld_rlx64(yb + nt * 32768);
                    g0 = ld_rlx(gp); g1 = ld_rlx(gp + 32);
                    if (++n > SPIN_LIMIT) break;
                }
            }
            if (warp == 0) STAMP(28);
            wg_wait<0>();
            fence_regs<64>(oc);
        }
        {
            bar_named(3 + wg, 128);
            const uint32_t xw = sb + wg * 2 * SLOT + (tid & 127) * 16, xr = sb + (wg ^ 1) * 2 * SLOT + (tid & 127) * 16;
#pragma unroll
            for (int r = 0; r < 8; r++) {
                const float* o = oc + 4 * r;
                sts128(xw + r * 2048, __float_as_uint(wg ? o[0] : o[32]), __float_as_uint(wg ? o[1] : o[33]), __float_as_uint(wg ? o[2] : o[34]), __float_as_uint(wg ? o[3] : o[35]));
            }
#pragma unroll
            for (int r = 0; r < 32; r++) oc[r] = wg ? oc[32 + r] : oc[r];
            bar_named(1, 256);
            if (warp == 0) STAMP(8);
            const float ga = bf_hi(g0), gb = bf_hi(g1);
            const float ha = bf_round(1.0f - ga), hb = bf_round(1.0f - gb);
            uint32_t w[8][2];
#pragma unroll
            for (int nt = 0; nt < 8; nt++) {
                const uint4 p = lds128(xr + nt * 2048);
                w[nt][0] = pack2(fmaf(ga, oc[4 * nt] + __uint_as_float(p.x), ha * bf_lo(yv[nt].x)), fmaf(ga, oc[4 * nt + 1] + __uint_as_float(p.y), ha * bf_hi(yv[nt].x)));
                w[nt][1] = pack2(fmaf(gb, oc[4 * nt + 2] + __uint_as_float(p.z), hb * bf_lo(yv[nt].y)), fmaf(gb, oc[4 * nt + 3] + __uint_as_float(p.w), hb * bf_hi(yv[nt].y)));
            }
            const uint32_t ob = sb + wg * 2 * SLOT + 16384 + w4 * 2048;
#pragma unroll
            for (int nt = 0; nt < 8; nt += 2)
                stsm4(ob + (lane & 15) * 128 + (((nt + shi) ^ (lane & 7)) << 4), w[nt][0], w[nt][1], w[nt + 1][0], w[nt + 1][1]);
            __syncwarp();
            bf16* op = out + (size_t)(slab * 16) * 512 + (bi_j & 3) * 128 + wg * 64 + (lane & 7) * 8;
#pragma unroll
            for (int it = 0; it < 4; it++) {
                const int r = it * 4 + (lane >> 3);
                uint4 v = lds128(ob + r * 128 + (((lane & 7) ^ (r & 7)) << 4));
                *(uint4*)(op + r * 512) = v;
            }
        }
        if (warp == 0) STAMP(10);
    } else if (warp < 12) {
        mbar_wait(bar + 8 * BAR_KG, 0);
#pragma unroll
        for (int t = 0; t < 18; t++) {
            const uint4 v = lds128(stg_of(w4 + (t / 6) * 4) + ((t % 6) * 32 + lane) * 16);
            kc[4 * (t % 6)] += __uint_as_float(v.x); kc[4 * (t % 6) + 1] += __uint_as_float(v.y); kc[4 * (t % 6) + 2] += __uint_as_float(v.z); kc[4 * (t % 6) + 3] += __uint_as_float(v.w);
        }
        asm volatile("fence.proxy.async.shared::cta;" ::: "memory");
        bar_named(2, 128);
        if (st == 0) { load_stage(2); load_stage(3); mbar_arrive(bar + 8 * BAR_SP); }
        if (warp == 8) STAMP(22);
        if (lane == 0) kc[4 * 0 + 0] += ((ch & 1) ? bf_hi(pds) : bf_lo(pds));
        const uint32_t k1024 = __shfl_sync(~0u, pack2(kc[4 * 4 + 0], 0.f), 0);
#pragma unroll
        for (int i = 0; i < 2; i++) {
            const int be = g + 8 * i;
#pragma unroll
            for (int t = 0; t < 2; t++) {
                const uint32_t a = kb_ + (KW_D + 128 * t + 8 * be + 2 * q) * 4;
                const uint32_t w = pack2(kc[4 * t + 2 * i + 1], kc[4 * t + 2 * i]);
                sts32(a + 4, w); sts16(a, w >> 16); sts16(a + 10, w);
            }
            {
                const int p = 256 + 128 * (q >> 1) + 8 * be + 4 * (q & 1);
                const uint32_t a = kb_ + (KW_D + p) * 4;
                const uint32_t w = pack2(kc[4 * 2 + 2 * i + 1], kc[4 * 2 + 2 * i]);
                const uint32_t aa = (w >> 16) | (w & 0xffff0000u);
                if (p != 256) { sts16(a - 4, aa); sts32(a, aa); } else sts16(a, aa);
                sts32(a + 4, aa); sts32(a + 8, w); sts16(a + 14, w);
            }
            {
                const int k = 64 + 16 * q + be;
                const uint32_t w = pack2(kc[4 * 3 + 2 * i], kc[4 * 3 + 2 * i + 1]);
                if (k != 64) sts16(kb_ + (KW_2 + ((k - 1) >> 1) - 24) * 4 + (k & 1) * 2, w);
                else {
                    const uint32_t a = kb_ + (KW_D + 511) * 4, aa = (w << 16) | (w & 0xffffu);
                    sts16(a, w); sts32(a + 4, aa); sts32(a + 8, aa); sts32(a + 12, aa); sts16(a + 18, w);
                }
                sts16(kb_ + (KW_2 + 48 + (k >> 1) - 24) * 4 + ((k & 1) ^ 1) * 2, w >> 16);
            }
#pragma unroll
            for (int b = 0; b < 2; b++) {
                const int k = 64 + 8 * (2 * q + b) + (be >> 1);
                const uint32_t w = pack2(kc[4 * 4 + 2 * i + b], 0.f);
                if (!(be & 1) && k == 64) sts16(kb_ + (KW_2 + 63 - 24) * 4, w);
                else {
                    const uint32_t a = kb_ + (KW_3 + ((be & 1) ? 80 + k : k - 1) - 48) * 4;
                    sts16(a, w);
                    if (!((be & 1) && k == 127)) sts16(a + 6, w);
                }
            }
        }
        if (lane == 0) sts16(kb_ + (KW_3 + 127 - 48) * 4, pack2(kc[4 * 5 + 0], 0.f));
        if (st < 8) st_rlx32(scr->yflag + bi * 8 + st, tag ^ 1u);
        if (warp == 8) {
            STAMP(17);
            const int row = bi_j * 16 + (lane >> 1), half = lane & 1;
            unsigned* gp = scr->g + (bi_i * 64 + bi_j * 8) * 8 + lane * 2;
            st_rlx64(gp, tag ^ 1u, tag ^ 1u);
            float gs0 = 0.f, gs1 = 0.f;
            mbar_wait(bar + 8 * BAR_WPHI, 0);
#pragma unroll 1
            for (int kb = 0; kb < 8; kb++) {
                const int s = kb & 3;
                mbar_wait(bar + 8 * (BAR_FULL + s), kb >> 2);
#pragma unroll
                for (int c = 0; c < 4; c++) {
                    const uint4 xv = lds128(sb + s * SLOT + row * 128 + (((half * 4 + c) ^ (row & 7)) << 4));
                    const uint4 gw = lds128(sb + OFF_GW + ((kb + rot) & 7) * 128 + half * 64 + c * 16);
                    const uint32_t p0 = hmul2(xv.x, gw.x), p1 = hmul2(xv.y, gw.y), p2 = hmul2(xv.z, gw.z), p3 = hmul2(xv.w, gw.w);
                    gs0 += (bf_lo(p0) + bf_lo(p1)) + (bf_lo(p2) + bf_lo(p3));
                    gs1 += (bf_hi(p0) + bf_hi(p1)) + (bf_hi(p2) + bf_hi(p3));
                }
                if (kb < 6) {
                    mbar_wait(bar + 8 * (BAR_EMPTY + s), kb >> 2);
                    if (kb == xkb) mbar_wait(bar + 8 * BAR_XT, 0);
                    if (lane == 0) {
                        STAMP(48 + kb);
                        if (kb < 4) load_stage(kb + 4);
                        else {
                            mbar_expect(bar + 8 * BAR_WO, 32768);
                            tma2d(sb + s * SLOT, &mwo, (bi_j & 3) * 128 + s * 64, 0, bar + 8 * BAR_WO);
                            if (kb == 5) mbar_arrive(bar + 8 * BAR_SP2);
                        }
                    }
                }
                __syncwarp();
            }
            if (lane == 0) mbar_arrive(bar + 8 * BAR_DONE);
            float gs = gs0 + gs1;
            gs += __shfl_xor_sync(~0u, gs, 1);
            const uint32_t gv = __float_as_uint(bf_round(rcp(1.0f + ex2(-1.4426950408889634f * bf_round(gs))))) | tag;
            st_rlx64(gp, gv, gv);
        }
        mbar_wait(bar + 8 * BAR_UR, 0);
        mbar_wait(bar + 8 * BAR_DONE, 0);
        if (warp == 8) STAMP(23);
        float y[16][4];
#pragma unroll
        for (int nt = 0; nt < 16; nt++) { y[nt][0] = y[nt][1] = y[nt][2] = y[nt][3] = 0.f; }
        {
            uint32_t Bp[32], A[5][3];
            auto uaddr = [&](int rho) { const int R0 = (lane >> 4) * 8 + (lane & 7) - rho; return ub + (((2 * R0 + ((lane >> 3) & 1)) ^ ((R0 >> 2) & 1)) << 4); };
            const uint32_t kd = kb_ + (KW_D + g - 2 * q) * 4;
            auto lda = [&](int rho) {
#pragma unroll
                for (int ga = 0; ga < 5; ga++) {
                    const uint32_t a = kd + (ga < 4 ? rho : (rho & 1)) * 64 + ga * 512;
                    A[ga][0] = lds32(a); A[ga][1] = lds32(a + 32); A[ga][2] = lds32(a - 32);
                }
            };
            {
                const uint32_t a = uaddr(0);
#pragma unroll
                for (int p = 0; p < 8; p++) ldsm4(Bp + 4 * p, a + p * 512);
            }
#pragma unroll 1
            for (int rho = 0; rho < 8; rho++) {
                lda(rho);
                if (rho < 2) {
#pragma unroll
                    for (int nt = 4; nt < 16; nt++) mma16816(y[nt], A[4][0], A[4][1], A[4][2], A[4][0], Bp[2 * (nt - 4)], Bp[2 * (nt - 4) + 1]);
                }
#pragma unroll
                for (int ga = 0; ga < 3; ga++)
#pragma unroll
                    for (int nt = 15; nt >= ga; nt--) mma16816(y[nt], A[ga][0], A[ga][1], A[ga][2], A[ga][0], Bp[2 * (nt - ga)], Bp[2 * (nt - ga) + 1]);
                const uint32_t an = uaddr(rho + 1);
                ldsm4(Bp + 28, an + 7 * 512);
#pragma unroll
                for (int nt = 15; nt >= 3; nt--) {
                    mma16816(y[nt], A[3][0], A[3][1], A[3][2], A[3][0], Bp[2 * (nt - 3)], Bp[2 * (nt - 3) + 1]);
                    if (nt & 1) ldsm4(Bp + 2 * (nt - 3), an + ((nt - 3) >> 1) * 512);
                }
            }
        }
        if (warp == 8) STAMP(18);
        mbar_wait(bar + 8 * BAR_WR, 0);
#pragma unroll 1
        for (int ph = 0; ph < 2; ph++) {
            uint32_t B[5][2];
            const uint32_t ka = kb_ + (KW_2 + ph * 48 + 8 + g - q) * 4;
#pragma unroll
            for (int dd = 0; dd < 5; dd++) { B[dd][0] = lds32(ka + dd * 32); B[dd][1] = lds32(ka + dd * 32 - 16); }
            const uint32_t wa = buf + ph * W3_OFF + ((lane & 7) + ((lane >> 3) & 1) + (lane >> 4) * 8) * 16;
#pragma unroll
            for (int s = 0; s < 12; s++) {
                uint32_t A[4];
                ldsm4t(A, wa + s * 256);
#pragma unroll
                for (int dd = 0; dd < 5; dd++)
                    if (s + 4 + dd < 16) mma16816(y[s + 4 + dd], A[0], A[1], A[2], A[3], B[dd][0], B[dd][1]);
            }
        }
        {
            const int ap = (lane & 7) + (lane >> 4) * 8;
            const uint32_t loff = ((2 * ap + ((lane >> 3) & 1)) ^ ((ap >> 2) & 1)) << 4;
#pragma unroll 1
            for (int ph = 0; ph < 2; ph++) {
                uint32_t B[8][2];
                const uint32_t wb = (ph ? spare : buf + W9_OFF) + loff;
                const uint32_t ka = kb_ + (KW_3 + ph * 80 + 16 + g - 2 * q) * 4;
#pragma unroll
                for (int dd = 0; dd < 8; dd++) { B[dd][0] = lds32(ka + dd * 32); B[dd][1] = lds32(ka + dd * 32 - 32); }
#pragma unroll
                for (int s = 0; s < 4; s++) {
                    uint32_t A[4];
                    ldsm4t(A, wb + s * 512);
#pragma unroll
                    for (int dd = 0; dd < 8; dd++)
                        if (8 + 2 * s + dd < 16) mma16816(y[8 + 2 * s + dd], A[0], A[1], A[2], A[3], B[dd][0], B[dd][1]);
                }
            }
            const uint32_t idw = (g == 2 * q) ? k1024 : ((g == 2 * q + 1) ? (k1024 << 16) : 0u);
#pragma unroll
            for (int s = 0; s < 4; s++) {
                uint32_t A[4];
                ldsm4t(A, spare + 2048 + loff + s * 512);
                mma16816(y[8 + 2 * s], A[0], A[1], A[2], A[3], idw, 0u);
                mma16816(y[9 + 2 * s], A[0], A[1], A[2], A[3], 0u, idw);
            }
        }
        __syncwarp();
        if (warp == 8) STAMP(19);
#pragma unroll
        for (int nt = 0; nt < 16; nt++)
#pragma unroll
            for (int b = 0; b < 2; b++) sts32(buf + ((8 * nt + 2 * q + b) * 8 + g) * 4, pack2(y[nt][b], y[nt][2 + b]));
        bar_named(2, 128);
        uint4* yp = scr->y + bi * 1024 + st;
#pragma unroll
        for (int v = 0; v < 8; v++) {
            const uint32_t a = sb + OFF_BUF + (st + 128 * v) * 4;
            const uint32_t w0 = lds32(a), w1 = lds32(a + BUF_STRIDE), w2 = lds32(a + 2 * BUF_STRIDE), w3 = lds32(a + 3 * BUF_STRIDE);
            st_rlx128(yp + v * 128, tag4(__byte_perm(w0, w1, 0x5410), __byte_perm(w0, w1, 0x7632), __byte_perm(w2, w3, 0x5410), __byte_perm(w2, w3, 0x7632), tag));
        }
        if (st < 8) st_rlx32(scr->yflag + bi * 8 + st, tag);
        if (warp == 8) STAMP(20);
    } else {
        asm volatile("setmaxnreg.dec.sync.aligned.u32 64;");
        {
            mbar_wait(bar + 8 * (BAR_FULL + xkb), 0);
#pragma unroll 1
            for (int hf = 0; hf < 2; hf++) {
                const int r = w4 * 32 + hf * 16 + (lane & 15);
                uint32_t* xt = (uint32_t*)scr->xt + ((xkb + rot) * 16 + (g >> 2)) * 4096 + (bi_i * 16 + w4 * 4 + hf * 2) * 16 + (g & 3) * 4 + q;
#pragma unroll
                for (int cb = 0; cb < 8; cb += 2) {
                    uint32_t v[4];
                    ldsm4t(v, sb + xkb * SLOT + r * 128 + (((cb + (lane >> 4)) ^ (r & 7)) << 4));
                    xt[cb * 8192] = v[0]; xt[cb * 8192 + 16] = v[1]; xt[cb * 8192 + 8192] = v[2]; xt[cb * 8192 + 8192 + 16] = v[3];
                }
            }
            __syncwarp();
            if (lane == 0) mbar_arrive(bar + 8 * BAR_XT);
            if (warp == 12) {
                mbar_wait(bar + 8 * BAR_XT, 0);
                if (lane == 0) asm volatile("red.release.gpu.global.add.u32 [%0],8;" ::"l"(scr->xcnt + (xkb + rot) * 32) : "memory");
                __syncwarp();
            }
        }
        const int qq = (bi_i & 2) + ((lane >> 1) & 1);
        uint2* kvf_h = (uint2*)(scr->kvf + (bi_j * 4 + (bi_i >> 2)) * 68);
        {
            const uint32_t old = tag ^ 1u;
            const uint4 z4 = make_uint4(old, 0, old, 0);
#pragma unroll
            for (int v = 0; v < 5; v++) if (v < 4 || st < 32) st_rlx128(scr->kvp + bi * 544 + v * 128 + st, z4);
            if (st < 16) st_rlx128(scr->o + ((bi_i * 8 + (st >> 1)) * 32 + bi_j * 4 + 3) * 32 + 30 + (st & 1), z4);
            if (lane < 8) st_rlx64(kvf_h + ((bi_i & 3) * 8 + w4 * 2 + (lane & 1)) * 4 + (lane >> 1), old, 0);
            if (st < 4 && !(bi_i & 1)) st_rlx64(kvf_h + (64 + qq) * 2 + (lane & 1), old, 0);
            __syncwarp();
            if (lane == 0) mbar_arrive(bar + 8 * BAR_PREP);
        }
        {
            int n = 0;
#pragma unroll 1
            while (__any_sync(~0u, (int)(ld_acq(scr->xcnt + bi_j * 32) - (epoch1 << 7)) < 0)) { __nanosleep(100); if (++n > SPIN_LIMIT) break; }
            if (warp == 12) STAMP(15);
            uint4 ur[8];
#pragma unroll
            for (int v = 0; v < 8; v++) ur[v] = __ldcg(scr->xt + bi * 1024 + st + 128 * v);
            mbar_wait(bar + 8 * BAR_SP, 0);
            if (lane < 16) sts128(ub - 256 + lane * 16, 0, 0, 0, 0);
#pragma unroll
            for (int v = 0; v < 8; v++) {
                const int ci = (st >> 2) + 32 * v;
                sts128(sb + OFF_U + (st & 3) * U_STRIDE + 256 + ((ci ^ ((ci >> 3) & 1)) << 4), ur[v].x, ur[v].y, ur[v].z, ur[v].w);
            }
            __syncwarp();
            if (lane == 0) mbar_arrive(bar + 8 * BAR_UR);
            mbar_wait(bar + 8 * BAR_UR, 0);
            if (warp == 12) STAMP(16);
        }
        if (lane < 2) sts128(buf + lane * W3_OFF, 0, 0, 0, 0);
#pragma unroll 1
        for (int rho = 5; rho >= 0; rho--) {
            if (rho == 3) mbar_wait(bar + 8 * BAR_SP2, 0);
            const int ci = lane + 32 * rho;
            uint4 e4[4];
#pragma unroll
            for (int v = 0; v < 4; v++) { const int cc = ci - 3 + v; e4[v] = lds128(ub + ((cc ^ ((cc >> 3) & 1)) << 4)); }
            float S[29];
            const uint32_t* ew = (const uint32_t*)e4;
            S[3] = 0.f;
#pragma unroll
            for (int k = 4; k <= 28; k++) S[k] = S[k - 1] + ((k & 1) ? bf_hi(ew[k >> 1]) : bf_lo(ew[k >> 1]));
            auto win = [&](int lo, int hi, uint32_t a) {
                sts128(a, pack2(S[hi] - S[lo - 1], S[hi + 1] - S[lo]), pack2(S[hi + 2] - S[lo + 1], S[hi + 3] - S[lo + 2]),
                       pack2(S[hi + 4] - S[lo + 3], S[hi + 5] - S[lo + 4]), pack2(S[hi + 6] - S[lo + 5], S[hi + 7] - S[lo + 6]));
            };
            win(14, 18, buf + W5_OFF + 16 + ci * 16); win(19, 21, buf + W3_OFF + 16 + ci * 16);
            if (rho < 4) {
                const uint32_t sw = (ci ^ ((ci >> 3) & 1)) << 4;
                win(4, 12, buf + W9_OFF + sw); win(13, 19, spare + sw); win(20, 21, spare + 2048 + sw);
            }
        }
        __syncwarp();
        if (lane == 0) mbar_arrive(bar + 8 * BAR_WR);
        if (warp == 12) STAMP(24);
        mbar_wait(bar + 8 * BAR_PUB, 0);
        if (warp == 12) STAMP(12);
#pragma unroll 1
        for (int zw = 0; zw < ((st < 32 && !(bi_i & 1)) ? 2 : 1); zw++) {
            const int kvf_n = zw ? 4 : 8;
            uint2* kvf_dst = kvf_h + (zw ? (64 + qq) * 2 + (lane & 1) : ((bi_i & 3) * 8 + w4 * 2 + (lane & 1)) * 4 + (lane >> 1));
            const uint4* src = scr->kvp + bi_j * (16 * 544) + (bi_i >> 2) * 136 +
                               (zw ? (lane >> 2) * (2 * 544) + 128 + (lane & 1) * 4 + qq
                                   : (lane >> 3) * (4 * 544) + ((lane >> 1) & 3) * 32 + (bi_i & 3) * 8 + w4 * 2 + (lane & 1));
            const int s23 = zw ? 0 : 2 * 544;
            uint4 v[4];
            int n = 0;
#pragma unroll 1
            while (true) {
                v[0] = ld_rlx128(src); v[1] = ld_rlx128(src + 544); v[2] = ld_rlx128(src + s23); v[3] = ld_rlx128(src + s23 + 544);
                if (!__any_sync(~0u, (bad4(v[0], tag) | bad4(v[1], tag) | bad4(v[2], tag) | bad4(v[3], tag)) & 1)) break;
                if (++n > SPIN_LIMIT) break;
            }
            float f[4];
            f[0] = __uint_as_float(v[2].x) + __uint_as_float(v[3].x); f[1] = __uint_as_float(v[2].y) + __uint_as_float(v[3].y);
            f[2] = __uint_as_float(v[2].z) + __uint_as_float(v[3].z); f[3] = __uint_as_float(v[2].w) + __uint_as_float(v[3].w);
            float e0 = __uint_as_float(v[0].x) + __uint_as_float(v[1].x), e1 = __uint_as_float(v[0].y) + __uint_as_float(v[1].y);
            float e2 = __uint_as_float(v[0].z) + __uint_as_float(v[1].z), e3 = __uint_as_float(v[0].w) + __uint_as_float(v[1].w);
            if (zw) {
                e0 = __shfl_xor_sync(~0u, f[0], 4); e1 = __shfl_xor_sync(~0u, f[1], 4);
                e2 = __shfl_xor_sync(~0u, f[2], 4); e3 = __shfl_xor_sync(~0u, f[3], 4);
            }
            f[0] += e0; f[1] += e1; f[2] += e2; f[3] += e3;
#pragma unroll
            for (int o = 8; o <= 16; o <<= 1)
#pragma unroll
                for (int r = 0; r < 4; r++) f[r] += __shfl_xor_sync(~0u, f[r], o);
            if (lane < kvf_n) st_rlx64(kvf_dst, tagw(pack2(f[0], f[1]), tag), pack2(f[2], f[3]));
        }
        if (warp == 12) STAMP(13);
        if (st == 32) {
            mbar_expect(bar + 8 * BAR_WO2, 65536);
            tma2d(sb + OFF_P, &mwo, (bi_j & 3) * 128, 256, bar + 8 * BAR_WO2);
            tma2d(sb + OFF_V, &mwo, (bi_j & 3) * 128 + 64, 256, bar + 8 * BAR_WO2);
        }
        __syncwarp();
        {
            const uint4* kp = scr->kvf + bi_j * 272 + st;
            uint4 v0, v1, v2;
            int n = 0;
#pragma unroll 1
            while (true) {
                v0 = ld_rlx128(kp); v1 = ld_rlx128(kp + 128); v2 = ld_rlx128(kp + (st < 16 ? 256 : 0));
                if (!__any_sync(~0u, (bad4(v0, tag) | bad4(v1, tag) | bad4(v2, tag)) & 1)) break;
                if (++n > SPIN_LIMIT) break;
            }
            sts128(sb + OFF_KVF + st * 16, v0.x, v0.y, v0.z, v0.w);
            sts128(sb + OFF_KVF + 2048 + st * 16, v1.x, v1.y, v1.z, v1.w);
            if (st < 16) sts128(sb + OFF_KVF + 4096 + st * 16, v2.x, v2.y, v2.z, v2.w);
            __syncwarp();
            if (lane == 0) mbar_arrive(bar + 8 * BAR_KVF);
        }
        if (warp == 12) STAMP(25);
    }
    __syncwarp();
    if (lane == 0) {
        unsigned old;
        asm volatile("atom.acq_rel.cta.shared.add.u32 %0,[%1],1;" : "=r"(old) : "r"(bar + OFF_CNT) : "memory");
        if (old == 15) {
            atomicAdd(scr->done, 1u);
        }
    }
}

typedef CUresult (*EncFn)(CUtensorMap*, CUtensorMapDataType, cuuint32_t, void*, const cuuint64_t*, const cuuint64_t*, const cuuint32_t*,
                          const cuuint32_t*, CUtensorMapInterleave, CUtensorMapSwizzle, CUtensorMapL2promotion, CUtensorMapFloatOOBfill);

extern "C" void kernel_launch(void* const* d_in, const int* in_sizes, int n_in, void* d_out, int out_size) {
    static EncFn enc = nullptr;
    static Scratch* scr = nullptr;
    if (!enc) {
        cudaGetSymbolAddress((void**)&scr, g_scr);
        cudaDriverEntryPointQueryResult qr;
        cudaGetDriverEntryPoint("cuTensorMapEncodeTiled", (void**)&enc, cudaEnableDefault, &qr);
        cudaFuncSetAttribute(fused_kernel, cudaFuncAttributeMaxDynamicSharedMemorySize, SMEM_BYTES);
    }
    CUtensorMap mx, mw, mwo;
    const cuuint32_t es[3] = {1, 1, 1};
    {
        cuuint64_t d[2] = {512, 2048}, s[1] = {1024}; cuuint32_t b[2] = {64, 128};
        enc(&mx, CU_TENSOR_MAP_DATA_TYPE_BFLOAT16, 2, d_in[0], d, s, b, es, CU_TENSOR_MAP_INTERLEAVE_NONE, CU_TENSOR_MAP_SWIZZLE_128B,
            CU_TENSOR_MAP_L2_PROMOTION_L2_128B, CU_TENSOR_MAP_FLOAT_OOB_FILL_NONE);
    }
    {
        cuuint64_t d[3] = {512, 512, 3}, s[2] = {3072, 1024}; cuuint32_t b[3] = {64, 64, 3};
        enc(&mw, CU_TENSOR_MAP_DATA_TYPE_BFLOAT16, 3, d_in[1], d, s, b, es, CU_TENSOR_MAP_INTERLEAVE_NONE, CU_TENSOR_MAP_SWIZZLE_128B,
            CU_TENSOR_MAP_L2_PROMOTION_L2_128B, CU_TENSOR_MAP_FLOAT_OOB_FILL_NONE);
    }
    {
        cuuint64_t d[2] = {512, 512}, s[1] = {1024}; cuuint32_t b[2] = {64, 256};
        enc(&mwo, CU_TENSOR_MAP_DATA_TYPE_BFLOAT16, 2, d_in[3], d, s, b, es, CU_TENSOR_MAP_INTERLEAVE_NONE, CU_TENSOR_MAP_SWIZZLE_128B,
            CU_TENSOR_MAP_L2_PROMOTION_L2_128B, CU_TENSOR_MAP_FLOAT_OOB_FILL_NONE);
    }
    fused_kernel<<<128, 512, SMEM_BYTES, cudaStreamPerThread>>>(
        scr, (const bf16*)d_in[5], (const bf16*)d_in[6], (const bf16*)d_in[7], (const bf16*)d_in[8], (const bf16*)d_in[9],
        (const bf16*)d_in[10], (const bf16*)d_in[2], (const bf16*)d_in[11], (bf16*)d_out, mx, mw, mwo);
}
```

```cpp
#include <cuda_runtime.h>
#include <cuda.h>
#include <cuda_bf16.h>
#include <stdint.h>

typedef __nv_bfloat16 bf16;

struct Scratch {
    uint4 xt[128 * 1024];
    uint4 o[16 * 8 * 32 * 32];
    uint4 y[128 * 1024];
    uint4 kvp[8 * 16 * 544];
    uint4 kvf[8 * 4 * 68];
    unsigned g[1024 * 8];
    unsigned yflag[128 * 8];
    unsigned xcnt[8 * 32];
    unsigned done[32];
};
__device__ Scratch g_scr;
#define STAMP(n)

constexpr int SLOT = 40960;
constexpr int OFF_SP0 = 32768, OFF_SP1 = SLOT + 32768;
constexpr int OFF_P = 2 * SLOT, OFF_V = OFF_P + 32768;
constexpr int OFF_KVF = OFF_V + 32768;
constexpr int KT_BYTES = 3264, KW_D = 16, KW_2 = 560, KW_3 = 656;
constexpr int OFF_U = 4 * SLOT, U_STRIDE = 4096 + 256 + 32;
constexpr int OFF_BUF = OFF_U + 4 * U_STRIDE, BUF_STRIDE = 8320;
constexpr int OFF_K = OFF_BUF + 4 * BUF_STRIDE;
constexpr int OFF_WPHI = OFF_K + 4 * KT_BYTES;
constexpr int OFF_GW = OFF_WPHI + 2048;
constexpr int OFF_BAR = OFF_GW + 1024;
constexpr int SMEM_BYTES = OFF_BAR + 256 + 256;
static_assert(SMEM_BYTES <= 232448 && OFF_BUF % 128 == 0, "smem");
constexpr int W5_OFF = 0, W3_OFF = 3088, W9_OFF = 6176;
constexpr int BAR_FULL = 0, BAR_EMPTY = 4, BAR_WPHI = 8, BAR_WO = 9, BAR_WO2 = 10, BAR_XT = 11, BAR_DONE = 12, BAR_KG = 13, BAR_SP = 14,
              BAR_PUB = 15, BAR_KVF = 16, BAR_UR = 17, BAR_WR = 18, BAR_PREP = 19, BAR_SP2 = 20, OFF_CNT = 192;
constexpr int SPIN_LIMIT = 1 << 17;

__device__ __forceinline__ uint32_t s2u(const void* p) { return (uint32_t)__cvta_generic_to_shared(p); }
__device__ __forceinline__ void mbar_init(uint32_t b, int c) { asm volatile("mbarrier.init.shared::cta.b64 [%0],%1;" ::"r"(b), "r"(c) : "memory"); }
__device__ __forceinline__ void mbar_expect(uint32_t b, int bytes) { asm volatile("mbarrier.arrive.expect_tx.shared::cta.b64 _,[%0],%1;" ::"r"(b), "r"(bytes) : "memory"); }
__device__ __forceinline__ void mbar_arrive(uint32_t b) { asm volatile("mbarrier.arrive.shared::cta.b64 _,[%0];" ::"r"(b) : "memory"); }
__device__ __forceinline__ void mbar_wait(uint32_t b, int ph) {
    asm volatile("{\n.reg .pred p;\n.reg .u32 n;\nmov.u32 n,0;\nLW_%=:\nmbarrier.try_wait.parity.shared::cta.b64 p,[%0],%1;\n@p bra LD_%=;\n"
                 "add.u32 n,n,1;\nsetp.lt.u32 p,n,131072;\n@p bra LW_%=;\nLD_%=:\n}" ::"r"(b), "r"(ph) : "memory");
}
__device__ __forceinline__ void tma2d(uint32_t dst, const CUtensorMap* m, int c0, int c1, uint32_t bar) {
    asm volatile("cp.async.bulk.tensor.2d.shared::cluster.global.mbarrier::complete_tx::bytes [%0],[%1,{%3,%4}],[%2];" ::"r"(dst), "l"(m), "r"(bar), "r"(c0), "r"(c1) : "memory");
}
__device__ __forceinline__ void tma3d(uint32_t dst, const CUtensorMap* m, int c0, int c1, int c2, uint32_t bar) {
    asm volatile("cp.async.bulk.tensor.3d.shared::cluster.global.mbarrier::complete_tx::bytes [%0],[%1,{%3,%4,%5}],[%2];" ::"r"(dst), "l"(m), "r"(bar), "r"(c0), "r"(c1), "r"(c2) : "memory");
}
__device__ __forceinline__ void bulk_g2s(uint32_t dst, const void* src, int bytes, uint32_t bar) {
    asm volatile("cp.async.bulk.shared::cluster.global.mbarrier::complete_tx::bytes [%0],[%1],%2,[%3];" ::"r"(dst), "l"(src), "r"(bytes), "r"(bar) : "memory");
}
__device__ __forceinline__ uint64_t mkdesc(uint32_t addr, uint32_t lbo, uint32_t sbo) {
    return (uint64_t)((addr & 0x3FFFF) >> 4) | ((uint64_t)(lbo >> 4) << 16) | ((uint64_t)(sbo >> 4) << 32) | ((uint64_t)1 << 62);
}
__device__ __forceinline__ void wg_fence() { asm volatile("wgmma.fence.sync.aligned;" ::: "memory"); }
__device__ __forceinline__ void wg_commit() { asm volatile("wgmma.commit_group.sync.aligned;" ::: "memory"); }
template <int N> __device__ __forceinline__ void wg_wait() { asm volatile("wgmma.wait_group.sync.aligned %0;" ::"n"(N) : "memory"); }
template <int N> __device__ __forceinline__ void fence_regs(float* d) {
#pragma unroll
    for (int i = 0; i < N; i++) asm volatile("" : "+f"(d[i])::"memory");
}
#define R8(d, o) "+f"(d[o]), "+f"(d[o + 1]), "+f"(d[o + 2]), "+f"(d[o + 3]), "+f"(d[o + 4]), "+f"(d[o + 5]), "+f"(d[o + 6]), "+f"(d[o + 7])
__device__ __forceinline__ void wgmma192(float* d, uint64_t da, uint64_t db) {
    asm volatile("wgmma.mma_async.sync.aligned.m64n192k16.f32.bf16.bf16 {"
                 "%0,%1,%2,%3,%4,%5,%6,%7,%8,%9,%10,%11,%12,%13,%14,%15,%16,%17,%18,%19,%20,%21,%22,%23,%24,%25,%26,%27,%28,%29,%30,%31,"
                 "%32,%33,%34,%35,%36,%37,%38,%39,%40,%41,%42,%43,%44,%45,%46,%47,%48,%49,%50,%51,%52,%53,%54,%55,%56,%57,%58,%59,%60,%61,%62,%63,"
                 "%64,%65,%66,%67,%68,%69,%70,%71,%72,%73,%74,%75,%76,%77,%78,%79,%80,%81,%82,%83,%84,%85,%86,%87,%88,%89,%90,%91,%92,%93,%94,%95},"
                 "%96,%97,1,1,1,0,1;"
                 : R8(d, 0), R8(d, 8), R8(d, 16), R8(d, 24), R8(d, 32), R8(d, 40), R8(d, 48), R8(d, 56), R8(d, 64), R8(d, 72), R8(d, 80), R8(d, 88)
                 : "l"(da), "l"(db));
}
__device__ __forceinline__ void wgmma64_tt(float* d, uint64_t da, uint64_t db, int sc) {
    asm volatile("{.reg .pred p; setp.ne.b32 p,%34,0; wgmma.mma_async.sync.aligned.m64n64k16.f32.bf16.bf16 {"
                 "%0,%1,%2,%3,%4,%5,%6,%7,%8,%9,%10,%11,%12,%13,%14,%15,%16,%17,%18,%19,%20,%21,%22,%23,%24,%25,%26,%27,%28,%29,%30,%31},"
                 "%32,%33,p,1,1,1,1;}"
                 : R8(d, 0), R8(d, 8), R8(d, 16), R8(d, 24)
                 : "l"(da), "l"(db), "r"(sc));
}
__device__ __forceinline__ void wgmma128_rs(float* d, const uint4& a, uint64_t db, int sc) {
    asm volatile("{.reg .pred p; setp.ne.b32 p,%69,0; wgmma.mma_async.sync.aligned.m64n128k16.f32.bf16.bf16 {"
                 "%0,%1,%2,%3,%4,%5,%6,%7,%8,%9,%10,%11,%12,%13,%14,%15,%16,%17,%18,%19,%20,%21,%22,%23,%24,%25,%26,%27,%28,%29,%30,%31,"
                 "%32,%33,%34,%35,%36,%37,%38,%39,%40,%41,%42,%43,%44,%45,%46,%47,%48,%49,%50,%51,%52,%53,%54,%55,%56,%57,%58,%59,%60,%61,%62,%63},"
                 "{%64,%65,%66,%67},%68,p,1,1,1;}"
                 : R8(d, 0), R8(d, 8), R8(d, 16), R8(d, 24), R8(d, 32), R8(d, 40), R8(d, 48), R8(d, 56)
                 : "r"(a.x), "r"(a.y), "r"(a.z), "r"(a.w), "l"(db), "r"(sc));
}
__device__ __forceinline__ void mma16816(float* c, uint32_t a0, uint32_t a1, uint32_t a2, uint32_t a3, uint32_t b0, uint32_t b1) {
    asm("mma.sync.aligned.m16n8k16.row.col.f32.bf16.bf16.f32 {%0,%1,%2,%3},{%4,%5,%6,%7},{%8,%9},{%0,%1,%2,%3};"
        : "+f"(c[0]), "+f"(c[1]), "+f"(c[2]), "+f"(c[3]) : "r"(a0), "r"(a1), "r"(a2), "r"(a3), "r"(b0), "r"(b1));
}
__device__ __forceinline__ void ldsm4(uint32_t* r, uint32_t a) {
    asm volatile("ldmatrix.sync.aligned.m8n8.x4.shared.b16 {%0,%1,%2,%3},[%4];" : "=r"(r[0]), "=r"(r[1]), "=r"(r[2]), "=r"(r[3]) : "r"(a) : "memory");
}
__device__ __forceinline__ void ldsm4t(uint32_t* r, uint32_t a) {
    asm volatile("ldmatrix.sync.aligned.m8n8.x4.trans.shared.b16 {%0,%1,%2,%3},[%4];" : "=r"(r[0]), "=r"(r[1]), "=r"(r[2]), "=r"(r[3]) : "r"(a) : "memory");
}
__device__ __forceinline__ void stsm4(uint32_t a, uint32_t r0, uint32_t r1, uint32_t r2, uint32_t r3) {
    asm volatile("stmatrix.sync.aligned.m8n8.x4.shared.b16 [%0],{%1,%2,%3,%4};" ::"r"(a), "r"(r0), "r"(r1), "r"(r2), "r"(r3) : "memory");
}
__device__ __forceinline__ uint32_t lds32(uint32_t a) { uint32_t v; asm volatile("ld.shared.b32 %0,[%1];" : "=r"(v) : "r"(a) : "memory"); return v; }
__device__ __forceinline__ uint4 lds128(uint32_t a) { uint4 v; asm volatile("ld.shared.v4.b32 {%0,%1,%2,%3},[%4];" : "=r"(v.x), "=r"(v.y), "=r"(v.z), "=r"(v.w) : "r"(a) : "memory"); return v; }
__device__ __forceinline__ void sts16(uint32_t a, uint32_t v) { asm volatile("st.shared.b16 [%0],%1;" ::"r"(a), "h"((unsigned short)v) : "memory"); }
__device__ __forceinline__ void sts32(uint32_t a, uint32_t v) { asm volatile("st.shared.b32 [%0],%1;" ::"r"(a), "r"(v) : "memory"); }
__device__ __forceinline__ void sts64(uint32_t a, uint32_t x, uint32_t y) { asm volatile("st.shared.v2.b32 [%0],{%1,%2};" ::"r"(a), "r"(x), "r"(y) : "memory"); }
__device__ __forceinline__ void sts128(uint32_t a, uint32_t x, uint32_t y, uint32_t z, uint32_t w) { asm volatile("st.shared.v4.b32 [%0],{%1,%2,%3,%4};" ::"r"(a), "r"(x), "r"(y), "r"(z), "r"(w) : "memory"); }
__device__ __forceinline__ uint32_t pack2(float lo, float hi) { uint32_t d; asm("cvt.rn.bf16x2.f32 %0,%1,%2;" : "=r"(d) : "f"(hi), "f"(lo)); return d; }
__device__ __forceinline__ float bf_lo(uint32_t v) { return __uint_as_float(v << 16); }
__device__ __forceinline__ float bf_hi(uint32_t v) { return __uint_as_float(v & 0xffff0000u); }
__device__ __forceinline__ float bf_round(float v) { return bf_lo(pack2(v, 0.f)); }
__device__ __forceinline__ uint32_t hmax2(uint32_t a, uint32_t b) { uint32_t d; asm("max.bf16x2 %0,%1,%2;" : "=r"(d) : "r"(a), "r"(b)); return d; }
__device__ __forceinline__ uint32_t hmin2(uint32_t a, uint32_t b) { uint32_t d; asm("min.bf16x2 %0,%1,%2;" : "=r"(d) : "r"(a), "r"(b)); return d; }
__device__ __forceinline__ uint32_t hmul2(uint32_t a, uint32_t b) { uint32_t d; asm("mul.rn.bf16x2 %0,%1,%2;" : "=r"(d) : "r"(a), "r"(b)); return d; }
__device__ __forceinline__ float ex2(float x) { float y; asm("ex2.approx.ftz.f32 %0,%1;" : "=f"(y) : "f"(x)); return y; }
__device__ __forceinline__ float rcp(float x) { float y; asm("rcp.approx.ftz.f32 %0,%1;" : "=f"(y) : "f"(x)); return y; }
__device__ __forceinline__ uint32_t ld_nc(const uint32_t* p) { uint32_t v; asm volatile("ld.global.nc.b32 %0,[%1];" : "=r"(v) : "l"(p)); return v; }
__device__ __forceinline__ uint2 ld_nc64(const uint2* p) { uint2 v; asm volatile("ld.global.nc.v2.b32 {%0,%1},[%2];" : "=r"(v.x), "=r"(v.y) : "l"(p)); return v; }
__device__ __forceinline__ unsigned ld_acq(const unsigned* p) { unsigned v; asm volatile("ld.acquire.gpu.global.u32 %0,[%1];" : "=r"(v) : "l"(p) : "memory"); return v; }
__device__ __forceinline__ unsigned ld_rlx(const unsigned* p) { unsigned v; asm volatile("ld.relaxed.gpu.global.u32 %0,[%1];" : "=r"(v) : "l"(p) : "memory"); return v; }
__device__ __forceinline__ uint2 ld_rlx64(const void* p) { uint2 v; asm volatile("{.reg .b64 t; ld.relaxed.gpu.global.b64 t,[%2]; mov.b64 {%0,%1},t;}" : "=r"(v.x), "=r"(v.y) : "l"(p) : "memory"); return v; }
__device__ __forceinline__ uint4 ld_rlx128(const void* p) {
    uint4 v;
    asm volatile("{.reg .b64 t,u; ld.relaxed.gpu.global.v2.b64 {t,u},[%4]; mov.b64 {%0,%1},t; mov.b64 {%2,%3},u;}" : "=r"(v.x), "=r"(v.y), "=r"(v.z), "=r"(v.w) : "l"(p) : "memory");
    return v;
}
__device__ __forceinline__ void st_rlx32(void* p, uint32_t x) { asm volatile("st.relaxed.gpu.global.u32 [%0],%1;" ::"l"(p), "r"(x) : "memory"); }
__device__ __forceinline__ void st_rlx64(void* p, uint32_t x, uint32_t y) { asm volatile("{.reg .b64 t; mov.b64 t,{%1,%2}; st.relaxed.gpu.global.b64 [%0],t;}" ::"l"(p), "r"(x), "r"(y) : "memory"); }
__device__ __forceinline__ void st_rlx128(void* p, uint4 v) {
    asm volatile("{.reg .b64 t,u; mov.b64 t,{%1,%2}; mov.b64 u,{%3,%4}; st.relaxed.gpu.global.v2.b64 [%0],{t,u};}" ::"l"(p), "r"(v.x), "r"(v.y), "r"(v.z), "r"(v.w) : "memory");
}
__device__ __forceinline__ uint32_t tagw(uint32_t w, uint32_t tag) { return (w & ~1u) | tag; }
__device__ __forceinline__ uint4 tag4(uint32_t x, uint32_t y, uint32_t z, uint32_t w, uint32_t tag) { return make_uint4(tagw(x, tag), y, tagw(z, tag), w); }
__device__ __forceinline__ uint32_t bad4(const uint4& v, uint32_t tag) { return (v.x ^ tag) | (v.z ^ tag); }
__device__ __forceinline__ void bar_named(int id, int n) { asm volatile("bar.sync %0,%1;" ::"r"(id), "r"(n) : "memory"); }

struct cf { float re, im; };
__device__ __forceinline__ cf cmul(cf a, cf b) { cf r; r.re = a.re * b.re - a.im * b.im; r.im = a.re * b.im + a.im * b.re; return r; }
__device__ __forceinline__ cf cexp_p(float arl, float ait, float p) {
    float mag = ex2(arl * p);
    float t = ait * p;
    t = (t - rintf(t)) * 6.283185307179586f;
    cf r; r.re = mag * __cosf(t); r.im = mag * __sinf(t);
    return r;
}

__device__ __forceinline__ void hedgehog2(const uint32_t* a, uint32_t wphi_addr, uint32_t (*out)[8]) {
    float p[2][2][4], mx[2][2];
#pragma unroll
    for (int h = 0; h < 2; h++) {
        uint32_t b[4];
        ldsm4t(b, wphi_addr + h * 512);
        float c0[4] = {0.f, 0.f, 0.f, 0.f}, c1[4] = {0.f, 0.f, 0.f, 0.f};
        mma16816(c0, a[4 * h], a[4 * h + 1], a[4 * h + 2], a[4 * h + 3], b[0], b[1]);
        mma16816(c1, a[4 * h], a[4 * h + 1], a[4 * h + 2], a[4 * h + 3], b[2], b[3]);
#pragma unroll
        for (int k = 0; k < 2; k++) {
            p[h][k][0] = c0[2 * k]; p[h][k][1] = c0[2 * k + 1]; p[h][k][2] = c1[2 * k]; p[h][k][3] = c1[2 * k + 1];
            mx[h][k] = fmaxf(fmaxf(p[h][k][0], p[h][k][1]), fmaxf(p[h][k][2], p[h][k][3]));
        }
    }
#pragma unroll
    for (int o = 1; o <= 2; o <<= 1)
#pragma unroll
        for (int h = 0; h < 2; h++)
#pragma unroll
            for (int k = 0; k < 2; k++) mx[h][k] = fmaxf(mx[h][k], __shfl_xor_sync(~0u, mx[h][k], o));
    const float L = 1.4426950408889634f;
    float pmin = 1.f;
#pragma unroll
    for (int h = 0; h < 2; h++)
#pragma unroll
        for (int k = 0; k < 2; k++) {
            const float m = -mx[h][k] * L;
            const float e0 = ex2(fmaf(p[h][k][0], L, m)), e1 = ex2(fmaf(p[h][k][1], L, m)), e2 = ex2(fmaf(p[h][k][2], L, m)), e3 = ex2(fmaf(p[h][k][3], L, m));
            const float p01 = e0 * e1, p23 = e2 * e3, pp = p01 * p23, r = rcp(pp), r01 = r * p23, r23 = r * p01;
            pmin = fminf(pmin, pp);
            out[h][k] = pack2(e0, e1); out[h][k + 2] = pack2(e2, e3);
            out[h][4 + k] = pack2(r01 * e1, r01 * e0); out[h][4 + k + 2] = pack2(r23 * e3, r23 * e2);
        }
    if (__builtin_expect(__any_sync(~0u, !(pmin > 1e-18f)), 0)) {
#pragma unroll
        for (int h = 0; h < 2; h++)
#pragma unroll
            for (int k = 0; k < 2; k++) {
                float m = fminf(fminf(p[h][k][0], p[h][k][1]), fminf(p[h][k][2], p[h][k][3]));
                m = fminf(m, __shfl_xor_sync(~0u, m, 1));
                m = fminf(m, __shfl_xor_sync(~0u, m, 2)) * L;
                out[h][4 + k] = pack2(ex2(fmaf(p[h][k][0], -L, m)), ex2(fmaf(p[h][k][1], -L, m)));
                out[h][4 + k + 2] = pack2(ex2(fmaf(p[h][k][2], -L, m)), ex2(fmaf(p[h][k][3], -L, m)));
            }
    }
}

__global__ void __launch_bounds__(512, 1)
fused_kernel(Scratch* __restrict__ scr, const bf16* __restrict__ logA, const bf16* __restrict__ Aim, const bf16* __restrict__ Cre,
             const bf16* __restrict__ Cim, const bf16* __restrict__ logdt, const bf16* __restrict__ Dskip, const bf16* __restrict__ wphi,
             const bf16* __restrict__ gatew, bf16* __restrict__ out,
             const __grid_constant__ CUtensorMap mx, const __grid_constant__ CUtensorMap mw, const __grid_constant__ CUtensorMap mwo) {
    extern __shared__ __align__(1024) uint8_t smem[];
    const uint32_t sb = s2u(smem);
    const int tid = threadIdx.x, warp = __shfl_sync(~0u, tid >> 5, 0), lane = tid & 31;
    const int g = lane >> 2, q = lane & 3, w4 = warp & 3;
    const int bi = blockIdx.x, bi_i = bi & 15, bi_j = bi >> 4;
    const uint32_t bar = sb + OFF_BAR;
    const int rot = (bi_j & 3) * 2, xkb = bi_j >> 2;
    auto load_stage = [&](int kb) {
        const uint32_t b = bar + 8 * (BAR_FULL + (kb & 3)), d = sb + (kb & 3) * SLOT;
        const int kc = ((kb + rot) & 7) * 64;
        mbar_expect(b, SLOT);
        tma2d(d, &mx, kc, bi_i * 128, b);
        tma3d(d + 16384, &mw, bi_j * 64, kc, 0, b);
    };

    const int ch = bi * 4 + w4;
    uint32_t pla = 0, pai = 0, pcr = 0, pci = 0, pdt = 0, pds = 0;
    if (warp >= 8) {
        const int pidx = ch * 64 + lane * 2 + (warp >= 12);
        pla = ld_nc((const uint32_t*)logA + pidx); pai = ld_nc((const uint32_t*)Aim + pidx);
        pcr = ld_nc((const uint32_t*)Cre + pidx); pci = ld_nc((const uint32_t*)Cim + pidx);
        pdt = ld_nc((const uint32_t*)logdt + (ch >> 1)); pds = ld_nc((const uint32_t*)Dskip + (ch >> 1));
    }
    unsigned done0 = ld_rlx(scr->done);
    if (tid == 0) {
        for (int s = 0; s < 4; s++) mbar_init(bar + 8 * (BAR_FULL + s), 1);
        asm volatile("fence.mbarrier_init.release.cluster;" ::: "memory");
        load_stage(0); load_stage(1); load_stage(2);
        STAMP(11);
    } else if (tid == 32) {
        if (sb & 1023) __trap();
        sts32(bar + OFF_CNT, 0);
        for (int s = 0; s < 4; s++) mbar_init(bar + 8 * (BAR_EMPTY + s), 8);
        mbar_init(bar + 8 * BAR_WPHI, 1); mbar_init(bar + 8 * BAR_WO, 2); mbar_init(bar + 8 * BAR_WO2, 1); mbar_init(bar + 8 * BAR_XT, 4);
        mbar_init(bar + 8 * BAR_DONE, 9); mbar_init(bar + 8 * BAR_KG, 4); mbar_init(bar + 8 * BAR_SP, 4); mbar_init(bar + 8 * BAR_PUB, 8);
        mbar_init(bar + 8 * BAR_KVF, 4); mbar_init(bar + 8 * BAR_UR, 4); mbar_init(bar + 8 * BAR_WR, 4); mbar_init(bar + 8 * BAR_PREP, 4);
        asm volatile("fence.mbarrier_init.release.cluster;" ::: "memory");
        mbar_expect(bar + 8 * BAR_WPHI, 3072);
        bulk_g2s(sb + OFF_GW, gatew, 1024, bar + 8 * BAR_WPHI);
        bulk_g2s(sb + OFF_WPHI, wphi + bi_j * 1024, 2048, bar + 8 * BAR_WPHI);
    } else if (tid == 64) {
        asm volatile("prefetch.tensormap [%0];" ::"l"(&mw) : "memory");
    }
    const uint32_t buf = sb + OFF_BUF + w4 * BUF_STRIDE, kb_ = sb + OFF_K + w4 * KT_BYTES;
    if ((warp >> 2) == 2) {
#pragma unroll
        for (int v = 0; v < 7; v++) if (v * 32 + lane < KT_BYTES / 16) sts128(kb_ + (v * 32 + lane) * 16, 0, 0, 0, 0);
    }
    __syncthreads();
    asm volatile("" : "+r"(pdt), "+r"(done0)::"memory");
    const unsigned epoch1 = (done0 >> 7) + 1u;
    const uint32_t tag = epoch1 & 1u;

    const int st = tid & 127;
    const uint32_t ub = sb + OFF_U + w4 * U_STRIDE + 256, spare = sb + (w4 < 2 ? OFF_SP0 : OFF_SP1) + (w4 & 1) * 4096;

    if (warp < 8) {
        const int wg = warp >> 2;
        if (warp == 0) STAMP(21);
        float acc[96];
        const int srow = warp * 16 + (lane & 15);
        const uint32_t srow_a = srow * 128;
        const int sx = srow & 7, shi = lane >> 4;
#pragma unroll
        for (int r = 0; r < 96; r++) acc[r] = 0.f;
        fence_regs<96>(acc);
        const uint64_t da0 = mkdesc(sb + wg * 8192, 16, 1024), db0 = mkdesc(sb + 16384, 8192, 1024);
#pragma unroll 1
        for (int kb = 0; kb < 8; kb++) {
            const int s = kb & 3;
            const uint64_t da = da0 + s * (SLOT >> 4), db = db0 + s * (SLOT >> 4);
            if (warp == 0) STAMP(40 + kb);
            mbar_wait(bar + 8 * (BAR_FULL + s), kb >> 2);
            if (warp == 0) STAMP(32 + kb);
            wg_fence();
#pragma unroll
            for (int k = 0; k < 4; k++) wgmma192(acc, da + 2 * k, db + 128 * k);
            wg_commit();
            wg_wait<1>();
            if (lane == 0 && kb > 0) mbar_arrive(bar + 8 * (BAR_EMPTY + ((kb - 1) & 3)));
        }
        mbar_wait(bar + 8 * BAR_WPHI, 0);
        wg_wait<0>();
        fence_regs<96>(acc);
        if (lane == 0) mbar_arrive(bar + 8 * BAR_DONE);
        if (warp == 0) STAMP(1);
        uint32_t in[32], va[16];
#pragma unroll
        for (int r = 0; r < 16; r++) {
            in[r] = pack2(acc[32 + 2 * r], acc[32 + 2 * r + 1]);
            in[16 + r] = pack2(acc[2 * r], acc[2 * r + 1]);
            va[r] = pack2(acc[64 + 2 * r], acc[64 + 2 * r + 1]);
        }
        const uint32_t wphi_a = sb + OFF_WPHI + (lane & 15) * 32 + (lane >> 4) * 16;
        uint32_t pq[4][8];
#pragma unroll 1
        for (int it = 0; it < 4; it++) {
            hedgehog2(in, wphi_a + (it & 1) * 1024, pq + 2);
#pragma unroll
            for (int r = 0; r < 24; r++) in[r] = in[r + 8];
            if (it < 2) {
#pragma unroll
                for (int hs = 0; hs < 4; hs++) {
                    float c[4] = {0.f, 0.f, 0.f, 0.f};
                    uint32_t* o = pq[2 + (hs >> 1)] + 4 * (hs & 1);
                    mma16816(c, o[0], o[1], o[2], o[3], 0x3f803f80u, 0x3f803f80u);
                    const float r0 = rcp(c[0]), r1 = rcp(c[2]);
                    const uint32_t s0 = pack2(r0, r0), s1 = pack2(r1, r1);
                    o[0] = hmul2(o[0], s0); o[1] = hmul2(o[1], s1); o[2] = hmul2(o[2], s0); o[3] = hmul2(o[3], s1);
                }
                if (it == 0) mbar_wait(bar + 8 * BAR_DONE, 0);
                const uint32_t pt = sb + OFF_P + it * 16384 + srow_a, vt = sb + OFF_V + it * 16384 + srow_a;
#pragma unroll
                for (int hl = 0; hl < 2; hl++) {
                    stsm4(pt + (((4 * hl + shi) ^ sx) << 4), pq[2 + hl][0], pq[2 + hl][1], pq[2 + hl][2], pq[2 + hl][3]);
                    stsm4(pt + (((4 * hl + 2 + shi) ^ sx) << 4), pq[2 + hl][4], pq[2 + hl][5], pq[2 + hl][6], pq[2 + hl][7]);
                    stsm4(vt + (((2 * hl + shi) ^ sx) << 4), va[4 * hl], va[4 * hl + 1], va[4 * hl + 2], va[4 * hl + 3]);
                }
                if (lane < 16) sts128(vt + ((4 ^ sx) << 4), 0x3f803f80u, 0x3f803f80u, 0x3f803f80u, 0x3f803f80u);
#pragma unroll
                for (int r = 0; r < 8; r++) va[r] = va[r + 8];
            }
            if (it == 1) {
                asm volatile("fence.proxy.async.shared::cta;" ::: "memory");
                bar_named(1, 256);
                if (warp == 0) STAMP(2);
                float d[32];
                const uint64_t dv = mkdesc(sb + OFF_V + wg * 16384, 16, 1024), dp = mkdesc(sb + OFF_P + wg * 16384, 16, 1024);
                wg_fence();
#pragma unroll
                for (int k = 0; k < 8; k++) wgmma64_tt(d, dv + 128 * k, dp + 128 * k, k != 0);
                wg_commit();
                wg_wait<0>();
                fence_regs<32>(d);
                mbar_wait(bar + 8 * BAR_PREP, 0);
                uint4* kvp = scr->kvp + bi * 544 + wg * 272;
                if (w4 < 2) {
                    uint32_t e[16];
#pragma unroll
                    for (int r = 0; r < 16; r++) e[r] = __float_as_uint(w4 ? d[16 + r] : d[r]);
                    uint4* p = kvp + w4 * 136 + lane;
#pragma unroll
                    for (int ks = 0; ks < 2; ks++)
#pragma unroll
                        for (int nt = 0; nt < 2; nt++)
                            st_rlx128(p + (ks * 2 + nt) * 32, tag4(e[8 * ks + 2 * nt], e[8 * ks + 2 * nt + 1], e[8 * ks + 4 + 2 * nt], e[8 * ks + 4 + 2 * nt + 1], tag));
                } else if (w4 == 2 && lane < 4) {
#pragma unroll
                    for (int hl = 0; hl < 2; hl++)
#pragma unroll
                        for (int ks = 0; ks < 2; ks++)
                            st_rlx128(kvp + hl * 136 + 128 + ks * 4 + lane, tag4(__float_as_uint(d[16 * hl + 8 * ks]), __float_as_uint(d[16 * hl + 8 * ks + 1]),
                                                                                __float_as_uint(d[16 * hl + 8 * ks + 4]), __float_as_uint(d[16 * hl + 8 * ks + 5]), tag));
                }
                __syncwarp();
                if (lane == 0) mbar_arrive(bar + 8 * BAR_PUB);
                if (warp == 0) STAMP(3);
            }
            if (it == 2) {
#pragma unroll
                for (int r = 0; r < 8; r++) { pq[0][r] = pq[2][r]; pq[1][r] = pq[3][r]; }
            }
        }
        if (warp == 0) STAMP(4);
        asm volatile("setmaxnreg.inc.sync.aligned.u32 160;");
        {
            mbar_wait(bar + 8 * BAR_KVF, 0);
            uint4 kf[4][3];
#pragma unroll
            for (int hh = 0; hh < 4; hh++) {
                const uint32_t a = sb + OFF_KVF + hh * 1088;
                kf[hh][0] = lds128(a + lane * 32); kf[hh][1] = lds128(a + lane * 32 + 16); kf[hh][2] = lds128(a + 1024 + q * 16);
            }
            if (warp == 0) STAMP(5);
            uint4 own[4];
#pragma unroll
            for (int hh = 0; hh < 4; hh++) {
                float c[6][4];
#pragma unroll
                for (int t = 0; t < 6; t++) { c[t][0] = c[t][1] = c[t][2] = c[t][3] = 0.f; }
                const uint32_t* a = pq[hh];
                const bool od = g & 1;
                mma16816(c[0], a[0], a[1], a[2], a[3], od ? 0x3f803f80u : kf[hh][2].x, od ? 0x3f803f80u : kf[hh][2].y);
                mma16816(c[1], a[4], a[5], a[6], a[7], od ? 0x3f803f80u : kf[hh][2].z, od ? 0x3f803f80u : kf[hh][2].w);
                mma16816(c[2], a[0], a[1], a[2], a[3], kf[hh][0].x, kf[hh][0].y);
                mma16816(c[3], a[0], a[1], a[2], a[3], kf[hh][0].z, kf[hh][0].w);
                mma16816(c[4], a[4], a[5], a[6], a[7], kf[hh][1].x, kf[hh][1].y);
                mma16816(c[5], a[4], a[5], a[6], a[7], kf[hh][1].z, kf[hh][1].w);
                uint32_t w[4];
#pragma unroll
                for (int k = 0; k < 2; k++) {
                    const float rho = c[0][2 * k + 1] * rcp(c[1][2 * k + 1]);
                    const float r = rcp(fmaf(c[0][2 * k + 1], 1e-6f, fmaf(rho, c[1][2 * k], c[0][2 * k]))), rr = r * rho;
                    w[k] = pack2(fmaf(c[4][2 * k], rr, c[2][2 * k] * r), fmaf(c[4][2 * k + 1], rr, c[2][2 * k + 1] * r));
                    w[2 + k] = pack2(fmaf(c[5][2 * k], rr, c[3][2 * k] * r), fmaf(c[5][2 * k + 1], rr, c[3][2 * k + 1] * r));
                }
                own[hh] = tag4(w[0], w[1], w[2], w[3], tag);
            }
            uint4* og = scr->o + ((bi_i * 8 + warp) * 32 + bi_j * 4) * 32 + lane;
#pragma unroll
            for (int hh = 0; hh < 4; hh++) st_rlx128(og + hh * 32, own[hh]);
        }
        if (warp == 0) STAMP(6);
        float oc[64];
        const int slab = bi_i * 8 + (bi_j >> 2) * 4 + w4;
        const uint8_t* yb = (const uint8_t*)scr->y + (size_t)((bi_j & 3) * 32 + wg * 16 + (q >> 1)) * 16384 + slab * 128 + g * 16 + (q & 1) * 8;
        const unsigned* gp = scr->g + (slab * 8 + (g >> 1)) * 8 + (g & 1) * 4;
        uint2 yv[8]; unsigned g0, g1;
        {
            const uint4* osrc = scr->o + (slab * 32 + wg * 16) * 32 + lane;
            uint4 fr[16];
            const unsigned* probe = (const unsigned*)(osrc - lane + ((lane & 3) * 4 + 3) * 32 + 31) + 2;
            {
                unsigned miss = ~0u;
                int n = 0;
#pragma unroll
                for (int s = 0; s < 4; s++) {
#pragma unroll 1
                    while ((miss >> s) & 1) { miss = __ballot_sync(~0u, (ld_rlx(probe) ^ tag) & 1); if (++n > SPIN_LIMIT) break; }
#pragma unroll
                    for (int k = 4 * s; k < 4 * s + 4; k++) fr[k] = ld_rlx128(osrc + k * 32);
                }
            }
            if (warp == 0) STAMP(14);
            mbar_wait(bar + 8 * (wg ? BAR_WO2 : BAR_WO), 0);
            const uint64_t dw = mkdesc(sb + wg * 2 * SLOT, wg ? 32768 : SLOT, 1024);
#pragma unroll
            for (int s = 0; s < 4; s++) {
                int n = 0;
#pragma unroll 1
                while (__builtin_expect(__any_sync(~0u, (bad4(fr[4 * s], tag) | bad4(fr[4 * s + 1], tag) | bad4(fr[4 * s + 2], tag) | bad4(fr[4 * s + 3], tag)) & 1), 0)) {
#pragma unroll
                    for (int k = 4 * s; k < 4 * s + 4; k++) fr[k] = ld_rlx128(osrc + k * 32);
                    if (++n > SPIN_LIMIT) break;
                }
                wg_fence();
#pragma unroll
                for (int hh = 0; hh < 4; hh++) wgmma128_rs(oc, fr[4 * s + hh], dw + 128 * (4 * s + hh), (s | hh) != 0);
                wg_commit();
                if (s == 1) {
                    wg_wait<1>();
#pragma unroll
                    for (int nt = 0; nt < 8; nt++) yv[nt] = ld_rlx64(yb + nt * 32768);
                    g0 = ld_rlx(gp); g1 = ld_rlx(gp + 32);
                }
            }
            if (warp == 0) STAMP(7);
            {
                const unsigned* yprobe = scr->yflag + ((bi_j & 3) * 32 + wg * 16 + (lane & 15)) * 8;
                int n = 0;
#pragma unroll 1
                while (true) {
                    uint32_t bad = (g0 ^ tag) | (g1 ^ tag);
#pragma unroll
                    for (int nt = 0; nt < 8; nt++) bad |= yv[nt].x ^ tag;
                    if (!__any_sync(~0u, bad & 1)) break;
#pragma unroll 1
                    while (__any_sync(~0u, (ld_rlx(yprobe) ^ tag) & 1)) { if (++n > SPIN_LIMIT) break; }
#pragma unroll
                    for (int nt = 0; nt < 8; nt++) yv[nt] = ld_rlx64(yb + nt * 32768);
                    g0 = ld_rlx(gp); g1 = ld_rlx(gp + 32);
                    if (++n > SPIN_LIMIT) break;
                }
            }
            if (warp == 0) STAMP(28);
            wg_wait<0>();
            fence_regs<64>(oc);
        }
        {
            bar_named(3 + wg, 128);
            const uint32_t xw = sb + wg * 2 * SLOT + (tid & 127) * 16, xr = sb + (wg ^ 1) * 2 * SLOT + (tid & 127) * 16;
#pragma unroll
            for (int r = 0; r < 8; r++) {
                const float* o = oc + 4 * r;
                sts128(xw + r * 2048, __float_as_uint(wg ? o[0] : o[32]), __float_as_uint(wg ? o[1] : o[33]), __float_as_uint(wg ? o[2] : o[34]), __float_as_uint(wg ? o[3] : o[35]));
            }
#pragma unroll
            for (int r = 0; r < 32; r++) oc[r] = wg ? oc[32 + r] : oc[r];
            bar_named(1, 256);
            if (warp == 0) STAMP(8);
            const float ga = bf_hi(g0), gb = bf_hi(g1);
            const float ha = bf_round(1.0f - ga), hb = bf_round(1.0f - gb);
            uint32_t w[8][2];
#pragma unroll
            for (int nt = 0; nt < 8; nt++) {
                const uint4 p = lds128(xr + nt * 2048);
                w[nt][0] = pack2(fmaf(ga, oc[4 * nt] + __uint_as_float(p.x), ha * bf_lo(yv[nt].x)), fmaf(ga, oc[4 * nt + 1] + __uint_as_float(p.y), ha * bf_hi(yv[nt].x)));
                w[nt][1] = pack2(fmaf(gb, oc[4 * nt + 2] + __uint_as_float(p.z), hb * bf_lo(yv[nt].y)), fmaf(gb, oc[4 * nt + 3] + __uint_as_float(p.w), hb * bf_hi(yv[nt].y)));
            }
            const uint32_t ob = sb + wg * 2 * SLOT + 16384 + w4 * 2048;
#pragma unroll
            for (int nt = 0; nt < 8; nt += 2)
                stsm4(ob + (lane & 15) * 128 + (((nt + shi) ^ (lane & 7)) << 4), w[nt][0], w[nt][1], w[nt + 1][0], w[nt + 1][1]);
            __syncwarp();
            bf16* op = out + (size_t)(slab * 16) * 512 + (bi_j & 3) * 128 + wg * 64 + (lane & 7) * 8;
#pragma unroll
            for (int it = 0; it < 4; it++) {
                const int r = it * 4 + (lane >> 3);
                uint4 v = lds128(ob + r * 128 + (((lane & 7) ^ (r & 7)) << 4));
                *(uint4*)(op + r * 512) = v;
            }
        }
        if (warp == 0) STAMP(10);
    } else {
        const bool hw = warp >= 12;
        const int qq = (bi_i & 2) + ((lane >> 1) & 1);
        uint2* kvf_h = (uint2*)(scr->kvf + (bi_j * 4 + (bi_i >> 2)) * 68);
        float kc[24];
#pragma unroll
        for (int t = 0; t < 24; t++) kc[t] = 0.f;
        const float dt = bf_round(expf((ch & 1) ? bf_hi(pdt) : bf_lo(pdt)));
#pragma unroll 1
        for (int it = 0; it < 2; it++) {
            const uint32_t hstg = it == 0 ? sb + 3 * SLOT + w4 * 7296 : (w4 < 2 ? sb + OFF_SP0 + w4 * SLOT : sb + OFF_KVF + (w4 & 1) * 8192);
            const uint32_t stg = hw ? hstg : buf;
            if (it == 1) {
                if (hw) {
                    {
                        mbar_wait(bar + 8 * (BAR_FULL + xkb), 0);
#pragma unroll 1
                        for (int hf = 0; hf < 2; hf++) {
                            const int r = w4 * 32 + hf * 16 + (lane & 15);
                            uint32_t* xt = (uint32_t*)scr->xt + ((xkb + rot) * 16 + (g >> 2)) * 4096 + (bi_i * 16 + w4 * 4 + hf * 2) * 16 + (g & 3) * 4 + q;
#pragma unroll
                            for (int cb = 0; cb < 8; cb += 2) {
                                uint32_t v[4];
                                ldsm4t(v, sb + xkb * SLOT + r * 128 + (((cb + (lane >> 4)) ^ (r & 7)) << 4));
                                xt[cb * 8192] = v[0]; xt[cb * 8192 + 16] = v[1]; xt[cb * 8192 + 8192] = v[2]; xt[cb * 8192 + 8192 + 16] = v[3];
                            }
                        }
                        __syncwarp();
                        if (lane == 0) mbar_arrive(bar + 8 * BAR_XT);
                        if (warp == 12) {
                            mbar_wait(bar + 8 * BAR_XT, 0);
                            if (lane == 0) asm volatile("red.release.gpu.global.add.u32 [%0],8;" ::"l"(scr->xcnt + (xkb + rot) * 32) : "memory");
                            __syncwarp();
                        }
                    }
                    {
                        const uint32_t old = tag ^ 1u;
                        const uint4 z4 = make_uint4(old, 0, old, 0);
#pragma unroll
                        for (int v = 0; v < 5; v++) if (v < 4 || st < 32) st_rlx128(scr->kvp + bi * 544 + v * 128 + st, z4);
                        if (st < 16) st_rlx128(scr->o + ((bi_i * 8 + (st >> 1)) * 32 + bi_j * 4 + 3) * 32 + 30 + (st & 1), z4);
                        if (lane < 8) st_rlx64(kvf_h + ((bi_i & 3) * 8 + w4 * 2 + (lane & 1)) * 4 + (lane >> 1), old, 0);
                        if (st < 4 && !(bi_i & 1)) st_rlx64(kvf_h + (64 + qq) * 2 + (lane & 1), old, 0);
                        __syncwarp();
                        if (lane == 0) mbar_arrive(bar + 8 * BAR_PREP);
                    }
                    {
                        int n = 0;
#pragma unroll 1
                        while (__any_sync(~0u, (int)(ld_acq(scr->xcnt + bi_j * 32) - (epoch1 << 7)) < 0)) { __nanosleep(100); if (++n > SPIN_LIMIT) break; }
                        if (warp == 12) STAMP(15);
                        uint4 ur[8];
#pragma unroll
                        for (int v = 0; v < 8; v++) ur[v] = __ldcg(scr->xt + bi * 1024 + st + 128 * v);
                        if (lane < 16) sts128(ub - 256 + lane * 16, 0, 0, 0, 0);
#pragma unroll
                        for (int v = 0; v < 8; v++) {
                            const int ci = (st >> 2) + 32 * v;
                            sts128(sb + OFF_U + (st & 3) * U_STRIDE + 256 + ((ci ^ ((ci >> 3) & 1)) << 4), ur[v].x, ur[v].y, ur[v].z, ur[v].w);
                        }
                        __syncwarp();
                        if (lane == 0) mbar_arrive(bar + 8 * BAR_UR);
                        mbar_wait(bar + 8 * BAR_UR, 0);
                        if (warp == 12) STAMP(16);
                    }
        mbar_wait(bar + 8 * BAR_DONE, 0);
                } else {
                    if (warp == 8) {
                        STAMP(17);
                        const int row = bi_j * 16 + (lane >> 1), half = lane & 1;
                        unsigned* gp = scr->g + (bi_i * 64 + bi_j * 8) * 8 + lane * 2;
                        st_rlx64(gp, tag ^ 1u, tag ^ 1u);
                        float gs0 = 0.f, gs1 = 0.f;
                        mbar_wait(bar + 8 * BAR_WPHI, 0);
#pragma unroll 1
                        for (int kb = 0; kb < 8; kb++) {
                            const int s = kb & 3;
                            mbar_wait(bar + 8 * (BAR_FULL + s), kb >> 2);
#pragma unroll
                            for (int c = 0; c < 4; c++) {
                                const uint4 xv = lds128(sb + s * SLOT + row * 128 + (((half * 4 + c) ^ (row & 7)) << 4));
                                const uint4 gw = lds128(sb + OFF_GW + ((kb + rot) & 7) * 128 + half * 64 + c * 16);
                                const uint32_t p0 = hmul2(xv.x, gw.x), p1 = hmul2(xv.y, gw.y), p2 = hmul2(xv.z, gw.z), p3 = hmul2(xv.w, gw.w);
                                gs0 += (bf_lo(p0) + bf_lo(p1)) + (bf_lo(p2) + bf_lo(p3));
                                gs1 += (bf_hi(p0) + bf_hi(p1)) + (bf_hi(p2) + bf_hi(p3));
                            }
                            if (kb < 6) {
                                mbar_wait(bar + 8 * (BAR_EMPTY + s), kb >> 2);
                                if (kb == xkb) mbar_wait(bar + 8 * BAR_XT, 0);
                                if (lane == 0) {
                                    STAMP(48 + kb);
                                    if (kb < 4) load_stage(kb + 4);
                                    else {
                                        mbar_expect(bar + 8 * BAR_WO, 32768);
                                        tma2d(sb + s * SLOT, &mwo, (bi_j & 3) * 128 + s * 64, 0, bar + 8 * BAR_WO);
                                                }
                                }
                            }
                            __syncwarp();
                        }
                        if (lane == 0) mbar_arrive(bar + 8 * BAR_DONE);
                        float gs = gs0 + gs1;
                        gs += __shfl_xor_sync(~0u, gs, 1);
                        const uint32_t gv = __float_as_uint(bf_round(rcp(1.0f + ex2(-1.4426950408889634f * bf_round(gs))))) | tag;
                        st_rlx64(gp, gv, gv);
                    }
        }
            }
            const int sh = it * 16;
            auto pick = [&](uint32_t v) { return __uint_as_float((v >> sh) << 16); };
            const float ea = bf_round(expf(pick(pla)));
            const float arl = (-ea * dt) * 1.4426950408889634f, ait = (pick(pai) * dt) * 0.15915494309189535f;
            cf C2; C2.re = 2.0f * (pick(pcr) * dt); C2.im = 2.0f * (pick(pci) * dt);
            const cf z1 = cexp_p(arl, ait, 1.0f), z128 = cexp_p(arl, ait, 128.0f);
            cf z8 = cexp_p(arl, ait, 8.0f); z8.im = -z8.im;
            const uint32_t lp = stg + lane * 4;
            auto put = [&](int row, const cf& v) { sts32((lp ^ ((row & 7) << 4)) + row * 128, pack2(v.re, v.im)); };
            {
                const cf z16 = cmul(z8, z8);
                cf e; e.re = 1.f; e.im = 0.f;
                cf o = z8;
                put(0, e); put(1, o);
                e = z16; put(2, e);
#pragma unroll
                for (int b = 3; b < 16; b += 2) {
                    o = cmul(o, z16); put(b, o);
                    if (b + 1 < 16) { e = cmul(e, z16); put(b + 1, e); }
                }
            }
            cf h[8];
            h[0] = C2; put(16, h[0]);
            {
                const cf z2 = cmul(z1, z1);
                h[1] = cmul(h[0], z1);
#pragma unroll
                for (int r = 2; r < 8; r++) h[r] = cmul(h[r - 2], z2);
#pragma unroll
                for (int r = 1; r < 8; r++) put(16 + r, h[r]);
            }
#pragma unroll
            for (int r = 0; r < 8; r++) { h[r] = cmul(h[r], z128); put(24 + r, h[r]); }
#pragma unroll
            for (int al = 0; al < 2; al++)
#pragma unroll
                for (int r = 0; r < 4; r++) { h[2 * r] = cmul(h[2 * r], z128); put(32 + al * 4 + r, h[2 * r]); }
#pragma unroll
            for (int al = 0; al < 4; al++)
#pragma unroll
                for (int r = 0; r < 2; r++) { h[4 * r] = cmul(h[4 * r], z128); put(40 + al * 2 + r, h[4 * r]); }
#pragma unroll
            for (int al = 0; al < 9; al++) { h[0] = cmul(h[0], z128); put(48 + al, h[0]); }
        __syncwarp();
            if (it == 1) mbar_wait(bar + 8 * BAR_DONE, 0);
            const int lr = lane & 7, lm = lane >> 3;
#pragma unroll
            for (int kp = 0; kp < 2; kp++) {
                uint32_t a0[4], a1[4];
                ldsm4(a0, stg + ((lm & 1) * 8 + lr) * 128 + (((4 * kp + (lm >> 1)) ^ lr) << 4));
                ldsm4(a1, stg + ((lm & 1) * 8 + lr) * 128 + (((4 * kp + 2 + (lm >> 1)) ^ lr) << 4));
#pragma unroll
                for (int t = 0; t < 6; t++) {
                    uint32_t b[4];
                    ldsm4(b, stg + (16 + 8 * t + lr) * 128 + (((4 * kp + lm) ^ lr) << 4));
                    mma16816(kc + 4 * t, a0[0], a0[1], a0[2], a0[3], b[0], b[1]);
                    mma16816(kc + 4 * t, a1[0], a1[1], a1[2], a1[3], b[2], b[3]);
                }
            }
            __syncwarp();
        if (hw) {
                if (it == 1) {
#pragma unroll
                    for (int t = 0; t < 6; t++)
                        sts128(stg + (t * 32 + lane) * 16, __float_as_uint(kc[4 * t]), __float_as_uint(kc[4 * t + 1]), __float_as_uint(kc[4 * t + 2]), __float_as_uint(kc[4 * t + 3]));
                    __syncwarp();
                    if (lane == 0) mbar_arrive(bar + 8 * BAR_KG);
                } else {
                    asm volatile("fence.proxy.async.shared::cta;" ::: "memory");
                    bar_named(5, 128);
                    if (st == 0) load_stage(3);
                    if (warp == 12) STAMP(22);
                }
            } else if (it == 1) {
                mbar_wait(bar + 8 * BAR_KG, 0);
#pragma unroll
                for (int t = 0; t < 6; t++) {
                    const uint4 v = lds128(hstg + (t * 32 + lane) * 16);
                    kc[4 * t] += __uint_as_float(v.x); kc[4 * t + 1] += __uint_as_float(v.y); kc[4 * t + 2] += __uint_as_float(v.z); kc[4 * t + 3] += __uint_as_float(v.w);
                }
                __syncwarp();
                if (lane == 0) mbar_arrive(bar + 8 * BAR_SP);
            }
        }
        if (!hw) {
            if (lane == 0) kc[4 * 0 + 0] += ((ch & 1) ? bf_hi(pds) : bf_lo(pds));
            const uint32_t k1024 = __shfl_sync(~0u, pack2(kc[4 * 4 + 0], 0.f), 0);
#pragma unroll
            for (int i = 0; i < 2; i++) {
                const int be = g + 8 * i;
#pragma unroll
                for (int t = 0; t < 2; t++) {
                    const uint32_t a = kb_ + (KW_D + 128 * t + 8 * be + 2 * q) * 4;
                    const uint32_t w = pack2(kc[4 * t + 2 * i + 1], kc[4 * t + 2 * i]);
                    sts32(a + 4, w); sts16(a, w >> 16); sts16(a + 10, w);
                }
                {
                    const int p = 256 + 128 * (q >> 1) + 8 * be + 4 * (q & 1);
                    const uint32_t a = kb_ + (KW_D + p) * 4;
                    const uint32_t w = pack2(kc[4 * 2 + 2 * i + 1], kc[4 * 2 + 2 * i]);
                    const uint32_t aa = (w >> 16) | (w & 0xffff0000u);
                    if (p != 256) { sts16(a - 4, aa); sts32(a, aa); } else sts16(a, aa);
                    sts32(a + 4, aa); sts32(a + 8, w); sts16(a + 14, w);
                }
                {
                    const int k = 64 + 16 * q + be;
                    const uint32_t w = pack2(kc[4 * 3 + 2 * i], kc[4 * 3 + 2 * i + 1]);
                    if (k != 64) sts16(kb_ + (KW_2 + ((k - 1) >> 1) - 24) * 4 + (k & 1) * 2, w);
                    else {
                        const uint32_t a = kb_ + (KW_D + 511) * 4, aa = (w << 16) | (w & 0xffffu);
                        sts16(a, w); sts32(a + 4, aa); sts32(a + 8, aa); sts32(a + 12, aa); sts16(a + 18, w);
                    }
                    sts16(kb_ + (KW_2 + 48 + (k >> 1) - 24) * 4 + ((k & 1) ^ 1) * 2, w >> 16);
                }
#pragma unroll
                for (int b = 0; b < 2; b++) {
                    const int k = 64 + 8 * (2 * q + b) + (be >> 1);
                    const uint32_t w = pack2(kc[4 * 4 + 2 * i + b], 0.f);
                    if (!(be & 1) && k == 64) sts16(kb_ + (KW_2 + 63 - 24) * 4, w);
                    else {
                        const uint32_t a = kb_ + (KW_3 + ((be & 1) ? 80 + k : k - 1) - 48) * 4;
                        sts16(a, w);
                        if (!((be & 1) && k == 127)) sts16(a + 6, w);
                    }
                }
            }
            if (lane == 0) sts16(kb_ + (KW_3 + 127 - 48) * 4, pack2(kc[4 * 5 + 0], 0.f));
        if (st < 8) st_rlx32(scr->yflag + bi * 8 + st, tag ^ 1u);
            __syncwarp();
            mbar_wait(bar + 8 * BAR_UR, 0);
            if (warp == 8) STAMP(23);
            float y[16][4];
#pragma unroll
            for (int nt = 0; nt < 16; nt++) { y[nt][0] = y[nt][1] = y[nt][2] = y[nt][3] = 0.f; }
            {
                uint32_t Bp[32], A[5][3];
                auto uaddr = [&](int rho) { const int R0 = (lane >> 4) * 8 + (lane & 7) - rho; return ub + (((2 * R0 + ((lane >> 3) & 1)) ^ ((R0 >> 2) & 1)) << 4); };
                const uint32_t kd = kb_ + (KW_D + g - 2 * q) * 4;
                auto lda = [&](int rho) {
#pragma unroll
                    for (int ga = 0; ga < 5; ga++) {
                        const uint32_t a = kd + (ga < 4 ? rho : (rho & 1)) * 64 + ga * 512;
                        A[ga][0] = lds32(a); A[ga][1] = lds32(a + 32); A[ga][2] = lds32(a - 32);
                    }
                };
                {
                    const uint32_t a = uaddr(0);
#pragma unroll
                    for (int p = 0; p < 8; p++) ldsm4(Bp + 4 * p, a + p * 512);
                }
#pragma unroll 1
                for (int rho = 0; rho < 8; rho++) {
                    lda(rho);
                    if (rho < 2) {
#pragma unroll
                        for (int nt = 4; nt < 16; nt++) mma16816(y[nt], A[4][0], A[4][1], A[4][2], A[4][0], Bp[2 * (nt - 4)], Bp[2 * (nt - 4) + 1]);
                    }
#pragma unroll
                    for (int ga = 0; ga < 3; ga++)
#pragma unroll
                        for (int nt = 15; nt >= ga; nt--) mma16816(y[nt], A[ga][0], A[ga][1], A[ga][2], A[ga][0], Bp[2 * (nt - ga)], Bp[2 * (nt - ga) + 1]);
                    const uint32_t an = uaddr(rho + 1);
                    ldsm4(Bp + 28, an + 7 * 512);
#pragma unroll
                    for (int nt = 15; nt >= 3; nt--) {
                        mma16816(y[nt], A[3][0], A[3][1], A[3][2], A[3][0], Bp[2 * (nt - 3)], Bp[2 * (nt - 3) + 1]);
                        if (nt & 1) ldsm4(Bp + 2 * (nt - 3), an + ((nt - 3) >> 1) * 512);
                    }
                }
            }
            if (warp == 8) STAMP(18);
            mbar_wait(bar + 8 * BAR_WR, 0);
#pragma unroll 1
            for (int ph = 0; ph < 2; ph++) {
                uint32_t B[5][2];
                const uint32_t ka = kb_ + (KW_2 + ph * 48 + 8 + g - q) * 4;
#pragma unroll
                for (int dd = 0; dd < 5; dd++) { B[dd][0] = lds32(ka + dd * 32); B[dd][1] = lds32(ka + dd * 32 - 16); }
                const uint32_t wa = buf + ph * W3_OFF + ((lane & 7) + ((lane >> 3) & 1) + (lane >> 4) * 8) * 16;
#pragma unroll
                for (int s = 0; s < 12; s++) {
                    uint32_t A[4];
                    ldsm4t(A, wa + s * 256);
#pragma unroll
                    for (int dd = 0; dd < 5; dd++)
                        if (s + 4 + dd < 16) mma16816(y[s + 4 + dd], A[0], A[1], A[2], A[3], B[dd][0], B[dd][1]);
                }
            }
            {
                const int ap = (lane & 7) + (lane >> 4) * 8;
                const uint32_t loff = ((2 * ap + ((lane >> 3) & 1)) ^ ((ap >> 2) & 1)) << 4;
#pragma unroll 1
                for (int ph = 0; ph < 2; ph++) {
                    uint32_t B[8][2];
                    const uint32_t wb = (ph ? spare : buf + W9_OFF) + loff;
                    const uint32_t ka = kb_ + (KW_3 + ph * 80 + 16 + g - 2 * q) * 4;
#pragma unroll
                    for (int dd = 0; dd < 8; dd++) { B[dd][0] = lds32(ka + dd * 32); B[dd][1] = lds32(ka + dd * 32 - 32); }
#pragma unroll
                    for (int s = 0; s < 4; s++) {
                        uint32_t A[4];
                        ldsm4t(A, wb + s * 512);
#pragma unroll
                        for (int dd = 0; dd < 8; dd++)
                            if (8 + 2 * s + dd < 16) mma16816(y[8 + 2 * s + dd], A[0], A[1], A[2], A[3], B[dd][0], B[dd][1]);
                    }
                }
                const uint32_t idw = (g == 2 * q) ? k1024 : ((g == 2 * q + 1) ? (k1024 << 16) : 0u);
#pragma unroll
                for (int s = 0; s < 4; s++) {
                    uint32_t A[4];
                    ldsm4t(A, spare + 2048 + loff + s * 512);
                    mma16816(y[8 + 2 * s], A[0], A[1], A[2], A[3], idw, 0u);
                    mma16816(y[9 + 2 * s], A[0], A[1], A[2], A[3], 0u, idw);
                }
            }
            __syncwarp();
            if (warp == 8) STAMP(19);
#pragma unroll
            for (int nt = 0; nt < 16; nt++)
#pragma unroll
                for (int b = 0; b < 2; b++) sts32(buf + ((8 * nt + 2 * q + b) * 8 + g) * 4, pack2(y[nt][b], y[nt][2 + b]));
            bar_named(2, 128);
            uint4* yp = scr->y + bi * 1024 + st;
#pragma unroll
            for (int v = 0; v < 8; v++) {
                const uint32_t a = sb + OFF_BUF + (st + 128 * v) * 4;
                const uint32_t w0 = lds32(a), w1 = lds32(a + BUF_STRIDE), w2 = lds32(a + 2 * BUF_STRIDE), w3 = lds32(a + 3 * BUF_STRIDE);
                st_rlx128(yp + v * 128, tag4(__byte_perm(w0, w1, 0x5410), __byte_perm(w0, w1, 0x7632), __byte_perm(w2, w3, 0x5410), __byte_perm(w2, w3, 0x7632), tag));
            }
            if (st < 8) st_rlx32(scr->yflag + bi * 8 + st, tag);
            if (warp == 8) STAMP(20);
    } else {
            asm volatile("setmaxnreg.dec.sync.aligned.u32 64;");
            mbar_wait(bar + 8 * BAR_SP, 0);
            if (lane < 2) sts128(buf + lane * W3_OFF, 0, 0, 0, 0);
#pragma unroll 1
            for (int rho = 5; rho >= 0; rho--) {
                const int ci = lane + 32 * rho;
                uint4 e4[4];
#pragma unroll
                for (int v = 0; v < 4; v++) { const int cc = ci - 3 + v; e4[v] = lds128(ub + ((cc ^ ((cc >> 3) & 1)) << 4)); }
                float S[29];
                const uint32_t* ew = (const uint32_t*)e4;
                S[3] = 0.f;
#pragma unroll
                for (int k = 4; k <= 28; k++) S[k] = S[k - 1] + ((k & 1) ? bf_hi(ew[k >> 1]) : bf_lo(ew[k >> 1]));
                auto win = [&](int lo, int hi, uint32_t a) {
                    sts128(a, pack2(S[hi] - S[lo - 1], S[hi + 1] - S[lo]), pack2(S[hi + 2] - S[lo + 1], S[hi + 3] - S[lo + 2]),
                           pack2(S[hi + 4] - S[lo + 3], S[hi + 5] - S[lo + 4]), pack2(S[hi + 6] - S[lo + 5], S[hi + 7] - S[lo + 6]));
                };
                win(14, 18, buf + W5_OFF + 16 + ci * 16); win(19, 21, buf + W3_OFF + 16 + ci * 16);
                if (rho < 4) {
                    const uint32_t sw = (ci ^ ((ci >> 3) & 1)) << 4;
                    win(4, 12, buf + W9_OFF + sw); win(13, 19, spare + sw); win(20, 21, spare + 2048 + sw);
                }
            }
            __syncwarp();
            if (lane == 0) mbar_arrive(bar + 8 * BAR_WR);
            if (warp == 12) STAMP(24);
            mbar_wait(bar + 8 * BAR_PUB, 0);
            if (warp == 12) STAMP(12);
#pragma unroll 1
            for (int zw = 0; zw < ((st < 32 && !(bi_i & 1)) ? 2 : 1); zw++) {
                const int kvf_n = zw ? 4 : 8;
                uint2* kvf_dst = kvf_h + (zw ? (64 + qq) * 2 + (lane & 1) : ((bi_i & 3) * 8 + w4 * 2 + (lane & 1)) * 4 + (lane >> 1));
                const uint4* src = scr->kvp + bi_j * (16 * 544) + (bi_i >> 2) * 136 +
                                   (zw ? (lane >> 2) * (2 * 544) + 128 + (lane & 1) * 4 + qq
                                       : (lane >> 3) * (4 * 544) + ((lane >> 1) & 3) * 32 + (bi_i & 3) * 8 + w4 * 2 + (lane & 1));
                const int s23 = zw ? 0 : 2 * 544;
                uint4 v[4];
                int n = 0;
#pragma unroll 1
                while (true) {
                    v[0] = ld_rlx128(src); v[1] = ld_rlx128(src + 544); v[2] = ld_rlx128(src + s23); v[3] = ld_rlx128(src + s23 + 544);
                    if (!__any_sync(~0u, (bad4(v[0], tag) | bad4(v[1], tag) | bad4(v[2], tag) | bad4(v[3], tag)) & 1)) break;
                    if (++n > SPIN_LIMIT) break;
                }
                float f[4];
                f[0] = __uint_as_float(v[2].x) + __uint_as_float(v[3].x); f[1] = __uint_as_float(v[2].y) + __uint_as_float(v[3].y);
                f[2] = __uint_as_float(v[2].z) + __uint_as_float(v[3].z); f[3] = __uint_as_float(v[2].w) + __uint_as_float(v[3].w);
                float e0 = __uint_as_float(v[0].x) + __uint_as_float(v[1].x), e1 = __uint_as_float(v[0].y) + __uint_as_float(v[1].y);
                float e2 = __uint_as_float(v[0].z) + __uint_as_float(v[1].z), e3 = __uint_as_float(v[0].w) + __uint_as_float(v[1].w);
                if (zw) {
                    e0 = __shfl_xor_sync(~0u, f[0], 4); e1 = __shfl_xor_sync(~0u, f[1], 4);
                    e2 = __shfl_xor_sync(~0u, f[2], 4); e3 = __shfl_xor_sync(~0u, f[3], 4);
                }
                f[0] += e0; f[1] += e1; f[2] += e2; f[3] += e3;
#pragma unroll
                for (int o = 8; o <= 16; o <<= 1)
#pragma unroll
                    for (int r = 0; r < 4; r++) f[r] += __shfl_xor_sync(~0u, f[r], o);
                if (lane < kvf_n) st_rlx64(kvf_dst, tagw(pack2(f[0], f[1]), tag), pack2(f[2], f[3]));
            }
            if (warp == 12) STAMP(13);
            if (st == 32) {
                mbar_expect(bar + 8 * BAR_WO2, 65536);
                tma2d(sb + OFF_P, &mwo, (bi_j & 3) * 128, 256, bar + 8 * BAR_WO2);
                tma2d(sb + OFF_V, &mwo, (bi_j & 3) * 128 + 64, 256, bar + 8 * BAR_WO2);
            }
            __syncwarp();
            {
                const uint4* kp = scr->kvf + bi_j * 272 + st;
                uint4 v0, v1, v2;
                int n = 0;
#pragma unroll 1
                while (true) {
                    v0 = ld_rlx128(kp); v1 = ld_rlx128(kp + 128); v2 = ld_rlx128(kp + (st < 16 ? 256 : 0));
                    if (!__any_sync(~0u, (bad4(v0, tag) | bad4(v1, tag) | bad4(v2, tag)) & 1)) break;
                    if (++n > SPIN_LIMIT) break;
                }
                sts128(sb + OFF_KVF + st * 16, v0.x, v0.y, v0.z, v0.w);
                sts128(sb + OFF_KVF + 2048 + st * 16, v1.x, v1.y, v1.z, v1.w);
                if (st < 16) sts128(sb + OFF_KVF + 4096 + st * 16, v2.x, v2.y, v2.z, v2.w);
                __syncwarp();
                if (lane == 0) mbar_arrive(bar + 8 * BAR_KVF);
            }
            if (warp == 12) STAMP(25);
    }
    }
    __syncwarp();
    if (lane == 0) {
        unsigned old;
        asm volatile("atom.acq_rel.cta.shared.add.u32 %0,[%1],1;" : "=r"(old) : "r"(bar + OFF_CNT) : "memory");
        if (old == 15) {
            atomicAdd(scr->done, 1u);
        }
    }
}

typedef CUresult (*EncFn)(CUtensorMap*, CUtensorMapDataType, cuuint32_t, void*, const cuuint64_t*, const cuuint64_t*, const cuuint32_t*,
                          const cuuint32_t*, CUtensorMapInterleave, CUtensorMapSwizzle, CUtensorMapL2promotion, CUtensorMapFloatOOBfill);

extern "C" void kernel_launch(void* const* d_in, const int* in_sizes, int n_in, void* d_out, int out_size) {
    static EncFn enc = nullptr;
    static Scratch* scr = nullptr;
    if (!enc) {
        cudaGetSymbolAddress((void**)&scr, g_scr);
        cudaDriverEntryPointQueryResult qr;
        cudaGetDriverEntryPoint("cuTensorMapEncodeTiled", (void**)&enc, cudaEnableDefault, &qr);
        cudaFuncSetAttribute(fused_kernel, cudaFuncAttributeMaxDynamicSharedMemorySize, SMEM_BYTES);
    }
    CUtensorMap mx, mw, mwo;
    const cuuint32_t es[3] = {1, 1, 1};
    {
        cuuint64_t d[2] = {512, 2048}, s[1] = {1024}; cuuint32_t b[2] = {64, 128};
        enc(&mx, CU_TENSOR_MAP_DATA_TYPE_BFLOAT16, 2, d_in[0], d, s, b, es, CU_TENSOR_MAP_INTERLEAVE_NONE, CU_TENSOR_MAP_SWIZZLE_128B,
            CU_TENSOR_MAP_L2_PROMOTION_L2_128B, CU_TENSOR_MAP_FLOAT_OOB_FILL_NONE);
    }
    {
        cuuint64_t d[3] = {512, 512, 3}, s[2] = {3072, 1024}; cuuint32_t b[3] = {64, 64, 3};
        enc(&mw, CU_TENSOR_MAP_DATA_TYPE_BFLOAT16, 3, d_in[1], d, s, b, es, CU_TENSOR_MAP_INTERLEAVE_NONE, CU_TENSOR_MAP_SWIZZLE_128B,
            CU_TENSOR_MAP_L2_PROMOTION_L2_128B, CU_TENSOR_MAP_FLOAT_OOB_FILL_NONE);
    }
    {
        cuuint64_t d[2] = {512, 512}, s[1] = {1024}; cuuint32_t b[2] = {64, 256};
        enc(&mwo, CU_TENSOR_MAP_DATA_TYPE_BFLOAT16, 2, d_in[3], d, s, b, es, CU_TENSOR_MAP_INTERLEAVE_NONE, CU_TENSOR_MAP_SWIZZLE_128B,
            CU_TENSOR_MAP_L2_PROMOTION_L2_128B, CU_TENSOR_MAP_FLOAT_OOB_FILL_NONE);
    }
    fused_kernel<<<128, 512, SMEM_BYTES, cudaStreamPerThread>>>(
        scr, (const bf16*)d_in[5], (const bf16*)d_in[6], (const bf16*)d_in[7], (const bf16*)d_in[8], (const bf16*)d_in[9],
        (const bf16*)d_in[10], (const bf16*)d_in[2], (const bf16*)d_in[11], (bf16*)d_out, mx, mw, mwo);
}
```

```cpp
#include <cuda_runtime.h>
#include <cuda.h>
#include <cuda_bf16.h>
#include <stdint.h>

typedef __nv_bfloat16 bf16;

struct Scratch {
    uint4 xt[128 * 1024];
    uint4 o[16 * 8 * 32 * 32];
    uint4 y[128 * 1024];
    uint4 kvp[8 * 16 * 544];
    uint4 kvf[8 * 4 * 68];
    unsigned g[1024 * 8];
    unsigned yflag[128 * 8];
    unsigned xcnt[8 * 32];
    unsigned done[32];
};
__device__ Scratch g_scr;
#define STAMP(n)

constexpr int SLOT = 40960;
constexpr int OFF_SP0 = 32768, OFF_SP1 = SLOT + 32768;
constexpr int OFF_P = 2 * SLOT, OFF_V = OFF_P + 32768;
constexpr int OFF_KVF = OFF_V + 32768;
constexpr int KT_BYTES = 3264, KW_D = 16, KW_2 = 560, KW_3 = 656;
constexpr int OFF_U = 4 * SLOT, U_STRIDE = 4096 + 256 + 32;
constexpr int OFF_BUF = OFF_U + 4 * U_STRIDE, BUF_STRIDE = 8320;
constexpr int OFF_K = OFF_BUF + 4 * BUF_STRIDE;
constexpr int OFF_WPHI = OFF_K + 4 * KT_BYTES;
constexpr int OFF_GW = OFF_WPHI + 2048;
constexpr int OFF_BAR = OFF_GW + 1024;
constexpr int SMEM_BYTES = OFF_BAR + 256 + 256;
static_assert(SMEM_BYTES <= 232448 && OFF_BUF % 128 == 0, "smem");
constexpr int W5_OFF = 0, W3_OFF = 3088, W9_OFF = 6176;
constexpr int BAR_FULL = 0, BAR_EMPTY = 4, BAR_WPHI = 8, BAR_WO = 9, BAR_WO2 = 10, BAR_XT = 11, BAR_DONE = 12, BAR_KG = 13, BAR_SP = 14,
              BAR_PUB = 15, BAR_KVF = 16, BAR_UR = 17, BAR_WR = 18, BAR_PREP = 19, BAR_KGA = 20, BAR_SP2 = 21, OFF_CNT = 192;
constexpr int SPIN_LIMIT = 1 << 17;

__device__ __forceinline__ uint32_t s2u(const void* p) { return (uint32_t)__cvta_generic_to_shared(p); }
__device__ __forceinline__ void mbar_init(uint32_t b, int c) { asm volatile("mbarrier.init.shared::cta.b64 [%0],%1;" ::"r"(b), "r"(c) : "memory"); }
__device__ __forceinline__ void mbar_expect(uint32_t b, int bytes) { asm volatile("mbarrier.arrive.expect_tx.shared::cta.b64 _,[%0],%1;" ::"r"(b), "r"(bytes) : "memory"); }
__device__ __forceinline__ void mbar_arrive(uint32_t b) { asm volatile("mbarrier.arrive.shared::cta.b64 _,[%0];" ::"r"(b) : "memory"); }
__device__ __forceinline__ void mbar_wait(uint32_t b, int ph) {
    asm volatile("{\n.reg .pred p;\n.reg .u32 n;\nmov.u32 n,0;\nLW_%=:\nmbarrier.try_wait.parity.shared::cta.b64 p,[%0],%1;\n@p bra LD_%=;\n"
                 "add.u32 n,n,1;\nsetp.lt.u32 p,n,16384;\n@p bra LW_%=;\nLD_%=:\n}" ::"r"(b), "r"(ph) : "memory");
}
__device__ __forceinline__ void tma2d(uint32_t dst, const CUtensorMap* m, int c0, int c1, uint32_t bar) {
    asm volatile("cp.async.bulk.tensor.2d.shared::cluster.global.mbarrier::complete_tx::bytes [%0],[%1,{%3,%4}],[%2];" ::"r"(dst), "l"(m), "r"(bar), "r"(c0), "r"(c1) : "memory");
}
__device__ __forceinline__ void tma3d(uint32_t dst, const CUtensorMap* m, int c0, int c1, int c2, uint32_t bar) {
    asm volatile("cp.async.bulk.tensor.3d.shared::cluster.global.mbarrier::complete_tx::bytes [%0],[%1,{%3,%4,%5}],[%2];" ::"r"(dst), "l"(m), "r"(bar), "r"(c0), "r"(c1), "r"(c2) : "memory");
}
__device__ __forceinline__ void bulk_g2s(uint32_t dst, const void* src, int bytes, uint32_t bar) {
    asm volatile("cp.async.bulk.shared::cluster.global.mbarrier::complete_tx::bytes [%0],[%1],%2,[%3];" ::"r"(dst), "l"(src), "r"(bytes), "r"(bar) : "memory");
}
__device__ __forceinline__ uint64_t mkdesc(uint32_t addr, uint32_t lbo, uint32_t sbo) {
    return (uint64_t)((addr & 0x3FFFF) >> 4) | ((uint64_t)(lbo >> 4) << 16) | ((uint64_t)(sbo >> 4) << 32) | ((uint64_t)1 << 62);
}
__device__ __forceinline__ void wg_fence() { asm volatile("wgmma.fence.sync.aligned;" ::: "memory"); }
__device__ __forceinline__ void wg_commit() { asm volatile("wgmma.commit_group.sync.aligned;" ::: "memory"); }
template <int N> __device__ __forceinline__ void wg_wait() { asm volatile("wgmma.wait_group.sync.aligned %0;" ::"n"(N) : "memory"); }
template <int N> __device__ __forceinline__ void fence_regs(float* d) {
#pragma unroll
    for (int i = 0; i < N; i++) asm volatile("" : "+f"(d[i])::"memory");
}
#define R8(d, o) "+f"(d[o]), "+f"(d[o + 1]), "+f"(d[o + 2]), "+f"(d[o + 3]), "+f"(d[o + 4]), "+f"(d[o + 5]), "+f"(d[o + 6]), "+f"(d[o + 7])
__device__ __forceinline__ void wgmma192(float* d, uint64_t da, uint64_t db) {
    asm volatile("wgmma.mma_async.sync.aligned.m64n192k16.f32.bf16.bf16 {"
                 "%0,%1,%2,%3,%4,%5,%6,%7,%8,%9,%10,%11,%12,%13,%14,%15,%16,%17,%18,%19,%20,%21,%22,%23,%24,%25,%26,%27,%28,%29,%30,%31,"
                 "%32,%33,%34,%35,%36,%37,%38,%39,%40,%41,%42,%43,%44,%45,%46,%47,%48,%49,%50,%51,%52,%53,%54,%55,%56,%57,%58,%59,%60,%61,%62,%63,"
                 "%64,%65,%66,%67,%68,%69,%70,%71,%72,%73,%74,%75,%76,%77,%78,%79,%80,%81,%82,%83,%84,%85,%86,%87,%88,%89,%90,%91,%92,%93,%94,%95},"
                 "%96,%97,1,1,1,0,1;"
                 : R8(d, 0), R8(d, 8), R8(d, 16), R8(d, 24), R8(d, 32), R8(d, 40), R8(d, 48), R8(d, 56), R8(d, 64), R8(d, 72), R8(d, 80), R8(d, 88)
                 : "l"(da), "l"(db));
}
__device__ __forceinline__ void wgmma64_tt(float* d, uint64_t da, uint64_t db, int sc) {
    asm volatile("{.reg .pred p; setp.ne.b32 p,%34,0; wgmma.mma_async.sync.aligned.m64n64k16.f32.bf16.bf16 {"
                 "%0,%1,%2,%3,%4,%5,%6,%7,%8,%9,%10,%11,%12,%13,%14,%15,%16,%17,%18,%19,%20,%21,%22,%23,%24,%25,%26,%27,%28,%29,%30,%31},"
                 "%32,%33,p,1,1,1,1;}"
                 : R8(d, 0), R8(d, 8), R8(d, 16), R8(d, 24)
                 : "l"(da), "l"(db), "r"(sc));
}
__device__ __forceinline__ void wgmma128_rs(float* d, const uint4& a, uint64_t db, int sc) {
    asm volatile("{.reg .pred p; setp.ne.b32 p,%69,0; wgmma.mma_async.sync.aligned.m64n128k16.f32.bf16.bf16 {"
                 "%0,%1,%2,%3,%4,%5,%6,%7,%8,%9,%10,%11,%12,%13,%14,%15,%16,%17,%18,%19,%20,%21,%22,%23,%24,%25,%26,%27,%28,%29,%30,%31,"
                 "%32,%33,%34,%35,%36,%37,%38,%39,%40,%41,%42,%43,%44,%45,%46,%47,%48,%49,%50,%51,%52,%53,%54,%55,%56,%57,%58,%59,%60,%61,%62,%63},"
                 "{%64,%65,%66,%67},%68,p,1,1,1;}"
                 : R8(d, 0), R8(d, 8), R8(d, 16), R8(d, 24), R8(d, 32), R8(d, 40), R8(d, 48), R8(d, 56)
                 : "r"(a.x), "r"(a.y), "r"(a.z), "r"(a.w), "l"(db), "r"(sc));
}
__device__ __forceinline__ void mma16816(float* c, uint32_t a0, uint32_t a1, uint32_t a2, uint32_t a3, uint32_t b0, uint32_t b1) {
    asm("mma.sync.aligned.m16n8k16.row.col.f32.bf16.bf16.f32 {%0,%1,%2,%3},{%4,%5,%6,%7},{%8,%9},{%0,%1,%2,%3};"
        : "+f"(c[0]), "+f"(c[1]), "+f"(c[2]), "+f"(c[3]) : "r"(a0), "r"(a1), "r"(a2), "r"(a3), "r"(b0), "r"(b1));
}
__device__ __forceinline__ void ldsm4(uint32_t* r, uint32_t a) {
    asm volatile("ldmatrix.sync.aligned.m8n8.x4.shared.b16 {%0,%1,%2,%3},[%4];" : "=r"(r[0]), "=r"(r[1]), "=r"(r[2]), "=r"(r[3]) : "r"(a) : "memory");
}
__device__ __forceinline__ void ldsm4t(uint32_t* r, uint32_t a) {
    asm volatile("ldmatrix.sync.aligned.m8n8.x4.trans.shared.b16 {%0,%1,%2,%3},[%4];" : "=r"(r[0]), "=r"(r[1]), "=r"(r[2]), "=r"(r[3]) : "r"(a) : "memory");
}
__device__ __forceinline__ void stsm4(uint32_t a, uint32_t r0, uint32_t r1, uint32_t r2, uint32_t r3) {
    asm volatile("stmatrix.sync.aligned.m8n8.x4.shared.b16 [%0],{%1,%2,%3,%4};" ::"r"(a), "r"(r0), "r"(r1), "r"(r2), "r"(r3) : "memory");
}
__device__ __forceinline__ uint32_t lds32(uint32_t a) { uint32_t v; asm volatile("ld.shared.b32 %0,[%1];" : "=r"(v) : "r"(a) : "memory"); return v; }
__device__ __forceinline__ uint4 lds128(uint32_t a) { uint4 v; asm volatile("ld.shared.v4.b32 {%0,%1,%2,%3},[%4];" : "=r"(v.x), "=r"(v.y), "=r"(v.z), "=r"(v.w) : "r"(a) : "memory"); return v; }
__device__ __forceinline__ void sts16(uint32_t a, uint32_t v) { asm volatile("st.shared.b16 [%0],%1;" ::"r"(a), "h"((unsigned short)v) : "memory"); }
__device__ __forceinline__ void sts32(uint32_t a, uint32_t v) { asm volatile("st.shared.b32 [%0],%1;" ::"r"(a), "r"(v) : "memory"); }
__device__ __forceinline__ void sts64(uint32_t a, uint32_t x, uint32_t y) { asm volatile("st.shared.v2.b32 [%0],{%1,%2};" ::"r"(a), "r"(x), "r"(y) : "memory"); }
__device__ __forceinline__ void sts128(uint32_t a, uint32_t x, uint32_t y, uint32_t z, uint32_t w) { asm volatile("st.shared.v4.b32 [%0],{%1,%2,%3,%4};" ::"r"(a), "r"(x), "r"(y), "r"(z), "r"(w) : "memory"); }
__device__ __forceinline__ uint32_t pack2(float lo, float hi) { uint32_t d; asm("cvt.rn.bf16x2.f32 %0,%1,%2;" : "=r"(d) : "f"(hi), "f"(lo)); return d; }
__device__ __forceinline__ float bf_lo(uint32_t v) { return __uint_as_float(v << 16); }
__device__ __forceinline__ float bf_hi(uint32_t v) { return __uint_as_float(v & 0xffff0000u); }
__device__ __forceinline__ float bf_round(float v) { return bf_lo(pack2(v, 0.f)); }
__device__ __forceinline__ uint32_t hmax2(uint32_t a, uint32_t b) { uint32_t d; asm("max.bf16x2 %0,%1,%2;" : "=r"(d) : "r"(a), "r"(b)); return d; }
__device__ __forceinline__ uint32_t hmin2(uint32_t a, uint32_t b) { uint32_t d; asm("min.bf16x2 %0,%1,%2;" : "=r"(d) : "r"(a), "r"(b)); return d; }
__device__ __forceinline__ uint32_t hmul2(uint32_t a, uint32_t b) { uint32_t d; asm("mul.rn.bf16x2 %0,%1,%2;" : "=r"(d) : "r"(a), "r"(b)); return d; }
__device__ __forceinline__ float ex2(float x) { float y; asm("ex2.approx.ftz.f32 %0,%1;" : "=f"(y) : "f"(x)); return y; }
__device__ __forceinline__ float rcp(float x) { float y; asm("rcp.approx.ftz.f32 %0,%1;" : "=f"(y) : "f"(x)); return y; }
__device__ __forceinline__ uint32_t ld_nc(const uint32_t* p) { uint32_t v; asm volatile("ld.global.nc.b32 %0,[%1];" : "=r"(v) : "l"(p)); return v; }
__device__ __forceinline__ uint2 ld_nc64(const uint2* p) { uint2 v; asm volatile("ld.global.nc.v2.b32 {%0,%1},[%2];" : "=r"(v.x), "=r"(v.y) : "l"(p)); return v; }
__device__ __forceinline__ unsigned ld_acq(const unsigned* p) { unsigned v; asm volatile("ld.acquire.gpu.global.u32 %0,[%1];" : "=r"(v) : "l"(p) : "memory"); return v; }
__device__ __forceinline__ unsigned ld_rlx(const unsigned* p) { unsigned v; asm volatile("ld.relaxed.gpu.global.u32 %0,[%1];" : "=r"(v) : "l"(p) : "memory"); return v; }
__device__ __forceinline__ uint2 ld_rlx64(const void* p) { uint2 v; asm volatile("{.reg .b64 t; ld.relaxed.gpu.global.b64 t,[%2]; mov.b64 {%0,%1},t;}" : "=r"(v.x), "=r"(v.y) : "l"(p) : "memory"); return v; }
__device__ __forceinline__ uint4 ld_rlx128(const void* p) {
    uint4 v;
    asm volatile("{.reg .b64 t,u; ld.relaxed.gpu.global.v2.b64 {t,u},[%4]; mov.b64 {%0,%1},t; mov.b64 {%2,%3},u;}" : "=r"(v.x), "=r"(v.y), "=r"(v.z), "=r"(v.w) : "l"(p) : "memory");
    return v;
}
__device__ __forceinline__ void st_rlx32(void* p, uint32_t x) { asm volatile("st.relaxed.gpu.global.u32 [%0],%1;" ::"l"(p), "r"(x) : "memory"); }
__device__ __forceinline__ void st_rlx64(void* p, uint32_t x, uint32_t y) { asm volatile("{.reg .b64 t; mov.b64 t,{%1,%2}; st.relaxed.gpu.global.b64 [%0],t;}" ::"l"(p), "r"(x), "r"(y) : "memory"); }
__device__ __forceinline__ void st_rlx128(void* p, uint4 v) {
    asm volatile("{.reg .b64 t,u; mov.b64 t,{%1,%2}; mov.b64 u,{%3,%4}; st.relaxed.gpu.global.v2.b64 [%0],{t,u};}" ::"l"(p), "r"(v.x), "r"(v.y), "r"(v.z), "r"(v.w) : "memory");
}
__device__ __forceinline__ uint32_t tagw(uint32_t w, uint32_t tag) { return (w & ~1u) | tag; }
__device__ __forceinline__ uint4 tag4(uint32_t x, uint32_t y, uint32_t z, uint32_t w, uint32_t tag) { return make_uint4(tagw(x, tag), y, tagw(z, tag), w); }
__device__ __forceinline__ uint32_t bad4(const uint4& v, uint32_t tag) { return (v.x ^ tag) | (v.z ^ tag); }
__device__ __forceinline__ void bar_named(int id, int n) { asm volatile("bar.sync %0,%1;" ::"r"(id), "r"(n) : "memory"); }

struct cf { float re, im; };
__device__ __forceinline__ cf cmul(cf a, cf b) { cf r; r.re = a.re * b.re - a.im * b.im; r.im = a.re * b.im + a.im * b.re; return r; }
__device__ __forceinline__ cf cexp_p(float arl, float ait, float p) {
    float mag = ex2(arl * p);
    float t = ait * p;
    t = (t - rintf(t)) * 6.283185307179586f;
    cf r; r.re = mag * __cosf(t); r.im = mag * __sinf(t);
    return r;
}

__device__ __forceinline__ void hedgehog2(const uint32_t* a, uint32_t wphi_addr, uint32_t (*out)[8]) {
    float p[2][2][4], mx[2][2];
#pragma unroll
    for (int h = 0; h < 2; h++) {
        uint32_t b[4];
        ldsm4t(b, wphi_addr + h * 512);
        float c0[4] = {0.f, 0.f, 0.f, 0.f}, c1[4] = {0.f, 0.f, 0.f, 0.f};
        mma16816(c0, a[4 * h], a[4 * h + 1], a[4 * h + 2], a[4 * h + 3], b[0], b[1]);
        mma16816(c1, a[4 * h], a[4 * h + 1], a[4 * h + 2], a[4 * h + 3], b[2], b[3]);
#pragma unroll
        for (int k = 0; k < 2; k++) {
            p[h][k][0] = c0[2 * k]; p[h][k][1] = c0[2 * k + 1]; p[h][k][2] = c1[2 * k]; p[h][k][3] = c1[2 * k + 1];
            mx[h][k] = fmaxf(fmaxf(p[h][k][0], p[h][k][1]), fmaxf(p[h][k][2], p[h][k][3]));
        }
    }
#pragma unroll
    for (int o = 1; o <= 2; o <<= 1)
#pragma unroll
        for (int h = 0; h < 2; h++)
#pragma unroll
            for (int k = 0; k < 2; k++) mx[h][k] = fmaxf(mx[h][k], __shfl_xor_sync(~0u, mx[h][k], o));
    const float L = 1.4426950408889634f;
    float pmin = 1.f;
#pragma unroll
    for (int h = 0; h < 2; h++)
#pragma unroll
        for (int k = 0; k < 2; k++) {
            const float m = -mx[h][k] * L;
            const float e0 = ex2(fmaf(p[h][k][0], L, m)), e1 = ex2(fmaf(p[h][k][1], L, m)), e2 = ex2(fmaf(p[h][k][2], L, m)), e3 = ex2(fmaf(p[h][k][3], L, m));
            const float p01 = e0 * e1, p23 = e2 * e3, pp = p01 * p23, r = rcp(pp), r01 = r * p23, r23 = r * p01;
            pmin = fminf(pmin, pp);
            out[h][k] = pack2(e0, e1); out[h][k + 2] = pack2(e2, e3);
            out[h][4 + k] = pack2(r01 * e1, r01 * e0); out[h][4 + k + 2] = pack2(r23 * e3, r23 * e2);
        }
    if (__builtin_expect(__any_sync(~0u, !(pmin > 1e-18f)), 0)) {
#pragma unroll
        for (int h = 0; h < 2; h++)
#pragma unroll
            for (int k = 0; k < 2; k++) {
                float m = fminf(fminf(p[h][k][0], p[h][k][1]), fminf(p[h][k][2], p[h][k][3]));
                m = fminf(m, __shfl_xor_sync(~0u, m, 1));
                m = fminf(m, __shfl_xor_sync(~0u, m, 2)) * L;
                out[h][4 + k] = pack2(ex2(fmaf(p[h][k][0], -L, m)), ex2(fmaf(p[h][k][1], -L, m)));
                out[h][4 + k + 2] = pack2(ex2(fmaf(p[h][k][2], -L, m)), ex2(fmaf(p[h][k][3], -L, m)));
            }
    }
}

__global__ void __launch_bounds__(512, 1)
fused_kernel(Scratch* __restrict__ scr, const bf16* __restrict__ logA, const bf16* __restrict__ Aim, const bf16* __restrict__ Cre,
             const bf16* __restrict__ Cim, const bf16* __restrict__ logdt, const bf16* __restrict__ Dskip, const bf16* __restrict__ wphi,
             const bf16* __restrict__ gatew, bf16* __restrict__ out,
             const __grid_constant__ CUtensorMap mx, const __grid_constant__ CUtensorMap mw, const __grid_constant__ CUtensorMap mwo) {
    extern __shared__ __align__(1024) uint8_t smem[];
    const uint32_t sb = s2u(smem);
    const int tid = threadIdx.x, warp = __shfl_sync(~0u, tid >> 5, 0), lane = tid & 31;
    const int g = lane >> 2, q = lane & 3, w4 = warp & 3;
    const int bi = blockIdx.x, bi_i = bi & 15, bi_j = bi >> 4;
    const uint32_t bar = sb + OFF_BAR;
    const int rot = (bi_j & 3) * 2, xkb = bi_j >> 2;
    auto load_stage = [&](int kb) {
        const uint32_t b = bar + 8 * (BAR_FULL + (kb & 3)), d = sb + (kb & 3) * SLOT;
        const int kc = ((kb + rot) & 7) * 64;
        mbar_expect(b, SLOT);
        tma2d(d, &mx, kc, bi_i * 128, b);
        tma3d(d + 16384, &mw, bi_j * 64, kc, 0, b);
    };

    const int ch = bi * 4 + w4;
    uint32_t pla = 0, pai = 0, pcr = 0, pci = 0, pdt = 0, pds = 0;
    if (warp >= 8) {
        const int pidx = ch * 64 + lane * 2 + (warp >= 12);
        pla = ld_nc((const uint32_t*)logA + pidx); pai = ld_nc((const uint32_t*)Aim + pidx);
        pcr = ld_nc((const uint32_t*)Cre + pidx); pci = ld_nc((const uint32_t*)Cim + pidx);
        pdt = ld_nc((const uint32_t*)logdt + (ch >> 1)); pds = ld_nc((const uint32_t*)Dskip + (ch >> 1));
    }
    unsigned done0 = ld_rlx(scr->done);
    if (tid == 0) {
        for (int s = 0; s < 4; s++) mbar_init(bar + 8 * (BAR_FULL + s), 1);
        asm volatile("fence.mbarrier_init.release.cluster;" ::: "memory");
        load_stage(0); load_stage(1); load_stage(2);
        STAMP(11);
    } else if (tid == 32) {
        if (sb & 1023) __trap();
        sts32(bar + OFF_CNT, 0);
        for (int s = 0; s < 4; s++) mbar_init(bar + 8 * (BAR_EMPTY + s), 8);
        mbar_init(bar + 8 * BAR_WPHI, 1); mbar_init(bar + 8 * BAR_WO, 1); mbar_init(bar + 8 * BAR_WO2, 1); mbar_init(bar + 8 * BAR_XT, 4);
        mbar_init(bar + 8 * BAR_DONE, 9); mbar_init(bar + 8 * BAR_KG, 4); mbar_init(bar + 8 * BAR_SP, 4); mbar_init(bar + 8 * BAR_PUB, 8);
        mbar_init(bar + 8 * BAR_KVF, 4); mbar_init(bar + 8 * BAR_UR, 4); mbar_init(bar + 8 * BAR_WR, 4); mbar_init(bar + 8 * BAR_PREP, 4); mbar_init(bar + 8 * BAR_KGA, 8); mbar_init(bar + 8 * BAR_SP2, 1);
        asm volatile("fence.mbarrier_init.release.cluster;" ::: "memory");
        mbar_expect(bar + 8 * BAR_WPHI, 3072);
        bulk_g2s(sb + OFF_GW, gatew, 1024, bar + 8 * BAR_WPHI);
        bulk_g2s(sb + OFF_WPHI, wphi + bi_j * 1024, 2048, bar + 8 * BAR_WPHI);
    } else if (tid == 64) {
        asm volatile("prefetch.tensormap [%0];" ::"l"(&mw) : "memory");
    }
    const uint32_t buf = sb + OFF_BUF + w4 * BUF_STRIDE, kb_ = sb + OFF_K + w4 * KT_BYTES;
    if ((warp >> 2) == 2) {
#pragma unroll
        for (int v = 0; v < 7; v++) if (v * 32 + lane < KT_BYTES / 16) sts128(kb_ + (v * 32 + lane) * 16, 0, 0, 0, 0);
    }
    __syncthreads();
    asm volatile("" : "+r"(pdt), "+r"(done0)::"memory");
    const unsigned epoch1 = (done0 >> 7) + 1u;
    const uint32_t tag = epoch1 & 1u;

    const int st = tid & 127;
    const uint32_t ub = sb + OFF_U + w4 * U_STRIDE + 256, spare = sb + (w4 < 2 ? OFF_SP0 : OFF_SP1) + (w4 & 1) * 4096;

    if (warp < 8) {
        const int wg = warp >> 2;
        if (warp == 0) STAMP(21);
        float acc[96];
        const int srow = warp * 16 + (lane & 15);
        const uint32_t srow_a = srow * 128;
        const int sx = srow & 7, shi = lane >> 4;
#pragma unroll
        for (int r = 0; r < 96; r++) acc[r] = 0.f;
        fence_regs<96>(acc);
        const uint64_t da0 = mkdesc(sb + wg * 8192, 16, 1024), db0 = mkdesc(sb + 16384, 8192, 1024);
        mbar_wait(bar + 8 * BAR_KGA, 0);
#pragma unroll 1
        for (int kb = 0; kb < 8; kb++) {
            const int s = kb & 3;
            const uint64_t da = da0 + s * (SLOT >> 4), db = db0 + s * (SLOT >> 4);
            if (warp == 0) STAMP(40 + kb);
            mbar_wait(bar + 8 * (BAR_FULL + s), kb >> 2);
            if (warp == 0) STAMP(32 + kb);
            wg_fence();
#pragma unroll
            for (int k = 0; k < 4; k++) wgmma192(acc, da + 2 * k, db + 128 * k);
            wg_commit();
            wg_wait<1>();
            if (lane == 0 && kb > 0) mbar_arrive(bar + 8 * (BAR_EMPTY + ((kb - 1) & 3)));
        }
        mbar_wait(bar + 8 * BAR_WPHI, 0);
        wg_wait<0>();
        fence_regs<96>(acc);
        if (lane == 0) mbar_arrive(bar + 8 * BAR_DONE);
        if (warp == 0) STAMP(1);
        uint32_t in[32], va[16];
#pragma unroll
        for (int r = 0; r < 16; r++) {
            in[r] = pack2(acc[32 + 2 * r], acc[32 + 2 * r + 1]);
            in[16 + r] = pack2(acc[2 * r], acc[2 * r + 1]);
            va[r] = pack2(acc[64 + 2 * r], acc[64 + 2 * r + 1]);
        }
        const uint32_t wphi_a = sb + OFF_WPHI + (lane & 15) * 32 + (lane >> 4) * 16;
        uint32_t pq[4][8];
#pragma unroll 1
        for (int it = 0; it < 4; it++) {
            hedgehog2(in, wphi_a + (it & 1) * 1024, pq + 2);
#pragma unroll
            for (int r = 0; r < 24; r++) in[r] = in[r + 8];
            if (it < 2) {
#pragma unroll
                for (int hs = 0; hs < 4; hs++) {
                    float c[4] = {0.f, 0.f, 0.f, 0.f};
                    uint32_t* o = pq[2 + (hs >> 1)] + 4 * (hs & 1);
                    mma16816(c, o[0], o[1], o[2], o[3], 0x3f803f80u, 0x3f803f80u);
                    const float r0 = rcp(c[0]), r1 = rcp(c[2]);
                    const uint32_t s0 = pack2(r0, r0), s1 = pack2(r1, r1);
                    o[0] = hmul2(o[0], s0); o[1] = hmul2(o[1], s1); o[2] = hmul2(o[2], s0); o[3] = hmul2(o[3], s1);
                }
                if (it == 0) mbar_wait(bar + 8 * BAR_DONE, 0);
                const uint32_t pt = sb + OFF_P + it * 16384 + srow_a, vt = sb + OFF_V + it * 16384 + srow_a;
#pragma unroll
                for (int hl = 0; hl < 2; hl++) {
                    stsm4(pt + (((4 * hl + shi) ^ sx) << 4), pq[2 + hl][0], pq[2 + hl][1], pq[2 + hl][2], pq[2 + hl][3]);
                    stsm4(pt + (((4 * hl + 2 + shi) ^ sx) << 4), pq[2 + hl][4], pq[2 + hl][5], pq[2 + hl][6], pq[2 + hl][7]);
                    stsm4(vt + (((2 * hl + shi) ^ sx) << 4), va[4 * hl], va[4 * hl + 1], va[4 * hl + 2], va[4 * hl + 3]);
                }
                if (lane < 16) sts128(vt + ((4 ^ sx) << 4), 0x3f803f80u, 0x3f803f80u, 0x3f803f80u, 0x3f803f80u);
#pragma unroll
                for (int r = 0; r < 8; r++) va[r] = va[r + 8];
            }
            if (it == 1) {
                asm volatile("fence.proxy.async.shared::cta;" ::: "memory");
                bar_named(1, 256);
                if (warp == 0) STAMP(2);
                float d[32];
                const uint64_t dv = mkdesc(sb + OFF_V + wg * 16384, 16, 1024), dp = mkdesc(sb + OFF_P + wg * 16384, 16, 1024);
                wg_fence();
#pragma unroll
                for (int k = 0; k < 8; k++) wgmma64_tt(d, dv + 128 * k, dp + 128 * k, k != 0);
                wg_commit();
                wg_wait<0>();
                fence_regs<32>(d);
                mbar_wait(bar + 8 * BAR_PREP, 0);
                uint4* kvp = scr->kvp + bi * 544 + wg * 272;
                if (w4 < 2) {
                    uint32_t e[16];
#pragma unroll
                    for (int r = 0; r < 16; r++) e[r] = __float_as_uint(w4 ? d[16 + r] : d[r]);
                    uint4* p = kvp + w4 * 136 + lane;
#pragma unroll
                    for (int ks = 0; ks < 2; ks++)
#pragma unroll
                        for (int nt = 0; nt < 2; nt++)
                            st_rlx128(p + (ks * 2 + nt) * 32, tag4(e[8 * ks + 2 * nt], e[8 * ks + 2 * nt + 1], e[8 * ks + 4 + 2 * nt], e[8 * ks + 4 + 2 * nt + 1], tag));
                } else if (w4 == 2 && lane < 4) {
#pragma unroll
                    for (int hl = 0; hl < 2; hl++)
#pragma unroll
                        for (int ks = 0; ks < 2; ks++)
                            st_rlx128(kvp + hl * 136 + 128 + ks * 4 + lane, tag4(__float_as_uint(d[16 * hl + 8 * ks]), __float_as_uint(d[16 * hl + 8 * ks + 1]),
                                                                                __float_as_uint(d[16 * hl + 8 * ks + 4]), __float_as_uint(d[16 * hl + 8 * ks + 5]), tag));
                }
                __syncwarp();
                if (lane == 0) mbar_arrive(bar + 8 * BAR_PUB);
                if (warp == 0) STAMP(3);
            }
            if (it == 2) {
#pragma unroll
                for (int r = 0; r < 8; r++) { pq[0][r] = pq[2][r]; pq[1][r] = pq[3][r]; }
            }
        }
        if (warp == 0) STAMP(4);
        asm volatile("setmaxnreg.inc.sync.aligned.u32 160;");
        {
            mbar_wait(bar + 8 * BAR_KVF, 0);
            uint4 kf[4][3];
#pragma unroll
            for (int hh = 0; hh < 4; hh++) {
                const uint32_t a = sb + OFF_KVF + hh * 1088;
                kf[hh][0] = lds128(a + lane * 32); kf[hh][1] = lds128(a + lane * 32 + 16); kf[hh][2] = lds128(a + 1024 + q * 16);
            }
            if (warp == 0) STAMP(5);
            uint4 own[4];
#pragma unroll
            for (int hh = 0; hh < 4; hh++) {
                float c[6][4];
#pragma unroll
                for (int t = 0; t < 6; t++) { c[t][0] = c[t][1] = c[t][2] = c[t][3] = 0.f; }
                const uint32_t* a = pq[hh];
                const bool od = g & 1;
                mma16816(c[0], a[0], a[1], a[2], a[3], od ? 0x3f803f80u : kf[hh][2].x, od ? 0x3f803f80u : kf[hh][2].y);
                mma16816(c[1], a[4], a[5], a[6], a[7], od ? 0x3f803f80u : kf[hh][2].z, od ? 0x3f803f80u : kf[hh][2].w);
                mma16816(c[2], a[0], a[1], a[2], a[3], kf[hh][0].x, kf[hh][0].y);
                mma16816(c[3], a[0], a[1], a[2], a[3], kf[hh][0].z, kf[hh][0].w);
                mma16816(c[4], a[4], a[5], a[6], a[7], kf[hh][1].x, kf[hh][1].y);
                mma16816(c[5], a[4], a[5], a[6], a[7], kf[hh][1].z, kf[hh][1].w);
                uint32_t w[4];
#pragma unroll
                for (int k = 0; k < 2; k++) {
                    const float rho = c[0][2 * k + 1] * rcp(c[1][2 * k + 1]);
                    const float r = rcp(fmaf(c[0][2 * k + 1], 1e-6f, fmaf(rho, c[1][2 * k], c[0][2 * k]))), rr = r * rho;
                    w[k] = pack2(fmaf(c[4][2 * k], rr, c[2][2 * k] * r), fmaf(c[4][2 * k + 1], rr, c[2][2 * k + 1] * r));
                    w[2 + k] = pack2(fmaf(c[5][2 * k], rr, c[3][2 * k] * r), fmaf(c[5][2 * k + 1], rr, c[3][2 * k + 1] * r));
                }
                own[hh] = tag4(w[0], w[1], w[2], w[3], tag);
            }
            uint4* og = scr->o + ((bi_i * 8 + warp) * 32 + bi_j * 4) * 32 + lane;
#pragma unroll
            for (int hh = 0; hh < 4; hh++) st_rlx128(og + hh * 32, own[hh]);
        }
        if (warp == 0) STAMP(6);
        float oc[64];
        const int slab = bi_i * 8 + (bi_j >> 2) * 4 + w4;
        const uint8_t* yb = (const uint8_t*)scr->y + (size_t)((bi_j & 3) * 32 + wg * 16 + (q >> 1)) * 16384 + slab * 128 + g * 16 + (q & 1) * 8;
        const unsigned* gp = scr->g + (slab * 8 + (g >> 1)) * 8 + (g & 1) * 4;
        uint2 yv[8]; unsigned g0, g1;
        {
            const uint4* osrc = scr->o + (slab * 32 + wg * 16) * 32 + lane;
            uint4 fr[16];
            const unsigned* probe = (const unsigned*)(osrc - lane + ((lane & 3) * 4 + 3) * 32 + 31) + 2;
            {
                unsigned miss = ~0u;
                int n = 0;
#pragma unroll
                for (int s = 0; s < 4; s++) {
#pragma unroll 1
                    while ((miss >> s) & 1) { miss = __ballot_sync(~0u, (ld_rlx(probe) ^ tag) & 1); if (++n > SPIN_LIMIT) break; }
#pragma unroll
                    for (int k = 4 * s; k < 4 * s + 4; k++) fr[k] = ld_rlx128(osrc + k * 32);
                }
            }
            if (warp == 0) STAMP(14);
            mbar_wait(bar + 8 * (wg ? BAR_WO2 : BAR_WO), 0);
            const uint64_t dw = mkdesc(sb + wg * 2 * SLOT, wg ? 32768 : SLOT, 1024);
#pragma unroll
            for (int s = 0; s < 4; s++) {
                int n = 0;
#pragma unroll 1
                while (__builtin_expect(__any_sync(~0u, (bad4(fr[4 * s], tag) | bad4(fr[4 * s + 1], tag) | bad4(fr[4 * s + 2], tag) | bad4(fr[4 * s + 3], tag)) & 1), 0)) {
#pragma unroll
                    for (int k = 4 * s; k < 4 * s + 4; k++) fr[k] = ld_rlx128(osrc + k * 32);
                    if (++n > SPIN_LIMIT) break;
                }
                wg_fence();
#pragma unroll
                for (int hh = 0; hh < 4; hh++) wgmma128_rs(oc, fr[4 * s + hh], dw + 128 * (4 * s + hh), (s | hh) != 0);
                wg_commit();
                if (s == 1) {
                    wg_wait<1>();
#pragma unroll
                    for (int nt = 0; nt < 8; nt++) yv[nt] = ld_rlx64(yb + nt * 32768);
                    g0 = ld_rlx(gp); g1 = ld_rlx(gp + 32);
                }
            }
            if (warp == 0) STAMP(7);
            {
                const unsigned* yprobe = scr->yflag + ((bi_j & 3) * 32 + wg * 16 + (lane & 15)) * 8;
                int n = 0;
#pragma unroll 1
                while (true) {
                    uint32_t bad = (g0 ^ tag) | (g1 ^ tag);
#pragma unroll
                    for (int nt = 0; nt < 8; nt++) bad |= yv[nt].x ^ tag;
                    if (!__any_sync(~0u, bad & 1)) break;
#pragma unroll 1
                    while (__any_sync(~0u, (ld_rlx(yprobe) ^ tag) & 1)) { if (++n > SPIN_LIMIT) break; }
#pragma unroll
                    for (int nt = 0; nt < 8; nt++) yv[nt] = ld_rlx64(yb + nt * 32768);
                    g0 = ld_rlx(gp); g1 = ld_rlx(gp + 32);
                    if (++n > SPIN_LIMIT) break;
                }
            }
            if (warp == 0) STAMP(28);
            wg_wait<0>();
            fence_regs<64>(oc);
        }
        {
            bar_named(3 + wg, 128);
            const uint32_t xw = sb + wg * 2 * SLOT + (tid & 127) * 16, xr = sb + (wg ^ 1) * 2 * SLOT + (tid & 127) * 16;
#pragma unroll
            for (int r = 0; r < 8; r++) {
                const float* o = oc + 4 * r;
                sts128(xw + r * 2048, __float_as_uint(wg ? o[0] : o[32]), __float_as_uint(wg ? o[1] : o[33]), __float_as_uint(wg ? o[2] : o[34]), __float_as_uint(wg ? o[3] : o[35]));
            }
#pragma unroll
            for (int r = 0; r < 32; r++) oc[r] = wg ? oc[32 + r] : oc[r];
            bar_named(1, 256);
            if (warp == 0) STAMP(8);
            const float ga = bf_hi(g0), gb = bf_hi(g1);
            const float ha = bf_round(1.0f - ga), hb = bf_round(1.0f - gb);
            uint32_t w[8][2];
#pragma unroll
            for (int nt = 0; nt < 8; nt++) {
                const uint4 p = lds128(xr + nt * 2048);
                w[nt][0] = pack2(fmaf(ga, oc[4 * nt] + __uint_as_float(p.x), ha * bf_lo(yv[nt].x)), fmaf(ga, oc[4 * nt + 1] + __uint_as_float(p.y), ha * bf_hi(yv[nt].x)));
                w[nt][1] = pack2(fmaf(gb, oc[4 * nt + 2] + __uint_as_float(p.z), hb * bf_lo(yv[nt].y)), fmaf(gb, oc[4 * nt + 3] + __uint_as_float(p.w), hb * bf_hi(yv[nt].y)));
            }
            const uint32_t ob = sb + wg * 2 * SLOT + 16384 + w4 * 2048;
#pragma unroll
            for (int nt = 0; nt < 8; nt += 2)
                stsm4(ob + (lane & 15) * 128 + (((nt + shi) ^ (lane & 7)) << 4), w[nt][0], w[nt][1], w[nt + 1][0], w[nt + 1][1]);
            __syncwarp();
            bf16* op = out + (size_t)(slab * 16) * 512 + (bi_j & 3) * 128 + wg * 64 + (lane & 7) * 8;
#pragma unroll
            for (int it = 0; it < 4; it++) {
                const int r = it * 4 + (lane >> 3);
                uint4 v = lds128(ob + r * 128 + (((lane & 7) ^ (r & 7)) << 4));
                *(uint4*)(op + r * 512) = v;
            }
        }
        if (warp == 0) STAMP(10);
    } else {
        const bool hw = warp >= 12;
        const int qq = (bi_i & 2) + ((lane >> 1) & 1);
        uint2* kvf_h = (uint2*)(scr->kvf + (bi_j * 4 + (bi_i >> 2)) * 68);
        auto windows = [&](int rhi, int rlo) {
#pragma unroll 1
            for (int rho = rhi; rho >= rlo; rho--) {
                const int ci = lane + 32 * rho;
                uint4 e4[4];
#pragma unroll
                for (int v = 0; v < 4; v++) { const int cc = ci - 3 + v; e4[v] = lds128(ub + ((cc ^ ((cc >> 3) & 1)) << 4)); }
                float S[29];
                const uint32_t* ew = (const uint32_t*)e4;
                S[3] = 0.f;
#pragma unroll
                for (int k = 4; k <= 28; k++) S[k] = S[k - 1] + ((k & 1) ? bf_hi(ew[k >> 1]) : bf_lo(ew[k >> 1]));
                auto win = [&](int lo, int hi, uint32_t a) {
                    sts128(a, pack2(S[hi] - S[lo - 1], S[hi + 1] - S[lo]), pack2(S[hi + 2] - S[lo + 1], S[hi + 3] - S[lo + 2]),
                           pack2(S[hi + 4] - S[lo + 3], S[hi + 5] - S[lo + 4]), pack2(S[hi + 6] - S[lo + 5], S[hi + 7] - S[lo + 6]));
                };
                win(14, 18, buf + W5_OFF + 16 + ci * 16); win(19, 21, buf + W3_OFF + 16 + ci * 16);
                if (rho < 4) {
                    const uint32_t sw = (ci ^ ((ci >> 3) & 1)) << 4;
                    win(4, 12, buf + W9_OFF + sw); win(13, 19, spare + sw); win(20, 21, spare + 2048 + sw);
                }
            }
        };
        float kc[24];
#pragma unroll
        for (int t = 0; t < 24; t++) kc[t] = 0.f;
        const float dt = bf_round(expf((ch & 1) ? bf_hi(pdt) : bf_lo(pdt)));
#pragma unroll 1
        for (int it = 0; it < 2; it++) {
            const uint32_t hstg = sb + (it == 0 ? 3 : 1) * SLOT + w4 * 7296;
            const uint32_t stg = hw ? hstg : (it == 0 ? buf : sb + w4 * 7296);
            if (it == 1) {
                if (hw) {
                    mbar_wait(bar + 8 * (BAR_FULL + xkb), 0);
#pragma unroll 1
                    for (int hf = 0; hf < 2; hf++) {
                        const int r = w4 * 32 + hf * 16 + (lane & 15);
                        uint32_t* xt = (uint32_t*)scr->xt + ((xkb + rot) * 16 + (g >> 2)) * 4096 + (bi_i * 16 + w4 * 4 + hf * 2) * 16 + (g & 3) * 4 + q;
#pragma unroll
                        for (int cb = 0; cb < 8; cb += 2) {
                            uint32_t v[4];
                            ldsm4t(v, sb + xkb * SLOT + r * 128 + (((cb + (lane >> 4)) ^ (r & 7)) << 4));
                            xt[cb * 8192] = v[0]; xt[cb * 8192 + 16] = v[1]; xt[cb * 8192 + 8192] = v[2]; xt[cb * 8192 + 8192 + 16] = v[3];
                        }
                    }
                    __syncwarp();
                    if (lane == 0) mbar_arrive(bar + 8 * BAR_XT);
                    if (warp == 12) {
                        STAMP(26);
                        mbar_wait(bar + 8 * BAR_XT, 0);
                        if (lane == 0) asm volatile("red.release.gpu.global.add.u32 [%0],8;" ::"l"(scr->xcnt + (xkb + rot) * 32) : "memory");
                        __syncwarp();
                        STAMP(27);
                    }
                    {
                        const uint32_t old = tag ^ 1u;
                        const uint4 z4 = make_uint4(old, 0, old, 0);
#pragma unroll
                        for (int v = 0; v < 5; v++) if (v < 4 || st < 32) st_rlx128(scr->kvp + bi * 544 + v * 128 + st, z4);
                        if (st < 16) st_rlx128(scr->o + ((bi_i * 8 + (st >> 1)) * 32 + bi_j * 4 + 3) * 32 + 30 + (st & 1), z4);
                        if (lane < 8) st_rlx64(kvf_h + ((bi_i & 3) * 8 + w4 * 2 + (lane & 1)) * 4 + (lane >> 1), old, 0);
                        if (st < 4 && !(bi_i & 1)) st_rlx64(kvf_h + (64 + qq) * 2 + (lane & 1), old, 0);
                        __syncwarp();
                        if (lane == 0) mbar_arrive(bar + 8 * BAR_PREP);
                    }
                    int n = 0;
#pragma unroll 1
                    while (__any_sync(~0u, (int)(ld_acq(scr->xcnt + bi_j * 32) - (epoch1 << 7)) < 0)) { if (++n > SPIN_LIMIT) break; }
                    if (warp == 12) STAMP(15);
                    uint4 ur[8];
#pragma unroll
                    for (int v = 0; v < 8; v++) ur[v] = __ldcg(scr->xt + bi * 1024 + st + 128 * v);
                    if (lane < 16) sts128(ub - 256 + lane * 16, 0, 0, 0, 0);
                    if (lane < 2) sts128(buf + lane * W3_OFF, 0, 0, 0, 0);
#pragma unroll
                    for (int v = 0; v < 8; v++) {
                        const int ci = (st >> 2) + 32 * v;
                        sts128(sb + OFF_U + (st & 3) * U_STRIDE + 256 + ((ci ^ ((ci >> 3) & 1)) << 4), ur[v].x, ur[v].y, ur[v].z, ur[v].w);
                    }
                    __syncwarp();
                    if (lane == 0) mbar_arrive(bar + 8 * BAR_UR);
                    mbar_wait(bar + 8 * BAR_UR, 0);
                    if (warp == 12) STAMP(16);
                    windows(5, 4);
                } else if (warp == 8) {
                    const int row = bi_j * 16 + (lane >> 1), half = lane & 1;
                    unsigned* gp = scr->g + (bi_i * 64 + bi_j * 8) * 8 + lane * 2;
                    st_rlx64(gp, tag ^ 1u, tag ^ 1u);
                    if (lane < 8) st_rlx32(scr->yflag + bi * 8 + lane, tag ^ 1u);
                    float gs0 = 0.f, gs1 = 0.f;
                    mbar_wait(bar + 8 * BAR_WPHI, 0);
#pragma unroll 1
                    for (int kb = 0; kb < 8; kb++) {
                        const int s = kb & 3;
                        mbar_wait(bar + 8 * (BAR_FULL + s), kb >> 2);
#pragma unroll
                        for (int c = 0; c < 4; c++) {
                            const uint4 xv = lds128(sb + s * SLOT + row * 128 + (((half * 4 + c) ^ (row & 7)) << 4));
                            const uint4 gw = lds128(sb + OFF_GW + ((kb + rot) & 7) * 128 + half * 64 + c * 16);
                            const uint32_t p0 = hmul2(xv.x, gw.x), p1 = hmul2(xv.y, gw.y), p2 = hmul2(xv.z, gw.z), p3 = hmul2(xv.w, gw.w);
                            gs0 += (bf_lo(p0) + bf_lo(p1)) + (bf_lo(p2) + bf_lo(p3));
                            gs1 += (bf_hi(p0) + bf_hi(p1)) + (bf_hi(p2) + bf_hi(p3));
                        }
                        if (kb < 4 || kb == 6) {
                            mbar_wait(bar + 8 * (BAR_EMPTY + (kb < 4 ? s : 1)), kb >> 2);
                            if (kb == xkb) mbar_wait(bar + 8 * BAR_XT, 0);
                            if (lane == 0) {
                                STAMP(48 + kb);
                                if (kb < 4) load_stage(kb + 4);
                                else mbar_arrive(bar + 8 * BAR_SP2);
                            }
                        }
                        __syncwarp();
                    }
                    if (lane == 0) mbar_arrive(bar + 8 * BAR_DONE);
                    float gs = gs0 + gs1;
                    gs += __shfl_xor_sync(~0u, gs, 1);
                    const uint32_t gv = __float_as_uint(bf_round(rcp(1.0f + ex2(-1.4426950408889634f * bf_round(gs))))) | tag;
                    st_rlx64(gp, gv, gv);
                }
                mbar_wait(bar + 8 * BAR_SP2, 0);
            }
            const int sh = it * 16;
            auto pick = [&](uint32_t v) { return __uint_as_float((v >> sh) << 16); };
            const float ea = bf_round(expf(pick(pla)));
            const float arl = (-ea * dt) * 1.4426950408889634f, ait = (pick(pai) * dt) * 0.15915494309189535f;
            cf C2; C2.re = 2.0f * (pick(pcr) * dt); C2.im = 2.0f * (pick(pci) * dt);
            const cf z1 = cexp_p(arl, ait, 1.0f), z128 = cexp_p(arl, ait, 128.0f);
            cf z8 = cexp_p(arl, ait, 8.0f); z8.im = -z8.im;
            const uint32_t lp = stg + lane * 4;
            auto put = [&](int row, const cf& v) { sts32((lp ^ ((row & 7) << 4)) + row * 128, pack2(v.re, v.im)); };
            {
                const cf z16 = cmul(z8, z8);
                cf e; e.re = 1.f; e.im = 0.f;
                cf o = z8;
                put(0, e); put(1, o);
                e = z16; put(2, e);
#pragma unroll
                for (int b = 3; b < 16; b += 2) {
                    o = cmul(o, z16); put(b, o);
                    if (b + 1 < 16) { e = cmul(e, z16); put(b + 1, e); }
                }
            }
            cf h[8];
            h[0] = C2; put(16, h[0]);
            {
                const cf z2 = cmul(z1, z1);
                h[1] = cmul(h[0], z1);
#pragma unroll
                for (int r = 2; r < 8; r++) h[r] = cmul(h[r - 2], z2);
#pragma unroll
                for (int r = 1; r < 8; r++) put(16 + r, h[r]);
            }
#pragma unroll
            for (int r = 0; r < 8; r++) { h[r] = cmul(h[r], z128); put(24 + r, h[r]); }
#pragma unroll
            for (int al = 0; al < 2; al++)
#pragma unroll
                for (int r = 0; r < 4; r++) { h[2 * r] = cmul(h[2 * r], z128); put(32 + al * 4 + r, h[2 * r]); }
#pragma unroll
            for (int al = 0; al < 4; al++)
#pragma unroll
                for (int r = 0; r < 2; r++) { h[4 * r] = cmul(h[4 * r], z128); put(40 + al * 2 + r, h[4 * r]); }
#pragma unroll
            for (int al = 0; al < 9; al++) { h[0] = cmul(h[0], z128); put(48 + al, h[0]); }
            __syncwarp();
            if (it == 1) mbar_wait(bar + 8 * BAR_DONE, 0);
            const int lr = lane & 7, lm = lane >> 3;
#pragma unroll
            for (int kp = 0; kp < 2; kp++) {
                uint32_t a0[4], a1[4];
                ldsm4(a0, stg + ((lm & 1) * 8 + lr) * 128 + (((4 * kp + (lm >> 1)) ^ lr) << 4));
                ldsm4(a1, stg + ((lm & 1) * 8 + lr) * 128 + (((4 * kp + 2 + (lm >> 1)) ^ lr) << 4));
#pragma unroll
                for (int t = 0; t < 6; t++) {
                    uint32_t b[4];
                    ldsm4(b, stg + (16 + 8 * t + lr) * 128 + (((4 * kp + lm) ^ lr) << 4));
                    mma16816(kc + 4 * t, a0[0], a0[1], a0[2], a0[3], b[0], b[1]);
                    mma16816(kc + 4 * t, a1[0], a1[1], a1[2], a1[3], b[2], b[3]);
                }
            }
            __syncwarp();
            if (it == 0) {
                if (lane == 0) mbar_arrive(bar + 8 * BAR_KGA);
                if (hw) {
                    asm volatile("fence.proxy.async.shared::cta;" ::: "memory");
                    bar_named(5, 128);
                    if (st == 0) load_stage(3);
                    if (warp == 12) STAMP(22);
                }
            } else if (hw) {
#pragma unroll
                for (int t = 0; t < 6; t++)
                    sts128(stg + (t * 32 + lane) * 16, __float_as_uint(kc[4 * t]), __float_as_uint(kc[4 * t + 1]), __float_as_uint(kc[4 * t + 2]), __float_as_uint(kc[4 * t + 3]));
                asm volatile("fence.proxy.async.shared::cta;" ::: "memory");
                __syncwarp();
                if (lane == 0) mbar_arrive(bar + 8 * BAR_KG);
            } else {
                mbar_wait(bar + 8 * BAR_KG, 0);
#pragma unroll
                for (int t = 0; t < 6; t++) {
                    const uint4 v = lds128(hstg + (t * 32 + lane) * 16);
                    kc[4 * t] += __uint_as_float(v.x); kc[4 * t + 1] += __uint_as_float(v.y); kc[4 * t + 2] += __uint_as_float(v.z); kc[4 * t + 3] += __uint_as_float(v.w);
                }
                asm volatile("fence.proxy.async.shared::cta;" ::: "memory");
                __syncwarp();
                if (lane == 0) mbar_arrive(bar + 8 * BAR_SP);
            }
        }
        if (!hw) {
            if (warp == 8) STAMP(17);
            if (lane == 0) kc[4 * 0 + 0] += ((ch & 1) ? bf_hi(pds) : bf_lo(pds));
            const uint32_t k1024 = __shfl_sync(~0u, pack2(kc[4 * 4 + 0], 0.f), 0);
#pragma unroll
            for (int i = 0; i < 2; i++) {
                const int be = g + 8 * i;
#pragma unroll
                for (int t = 0; t < 2; t++) {
                    const uint32_t a = kb_ + (KW_D + 128 * t + 8 * be + 2 * q) * 4;
                    const uint32_t w = pack2(kc[4 * t + 2 * i + 1], kc[4 * t + 2 * i]);
                    sts32(a + 4, w); sts16(a, w >> 16); sts16(a + 10, w);
                }
                {
                    const int p = 256 + 128 * (q >> 1) + 8 * be + 4 * (q & 1);
                    const uint32_t a = kb_ + (KW_D + p) * 4;
                    const uint32_t w = pack2(kc[4 * 2 + 2 * i + 1], kc[4 * 2 + 2 * i]);
                    const uint32_t aa = (w >> 16) | (w & 0xffff0000u);
                    if (p != 256) { sts16(a - 4, aa); sts32(a, aa); } else sts16(a, aa);
                    sts32(a + 4, aa); sts32(a + 8, w); sts16(a + 14, w);
                }
                {
                    const int k = 64 + 16 * q + be;
                    const uint32_t w = pack2(kc[4 * 3 + 2 * i], kc[4 * 3 + 2 * i + 1]);
                    if (k != 64) sts16(kb_ + (KW_2 + ((k - 1) >> 1) - 24) * 4 + (k & 1) * 2, w);
                    else {
                        const uint32_t a = kb_ + (KW_D + 511) * 4, aa = (w << 16) | (w & 0xffffu);
                        sts16(a, w); sts32(a + 4, aa); sts32(a + 8, aa); sts32(a + 12, aa); sts16(a + 18, w);
                    }
                    sts16(kb_ + (KW_2 + 48 + (k >> 1) - 24) * 4 + ((k & 1) ^ 1) * 2, w >> 16);
                }
#pragma unroll
                for (int b = 0; b < 2; b++) {
                    const int k = 64 + 8 * (2 * q + b) + (be >> 1);
                    const uint32_t w = pack2(kc[4 * 4 + 2 * i + b], 0.f);
                    if (!(be & 1) && k == 64) sts16(kb_ + (KW_2 + 63 - 24) * 4, w);
                    else {
                        const uint32_t a = kb_ + (KW_3 + ((be & 1) ? 80 + k : k - 1) - 48) * 4;
                        sts16(a, w);
                        if (!((be & 1) && k == 127)) sts16(a + 6, w);
                    }
                }
            }
            if (lane == 0) sts16(kb_ + (KW_3 + 127 - 48) * 4, pack2(kc[4 * 5 + 0], 0.f));
            __syncwarp();
            mbar_wait(bar + 8 * BAR_UR, 0);
            if (warp == 8) STAMP(23);
            float y[16][4];
#pragma unroll
            for (int nt = 0; nt < 16; nt++) { y[nt][0] = y[nt][1] = y[nt][2] = y[nt][3] = 0.f; }
            {
                uint32_t Bp[32], A[5][3];
                auto uaddr = [&](int rho) { const int R0 = (lane >> 4) * 8 + (lane & 7) - rho; return ub + (((2 * R0 + ((lane >> 3) & 1)) ^ ((R0 >> 2) & 1)) << 4); };
                const uint32_t kd = kb_ + (KW_D + g - 2 * q) * 4;
                auto lda = [&](int rho) {
#pragma unroll
                    for (int ga = 0; ga < 5; ga++) {
                        const uint32_t a = kd + (ga < 4 ? rho : (rho & 1)) * 64 + ga * 512;
                        A[ga][0] = lds32(a); A[ga][1] = lds32(a + 32); A[ga][2] = lds32(a - 32);
                    }
                };
                {
                    const uint32_t a = uaddr(0);
#pragma unroll
                    for (int p = 0; p < 8; p++) ldsm4(Bp + 4 * p, a + p * 512);
                }
#pragma unroll 1
                for (int rho = 0; rho < 8; rho++) {
                    lda(rho);
                    if (rho < 2) {
#pragma unroll
                        for (int nt = 4; nt < 16; nt++) mma16816(y[nt], A[4][0], A[4][1], A[4][2], A[4][0], Bp[2 * (nt - 4)], Bp[2 * (nt - 4) + 1]);
                    }
#pragma unroll
                    for (int ga = 0; ga < 3; ga++)
#pragma unroll
                        for (int nt = 15; nt >= ga; nt--) mma16816(y[nt], A[ga][0], A[ga][1], A[ga][2], A[ga][0], Bp[2 * (nt - ga)], Bp[2 * (nt - ga) + 1]);
                    const uint32_t an = uaddr(rho + 1);
                    ldsm4(Bp + 28, an + 7 * 512);
#pragma unroll
                    for (int nt = 15; nt >= 3; nt--) {
                        mma16816(y[nt], A[3][0], A[3][1], A[3][2], A[3][0], Bp[2 * (nt - 3)], Bp[2 * (nt - 3) + 1]);
                        if (nt & 1) ldsm4(Bp + 2 * (nt - 3), an + ((nt - 3) >> 1) * 512);
                    }
                }
            }
            if (warp == 8) STAMP(18);
            mbar_wait(bar + 8 * BAR_WR, 0);
#pragma unroll 1
            for (int ph = 0; ph < 2; ph++) {
                uint32_t B[5][2];
                const uint32_t ka = kb_ + (KW_2 + ph * 48 + 8 + g - q) * 4;
#pragma unroll
                for (int dd = 0; dd < 5; dd++) { B[dd][0] = lds32(ka + dd * 32); B[dd][1] = lds32(ka + dd * 32 - 16); }
                const uint32_t wa = buf + ph * W3_OFF + ((lane & 7) + ((lane >> 3) & 1) + (lane >> 4) * 8) * 16;
#pragma unroll
                for (int s = 0; s < 12; s++) {
                    uint32_t A[4];
                    ldsm4t(A, wa + s * 256);
#pragma unroll
                    for (int dd = 0; dd < 5; dd++)
                        if (s + 4 + dd < 16) mma16816(y[s + 4 + dd], A[0], A[1], A[2], A[3], B[dd][0], B[dd][1]);
                }
            }
            {
                const int ap = (lane & 7) + (lane >> 4) * 8;
                const uint32_t loff = ((2 * ap + ((lane >> 3) & 1)) ^ ((ap >> 2) & 1)) << 4;
#pragma unroll 1
                for (int ph = 0; ph < 2; ph++) {
                    uint32_t B[8][2];
                    const uint32_t wb = (ph ? spare : buf + W9_OFF) + loff;
                    const uint32_t ka = kb_ + (KW_3 + ph * 80 + 16 + g - 2 * q) * 4;
#pragma unroll
                    for (int dd = 0; dd < 8; dd++) { B[dd][0] = lds32(ka + dd * 32); B[dd][1] = lds32(ka + dd * 32 - 32); }
#pragma unroll
                    for (int s = 0; s < 4; s++) {
                        uint32_t A[4];
                        ldsm4t(A, wb + s * 512);
#pragma unroll
                        for (int dd = 0; dd < 8; dd++)
                            if (8 + 2 * s + dd < 16) mma16816(y[8 + 2 * s + dd], A[0], A[1], A[2], A[3], B[dd][0], B[dd][1]);
                    }
                }
                const uint32_t idw = (g == 2 * q) ? k1024 : ((g == 2 * q + 1) ? (k1024 << 16) : 0u);
#pragma unroll
                for (int s = 0; s < 4; s++) {
                    uint32_t A[4];
                    ldsm4t(A, spare + 2048 + loff + s * 512);
                    mma16816(y[8 + 2 * s], A[0], A[1], A[2], A[3], idw, 0u);
                    mma16816(y[9 + 2 * s], A[0], A[1], A[2], A[3], 0u, idw);
                }
            }
            __syncwarp();
            if (warp == 8) STAMP(19);
#pragma unroll
            for (int nt = 0; nt < 16; nt++)
#pragma unroll
                for (int b = 0; b < 2; b++) sts32(buf + ((8 * nt + 2 * q + b) * 8 + g) * 4, pack2(y[nt][b], y[nt][2 + b]));
            bar_named(2, 128);
            uint4* yp = scr->y + bi * 1024 + st;
#pragma unroll
            for (int v = 0; v < 8; v++) {
                const uint32_t a = sb + OFF_BUF + (st + 128 * v) * 4;
                const uint32_t w0 = lds32(a), w1 = lds32(a + BUF_STRIDE), w2 = lds32(a + 2 * BUF_STRIDE), w3 = lds32(a + 3 * BUF_STRIDE);
                st_rlx128(yp + v * 128, tag4(__byte_perm(w0, w1, 0x5410), __byte_perm(w0, w1, 0x7632), __byte_perm(w2, w3, 0x5410), __byte_perm(w2, w3, 0x7632), tag));
            }
            if (st < 8) st_rlx32(scr->yflag + bi * 8 + st, tag);
            if (warp == 8) STAMP(20);
        } else {
            asm volatile("setmaxnreg.dec.sync.aligned.u32 64;");
            if (warp == 13) {
                mbar_wait(bar + 8 * BAR_SP, 0);
                if (lane == 0) {
                    mbar_expect(bar + 8 * BAR_WO, 65536);
                    tma2d(sb, &mwo, (bi_j & 3) * 128, 0, bar + 8 * BAR_WO);
                    tma2d(sb + SLOT, &mwo, (bi_j & 3) * 128 + 64, 0, bar + 8 * BAR_WO);
                }
                __syncwarp();
            }
            windows(3, 0);
            __syncwarp();
            if (lane == 0) mbar_arrive(bar + 8 * BAR_WR);
            if (warp == 12) STAMP(24);
            mbar_wait(bar + 8 * BAR_PUB, 0);
            if (warp == 12) STAMP(12);
#pragma unroll 1
            for (int zw = 0; zw < ((st < 32 && !(bi_i & 1)) ? 2 : 1); zw++) {
                const int kvf_n = zw ? 4 : 8;
                uint2* kvf_dst = kvf_h + (zw ? (64 + qq) * 2 + (lane & 1) : ((bi_i & 3) * 8 + w4 * 2 + (lane & 1)) * 4 + (lane >> 1));
                const uint4* src = scr->kvp + bi_j * (16 * 544) + (bi_i >> 2) * 136 +
                                   (zw ? (lane >> 2) * (2 * 544) + 128 + (lane & 1) * 4 + qq
                                       : (lane >> 3) * (4 * 544) + ((lane >> 1) & 3) * 32 + (bi_i & 3) * 8 + w4 * 2 + (lane & 1));
                const int s23 = zw ? 0 : 2 * 544;
                uint4 v[4];
                int n = 0;
#pragma unroll 1
                while (true) {
                    v[0] = ld_rlx128(src); v[1] = ld_rlx128(src + 544); v[2] = ld_rlx128(src + s23); v[3] = ld_rlx128(src + s23 + 544);
                    if (!__any_sync(~0u, (bad4(v[0], tag) | bad4(v[1], tag) | bad4(v[2], tag) | bad4(v[3], tag)) & 1)) break;
                    if (++n > SPIN_LIMIT) break;
                }
                float f[4];
                f[0] = __uint_as_float(v[2].x) + __uint_as_float(v[3].x); f[1] = __uint_as_float(v[2].y) + __uint_as_float(v[3].y);
                f[2] = __uint_as_float(v[2].z) + __uint_as_float(v[3].z); f[3] = __uint_as_float(v[2].w) + __uint_as_float(v[3].w);
                float e0 = __uint_as_float(v[0].x) + __uint_as_float(v[1].x), e1 = __uint_as_float(v[0].y) + __uint_as_float(v[1].y);
                float e2 = __uint_as_float(v[0].z) + __uint_as_float(v[1].z), e3 = __uint_as_float(v[0].w) + __uint_as_float(v[1].w);
                if (zw) {
                    e0 = __shfl_xor_sync(~0u, f[0], 4); e1 = __shfl_xor_sync(~0u, f[1], 4);
                    e2 = __shfl_xor_sync(~0u, f[2], 4); e3 = __shfl_xor_sync(~0u, f[3], 4);
                }
                f[0] += e0; f[1] += e1; f[2] += e2; f[3] += e3;
#pragma unroll
                for (int o = 8; o <= 16; o <<= 1)
#pragma unroll
                    for (int r = 0; r < 4; r++) f[r] += __shfl_xor_sync(~0u, f[r], o);
                if (lane < kvf_n) st_rlx64(kvf_dst, tagw(pack2(f[0], f[1]), tag), pack2(f[2], f[3]));
            }
            if (warp == 12) STAMP(13);
            if (st == 32) {
                mbar_expect(bar + 8 * BAR_WO2, 65536);
                tma2d(sb + OFF_P, &mwo, (bi_j & 3) * 128, 256, bar + 8 * BAR_WO2);
                tma2d(sb + OFF_V, &mwo, (bi_j & 3) * 128 + 64, 256, bar + 8 * BAR_WO2);
            }
            __syncwarp();
            {
                const uint4* kp = scr->kvf + bi_j * 272 + st;
                uint4 v0, v1, v2;
                int n = 0;
#pragma unroll 1
                while (true) {
                    v0 = ld_rlx128(kp); v1 = ld_rlx128(kp + 128); v2 = ld_rlx128(kp + (st < 16 ? 256 : 0));
                    if (!__any_sync(~0u, (bad4(v0, tag) | bad4(v1, tag) | bad4(v2, tag)) & 1)) break;
                    if (++n > SPIN_LIMIT) break;
                }
                sts128(sb + OFF_KVF + st * 16, v0.x, v0.y, v0.z, v0.w);
                sts128(sb + OFF_KVF + 2048 + st * 16, v1.x, v1.y, v1.z, v1.w);
                if (st < 16) sts128(sb + OFF_KVF + 4096 + st * 16, v2.x, v2.y, v2.z, v2.w);
                __syncwarp();
                if (lane == 0) mbar_arrive(bar + 8 * BAR_KVF);
            }
            if (warp == 12) STAMP(25);
        }
    }
    __syncwarp();
    if (lane == 0) {
        unsigned old;
        asm volatile("atom.acq_rel.cta.shared.add.u32 %0,[%1],1;" : "=r"(old) : "r"(bar + OFF_CNT) : "memory");
        if (old == 15) {
            atomicAdd(scr->done, 1u);
        }
    }
}

typedef CUresult (*EncFn)(CUtensorMap*, CUtensorMapDataType, cuuint32_t, void*, const cuuint64_t*, const cuuint64_t*, const cuuint32_t*,
                          const cuuint32_t*, CUtensorMapInterleave, CUtensorMapSwizzle, CUtensorMapL2promotion, CUtensorMapFloatOOBfill);

extern "C" void kernel_launch(void* const* d_in, const int* in_sizes, int n_in, void* d_out, int out_size) {
    static EncFn enc = nullptr;
    static Scratch* scr = nullptr;
    if (!enc) {
        cudaGetSymbolAddress((void**)&scr, g_scr);
        cudaDriverEntryPointQueryResult qr;
        cudaGetDriverEntryPoint("cuTensorMapEncodeTiled", (void**)&enc, cudaEnableDefault, &qr);
        cudaFuncSetAttribute(fused_kernel, cudaFuncAttributeMaxDynamicSharedMemorySize, SMEM_BYTES);
    }
    CUtensorMap mx, mw, mwo;
    const cuuint32_t es[3] = {1, 1, 1};
    {
        cuuint64_t d[2] = {512, 2048}, s[1] = {1024}; cuuint32_t b[2] = {64, 128};
        enc(&mx, CU_TENSOR_MAP_DATA_TYPE_BFLOAT16, 2, d_in[0], d, s, b, es, CU_TENSOR_MAP_INTERLEAVE_NONE, CU_TENSOR_MAP_SWIZZLE_128B,
            CU_TENSOR_MAP_L2_PROMOTION_L2_128B, CU_TENSOR_MAP_FLOAT_OOB_FILL_NONE);
    }
    {
        cuuint64_t d[3] = {512, 512, 3}, s[2] = {3072, 1024}; cuuint32_t b[3] = {64, 64, 3};
        enc(&mw, CU_TENSOR_MAP_DATA_TYPE_BFLOAT16, 3, d_in[1], d, s, b, es, CU_TENSOR_MAP_INTERLEAVE_NONE, CU_TENSOR_MAP_SWIZZLE_128B,
            CU_TENSOR_MAP_L2_PROMOTION_L2_128B, CU_TENSOR_MAP_FLOAT_OOB_FILL_NONE);
    }
    {
        cuuint64_t d[2] = {512, 512}, s[1] = {1024}; cuuint32_t b[2] = {64, 256};
        enc(&mwo, CU_TENSOR_MAP_DATA_TYPE_BFLOAT16, 2, d_in[3], d, s, b, es, CU_TENSOR_MAP_INTERLEAVE_NONE, CU_TENSOR_MAP_SWIZZLE_128B,
            CU_TENSOR_MAP_L2_PROMOTION_L2_128B, CU_TENSOR_MAP_FLOAT_OOB_FILL_NONE);
    }
    fused_kernel<<<128, 512, SMEM_BYTES, cudaStreamPerThread>>>(
        scr, (const bf16*)d_in[5], (const bf16*)d_in[6], (const bf16*)d_in[7], (const bf16*)d_in[8], (const bf16*)d_in[9],
        (const bf16*)d_in[10], (const bf16*)d_in[2], (const bf16*)d_in[11], (bf16*)d_out, mx, mw, mwo);
}
```

```cpp
#include <cuda_runtime.h>
#include <cuda.h>
#include <cuda_bf16.h>
#include <stdint.h>

typedef __nv_bfloat16 bf16;

struct Scratch {
    uint4 xt[128 * 1024];
    uint4 o[16 * 8 * 32 * 32];
    uint4 y[128 * 1024];
    uint4 kvp[8 * 16 * 544];
    uint4 kvf[8 * 4 * 68];
    unsigned g[1024 * 8];
    unsigned yflag[128 * 8];
    unsigned xcnt[8 * 32];
    unsigned done[32];
};
__device__ Scratch g_scr;
#define STAMP(n)

constexpr int SLOT = 40960;
constexpr int OFF_SP0 = 32768, OFF_SP1 = SLOT + 32768;
constexpr int OFF_P = 2 * SLOT, OFF_V = OFF_P + 32768;
constexpr int OFF_KVF = OFF_V + 32768;
constexpr int KT_BYTES = 3264, KW_D = 16, KW_2 = 560, KW_3 = 656;
constexpr int OFF_U = 4 * SLOT, U_STRIDE = 4096 + 256 + 32;
constexpr int OFF_BUF = OFF_U + 4 * U_STRIDE, BUF_STRIDE = 8320;
constexpr int OFF_K = OFF_BUF + 4 * BUF_STRIDE;
constexpr int OFF_WPHI = OFF_K + 4 * KT_BYTES;
constexpr int OFF_GW = OFF_WPHI + 2048;
constexpr int OFF_BAR = OFF_GW + 1024;
constexpr int SMEM_BYTES = OFF_BAR + 256 + 256;
static_assert(SMEM_BYTES <= 232448 && OFF_BUF % 128 == 0, "smem");
constexpr int W5_OFF = 0, W3_OFF = 3088, W9_OFF = 6176;
constexpr int BAR_FULL = 0, BAR_EMPTY = 4, BAR_WPHI = 8, BAR_WO = 9, BAR_WO2 = 10, BAR_XT = 11, BAR_DONE = 12, BAR_KG = 13, BAR_SP = 14,
              BAR_PUB = 15, BAR_KVF = 16, BAR_UR = 17, BAR_WR = 18, BAR_PREP = 19, BAR_KGA = 20, BAR_SP2 = 21, OFF_CNT = 192;
constexpr int SPIN_LIMIT = 1 << 17;

__device__ __forceinline__ uint32_t s2u(const void* p) { return (uint32_t)__cvta_generic_to_shared(p); }
__device__ __forceinline__ void mbar_init(uint32_t b, int c) { asm volatile("mbarrier.init.shared::cta.b64 [%0],%1;" ::"r"(b), "r"(c) : "memory"); }
__device__ __forceinline__ void mbar_expect(uint32_t b, int bytes) { asm volatile("mbarrier.arrive.expect_tx.shared::cta.b64 _,[%0],%1;" ::"r"(b), "r"(bytes) : "memory"); }
__device__ __forceinline__ void mbar_arrive(uint32_t b) { asm volatile("mbarrier.arrive.shared::cta.b64 _,[%0];" ::"r"(b) : "memory"); }
__device__ __forceinline__ void mbar_wait(uint32_t b, int ph) {
    asm volatile("{\n.reg .pred p;\n.reg .u32 n;\nmov.u32 n,0;\nLW_%=:\nmbarrier.try_wait.parity.shared::cta.b64 p,[%0],%1;\n@p bra LD_%=;\n"
                 "add.u32 n,n,1;\nsetp.lt.u32 p,n,16384;\n@p bra LW_%=;\nLD_%=:\n}" ::"r"(b), "r"(ph) : "memory");
}
__device__ __forceinline__ void tma2d(uint32_t dst, const CUtensorMap* m, int c0, int c1, uint32_t bar) {
    asm volatile("cp.async.bulk.tensor.2d.shared::cluster.global.mbarrier::complete_tx::bytes [%0],[%1,{%3,%4}],[%2];" ::"r"(dst), "l"(m), "r"(bar), "r"(c0), "r"(c1) : "memory");
}
__device__ __forceinline__ void tma3d(uint32_t dst, const CUtensorMap* m, int c0, int c1, int c2, uint32_t bar) {
    asm volatile("cp.async.bulk.tensor.3d.shared::cluster.global.mbarrier::complete_tx::bytes [%0],[%1,{%3,%4,%5}],[%2];" ::"r"(dst), "l"(m), "r"(bar), "r"(c0), "r"(c1), "r"(c2) : "memory");
}
__device__ __forceinline__ void bulk_g2s(uint32_t dst, const void* src, int bytes, uint32_t bar) {
    asm volatile("cp.async.bulk.shared::cluster.global.mbarrier::complete_tx::bytes [%0],[%1],%2,[%3];" ::"r"(dst), "l"(src), "r"(bytes), "r"(bar) : "memory");
}
__device__ __forceinline__ uint64_t mkdesc(uint32_t addr, uint32_t lbo, uint32_t sbo) {
    return (uint64_t)((addr & 0x3FFFF) >> 4) | ((uint64_t)(lbo >> 4) << 16) | ((uint64_t)(sbo >> 4) << 32) | ((uint64_t)1 << 62);
}
__device__ __forceinline__ void wg_fence() { asm volatile("wgmma.fence.sync.aligned;" ::: "memory"); }
__device__ __forceinline__ void wg_commit() { asm volatile("wgmma.commit_group.sync.aligned;" ::: "memory"); }
template <int N> __device__ __forceinline__ void wg_wait() { asm volatile("wgmma.wait_group.sync.aligned %0;" ::"n"(N) : "memory"); }
template <int N> __device__ __forceinline__ void fence_regs(float* d) {
#pragma unroll
    for (int i = 0; i < N; i++) asm volatile("" : "+f"(d[i])::"memory");
}
#define R8(d, o) "+f"(d[o]), "+f"(d[o + 1]), "+f"(d[o + 2]), "+f"(d[o + 3]), "+f"(d[o + 4]), "+f"(d[o + 5]), "+f"(d[o + 6]), "+f"(d[o + 7])
__device__ __forceinline__ void wgmma192(float* d, uint64_t da, uint64_t db) {
    asm volatile("wgmma.mma_async.sync.aligned.m64n192k16.f32.bf16.bf16 {"
                 "%0,%1,%2,%3,%4,%5,%6,%7,%8,%9,%10,%11,%12,%13,%14,%15,%16,%17,%18,%19,%20,%21,%22,%23,%24,%25,%26,%27,%28,%29,%30,%31,"
                 "%32,%33,%34,%35,%36,%37,%38,%39,%40,%41,%42,%43,%44,%45,%46,%47,%48,%49,%50,%51,%52,%53,%54,%55,%56,%57,%58,%59,%60,%61,%62,%63,"
                 "%64,%65,%66,%67,%68,%69,%70,%71,%72,%73,%74,%75,%76,%77,%78,%79,%80,%81,%82,%83,%84,%85,%86,%87,%88,%89,%90,%91,%92,%93,%94,%95},"
                 "%96,%97,1,1,1,0,1;"
                 : R8(d, 0), R8(d, 8), R8(d, 16), R8(d, 24), R8(d, 32), R8(d, 40), R8(d, 48), R8(d, 56), R8(d, 64), R8(d, 72), R8(d, 80), R8(d, 88)
                 : "l"(da), "l"(db));
}
__device__ __forceinline__ void wgmma64_tt(float* d, uint64_t da, uint64_t db, int sc) {
    asm volatile("{.reg .pred p; setp.ne.b32 p,%34,0; wgmma.mma_async.sync.aligned.m64n64k16.f32.bf16.bf16 {"
                 "%0,%1,%2,%3,%4,%5,%6,%7,%8,%9,%10,%11,%12,%13,%14,%15,%16,%17,%18,%19,%20,%21,%22,%23,%24,%25,%26,%27,%28,%29,%30,%31},"
                 "%32,%33,p,1,1,1,1;}"
                 : R8(d, 0), R8(d, 8), R8(d, 16), R8(d, 24)
                 : "l"(da), "l"(db), "r"(sc));
}
__device__ __forceinline__ void wgmma128_rs(float* d, const uint4& a, uint64_t db, int sc) {
    asm volatile("{.reg .pred p; setp.ne.b32 p,%69,0; wgmma.mma_async.sync.aligned.m64n128k16.f32.bf16.bf16 {"
                 "%0,%1,%2,%3,%4,%5,%6,%7,%8,%9,%10,%11,%12,%13,%14,%15,%16,%17,%18,%19,%20,%21,%22,%23,%24,%25,%26,%27,%28,%29,%30,%31,"
                 "%32,%33,%34,%35,%36,%37,%38,%39,%40,%41,%42,%43,%44,%45,%46,%47,%48,%49,%50,%51,%52,%53,%54,%55,%56,%57,%58,%59,%60,%61,%62,%63},"
                 "{%64,%65,%66,%67},%68,p,1,1,1;}"
                 : R8(d, 0), R8(d, 8), R8(d, 16), R8(d, 24), R8(d, 32), R8(d, 40), R8(d, 48), R8(d, 56)
                 : "r"(a.x), "r"(a.y), "r"(a.z), "r"(a.w), "l"(db), "r"(sc));
}
__device__ __forceinline__ void mma16816(float* c, uint32_t a0, uint32_t a1, uint32_t a2, uint32_t a3, uint32_t b0, uint32_t b1) {
    asm("mma.sync.aligned.m16n8k16.row.col.f32.bf16.bf16.f32 {%0,%1,%2,%3},{%4,%5,%6,%7},{%8,%9},{%0,%1,%2,%3};"
        : "+f"(c[0]), "+f"(c[1]), "+f"(c[2]), "+f"(c[3]) : "r"(a0), "r"(a1), "r"(a2), "r"(a3), "r"(b0), "r"(b1));
}
__device__ __forceinline__ void ldsm4(uint32_t* r, uint32_t a) {
    asm volatile("ldmatrix.sync.aligned.m8n8.x4.shared.b16 {%0,%1,%2,%3},[%4];" : "=r"(r[0]), "=r"(r[1]), "=r"(r[2]), "=r"(r[3]) : "r"(a) : "memory");
}
__device__ __forceinline__ void ldsm4t(uint32_t* r, uint32_t a) {
    asm volatile("ldmatrix.sync.aligned.m8n8.x4.trans.shared.b16 {%0,%1,%2,%3},[%4];" : "=r"(r[0]), "=r"(r[1]), "=r"(r[2]), "=r"(r[3]) : "r"(a) : "memory");
}
__device__ __forceinline__ void stsm4(uint32_t a, uint32_t r0, uint32_t r1, uint32_t r2, uint32_t r3) {
    asm volatile("stmatrix.sync.aligned.m8n8.x4.shared.b16 [%0],{%1,%2,%3,%4};" ::"r"(a), "r"(r0), "r"(r1), "r"(r2), "r"(r3) : "memory");
}
__device__ __forceinline__ uint32_t lds32(uint32_t a) { uint32_t v; asm volatile("ld.shared.b32 %0,[%1];" : "=r"(v) : "r"(a) : "memory"); return v; }
__device__ __forceinline__ uint4 lds128(uint32_t a) { uint4 v; asm volatile("ld.shared.v4.b32 {%0,%1,%2,%3},[%4];" : "=r"(v.x), "=r"(v.y), "=r"(v.z), "=r"(v.w) : "r"(a) : "memory"); return v; }
__device__ __forceinline__ void sts16(uint32_t a, uint32_t v) { asm volatile("st.shared.b16 [%0],%1;" ::"r"(a), "h"((unsigned short)v) : "memory"); }
__device__ __forceinline__ void sts32(uint32_t a, uint32_t v) { asm volatile("st.shared.b32 [%0],%1;" ::"r"(a), "r"(v) : "memory"); }
__device__ __forceinline__ void sts64(uint32_t a, uint32_t x, uint32_t y) { asm volatile("st.shared.v2.b32 [%0],{%1,%2};" ::"r"(a), "r"(x), "r"(y) : "memory"); }
__device__ __forceinline__ void sts128(uint32_t a, uint32_t x, uint32_t y, uint32_t z, uint32_t w) { asm volatile("st.shared.v4.b32 [%0],{%1,%2,%3,%4};" ::"r"(a), "r"(x), "r"(y), "r"(z), "r"(w) : "memory"); }
__device__ __forceinline__ uint32_t pack2(float lo, float hi) { uint32_t d; asm("cvt.rn.bf16x2.f32 %0,%1,%2;" : "=r"(d) : "f"(hi), "f"(lo)); return d; }
__device__ __forceinline__ float bf_lo(uint32_t v) { return __uint_as_float(v << 16); }
__device__ __forceinline__ float bf_hi(uint32_t v) { return __uint_as_float(v & 0xffff0000u); }
__device__ __forceinline__ float bf_round(float v) { return bf_lo(pack2(v, 0.f)); }
__device__ __forceinline__ uint32_t hmax2(uint32_t a, uint32_t b) { uint32_t d; asm("max.bf16x2 %0,%1,%2;" : "=r"(d) : "r"(a), "r"(b)); return d; }
__device__ __forceinline__ uint32_t hmin2(uint32_t a, uint32_t b) { uint32_t d; asm("min.bf16x2 %0,%1,%2;" : "=r"(d) : "r"(a), "r"(b)); return d; }
__device__ __forceinline__ uint32_t hmul2(uint32_t a, uint32_t b) { uint32_t d; asm("mul.rn.bf16x2 %0,%1,%2;" : "=r"(d) : "r"(a), "r"(b)); return d; }
__device__ __forceinline__ float ex2(float x) { float y; asm("ex2.approx.ftz.f32 %0,%1;" : "=f"(y) : "f"(x)); return y; }
__device__ __forceinline__ float rcp(float x) { float y; asm("rcp.approx.ftz.f32 %0,%1;" : "=f"(y) : "f"(x)); return y; }
__device__ __forceinline__ uint32_t ld_nc(const uint32_t* p) { uint32_t v; asm volatile("ld.global.nc.b32 %0,[%1];" : "=r"(v) : "l"(p)); return v; }
__device__ __forceinline__ uint2 ld_nc64(const uint2* p) { uint2 v; asm volatile("ld.global.nc.v2.b32 {%0,%1},[%2];" : "=r"(v.x), "=r"(v.y) : "l"(p)); return v; }
__device__ __forceinline__ unsigned ld_acq(const unsigned* p) { unsigned v; asm volatile("ld.acquire.gpu.global.u32 %0,[%1];" : "=r"(v) : "l"(p) : "memory"); return v; }
__device__ __forceinline__ unsigned ld_rlx(const unsigned* p) { unsigned v; asm volatile("ld.relaxed.gpu.global.u32 %0,[%1];" : "=r"(v) : "l"(p) : "memory"); return v; }
__device__ __forceinline__ uint2 ld_rlx64(const void* p) { uint2 v; asm volatile("{.reg .b64 t; ld.relaxed.gpu.global.b64 t,[%2]; mov.b64 {%0,%1},t;}" : "=r"(v.x), "=r"(v.y) : "l"(p) : "memory"); return v; }
__device__ __forceinline__ uint4 ld_rlx128(const void* p) {
    uint4 v;
    asm volatile("{.reg .b64 t,u; ld.relaxed.gpu.global.v2.b64 {t,u},[%4]; mov.b64 {%0,%1},t; mov.b64 {%2,%3},u;}" : "=r"(v.x), "=r"(v.y), "=r"(v.z), "=r"(v.w) : "l"(p) : "memory");
    return v;
}
__device__ __forceinline__ void st_rlx32(void* p, uint32_t x) { asm volatile("st.relaxed.gpu.global.u32 [%0],%1;" ::"l"(p), "r"(x) : "memory"); }
__device__ __forceinline__ void st_rlx64(void* p, uint32_t x, uint32_t y) { asm volatile("{.reg .b64 t; mov.b64 t,{%1,%2}; st.relaxed.gpu.global.b64 [%0],t;}" ::"l"(p), "r"(x), "r"(y) : "memory"); }
__device__ __forceinline__ void st_rlx128(void* p, uint4 v) {
    asm volatile("{.reg .b64 t,u; mov.b64 t,{%1,%2}; mov.b64 u,{%3,%4}; st.relaxed.gpu.global.v2.b64 [%0],{t,u};}" ::"l"(p), "r"(v.x), "r"(v.y), "r"(v.z), "r"(v.w) : "memory");
}
__device__ __forceinline__ uint32_t tagw(uint32_t w, uint32_t tag) { return (w & ~1u) | tag; }
__device__ __forceinline__ uint4 tag4(uint32_t x, uint32_t y, uint32_t z, uint32_t w, uint32_t tag) { return make_uint4(tagw(x, tag), y, tagw(z, tag), w); }
__device__ __forceinline__ uint32_t bad4(const uint4& v, uint32_t tag) { return (v.x ^ tag) | (v.z ^ tag); }
__device__ __forceinline__ void bar_named(int id, int n) { asm volatile("bar.sync %0,%1;" ::"r"(id), "r"(n) : "memory"); }

struct cf { float re, im; };
__device__ __forceinline__ cf cmul(cf a, cf b) { cf r; r.re = a.re * b.re - a.im * b.im; r.im = a.re * b.im + a.im * b.re; return r; }
__device__ __forceinline__ cf cexp_p(float arl, float ait, float p) {
    float mag = ex2(arl * p);
    float t = ait * p;
    t = (t - rintf(t)) * 6.283185307179586f;
    cf r; r.re = mag * __cosf(t); r.im = mag * __sinf(t);
    return r;
}

__device__ __forceinline__ void hedgehog2(const uint32_t* a, uint32_t wphi_addr, uint32_t (*out)[8]) {
    float p[2][2][4], mx[2][2];
#pragma unroll
    for (int h = 0; h < 2; h++) {
        uint32_t b[4];
        ldsm4t(b, wphi_addr + h * 512);
        float c0[4] = {0.f, 0.f, 0.f, 0.f}, c1[4] = {0.f, 0.f, 0.f, 0.f};
        mma16816(c0, a[4 * h], a[4 * h + 1], a[4 * h + 2], a[4 * h + 3], b[0], b[1]);
        mma16816(c1, a[4 * h], a[4 * h + 1], a[4 * h + 2], a[4 * h + 3], b[2], b[3]);
#pragma unroll
        for (int k = 0; k < 2; k++) {
            p[h][k][0] = c0[2 * k]; p[h][k][1] = c0[2 * k + 1]; p[h][k][2] = c1[2 * k]; p[h][k][3] = c1[2 * k + 1];
            mx[h][k] = fmaxf(fmaxf(p[h][k][0], p[h][k][1]), fmaxf(p[h][k][2], p[h][k][3]));
        }
    }
#pragma unroll
    for (int o = 1; o <= 2; o <<= 1)
#pragma unroll
        for (int h = 0; h < 2; h++)
#pragma unroll
            for (int k = 0; k < 2; k++) mx[h][k] = fmaxf(mx[h][k], __shfl_xor_sync(~0u, mx[h][k], o));
    const float L = 1.4426950408889634f;
    float pmin = 1.f;
#pragma unroll
    for (int h = 0; h < 2; h++)
#pragma unroll
        for (int k = 0; k < 2; k++) {
            const float m = -mx[h][k] * L;
            const float e0 = ex2(fmaf(p[h][k][0], L, m)), e1 = ex2(fmaf(p[h][k][1], L, m)), e2 = ex2(fmaf(p[h][k][2], L, m)), e3 = ex2(fmaf(p[h][k][3], L, m));
            const float p01 = e0 * e1, p23 = e2 * e3, pp = p01 * p23, r = rcp(pp), r01 = r * p23, r23 = r * p01;
            pmin = fminf(pmin, pp);
            out[h][k] = pack2(e0, e1); out[h][k + 2] = pack2(e2, e3);
            out[h][4 + k] = pack2(r01 * e1, r01 * e0); out[h][4 + k + 2] = pack2(r23 * e3, r23 * e2);
        }
    if (__builtin_expect(__any_sync(~0u, !(pmin > 1e-18f)), 0)) {
#pragma unroll
        for (int h = 0; h < 2; h++)
#pragma unroll
            for (int k = 0; k < 2; k++) {
                float m = fminf(fminf(p[h][k][0], p[h][k][1]), fminf(p[h][k][2], p[h][k][3]));
                m = fminf(m, __shfl_xor_sync(~0u, m, 1));
                m = fminf(m, __shfl_xor_sync(~0u, m, 2)) * L;
                out[h][4 + k] = pack2(ex2(fmaf(p[h][k][0], -L, m)), ex2(fmaf(p[h][k][1], -L, m)));
                out[h][4 + k + 2] = pack2(ex2(fmaf(p[h][k][2], -L, m)), ex2(fmaf(p[h][k][3], -L, m)));
            }
    }
}

__global__ void __launch_bounds__(512, 1)
fused_kernel(Scratch* __restrict__ scr, const bf16* __restrict__ logA, const bf16* __restrict__ Aim, const bf16* __restrict__ Cre,
             const bf16* __restrict__ Cim, const bf16* __restrict__ logdt, const bf16* __restrict__ Dskip, const bf16* __restrict__ wphi,
             const bf16* __restrict__ gatew, bf16* __restrict__ out,
             const __grid_constant__ CUtensorMap mx, const __grid_constant__ CUtensorMap mw, const __grid_constant__ CUtensorMap mwo) {
    extern __shared__ __align__(1024) uint8_t smem[];
    const uint32_t sb = s2u(smem);
    const int tid = threadIdx.x, warp = __shfl_sync(~0u, tid >> 5, 0), lane = tid & 31;
    const int g = lane >> 2, q = lane & 3, w4 = warp & 3;
    const int bi = blockIdx.x, bi_i = bi & 15, bi_j = bi >> 4;
    const uint32_t bar = sb + OFF_BAR;
    const int rot = (bi_j & 3) * 2, xkb = bi_j >> 2;
    auto load_stage = [&](int kb) {
        const uint32_t b = bar + 8 * (BAR_FULL + (kb & 3)), d = sb + (kb & 3) * SLOT;
        const int kc = ((kb + rot) & 7) * 64;
        mbar_expect(b, SLOT);
        tma2d(d, &mx, kc, bi_i * 128, b);
        tma3d(d + 16384, &mw, bi_j * 64, kc, 0, b);
    };

    const int ch = bi * 4 + w4;
    uint32_t pla = 0, pai = 0, pcr = 0, pci = 0, pdt = 0, pds = 0;
    if (warp >= 8) {
        const int pidx = ch * 64 + lane * 2 + (warp >= 12);
        pla = ld_nc((const uint32_t*)logA + pidx); pai = ld_nc((const uint32_t*)Aim + pidx);
        pcr = ld_nc((const uint32_t*)Cre + pidx); pci = ld_nc((const uint32_t*)Cim + pidx);
        pdt = ld_nc((const uint32_t*)logdt + (ch >> 1)); pds = ld_nc((const uint32_t*)Dskip + (ch >> 1));
    }
    unsigned done0 = ld_rlx(scr->done);
    if (tid == 0) {
        for (int s = 0; s < 4; s++) mbar_init(bar + 8 * (BAR_FULL + s), 1);
        asm volatile("fence.mbarrier_init.release.cluster;" ::: "memory");
        load_stage(0); load_stage(1); load_stage(2);
        STAMP(11);
    } else if (tid == 32) {
        if (sb & 1023) __trap();
        sts32(bar + OFF_CNT, 0);
        for (int s = 0; s < 4; s++) mbar_init(bar + 8 * (BAR_EMPTY + s), 8);
        mbar_init(bar + 8 * BAR_WPHI, 1); mbar_init(bar + 8 * BAR_WO, 1); mbar_init(bar + 8 * BAR_WO2, 1); mbar_init(bar + 8 * BAR_XT, 4);
        mbar_init(bar + 8 * BAR_DONE, 9); mbar_init(bar + 8 * BAR_KG, 4); mbar_init(bar + 8 * BAR_SP, 4); mbar_init(bar + 8 * BAR_PUB, 8);
        mbar_init(bar + 8 * BAR_KVF, 4); mbar_init(bar + 8 * BAR_UR, 4); mbar_init(bar + 8 * BAR_WR, 4); mbar_init(bar + 8 * BAR_PREP, 4); mbar_init(bar + 8 * BAR_KGA, 8); mbar_init(bar + 8 * BAR_SP2, 1);
        asm volatile("fence.mbarrier_init.release.cluster;" ::: "memory");
        mbar_expect(bar + 8 * BAR_WPHI, 3072);
        bulk_g2s(sb + OFF_GW, gatew, 1024, bar + 8 * BAR_WPHI);
        bulk_g2s(sb + OFF_WPHI, wphi + bi_j * 1024, 2048, bar + 8 * BAR_WPHI);
    } else if (tid == 64) {
        asm volatile("prefetch.tensormap [%0];" ::"l"(&mw) : "memory");
    }
    const uint32_t buf = sb + OFF_BUF + w4 * BUF_STRIDE, kb_ = sb + OFF_K + w4 * KT_BYTES;
    if ((warp >> 2) == 2) {
#pragma unroll
        for (int v = 0; v < 7; v++) if (v * 32 + lane < KT_BYTES / 16) sts128(kb_ + (v * 32 + lane) * 16, 0, 0, 0, 0);
    }
    __syncthreads();
    asm volatile("" : "+r"(pdt), "+r"(done0)::"memory");
    const unsigned epoch1 = (done0 >> 7) + 1u;
    const uint32_t tag = epoch1 & 1u;

    const int st = tid & 127;
    const uint32_t ub = sb + OFF_U + w4 * U_STRIDE + 256, spare = sb + (w4 < 2 ? OFF_SP0 : OFF_SP1) + (w4 & 1) * 4096;

    if (warp < 8) {
        const int wg = warp >> 2;
        if (warp == 0) STAMP(21);
        float acc[96];
        const int srow = warp * 16 + (lane & 15);
        const uint32_t srow_a = srow * 128;
        const int sx = srow & 7, shi = lane >> 4;
#pragma unroll
        for (int r = 0; r < 96; r++) acc[r] = 0.f;
        fence_regs<96>(acc);
        const uint64_t da0 = mkdesc(sb + wg * 8192, 16, 1024), db0 = mkdesc(sb + 16384, 8192, 1024);
        mbar_wait(bar + 8 * BAR_KGA, 0);
#pragma unroll 1
        for (int kb = 0; kb < 8; kb++) {
            const int s = kb & 3;
            const uint64_t da = da0 + s * (SLOT >> 4), db = db0 + s * (SLOT >> 4);
            if (warp == 0) STAMP(40 + kb);
            mbar_wait(bar + 8 * (BAR_FULL + s), kb >> 2);
            if (warp == 0) STAMP(32 + kb);
            wg_fence();
#pragma unroll
            for (int k = 0; k < 4; k++) wgmma192(acc, da + 2 * k, db + 128 * k);
            wg_commit();
            wg_wait<1>();
            if (lane == 0 && kb > 0) mbar_arrive(bar + 8 * (BAR_EMPTY + ((kb - 1) & 3)));
        }
        mbar_wait(bar + 8 * BAR_WPHI, 0);
        wg_wait<0>();
        fence_regs<96>(acc);
        if (lane == 0) mbar_arrive(bar + 8 * BAR_DONE);
        if (warp == 0) STAMP(1);
        uint32_t in[32], va[16];
#pragma unroll
        for (int r = 0; r < 16; r++) {
            in[r] = pack2(acc[32 + 2 * r], acc[32 + 2 * r + 1]);
            in[16 + r] = pack2(acc[2 * r], acc[2 * r + 1]);
            va[r] = pack2(acc[64 + 2 * r], acc[64 + 2 * r + 1]);
        }
        const uint32_t wphi_a = sb + OFF_WPHI + (lane & 15) * 32 + (lane >> 4) * 16;
        uint32_t pq[4][8];
#pragma unroll 1
        for (int it = 0; it < 4; it++) {
            hedgehog2(in, wphi_a + (it & 1) * 1024, pq + 2);
#pragma unroll
            for (int r = 0; r < 24; r++) in[r] = in[r + 8];
            if (it < 2) {
#pragma unroll
                for (int hs = 0; hs < 4; hs++) {
                    float c[4] = {0.f, 0.f, 0.f, 0.f};
                    uint32_t* o = pq[2 + (hs >> 1)] + 4 * (hs & 1);
                    mma16816(c, o[0], o[1], o[2], o[3], 0x3f803f80u, 0x3f803f80u);
                    const float r0 = rcp(c[0]), r1 = rcp(c[2]);
                    const uint32_t s0 = pack2(r0, r0), s1 = pack2(r1, r1);
                    o[0] = hmul2(o[0], s0); o[1] = hmul2(o[1], s1); o[2] = hmul2(o[2], s0); o[3] = hmul2(o[3], s1);
                }
                if (it == 0) mbar_wait(bar + 8 * BAR_DONE, 0);
                const uint32_t pt = sb + OFF_P + it * 16384 + srow_a, vt = sb + OFF_V + it * 16384 + srow_a;
#pragma unroll
                for (int hl = 0; hl < 2; hl++) {
                    stsm4(pt + (((4 * hl + shi) ^ sx) << 4), pq[2 + hl][0], pq[2 + hl][1], pq[2 + hl][2], pq[2 + hl][3]);
                    stsm4(pt + (((4 * hl + 2 + shi) ^ sx) << 4), pq[2 + hl][4], pq[2 + hl][5], pq[2 + hl][6], pq[2 + hl][7]);
                    stsm4(vt + (((2 * hl + shi) ^ sx) << 4), va[4 * hl], va[4 * hl + 1], va[4 * hl + 2], va[4 * hl + 3]);
                }
                if (lane < 16) sts128(vt + ((4 ^ sx) << 4), 0x3f803f80u, 0x3f803f80u, 0x3f803f80u, 0x3f803f80u);
#pragma unroll
                for (int r = 0; r < 8; r++) va[r] = va[r + 8];
            }
            if (it == 1) {
                asm volatile("fence.proxy.async.shared::cta;" ::: "memory");
                bar_named(1, 256);
                if (warp == 0) STAMP(2);
                float d[32];
                const uint64_t dv = mkdesc(sb + OFF_V + wg * 16384, 16, 1024), dp = mkdesc(sb + OFF_P + wg * 16384, 16, 1024);
                wg_fence();
#pragma unroll
                for (int k = 0; k < 8; k++) wgmma64_tt(d, dv + 128 * k, dp + 128 * k, k != 0);
                wg_commit();
                wg_wait<0>();
                fence_regs<32>(d);
                mbar_wait(bar + 8 * BAR_PREP, 0);
                uint4* kvp = scr->kvp + bi * 544 + wg * 272;
                if (w4 < 2) {
                    uint32_t e[16];
#pragma unroll
                    for (int r = 0; r < 16; r++) e[r] = __float_as_uint(w4 ? d[16 + r] : d[r]);
                    uint4* p = kvp + w4 * 136 + lane;
#pragma unroll
                    for (int ks = 0; ks < 2; ks++)
#pragma unroll
                        for (int nt = 0; nt < 2; nt++)
                            st_rlx128(p + (ks * 2 + nt) * 32, tag4(e[8 * ks + 2 * nt], e[8 * ks + 2 * nt + 1], e[8 * ks + 4 + 2 * nt], e[8 * ks + 4 + 2 * nt + 1], tag));
                } else if (w4 == 2 && lane < 4) {
#pragma unroll
                    for (int hl = 0; hl < 2; hl++)
#pragma unroll
                        for (int ks = 0; ks < 2; ks++)
                            st_rlx128(kvp + hl * 136 + 128 + ks * 4 + lane, tag4(__float_as_uint(d[16 * hl + 8 * ks]), __float_as_uint(d[16 * hl + 8 * ks + 1]),
                                                                                __float_as_uint(d[16 * hl + 8 * ks + 4]), __float_as_uint(d[16 * hl + 8 * ks + 5]), tag));
                }
                __syncwarp();
                if (lane == 0) mbar_arrive(bar + 8 * BAR_PUB);
                if (warp == 0) STAMP(3);
            }
            if (it == 2) {
#pragma unroll
                for (int r = 0; r < 8; r++) { pq[0][r] = pq[2][r]; pq[1][r] = pq[3][r]; }
            }
        }
        if (warp == 0) STAMP(4);
        asm volatile("setmaxnreg.inc.sync.aligned.u32 160;");
        {
            mbar_wait(bar + 8 * BAR_KVF, 0);
            uint4 kf[4][3];
#pragma unroll
            for (int hh = 0; hh < 4; hh++) {
                const uint32_t a = sb + OFF_KVF + hh * 1088;
                kf[hh][0] = lds128(a + lane * 32); kf[hh][1] = lds128(a + lane * 32 + 16); kf[hh][2] = lds128(a + 1024 + q * 16);
            }
            if (warp == 0) STAMP(5);
            uint4 own[4];
#pragma unroll
            for (int hh = 0; hh < 4; hh++) {
                float c[6][4];
#pragma unroll
                for (int t = 0; t < 6; t++) { c[t][0] = c[t][1] = c[t][2] = c[t][3] = 0.f; }
                const uint32_t* a = pq[hh];
                const bool od = g & 1;
                mma16816(c[0], a[0], a[1], a[2], a[3], od ? 0x3f803f80u : kf[hh][2].x, od ? 0x3f803f80u : kf[hh][2].y);
                mma16816(c[1], a[4], a[5], a[6], a[7], od ? 0x3f803f80u : kf[hh][2].z, od ? 0x3f803f80u : kf[hh][2].w);
                mma16816(c[2], a[0], a[1], a[2], a[3], kf[hh][0].x, kf[hh][0].y);
                mma16816(c[3], a[0], a[1], a[2], a[3], kf[hh][0].z, kf[hh][0].w);
                mma16816(c[4], a[4], a[5], a[6], a[7], kf[hh][1].x, kf[hh][1].y);
                mma16816(c[5], a[4], a[5], a[6], a[7], kf[hh][1].z, kf[hh][1].w);
                uint32_t w[4];
#pragma unroll
                for (int k = 0; k < 2; k++) {
                    const float rho = c[0][2 * k + 1] * rcp(c[1][2 * k + 1]);
                    const float r = rcp(fmaf(c[0][2 * k + 1], 1e-6f, fmaf(rho, c[1][2 * k], c[0][2 * k]))), rr = r * rho;
                    w[k] = pack2(fmaf(c[4][2 * k], rr, c[2][2 * k] * r), fmaf(c[4][2 * k + 1], rr, c[2][2 * k + 1] * r));
                    w[2 + k] = pack2(fmaf(c[5][2 * k], rr, c[3][2 * k] * r), fmaf(c[5][2 * k + 1], rr, c[3][2 * k + 1] * r));
                }
                own[hh] = tag4(w[0], w[1], w[2], w[3], tag);
            }
            uint4* og = scr->o + ((bi_i * 8 + warp) * 32 + bi_j * 4) * 32 + lane;
#pragma unroll
            for (int hh = 0; hh < 4; hh++) st_rlx128(og + hh * 32, own[hh]);
        }
        if (warp == 0) STAMP(6);
        float oc[64];
        const int slab = bi_i * 8 + (bi_j >> 2) * 4 + w4;
        const uint8_t* yb = (const uint8_t*)scr->y + (size_t)((bi_j & 3) * 32 + wg * 16 + (q >> 1)) * 16384 + slab * 128 + g * 16 + (q & 1) * 8;
        const unsigned* gp = scr->g + (slab * 8 + (g >> 1)) * 8 + (g & 1) * 4;
        uint2 yv[8]; unsigned g0, g1;
        {
            const uint4* osrc = scr->o + (slab * 32 + wg * 16) * 32 + lane;
            uint4 fr[16];
            const unsigned* probe = (const unsigned*)(osrc - lane + ((lane & 3) * 4 + 3) * 32 + 31) + 2;
            {
                unsigned miss = ~0u;
                int n = 0;
#pragma unroll
                for (int s = 0; s < 4; s++) {
#pragma unroll 1
                    while ((miss >> s) & 1) { miss = __ballot_sync(~0u, (ld_rlx(probe) ^ tag) & 1); if (++n > SPIN_LIMIT) break; }
#pragma unroll
                    for (int k = 4 * s; k < 4 * s + 4; k++) fr[k] = ld_rlx128(osrc + k * 32);
                }
            }
            if (warp == 0) STAMP(14);
            mbar_wait(bar + 8 * (wg ? BAR_WO2 : BAR_WO), 0);
            const uint64_t dw = mkdesc(sb + wg * 2 * SLOT, wg ? 32768 : SLOT, 1024);
#pragma unroll
            for (int s = 0; s < 4; s++) {
                int n = 0;
#pragma unroll 1
                while (__builtin_expect(__any_sync(~0u, (bad4(fr[4 * s], tag) | bad4(fr[4 * s + 1], tag) | bad4(fr[4 * s + 2], tag) | bad4(fr[4 * s + 3], tag)) & 1), 0)) {
#pragma unroll
                    for (int k = 4 * s; k < 4 * s + 4; k++) fr[k] = ld_rlx128(osrc + k * 32);
                    if (++n > SPIN_LIMIT) break;
                }
                wg_fence();
#pragma unroll
                for (int hh = 0; hh < 4; hh++) wgmma128_rs(oc, fr[4 * s + hh], dw + 128 * (4 * s + hh), (s | hh) != 0);
                wg_commit();
                if (s == 1) {
                    wg_wait<1>();
#pragma unroll
                    for (int nt = 0; nt < 8; nt++) yv[nt] = ld_rlx64(yb + nt * 32768);
                    g0 = ld_rlx(gp); g1 = ld_rlx(gp + 32);
                }
            }
            if (warp == 0) STAMP(7);
            {
                const unsigned* yprobe = scr->yflag + ((bi_j & 3) * 32 + wg * 16 + (lane & 15)) * 8;
                int n = 0;
#pragma unroll 1
                while (true) {
                    uint32_t bad = (g0 ^ tag) | (g1 ^ tag);
#pragma unroll
                    for (int nt = 0; nt < 8; nt++) bad |= yv[nt].x ^ tag;
                    if (!__any_sync(~0u, bad & 1)) break;
#pragma unroll 1
                    while (__any_sync(~0u, (ld_rlx(yprobe) ^ tag) & 1)) { if (++n > SPIN_LIMIT) break; }
#pragma unroll
                    for (int nt = 0; nt < 8; nt++) yv[nt] = ld_rlx64(yb + nt * 32768);
                    g0 = ld_rlx(gp); g1 = ld_rlx(gp + 32);
                    if (++n > SPIN_LIMIT) break;
                }
            }
            if (warp == 0) STAMP(28);
            wg_wait<0>();
            fence_regs<64>(oc);
        }
        {
            bar_named(3 + wg, 128);
            const uint32_t xw = sb + wg * 2 * SLOT + (tid & 127) * 16, xr = sb + (wg ^ 1) * 2 * SLOT + (tid & 127) * 16;
#pragma unroll
            for (int r = 0; r < 8; r++) {
                const float* o = oc + 4 * r;
                sts128(xw + r * 2048, __float_as_uint(wg ? o[0] : o[32]), __float_as_uint(wg ? o[1] : o[33]), __float_as_uint(wg ? o[2] : o[34]), __float_as_uint(wg ? o[3] : o[35]));
            }
#pragma unroll
            for (int r = 0; r < 32; r++) oc[r] = wg ? oc[32 + r] : oc[r];
            bar_named(1, 256);
            if (warp == 0) STAMP(8);
            const float ga = bf_hi(g0), gb = bf_hi(g1);
            const float ha = bf_round(1.0f - ga), hb = bf_round(1.0f - gb);
            uint32_t w[8][2];
#pragma unroll
            for (int nt = 0; nt < 8; nt++) {
                const uint4 p = lds128(xr + nt * 2048);
                w[nt][0] = pack2(fmaf(ga, oc[4 * nt] + __uint_as_float(p.x), ha * bf_lo(yv[nt].x)), fmaf(ga, oc[4 * nt + 1] + __uint_as_float(p.y), ha * bf_hi(yv[nt].x)));
                w[nt][1] = pack2(fmaf(gb, oc[4 * nt + 2] + __uint_as_float(p.z), hb * bf_lo(yv[nt].y)), fmaf(gb, oc[4 * nt + 3] + __uint_as_float(p.w), hb * bf_hi(yv[nt].y)));
            }
            const uint32_t ob = sb + wg * 2 * SLOT + 16384 + w4 * 2048;
#pragma unroll
            for (int nt = 0; nt < 8; nt += 2)
                stsm4(ob + (lane & 15) * 128 + (((nt + shi) ^ (lane & 7)) << 4), w[nt][0], w[nt][1], w[nt + 1][0], w[nt + 1][1]);
            __syncwarp();
            bf16* op = out + (size_t)(slab * 16) * 512 + (bi_j & 3) * 128 + wg * 64 + (lane & 7) * 8;
#pragma unroll
            for (int it = 0; it < 4; it++) {
                const int r = it * 4 + (lane >> 3);
                uint4 v = lds128(ob + r * 128 + (((lane & 7) ^ (r & 7)) << 4));
                *(uint4*)(op + r * 512) = v;
            }
        }
        if (warp == 0) STAMP(10);
    } else {
        const bool hw = warp >= 12;
        const int qq = (bi_i & 2) + ((lane >> 1) & 1);
        uint2* kvf_h = (uint2*)(scr->kvf + (bi_j * 4 + (bi_i >> 2)) * 68);
        auto windows = [&](int rhi, int rlo) {
#pragma unroll 1
            for (int rho = rhi; rho >= rlo; rho--) {
                const int ci = lane + 32 * rho;
                uint4 e4[4];
#pragma unroll
                for (int v = 0; v < 4; v++) { const int cc = ci - 3 + v; e4[v] = lds128(ub + ((cc ^ ((cc >> 3) & 1)) << 4)); }
                float S[29];
                const uint32_t* ew = (const uint32_t*)e4;
                S[3] = 0.f;
#pragma unroll
                for (int k = 4; k <= 28; k++) S[k] = S[k - 1] + ((k & 1) ? bf_hi(ew[k >> 1]) : bf_lo(ew[k >> 1]));
                auto win = [&](int lo, int hi, uint32_t a) {
                    sts128(a, pack2(S[hi] - S[lo - 1], S[hi + 1] - S[lo]), pack2(S[hi + 2] - S[lo + 1], S[hi + 3] - S[lo + 2]),
                           pack2(S[hi + 4] - S[lo + 3], S[hi + 5] - S[lo + 4]), pack2(S[hi + 6] - S[lo + 5], S[hi + 7] - S[lo + 6]));
                };
                win(14, 18, buf + W5_OFF + 16 + ci * 16); win(19, 21, buf + W3_OFF + 16 + ci * 16);
                if (rho < 4) {
                    const uint32_t sw = (ci ^ ((ci >> 3) & 1)) << 4;
                    win(4, 12, buf + W9_OFF + sw); win(13, 19, spare + sw); win(20, 21, spare + 2048 + sw);
                }
            }
        };
        float kc[24];
#pragma unroll
        for (int t = 0; t < 24; t++) kc[t] = 0.f;
        const float dt = bf_round(expf((ch & 1) ? bf_hi(pdt) : bf_lo(pdt)));
#pragma unroll 1
        for (int it = 0; it < 2; it++) {
            const uint32_t hstg = sb + (it == 0 ? 3 * SLOT : 0) + w4 * 7296;
            const uint32_t stg = hw ? hstg : buf;
            if (it == 1) {
                if (hw) {
                    mbar_wait(bar + 8 * (BAR_FULL + xkb), 0);
#pragma unroll 1
                    for (int hf = 0; hf < 2; hf++) {
                        const int r = w4 * 32 + hf * 16 + (lane & 15);
                        uint32_t* xt = (uint32_t*)scr->xt + ((xkb + rot) * 16 + (g >> 2)) * 4096 + (bi_i * 16 + w4 * 4 + hf * 2) * 16 + (g & 3) * 4 + q;
#pragma unroll
                        for (int cb = 0; cb < 8; cb += 2) {
                            uint32_t v[4];
                            ldsm4t(v, sb + xkb * SLOT + r * 128 + (((cb + (lane >> 4)) ^ (r & 7)) << 4));
                            xt[cb * 8192] = v[0]; xt[cb * 8192 + 16] = v[1]; xt[cb * 8192 + 8192] = v[2]; xt[cb * 8192 + 8192 + 16] = v[3];
                        }
                    }
                    __syncwarp();
                    if (lane == 0) mbar_arrive(bar + 8 * BAR_XT);
                    if (warp == 12) {
                        STAMP(26);
                        mbar_wait(bar + 8 * BAR_XT, 0);
                        if (lane == 0) asm volatile("red.release.gpu.global.add.u32 [%0],8;" ::"l"(scr->xcnt + (xkb + rot) * 32) : "memory");
                        __syncwarp();
                        STAMP(27);
                    }
                    {
                        const uint32_t old = tag ^ 1u;
                        const uint4 z4 = make_uint4(old, 0, old, 0);
#pragma unroll
                        for (int v = 0; v < 5; v++) if (v < 4 || st < 32) st_rlx128(scr->kvp + bi * 544 + v * 128 + st, z4);
                        if (st < 16) st_rlx128(scr->o + ((bi_i * 8 + (st >> 1)) * 32 + bi_j * 4 + 3) * 32 + 30 + (st & 1), z4);
                        if (lane < 8) st_rlx64(kvf_h + ((bi_i & 3) * 8 + w4 * 2 + (lane & 1)) * 4 + (lane >> 1), old, 0);
                        if (st < 4 && !(bi_i & 1)) st_rlx64(kvf_h + (64 + qq) * 2 + (lane & 1), old, 0);
                        __syncwarp();
                        if (lane == 0) mbar_arrive(bar + 8 * BAR_PREP);
                    }
                    mbar_wait(bar + 8 * BAR_SP2, 0);
                }
            }
            const int sh = it * 16;
            auto pick = [&](uint32_t v) { return __uint_as_float((v >> sh) << 16); };
            const float ea = bf_round(expf(pick(pla)));
            const float arl = (-ea * dt) * 1.4426950408889634f, ait = (pick(pai) * dt) * 0.15915494309189535f;
            cf C2; C2.re = 2.0f * (pick(pcr) * dt); C2.im = 2.0f * (pick(pci) * dt);
            const cf z1 = cexp_p(arl, ait, 1.0f), z128 = cexp_p(arl, ait, 128.0f);
            cf z8 = cexp_p(arl, ait, 8.0f); z8.im = -z8.im;
            const uint32_t lp = stg + lane * 4;
            auto put = [&](int row, const cf& v) { sts32((lp ^ ((row & 7) << 4)) + row * 128, pack2(v.re, v.im)); };
            {
                const cf z16 = cmul(z8, z8);
                cf e; e.re = 1.f; e.im = 0.f;
                cf o = z8;
                put(0, e); put(1, o);
                e = z16; put(2, e);
#pragma unroll
                for (int b = 3; b < 16; b += 2) {
                    o = cmul(o, z16); put(b, o);
                    if (b + 1 < 16) { e = cmul(e, z16); put(b + 1, e); }
                }
            }
            cf h[8];
            h[0] = C2; put(16, h[0]);
            {
                const cf z2 = cmul(z1, z1);
                h[1] = cmul(h[0], z1);
#pragma unroll
                for (int r = 2; r < 8; r++) h[r] = cmul(h[r - 2], z2);
#pragma unroll
                for (int r = 1; r < 8; r++) put(16 + r, h[r]);
            }
#pragma unroll
            for (int r = 0; r < 8; r++) { h[r] = cmul(h[r], z128); put(24 + r, h[r]); }
#pragma unroll
            for (int al = 0; al < 2; al++)
#pragma unroll
                for (int r = 0; r < 4; r++) { h[2 * r] = cmul(h[2 * r], z128); put(32 + al * 4 + r, h[2 * r]); }
#pragma unroll
            for (int al = 0; al < 4; al++)
#pragma unroll
                for (int r = 0; r < 2; r++) { h[4 * r] = cmul(h[4 * r], z128); put(40 + al * 2 + r, h[4 * r]); }
#pragma unroll
            for (int al = 0; al < 9; al++) { h[0] = cmul(h[0], z128); put(48 + al, h[0]); }
            __syncwarp();
            if (it == 1) {
                if (hw) {
                    int n = 0;
#pragma unroll 1
                    while (__any_sync(~0u, (int)(ld_acq(scr->xcnt + bi_j * 32) - (epoch1 << 7)) < 0)) { if (++n > SPIN_LIMIT) break; }
                    if (warp == 12) STAMP(15);
                    uint4 ur[8];
#pragma unroll
                    for (int v = 0; v < 8; v++) ur[v] = __ldcg(scr->xt + bi * 1024 + st + 128 * v);
                    if (lane < 16) sts128(ub - 256 + lane * 16, 0, 0, 0, 0);
#pragma unroll
                    for (int v = 0; v < 8; v++) {
                        const int ci = (st >> 2) + 32 * v;
                        sts128(sb + OFF_U + (st & 3) * U_STRIDE + 256 + ((ci ^ ((ci >> 3) & 1)) << 4), ur[v].x, ur[v].y, ur[v].z, ur[v].w);
                    }
                    __syncwarp();
                    if (lane == 0) mbar_arrive(bar + 8 * BAR_UR);
                    mbar_wait(bar + 8 * BAR_UR, 0);
                    if (warp == 12) STAMP(16);
                } else if (warp == 8) {
                    const int row = bi_j * 16 + (lane >> 1), half = lane & 1;
                    unsigned* gp = scr->g + (bi_i * 64 + bi_j * 8) * 8 + lane * 2;
                    st_rlx64(gp, tag ^ 1u, tag ^ 1u);
                    if (lane < 8) st_rlx32(scr->yflag + bi * 8 + lane, tag ^ 1u);
                    float gs0 = 0.f, gs1 = 0.f;
                    mbar_wait(bar + 8 * BAR_WPHI, 0);
#pragma unroll 1
                    for (int kb = 0; kb < 8; kb++) {
                        const int s = kb & 3;
                        mbar_wait(bar + 8 * (BAR_FULL + s), kb >> 2);
#pragma unroll
                        for (int c = 0; c < 4; c++) {
                            const uint4 xv = lds128(sb + s * SLOT + row * 128 + (((half * 4 + c) ^ (row & 7)) << 4));
                            const uint4 gw = lds128(sb + OFF_GW + ((kb + rot) & 7) * 128 + half * 64 + c * 16);
                            const uint32_t p0 = hmul2(xv.x, gw.x), p1 = hmul2(xv.y, gw.y), p2 = hmul2(xv.z, gw.z), p3 = hmul2(xv.w, gw.w);
                            gs0 += (bf_lo(p0) + bf_lo(p1)) + (bf_lo(p2) + bf_lo(p3));
                            gs1 += (bf_hi(p0) + bf_hi(p1)) + (bf_hi(p2) + bf_hi(p3));
                        }
                        if (kb < 5) {
                            mbar_wait(bar + 8 * (BAR_EMPTY + s), kb >> 2);
                            if (kb == xkb) mbar_wait(bar + 8 * BAR_XT, 0);
                            if (lane == 0) {
                                STAMP(48 + kb);
                                if (kb < 4) load_stage(kb + 4);
                                else mbar_arrive(bar + 8 * BAR_SP2);
                            }
                        }
                        __syncwarp();
                    }
                    if (lane == 0) mbar_arrive(bar + 8 * BAR_DONE);
                    float gs = gs0 + gs1;
                    gs += __shfl_xor_sync(~0u, gs, 1);
                    const uint32_t gv = __float_as_uint(bf_round(rcp(1.0f + ex2(-1.4426950408889634f * bf_round(gs))))) | tag;
                    st_rlx64(gp, gv, gv);
                }
                mbar_wait(bar + 8 * BAR_DONE, 0);
            }
            const int lr = lane & 7, lm = lane >> 3;
#pragma unroll
            for (int kp = 0; kp < 2; kp++) {
                uint32_t a0[4], a1[4];
                ldsm4(a0, stg + ((lm & 1) * 8 + lr) * 128 + (((4 * kp + (lm >> 1)) ^ lr) << 4));
                ldsm4(a1, stg + ((lm & 1) * 8 + lr) * 128 + (((4 * kp + 2 + (lm >> 1)) ^ lr) << 4));
#pragma unroll
                for (int t = 0; t < 6; t++) {
                    uint32_t b[4];
                    ldsm4(b, stg + (16 + 8 * t + lr) * 128 + (((4 * kp + lm) ^ lr) << 4));
                    mma16816(kc + 4 * t, a0[0], a0[1], a0[2], a0[3], b[0], b[1]);
                    mma16816(kc + 4 * t, a1[0], a1[1], a1[2], a1[3], b[2], b[3]);
                }
            }
            __syncwarp();
            if (it == 0) {
                if (lane == 0) mbar_arrive(bar + 8 * BAR_KGA);
                if (hw) {
                    asm volatile("fence.proxy.async.shared::cta;" ::: "memory");
                    bar_named(5, 128);
                    if (st == 0) load_stage(3);
                    if (warp == 12) STAMP(22);
                }
            } else if (hw) {
#pragma unroll
                for (int t = 0; t < 6; t++)
                    sts128(stg + (t * 32 + lane) * 16, __float_as_uint(kc[4 * t]), __float_as_uint(kc[4 * t + 1]), __float_as_uint(kc[4 * t + 2]), __float_as_uint(kc[4 * t + 3]));
                asm volatile("fence.proxy.async.shared::cta;" ::: "memory");
                __syncwarp();
                if (lane == 0) mbar_arrive(bar + 8 * BAR_KG);
            } else {
                mbar_wait(bar + 8 * BAR_KG, 0);
#pragma unroll
                for (int t = 0; t < 6; t++) {
                    const uint4 v = lds128(hstg + (t * 32 + lane) * 16);
                    kc[4 * t] += __uint_as_float(v.x); kc[4 * t + 1] += __uint_as_float(v.y); kc[4 * t + 2] += __uint_as_float(v.z); kc[4 * t + 3] += __uint_as_float(v.w);
                }
                asm volatile("fence.proxy.async.shared::cta;" ::: "memory");
                __syncwarp();
                if (lane == 0) mbar_arrive(bar + 8 * BAR_SP);
            }
        }
        if (!hw) {
            if (warp == 8) STAMP(17);
            if (lane == 0) kc[4 * 0 + 0] += ((ch & 1) ? bf_hi(pds) : bf_lo(pds));
            const uint32_t k1024 = __shfl_sync(~0u, pack2(kc[4 * 4 + 0], 0.f), 0);
#pragma unroll
            for (int i = 0; i < 2; i++) {
                const int be = g + 8 * i;
#pragma unroll
                for (int t = 0; t < 2; t++) {
                    const uint32_t a = kb_ + (KW_D + 128 * t + 8 * be + 2 * q) * 4;
                    const uint32_t w = pack2(kc[4 * t + 2 * i + 1], kc[4 * t + 2 * i]);
                    sts32(a + 4, w); sts16(a, w >> 16); sts16(a + 10, w);
                }
                {
                    const int p = 256 + 128 * (q >> 1) + 8 * be + 4 * (q & 1);
                    const uint32_t a = kb_ + (KW_D + p) * 4;
                    const uint32_t w = pack2(kc[4 * 2 + 2 * i + 1], kc[4 * 2 + 2 * i]);
                    const uint32_t aa = (w >> 16) | (w & 0xffff0000u);
                    if (p != 256) { sts16(a - 4, aa); sts32(a, aa); } else sts16(a, aa);
                    sts32(a + 4, aa); sts32(a + 8, w); sts16(a + 14, w);
                }
                {
                    const int k = 64 + 16 * q + be;
                    const uint32_t w = pack2(kc[4 * 3 + 2 * i], kc[4 * 3 + 2 * i + 1]);
                    if (k != 64) sts16(kb_ + (KW_2 + ((k - 1) >> 1) - 24) * 4 + (k & 1) * 2, w);
                    else {
                        const uint32_t a = kb_ + (KW_D + 511) * 4, aa = (w << 16) | (w & 0xffffu);
                        sts16(a, w); sts32(a + 4, aa); sts32(a + 8, aa); sts32(a + 12, aa); sts16(a + 18, w);
                    }
                    sts16(kb_ + (KW_2 + 48 + (k >> 1) - 24) * 4 + ((k & 1) ^ 1) * 2, w >> 16);
                }
#pragma unroll
                for (int b = 0; b < 2; b++) {
                    const int k = 64 + 8 * (2 * q + b) + (be >> 1);
                    const uint32_t w = pack2(kc[4 * 4 + 2 * i + b], 0.f);
                    if (!(be & 1) && k == 64) sts16(kb_ + (KW_2 + 63 - 24) * 4, w);
                    else {
                        const uint32_t a = kb_ + (KW_3 + ((be & 1) ? 80 + k : k - 1) - 48) * 4;
                        sts16(a, w);
                        if (!((be & 1) && k == 127)) sts16(a + 6, w);
                    }
                }
            }
            if (lane == 0) sts16(kb_ + (KW_3 + 127 - 48) * 4, pack2(kc[4 * 5 + 0], 0.f));
            __syncwarp();
            mbar_wait(bar + 8 * BAR_UR, 0);
            if (warp == 8) STAMP(23);
            float y[16][4];
#pragma unroll
            for (int nt = 0; nt < 16; nt++) { y[nt][0] = y[nt][1] = y[nt][2] = y[nt][3] = 0.f; }
            {
                uint32_t Bp[32], A[5][3];
                auto uaddr = [&](int rho) { const int R0 = (lane >> 4) * 8 + (lane & 7) - rho; return ub + (((2 * R0 + ((lane >> 3) & 1)) ^ ((R0 >> 2) & 1)) << 4); };
                const uint32_t kd = kb_ + (KW_D + g - 2 * q) * 4;
                auto lda = [&](int rho) {
#pragma unroll
                    for (int ga = 0; ga < 5; ga++) {
                        const uint32_t a = kd + (ga < 4 ? rho : (rho & 1)) * 64 + ga * 512;
                        A[ga][0] = lds32(a); A[ga][1] = lds32(a + 32); A[ga][2] = lds32(a - 32);
                    }
                };
                {
                    const uint32_t a = uaddr(0);
#pragma unroll
                    for (int p = 0; p < 8; p++) ldsm4(Bp + 4 * p, a + p * 512);
                }
#pragma unroll 1
                for (int rho = 0; rho < 8; rho++) {
                    lda(rho);
                    if (rho < 2) {
#pragma unroll
                        for (int nt = 4; nt < 16; nt++) mma16816(y[nt], A[4][0], A[4][1], A[4][2], A[4][0], Bp[2 * (nt - 4)], Bp[2 * (nt - 4) + 1]);
                    }
#pragma unroll
                    for (int ga = 0; ga < 3; ga++)
#pragma unroll
                        for (int nt = 15; nt >= ga; nt--) mma16816(y[nt], A[ga][0], A[ga][1], A[ga][2], A[ga][0], Bp[2 * (nt - ga)], Bp[2 * (nt - ga) + 1]);
                    const uint32_t an = uaddr(rho + 1);
                    ldsm4(Bp + 28, an + 7 * 512);
#pragma unroll
                    for (int nt = 15; nt >= 3; nt--) {
                        mma16816(y[nt], A[3][0], A[3][1], A[3][2], A[3][0], Bp[2 * (nt - 3)], Bp[2 * (nt - 3) + 1]);
                        if (nt & 1) ldsm4(Bp + 2 * (nt - 3), an + ((nt - 3) >> 1) * 512);
                    }
                }
            }
            if (warp == 8) STAMP(18);
            mbar_wait(bar + 8 * BAR_WR, 0);
#pragma unroll 1
            for (int ph = 0; ph < 2; ph++) {
                uint32_t B[5][2];
                const uint32_t ka = kb_ + (KW_2 + ph * 48 + 8 + g - q) * 4;
#pragma unroll
                for (int dd = 0; dd < 5; dd++) { B[dd][0] = lds32(ka + dd * 32); B[dd][1] = lds32(ka + dd * 32 - 16); }
                const uint32_t wa = buf + ph * W3_OFF + ((lane & 7) + ((lane >> 3) & 1) + (lane >> 4) * 8) * 16;
#pragma unroll
                for (int s = 0; s < 12; s++) {
                    uint32_t A[4];
                    ldsm4t(A, wa + s * 256);
#pragma unroll
                    for (int dd = 0; dd < 5; dd++)
                        if (s + 4 + dd < 16) mma16816(y[s + 4 + dd], A[0], A[1], A[2], A[3], B[dd][0], B[dd][1]);
                }
            }
            {
                const int ap = (lane & 7) + (lane >> 4) * 8;
                const uint32_t loff = ((2 * ap + ((lane >> 3) & 1)) ^ ((ap >> 2) & 1)) << 4;
#pragma unroll 1
                for (int ph = 0; ph < 2; ph++) {
                    uint32_t B[8][2];
                    const uint32_t wb = (ph ? spare : buf + W9_OFF) + loff;
                    const uint32_t ka = kb_ + (KW_3 + ph * 80 + 16 + g - 2 * q) * 4;
#pragma unroll
                    for (int dd = 0; dd < 8; dd++) { B[dd][0] = lds32(ka + dd * 32); B[dd][1] = lds32(ka + dd * 32 - 32); }
#pragma unroll
                    for (int s = 0; s < 4; s++) {
                        uint32_t A[4];
                        ldsm4t(A, wb + s * 512);
#pragma unroll
                        for (int dd = 0; dd < 8; dd++)
                            if (8 + 2 * s + dd < 16) mma16816(y[8 + 2 * s + dd], A[0], A[1], A[2], A[3], B[dd][0], B[dd][1]);
                    }
                }
                const uint32_t idw = (g == 2 * q) ? k1024 : ((g == 2 * q + 1) ? (k1024 << 16) : 0u);
#pragma unroll
                for (int s = 0; s < 4; s++) {
                    uint32_t A[4];
                    ldsm4t(A, spare + 2048 + loff + s * 512);
                    mma16816(y[8 + 2 * s], A[0], A[1], A[2], A[3], idw, 0u);
                    mma16816(y[9 + 2 * s], A[0], A[1], A[2], A[3], 0u, idw);
                }
            }
            __syncwarp();
            if (warp == 8) STAMP(19);
#pragma unroll
            for (int nt = 0; nt < 16; nt++)
#pragma unroll
                for (int b = 0; b < 2; b++) sts32(buf + ((8 * nt + 2 * q + b) * 8 + g) * 4, pack2(y[nt][b], y[nt][2 + b]));
            bar_named(2, 128);
            uint4* yp = scr->y + bi * 1024 + st;
#pragma unroll
            for (int v = 0; v < 8; v++) {
                const uint32_t a = sb + OFF_BUF + (st + 128 * v) * 4;
                const uint32_t w0 = lds32(a), w1 = lds32(a + BUF_STRIDE), w2 = lds32(a + 2 * BUF_STRIDE), w3 = lds32(a + 3 * BUF_STRIDE);
                st_rlx128(yp + v * 128, tag4(__byte_perm(w0, w1, 0x5410), __byte_perm(w0, w1, 0x7632), __byte_perm(w2, w3, 0x5410), __byte_perm(w2, w3, 0x7632), tag));
            }
            if (st < 8) st_rlx32(scr->yflag + bi * 8 + st, tag);
            if (warp == 8) STAMP(20);
        } else {
            asm volatile("setmaxnreg.dec.sync.aligned.u32 64;");
            mbar_wait(bar + 8 * BAR_SP, 0);
            if (lane < 2) sts128(buf + lane * W3_OFF, 0, 0, 0, 0);
            if (warp == 13) {
                if (lane == 0) {
                    mbar_expect(bar + 8 * BAR_WO, 65536);
                    tma2d(sb, &mwo, (bi_j & 3) * 128, 0, bar + 8 * BAR_WO);
                    tma2d(sb + SLOT, &mwo, (bi_j & 3) * 128 + 64, 0, bar + 8 * BAR_WO);
                }
                __syncwarp();
            }
            windows(5, 0);
            __syncwarp();
            if (lane == 0) mbar_arrive(bar + 8 * BAR_WR);
            if (warp == 12) STAMP(24);
            mbar_wait(bar + 8 * BAR_PUB, 0);
            if (warp == 12) STAMP(12);
#pragma unroll 1
            for (int zw = 0; zw < ((st < 32 && !(bi_i & 1)) ? 2 : 1); zw++) {
                const int kvf_n = zw ? 4 : 8;
                uint2* kvf_dst = kvf_h + (zw ? (64 + qq) * 2 + (lane & 1) : ((bi_i & 3) * 8 + w4 * 2 + (lane & 1)) * 4 + (lane >> 1));
                const uint4* src = scr->kvp + bi_j * (16 * 544) + (bi_i >> 2) * 136 +
                                   (zw ? (lane >> 2) * (2 * 544) + 128 + (lane & 1) * 4 + qq
                                       : (lane >> 3) * (4 * 544) + ((lane >> 1) & 3) * 32 + (bi_i & 3) * 8 + w4 * 2 + (lane & 1));
                const int s23 = zw ? 0 : 2 * 544;
                uint4 v[4];
                int n = 0;
#pragma unroll 1
                while (true) {
                    v[0] = ld_rlx128(src); v[1] = ld_rlx128(src + 544); v[2] = ld_rlx128(src + s23); v[3] = ld_rlx128(src + s23 + 544);
                    if (!__any_sync(~0u, (bad4(v[0], tag) | bad4(v[1], tag) | bad4(v[2], tag) | bad4(v[3], tag)) & 1)) break;
                    if (++n > SPIN_LIMIT) break;
                }
                float f[4];
                f[0] = __uint_as_float(v[2].x) + __uint_as_float(v[3].x); f[1] = __uint_as_float(v[2].y) + __uint_as_float(v[3].y);
                f[2] = __uint_as_float(v[2].z) + __uint_as_float(v[3].z); f[3] = __uint_as_float(v[2].w) + __uint_as_float(v[3].w);
                float e0 = __uint_as_float(v[0].x) + __uint_as_float(v[1].x), e1 = __uint_as_float(v[0].y) + __uint_as_float(v[1].y);
                float e2 = __uint_as_float(v[0].z) + __uint_as_float(v[1].z), e3 = __uint_as_float(v[0].w) + __uint_as_float(v[1].w);
                if (zw) {
                    e0 = __shfl_xor_sync(~0u, f[0], 4); e1 = __shfl_xor_sync(~0u, f[1], 4);
                    e2 = __shfl_xor_sync(~0u, f[2], 4); e3 = __shfl_xor_sync(~0u, f[3], 4);
                }
                f[0] += e0; f[1] += e1; f[2] += e2; f[3] += e3;
#pragma unroll
                for (int o = 8; o <= 16; o <<= 1)
#pragma unroll
                    for (int r = 0; r < 4; r++) f[r] += __shfl_xor_sync(~0u, f[r], o);
                if (lane < kvf_n) st_rlx64(kvf_dst, tagw(pack2(f[0], f[1]), tag), pack2(f[2], f[3]));
            }
            if (warp == 12) STAMP(13);
            if (st == 32) {
                mbar_expect(bar + 8 * BAR_WO2, 65536);
                tma2d(sb + OFF_P, &mwo, (bi_j & 3) * 128, 256, bar + 8 * BAR_WO2);
                tma2d(sb + OFF_V, &mwo, (bi_j & 3) * 128 + 64, 256, bar + 8 * BAR_WO2);
            }
            __syncwarp();
            {
                const uint4* kp = scr->kvf + bi_j * 272 + st;
                uint4 v0, v1, v2;
                int n = 0;
#pragma unroll 1
                while (true) {
                    v0 = ld_rlx128(kp); v1 = ld_rlx128(kp + 128); v2 = ld_rlx128(kp + (st < 16 ? 256 : 0));
                    if (!__any_sync(~0u, (bad4(v0, tag) | bad4(v1, tag) | bad4(v2, tag)) & 1)) break;
                    if (++n > SPIN_LIMIT) break;
                }
                sts128(sb + OFF_KVF + st * 16, v0.x, v0.y, v0.z, v0.w);
                sts128(sb + OFF_KVF + 2048 + st * 16, v1.x, v1.y, v1.z, v1.w);
                if (st < 16) sts128(sb + OFF_KVF + 4096 + st * 16, v2.x, v2.y, v2.z, v2.w);
                __syncwarp();
                if (lane == 0) mbar_arrive(bar + 8 * BAR_KVF);
            }
            if (warp == 12) STAMP(25);
        }
    }
    __syncwarp();
    if (lane == 0) {
        unsigned old;
        asm volatile("atom.acq_rel.cta.shared.add.u32 %0,[%1],1;" : "=r"(old) : "r"(bar + OFF_CNT) : "memory");
        if (old == 15) {
            atomicAdd(scr->done, 1u);
        }
    }
}

typedef CUresult (*EncFn)(CUtensorMap*, CUtensorMapDataType, cuuint32_t, void*, const cuuint64_t*, const cuuint64_t*, const cuuint32_t*,
                          const cuuint32_t*, CUtensorMapInterleave, CUtensorMapSwizzle, CUtensorMapL2promotion, CUtensorMapFloatOOBfill);

extern "C" void kernel_launch(void* const* d_in, const int* in_sizes, int n_in, void* d_out, int out_size) {
    static EncFn enc = nullptr;
    static Scratch* scr = nullptr;
    if (!enc) {
        cudaGetSymbolAddress((void**)&scr, g_scr);
        cudaDriverEntryPointQueryResult qr;
        cudaGetDriverEntryPoint("cuTensorMapEncodeTiled", (void**)&enc, cudaEnableDefault, &qr);
        cudaFuncSetAttribute(fused_kernel, cudaFuncAttributeMaxDynamicSharedMemorySize, SMEM_BYTES);
    }
    CUtensorMap mx, mw, mwo;
    const cuuint32_t es[3] = {1, 1, 1};
    {
        cuuint64_t d[2] = {512, 2048}, s[1] = {1024}; cuuint32_t b[2] = {64, 128};
        enc(&mx, CU_TENSOR_MAP_DATA_TYPE_BFLOAT16, 2, d_in[0], d, s, b, es, CU_TENSOR_MAP_INTERLEAVE_NONE, CU_TENSOR_MAP_SWIZZLE_128B,
            CU_TENSOR_MAP_L2_PROMOTION_L2_128B, CU_TENSOR_MAP_FLOAT_OOB_FILL_NONE);
    }
    {
        cuuint64_t d[3] = {512, 512, 3}, s[2] = {3072, 1024}; cuuint32_t b[3] = {64, 64, 3};
        enc(&mw, CU_TENSOR_MAP_DATA_TYPE_BFLOAT16, 3, d_in[1], d, s, b, es, CU_TENSOR_MAP_INTERLEAVE_NONE, CU_TENSOR_MAP_SWIZZLE_128B,
            CU_TENSOR_MAP_L2_PROMOTION_L2_128B, CU_TENSOR_MAP_FLOAT_OOB_FILL_NONE);
    }
    {
        cuuint64_t d[2] = {512, 512}, s[1] = {1024}; cuuint32_t b[2] = {64, 256};
        enc(&mwo, CU_TENSOR_MAP_DATA_TYPE_BFLOAT16, 2, d_in[3], d, s, b, es, CU_TENSOR_MAP_INTERLEAVE_NONE, CU_TENSOR_MAP_SWIZZLE_128B,
            CU_TENSOR_MAP_L2_PROMOTION_L2_128B, CU_TENSOR_MAP_FLOAT_OOB_FILL_NONE);
    }
    fused_kernel<<<128, 512, SMEM_BYTES, cudaStreamPerThread>>>(
        scr, (const bf16*)d_in[5], (const bf16*)d_in[6], (const bf16*)d_in[7], (const bf16*)d_in[8], (const bf16*)d_in[9],
        (const bf16*)d_in[10], (const bf16*)d_in[2], (const bf16*)d_in[11], (bf16*)d_out, mx, mw, mwo);
}
```

```cpp
#include <cuda_runtime.h>
#include <cuda.h>
#include <cuda_bf16.h>
#include <stdint.h>

typedef __nv_bfloat16 bf16;

struct Scratch {
    uint4 xt[128 * 1024];
    uint4 o[16 * 8 * 32 * 32];
    uint4 y[128 * 1024];
    uint4 kvp[8 * 16 * 544];
    uint4 kvf[8 * 4 * 68];
    unsigned g[1024 * 8];
    unsigned yflag[128 * 8];
    unsigned xcnt[8 * 32];
    unsigned done[32];
};
__device__ Scratch g_scr;
#define STAMP(n)

constexpr int SLOT = 40960;
constexpr int OFF_SP0 = 32768, OFF_SP1 = SLOT + 32768;
constexpr int OFF_P = 2 * SLOT, OFF_V = OFF_P + 32768;
constexpr int OFF_KVF = OFF_V + 32768;
constexpr int KT_BYTES = 3264, KW_D = 16, KW_2 = 560, KW_3 = 656;
constexpr int OFF_U = 4 * SLOT, U_STRIDE = 4096 + 256 + 32;
constexpr int OFF_BUF = OFF_U + 4 * U_STRIDE, BUF_STRIDE = 8320;
constexpr int OFF_K = OFF_BUF + 4 * BUF_STRIDE;
constexpr int OFF_WPHI = OFF_K + 4 * KT_BYTES;
constexpr int OFF_GW = OFF_WPHI + 2048;
constexpr int OFF_BAR = OFF_GW + 1024;
constexpr int SMEM_BYTES = OFF_BAR + 256 + 256;
static_assert(SMEM_BYTES <= 232448 && OFF_BUF % 128 == 0, "smem");
constexpr int W5_OFF = 0, W3_OFF = 3088, W9_OFF = 6176;
constexpr int BAR_FULL = 0, BAR_EMPTY = 4, BAR_WPHI = 8, BAR_WO = 9, BAR_WO2 = 10, BAR_XT = 11, BAR_DONE = 12, BAR_KG = 13, BAR_SP = 14,
              BAR_PUB = 15, BAR_KVF = 16, BAR_UR = 17, BAR_WR = 18, BAR_PREP = 19, BAR_KGA = 20, BAR_SP2 = 21, OFF_CNT = 192;
constexpr int SPIN_LIMIT = 1 << 17;

__device__ __forceinline__ uint32_t s2u(const void* p) { return (uint32_t)__cvta_generic_to_shared(p); }
__device__ __forceinline__ void mbar_init(uint32_t b, int c) { asm volatile("mbarrier.init.shared::cta.b64 [%0],%1;" ::"r"(b), "r"(c) : "memory"); }
__device__ __forceinline__ void mbar_expect(uint32_t b, int bytes) { asm volatile("mbarrier.arrive.expect_tx.shared::cta.b64 _,[%0],%1;" ::"r"(b), "r"(bytes) : "memory"); }
__device__ __forceinline__ void mbar_arrive(uint32_t b) { asm volatile("mbarrier.arrive.shared::cta.b64 _,[%0];" ::"r"(b) : "memory"); }
__device__ __forceinline__ void mbar_wait(uint32_t b, int ph) {
    asm volatile("{\n.reg .pred p;\n.reg .u32 n;\nmov.u32 n,0;\nLW_%=:\nmbarrier.try_wait.parity.shared::cta.b64 p,[%0],%1;\n@p bra LD_%=;\n"
                 "add.u32 n,n,1;\nsetp.lt.u32 p,n,16384;\n@p bra LW_%=;\nLD_%=:\n}" ::"r"(b), "r"(ph) : "memory");
}
__device__ __forceinline__ void tma2d(uint32_t dst, const CUtensorMap* m, int c0, int c1, uint32_t bar) {
    asm volatile("cp.async.bulk.tensor.2d.shared::cluster.global.mbarrier::complete_tx::bytes [%0],[%1,{%3,%4}],[%2];" ::"r"(dst), "l"(m), "r"(bar), "r"(c0), "r"(c1) : "memory");
}
__device__ __forceinline__ void tma3d(uint32_t dst, const CUtensorMap* m, int c0, int c1, int c2, uint32_t bar) {
    asm volatile("cp.async.bulk.tensor.3d.shared::cluster.global.mbarrier::complete_tx::bytes [%0],[%1,{%3,%4,%5}],[%2];" ::"r"(dst), "l"(m), "r"(bar), "r"(c0), "r"(c1), "r"(c2) : "memory");
}
__device__ __forceinline__ void bulk_g2s(uint32_t dst, const void* src, int bytes, uint32_t bar) {
    asm volatile("cp.async.bulk.shared::cluster.global.mbarrier::complete_tx::bytes [%0],[%1],%2,[%3];" ::"r"(dst), "l"(src), "r"(bytes), "r"(bar) : "memory");
}
__device__ __forceinline__ uint64_t mkdesc(uint32_t addr, uint32_t lbo, uint32_t sbo) {
    return (uint64_t)((addr & 0x3FFFF) >> 4) | ((uint64_t)(lbo >> 4) << 16) | ((uint64_t)(sbo >> 4) << 32) | ((uint64_t)1 << 62);
}
__device__ __forceinline__ void wg_fence() { asm volatile("wgmma.fence.sync.aligned;" ::: "memory"); }
__device__ __forceinline__ void wg_commit() { asm volatile("wgmma.commit_group.sync.aligned;" ::: "memory"); }
template <int N> __device__ __forceinline__ void wg_wait() { asm volatile("wgmma.wait_group.sync.aligned %0;" ::"n"(N) : "memory"); }
template <int N> __device__ __forceinline__ void fence_regs(float* d) {
#pragma unroll
    for (int i = 0; i < N; i++) asm volatile("" : "+f"(d[i])::"memory");
}
#define R8(d, o) "+f"(d[o]), "+f"(d[o + 1]), "+f"(d[o + 2]), "+f"(d[o + 3]), "+f"(d[o + 4]), "+f"(d[o + 5]), "+f"(d[o + 6]), "+f"(d[o + 7])
__device__ __forceinline__ void wgmma192(float* d, uint64_t da, uint64_t db) {
    asm volatile("wgmma.mma_async.sync.aligned.m64n192k16.f32.bf16.bf16 {"
                 "%0,%1,%2,%3,%4,%5,%6,%7,%8,%9,%10,%11,%12,%13,%14,%15,%16,%17,%18,%19,%20,%21,%22,%23,%24,%25,%26,%27,%28,%29,%30,%31,"
                 "%32,%33,%34,%35,%36,%37,%38,%39,%40,%41,%42,%43,%44,%45,%46,%47,%48,%49,%50,%51,%52,%53,%54,%55,%56,%57,%58,%59,%60,%61,%62,%63,"
                 "%64,%65,%66,%67,%68,%69,%70,%71,%72,%73,%74,%75,%76,%77,%78,%79,%80,%81,%82,%83,%84,%85,%86,%87,%88,%89,%90,%91,%92,%93,%94,%95},"
                 "%96,%97,1,1,1,0,1;"
                 : R8(d, 0), R8(d, 8), R8(d, 16), R8(d, 24), R8(d, 32), R8(d, 40), R8(d, 48), R8(d, 56), R8(d, 64), R8(d, 72), R8(d, 80), R8(d, 88)
                 : "l"(da), "l"(db));
}
__device__ __forceinline__ void wgmma64_tt(float* d, uint64_t da, uint64_t db, int sc) {
    asm volatile("{.reg .pred p; setp.ne.b32 p,%34,0; wgmma.mma_async.sync.aligned.m64n64k16.f32.bf16.bf16 {"
                 "%0,%1,%2,%3,%4,%5,%6,%7,%8,%9,%10,%11,%12,%13,%14,%15,%16,%17,%18,%19,%20,%21,%22,%23,%24,%25,%26,%27,%28,%29,%30,%31},"
                 "%32,%33,p,1,1,1,1;}"
                 : R8(d, 0), R8(d, 8), R8(d, 16), R8(d, 24)
                 : "l"(da), "l"(db), "r"(sc));
}
__device__ __forceinline__ void wgmma128_rs(float* d, const uint4& a, uint64_t db, int sc) {
    asm volatile("{.reg .pred p; setp.ne.b32 p,%69,0; wgmma.mma_async.sync.aligned.m64n128k16.f32.bf16.bf16 {"
                 "%0,%1,%2,%3,%4,%5,%6,%7,%8,%9,%10,%11,%12,%13,%14,%15,%16,%17,%18,%19,%20,%21,%22,%23,%24,%25,%26,%27,%28,%29,%30,%31,"
                 "%32,%33,%34,%35,%36,%37,%38,%39,%40,%41,%42,%43,%44,%45,%46,%47,%48,%49,%50,%51,%52,%53,%54,%55,%56,%57,%58,%59,%60,%61,%62,%63},"
                 "{%64,%65,%66,%67},%68,p,1,1,1;}"
                 : R8(d, 0), R8(d, 8), R8(d, 16), R8(d, 24), R8(d, 32), R8(d, 40), R8(d, 48), R8(d, 56)
                 : "r"(a.x), "r"(a.y), "r"(a.z), "r"(a.w), "l"(db), "r"(sc));
}
__device__ __forceinline__ void mma16816(float* c, uint32_t a0, uint32_t a1, uint32_t a2, uint32_t a3, uint32_t b0, uint32_t b1) {
    asm("mma.sync.aligned.m16n8k16.row.col.f32.bf16.bf16.f32 {%0,%1,%2,%3},{%4,%5,%6,%7},{%8,%9},{%0,%1,%2,%3};"
        : "+f"(c[0]), "+f"(c[1]), "+f"(c[2]), "+f"(c[3]) : "r"(a0), "r"(a1), "r"(a2), "r"(a3), "r"(b0), "r"(b1));
}
__device__ __forceinline__ void ldsm4(uint32_t* r, uint32_t a) {
    asm volatile("ldmatrix.sync.aligned.m8n8.x4.shared.b16 {%0,%1,%2,%3},[%4];" : "=r"(r[0]), "=r"(r[1]), "=r"(r[2]), "=r"(r[3]) : "r"(a) : "memory");
}
__device__ __forceinline__ void ldsm4t(uint32_t* r, uint32_t a) {
    asm volatile("ldmatrix.sync.aligned.m8n8.x4.trans.shared.b16 {%0,%1,%2,%3},[%4];" : "=r"(r[0]), "=r"(r[1]), "=r"(r[2]), "=r"(r[3]) : "r"(a) : "memory");
}
__device__ __forceinline__ void stsm4(uint32_t a, uint32_t r0, uint32_t r1, uint32_t r2, uint32_t r3) {
    asm volatile("stmatrix.sync.aligned.m8n8.x4.shared.b16 [%0],{%1,%2,%3,%4};" ::"r"(a), "r"(r0), "r"(r1), "r"(r2), "r"(r3) : "memory");
}
__device__ __forceinline__ uint32_t lds32(uint32_t a) { uint32_t v; asm volatile("ld.shared.b32 %0,[%1];" : "=r"(v) : "r"(a) : "memory"); return v; }
__device__ __forceinline__ uint4 lds128(uint32_t a) { uint4 v; asm volatile("ld.shared.v4.b32 {%0,%1,%2,%3},[%4];" : "=r"(v.x), "=r"(v.y), "=r"(v.z), "=r"(v.w) : "r"(a) : "memory"); return v; }
__device__ __forceinline__ void sts16(uint32_t a, uint32_t v) { asm volatile("st.shared.b16 [%0],%1;" ::"r"(a), "h"((unsigned short)v) : "memory"); }
__device__ __forceinline__ void sts32(uint32_t a, uint32_t v) { asm volatile("st.shared.b32 [%0],%1;" ::"r"(a), "r"(v) : "memory"); }
__device__ __forceinline__ void sts64(uint32_t a, uint32_t x, uint32_t y) { asm volatile("st.shared.v2.b32 [%0],{%1,%2};" ::"r"(a), "r"(x), "r"(y) : "memory"); }
__device__ __forceinline__ void sts128(uint32_t a, uint32_t x, uint32_t y, uint32_t z, uint32_t w) { asm volatile("st.shared.v4.b32 [%0],{%1,%2,%3,%4};" ::"r"(a), "r"(x), "r"(y), "r"(z), "r"(w) : "memory"); }
__device__ __forceinline__ uint32_t pack2(float lo, float hi) { uint32_t d; asm("cvt.rn.bf16x2.f32 %0,%1,%2;" : "=r"(d) : "f"(hi), "f"(lo)); return d; }
__device__ __forceinline__ float bf_lo(uint32_t v) { return __uint_as_float(v << 16); }
__device__ __forceinline__ float bf_hi(uint32_t v) { return __uint_as_float(v & 0xffff0000u); }
__device__ __forceinline__ float bf_round(float v) { return bf_lo(pack2(v, 0.f)); }
__device__ __forceinline__ uint32_t hmax2(uint32_t a, uint32_t b) { uint32_t d; asm("max.bf16x2 %0,%1,%2;" : "=r"(d) : "r"(a), "r"(b)); return d; }
__device__ __forceinline__ uint32_t hmin2(uint32_t a, uint32_t b) { uint32_t d; asm("min.bf16x2 %0,%1,%2;" : "=r"(d) : "r"(a), "r"(b)); return d; }
__device__ __forceinline__ uint32_t hmul2(uint32_t a, uint32_t b) { uint32_t d; asm("mul.rn.bf16x2 %0,%1,%2;" : "=r"(d) : "r"(a), "r"(b)); return d; }
__device__ __forceinline__ float ex2(float x) { float y; asm("ex2.approx.ftz.f32 %0,%1;" : "=f"(y) : "f"(x)); return y; }
__device__ __forceinline__ float rcp(float x) { float y; asm("rcp.approx.ftz.f32 %0,%1;" : "=f"(y) : "f"(x)); return y; }
__device__ __forceinline__ uint32_t ld_nc(const uint32_t* p) { uint32_t v; asm volatile("ld.global.nc.b32 %0,[%1];" : "=r"(v) : "l"(p)); return v; }
__device__ __forceinline__ uint2 ld_nc64(const uint2* p) { uint2 v; asm volatile("ld.global.nc.v2.b32 {%0,%1},[%2];" : "=r"(v.x), "=r"(v.y) : "l"(p)); return v; }
__device__ __forceinline__ unsigned ld_acq(const unsigned* p) { unsigned v; asm volatile("ld.acquire.gpu.global.u32 %0,[%1];" : "=r"(v) : "l"(p) : "memory"); return v; }
__device__ __forceinline__ unsigned ld_rlx(const unsigned* p) { unsigned v; asm volatile("ld.relaxed.gpu.global.u32 %0,[%1];" : "=r"(v) : "l"(p) : "memory"); return v; }
__device__ __forceinline__ uint2 ld_rlx64(const void* p) { uint2 v; asm volatile("{.reg .b64 t; ld.relaxed.gpu.global.b64 t,[%2]; mov.b64 {%0,%1},t;}" : "=r"(v.x), "=r"(v.y) : "l"(p) : "memory"); return v; }
__device__ __forceinline__ uint4 ld_rlx128(const void* p) {
    uint4 v;
    asm volatile("{.reg .b64 t,u; ld.relaxed.gpu.global.v2.b64 {t,u},[%4]; mov.b64 {%0,%1},t; mov.b64 {%2,%3},u;}" : "=r"(v.x), "=r"(v.y), "=r"(v.z), "=r"(v.w) : "l"(p) : "memory");
    return v;
}
__device__ __forceinline__ void st_rlx32(void* p, uint32_t x) { asm volatile("st.relaxed.gpu.global.u32 [%0],%1;" ::"l"(p), "r"(x) : "memory"); }
__device__ __forceinline__ void st_rlx64(void* p, uint32_t x, uint32_t y) { asm volatile("{.reg .b64 t; mov.b64 t,{%1,%2}; st.relaxed.gpu.global.b64 [%0],t;}" ::"l"(p), "r"(x), "r"(y) : "memory"); }
__device__ __forceinline__ void st_rlx128(void* p, uint4 v) {
    asm volatile("{.reg .b64 t,u; mov.b64 t,{%1,%2}; mov.b64 u,{%3,%4}; st.relaxed.gpu.global.v2.b64 [%0],{t,u};}" ::"l"(p), "r"(v.x), "r"(v.y), "r"(v.z), "r"(v.w) : "memory");
}
__device__ __forceinline__ uint32_t tagw(uint32_t w, uint32_t tag) { return (w & ~1u) | tag; }
__device__ __forceinline__ uint4 tag4(uint32_t x, uint32_t y, uint32_t z, uint32_t w, uint32_t tag) { return make_uint4(tagw(x, tag), y, tagw(z, tag), w); }
__device__ __forceinline__ uint32_t bad4(const uint4& v, uint32_t tag) { return (v.x ^ tag) | (v.z ^ tag); }
__device__ __forceinline__ void bar_named(int id, int n) { asm volatile("bar.sync %0,%1;" ::"r"(id), "r"(n) : "memory"); }

struct cf { float re, im; };
__device__ __forceinline__ cf cmul(cf a, cf b) { cf r; r.re = a.re * b.re - a.im * b.im; r.im = a.re * b.im + a.im * b.re; return r; }
__device__ __forceinline__ cf cexp_p(float arl, float ait, float p) {
    float mag = ex2(arl * p);
    float t = ait * p;
    t = (t - rintf(t)) * 6.283185307179586f;
    cf r; r.re = mag * __cosf(t); r.im = mag * __sinf(t);
    return r;
}

__device__ __forceinline__ void hedgehog2(const uint32_t* a, uint32_t wphi_addr, uint32_t (*out)[8]) {
    float p[2][2][4], mx[2][2];
#pragma unroll
    for (int h = 0; h < 2; h++) {
        uint32_t b[4];
        ldsm4t(b, wphi_addr + h * 512);
        float c0[4] = {0.f, 0.f, 0.f, 0.f}, c1[4] = {0.f, 0.f, 0.f, 0.f};
        mma16816(c0, a[4 * h], a[4 * h + 1], a[4 * h + 2], a[4 * h + 3], b[0], b[1]);
        mma16816(c1, a[4 * h], a[4 * h + 1], a[4 * h + 2], a[4 * h + 3], b[2], b[3]);
#pragma unroll
        for (int k = 0; k < 2; k++) {
            p[h][k][0] = c0[2 * k]; p[h][k][1] = c0[2 * k + 1]; p[h][k][2] = c1[2 * k]; p[h][k][3] = c1[2 * k + 1];
            mx[h][k] = fmaxf(fmaxf(p[h][k][0], p[h][k][1]), fmaxf(p[h][k][2], p[h][k][3]));
        }
    }
#pragma unroll
    for (int o = 1; o <= 2; o <<= 1)
#pragma unroll
        for (int h = 0; h < 2; h++)
#pragma unroll
            for (int k = 0; k < 2; k++) mx[h][k] = fmaxf(mx[h][k], __shfl_xor_sync(~0u, mx[h][k], o));
    const float L = 1.4426950408889634f;
    float pmin = 1.f;
#pragma unroll
    for (int h = 0; h < 2; h++)
#pragma unroll
        for (int k = 0; k < 2; k++) {
            const float m = -mx[h][k] * L;
            const float e0 = ex2(fmaf(p[h][k][0], L, m)), e1 = ex2(fmaf(p[h][k][1], L, m)), e2 = ex2(fmaf(p[h][k][2], L, m)), e3 = ex2(fmaf(p[h][k][3], L, m));
            const float p01 = e0 * e1, p23 = e2 * e3, pp = p01 * p23, r = rcp(pp), r01 = r * p23, r23 = r * p01;
            pmin = fminf(pmin, pp);
            out[h][k] = pack2(e0, e1); out[h][k + 2] = pack2(e2, e3);
            out[h][4 + k] = pack2(r01 * e1, r01 * e0); out[h][4 + k + 2] = pack2(r23 * e3, r23 * e2);
        }
    if (__builtin_expect(__any_sync(~0u, !(pmin > 1e-18f)), 0)) {
#pragma unroll
        for (int h = 0; h < 2; h++)
#pragma unroll
            for (int k = 0; k < 2; k++) {
                float m = fminf(fminf(p[h][k][0], p[h][k][1]), fminf(p[h][k][2], p[h][k][3]));
                m = fminf(m, __shfl_xor_sync(~0u, m, 1));
                m = fminf(m, __shfl_xor_sync(~0u, m, 2)) * L;
                out[h][4 + k] = pack2(ex2(fmaf(p[h][k][0], -L, m)), ex2(fmaf(p[h][k][1], -L, m)));
                out[h][4 + k + 2] = pack2(ex2(fmaf(p[h][k][2], -L, m)), ex2(fmaf(p[h][k][3], -L, m)));
            }
    }
}

__global__ void __launch_bounds__(512, 1)
fused_kernel(Scratch* __restrict__ scr, const bf16* __restrict__ logA, const bf16* __restrict__ Aim, const bf16* __restrict__ Cre,
             const bf16* __restrict__ Cim, const bf16* __restrict__ logdt, const bf16* __restrict__ Dskip, const bf16* __restrict__ wphi,
             const bf16* __restrict__ gatew, bf16* __restrict__ out,
             const __grid_constant__ CUtensorMap mx, const __grid_constant__ CUtensorMap mw, const __grid_constant__ CUtensorMap mwo) {
    extern __shared__ __align__(1024) uint8_t smem[];
    const uint32_t sb = s2u(smem);
    const int tid = threadIdx.x, warp = __shfl_sync(~0u, tid >> 5, 0), lane = tid & 31;
    const int g = lane >> 2, q = lane & 3, w4 = warp & 3;
    const int bi = blockIdx.x, bi_i = bi & 15, bi_j = bi >> 4;
    const uint32_t bar = sb + OFF_BAR;
    const int rot = (bi_j & 3) * 2, xkb = bi_j >> 2;
    auto load_stage = [&](int kb) {
        const uint32_t b = bar + 8 * (BAR_FULL + (kb & 3)), d = sb + (kb & 3) * SLOT;
        const int kc = ((kb + rot) & 7) * 64;
        mbar_expect(b, SLOT);
        tma2d(d, &mx, kc, bi_i * 128, b);
        tma3d(d + 16384, &mw, bi_j * 64, kc, 0, b);
    };

    const int ch = bi * 4 + w4;
    uint32_t pla = 0, pai = 0, pcr = 0, pci = 0, pdt = 0, pds = 0;
    if (warp >= 8) {
        const int pidx = ch * 64 + lane * 2 + (warp >= 12);
        pla = ld_nc((const uint32_t*)logA + pidx); pai = ld_nc((const uint32_t*)Aim + pidx);
        pcr = ld_nc((const uint32_t*)Cre + pidx); pci = ld_nc((const uint32_t*)Cim + pidx);
        pdt = ld_nc((const uint32_t*)logdt + (ch >> 1)); pds = ld_nc((const uint32_t*)Dskip + (ch >> 1));
    }
    unsigned done0 = ld_rlx(scr->done);
    if (tid == 0) {
        for (int s = 0; s < 4; s++) mbar_init(bar + 8 * (BAR_FULL + s), 1);
        asm volatile("fence.mbarrier_init.release.cluster;" ::: "memory");
        load_stage(0); load_stage(1); load_stage(2);
        STAMP(11);
    } else if (tid == 32) {
        if (sb & 1023) __trap();
        sts32(bar + OFF_CNT, 0);
        for (int s = 0; s < 4; s++) mbar_init(bar + 8 * (BAR_EMPTY + s), 8);
        mbar_init(bar + 8 * BAR_WPHI, 1); mbar_init(bar + 8 * BAR_WO, 1); mbar_init(bar + 8 * BAR_WO2, 1); mbar_init(bar + 8 * BAR_XT, 4);
        mbar_init(bar + 8 * BAR_DONE, 9); mbar_init(bar + 8 * BAR_KG, 4); mbar_init(bar + 8 * BAR_SP, 4); mbar_init(bar + 8 * BAR_PUB, 8);
        mbar_init(bar + 8 * BAR_KVF, 4); mbar_init(bar + 8 * BAR_UR, 4); mbar_init(bar + 8 * BAR_WR, 4); mbar_init(bar + 8 * BAR_PREP, 4); mbar_init(bar + 8 * BAR_KGA, 8); mbar_init(bar + 8 * BAR_SP2, 1);
        asm volatile("fence.mbarrier_init.release.cluster;" ::: "memory");
        mbar_expect(bar + 8 * BAR_WPHI, 3072);
        bulk_g2s(sb + OFF_GW, gatew, 1024, bar + 8 * BAR_WPHI);
        bulk_g2s(sb + OFF_WPHI, wphi + bi_j * 1024, 2048, bar + 8 * BAR_WPHI);
    } else if (tid == 64) {
        asm volatile("prefetch.tensormap [%0];" ::"l"(&mw) : "memory");
    }
    const uint32_t buf = sb + OFF_BUF + w4 * BUF_STRIDE, kb_ = sb + OFF_K + w4 * KT_BYTES;
    if ((warp >> 2) == 2) {
#pragma unroll
        for (int v = 0; v < 7; v++) if (v * 32 + lane < KT_BYTES / 16) sts128(kb_ + (v * 32 + lane) * 16, 0, 0, 0, 0);
    }
    __syncthreads();
    asm volatile("" : "+r"(pdt), "+r"(done0)::"memory");
    const unsigned epoch1 = (done0 >> 7) + 1u;
    const uint32_t tag = epoch1 & 1u;

    const int st = tid & 127;
    const uint32_t ub = sb + OFF_U + w4 * U_STRIDE + 256, spare = sb + (w4 < 2 ? OFF_SP0 : OFF_SP1) + (w4 & 1) * 4096;

    if (warp < 8) {
        const int wg = warp >> 2;
        if (warp == 0) STAMP(21);
        float acc[96];
        const int srow = warp * 16 + (lane & 15);
        const uint32_t srow_a = srow * 128;
        const int sx = srow & 7, shi = lane >> 4;
#pragma unroll
        for (int r = 0; r < 96; r++) acc[r] = 0.f;
        fence_regs<96>(acc);
        const uint64_t da0 = mkdesc(sb + wg * 8192, 16, 1024), db0 = mkdesc(sb + 16384, 8192, 1024);
        mbar_wait(bar + 8 * BAR_KGA, 0);
#pragma unroll 1
        for (int kb = 0; kb < 8; kb++) {
            const int s = kb & 3;
            const uint64_t da = da0 + s * (SLOT >> 4), db = db0 + s * (SLOT >> 4);
            if (warp == 0) STAMP(40 + kb);
            mbar_wait(bar + 8 * (BAR_FULL + s), kb >> 2);
            if (warp == 0) STAMP(32 + kb);
            wg_fence();
#pragma unroll
            for (int k = 0; k < 4; k++) wgmma192(acc, da + 2 * k, db + 128 * k);
            wg_commit();
            wg_wait<1>();
            if (lane == 0 && kb > 0) mbar_arrive(bar + 8 * (BAR_EMPTY + ((kb - 1) & 3)));
        }
        mbar_wait(bar + 8 * BAR_WPHI, 0);
        wg_wait<0>();
        fence_regs<96>(acc);
        if (lane == 0) mbar_arrive(bar + 8 * BAR_DONE);
        if (warp == 0) STAMP(1);
        uint32_t in[32], va[16];
#pragma unroll
        for (int r = 0; r < 16; r++) {
            in[r] = pack2(acc[32 + 2 * r], acc[32 + 2 * r + 1]);
            in[16 + r] = pack2(acc[2 * r], acc[2 * r + 1]);
            va[r] = pack2(acc[64 + 2 * r], acc[64 + 2 * r + 1]);
        }
        const uint32_t wphi_a = sb + OFF_WPHI + (lane & 15) * 32 + (lane >> 4) * 16;
        uint32_t pq[4][8];
#pragma unroll 1
        for (int it = 0; it < 4; it++) {
            hedgehog2(in, wphi_a + (it & 1) * 1024, pq + 2);
#pragma unroll
            for (int r = 0; r < 24; r++) in[r] = in[r + 8];
            if (it < 2) {
#pragma unroll
                for (int hs = 0; hs < 4; hs++) {
                    float c[4] = {0.f, 0.f, 0.f, 0.f};
                    uint32_t* o = pq[2 + (hs >> 1)] + 4 * (hs & 1);
                    mma16816(c, o[0], o[1], o[2], o[3], 0x3f803f80u, 0x3f803f80u);
                    const float r0 = rcp(c[0]), r1 = rcp(c[2]);
                    const uint32_t s0 = pack2(r0, r0), s1 = pack2(r1, r1);
                    o[0] = hmul2(o[0], s0); o[1] = hmul2(o[1], s1); o[2] = hmul2(o[2], s0); o[3] = hmul2(o[3], s1);
                }
                if (it == 0) mbar_wait(bar + 8 * BAR_DONE, 0);
                const uint32_t pt = sb + OFF_P + it * 16384 + srow_a, vt = sb + OFF_V + it * 16384 + srow_a;
#pragma unroll
                for (int hl = 0; hl < 2; hl++) {
                    stsm4(pt + (((4 * hl + shi) ^ sx) << 4), pq[2 + hl][0], pq[2 + hl][1], pq[2 + hl][2], pq[2 + hl][3]);
                    stsm4(pt + (((4 * hl + 2 + shi) ^ sx) << 4), pq[2 + hl][4], pq[2 + hl][5], pq[2 + hl][6], pq[2 + hl][7]);
                    stsm4(vt + (((2 * hl + shi) ^ sx) << 4), va[4 * hl], va[4 * hl + 1], va[4 * hl + 2], va[4 * hl + 3]);
                }
                if (lane < 16) sts128(vt + ((4 ^ sx) << 4), 0x3f803f80u, 0x3f803f80u, 0x3f803f80u, 0x3f803f80u);
#pragma unroll
                for (int r = 0; r < 8; r++) va[r] = va[r + 8];
            }
            if (it == 1) {
                asm volatile("fence.proxy.async.shared::cta;" ::: "memory");
                bar_named(1, 256);
                if (warp == 0) STAMP(2);
                float d[32];
                const uint64_t dv = mkdesc(sb + OFF_V + wg * 16384, 16, 1024), dp = mkdesc(sb + OFF_P + wg * 16384, 16, 1024);
                wg_fence();
#pragma unroll
                for (int k = 0; k < 8; k++) wgmma64_tt(d, dv + 128 * k, dp + 128 * k, k != 0);
                wg_commit();
                wg_wait<0>();
                fence_regs<32>(d);
                mbar_wait(bar + 8 * BAR_PREP, 0);
                uint4* kvp = scr->kvp + bi * 544 + wg * 272;
                if (w4 < 2) {
                    uint32_t e[16];
#pragma unroll
                    for (int r = 0; r < 16; r++) e[r] = __float_as_uint(w4 ? d[16 + r] : d[r]);
                    uint4* p = kvp + w4 * 136 + lane;
#pragma unroll
                    for (int ks = 0; ks < 2; ks++)
#pragma unroll
                        for (int nt = 0; nt < 2; nt++)
                            st_rlx128(p + (ks * 2 + nt) * 32, tag4(e[8 * ks + 2 * nt], e[8 * ks + 2 * nt + 1], e[8 * ks + 4 + 2 * nt], e[8 * ks + 4 + 2 * nt + 1], tag));
                } else if (w4 == 2 && lane < 4) {
#pragma unroll
                    for (int hl = 0; hl < 2; hl++)
#pragma unroll
                        for (int ks = 0; ks < 2; ks++)
                            st_rlx128(kvp + hl * 136 + 128 + ks * 4 + lane, tag4(__float_as_uint(d[16 * hl + 8 * ks]), __float_as_uint(d[16 * hl + 8 * ks + 1]),
                                                                                __float_as_uint(d[16 * hl + 8 * ks + 4]), __float_as_uint(d[16 * hl + 8 * ks + 5]), tag));
                }
                __syncwarp();
                if (lane == 0) mbar_arrive(bar + 8 * BAR_PUB);
                if (warp == 0) STAMP(3);
            }
            if (it == 2) {
#pragma unroll
                for (int r = 0; r < 8; r++) { pq[0][r] = pq[2][r]; pq[1][r] = pq[3][r]; }
            }
        }
        if (warp == 0) STAMP(4);
        asm volatile("setmaxnreg.inc.sync.aligned.u32 160;");
        {
            mbar_wait(bar + 8 * BAR_KVF, 0);
            uint4 kf[4][3];
#pragma unroll
            for (int hh = 0; hh < 4; hh++) {
                const uint32_t a = sb + OFF_KVF + hh * 1088;
                kf[hh][0] = lds128(a + lane * 32); kf[hh][1] = lds128(a + lane * 32 + 16); kf[hh][2] = lds128(a + 1024 + q * 16);
            }
            if (warp == 0) STAMP(5);
            uint4 own[4];
#pragma unroll
            for (int hh = 0; hh < 4; hh++) {
                float c[6][4];
#pragma unroll
                for (int t = 0; t < 6; t++) { c[t][0] = c[t][1] = c[t][2] = c[t][3] = 0.f; }
                const uint32_t* a = pq[hh];
                const bool od = g & 1;
                mma16816(c[0], a[0], a[1], a[2], a[3], od ? 0x3f803f80u : kf[hh][2].x, od ? 0x3f803f80u : kf[hh][2].y);
                mma16816(c[1], a[4], a[5], a[6], a[7], od ? 0x3f803f80u : kf[hh][2].z, od ? 0x3f803f80u : kf[hh][2].w);
                mma16816(c[2], a[0], a[1], a[2], a[3], kf[hh][0].x, kf[hh][0].y);
                mma16816(c[3], a[0], a[1], a[2], a[3], kf[hh][0].z, kf[hh][0].w);
                mma16816(c[4], a[4], a[5], a[6], a[7], kf[hh][1].x, kf[hh][1].y);
                mma16816(c[5], a[4], a[5], a[6], a[7], kf[hh][1].z, kf[hh][1].w);
                uint32_t w[4];
#pragma unroll
                for (int k = 0; k < 2; k++) {
                    const float rho = c[0][2 * k + 1] * rcp(c[1][2 * k + 1]);
                    const float r = rcp(fmaf(c[0][2 * k + 1], 1e-6f, fmaf(rho, c[1][2 * k], c[0][2 * k]))), rr = r * rho;
                    w[k] = pack2(fmaf(c[4][2 * k], rr, c[2][2 * k] * r), fmaf(c[4][2 * k + 1], rr, c[2][2 * k + 1] * r));
                    w[2 + k] = pack2(fmaf(c[5][2 * k], rr, c[3][2 * k] * r), fmaf(c[5][2 * k + 1], rr, c[3][2 * k + 1] * r));
                }
                own[hh] = tag4(w[0], w[1], w[2], w[3], tag);
            }
            uint4* og = scr->o + ((bi_i * 8 + warp) * 32 + bi_j * 4) * 32 + lane;
#pragma unroll
            for (int hh = 0; hh < 4; hh++) st_rlx128(og + hh * 32, own[hh]);
        }
        if (warp == 0) STAMP(6);
        float oc[64];
        const int slab = bi_i * 8 + (bi_j >> 2) * 4 + w4;
        const uint8_t* yb = (const uint8_t*)scr->y + (size_t)((bi_j & 3) * 32 + wg * 16 + (q >> 1)) * 16384 + slab * 128 + g * 16 + (q & 1) * 8;
        const unsigned* gp = scr->g + (slab * 8 + (g >> 1)) * 8 + (g & 1) * 4;
        uint2 yv[8]; unsigned g0, g1;
        {
            const uint4* osrc = scr->o + (slab * 32 + wg * 16) * 32 + lane;
            uint4 fr[16];
            const unsigned* probe = (const unsigned*)(osrc - lane + ((lane & 3) * 4 + 3) * 32 + 31) + 2;
            {
                unsigned miss = ~0u;
                int n = 0;
#pragma unroll
                for (int s = 0; s < 4; s++) {
#pragma unroll 1
                    while ((miss >> s) & 1) { miss = __ballot_sync(~0u, (ld_rlx(probe) ^ tag) & 1); if (++n > SPIN_LIMIT) break; }
#pragma unroll
                    for (int k = 4 * s; k < 4 * s + 4; k++) fr[k] = ld_rlx128(osrc + k * 32);
                }
            }
            if (warp == 0) STAMP(14);
            mbar_wait(bar + 8 * (wg ? BAR_WO2 : BAR_WO), 0);
            const uint64_t dw = mkdesc(sb + wg * 2 * SLOT, wg ? 32768 : SLOT, 1024);
#pragma unroll
            for (int s = 0; s < 4; s++) {
                int n = 0;
#pragma unroll 1
                while (__builtin_expect(__any_sync(~0u, (bad4(fr[4 * s], tag) | bad4(fr[4 * s + 1], tag) | bad4(fr[4 * s + 2], tag) | bad4(fr[4 * s + 3], tag)) & 1), 0)) {
#pragma unroll
                    for (int k = 4 * s; k < 4 * s + 4; k++) fr[k] = ld_rlx128(osrc + k * 32);
                    if (++n > SPIN_LIMIT) break;
                }
                wg_fence();
#pragma unroll
                for (int hh = 0; hh < 4; hh++) wgmma128_rs(oc, fr[4 * s + hh], dw + 128 * (4 * s + hh), (s | hh) != 0);
                wg_commit();
                if (s == 1) {
                    wg_wait<1>();
#pragma unroll
                    for (int nt = 0; nt < 8; nt++) yv[nt] = ld_rlx64(yb + nt * 32768);
                    g0 = ld_rlx(gp); g1 = ld_rlx(gp + 32);
                }
            }
            if (warp == 0) STAMP(7);
            {
                const unsigned* yprobe = scr->yflag + ((bi_j & 3) * 32 + wg * 16 + (lane & 15)) * 8;
                int n = 0;
#pragma unroll 1
                while (true) {
                    uint32_t bad = (g0 ^ tag) | (g1 ^ tag);
#pragma unroll
                    for (int nt = 0; nt < 8; nt++) bad |= yv[nt].x ^ tag;
                    if (!__any_sync(~0u, bad & 1)) break;
#pragma unroll 1
                    while (__any_sync(~0u, (ld_rlx(yprobe) ^ tag) & 1)) { if (++n > SPIN_LIMIT) break; }
#pragma unroll
                    for (int nt = 0; nt < 8; nt++) yv[nt] = ld_rlx64(yb + nt * 32768);
                    g0 = ld_rlx(gp); g1 = ld_rlx(gp + 32);
                    if (++n > SPIN_LIMIT) break;
                }
            }
            if (warp == 0) STAMP(28);
            wg_wait<0>();
            fence_regs<64>(oc);
        }
        {
            bar_named(3 + wg, 128);
            const uint32_t xw = sb + wg * 2 * SLOT + (tid & 127) * 16, xr = sb + (wg ^ 1) * 2 * SLOT + (tid & 127) * 16;
#pragma unroll
            for (int r = 0; r < 8; r++) {
                const float* o = oc + 4 * r;
                sts128(xw + r * 2048, __float_as_uint(wg ? o[0] : o[32]), __float_as_uint(wg ? o[1] : o[33]), __float_as_uint(wg ? o[2] : o[34]), __float_as_uint(wg ? o[3] : o[35]));
            }
#pragma unroll
            for (int r = 0; r < 32; r++) oc[r] = wg ? oc[32 + r] : oc[r];
            bar_named(1, 256);
            if (warp == 0) STAMP(8);
            const float ga = bf_hi(g0), gb = bf_hi(g1);
            const float ha = bf_round(1.0f - ga), hb = bf_round(1.0f - gb);
            uint32_t w[8][2];
#pragma unroll
            for (int nt = 0; nt < 8; nt++) {
                const uint4 p = lds128(xr + nt * 2048);
                w[nt][0] = pack2(fmaf(ga, oc[4 * nt] + __uint_as_float(p.x), ha * bf_lo(yv[nt].x)), fmaf(ga, oc[4 * nt + 1] + __uint_as_float(p.y), ha * bf_hi(yv[nt].x)));
                w[nt][1] = pack2(fmaf(gb, oc[4 * nt + 2] + __uint_as_float(p.z), hb * bf_lo(yv[nt].y)), fmaf(gb, oc[4 * nt + 3] + __uint_as_float(p.w), hb * bf_hi(yv[nt].y)));
            }
            const uint32_t ob = sb + wg * 2 * SLOT + 16384 + w4 * 2048;
#pragma unroll
            for (int nt = 0; nt < 8; nt += 2)
                stsm4(ob + (lane & 15) * 128 + (((nt + shi) ^ (lane & 7)) << 4), w[nt][0], w[nt][1], w[nt + 1][0], w[nt + 1][1]);
            __syncwarp();
            bf16* op = out + (size_t)(slab * 16) * 512 + (bi_j & 3) * 128 + wg * 64 + (lane & 7) * 8;
#pragma unroll
            for (int it = 0; it < 4; it++) {
                const int r = it * 4 + (lane >> 3);
                uint4 v = lds128(ob + r * 128 + (((lane & 7) ^ (r & 7)) << 4));
                *(uint4*)(op + r * 512) = v;
            }
        }
        if (warp == 0) STAMP(10);
    } else {
        const bool hw = warp >= 12;
        const int qq = (bi_i & 2) + ((lane >> 1) & 1);
        uint2* kvf_h = (uint2*)(scr->kvf + (bi_j * 4 + (bi_i >> 2)) * 68);
        auto windows = [&](int rhi, int rlo) {
#pragma unroll 1
            for (int rho = rhi; rho >= rlo; rho--) {
                const int ci = lane + 32 * rho;
                uint4 e4[4];
#pragma unroll
                for (int v = 0; v < 4; v++) { const int cc = ci - 3 + v; e4[v] = lds128(ub + ((cc ^ ((cc >> 3) & 1)) << 4)); }
                float S[29];
                const uint32_t* ew = (const uint32_t*)e4;
                S[3] = 0.f;
#pragma unroll
                for (int k = 4; k <= 28; k++) S[k] = S[k - 1] + ((k & 1) ? bf_hi(ew[k >> 1]) : bf_lo(ew[k >> 1]));
                auto win = [&](int lo, int hi, uint32_t a) {
                    sts128(a, pack2(S[hi] - S[lo - 1], S[hi + 1] - S[lo]), pack2(S[hi + 2] - S[lo + 1], S[hi + 3] - S[lo + 2]),
                           pack2(S[hi + 4] - S[lo + 3], S[hi + 5] - S[lo + 4]), pack2(S[hi + 6] - S[lo + 5], S[hi + 7] - S[lo + 6]));
                };
                win(14, 18, buf + W5_OFF + 16 + ci * 16); win(19, 21, buf + W3_OFF + 16 + ci * 16);
                if (rho < 4) {
                    const uint32_t sw = (ci ^ ((ci >> 3) & 1)) << 4;
                    win(4, 12, buf + W9_OFF + sw); win(13, 19, spare + sw); win(20, 21, spare + 2048 + sw);
                }
            }
        };
        float kc[24];
#pragma unroll
        for (int t = 0; t < 24; t++) kc[t] = 0.f;
        const float dt = bf_round(expf((ch & 1) ? bf_hi(pdt) : bf_lo(pdt)));
#pragma unroll 1
        for (int it = 0; it < 2; it++) {
            const uint32_t hstg = sb + (it == 0 ? 3 : 1) * SLOT + w4 * 7296;
            const uint32_t stg = hw ? hstg : (it == 0 ? buf : sb + w4 * 7296);
            if (it == 1) {
                if (hw) {
                    mbar_wait(bar + 8 * (BAR_FULL + xkb), 0);
#pragma unroll 1
                    for (int hf = 0; hf < 2; hf++) {
                        const int r = w4 * 32 + hf * 16 + (lane & 15);
                        uint32_t* xt = (uint32_t*)scr->xt + ((xkb + rot) * 16 + (g >> 2)) * 4096 + (bi_i * 16 + w4 * 4 + hf * 2) * 16 + (g & 3) * 4 + q;
#pragma unroll
                        for (int cb = 0; cb < 8; cb += 2) {
                            uint32_t v[4];
                            ldsm4t(v, sb + xkb * SLOT + r * 128 + (((cb + (lane >> 4)) ^ (r & 7)) << 4));
                            xt[cb * 8192] = v[0]; xt[cb * 8192 + 16] = v[1]; xt[cb * 8192 + 8192] = v[2]; xt[cb * 8192 + 8192 + 16] = v[3];
                        }
                    }
                    __syncwarp();
                    if (lane == 0) mbar_arrive(bar + 8 * BAR_XT);
                    if (warp == 12) {
                        STAMP(26);
                        mbar_wait(bar + 8 * BAR_XT, 0);
                        if (lane == 0) asm volatile("red.release.gpu.global.add.u32 [%0],8;" ::"l"(scr->xcnt + (xkb + rot) * 32) : "memory");
                        __syncwarp();
                        STAMP(27);
                    }
                    {
                        const uint32_t old = tag ^ 1u;
                        const uint4 z4 = make_uint4(old, 0, old, 0);
#pragma unroll
                        for (int v = 0; v < 5; v++) if (v < 4 || st < 32) st_rlx128(scr->kvp + bi * 544 + v * 128 + st, z4);
                        if (st < 16) st_rlx128(scr->o + ((bi_i * 8 + (st >> 1)) * 32 + bi_j * 4 + 3) * 32 + 30 + (st & 1), z4);
                        if (lane < 8) st_rlx64(kvf_h + ((bi_i & 3) * 8 + w4 * 2 + (lane & 1)) * 4 + (lane >> 1), old, 0);
                        if (st < 4 && !(bi_i & 1)) st_rlx64(kvf_h + (64 + qq) * 2 + (lane & 1), old, 0);
                        __syncwarp();
                        if (lane == 0) mbar_arrive(bar + 8 * BAR_PREP);
                    }
                    int n = 0;
#pragma unroll 1
                    while (__any_sync(~0u, (int)(ld_acq(scr->xcnt + bi_j * 32) - (epoch1 << 7)) < 0)) { if (++n > SPIN_LIMIT) break; }
                    if (warp == 12) STAMP(15);
                    uint4 ur[8];
#pragma unroll
                    for (int v = 0; v < 8; v++) ur[v] = __ldcg(scr->xt + bi * 1024 + st + 128 * v);
                    if (lane < 16) sts128(ub - 256 + lane * 16, 0, 0, 0, 0);
                    if (lane < 2) sts128(buf + lane * W3_OFF, 0, 0, 0, 0);
#pragma unroll
                    for (int v = 0; v < 8; v++) {
                        const int ci = (st >> 2) + 32 * v;
                        sts128(sb + OFF_U + (st & 3) * U_STRIDE + 256 + ((ci ^ ((ci >> 3) & 1)) << 4), ur[v].x, ur[v].y, ur[v].z, ur[v].w);
                    }
                    __syncwarp();
                    if (lane == 0) mbar_arrive(bar + 8 * BAR_UR);
                    mbar_wait(bar + 8 * BAR_UR, 0);
                    if (warp == 12) STAMP(16);
                    windows(5, 4);
                } else if (warp == 8) {
                    const int row = bi_j * 16 + (lane >> 1), half = lane & 1;
                    unsigned* gp = scr->g + (bi_i * 64 + bi_j * 8) * 8 + lane * 2;
                    st_rlx64(gp, tag ^ 1u, tag ^ 1u);
                    if (lane < 8) st_rlx32(scr->yflag + bi * 8 + lane, tag ^ 1u);
                    float gs0 = 0.f, gs1 = 0.f;
                    mbar_wait(bar + 8 * BAR_WPHI, 0);
#pragma unroll 1
                    for (int kb = 0; kb < 8; kb++) {
                        const int s = kb & 3;
                        mbar_wait(bar + 8 * (BAR_FULL + s), kb >> 2);
#pragma unroll
                        for (int c = 0; c < 4; c++) {
                            const uint4 xv = lds128(sb + s * SLOT + row * 128 + (((half * 4 + c) ^ (row & 7)) << 4));
                            const uint4 gw = lds128(sb + OFF_GW + ((kb + rot) & 7) * 128 + half * 64 + c * 16);
                            const uint32_t p0 = hmul2(xv.x, gw.x), p1 = hmul2(xv.y, gw.y), p2 = hmul2(xv.z, gw.z), p3 = hmul2(xv.w, gw.w);
                            gs0 += (bf_lo(p0) + bf_lo(p1)) + (bf_lo(p2) + bf_lo(p3));
                            gs1 += (bf_hi(p0) + bf_hi(p1)) + (bf_hi(p2) + bf_hi(p3));
                        }
                        if (kb < 4 || kb == 5) {
                            mbar_wait(bar + 8 * (BAR_EMPTY + s), kb >> 2);
                            if (kb == xkb) mbar_wait(bar + 8 * BAR_XT, 0);
                            if (lane == 0) {
                                STAMP(48 + kb);
                                if (kb < 4) load_stage(kb + 4);
                                else mbar_arrive(bar + 8 * BAR_SP2);
                            }
                        }
                        __syncwarp();
                    }
                    if (lane == 0) mbar_arrive(bar + 8 * BAR_DONE);
                    float gs = gs0 + gs1;
                    gs += __shfl_xor_sync(~0u, gs, 1);
                    const uint32_t gv = __float_as_uint(bf_round(rcp(1.0f + ex2(-1.4426950408889634f * bf_round(gs))))) | tag;
                    st_rlx64(gp, gv, gv);
                }
                mbar_wait(bar + 8 * BAR_SP2, 0);
            }
            const int sh = it * 16;
            auto pick = [&](uint32_t v) { return __uint_as_float((v >> sh) << 16); };
            const float ea = bf_round(expf(pick(pla)));
            const float arl = (-ea * dt) * 1.4426950408889634f, ait = (pick(pai) * dt) * 0.15915494309189535f;
            cf C2; C2.re = 2.0f * (pick(pcr) * dt); C2.im = 2.0f * (pick(pci) * dt);
            const cf z1 = cexp_p(arl, ait, 1.0f), z128 = cexp_p(arl, ait, 128.0f);
            cf z8 = cexp_p(arl, ait, 8.0f); z8.im = -z8.im;
            const uint32_t lp = stg + lane * 4;
            auto put = [&](int row, const cf& v) { sts32((lp ^ ((row & 7) << 4)) + row * 128, pack2(v.re, v.im)); };
            {
                const cf z16 = cmul(z8, z8);
                cf e; e.re = 1.f; e.im = 0.f;
                cf o = z8;
                put(0, e); put(1, o);
                e = z16; put(2, e);
#pragma unroll
                for (int b = 3; b < 16; b += 2) {
                    o = cmul(o, z16); put(b, o);
                    if (b + 1 < 16) { e = cmul(e, z16); put(b + 1, e); }
                }
            }
            cf h[8];
            h[0] = C2; put(16, h[0]);
            {
                const cf z2 = cmul(z1, z1);
                h[1] = cmul(h[0], z1);
#pragma unroll
                for (int r = 2; r < 8; r++) h[r] = cmul(h[r - 2], z2);
#pragma unroll
                for (int r = 1; r < 8; r++) put(16 + r, h[r]);
            }
#pragma unroll
            for (int r = 0; r < 8; r++) { h[r] = cmul(h[r], z128); put(24 + r, h[r]); }
#pragma unroll
            for (int al = 0; al < 2; al++)
#pragma unroll
                for (int r = 0; r < 4; r++) { h[2 * r] = cmul(h[2 * r], z128); put(32 + al * 4 + r, h[2 * r]); }
#pragma unroll
            for (int al = 0; al < 4; al++)
#pragma unroll
                for (int r = 0; r < 2; r++) { h[4 * r] = cmul(h[4 * r], z128); put(40 + al * 2 + r, h[4 * r]); }
#pragma unroll
            for (int al = 0; al < 9; al++) { h[0] = cmul(h[0], z128); put(48 + al, h[0]); }
            __syncwarp();
            if (it == 1) mbar_wait(bar + 8 * BAR_DONE, 0);
            const int lr = lane & 7, lm = lane >> 3;
#pragma unroll
            for (int kp = 0; kp < 2; kp++) {
                uint32_t a0[4], a1[4];
                ldsm4(a0, stg + ((lm & 1) * 8 + lr) * 128 + (((4 * kp + (lm >> 1)) ^ lr) << 4));
                ldsm4(a1, stg + ((lm & 1) * 8 + lr) * 128 + (((4 * kp + 2 + (lm >> 1)) ^ lr) << 4));
#pragma unroll
                for (int t = 0; t < 6; t++) {
                    uint32_t b[4];
                    ldsm4(b, stg + (16 + 8 * t + lr) * 128 + (((4 * kp + lm) ^ lr) << 4));
                    mma16816(kc + 4 * t, a0[0], a0[1], a0[2], a0[3], b[0], b[1]);
                    mma16816(kc + 4 * t, a1[0], a1[1], a1[2], a1[3], b[2], b[3]);
                }
            }
            __syncwarp();
            if (it == 0) {
                if (lane == 0) mbar_arrive(bar + 8 * BAR_KGA);
                if (hw) {
                    asm volatile("fence.proxy.async.shared::cta;" ::: "memory");
                    bar_named(5, 128);
                    if (st == 0) load_stage(3);
                    if (warp == 12) STAMP(22);
                }
            } else if (hw) {
#pragma unroll
                for (int t = 0; t < 6; t++)
                    sts128(stg + (t * 32 + lane) * 16, __float_as_uint(kc[4 * t]), __float_as_uint(kc[4 * t + 1]), __float_as_uint(kc[4 * t + 2]), __float_as_uint(kc[4 * t + 3]));
                asm volatile("fence.proxy.async.shared::cta;" ::: "memory");
                __syncwarp();
                if (lane == 0) mbar_arrive(bar + 8 * BAR_KG);
            } else {
                mbar_wait(bar + 8 * BAR_KG, 0);
#pragma unroll
                for (int t = 0; t < 6; t++) {
                    const uint4 v = lds128(hstg + (t * 32 + lane) * 16);
                    kc[4 * t] += __uint_as_float(v.x); kc[4 * t + 1] += __uint_as_float(v.y); kc[4 * t + 2] += __uint_as_float(v.z); kc[4 * t + 3] += __uint_as_float(v.w);
                }
                asm volatile("fence.proxy.async.shared::cta;" ::: "memory");
                __syncwarp();
                if (lane == 0) mbar_arrive(bar + 8 * BAR_SP);
            }
        }
        if (!hw) {
            if (warp == 8) STAMP(17);
            if (lane == 0) kc[4 * 0 + 0] += ((ch & 1) ? bf_hi(pds) : bf_lo(pds));
            const uint32_t k1024 = __shfl_sync(~0u, pack2(kc[4 * 4 + 0], 0.f), 0);
#pragma unroll
            for (int i = 0; i < 2; i++) {
                const int be = g + 8 * i;
#pragma unroll
                for (int t = 0; t < 2; t++) {
                    const uint32_t a = kb_ + (KW_D + 128 * t + 8 * be + 2 * q) * 4;
                    const uint32_t w = pack2(kc[4 * t + 2 * i + 1], kc[4 * t + 2 * i]);
                    sts32(a + 4, w); sts16(a, w >> 16); sts16(a + 10, w);
                }
                {
                    const int p = 256 + 128 * (q >> 1) + 8 * be + 4 * (q & 1);
                    const uint32_t a = kb_ + (KW_D + p) * 4;
                    const uint32_t w = pack2(kc[4 * 2 + 2 * i + 1], kc[4 * 2 + 2 * i]);
                    const uint32_t aa = (w >> 16) | (w & 0xffff0000u);
                    if (p != 256) { sts16(a - 4, aa); sts32(a, aa); } else sts16(a, aa);
                    sts32(a + 4, aa); sts32(a + 8, w); sts16(a + 14, w);
                }
                {
                    const int k = 64 + 16 * q + be;
                    const uint32_t w = pack2(kc[4 * 3 + 2 * i], kc[4 * 3 + 2 * i + 1]);
                    if (k != 64) sts16(kb_ + (KW_2 + ((k - 1) >> 1) - 24) * 4 + (k & 1) * 2, w);
                    else {
                        const uint32_t a = kb_ + (KW_D + 511) * 4, aa = (w << 16) | (w & 0xffffu);
                        sts16(a, w); sts32(a + 4, aa); sts32(a + 8, aa); sts32(a + 12, aa); sts16(a + 18, w);
                    }
                    sts16(kb_ + (KW_2 + 48 + (k >> 1) - 24) * 4 + ((k & 1) ^ 1) * 2, w >> 16);
                }
#pragma unroll
                for (int b = 0; b < 2; b++) {
                    const int k = 64 + 8 * (2 * q + b) + (be >> 1);
                    const uint32_t w = pack2(kc[4 * 4 + 2 * i + b], 0.f);
                    if (!(be & 1) && k == 64) sts16(kb_ + (KW_2 + 63 - 24) * 4, w);
                    else {
                        const uint32_t a = kb_ + (KW_3 + ((be & 1) ? 80 + k : k - 1) - 48) * 4;
                        sts16(a, w);
                        if (!((be & 1) && k == 127)) sts16(a + 6, w);
                    }
                }
            }
            if (lane == 0) sts16(kb_ + (KW_3 + 127 - 48) * 4, pack2(kc[4 * 5 + 0], 0.f));
            __syncwarp();
            mbar_wait(bar + 8 * BAR_UR, 0);
            if (warp == 8) STAMP(23);
            float y[16][4];
#pragma unroll
            for (int nt = 0; nt < 16; nt++) { y[nt][0] = y[nt][1] = y[nt][2] = y[nt][3] = 0.f; }
            {
                uint32_t Bp[32], A[5][3];
                auto uaddr = [&](int rho) { const int R0 = (lane >> 4) * 8 + (lane & 7) - rho; return ub + (((2 * R0 + ((lane >> 3) & 1)) ^ ((R0 >> 2) & 1)) << 4); };
                const uint32_t kd = kb_ + (KW_D + g - 2 * q) * 4;
                auto lda = [&](int rho) {
#pragma unroll
                    for (int ga = 0; ga < 5; ga++) {
                        const uint32_t a = kd + (ga < 4 ? rho : (rho & 1)) * 64 + ga * 512;
                        A[ga][0] = lds32(a); A[ga][1] = lds32(a + 32); A[ga][2] = lds32(a - 32);
                    }
                };
                {
                    const uint32_t a = uaddr(0);
#pragma unroll
                    for (int p = 0; p < 8; p++) ldsm4(Bp + 4 * p, a + p * 512);
                }
#pragma unroll 1
                for (int rho = 0; rho < 8; rho++) {
                    lda(rho);
                    if (rho < 2) {
#pragma unroll
                        for (int nt = 4; nt < 16; nt++) mma16816(y[nt], A[4][0], A[4][1], A[4][2], A[4][0], Bp[2 * (nt - 4)], Bp[2 * (nt - 4) + 1]);
                    }
#pragma unroll
                    for (int ga = 0; ga < 3; ga++)
#pragma unroll
                        for (int nt = 15; nt >= ga; nt--) mma16816(y[nt], A[ga][0], A[ga][1], A[ga][2], A[ga][0], Bp[2 * (nt - ga)], Bp[2 * (nt - ga) + 1]);
                    const uint32_t an = uaddr(rho + 1);
                    ldsm4(Bp + 28, an + 7 * 512);
#pragma unroll
                    for (int nt = 15; nt >= 3; nt--) {
                        mma16816(y[nt], A[3][0], A[3][1], A[3][2], A[3][0], Bp[2 * (nt - 3)], Bp[2 * (nt - 3) + 1]);
                        if (nt & 1) ldsm4(Bp + 2 * (nt - 3), an + ((nt - 3) >> 1) * 512);
                    }
                }
            }
            if (warp == 8) STAMP(18);
            mbar_wait(bar + 8 * BAR_WR, 0);
#pragma unroll 1
            for (int ph = 0; ph < 2; ph++) {
                uint32_t B[5][2];
                const uint32_t ka = kb_ + (KW_2 + ph * 48 + 8 + g - q) * 4;
#pragma unroll
                for (int dd = 0; dd < 5; dd++) { B[dd][0] = lds32(ka + dd * 32); B[dd][1] = lds32(ka + dd * 32 - 16); }
                const uint32_t wa = buf + ph * W3_OFF + ((lane & 7) + ((lane >> 3) & 1) + (lane >> 4) * 8) * 16;
#pragma unroll
                for (int s = 0; s < 12; s++) {
                    uint32_t A[4];
                    ldsm4t(A, wa + s * 256);
#pragma unroll
                    for (int dd = 0; dd < 5; dd++)
                        if (s + 4 + dd < 16) mma16816(y[s + 4 + dd], A[0], A[1], A[2], A[3], B[dd][0], B[dd][1]);
                }
            }
            {
                const int ap = (lane & 7) + (lane >> 4) * 8;
                const uint32_t loff = ((2 * ap + ((lane >> 3) & 1)) ^ ((ap >> 2) & 1)) << 4;
#pragma unroll 1
                for (int ph = 0; ph < 2; ph++) {
                    uint32_t B[8][2];
                    const uint32_t wb = (ph ? spare : buf + W9_OFF) + loff;
                    const uint32_t ka = kb_ + (KW_3 + ph * 80 + 16 + g - 2 * q) * 4;
#pragma unroll
                    for (int dd = 0; dd < 8; dd++) { B[dd][0] = lds32(ka + dd * 32); B[dd][1] = lds32(ka + dd * 32 - 32); }
#pragma unroll
                    for (int s = 0; s < 4; s++) {
                        uint32_t A[4];
                        ldsm4t(A, wb + s * 512);
#pragma unroll
                        for (int dd = 0; dd < 8; dd++)
                            if (8 + 2 * s + dd < 16) mma16816(y[8 + 2 * s + dd], A[0], A[1], A[2], A[3], B[dd][0], B[dd][1]);
                    }
                }
                const uint32_t idw = (g == 2 * q) ? k1024 : ((g == 2 * q + 1) ? (k1024 << 16) : 0u);
#pragma unroll
                for (int s = 0; s < 4; s++) {
                    uint32_t A[4];
                    ldsm4t(A, spare + 2048 + loff + s * 512);
                    mma16816(y[8 + 2 * s], A[0], A[1], A[2], A[3], idw, 0u);
                    mma16816(y[9 + 2 * s], A[0], A[1], A[2], A[3], 0u, idw);
                }
            }
            __syncwarp();
            if (warp == 8) STAMP(19);
#pragma unroll
            for (int nt = 0; nt < 16; nt++)
#pragma unroll
                for (int b = 0; b < 2; b++) sts32(buf + ((8 * nt + 2 * q + b) * 8 + g) * 4, pack2(y[nt][b], y[nt][2 + b]));
            bar_named(2, 128);
            uint4* yp = scr->y + bi * 1024 + st;
#pragma unroll
            for (int v = 0; v < 8; v++) {
                const uint32_t a = sb + OFF_BUF + (st + 128 * v) * 4;
                const uint32_t w0 = lds32(a), w1 = lds32(a + BUF_STRIDE), w2 = lds32(a + 2 * BUF_STRIDE), w3 = lds32(a + 3 * BUF_STRIDE);
                st_rlx128(yp + v * 128, tag4(__byte_perm(w0, w1, 0x5410), __byte_perm(w0, w1, 0x7632), __byte_perm(w2, w3, 0x5410), __byte_perm(w2, w3, 0x7632), tag));
            }
            if (st < 8) st_rlx32(scr->yflag + bi * 8 + st, tag);
            if (warp == 8) STAMP(20);
        } else {
            asm volatile("setmaxnreg.dec.sync.aligned.u32 64;");
            if (warp == 13) {
                mbar_wait(bar + 8 * BAR_SP, 0);
                if (lane == 0) {
                    mbar_expect(bar + 8 * BAR_WO, 65536);
                    tma2d(sb, &mwo, (bi_j & 3) * 128, 0, bar + 8 * BAR_WO);
                    tma2d(sb + SLOT, &mwo, (bi_j & 3) * 128 + 64, 0, bar + 8 * BAR_WO);
                }
                __syncwarp();
            }
            windows(3, 0);
            __syncwarp();
            if (lane == 0) mbar_arrive(bar + 8 * BAR_WR);
            if (warp == 12) STAMP(24);
            {
                const bool zw = st < 32 && !(bi_i & 1);
                const uint4* src = scr->kvp + bi_j * (16 * 544) + (bi_i >> 2) * 136;
                const uint4* zsrc = src + (lane >> 2) * (2 * 544) + 128 + (lane & 1) * 4 + qq;
                src += (lane >> 3) * (4 * 544) + ((lane >> 1) & 3) * 32 + (bi_i & 3) * 8 + w4 * 2 + (lane & 1);
                if (!zw) zsrc = src;
                mbar_wait(bar + 8 * BAR_PUB, 0);
                if (warp == 12) STAMP(12);
                uint4 v[6];
                int n = 0;
#pragma unroll 1
                while (true) {
#pragma unroll
                    for (int k = 0; k < 4; k++) v[k] = ld_rlx128(src + k * 544);
                    v[4] = ld_rlx128(zsrc); v[5] = ld_rlx128(zsrc + 544);
                    if (!__any_sync(~0u, (bad4(v[0], tag) | bad4(v[1], tag) | bad4(v[2], tag) | bad4(v[3], tag) | bad4(v[4], tag) | bad4(v[5], tag)) & 1)) break;
                    if (++n > SPIN_LIMIT) break;
                }
                if (warp == 12) STAMP(30);
                float f[8];
                const float* vf = (const float*)v;
#pragma unroll
                for (int r = 0; r < 4; r++) {
                    f[r] = (vf[r] + vf[4 + r]) + (vf[8 + r] + vf[12 + r]);
                    f[4 + r] = vf[16 + r] + vf[20 + r];
                    f[4 + r] += __shfl_xor_sync(~0u, f[4 + r], 4);
                }
#pragma unroll
                for (int o = 8; o <= 16; o <<= 1)
#pragma unroll
                    for (int r = 0; r < 8; r++) f[r] += __shfl_xor_sync(~0u, f[r], o);
                if (lane < 8) st_rlx64(kvf_h + ((bi_i & 3) * 8 + w4 * 2 + (lane & 1)) * 4 + (lane >> 1), tagw(pack2(f[0], f[1]), tag), pack2(f[2], f[3]));
                if (zw && lane < 4) st_rlx64(kvf_h + (64 + qq) * 2 + (lane & 1), tagw(pack2(f[4], f[5]), tag), pack2(f[6], f[7]));
            }
            if (warp == 12) STAMP(13);
            {
                const uint4* kp = scr->kvf + bi_j * 272 + st;
                uint4 v0, v1, v2;
                int n = 0;
#pragma unroll 1
                while (true) {
                    v0 = ld_rlx128(kp); v1 = ld_rlx128(kp + 128); v2 = ld_rlx128(kp + (st < 16 ? 256 : 0));
                    if (!__any_sync(~0u, (bad4(v0, tag) | bad4(v1, tag) | bad4(v2, tag)) & 1)) break;
                    if (++n > SPIN_LIMIT) break;
                }
                sts128(sb + OFF_KVF + st * 16, v0.x, v0.y, v0.z, v0.w);
                sts128(sb + OFF_KVF + 2048 + st * 16, v1.x, v1.y, v1.z, v1.w);
                if (st < 16) sts128(sb + OFF_KVF + 4096 + st * 16, v2.x, v2.y, v2.z, v2.w);
                __syncwarp();
                if (lane == 0) mbar_arrive(bar + 8 * BAR_KVF);
            }
            if (warp == 13) {
                mbar_wait(bar + 8 * BAR_KVF, 0);
                if (lane == 0) {
                    mbar_expect(bar + 8 * BAR_WO2, 65536);
                    tma2d(sb + OFF_P, &mwo, (bi_j & 3) * 128, 256, bar + 8 * BAR_WO2);
                    tma2d(sb + OFF_V, &mwo, (bi_j & 3) * 128 + 64, 256, bar + 8 * BAR_WO2);
                }
            }
            if (warp == 12) STAMP(25);
        }
    }
    __syncwarp();
    if (lane == 0) {
        unsigned old;
        asm volatile("atom.acq_rel.cta.shared.add.u32 %0,[%1],1;" : "=r"(old) : "r"(bar + OFF_CNT) : "memory");
        if (old == 15) {
            atomicAdd(scr->done, 1u);
        }
    }
}

typedef CUresult (*EncFn)(CUtensorMap*, CUtensorMapDataType, cuuint32_t, void*, const cuuint64_t*, const cuuint64_t*, const cuuint32_t*,
                          const cuuint32_t*, CUtensorMapInterleave, CUtensorMapSwizzle, CUtensorMapL2promotion, CUtensorMapFloatOOBfill);

extern "C" void kernel_launch(void* const* d_in, const int* in_sizes, int n_in, void* d_out, int out_size) {
    static EncFn enc = nullptr;
    static Scratch* scr = nullptr;
    if (!enc) {
        cudaGetSymbolAddress((void**)&scr, g_scr);
        cudaDriverEntryPointQueryResult qr;
        cudaGetDriverEntryPoint("cuTensorMapEncodeTiled", (void**)&enc, cudaEnableDefault, &qr);
        cudaFuncSetAttribute(fused_kernel, cudaFuncAttributeMaxDynamicSharedMemorySize, SMEM_BYTES);
    }
    CUtensorMap mx, mw, mwo;
    const cuuint32_t es[3] = {1, 1, 1};
    {
        cuuint64_t d[2] = {512, 2048}, s[1] = {1024}; cuuint32_t b[2] = {64, 128};
        enc(&mx, CU_TENSOR_MAP_DATA_TYPE_BFLOAT16, 2, d_in[0], d, s, b, es, CU_TENSOR_MAP_INTERLEAVE_NONE, CU_TENSOR_MAP_SWIZZLE_128B,
            CU_TENSOR_MAP_L2_PROMOTION_L2_128B, CU_TENSOR_MAP_FLOAT_OOB_FILL_NONE);
    }
    {
        cuuint64_t d[3] = {512, 512, 3}, s[2] = {3072, 1024}; cuuint32_t b[3] = {64, 64, 3};
        enc(&mw, CU_TENSOR_MAP_DATA_TYPE_BFLOAT16, 3, d_in[1], d, s, b, es, CU_TENSOR_MAP_INTERLEAVE_NONE, CU_TENSOR_MAP_SWIZZLE_128B,
            CU_TENSOR_MAP_L2_PROMOTION_L2_128B, CU_TENSOR_MAP_FLOAT_OOB_FILL_NONE);
    }
    {
        cuuint64_t d[2] = {512, 512}, s[1] = {1024}; cuuint32_t b[2] = {64, 256};
        enc(&mwo, CU_TENSOR_MAP_DATA_TYPE_BFLOAT16, 2, d_in[3], d, s, b, es, CU_TENSOR_MAP_INTERLEAVE_NONE, CU_TENSOR_MAP_SWIZZLE_128B,
            CU_TENSOR_MAP_L2_PROMOTION_L2_128B, CU_TENSOR_MAP_FLOAT_OOB_FILL_NONE);
    }
    fused_kernel<<<128, 512, SMEM_BYTES, cudaStreamPerThread>>>(
        scr, (const bf16*)d_in[5], (const bf16*)d_in[6], (const bf16*)d_in[7], (const bf16*)d_in[8], (const bf16*)d_in[9],
        (const bf16*)d_in[10], (const bf16*)d_in[2], (const bf16*)d_in[11], (bf16*)d_out, mx, mw, mwo);
}
```

```cpp
#include <cuda_runtime.h>
#include <cuda.h>
#include <cuda_bf16.h>
#include <stdint.h>

typedef __nv_bfloat16 bf16;

struct Scratch {
    uint4 xt[128 * 1024];
    uint4 o[16 * 8 * 32 * 32];
    uint4 y[128 * 1024];
    uint4 kvp[8 * 16 * 544];
    uint4 kvf[8 * 4 * 68];
    unsigned g[1024 * 8];
    unsigned yflag[128 * 8];
    unsigned xcnt[8 * 32];
    unsigned done[32];
};
__device__ Scratch g_scr;
#define STAMP(n)

constexpr int SLOT = 40960;
constexpr int OFF_SP0 = 32768, OFF_SP1 = SLOT + 32768;
constexpr int OFF_P = 2 * SLOT, OFF_V = OFF_P + 32768;
constexpr int OFF_KVF = OFF_V + 32768;
constexpr int KT_BYTES = 3264, KW_D = 16, KW_2 = 560, KW_3 = 656;
constexpr int OFF_U = 4 * SLOT, U_STRIDE = 4096 + 256 + 32;
constexpr int OFF_BUF = OFF_U + 4 * U_STRIDE, BUF_STRIDE = 8320;
constexpr int OFF_K = OFF_BUF + 4 * BUF_STRIDE;
constexpr int OFF_WPHI = OFF_K + 4 * KT_BYTES;
constexpr int OFF_GW = OFF_WPHI + 2048;
constexpr int OFF_BAR = OFF_GW + 1024;
constexpr int SMEM_BYTES = OFF_BAR + 256 + 256;
static_assert(SMEM_BYTES <= 232448 && OFF_BUF % 128 == 0, "smem");
constexpr int W5_OFF = 0, W3_OFF = 3088, W9_OFF = 6176;
constexpr int BAR_FULL = 0, BAR_EMPTY = 4, BAR_WPHI = 8, BAR_WO = 9, BAR_WO2 = 10, BAR_XT = 11, BAR_DONE = 12, BAR_KG = 13, BAR_SP = 14,
              BAR_PUB = 15, BAR_KVF = 16, BAR_UR = 17, BAR_WR = 18, BAR_PREP = 19, BAR_KGA = 20, BAR_SP2 = 21, OFF_CNT = 192;
constexpr int SPIN_LIMIT = 1 << 17;

__device__ __forceinline__ uint32_t s2u(const void* p) { return (uint32_t)__cvta_generic_to_shared(p); }
__device__ __forceinline__ void mbar_init(uint32_t b, int c) { asm volatile("mbarrier.init.shared::cta.b64 [%0],%1;" ::"r"(b), "r"(c) : "memory"); }
__device__ __forceinline__ void mbar_expect(uint32_t b, int bytes) { asm volatile("mbarrier.arrive.expect_tx.shared::cta.b64 _,[%0],%1;" ::"r"(b), "r"(bytes) : "memory"); }
__device__ __forceinline__ void mbar_arrive(uint32_t b) { asm volatile("mbarrier.arrive.shared::cta.b64 _,[%0];" ::"r"(b) : "memory"); }
__device__ __forceinline__ void mbar_wait(uint32_t b, int ph) {
    asm volatile("{\n.reg .pred p;\n.reg .u32 n;\nmov.u32 n,0;\nLW_%=:\nmbarrier.try_wait.parity.shared::cta.b64 p,[%0],%1;\n@p bra LD_%=;\n"
                 "add.u32 n,n,1;\nsetp.lt.u32 p,n,16384;\n@p bra LW_%=;\nLD_%=:\n}" ::"r"(b), "r"(ph) : "memory");
}
__device__ __forceinline__ void tma2d(uint32_t dst, const CUtensorMap* m, int c0, int c1, uint32_t bar) {
    asm volatile("cp.async.bulk.tensor.2d.shared::cluster.global.mbarrier::complete_tx::bytes [%0],[%1,{%3,%4}],[%2];" ::"r"(dst), "l"(m), "r"(bar), "r"(c0), "r"(c1) : "memory");
}
__device__ __forceinline__ void tma3d(uint32_t dst, const CUtensorMap* m, int c0, int c1, int c2, uint32_t bar) {
    asm volatile("cp.async.bulk.tensor.3d.shared::cluster.global.mbarrier::complete_tx::bytes [%0],[%1,{%3,%4,%5}],[%2];" ::"r"(dst), "l"(m), "r"(bar), "r"(c0), "r"(c1), "r"(c2) : "memory");
}
__device__ __forceinline__ void bulk_g2s(uint32_t dst, const void* src, int bytes, uint32_t bar) {
    asm volatile("cp.async.bulk.shared::cluster.global.mbarrier::complete_tx::bytes [%0],[%1],%2,[%3];" ::"r"(dst), "l"(src), "r"(bytes), "r"(bar) : "memory");
}
__device__ __forceinline__ uint64_t mkdesc(uint32_t addr, uint32_t lbo, uint32_t sbo) {
    return (uint64_t)((addr & 0x3FFFF) >> 4) | ((uint64_t)(lbo >> 4) << 16) | ((uint64_t)(sbo >> 4) << 32) | ((uint64_t)1 << 62);
}
__device__ __forceinline__ void wg_fence() { asm volatile("wgmma.fence.sync.aligned;" ::: "memory"); }
__device__ __forceinline__ void wg_commit() { asm volatile("wgmma.commit_group.sync.aligned;" ::: "memory"); }
template <int N> __device__ __forceinline__ void wg_wait() { asm volatile("wgmma.wait_group.sync.aligned %0;" ::"n"(N) : "memory"); }
template <int N> __device__ __forceinline__ void fence_regs(float* d) {
#pragma unroll
    for (int i = 0; i < N; i++) asm volatile("" : "+f"(d[i])::"memory");
}
#define R8(d, o) "+f"(d[o]), "+f"(d[o + 1]), "+f"(d[o + 2]), "+f"(d[o + 3]), "+f"(d[o + 4]), "+f"(d[o + 5]), "+f"(d[o + 6]), "+f"(d[o + 7])
__device__ __forceinline__ void wgmma192(float* d, uint64_t da, uint64_t db) {
    asm volatile("wgmma.mma_async.sync.aligned.m64n192k16.f32.bf16.bf16 {"
                 "%0,%1,%2,%3,%4,%5,%6,%7,%8,%9,%10,%11,%12,%13,%14,%15,%16,%17,%18,%19,%20,%21,%22,%23,%24,%25,%26,%27,%28,%29,%30,%31,"
                 "%32,%33,%34,%35,%36,%37,%38,%39,%40,%41,%42,%43,%44,%45,%46,%47,%48,%49,%50,%51,%52,%53,%54,%55,%56,%57,%58,%59,%60,%61,%62,%63,"
                 "%64,%65,%66,%67,%68,%69,%70,%71,%72,%73,%74,%75,%76,%77,%78,%79,%80,%81,%82,%83,%84,%85,%86,%87,%88,%89,%90,%91,%92,%93,%94,%95},"
                 "%96,%97,1,1,1,0,1;"
                 : R8(d, 0), R8(d, 8), R8(d, 16), R8(d, 24), R8(d, 32), R8(d, 40), R8(d, 48), R8(d, 56), R8(d, 64), R8(d, 72), R8(d, 80), R8(d, 88)
                 : "l"(da), "l"(db));
}
__device__ __forceinline__ void wgmma64_tt(float* d, uint64_t da, uint64_t db, int sc) {
    asm volatile("{.reg .pred p; setp.ne.b32 p,%34,0; wgmma.mma_async.sync.aligned.m64n64k16.f32.bf16.bf16 {"
                 "%0,%1,%2,%3,%4,%5,%6,%7,%8,%9,%10,%11,%12,%13,%14,%15,%16,%17,%18,%19,%20,%21,%22,%23,%24,%25,%26,%27,%28,%29,%30,%31},"
                 "%32,%33,p,1,1,1,1;}"
                 : R8(d, 0), R8(d, 8), R8(d, 16), R8(d, 24)
                 : "l"(da), "l"(db), "r"(sc));
}
__device__ __forceinline__ void wgmma128_rs(float* d, const uint4& a, uint64_t db, int sc) {
    asm volatile("{.reg .pred p; setp.ne.b32 p,%69,0; wgmma.mma_async.sync.aligned.m64n128k16.f32.bf16.bf16 {"
                 "%0,%1,%2,%3,%4,%5,%6,%7,%8,%9,%10,%11,%12,%13,%14,%15,%16,%17,%18,%19,%20,%21,%22,%23,%24,%25,%26,%27,%28,%29,%30,%31,"
                 "%32,%33,%34,%35,%36,%37,%38,%39,%40,%41,%42,%43,%44,%45,%46,%47,%48,%49,%50,%51,%52,%53,%54,%55,%56,%57,%58,%59,%60,%61,%62,%63},"
                 "{%64,%65,%66,%67},%68,p,1,1,1;}"
                 : R8(d, 0), R8(d, 8), R8(d, 16), R8(d, 24), R8(d, 32), R8(d, 40), R8(d, 48), R8(d, 56)
                 : "r"(a.x), "r"(a.y), "r"(a.z), "r"(a.w), "l"(db), "r"(sc));
}
__device__ __forceinline__ void mma16816(float* c, uint32_t a0, uint32_t a1, uint32_t a2, uint32_t a3, uint32_t b0, uint32_t b1) {
    asm("mma.sync.aligned.m16n8k16.row.col.f32.bf16.bf16.f32 {%0,%1,%2,%3},{%4,%5,%6,%7},{%8,%9},{%0,%1,%2,%3};"
        : "+f"(c[0]), "+f"(c[1]), "+f"(c[2]), "+f"(c[3]) : "r"(a0), "r"(a1), "r"(a2), "r"(a3), "r"(b0), "r"(b1));
}
__device__ __forceinline__ void ldsm4(uint32_t* r, uint32_t a) {
    asm volatile("ldmatrix.sync.aligned.m8n8.x4.shared.b16 {%0,%1,%2,%3},[%4];" : "=r"(r[0]), "=r"(r[1]), "=r"(r[2]), "=r"(r[3]) : "r"(a) : "memory");
}
__device__ __forceinline__ void ldsm4t(uint32_t* r, uint32_t a) {
    asm volatile("ldmatrix.sync.aligned.m8n8.x4.trans.shared.b16 {%0,%1,%2,%3},[%4];" : "=r"(r[0]), "=r"(r[1]), "=r"(r[2]), "=r"(r[3]) : "r"(a) : "memory");
}
__device__ __forceinline__ void stsm4(uint32_t a, uint32_t r0, uint32_t r1, uint32_t r2, uint32_t r3) {
    asm volatile("stmatrix.sync.aligned.m8n8.x4.shared.b16 [%0],{%1,%2,%3,%4};" ::"r"(a), "r"(r0), "r"(r1), "r"(r2), "r"(r3) : "memory");
}
__device__ __forceinline__ uint32_t lds32(uint32_t a) { uint32_t v; asm volatile("ld.shared.b32 %0,[%1];" : "=r"(v) : "r"(a) : "memory"); return v; }
__device__ __forceinline__ uint4 lds128(uint32_t a) { uint4 v; asm volatile("ld.shared.v4.b32 {%0,%1,%2,%3},[%4];" : "=r"(v.x), "=r"(v.y), "=r"(v.z), "=r"(v.w) : "r"(a) : "memory"); return v; }
__device__ __forceinline__ void sts16(uint32_t a, uint32_t v) { asm volatile("st.shared.b16 [%0],%1;" ::"r"(a), "h"((unsigned short)v) : "memory"); }
__device__ __forceinline__ void sts32(uint32_t a, uint32_t v) { asm volatile("st.shared.b32 [%0],%1;" ::"r"(a), "r"(v) : "memory"); }
__device__ __forceinline__ void sts64(uint32_t a, uint32_t x, uint32_t y) { asm volatile("st.shared.v2.b32 [%0],{%1,%2};" ::"r"(a), "r"(x), "r"(y) : "memory"); }
__device__ __forceinline__ void sts128(uint32_t a, uint32_t x, uint32_t y, uint32_t z, uint32_t w) { asm volatile("st.shared.v4.b32 [%0],{%1,%2,%3,%4};" ::"r"(a), "r"(x), "r"(y), "r"(z), "r"(w) : "memory"); }
__device__ __forceinline__ uint32_t pack2(float lo, float hi) { uint32_t d; asm("cvt.rn.bf16x2.f32 %0,%1,%2;" : "=r"(d) : "f"(hi), "f"(lo)); return d; }
__device__ __forceinline__ float bf_lo(uint32_t v) { return __uint_as_float(v << 16); }
__device__ __forceinline__ float bf_hi(uint32_t v) { return __uint_as_float(v & 0xffff0000u); }
__device__ __forceinline__ float bf_round(float v) { return bf_lo(pack2(v, 0.f)); }
__device__ __forceinline__ uint32_t hmax2(uint32_t a, uint32_t b) { uint32_t d; asm("max.bf16x2 %0,%1,%2;" : "=r"(d) : "r"(a), "r"(b)); return d; }
__device__ __forceinline__ uint32_t hmin2(uint32_t a, uint32_t b) { uint32_t d; asm("min.bf16x2 %0,%1,%2;" : "=r"(d) : "r"(a), "r"(b)); return d; }
__device__ __forceinline__ uint32_t hmul2(uint32_t a, uint32_t b) { uint32_t d; asm("mul.rn.bf16x2 %0,%1,%2;" : "=r"(d) : "r"(a), "r"(b)); return d; }
__device__ __forceinline__ float ex2(float x) { float y; asm("ex2.approx.ftz.f32 %0,%1;" : "=f"(y) : "f"(x)); return y; }
__device__ __forceinline__ float rcp(float x) { float y; asm("rcp.approx.ftz.f32 %0,%1;" : "=f"(y) : "f"(x)); return y; }
__device__ __forceinline__ uint32_t ld_nc(const uint32_t* p) { uint32_t v; asm volatile("ld.global.nc.b32 %0,[%1];" : "=r"(v) : "l"(p)); return v; }
__device__ __forceinline__ uint2 ld_nc64(const uint2* p) { uint2 v; asm volatile("ld.global.nc.v2.b32 {%0,%1},[%2];" : "=r"(v.x), "=r"(v.y) : "l"(p)); return v; }
__device__ __forceinline__ unsigned ld_acq(const unsigned* p) { unsigned v; asm volatile("ld.acquire.gpu.global.u32 %0,[%1];" : "=r"(v) : "l"(p) : "memory"); return v; }
__device__ __forceinline__ unsigned ld_rlx(const unsigned* p) { unsigned v; asm volatile("ld.relaxed.gpu.global.u32 %0,[%1];" : "=r"(v) : "l"(p) : "memory"); return v; }
__device__ __forceinline__ uint2 ld_rlx64(const void* p) { uint2 v; asm volatile("{.reg .b64 t; ld.relaxed.gpu.global.b64 t,[%2]; mov.b64 {%0,%1},t;}" : "=r"(v.x), "=r"(v.y) : "l"(p) : "memory"); return v; }
__device__ __forceinline__ uint4 ld_rlx128(const void* p) {
    uint4 v;
    asm volatile("{.reg .b64 t,u; ld.relaxed.gpu.global.v2.b64 {t,u},[%4]; mov.b64 {%0,%1},t; mov.b64 {%2,%3},u;}" : "=r"(v.x), "=r"(v.y), "=r"(v.z), "=r"(v.w) : "l"(p) : "memory");
    return v;
}
__device__ __forceinline__ void st_rlx32(void* p, uint32_t x) { asm volatile("st.relaxed.gpu.global.u32 [%0],%1;" ::"l"(p), "r"(x) : "memory"); }
__device__ __forceinline__ void st_rlx64(void* p, uint32_t x, uint32_t y) { asm volatile("{.reg .b64 t; mov.b64 t,{%1,%2}; st.relaxed.gpu.global.b64 [%0],t;}" ::"l"(p), "r"(x), "r"(y) : "memory"); }
__device__ __forceinline__ void st_rlx128(void* p, uint4 v) {
    asm volatile("{.reg .b64 t,u; mov.b64 t,{%1,%2}; mov.b64 u,{%3,%4}; st.relaxed.gpu.global.v2.b64 [%0],{t,u};}" ::"l"(p), "r"(v.x), "r"(v.y), "r"(v.z), "r"(v.w) : "memory");
}
__device__ __forceinline__ uint32_t tagw(uint32_t w, uint32_t tag) { return (w & ~1u) | tag; }
__device__ __forceinline__ uint4 tag4(uint32_t x, uint32_t y, uint32_t z, uint32_t w, uint32_t tag) { return make_uint4(tagw(x, tag), y, tagw(z, tag), w); }
__device__ __forceinline__ uint32_t bad4(const uint4& v, uint32_t tag) { return (v.x ^ tag) | (v.z ^ tag); }
__device__ __forceinline__ void bar_named(int id, int n) { asm volatile("bar.sync %0,%1;" ::"r"(id), "r"(n) : "memory"); }

struct cf { float re, im; };
__device__ __forceinline__ cf cmul(cf a, cf b) { cf r; r.re = a.re * b.re - a.im * b.im; r.im = a.re * b.im + a.im * b.re; return r; }
__device__ __forceinline__ cf cexp_p(float arl, float ait, float p) {
    float mag = ex2(arl * p);
    float t = ait * p;
    t = (t - rintf(t)) * 6.283185307179586f;
    cf r; r.re = mag * __cosf(t); r.im = mag * __sinf(t);
    return r;
}

__device__ __forceinline__ void hedgehog2(const uint32_t* a, uint32_t wphi_addr, uint32_t (*out)[8]) {
    float p[2][2][4], mx[2][2];
#pragma unroll
    for (int h = 0; h < 2; h++) {
        uint32_t b[4];
        ldsm4t(b, wphi_addr + h * 512);
        float c0[4] = {0.f, 0.f, 0.f, 0.f}, c1[4] = {0.f, 0.f, 0.f, 0.f};
        mma16816(c0, a[4 * h], a[4 * h + 1], a[4 * h + 2], a[4 * h + 3], b[0], b[1]);
        mma16816(c1, a[4 * h], a[4 * h + 1], a[4 * h + 2], a[4 * h + 3], b[2], b[3]);
#pragma unroll
        for (int k = 0; k < 2; k++) {
            p[h][k][0] = c0[2 * k]; p[h][k][1] = c0[2 * k + 1]; p[h][k][2] = c1[2 * k]; p[h][k][3] = c1[2 * k + 1];
            mx[h][k] = fmaxf(fmaxf(p[h][k][0], p[h][k][1]), fmaxf(p[h][k][2], p[h][k][3]));
        }
    }
#pragma unroll
    for (int o = 1; o <= 2; o <<= 1)
#pragma unroll
        for (int h = 0; h < 2; h++)
#pragma unroll
            for (int k = 0; k < 2; k++) mx[h][k] = fmaxf(mx[h][k], __shfl_xor_sync(~0u, mx[h][k], o));
    const float L = 1.4426950408889634f;
    float pmin = 1.f;
#pragma unroll
    for (int h = 0; h < 2; h++)
#pragma unroll
        for (int k = 0; k < 2; k++) {
            const float m = -mx[h][k] * L;
            const float e0 = ex2(fmaf(p[h][k][0], L, m)), e1 = ex2(fmaf(p[h][k][1], L, m)), e2 = ex2(fmaf(p[h][k][2], L, m)), e3 = ex2(fmaf(p[h][k][3], L, m));
            const float p01 = e0 * e1, p23 = e2 * e3, pp = p01 * p23, r = rcp(pp), r01 = r * p23, r23 = r * p01;
            pmin = fminf(pmin, pp);
            out[h][k] = pack2(e0, e1); out[h][k + 2] = pack2(e2, e3);
            out[h][4 + k] = pack2(r01 * e1, r01 * e0); out[h][4 + k + 2] = pack2(r23 * e3, r23 * e2);
        }
    if (__builtin_expect(__any_sync(~0u, !(pmin > 1e-18f)), 0)) {
#pragma unroll
        for (int h = 0; h < 2; h++)
#pragma unroll
            for (int k = 0; k < 2; k++) {
                float m = fminf(fminf(p[h][k][0], p[h][k][1]), fminf(p[h][k][2], p[h][k][3]));
                m = fminf(m, __shfl_xor_sync(~0u, m, 1));
                m = fminf(m, __shfl_xor_sync(~0u, m, 2)) * L;
                out[h][4 + k] = pack2(ex2(fmaf(p[h][k][0], -L, m)), ex2(fmaf(p[h][k][1], -L, m)));
                out[h][4 + k + 2] = pack2(ex2(fmaf(p[h][k][2], -L, m)), ex2(fmaf(p[h][k][3], -L, m)));
            }
    }
}

__global__ void __launch_bounds__(512, 1)
fused_kernel(Scratch* __restrict__ scr, const bf16* __restrict__ logA, const bf16* __restrict__ Aim, const bf16* __restrict__ Cre,
             const bf16* __restrict__ Cim, const bf16* __restrict__ logdt, const bf16* __restrict__ Dskip, const bf16* __restrict__ wphi,
             const bf16* __restrict__ gatew, bf16* __restrict__ out,
             const __grid_constant__ CUtensorMap mx, const __grid_constant__ CUtensorMap mw, const __grid_constant__ CUtensorMap mwo) {
    extern __shared__ __align__(1024) uint8_t smem[];
    const uint32_t sb = s2u(smem);
    const int tid = threadIdx.x, warp = __shfl_sync(~0u, tid >> 5, 0), lane = tid & 31;
    const int g = lane >> 2, q = lane & 3, w4 = warp & 3;
    const int bi = blockIdx.x, bi_i = bi & 15, bi_j = bi >> 4;
    const uint32_t bar = sb + OFF_BAR;
    const int rot = (bi_j & 3) * 2, xkb = bi_j >> 2;
    auto load_stage = [&](int kb) {
        const uint32_t b = bar + 8 * (BAR_FULL + (kb & 3)), d = sb + (kb & 3) * SLOT;
        const int kc = ((kb + rot) & 7) * 64;
        mbar_expect(b, SLOT);
        tma2d(d, &mx, kc, bi_i * 128, b);
        tma3d(d + 16384, &mw, bi_j * 64, kc, 0, b);
    };

    const int ch = bi * 4 + w4;
    const int pidx = ch * 64 + lane * 2 + (warp >> 3);
    const uint32_t pla = ld_nc((const uint32_t*)logA + pidx), pai = ld_nc((const uint32_t*)Aim + pidx);
    const uint32_t pcr = ld_nc((const uint32_t*)Cre + pidx), pci = ld_nc((const uint32_t*)Cim + pidx);
    uint32_t pdt = ld_nc((const uint32_t*)logdt + (ch >> 1));
    const uint32_t pds = ld_nc((const uint32_t*)Dskip + (ch >> 1));
    unsigned done0 = ld_rlx(scr->done);
    if (tid == 0) {
        for (int s = 0; s < 4; s++) mbar_init(bar + 8 * (BAR_FULL + s), 1);
        asm volatile("fence.mbarrier_init.release.cluster;" ::: "memory");
        load_stage(0); load_stage(1);
        STAMP(11);
    } else if (tid == 32) {
        if (sb & 1023) __trap();
        sts32(bar + OFF_CNT, 0);
        for (int s = 0; s < 4; s++) mbar_init(bar + 8 * (BAR_EMPTY + s), 8);
        mbar_init(bar + 8 * BAR_WPHI, 1); mbar_init(bar + 8 * BAR_WO, 2); mbar_init(bar + 8 * BAR_WO2, 1); mbar_init(bar + 8 * BAR_XT, 4);
        mbar_init(bar + 8 * BAR_DONE, 9); mbar_init(bar + 8 * BAR_KG, 8); mbar_init(bar + 8 * BAR_SP, 1); mbar_init(bar + 8 * BAR_PUB, 8);
        mbar_init(bar + 8 * BAR_KVF, 4); mbar_init(bar + 8 * BAR_UR, 4); mbar_init(bar + 8 * BAR_WR, 4); mbar_init(bar + 8 * BAR_PREP, 4); mbar_init(bar + 8 * BAR_KGA, 4); mbar_init(bar + 8 * BAR_SP2, 1);
        asm volatile("fence.mbarrier_init.release.cluster;" ::: "memory");
        mbar_expect(bar + 8 * BAR_WPHI, 3072);
        bulk_g2s(sb + OFF_GW, gatew, 1024, bar + 8 * BAR_WPHI);
        bulk_g2s(sb + OFF_WPHI, wphi + bi_j * 1024, 2048, bar + 8 * BAR_WPHI);
    } else if (tid == 64) {
        asm volatile("prefetch.tensormap [%0];" ::"l"(&mw) : "memory");
    }
    const uint32_t buf = sb + OFF_BUF + w4 * BUF_STRIDE, kb_ = sb + OFF_K + w4 * KT_BYTES;
    if ((warp >> 2) == 2) {
#pragma unroll
        for (int v = 0; v < 7; v++) if (v * 32 + lane < KT_BYTES / 16) sts128(kb_ + (v * 32 + lane) * 16, 0, 0, 0, 0);
    }
    __syncthreads();
    asm volatile("" : "+r"(pdt), "+r"(done0)::"memory");
    const unsigned epoch1 = (done0 >> 7) + 1u;
    const uint32_t tag = epoch1 & 1u;

    const int st = tid & 127;
    const uint32_t ub = sb + OFF_U + w4 * U_STRIDE + 256, spare = sb + (w4 < 2 ? OFF_SP0 : OFF_SP1) + (w4 & 1) * 4096;

    auto stg_of = [&](int w) { return w < 8 ? sb + 3 * SLOT + w * 7296 : sb + 2 * SLOT + (w & 3) * 7296; };
    float kc[24];
#pragma unroll
    for (int t = 0; t < 24; t++) kc[t] = 0.f;
    {
        const float dt = bf_round(expf((ch & 1) ? bf_hi(pdt) : bf_lo(pdt)));
        const uint32_t stg = (warp >> 2) == 2 ? buf : stg_of(warp);
        const int sh = ((warp >> 2) & 1) * 16;
        auto pick = [&](uint32_t v) { return __uint_as_float((v >> sh) << 16); };
        const float ea = bf_round(expf(pick(pla)));
        const float arl = (-ea * dt) * 1.4426950408889634f, ait = (pick(pai) * dt) * 0.15915494309189535f;
        cf C2; C2.re = 2.0f * (pick(pcr) * dt); C2.im = 2.0f * (pick(pci) * dt);
        const cf z1 = cexp_p(arl, ait, 1.0f), z128 = cexp_p(arl, ait, 128.0f);
        cf z8 = cexp_p(arl, ait, 8.0f); z8.im = -z8.im;
        const uint32_t lp = stg + lane * 4;
        auto put = [&](int row, const cf& v) { sts32((lp ^ ((row & 7) << 4)) + row * 128, pack2(v.re, v.im)); };
        {
            const cf z16 = cmul(z8, z8);
            cf e; e.re = 1.f; e.im = 0.f;
            cf o = z8;
            put(0, e); put(1, o);
            e = z16; put(2, e);
#pragma unroll
            for (int b = 3; b < 16; b += 2) {
                o = cmul(o, z16); put(b, o);
                if (b + 1 < 16) { e = cmul(e, z16); put(b + 1, e); }
            }
        }
        cf h[8];
        h[0] = C2; put(16, h[0]);
        {
            const cf z2 = cmul(z1, z1);
            h[1] = cmul(h[0], z1);
#pragma unroll
            for (int r = 2; r < 8; r++) h[r] = cmul(h[r - 2], z2);
#pragma unroll
            for (int r = 1; r < 8; r++) put(16 + r, h[r]);
        }
#pragma unroll
        for (int r = 0; r < 8; r++) { h[r] = cmul(h[r], z128); put(24 + r, h[r]); }
#pragma unroll
        for (int al = 0; al < 2; al++)
#pragma unroll
            for (int r = 0; r < 4; r++) { h[2 * r] = cmul(h[2 * r], z128); put(32 + al * 4 + r, h[2 * r]); }
#pragma unroll
        for (int al = 0; al < 4; al++)
#pragma unroll
            for (int r = 0; r < 2; r++) { h[4 * r] = cmul(h[4 * r], z128); put(40 + al * 2 + r, h[4 * r]); }
#pragma unroll
        for (int al = 0; al < 9; al++) { h[0] = cmul(h[0], z128); put(48 + al, h[0]); }
        __syncwarp();
        const int lr = lane & 7, lm = lane >> 3;
#pragma unroll
        for (int kp = 0; kp < 2; kp++) {
            uint32_t a0[4], a1[4];
            ldsm4(a0, stg + ((lm & 1) * 8 + lr) * 128 + (((4 * kp + (lm >> 1)) ^ lr) << 4));
            ldsm4(a1, stg + ((lm & 1) * 8 + lr) * 128 + (((4 * kp + 2 + (lm >> 1)) ^ lr) << 4));
#pragma unroll
            for (int t = 0; t < 6; t++) {
                uint32_t b[4];
                ldsm4(b, stg + (16 + 8 * t + lr) * 128 + (((4 * kp + lm) ^ lr) << 4));
                mma16816(kc + 4 * t, a0[0], a0[1], a0[2], a0[3], b[0], b[1]);
                mma16816(kc + 4 * t, a1[0], a1[1], a1[2], a1[3], b[2], b[3]);
            }
        }
        __syncwarp();
        if ((warp >> 2) != 2) {
#pragma unroll
            for (int t = 0; t < 6; t++)
                sts128(stg + (t * 32 + lane) * 16, __float_as_uint(kc[4 * t]), __float_as_uint(kc[4 * t + 1]), __float_as_uint(kc[4 * t + 2]), __float_as_uint(kc[4 * t + 3]));
            asm volatile("fence.proxy.async.shared::cta;" ::: "memory");
            __syncwarp();
            if (lane == 0) mbar_arrive(bar + 8 * (warp < 8 ? BAR_KG : BAR_KGA));
        }
    }

    if (warp < 8) {
        const int wg = warp >> 2;
        if (warp == 0) STAMP(21);
        float acc[96];
        const int srow = warp * 16 + (lane & 15);
        const uint32_t srow_a = srow * 128;
        const int sx = srow & 7, shi = lane >> 4;
#pragma unroll
        for (int r = 0; r < 96; r++) acc[r] = 0.f;
        fence_regs<96>(acc);
        const uint64_t da0 = mkdesc(sb + wg * 8192, 16, 1024), db0 = mkdesc(sb + 16384, 8192, 1024);
#pragma unroll 1
        for (int kb = 0; kb < 8; kb++) {
            const int s = kb & 3;
            const uint64_t da = da0 + s * (SLOT >> 4), db = db0 + s * (SLOT >> 4);
            if (warp == 0) STAMP(40 + kb);
            mbar_wait(bar + 8 * (BAR_FULL + s), kb >> 2);
            if (warp == 0) STAMP(32 + kb);
            wg_fence();
#pragma unroll
            for (int k = 0; k < 4; k++) wgmma192(acc, da + 2 * k, db + 128 * k);
            wg_commit();
            wg_wait<1>();
            if (lane == 0 && kb > 0) mbar_arrive(bar + 8 * (BAR_EMPTY + ((kb - 1) & 3)));
        }
        mbar_wait(bar + 8 * BAR_WPHI, 0);
        wg_wait<0>();
        fence_regs<96>(acc);
        if (lane == 0) mbar_arrive(bar + 8 * BAR_DONE);
        if (warp == 0) STAMP(1);
        uint32_t in[32], va[16];
#pragma unroll
        for (int r = 0; r < 16; r++) {
            in[r] = pack2(acc[32 + 2 * r], acc[32 + 2 * r + 1]);
            in[16 + r] = pack2(acc[2 * r], acc[2 * r + 1]);
            va[r] = pack2(acc[64 + 2 * r], acc[64 + 2 * r + 1]);
        }
        const uint32_t wphi_a = sb + OFF_WPHI + (lane & 15) * 32 + (lane >> 4) * 16;
        uint32_t pq[4][8];
#pragma unroll 1
        for (int it = 0; it < 4; it++) {
            hedgehog2(in, wphi_a + (it & 1) * 1024, pq + 2);
#pragma unroll
            for (int r = 0; r < 24; r++) in[r] = in[r + 8];
            if (it < 2) {
#pragma unroll
                for (int hs = 0; hs < 4; hs++) {
                    float c[4] = {0.f, 0.f, 0.f, 0.f};
                    uint32_t* o = pq[2 + (hs >> 1)] + 4 * (hs & 1);
                    mma16816(c, o[0], o[1], o[2], o[3], 0x3f803f80u, 0x3f803f80u);
                    const float r0 = rcp(c[0]), r1 = rcp(c[2]);
                    const uint32_t s0 = pack2(r0, r0), s1 = pack2(r1, r1);
                    o[0] = hmul2(o[0], s0); o[1] = hmul2(o[1], s1); o[2] = hmul2(o[2], s0); o[3] = hmul2(o[3], s1);
                }
                if (it == 0) mbar_wait(bar + 8 * BAR_DONE, 0);
                const uint32_t pt = sb + OFF_P + it * 16384 + srow_a, vt = sb + OFF_V + it * 16384 + srow_a;
#pragma unroll
                for (int hl = 0; hl < 2; hl++) {
                    stsm4(pt + (((4 * hl + shi) ^ sx) << 4), pq[2 + hl][0], pq[2 + hl][1], pq[2 + hl][2], pq[2 + hl][3]);
                    stsm4(pt + (((4 * hl + 2 + shi) ^ sx) << 4), pq[2 + hl][4], pq[2 + hl][5], pq[2 + hl][6], pq[2 + hl][7]);
                    stsm4(vt + (((2 * hl + shi) ^ sx) << 4), va[4 * hl], va[4 * hl + 1], va[4 * hl + 2], va[4 * hl + 3]);
                }
                if (lane < 16) sts128(vt + ((4 ^ sx) << 4), 0x3f803f80u, 0x3f803f80u, 0x3f803f80u, 0x3f803f80u);
#pragma unroll
                for (int r = 0; r < 8; r++) va[r] = va[r + 8];
            }
            if (it == 1) {
                asm volatile("fence.proxy.async.shared::cta;" ::: "memory");
                bar_named(1, 256);
                if (warp == 0) STAMP(2);
                float d[32];
                const uint64_t dv = mkdesc(sb + OFF_V + wg * 16384, 16, 1024), dp = mkdesc(sb + OFF_P + wg * 16384, 16, 1024);
                wg_fence();
#pragma unroll
                for (int k = 0; k < 8; k++) wgmma64_tt(d, dv + 128 * k, dp + 128 * k, k != 0);
                wg_commit();
                wg_wait<0>();
                fence_regs<32>(d);
                mbar_wait(bar + 8 * BAR_PREP, 0);
                uint4* kvp = scr->kvp + bi * 544 + wg * 272;
                if (w4 < 2) {
                    uint32_t e[16];
#pragma unroll
                    for (int r = 0; r < 16; r++) e[r] = __float_as_uint(w4 ? d[16 + r] : d[r]);
                    uint4* p = kvp + w4 * 136 + lane;
#pragma unroll
                    for (int ks = 0; ks < 2; ks++)
#pragma unroll
                        for (int nt = 0; nt < 2; nt++)
                            st_rlx128(p + (ks * 2 + nt) * 32, tag4(e[8 * ks + 2 * nt], e[8 * ks + 2 * nt + 1], e[8 * ks + 4 + 2 * nt], e[8 * ks + 4 + 2 * nt + 1], tag));
                } else if (w4 == 2 && lane < 4) {
#pragma unroll
                    for (int hl = 0; hl < 2; hl++)
#pragma unroll
                        for (int ks = 0; ks < 2; ks++)
                            st_rlx128(kvp + hl * 136 + 128 + ks * 4 + lane, tag4(__float_as_uint(d[16 * hl + 8 * ks]), __float_as_uint(d[16 * hl + 8 * ks + 1]),
                                                                                __float_as_uint(d[16 * hl + 8 * ks + 4]), __float_as_uint(d[16 * hl + 8 * ks + 5]), tag));
                }
                __syncwarp();
                if (lane == 0) mbar_arrive(bar + 8 * BAR_PUB);
                if (warp == 0) STAMP(3);
            }
            if (it == 2) {
#pragma unroll
                for (int r = 0; r < 8; r++) { pq[0][r] = pq[2][r]; pq[1][r] = pq[3][r]; }
            }
        }
        if (warp == 0) STAMP(4);
        asm volatile("setmaxnreg.inc.sync.aligned.u32 160;");
        {
            mbar_wait(bar + 8 * BAR_KVF, 0);
            uint4 kf[4][3];
#pragma unroll
            for (int hh = 0; hh < 4; hh++) {
                const uint32_t a = sb + OFF_KVF + hh * 1088;
                kf[hh][0] = lds128(a + lane * 32); kf[hh][1] = lds128(a + lane * 32 + 16); kf[hh][2] = lds128(a + 1024 + q * 16);
            }
            if (warp == 0) STAMP(5);
            uint4 own[4];
#pragma unroll
            for (int hh = 0; hh < 4; hh++) {
                float c[6][4];
#pragma unroll
                for (int t = 0; t < 6; t++) { c[t][0] = c[t][1] = c[t][2] = c[t][3] = 0.f; }
                const uint32_t* a = pq[hh];
                const bool od = g & 1;
                mma16816(c[0], a[0], a[1], a[2], a[3], od ? 0x3f803f80u : kf[hh][2].x, od ? 0x3f803f80u : kf[hh][2].y);
                mma16816(c[1], a[4], a[5], a[6], a[7], od ? 0x3f803f80u : kf[hh][2].z, od ? 0x3f803f80u : kf[hh][2].w);
                mma16816(c[2], a[0], a[1], a[2], a[3], kf[hh][0].x, kf[hh][0].y);
                mma16816(c[3], a[0], a[1], a[2], a[3], kf[hh][0].z, kf[hh][0].w);
                mma16816(c[4], a[4], a[5], a[6], a[7], kf[hh][1].x, kf[hh][1].y);
                mma16816(c[5], a[4], a[5], a[6], a[7], kf[hh][1].z, kf[hh][1].w);
                uint32_t w[4];
#pragma unroll
                for (int k = 0; k < 2; k++) {
                    const float rho = c[0][2 * k + 1] * rcp(c[1][2 * k + 1]);
                    const float r = rcp(fmaf(c[0][2 * k + 1], 1e-6f, fmaf(rho, c[1][2 * k], c[0][2 * k]))), rr = r * rho;
                    w[k] = pack2(fmaf(c[4][2 * k], rr, c[2][2 * k] * r), fmaf(c[4][2 * k + 1], rr, c[2][2 * k + 1] * r));
                    w[2 + k] = pack2(fmaf(c[5][2 * k], rr, c[3][2 * k] * r), fmaf(c[5][2 * k + 1], rr, c[3][2 * k + 1] * r));
                }
                own[hh] = tag4(w[0], w[1], w[2], w[3], tag);
            }
            uint4* og = scr->o + ((bi_i * 8 + warp) * 32 + bi_j * 4) * 32 + lane;
#pragma unroll
            for (int hh = 0; hh < 4; hh++) st_rlx128(og + hh * 32, own[hh]);
        }
        if (warp == 0) STAMP(6);
        float oc[64];
        const int slab = bi_i * 8 + (bi_j >> 2) * 4 + w4;
        const uint8_t* yb = (const uint8_t*)scr->y + (size_t)((bi_j & 3) * 32 + wg * 16 + (q >> 1)) * 16384 + slab * 128 + g * 16 + (q & 1) * 8;
        const unsigned* gp = scr->g + (slab * 8 + (g >> 1)) * 8 + (g & 1) * 4;
        uint2 yv[8]; unsigned g0, g1;
        {
            const uint4* osrc = scr->o + (slab * 32 + wg * 16) * 32 + lane;
            uint4 fr[16];
            const unsigned* probe = (const unsigned*)(osrc - lane + ((lane & 3) * 4 + 3) * 32 + 31) + 2;
            {
                unsigned miss = ~0u;
                int n = 0;
#pragma unroll
                for (int s = 0; s < 4; s++) {
#pragma unroll 1
                    while ((miss >> s) & 1) { miss = __ballot_sync(~0u, (ld_rlx(probe) ^ tag) & 1); if (++n > SPIN_LIMIT) break; }
#pragma unroll
                    for (int k = 4 * s; k < 4 * s + 4; k++) fr[k] = ld_rlx128(osrc + k * 32);
                }
            }
            if (warp == 0) STAMP(14);
            mbar_wait(bar + 8 * (wg ? BAR_WO2 : BAR_WO), 0);
            const uint64_t dw = mkdesc(sb + wg * 2 * SLOT, wg ? 32768 : SLOT, 1024);
#pragma unroll
            for (int s = 0; s < 4; s++) {
                int n = 0;
#pragma unroll 1
                while (__builtin_expect(__any_sync(~0u, (bad4(fr[4 * s], tag) | bad4(fr[4 * s + 1], tag) | bad4(fr[4 * s + 2], tag) | bad4(fr[4 * s + 3], tag)) & 1), 0)) {
#pragma unroll
                    for (int k = 4 * s; k < 4 * s + 4; k++) fr[k] = ld_rlx128(osrc + k * 32);
                    if (++n > SPIN_LIMIT) break;
                }
                wg_fence();
#pragma unroll
                for (int hh = 0; hh < 4; hh++) wgmma128_rs(oc, fr[4 * s + hh], dw + 128 * (4 * s + hh), (s | hh) != 0);
                wg_commit();
                if (s == 1) {
                    wg_wait<1>();
#pragma unroll
                    for (int nt = 0; nt < 8; nt++) yv[nt] = ld_rlx64(yb + nt * 32768);
                    g0 = ld_rlx(gp); g1 = ld_rlx(gp + 32);
                }
            }
            if (warp == 0) STAMP(7);
            {
                const unsigned* yprobe = scr->yflag + ((bi_j & 3) * 32 + wg * 16 + (lane & 15)) * 8;
                int n = 0;
#pragma unroll 1
                while (true) {
                    uint32_t bad = (g0 ^ tag) | (g1 ^ tag);
#pragma unroll
                    for (int nt = 0; nt < 8; nt++) bad |= yv[nt].x ^ tag;
                    if (!__any_sync(~0u, bad & 1)) break;
#pragma unroll 1
                    while (__any_sync(~0u, (ld_rlx(yprobe) ^ tag) & 1)) { if (++n > SPIN_LIMIT) break; }
#pragma unroll
                    for (int nt = 0; nt < 8; nt++) yv[nt] = ld_rlx64(yb + nt * 32768);
                    g0 = ld_rlx(gp); g1 = ld_rlx(gp + 32);
                    if (++n > SPIN_LIMIT) break;
                }
            }
            if (warp == 0) STAMP(28);
            wg_wait<0>();
            fence_regs<64>(oc);
        }
        {
            bar_named(3 + wg, 128);
            const uint32_t xw = sb + wg * 2 * SLOT + (tid & 127) * 16, xr = sb + (wg ^ 1) * 2 * SLOT + (tid & 127) * 16;
#pragma unroll
            for (int r = 0; r < 8; r++) {
                const float* o = oc + 4 * r;
                sts128(xw + r * 2048, __float_as_uint(wg ? o[0] : o[32]), __float_as_uint(wg ? o[1] : o[33]), __float_as_uint(wg ? o[2] : o[34]), __float_as_uint(wg ? o[3] : o[35]));
            }
#pragma unroll
            for (int r = 0; r < 32; r++) oc[r] = wg ? oc[32 + r] : oc[r];
            bar_named(1, 256);
            if (warp == 0) STAMP(8);
            const float ga = bf_hi(g0), gb = bf_hi(g1);
            const float ha = bf_round(1.0f - ga), hb = bf_round(1.0f - gb);
            uint32_t w[8][2];
#pragma unroll
            for (int nt = 0; nt < 8; nt++) {
                const uint4 p = lds128(xr + nt * 2048);
                w[nt][0] = pack2(fmaf(ga, oc[4 * nt] + __uint_as_float(p.x), ha * bf_lo(yv[nt].x)), fmaf(ga, oc[4 * nt + 1] + __uint_as_float(p.y), ha * bf_hi(yv[nt].x)));
                w[nt][1] = pack2(fmaf(gb, oc[4 * nt + 2] + __uint_as_float(p.z), hb * bf_lo(yv[nt].y)), fmaf(gb, oc[4 * nt + 3] + __uint_as_float(p.w), hb * bf_hi(yv[nt].y)));
            }
            const uint32_t ob = sb + wg * 2 * SLOT + 16384 + w4 * 2048;
#pragma unroll
            for (int nt = 0; nt < 8; nt += 2)
                stsm4(ob + (lane & 15) * 128 + (((nt + shi) ^ (lane & 7)) << 4), w[nt][0], w[nt][1], w[nt + 1][0], w[nt + 1][1]);
            __syncwarp();
            bf16* op = out + (size_t)(slab * 16) * 512 + (bi_j & 3) * 128 + wg * 64 + (lane & 7) * 8;
#pragma unroll
            for (int it = 0; it < 4; it++) {
                const int r = it * 4 + (lane >> 3);
                uint4 v = lds128(ob + r * 128 + (((lane & 7) ^ (r & 7)) << 4));
                *(uint4*)(op + r * 512) = v;
            }
        }
        if (warp == 0) STAMP(10);
    } else if (warp < 12) {
#pragma unroll
        for (int src = 2; src >= 0; src--) {
            if (src != 0) mbar_wait(bar + 8 * (src == 2 ? BAR_KGA : BAR_KG), 0);
#pragma unroll
            for (int t = 0; t < 6; t++) {
                const uint4 v = lds128(stg_of(w4 + src * 4) + (t * 32 + lane) * 16);
                kc[4 * t] += __uint_as_float(v.x); kc[4 * t + 1] += __uint_as_float(v.y); kc[4 * t + 2] += __uint_as_float(v.z); kc[4 * t + 3] += __uint_as_float(v.w);
            }
            if (src != 1) {
                bar_named(2, 128);
                if (st == 0) { load_stage(src == 2 ? 2 : 3); if (src == 0) mbar_arrive(bar + 8 * BAR_SP); }
                if (warp == 8) STAMP(src == 2 ? 22 : 17);
            }
        }
        if (warp == 8) {
            const int row = bi_j * 16 + (lane >> 1), half = lane & 1;
            unsigned* gp = scr->g + (bi_i * 64 + bi_j * 8) * 8 + lane * 2;
            st_rlx64(gp, tag ^ 1u, tag ^ 1u);
            if (lane < 8) st_rlx32(scr->yflag + bi * 8 + lane, tag ^ 1u);
            float gs0 = 0.f, gs1 = 0.f;
            mbar_wait(bar + 8 * BAR_WPHI, 0);
#pragma unroll 1
            for (int kb = 0; kb < 8; kb++) {
                const int s = kb & 3;
                mbar_wait(bar + 8 * (BAR_FULL + s), kb >> 2);
#pragma unroll
                for (int c = 0; c < 4; c++) {
                    const uint4 xv = lds128(sb + s * SLOT + row * 128 + (((half * 4 + c) ^ (row & 7)) << 4));
                    const uint4 gw = lds128(sb + OFF_GW + ((kb + rot) & 7) * 128 + half * 64 + c * 16);
                    const uint32_t p0 = hmul2(xv.x, gw.x), p1 = hmul2(xv.y, gw.y), p2 = hmul2(xv.z, gw.z), p3 = hmul2(xv.w, gw.w);
                    gs0 += (bf_lo(p0) + bf_lo(p1)) + (bf_lo(p2) + bf_lo(p3));
                    gs1 += (bf_hi(p0) + bf_hi(p1)) + (bf_hi(p2) + bf_hi(p3));
                }
                if (kb < 6) {
                    mbar_wait(bar + 8 * (BAR_EMPTY + s), kb >> 2);
                    if (kb == xkb) mbar_wait(bar + 8 * BAR_XT, 0);
                    if (lane == 0) {
                        STAMP(48 + kb);
                        if (kb < 4) load_stage(kb + 4);
                        else {
                            mbar_expect(bar + 8 * BAR_WO, 32768);
                            tma2d(sb + s * SLOT, &mwo, (bi_j & 3) * 128 + s * 64, 0, bar + 8 * BAR_WO);
                            if (kb == 5) mbar_arrive(bar + 8 * BAR_SP2);
                        }
                    }
                }
                __syncwarp();
            }
            if (lane == 0) mbar_arrive(bar + 8 * BAR_DONE);
            float gs = gs0 + gs1;
            gs += __shfl_xor_sync(~0u, gs, 1);
            const uint32_t gv = __float_as_uint(bf_round(rcp(1.0f + ex2(-1.4426950408889634f * bf_round(gs))))) | tag;
            st_rlx64(gp, gv, gv);
        }
        if (lane == 0) kc[4 * 0 + 0] += ((ch & 1) ? bf_hi(pds) : bf_lo(pds));
        const uint32_t k1024 = __shfl_sync(~0u, pack2(kc[4 * 4 + 0], 0.f), 0);
#pragma unroll
        for (int i = 0; i < 2; i++) {
            const int be = g + 8 * i;
#pragma unroll
            for (int t = 0; t < 2; t++) {
                const uint32_t a = kb_ + (KW_D + 128 * t + 8 * be + 2 * q) * 4;
                const uint32_t w = pack2(kc[4 * t + 2 * i + 1], kc[4 * t + 2 * i]);
                sts32(a + 4, w); sts16(a, w >> 16); sts16(a + 10, w);
            }
            {
                const int p = 256 + 128 * (q >> 1) + 8 * be + 4 * (q & 1);
                const uint32_t a = kb_ + (KW_D + p) * 4;
                const uint32_t w = pack2(kc[4 * 2 + 2 * i + 1], kc[4 * 2 + 2 * i]);
                const uint32_t aa = (w >> 16) | (w & 0xffff0000u);
                if (p != 256) { sts16(a - 4, aa); sts32(a, aa); } else sts16(a, aa);
                sts32(a + 4, aa); sts32(a + 8, w); sts16(a + 14, w);
            }
            {
                const int k = 64 + 16 * q + be;
                const uint32_t w = pack2(kc[4 * 3 + 2 * i], kc[4 * 3 + 2 * i + 1]);
                if (k != 64) sts16(kb_ + (KW_2 + ((k - 1) >> 1) - 24) * 4 + (k & 1) * 2, w);
                else {
                    const uint32_t a = kb_ + (KW_D + 511) * 4, aa = (w << 16) | (w & 0xffffu);
                    sts16(a, w); sts32(a + 4, aa); sts32(a + 8, aa); sts32(a + 12, aa); sts16(a + 18, w);
                }
                sts16(kb_ + (KW_2 + 48 + (k >> 1) - 24) * 4 + ((k & 1) ^ 1) * 2, w >> 16);
            }
#pragma unroll
            for (int b = 0; b < 2; b++) {
                const int k = 64 + 8 * (2 * q + b) + (be >> 1);
                const uint32_t w = pack2(kc[4 * 4 + 2 * i + b], 0.f);
                if (!(be & 1) && k == 64) sts16(kb_ + (KW_2 + 63 - 24) * 4, w);
                else {
                    const uint32_t a = kb_ + (KW_3 + ((be & 1) ? 80 + k : k - 1) - 48) * 4;
                    sts16(a, w);
                    if (!((be & 1) && k == 127)) sts16(a + 6, w);
                }
            }
        }
        if (lane == 0) sts16(kb_ + (KW_3 + 127 - 48) * 4, pack2(kc[4 * 5 + 0], 0.f));
        __syncwarp();
        mbar_wait(bar + 8 * BAR_UR, 0);
        mbar_wait(bar + 8 * BAR_DONE, 0);
        if (warp == 8) STAMP(23);
        float y[16][4];
#pragma unroll
        for (int nt = 0; nt < 16; nt++) { y[nt][0] = y[nt][1] = y[nt][2] = y[nt][3] = 0.f; }
        {
            uint32_t Bp[32], A[5][3];
            auto uaddr = [&](int rho) { const int R0 = (lane >> 4) * 8 + (lane & 7) - rho; return ub + (((2 * R0 + ((lane >> 3) & 1)) ^ ((R0 >> 2) & 1)) << 4); };
            const uint32_t kd = kb_ + (KW_D + g - 2 * q) * 4;
            auto lda = [&](int rho) {
#pragma unroll
                for (int ga = 0; ga < 5; ga++) {
                    const uint32_t a = kd + (ga < 4 ? rho : (rho & 1)) * 64 + ga * 512;
                    A[ga][0] = lds32(a); A[ga][1] = lds32(a + 32); A[ga][2] = lds32(a - 32);
                }
            };
            {
                const uint32_t a = uaddr(0);
#pragma unroll
                for (int p = 0; p < 8; p++) ldsm4(Bp + 4 * p, a + p * 512);
            }
#pragma unroll 1
            for (int rho = 0; rho < 8; rho++) {
                lda(rho);
                if (rho < 2) {
#pragma unroll
                    for (int nt = 4; nt < 16; nt++) mma16816(y[nt], A[4][0], A[4][1], A[4][2], A[4][0], Bp[2 * (nt - 4)], Bp[2 * (nt - 4) + 1]);
                }
#pragma unroll
                for (int ga = 0; ga < 3; ga++)
#pragma unroll
                    for (int nt = 15; nt >= ga; nt--) mma16816(y[nt], A[ga][0], A[ga][1], A[ga][2], A[ga][0], Bp[2 * (nt - ga)], Bp[2 * (nt - ga) + 1]);
                const uint32_t an = uaddr(rho + 1);
                ldsm4(Bp + 28, an + 7 * 512);
#pragma unroll
                for (int nt = 15; nt >= 3; nt--) {
                    mma16816(y[nt], A[3][0], A[3][1], A[3][2], A[3][0], Bp[2 * (nt - 3)], Bp[2 * (nt - 3) + 1]);
                    if (nt & 1) ldsm4(Bp + 2 * (nt - 3), an + ((nt - 3) >> 1) * 512);
                }
            }
        }
        if (warp == 8) STAMP(18);
        mbar_wait(bar + 8 * BAR_WR, 0);
#pragma unroll 1
        for (int ph = 0; ph < 2; ph++) {
            uint32_t B[5][2];
            const uint32_t ka = kb_ + (KW_2 + ph * 48 + 8 + g - q) * 4;
#pragma unroll
            for (int dd = 0; dd < 5; dd++) { B[dd][0] = lds32(ka + dd * 32); B[dd][1] = lds32(ka + dd * 32 - 16); }
            const uint32_t wa = buf + ph * W3_OFF + ((lane & 7) + ((lane >> 3) & 1) + (lane >> 4) * 8) * 16;
#pragma unroll
            for (int s = 0; s < 12; s++) {
                uint32_t A[4];
                ldsm4t(A, wa + s * 256);
#pragma unroll
                for (int dd = 0; dd < 5; dd++)
                    if (s + 4 + dd < 16) mma16816(y[s + 4 + dd], A[0], A[1], A[2], A[3], B[dd][0], B[dd][1]);
            }
        }
        {
            const int ap = (lane & 7) + (lane >> 4) * 8;
            const uint32_t loff = ((2 * ap + ((lane >> 3) & 1)) ^ ((ap >> 2) & 1)) << 4;
#pragma unroll 1
            for (int ph = 0; ph < 2; ph++) {
                uint32_t B[8][2];
                const uint32_t wb = (ph ? spare : buf + W9_OFF) + loff;
                const uint32_t ka = kb_ + (KW_3 + ph * 80 + 16 + g - 2 * q) * 4;
#pragma unroll
                for (int dd = 0; dd < 8; dd++) { B[dd][0] = lds32(ka + dd * 32); B[dd][1] = lds32(ka + dd * 32 - 32); }
#pragma unroll
                for (int s = 0; s < 4; s++) {
                    uint32_t A[4];
                    ldsm4t(A, wb + s * 512);
#pragma unroll
                    for (int dd = 0; dd < 8; dd++)
                        if (8 + 2 * s + dd < 16) mma16816(y[8 + 2 * s + dd], A[0], A[1], A[2], A[3], B[dd][0], B[dd][1]);
                }
            }
            const uint32_t idw = (g == 2 * q) ? k1024 : ((g == 2 * q + 1) ? (k1024 << 16) : 0u);
#pragma unroll
            for (int s = 0; s < 4; s++) {
                uint32_t A[4];
                ldsm4t(A, spare + 2048 + loff + s * 512);
                mma16816(y[8 + 2 * s], A[0], A[1], A[2], A[3], idw, 0u);
                mma16816(y[9 + 2 * s], A[0], A[1], A[2], A[3], 0u, idw);
            }
        }
        __syncwarp();
        if (warp == 8) STAMP(19);
#pragma unroll
        for (int nt = 0; nt < 16; nt++)
#pragma unroll
            for (int b = 0; b < 2; b++) sts32(buf + ((8 * nt + 2 * q + b) * 8 + g) * 4, pack2(y[nt][b], y[nt][2 + b]));
        bar_named(2, 128);
        uint4* yp = scr->y + bi * 1024 + st;
#pragma unroll
        for (int v = 0; v < 8; v++) {
            const uint32_t a = sb + OFF_BUF + (st + 128 * v) * 4;
            const uint32_t w0 = lds32(a), w1 = lds32(a + BUF_STRIDE), w2 = lds32(a + 2 * BUF_STRIDE), w3 = lds32(a + 3 * BUF_STRIDE);
            st_rlx128(yp + v * 128, tag4(__byte_perm(w0, w1, 0x5410), __byte_perm(w0, w1, 0x7632), __byte_perm(w2, w3, 0x5410), __byte_perm(w2, w3, 0x7632), tag));
        }
        if (st < 8) st_rlx32(scr->yflag + bi * 8 + st, tag);
        if (warp == 8) STAMP(20);
    } else {
        asm volatile("setmaxnreg.dec.sync.aligned.u32 64;");
        const int qq = (bi_i & 2) + ((lane >> 1) & 1);
        uint2* kvf_h = (uint2*)(scr->kvf + (bi_j * 4 + (bi_i >> 2)) * 68);
        auto windows = [&](int rhi, int rlo) {
#pragma unroll 1
            for (int rho = rhi; rho >= rlo; rho--) {
                const int ci = lane + 32 * rho;
                uint4 e4[4];
#pragma unroll
                for (int v = 0; v < 4; v++) { const int cc = ci - 3 + v; e4[v] = lds128(ub + ((cc ^ ((cc >> 3) & 1)) << 4)); }
                float S[29];
                const uint32_t* ew = (const uint32_t*)e4;
                S[3] = 0.f;
#pragma unroll
                for (int k = 4; k <= 28; k++) S[k] = S[k - 1] + ((k & 1) ? bf_hi(ew[k >> 1]) : bf_lo(ew[k >> 1]));
                auto win = [&](int lo, int hi, uint32_t a) {
                    sts128(a, pack2(S[hi] - S[lo - 1], S[hi + 1] - S[lo]), pack2(S[hi + 2] - S[lo + 1], S[hi + 3] - S[lo + 2]),
                           pack2(S[hi + 4] - S[lo + 3], S[hi + 5] - S[lo + 4]), pack2(S[hi + 6] - S[lo + 5], S[hi + 7] - S[lo + 6]));
                };
                win(14, 18, buf + W5_OFF + 16 + ci * 16); win(19, 21, buf + W3_OFF + 16 + ci * 16);
                if (rho < 4) {
                    const uint32_t sw = (ci ^ ((ci >> 3) & 1)) << 4;
                    win(4, 12, buf + W9_OFF + sw); win(13, 19, spare + sw); win(20, 21, spare + 2048 + sw);
                }
            }
        };
        {
            mbar_wait(bar + 8 * (BAR_FULL + xkb), 0);
#pragma unroll 1
            for (int hf = 0; hf < 2; hf++) {
                const int r = w4 * 32 + hf * 16 + (lane & 15);
                uint32_t* xt = (uint32_t*)scr->xt + ((xkb + rot) * 16 + (g >> 2)) * 4096 + (bi_i * 16 + w4 * 4 + hf * 2) * 16 + (g & 3) * 4 + q;
#pragma unroll
                for (int cb = 0; cb < 8; cb += 2) {
                    uint32_t v[4];
                    ldsm4t(v, sb + xkb * SLOT + r * 128 + (((cb + (lane >> 4)) ^ (r & 7)) << 4));
                    xt[cb * 8192] = v[0]; xt[cb * 8192 + 16] = v[1]; xt[cb * 8192 + 8192] = v[2]; xt[cb * 8192 + 8192 + 16] = v[3];
                }
            }
            __syncwarp();
            if (lane == 0) mbar_arrive(bar + 8 * BAR_XT);
            if (warp == 12) {
                STAMP(26);
                mbar_wait(bar + 8 * BAR_XT, 0);
                if (lane == 0) asm volatile("red.release.gpu.global.add.u32 [%0],8;" ::"l"(scr->xcnt + (xkb + rot) * 32) : "memory");
                __syncwarp();
                STAMP(27);
            }
            {
                const uint32_t old = tag ^ 1u;
                const uint4 z4 = make_uint4(old, 0, old, 0);
#pragma unroll
                for (int v = 0; v < 5; v++) if (v < 4 || st < 32) st_rlx128(scr->kvp + bi * 544 + v * 128 + st, z4);
                if (st < 16) st_rlx128(scr->o + ((bi_i * 8 + (st >> 1)) * 32 + bi_j * 4 + 3) * 32 + 30 + (st & 1), z4);
                if (lane < 8) st_rlx64(kvf_h + ((bi_i & 3) * 8 + w4 * 2 + (lane & 1)) * 4 + (lane >> 1), old, 0);
                if (st < 4 && !(bi_i & 1)) st_rlx64(kvf_h + (64 + qq) * 2 + (lane & 1), old, 0);
                __syncwarp();
                if (lane == 0) mbar_arrive(bar + 8 * BAR_PREP);
            }
            int n = 0;
#pragma unroll 1
            while (__any_sync(~0u, (int)(ld_acq(scr->xcnt + bi_j * 32) - (epoch1 << 7)) < 0)) { if (++n > SPIN_LIMIT) break; }
            if (warp == 12) STAMP(15);
            uint4 ur[8];
#pragma unroll
            for (int v = 0; v < 8; v++) ur[v] = __ldcg(scr->xt + bi * 1024 + st + 128 * v);
            mbar_wait(bar + 8 * BAR_SP, 0);
            if (lane < 16) sts128(ub - 256 + lane * 16, 0, 0, 0, 0);
            if (lane < 2) sts128(buf + lane * W3_OFF, 0, 0, 0, 0);
#pragma unroll
            for (int v = 0; v < 8; v++) {
                const int ci = (st >> 2) + 32 * v;
                sts128(sb + OFF_U + (st & 3) * U_STRIDE + 256 + ((ci ^ ((ci >> 3) & 1)) << 4), ur[v].x, ur[v].y, ur[v].z, ur[v].w);
            }
            __syncwarp();
            if (lane == 0) mbar_arrive(bar + 8 * BAR_UR);
            mbar_wait(bar + 8 * BAR_UR, 0);
            if (warp == 12) STAMP(16);
            windows(5, 4);
        }
        mbar_wait(bar + 8 * BAR_SP2, 0);
        windows(3, 0);
        __syncwarp();
        if (lane == 0) mbar_arrive(bar + 8 * BAR_WR);
        if (warp == 12) STAMP(24);
        {
            const bool zw = st < 32 && !(bi_i & 1);
            const uint4* src = scr->kvp + bi_j * (16 * 544) + (bi_i >> 2) * 136;
            const uint4* zsrc = src + (lane >> 2) * (2 * 544) + 128 + (lane & 1) * 4 + qq;
            src += (lane >> 3) * (4 * 544) + ((lane >> 1) & 3) * 32 + (bi_i & 3) * 8 + w4 * 2 + (lane & 1);
            if (!zw) zsrc = src;
            mbar_wait(bar + 8 * BAR_PUB, 0);
            if (warp == 12) STAMP(12);
            uint4 v[6];
            int n = 0;
#pragma unroll 1
            while (true) {
#pragma unroll
                for (int k = 0; k < 4; k++) v[k] = ld_rlx128(src + k * 544);
                v[4] = ld_rlx128(zsrc); v[5] = ld_rlx128(zsrc + 544);
                if (!__any_sync(~0u, (bad4(v[0], tag) | bad4(v[1], tag) | bad4(v[2], tag) | bad4(v[3], tag) | bad4(v[4], tag) | bad4(v[5], tag)) & 1)) break;
                if (++n > SPIN_LIMIT) break;
            }
            if (warp == 12) STAMP(30);
            float f[8];
            const float* vf = (const float*)v;
#pragma unroll
            for (int r = 0; r < 4; r++) {
                f[r] = (vf[r] + vf[4 + r]) + (vf[8 + r] + vf[12 + r]);
                f[4 + r] = vf[16 + r] + vf[20 + r];
                f[4 + r] += __shfl_xor_sync(~0u, f[4 + r], 4);
            }
#pragma unroll
            for (int o = 8; o <= 16; o <<= 1)
#pragma unroll
                for (int r = 0; r < 8; r++) f[r] += __shfl_xor_sync(~0u, f[r], o);
            if (lane < 8) st_rlx64(kvf_h + ((bi_i & 3) * 8 + w4 * 2 + (lane & 1)) * 4 + (lane >> 1), tagw(pack2(f[0], f[1]), tag), pack2(f[2], f[3]));
            if (zw && lane < 4) st_rlx64(kvf_h + (64 + qq) * 2 + (lane & 1), tagw(pack2(f[4], f[5]), tag), pack2(f[6], f[7]));
        }
        if (warp == 12) STAMP(13);
        {
            const uint4* kp = scr->kvf + bi_j * 272 + st;
            uint4 v0, v1, v2;
            int n = 0;
#pragma unroll 1
            while (true) {
                v0 = ld_rlx128(kp); v1 = ld_rlx128(kp + 128); v2 = ld_rlx128(kp + (st < 16 ? 256 : 0));
                if (!__any_sync(~0u, (bad4(v0, tag) | bad4(v1, tag) | bad4(v2, tag)) & 1)) break;
                if (++n > SPIN_LIMIT) break;
            }
            sts128(sb + OFF_KVF + st * 16, v0.x, v0.y, v0.z, v0.w);
            sts128(sb + OFF_KVF + 2048 + st * 16, v1.x, v1.y, v1.z, v1.w);
            if (st < 16) sts128(sb + OFF_KVF + 4096 + st * 16, v2.x, v2.y, v2.z, v2.w);
            __syncwarp();
            if (lane == 0) mbar_arrive(bar + 8 * BAR_KVF);
        }
        if (warp == 13) {
            mbar_wait(bar + 8 * BAR_KVF, 0);
            if (lane == 0) {
                mbar_expect(bar + 8 * BAR_WO2, 65536);
                tma2d(sb + OFF_P, &mwo, (bi_j & 3) * 128, 256, bar + 8 * BAR_WO2);
                tma2d(sb + OFF_V, &mwo, (bi_j & 3) * 128 + 64, 256, bar + 8 * BAR_WO2);
            }
        }
        if (warp == 12) STAMP(25);
    }
    __syncwarp();
    if (lane == 0) {
        unsigned old;
        asm volatile("atom.acq_rel.cta.shared.add.u32 %0,[%1],1;" : "=r"(old) : "r"(bar + OFF_CNT) : "memory");
        if (old == 15) {
            atomicAdd(scr->done, 1u);
        }
    }
}

typedef CUresult (*EncFn)(CUtensorMap*, CUtensorMapDataType, cuuint32_t, void*, const cuuint64_t*, const cuuint64_t*, const cuuint32_t*,
                          const cuuint32_t*, CUtensorMapInterleave, CUtensorMapSwizzle, CUtensorMapL2promotion, CUtensorMapFloatOOBfill);

extern "C" void kernel_launch(void* const* d_in, const int* in_sizes, int n_in, void* d_out, int out_size) {
    static EncFn enc = nullptr;
    static Scratch* scr = nullptr;
    if (!enc) {
        cudaGetSymbolAddress((void**)&scr, g_scr);
        cudaDriverEntryPointQueryResult qr;
        cudaGetDriverEntryPoint("cuTensorMapEncodeTiled", (void**)&enc, cudaEnableDefault, &qr);
        cudaFuncSetAttribute(fused_kernel, cudaFuncAttributeMaxDynamicSharedMemorySize, SMEM_BYTES);
    }
    CUtensorMap mx, mw, mwo;
    const cuuint32_t es[3] = {1, 1, 1};
    {
        cuuint64_t d[2] = {512, 2048}, s[1] = {1024}; cuuint32_t b[2] = {64, 128};
        enc(&mx, CU_TENSOR_MAP_DATA_TYPE_BFLOAT16, 2, d_in[0], d, s, b, es, CU_TENSOR_MAP_INTERLEAVE_NONE, CU_TENSOR_MAP_SWIZZLE_128B,
            CU_TENSOR_MAP_L2_PROMOTION_L2_128B, CU_TENSOR_MAP_FLOAT_OOB_FILL_NONE);
    }
    {
        cuuint64_t d[3] = {512, 512, 3}, s[2] = {3072, 1024}; cuuint32_t b[3] = {64, 64, 3};
        enc(&mw, CU_TENSOR_MAP_DATA_TYPE_BFLOAT16, 3, d_in[1], d, s, b, es, CU_TENSOR_MAP_INTERLEAVE_NONE, CU_TENSOR_MAP_SWIZZLE_128B,
            CU_TENSOR_MAP_L2_PROMOTION_L2_128B, CU_TENSOR_MAP_FLOAT_OOB_FILL_NONE);
    }
    {
        cuuint64_t d[2] = {512, 512}, s[1] = {1024}; cuuint32_t b[2] = {64, 256};
        enc(&mwo, CU_TENSOR_MAP_DATA_TYPE_BFLOAT16, 2, d_in[3], d, s, b, es, CU_TENSOR_MAP_INTERLEAVE_NONE, CU_TENSOR_MAP_SWIZZLE_128B,
            CU_TENSOR_MAP_L2_PROMOTION_L2_128B, CU_TENSOR_MAP_FLOAT_OOB_FILL_NONE);
    }
    fused_kernel<<<128, 512, SMEM_BYTES, cudaStreamPerThread>>>(
        scr, (const bf16*)d_in[5], (const bf16*)d_in[6], (const bf16*)d_in[7], (const bf16*)d_in[8], (const bf16*)d_in[9],
        (const bf16*)d_in[10], (const bf16*)d_in[2], (const bf16*)d_in[11], (bf16*)d_out, mx, mw, mwo);
}
```

```cpp
#include <cuda_runtime.h>
#include <cuda.h>
#include <cuda_bf16.h>
#include <stdint.h>

typedef __nv_bfloat16 bf16;

struct Scratch {
    uint4 xt[128 * 1024];
    uint4 o[16 * 8 * 32 * 32];
    uint4 y[128 * 1024];
    uint4 kvp[8 * 16 * 544];
    uint4 kvf[8 * 4 * 68];
    unsigned g[1024 * 8];
    unsigned yflag[128 * 8];
    unsigned xcnt[8 * 32];
    unsigned done[32];
};
__device__ Scratch g_scr;
#define STAMP(n)

constexpr int SLOT = 40960;
constexpr int OFF_SP0 = 32768, OFF_SP1 = SLOT + 32768;
constexpr int OFF_P = 2 * SLOT, OFF_V = OFF_P + 32768;
constexpr int OFF_KVF = OFF_V + 32768;
constexpr int KT_BYTES = 3264, KW_D = 16, KW_2 = 560, KW_3 = 656;
constexpr int OFF_U = 4 * SLOT, U_STRIDE = 4096 + 256 + 32;
constexpr int OFF_BUF = OFF_U + 4 * U_STRIDE, BUF_STRIDE = 8320;
constexpr int OFF_K = OFF_BUF + 4 * BUF_STRIDE;
constexpr int OFF_WPHI = OFF_K + 4 * KT_BYTES;
constexpr int OFF_GW = OFF_WPHI + 2048;
constexpr int OFF_BAR = OFF_GW + 1024;
constexpr int SMEM_BYTES = OFF_BAR + 256 + 256;
static_assert(SMEM_BYTES <= 232448 && OFF_BUF % 128 == 0, "smem");
constexpr int W5_OFF = 0, W3_OFF = 3088, W9_OFF = 6176;
constexpr int BAR_FULL = 0, BAR_EMPTY = 4, BAR_WPHI = 8, BAR_WO = 9, BAR_WO2 = 10, BAR_XT = 11, BAR_DONE = 12, BAR_KG = 13, BAR_SP = 14,
              BAR_PUB = 15, BAR_KVF = 16, BAR_UR = 17, BAR_WR = 18, BAR_PREP = 19, BAR_KGA = 20, BAR_SP2 = 21, OFF_CNT = 192, OFF_PAUSE = 196;
#define CONV_START BAR_PUB
constexpr int SPIN_LIMIT = 1 << 17;

__device__ __forceinline__ uint32_t s2u(const void* p) { return (uint32_t)__cvta_generic_to_shared(p); }
__device__ __forceinline__ void mbar_init(uint32_t b, int c) { asm volatile("mbarrier.init.shared::cta.b64 [%0],%1;" ::"r"(b), "r"(c) : "memory"); }
__device__ __forceinline__ void mbar_expect(uint32_t b, int bytes) { asm volatile("mbarrier.arrive.expect_tx.shared::cta.b64 _,[%0],%1;" ::"r"(b), "r"(bytes) : "memory"); }
__device__ __forceinline__ void mbar_arrive(uint32_t b) { asm volatile("mbarrier.arrive.shared::cta.b64 _,[%0];" ::"r"(b) : "memory"); }
__device__ __forceinline__ void mbar_wait(uint32_t b, int ph) {
    asm volatile("{\n.reg .pred p;\n.reg .u32 n;\nmov.u32 n,0;\nLW_%=:\nmbarrier.try_wait.parity.shared::cta.b64 p,[%0],%1;\n@p bra LD_%=;\n"
                 "add.u32 n,n,1;\nsetp.lt.u32 p,n,16384;\n@p bra LW_%=;\nLD_%=:\n}" ::"r"(b), "r"(ph) : "memory");
}
__device__ __forceinline__ void tma2d(uint32_t dst, const CUtensorMap* m, int c0, int c1, uint32_t bar) {
    asm volatile("cp.async.bulk.tensor.2d.shared::cluster.global.mbarrier::complete_tx::bytes [%0],[%1,{%3,%4}],[%2];" ::"r"(dst), "l"(m), "r"(bar), "r"(c0), "r"(c1) : "memory");
}
__device__ __forceinline__ void tma3d(uint32_t dst, const CUtensorMap* m, int c0, int c1, int c2, uint32_t bar) {
    asm volatile("cp.async.bulk.tensor.3d.shared::cluster.global.mbarrier::complete_tx::bytes [%0],[%1,{%3,%4,%5}],[%2];" ::"r"(dst), "l"(m), "r"(bar), "r"(c0), "r"(c1), "r"(c2) : "memory");
}
__device__ __forceinline__ void bulk_g2s(uint32_t dst, const void* src, int bytes, uint32_t bar) {
    asm volatile("cp.async.bulk.shared::cluster.global.mbarrier::complete_tx::bytes [%0],[%1],%2,[%3];" ::"r"(dst), "l"(src), "r"(bytes), "r"(bar) : "memory");
}
__device__ __forceinline__ uint64_t mkdesc(uint32_t addr, uint32_t lbo, uint32_t sbo) {
    return (uint64_t)((addr & 0x3FFFF) >> 4) | ((uint64_t)(lbo >> 4) << 16) | ((uint64_t)(sbo >> 4) << 32) | ((uint64_t)1 << 62);
}
__device__ __forceinline__ void wg_fence() { asm volatile("wgmma.fence.sync.aligned;" ::: "memory"); }
__device__ __forceinline__ void wg_commit() { asm volatile("wgmma.commit_group.sync.aligned;" ::: "memory"); }
template <int N> __device__ __forceinline__ void wg_wait() { asm volatile("wgmma.wait_group.sync.aligned %0;" ::"n"(N) : "memory"); }
template <int N> __device__ __forceinline__ void fence_regs(float* d) {
#pragma unroll
    for (int i = 0; i < N; i++) asm volatile("" : "+f"(d[i])::"memory");
}
#define R8(d, o) "+f"(d[o]), "+f"(d[o + 1]), "+f"(d[o + 2]), "+f"(d[o + 3]), "+f"(d[o + 4]), "+f"(d[o + 5]), "+f"(d[o + 6]), "+f"(d[o + 7])
__device__ __forceinline__ void wgmma192(float* d, uint64_t da, uint64_t db) {
    asm volatile("wgmma.mma_async.sync.aligned.m64n192k16.f32.bf16.bf16 {"
                 "%0,%1,%2,%3,%4,%5,%6,%7,%8,%9,%10,%11,%12,%13,%14,%15,%16,%17,%18,%19,%20,%21,%22,%23,%24,%25,%26,%27,%28,%29,%30,%31,"
                 "%32,%33,%34,%35,%36,%37,%38,%39,%40,%41,%42,%43,%44,%45,%46,%47,%48,%49,%50,%51,%52,%53,%54,%55,%56,%57,%58,%59,%60,%61,%62,%63,"
                 "%64,%65,%66,%67,%68,%69,%70,%71,%72,%73,%74,%75,%76,%77,%78,%79,%80,%81,%82,%83,%84,%85,%86,%87,%88,%89,%90,%91,%92,%93,%94,%95},"
                 "%96,%97,1,1,1,0,1;"
                 : R8(d, 0), R8(d, 8), R8(d, 16), R8(d, 24), R8(d, 32), R8(d, 40), R8(d, 48), R8(d, 56), R8(d, 64), R8(d, 72), R8(d, 80), R8(d, 88)
                 : "l"(da), "l"(db));
}
__device__ __forceinline__ void wgmma64_tt(float* d, uint64_t da, uint64_t db, int sc) {
    asm volatile("{.reg .pred p; setp.ne.b32 p,%34,0; wgmma.mma_async.sync.aligned.m64n64k16.f32.bf16.bf16 {"
                 "%0,%1,%2,%3,%4,%5,%6,%7,%8,%9,%10,%11,%12,%13,%14,%15,%16,%17,%18,%19,%20,%21,%22,%23,%24,%25,%26,%27,%28,%29,%30,%31},"
                 "%32,%33,p,1,1,1,1;}"
                 : R8(d, 0), R8(d, 8), R8(d, 16), R8(d, 24)
                 : "l"(da), "l"(db), "r"(sc));
}
__device__ __forceinline__ void wgmma128_rs(float* d, const uint4& a, uint64_t db, int sc) {
    asm volatile("{.reg .pred p; setp.ne.b32 p,%69,0; wgmma.mma_async.sync.aligned.m64n128k16.f32.bf16.bf16 {"
                 "%0,%1,%2,%3,%4,%5,%6,%7,%8,%9,%10,%11,%12,%13,%14,%15,%16,%17,%18,%19,%20,%21,%22,%23,%24,%25,%26,%27,%28,%29,%30,%31,"
                 "%32,%33,%34,%35,%36,%37,%38,%39,%40,%41,%42,%43,%44,%45,%46,%47,%48,%49,%50,%51,%52,%53,%54,%55,%56,%57,%58,%59,%60,%61,%62,%63},"
                 "{%64,%65,%66,%67},%68,p,1,1,1;}"
                 : R8(d, 0), R8(d, 8), R8(d, 16), R8(d, 24), R8(d, 32), R8(d, 40), R8(d, 48), R8(d, 56)
                 : "r"(a.x), "r"(a.y), "r"(a.z), "r"(a.w), "l"(db), "r"(sc));
}
__device__ __forceinline__ void mma16816(float* c, uint32_t a0, uint32_t a1, uint32_t a2, uint32_t a3, uint32_t b0, uint32_t b1) {
    asm("mma.sync.aligned.m16n8k16.row.col.f32.bf16.bf16.f32 {%0,%1,%2,%3},{%4,%5,%6,%7},{%8,%9},{%0,%1,%2,%3};"
        : "+f"(c[0]), "+f"(c[1]), "+f"(c[2]), "+f"(c[3]) : "r"(a0), "r"(a1), "r"(a2), "r"(a3), "r"(b0), "r"(b1));
}
__device__ __forceinline__ void ldsm4(uint32_t* r, uint32_t a) {
    asm volatile("ldmatrix.sync.aligned.m8n8.x4.shared.b16 {%0,%1,%2,%3},[%4];" : "=r"(r[0]), "=r"(r[1]), "=r"(r[2]), "=r"(r[3]) : "r"(a) : "memory");
}
__device__ __forceinline__ void ldsm4t(uint32_t* r, uint32_t a) {
    asm volatile("ldmatrix.sync.aligned.m8n8.x4.trans.shared.b16 {%0,%1,%2,%3},[%4];" : "=r"(r[0]), "=r"(r[1]), "=r"(r[2]), "=r"(r[3]) : "r"(a) : "memory");
}
__device__ __forceinline__ void stsm4(uint32_t a, uint32_t r0, uint32_t r1, uint32_t r2, uint32_t r3) {
    asm volatile("stmatrix.sync.aligned.m8n8.x4.shared.b16 [%0],{%1,%2,%3,%4};" ::"r"(a), "r"(r0), "r"(r1), "r"(r2), "r"(r3) : "memory");
}
__device__ __forceinline__ uint32_t lds32(uint32_t a) { uint32_t v; asm volatile("ld.shared.b32 %0,[%1];" : "=r"(v) : "r"(a) : "memory"); return v; }
__device__ __forceinline__ uint4 lds128(uint32_t a) { uint4 v; asm volatile("ld.shared.v4.b32 {%0,%1,%2,%3},[%4];" : "=r"(v.x), "=r"(v.y), "=r"(v.z), "=r"(v.w) : "r"(a) : "memory"); return v; }
__device__ __forceinline__ void sts16(uint32_t a, uint32_t v) { asm volatile("st.shared.b16 [%0],%1;" ::"r"(a), "h"((unsigned short)v) : "memory"); }
__device__ __forceinline__ void sts32(uint32_t a, uint32_t v) { asm volatile("st.shared.b32 [%0],%1;" ::"r"(a), "r"(v) : "memory"); }
__device__ __forceinline__ void sts64(uint32_t a, uint32_t x, uint32_t y) { asm volatile("st.shared.v2.b32 [%0],{%1,%2};" ::"r"(a), "r"(x), "r"(y) : "memory"); }
__device__ __forceinline__ void sts128(uint32_t a, uint32_t x, uint32_t y, uint32_t z, uint32_t w) { asm volatile("st.shared.v4.b32 [%0],{%1,%2,%3,%4};" ::"r"(a), "r"(x), "r"(y), "r"(z), "r"(w) : "memory"); }
__device__ __forceinline__ uint32_t pack2(float lo, float hi) { uint32_t d; asm("cvt.rn.bf16x2.f32 %0,%1,%2;" : "=r"(d) : "f"(hi), "f"(lo)); return d; }
__device__ __forceinline__ float bf_lo(uint32_t v) { return __uint_as_float(v << 16); }
__device__ __forceinline__ float bf_hi(uint32_t v) { return __uint_as_float(v & 0xffff0000u); }
__device__ __forceinline__ float bf_round(float v) { return bf_lo(pack2(v, 0.f)); }
__device__ __forceinline__ uint32_t hmax2(uint32_t a, uint32_t b) { uint32_t d; asm("max.bf16x2 %0,%1,%2;" : "=r"(d) : "r"(a), "r"(b)); return d; }
__device__ __forceinline__ uint32_t hmin2(uint32_t a, uint32_t b) { uint32_t d; asm("min.bf16x2 %0,%1,%2;" : "=r"(d) : "r"(a), "r"(b)); return d; }
__device__ __forceinline__ uint32_t hmul2(uint32_t a, uint32_t b) { uint32_t d; asm("mul.rn.bf16x2 %0,%1,%2;" : "=r"(d) : "r"(a), "r"(b)); return d; }
__device__ __forceinline__ float ex2(float x) { float y; asm("ex2.approx.ftz.f32 %0,%1;" : "=f"(y) : "f"(x)); return y; }
__device__ __forceinline__ float rcp(float x) { float y; asm("rcp.approx.ftz.f32 %0,%1;" : "=f"(y) : "f"(x)); return y; }
__device__ __forceinline__ uint32_t ld_nc(const uint32_t* p) { uint32_t v; asm volatile("ld.global.nc.b32 %0,[%1];" : "=r"(v) : "l"(p)); return v; }
__device__ __forceinline__ uint2 ld_nc64(const uint2* p) { uint2 v; asm volatile("ld.global.nc.v2.b32 {%0,%1},[%2];" : "=r"(v.x), "=r"(v.y) : "l"(p)); return v; }
__device__ __forceinline__ unsigned ld_acq(const unsigned* p) { unsigned v; asm volatile("ld.acquire.gpu.global.u32 %0,[%1];" : "=r"(v) : "l"(p) : "memory"); return v; }
__device__ __forceinline__ unsigned ld_rlx(const unsigned* p) { unsigned v; asm volatile("ld.relaxed.gpu.global.u32 %0,[%1];" : "=r"(v) : "l"(p) : "memory"); return v; }
__device__ __forceinline__ uint2 ld_rlx64(const void* p) { uint2 v; asm volatile("{.reg .b64 t; ld.relaxed.gpu.global.b64 t,[%2]; mov.b64 {%0,%1},t;}" : "=r"(v.x), "=r"(v.y) : "l"(p) : "memory"); return v; }
__device__ __forceinline__ uint4 ld_rlx128(const void* p) {
    uint4 v;
    asm volatile("{.reg .b64 t,u; ld.relaxed.gpu.global.v2.b64 {t,u},[%4]; mov.b64 {%0,%1},t; mov.b64 {%2,%3},u;}" : "=r"(v.x), "=r"(v.y), "=r"(v.z), "=r"(v.w) : "l"(p) : "memory");
    return v;
}
__device__ __forceinline__ void st_rlx32(void* p, uint32_t x) { asm volatile("st.relaxed.gpu.global.u32 [%0],%1;" ::"l"(p), "r"(x) : "memory"); }
__device__ __forceinline__ void st_rlx64(void* p, uint32_t x, uint32_t y) { asm volatile("{.reg .b64 t; mov.b64 t,{%1,%2}; st.relaxed.gpu.global.b64 [%0],t;}" ::"l"(p), "r"(x), "r"(y) : "memory"); }
__device__ __forceinline__ void st_rlx128(void* p, uint4 v) {
    asm volatile("{.reg .b64 t,u; mov.b64 t,{%1,%2}; mov.b64 u,{%3,%4}; st.relaxed.gpu.global.v2.b64 [%0],{t,u};}" ::"l"(p), "r"(v.x), "r"(v.y), "r"(v.z), "r"(v.w) : "memory");
}
__device__ __forceinline__ uint32_t tagw(uint32_t w, uint32_t tag) { return (w & ~1u) | tag; }
__device__ __forceinline__ uint4 tag4(uint32_t x, uint32_t y, uint32_t z, uint32_t w, uint32_t tag) { return make_uint4(tagw(x, tag), y, tagw(z, tag), w); }
__device__ __forceinline__ uint32_t bad4(const uint4& v, uint32_t tag) { return (v.x ^ tag) | (v.z ^ tag); }
__device__ __forceinline__ void bar_named(int id, int n) { asm volatile("bar.sync %0,%1;" ::"r"(id), "r"(n) : "memory"); }

struct cf { float re, im; };
__device__ __forceinline__ cf cmul(cf a, cf b) { cf r; r.re = a.re * b.re - a.im * b.im; r.im = a.re * b.im + a.im * b.re; return r; }
__device__ __forceinline__ cf cexp_p(float arl, float ait, float p) {
    float mag = ex2(arl * p);
    float t = ait * p;
    t = (t - rintf(t)) * 6.283185307179586f;
    cf r; r.re = mag * __cosf(t); r.im = mag * __sinf(t);
    return r;
}

__device__ __forceinline__ void hedgehog2(const uint32_t* a, uint32_t wphi_addr, uint32_t (*out)[8]) {
    float p[2][2][4], mx[2][2];
#pragma unroll
    for (int h = 0; h < 2; h++) {
        uint32_t b[4];
        ldsm4t(b, wphi_addr + h * 512);
        float c0[4] = {0.f, 0.f, 0.f, 0.f}, c1[4] = {0.f, 0.f, 0.f, 0.f};
        mma16816(c0, a[4 * h], a[4 * h + 1], a[4 * h + 2], a[4 * h + 3], b[0], b[1]);
        mma16816(c1, a[4 * h], a[4 * h + 1], a[4 * h + 2], a[4 * h + 3], b[2], b[3]);
#pragma unroll
        for (int k = 0; k < 2; k++) {
            p[h][k][0] = c0[2 * k]; p[h][k][1] = c0[2 * k + 1]; p[h][k][2] = c1[2 * k]; p[h][k][3] = c1[2 * k + 1];
            mx[h][k] = fmaxf(fmaxf(p[h][k][0], p[h][k][1]), fmaxf(p[h][k][2], p[h][k][3]));
        }
    }
#pragma unroll
    for (int o = 1; o <= 2; o <<= 1)
#pragma unroll
        for (int h = 0; h < 2; h++)
#pragma unroll
            for (int k = 0; k < 2; k++) mx[h][k] = fmaxf(mx[h][k], __shfl_xor_sync(~0u, mx[h][k], o));
    const float L = 1.4426950408889634f;
    float pmin = 1.f;
#pragma unroll
    for (int h = 0; h < 2; h++)
#pragma unroll
        for (int k = 0; k < 2; k++) {
            const float m = -mx[h][k] * L;
            const float e0 = ex2(fmaf(p[h][k][0], L, m)), e1 = ex2(fmaf(p[h][k][1], L, m)), e2 = ex2(fmaf(p[h][k][2], L, m)), e3 = ex2(fmaf(p[h][k][3], L, m));
            const float p01 = e0 * e1, p23 = e2 * e3, pp = p01 * p23, r = rcp(pp), r01 = r * p23, r23 = r * p01;
            pmin = fminf(pmin, pp);
            out[h][k] = pack2(e0, e1); out[h][k + 2] = pack2(e2, e3);
            out[h][4 + k] = pack2(r01 * e1, r01 * e0); out[h][4 + k + 2] = pack2(r23 * e3, r23 * e2);
        }
    if (__builtin_expect(__any_sync(~0u, !(pmin > 1e-18f)), 0)) {
#pragma unroll
        for (int h = 0; h < 2; h++)
#pragma unroll
            for (int k = 0; k < 2; k++) {
                float m = fminf(fminf(p[h][k][0], p[h][k][1]), fminf(p[h][k][2], p[h][k][3]));
                m = fminf(m, __shfl_xor_sync(~0u, m, 1));
                m = fminf(m, __shfl_xor_sync(~0u, m, 2)) * L;
                out[h][4 + k] = pack2(ex2(fmaf(p[h][k][0], -L, m)), ex2(fmaf(p[h][k][1], -L, m)));
                out[h][4 + k + 2] = pack2(ex2(fmaf(p[h][k][2], -L, m)), ex2(fmaf(p[h][k][3], -L, m)));
            }
    }
}

__global__ void __launch_bounds__(512, 1)
fused_kernel(Scratch* __restrict__ scr, const bf16* __restrict__ logA, const bf16* __restrict__ Aim, const bf16* __restrict__ Cre,
             const bf16* __restrict__ Cim, const bf16* __restrict__ logdt, const bf16* __restrict__ Dskip, const bf16* __restrict__ wphi,
             const bf16* __restrict__ gatew, bf16* __restrict__ out,
             const __grid_constant__ CUtensorMap mx, const __grid_constant__ CUtensorMap mw, const __grid_constant__ CUtensorMap mwo) {
    extern __shared__ __align__(1024) uint8_t smem[];
    const uint32_t sb = s2u(smem);
    const int tid = threadIdx.x, warp = __shfl_sync(~0u, tid >> 5, 0), lane = tid & 31;
    const int g = lane >> 2, q = lane & 3, w4 = warp & 3;
    const int bi = blockIdx.x, bi_i = bi & 15, bi_j = bi >> 4;
    const uint32_t bar = sb + OFF_BAR;
    const int rot = (bi_j & 3) * 2, xkb = bi_j >> 2;
    auto load_stage = [&](int kb) {
        const uint32_t b = bar + 8 * (BAR_FULL + (kb & 3)), d = sb + (kb & 3) * SLOT;
        const int kc = ((kb + rot) & 7) * 64;
        mbar_expect(b, SLOT);
        tma2d(d, &mx, kc, bi_i * 128, b);
        tma3d(d + 16384, &mw, bi_j * 64, kc, 0, b);
    };

    const int ch = bi * 4 + w4;
    const int pidx = ch * 64 + lane * 2 + (warp >> 3);
    const uint32_t pla = ld_nc((const uint32_t*)logA + pidx), pai = ld_nc((const uint32_t*)Aim + pidx);
    const uint32_t pcr = ld_nc((const uint32_t*)Cre + pidx), pci = ld_nc((const uint32_t*)Cim + pidx);
    uint32_t pdt = ld_nc((const uint32_t*)logdt + (ch >> 1));
    const uint32_t pds = ld_nc((const uint32_t*)Dskip + (ch >> 1));
    unsigned done0 = ld_rlx(scr->done);
    if (tid == 0) {
        for (int s = 0; s < 4; s++) mbar_init(bar + 8 * (BAR_FULL + s), 1);
        asm volatile("fence.mbarrier_init.release.cluster;" ::: "memory");
        load_stage(0); load_stage(1);
        STAMP(11);
    } else if (tid == 32) {
        if (sb & 1023) __trap();
        sts32(bar + OFF_CNT, 0); sts32(bar + OFF_PAUSE, 0);
        for (int s = 0; s < 4; s++) mbar_init(bar + 8 * (BAR_EMPTY + s), 9);
        mbar_init(bar + 8 * BAR_WPHI, 1); mbar_init(bar + 8 * BAR_WO, 2); mbar_init(bar + 8 * BAR_WO2, 1); mbar_init(bar + 8 * BAR_XT, 4);
        mbar_init(bar + 8 * BAR_DONE, 9); mbar_init(bar + 8 * BAR_KG, 8); mbar_init(bar + 8 * BAR_SP, 1); mbar_init(bar + 8 * BAR_PUB, 8);
        mbar_init(bar + 8 * BAR_KVF, 4); mbar_init(bar + 8 * BAR_UR, 4); mbar_init(bar + 8 * BAR_WR, 4); mbar_init(bar + 8 * BAR_PREP, 4); mbar_init(bar + 8 * BAR_KGA, 4); mbar_init(bar + 8 * BAR_SP2, 1);
        asm volatile("fence.mbarrier_init.release.cluster;" ::: "memory");
        mbar_expect(bar + 8 * BAR_WPHI, 3072);
        bulk_g2s(sb + OFF_GW, gatew, 1024, bar + 8 * BAR_WPHI);
        bulk_g2s(sb + OFF_WPHI, wphi + bi_j * 1024, 2048, bar + 8 * BAR_WPHI);
    } else if (tid == 64) {
        asm volatile("prefetch.tensormap [%0];" ::"l"(&mw) : "memory");
    }
    const uint32_t buf = sb + OFF_BUF + w4 * BUF_STRIDE, kb_ = sb + OFF_K + w4 * KT_BYTES;
    if ((warp >> 2) == 2) {
#pragma unroll
        for (int v = 0; v < 7; v++) if (v * 32 + lane < KT_BYTES / 16) sts128(kb_ + (v * 32 + lane) * 16, 0, 0, 0, 0);
    }
    __syncthreads();
    asm volatile("" : "+r"(pdt), "+r"(done0)::"memory");
    const unsigned epoch1 = (done0 >> 7) + 1u;
    const uint32_t tag = epoch1 & 1u;

    const int st = tid & 127;
    const uint32_t ub = sb + OFF_U + w4 * U_STRIDE + 256, spare = sb + (w4 < 2 ? OFF_SP0 : OFF_SP1) + (w4 & 1) * 4096;

    auto stg_of = [&](int w) { return w < 8 ? sb + 3 * SLOT + w * 7296 : sb + 2 * SLOT + (w & 3) * 7296; };
    float kc[24];
#pragma unroll
    for (int t = 0; t < 24; t++) kc[t] = 0.f;
    {
        const float dt = bf_round(expf((ch & 1) ? bf_hi(pdt) : bf_lo(pdt)));
        const uint32_t stg = (warp >> 2) == 2 ? buf : stg_of(warp);
        const int sh = ((warp >> 2) & 1) * 16;
        auto pick = [&](uint32_t v) { return __uint_as_float((v >> sh) << 16); };
        const float ea = bf_round(expf(pick(pla)));
        const float arl = (-ea * dt) * 1.4426950408889634f, ait = (pick(pai) * dt) * 0.15915494309189535f;
        cf C2; C2.re = 2.0f * (pick(pcr) * dt); C2.im = 2.0f * (pick(pci) * dt);
        const cf z1 = cexp_p(arl, ait, 1.0f), z128 = cexp_p(arl, ait, 128.0f);
        cf z8 = cexp_p(arl, ait, 8.0f); z8.im = -z8.im;
        const uint32_t lp = stg + lane * 4;
        auto put = [&](int row, const cf& v) { sts32((lp ^ ((row & 7) << 4)) + row * 128, pack2(v.re, v.im)); };
        {
            const cf z16 = cmul(z8, z8);
            cf e; e.re = 1.f; e.im = 0.f;
            cf o = z8;
            put(0, e); put(1, o);
            e = z16; put(2, e);
#pragma unroll
            for (int b = 3; b < 16; b += 2) {
                o = cmul(o, z16); put(b, o);
                if (b + 1 < 16) { e = cmul(e, z16); put(b + 1, e); }
            }
        }
        cf h[8];
        h[0] = C2; put(16, h[0]);
        {
            const cf z2 = cmul(z1, z1);
            h[1] = cmul(h[0], z1);
#pragma unroll
            for (int r = 2; r < 8; r++) h[r] = cmul(h[r - 2], z2);
#pragma unroll
            for (int r = 1; r < 8; r++) put(16 + r, h[r]);
        }
#pragma unroll
        for (int r = 0; r < 8; r++) { h[r] = cmul(h[r], z128); put(24 + r, h[r]); }
#pragma unroll
        for (int al = 0; al < 2; al++)
#pragma unroll
            for (int r = 0; r < 4; r++) { h[2 * r] = cmul(h[2 * r], z128); put(32 + al * 4 + r, h[2 * r]); }
#pragma unroll
        for (int al = 0; al < 4; al++)
#pragma unroll
            for (int r = 0; r < 2; r++) { h[4 * r] = cmul(h[4 * r], z128); put(40 + al * 2 + r, h[4 * r]); }
#pragma unroll
        for (int al = 0; al < 9; al++) { h[0] = cmul(h[0], z128); put(48 + al, h[0]); }
        __syncwarp();
        const int lr = lane & 7, lm = lane >> 3;
#pragma unroll
        for (int kp = 0; kp < 2; kp++) {
            uint32_t a0[4], a1[4];
            ldsm4(a0, stg + ((lm & 1) * 8 + lr) * 128 + (((4 * kp + (lm >> 1)) ^ lr) << 4));
            ldsm4(a1, stg + ((lm & 1) * 8 + lr) * 128 + (((4 * kp + 2 + (lm >> 1)) ^ lr) << 4));
#pragma unroll
            for (int t = 0; t < 6; t++) {
                uint32_t b[4];
                ldsm4(b, stg + (16 + 8 * t + lr) * 128 + (((4 * kp + lm) ^ lr) << 4));
                mma16816(kc + 4 * t, a0[0], a0[1], a0[2], a0[3], b[0], b[1]);
                mma16816(kc + 4 * t, a1[0], a1[1], a1[2], a1[3], b[2], b[3]);
            }
        }
        __syncwarp();
        if ((warp >> 2) != 2) {
#pragma unroll
            for (int t = 0; t < 6; t++)
                sts128(stg + (t * 32 + lane) * 16, __float_as_uint(kc[4 * t]), __float_as_uint(kc[4 * t + 1]), __float_as_uint(kc[4 * t + 2]), __float_as_uint(kc[4 * t + 3]));
            asm volatile("fence.proxy.async.shared::cta;" ::: "memory");
            __syncwarp();
            if (lane == 0) mbar_arrive(bar + 8 * (warp < 8 ? BAR_KG : BAR_KGA));
        }
    }

    if (warp < 8) {
        const int wg = warp >> 2;
        if (warp == 0) STAMP(21);
        float acc[96];
        const int srow = warp * 16 + (lane & 15);
        const uint32_t srow_a = srow * 128;
        const int sx = srow & 7, shi = lane >> 4;
#pragma unroll
        for (int r = 0; r < 96; r++) acc[r] = 0.f;
        fence_regs<96>(acc);
        const uint64_t da0 = mkdesc(sb + wg * 8192, 16, 1024), db0 = mkdesc(sb + 16384, 8192, 1024);
#pragma unroll 1
        for (int kb = 0; kb < 8; kb++) {
            const int s = kb & 3;
            const uint64_t da = da0 + s * (SLOT >> 4), db = db0 + s * (SLOT >> 4);
            if (warp == 0) STAMP(40 + kb);
            mbar_wait(bar + 8 * (BAR_FULL + s), kb >> 2);
            if (warp == 0) STAMP(32 + kb);
            wg_fence();
#pragma unroll
            for (int k = 0; k < 4; k++) wgmma192(acc, da + 2 * k, db + 128 * k);
            wg_commit();
            wg_wait<1>();
            if (lane == 0 && kb > 0) mbar_arrive(bar + 8 * (BAR_EMPTY + ((kb - 1) & 3)));
        }
        mbar_wait(bar + 8 * BAR_WPHI, 0);
        wg_wait<0>();
        fence_regs<96>(acc);
        if (lane == 0) mbar_arrive(bar + 8 * BAR_DONE);
        if (warp == 0) STAMP(1);
        uint32_t in[32], va[16];
#pragma unroll
        for (int r = 0; r < 16; r++) {
            in[r] = pack2(acc[32 + 2 * r], acc[32 + 2 * r + 1]);
            in[16 + r] = pack2(acc[2 * r], acc[2 * r + 1]);
            va[r] = pack2(acc[64 + 2 * r], acc[64 + 2 * r + 1]);
        }
        const uint32_t wphi_a = sb + OFF_WPHI + (lane & 15) * 32 + (lane >> 4) * 16;
        uint32_t pq[4][8];
#pragma unroll 1
        for (int it = 0; it < 4; it++) {
            hedgehog2(in, wphi_a + (it & 1) * 1024, pq + 2);
#pragma unroll
            for (int r = 0; r < 24; r++) in[r] = in[r + 8];
            if (it < 2) {
#pragma unroll
                for (int hs = 0; hs < 4; hs++) {
                    float c[4] = {0.f, 0.f, 0.f, 0.f};
                    uint32_t* o = pq[2 + (hs >> 1)] + 4 * (hs & 1);
                    mma16816(c, o[0], o[1], o[2], o[3], 0x3f803f80u, 0x3f803f80u);
                    const float r0 = rcp(c[0]), r1 = rcp(c[2]);
                    const uint32_t s0 = pack2(r0, r0), s1 = pack2(r1, r1);
                    o[0] = hmul2(o[0], s0); o[1] = hmul2(o[1], s1); o[2] = hmul2(o[2], s0); o[3] = hmul2(o[3], s1);
                }
                if (it == 0) mbar_wait(bar + 8 * BAR_DONE, 0);
                const uint32_t pt = sb + OFF_P + it * 16384 + srow_a, vt = sb + OFF_V + it * 16384 + srow_a;
#pragma unroll
                for (int hl = 0; hl < 2; hl++) {
                    stsm4(pt + (((4 * hl + shi) ^ sx) << 4), pq[2 + hl][0], pq[2 + hl][1], pq[2 + hl][2], pq[2 + hl][3]);
                    stsm4(pt + (((4 * hl + 2 + shi) ^ sx) << 4), pq[2 + hl][4], pq[2 + hl][5], pq[2 + hl][6], pq[2 + hl][7]);
                    stsm4(vt + (((2 * hl + shi) ^ sx) << 4), va[4 * hl], va[4 * hl + 1], va[4 * hl + 2], va[4 * hl + 3]);
                }
                if (lane < 16) sts128(vt + ((4 ^ sx) << 4), 0x3f803f80u, 0x3f803f80u, 0x3f803f80u, 0x3f803f80u);
#pragma unroll
                for (int r = 0; r < 8; r++) va[r] = va[r + 8];
            }
            if (it == 1) {
                asm volatile("fence.proxy.async.shared::cta;" ::: "memory");
                bar_named(1, 256);
                if (warp == 0) STAMP(2);
                float d[32];
                const uint64_t dv = mkdesc(sb + OFF_V + wg * 16384, 16, 1024), dp = mkdesc(sb + OFF_P + wg * 16384, 16, 1024);
                wg_fence();
#pragma unroll
                for (int k = 0; k < 8; k++) wgmma64_tt(d, dv + 128 * k, dp + 128 * k, k != 0);
                wg_commit();
                wg_wait<0>();
                fence_regs<32>(d);
                mbar_wait(bar + 8 * BAR_PREP, 0);
                uint4* kvp = scr->kvp + bi * 544 + wg * 272;
                if (w4 < 2) {
                    uint32_t e[16];
#pragma unroll
                    for (int r = 0; r < 16; r++) e[r] = __float_as_uint(w4 ? d[16 + r] : d[r]);
                    uint4* p = kvp + w4 * 136 + lane;
#pragma unroll
                    for (int ks = 0; ks < 2; ks++)
#pragma unroll
                        for (int nt = 0; nt < 2; nt++)
                            st_rlx128(p + (ks * 2 + nt) * 32, tag4(e[8 * ks + 2 * nt], e[8 * ks + 2 * nt + 1], e[8 * ks + 4 + 2 * nt], e[8 * ks + 4 + 2 * nt + 1], tag));
                } else if (w4 == 2 && lane < 4) {
#pragma unroll
                    for (int hl = 0; hl < 2; hl++)
#pragma unroll
                        for (int ks = 0; ks < 2; ks++)
                            st_rlx128(kvp + hl * 136 + 128 + ks * 4 + lane, tag4(__float_as_uint(d[16 * hl + 8 * ks]), __float_as_uint(d[16 * hl + 8 * ks + 1]),
                                                                                __float_as_uint(d[16 * hl + 8 * ks + 4]), __float_as_uint(d[16 * hl + 8 * ks + 5]), tag));
                }
                __syncwarp();
                if (lane == 0) mbar_arrive(bar + 8 * BAR_PUB);
                if (warp == 0) STAMP(3);
            }
            if (it == 2) {
#pragma unroll
                for (int r = 0; r < 8; r++) { pq[0][r] = pq[2][r]; pq[1][r] = pq[3][r]; }
            }
        }
        if (warp == 0) STAMP(4);
        asm volatile("setmaxnreg.inc.sync.aligned.u32 160;");
        {
            mbar_wait(bar + 8 * BAR_KVF, 0);
            uint4 kf[4][3];
#pragma unroll
            for (int hh = 0; hh < 4; hh++) {
                const uint32_t a = sb + OFF_KVF + hh * 1088;
                kf[hh][0] = lds128(a + lane * 32); kf[hh][1] = lds128(a + lane * 32 + 16); kf[hh][2] = lds128(a + 1024 + q * 16);
            }
            if (warp == 0) STAMP(5);
            uint4 own[4];
#pragma unroll
            for (int hh = 0; hh < 4; hh++) {
                float c[6][4];
#pragma unroll
                for (int t = 0; t < 6; t++) { c[t][0] = c[t][1] = c[t][2] = c[t][3] = 0.f; }
                const uint32_t* a = pq[hh];
                const bool od = g & 1;
                mma16816(c[0], a[0], a[1], a[2], a[3], od ? 0x3f803f80u : kf[hh][2].x, od ? 0x3f803f80u : kf[hh][2].y);
                mma16816(c[1], a[4], a[5], a[6], a[7], od ? 0x3f803f80u : kf[hh][2].z, od ? 0x3f803f80u : kf[hh][2].w);
                mma16816(c[2], a[0], a[1], a[2], a[3], kf[hh][0].x, kf[hh][0].y);
                mma16816(c[3], a[0], a[1], a[2], a[3], kf[hh][0].z, kf[hh][0].w);
                mma16816(c[4], a[4], a[5], a[6], a[7], kf[hh][1].x, kf[hh][1].y);
                mma16816(c[5], a[4], a[5], a[6], a[7], kf[hh][1].z, kf[hh][1].w);
                uint32_t w[4];
#pragma unroll
                for (int k = 0; k < 2; k++) {
                    const float rho = c[0][2 * k + 1] * rcp(c[1][2 * k + 1]);
                    const float r = rcp(fmaf(c[0][2 * k + 1], 1e-6f, fmaf(rho, c[1][2 * k], c[0][2 * k]))), rr = r * rho;
                    w[k] = pack2(fmaf(c[4][2 * k], rr, c[2][2 * k] * r), fmaf(c[4][2 * k + 1], rr, c[2][2 * k + 1] * r));
                    w[2 + k] = pack2(fmaf(c[5][2 * k], rr, c[3][2 * k] * r), fmaf(c[5][2 * k + 1], rr, c[3][2 * k + 1] * r));
                }
                own[hh] = tag4(w[0], w[1], w[2], w[3], tag);
            }
            uint4* og = scr->o + ((bi_i * 8 + warp) * 32 + bi_j * 4) * 32 + lane;
#pragma unroll
            for (int hh = 0; hh < 4; hh++) st_rlx128(og + hh * 32, own[hh]);
        }
        if (tid == 0) sts32(bar + OFF_PAUSE, 0);
        if (warp == 0) STAMP(6);
        float oc[64];
        const int slab = bi_i * 8 + (bi_j >> 2) * 4 + w4;
        const uint8_t* yb = (const uint8_t*)scr->y + (size_t)((bi_j & 3) * 32 + wg * 16 + (q >> 1)) * 16384 + slab * 128 + g * 16 + (q & 1) * 8;
        const unsigned* gp = scr->g + (slab * 8 + (g >> 1)) * 8 + (g & 1) * 4;
        uint2 yv[8]; unsigned g0, g1;
        {
            const uint4* osrc = scr->o + (slab * 32 + wg * 16) * 32 + lane;
            uint4 fr[16];
            const unsigned* probe = (const unsigned*)(osrc - lane + ((lane & 3) * 4 + 3) * 32 + 31) + 2;
            {
                unsigned miss = ~0u;
                int n = 0;
#pragma unroll
                for (int s = 0; s < 4; s++) {
#pragma unroll 1
                    while ((miss >> s) & 1) { miss = __ballot_sync(~0u, (ld_rlx(probe) ^ tag) & 1); if (++n > SPIN_LIMIT) break; }
#pragma unroll
                    for (int k = 4 * s; k < 4 * s + 4; k++) fr[k] = ld_rlx128(osrc + k * 32);
                }
            }
            if (warp == 0) STAMP(14);
            mbar_wait(bar + 8 * (wg ? BAR_WO2 : BAR_WO), 0);
            const uint64_t dw = mkdesc(sb + wg * 2 * SLOT, wg ? 32768 : SLOT, 1024);
#pragma unroll
            for (int s = 0; s < 4; s++) {
                int n = 0;
#pragma unroll 1
                while (__builtin_expect(__any_sync(~0u, (bad4(fr[4 * s], tag) | bad4(fr[4 * s + 1], tag) | bad4(fr[4 * s + 2], tag) | bad4(fr[4 * s + 3], tag)) & 1), 0)) {
#pragma unroll
                    for (int k = 4 * s; k < 4 * s + 4; k++) fr[k] = ld_rlx128(osrc + k * 32);
                    if (++n > SPIN_LIMIT) break;
                }
                wg_fence();
#pragma unroll
                for (int hh = 0; hh < 4; hh++) wgmma128_rs(oc, fr[4 * s + hh], dw + 128 * (4 * s + hh), (s | hh) != 0);
                wg_commit();
                if (s == 1) {
                    wg_wait<1>();
#pragma unroll
                    for (int nt = 0; nt < 8; nt++) yv[nt] = ld_rlx64(yb + nt * 32768);
                    g0 = ld_rlx(gp); g1 = ld_rlx(gp + 32);
                }
            }
            if (warp == 0) STAMP(7);
            {
                const unsigned* yprobe = scr->yflag + ((bi_j & 3) * 32 + wg * 16 + (lane & 15)) * 8;
                int n = 0;
#pragma unroll 1
                while (true) {
                    uint32_t bad = (g0 ^ tag) | (g1 ^ tag);
#pragma unroll
                    for (int nt = 0; nt < 8; nt++) bad |= yv[nt].x ^ tag;
                    if (!__any_sync(~0u, bad & 1)) break;
#pragma unroll 1
                    while (__any_sync(~0u, (ld_rlx(yprobe) ^ tag) & 1)) { if (++n > SPIN_LIMIT) break; }
#pragma unroll
                    for (int nt = 0; nt < 8; nt++) yv[nt] = ld_rlx64(yb + nt * 32768);
                    g0 = ld_rlx(gp); g1 = ld_rlx(gp + 32);
                    if (++n > SPIN_LIMIT) break;
                }
            }
            if (warp == 0) STAMP(28);
            wg_wait<0>();
            fence_regs<64>(oc);
        }
        {
            bar_named(3 + wg, 128);
            const uint32_t xw = sb + wg * 2 * SLOT + (tid & 127) * 16, xr = sb + (wg ^ 1) * 2 * SLOT + (tid & 127) * 16;
#pragma unroll
            for (int r = 0; r < 8; r++) {
                const float* o = oc + 4 * r;
                sts128(xw + r * 2048, __float_as_uint(wg ? o[0] : o[32]), __float_as_uint(wg ? o[1] : o[33]), __float_as_uint(wg ? o[2] : o[34]), __float_as_uint(wg ? o[3] : o[35]));
            }
#pragma unroll
            for (int r = 0; r < 32; r++) oc[r] = wg ? oc[32 + r] : oc[r];
            bar_named(1, 256);
            if (warp == 0) STAMP(8);
            const float ga = bf_hi(g0), gb = bf_hi(g1);
            const float ha = bf_round(1.0f - ga), hb = bf_round(1.0f - gb);
            uint32_t w[8][2];
#pragma unroll
            for (int nt = 0; nt < 8; nt++) {
                const uint4 p = lds128(xr + nt * 2048);
                w[nt][0] = pack2(fmaf(ga, oc[4 * nt] + __uint_as_float(p.x), ha * bf_lo(yv[nt].x)), fmaf(ga, oc[4 * nt + 1] + __uint_as_float(p.y), ha * bf_hi(yv[nt].x)));
                w[nt][1] = pack2(fmaf(gb, oc[4 * nt + 2] + __uint_as_float(p.z), hb * bf_lo(yv[nt].y)), fmaf(gb, oc[4 * nt + 3] + __uint_as_float(p.w), hb * bf_hi(yv[nt].y)));
            }
            const uint32_t ob = sb + wg * 2 * SLOT + 16384 + w4 * 2048;
#pragma unroll
            for (int nt = 0; nt < 8; nt += 2)
                stsm4(ob + (lane & 15) * 128 + (((nt + shi) ^ (lane & 7)) << 4), w[nt][0], w[nt][1], w[nt + 1][0], w[nt + 1][1]);
            __syncwarp();
            bf16* op = out + (size_t)(slab * 16) * 512 + (bi_j & 3) * 128 + wg * 64 + (lane & 7) * 8;
#pragma unroll
            for (int it = 0; it < 4; it++) {
                const int r = it * 4 + (lane >> 3);
                uint4 v = lds128(ob + r * 128 + (((lane & 7) ^ (r & 7)) << 4));
                *(uint4*)(op + r * 512) = v;
            }
        }
        if (warp == 0) STAMP(10);
    } else if (warp < 12) {
#pragma unroll
        for (int src = 2; src >= 0; src--) {
            if (src != 0) mbar_wait(bar + 8 * (src == 2 ? BAR_KGA : BAR_KG), 0);
#pragma unroll
            for (int t = 0; t < 6; t++) {
                const uint4 v = lds128(stg_of(w4 + src * 4) + (t * 32 + lane) * 16);
                kc[4 * t] += __uint_as_float(v.x); kc[4 * t + 1] += __uint_as_float(v.y); kc[4 * t + 2] += __uint_as_float(v.z); kc[4 * t + 3] += __uint_as_float(v.w);
            }
            if (src != 1) {
                bar_named(2, 128);
                if (st == 0) { load_stage(src == 2 ? 2 : 3); if (src == 0) mbar_arrive(bar + 8 * BAR_SP); }
                if (warp == 8) STAMP(src == 2 ? 22 : 17);
            }
        }
        if (warp == 8) {
#pragma unroll 1
            for (int kb = 0; kb < 6; kb++) {
                const int s = kb & 3;
                mbar_wait(bar + 8 * (BAR_EMPTY + s), kb >> 2);
                if (kb == xkb) mbar_wait(bar + 8 * BAR_XT, 0);
                if (lane == 0) {
                    STAMP(48 + kb);
                    if (kb < 4) load_stage(kb + 4);
                    else {
                        mbar_expect(bar + 8 * BAR_WO, 32768);
                        tma2d(sb + s * SLOT, &mwo, (bi_j & 3) * 128 + s * 64, 0, bar + 8 * BAR_WO);
                        if (kb == 5) mbar_arrive(bar + 8 * BAR_SP2);
                    }
                }
                __syncwarp();
            }
        } else if (warp == 9) {
            const int row = bi_j * 16 + (lane >> 1), half = lane & 1;
            unsigned* gp = scr->g + (bi_i * 64 + bi_j * 8) * 8 + lane * 2;
            st_rlx64(gp, tag ^ 1u, tag ^ 1u);
            if (lane < 8) st_rlx32(scr->yflag + bi * 8 + lane, tag ^ 1u);
            float gs0 = 0.f, gs1 = 0.f;
            mbar_wait(bar + 8 * BAR_WPHI, 0);
#pragma unroll 1
            for (int kb = 0; kb < 8; kb++) {
                const int s = kb & 3;
                mbar_wait(bar + 8 * (BAR_FULL + s), kb >> 2);
#pragma unroll
                for (int c = 0; c < 4; c++) {
                    const uint4 xv = lds128(sb + s * SLOT + row * 128 + (((half * 4 + c) ^ (row & 7)) << 4));
                    const uint4 gw = lds128(sb + OFF_GW + ((kb + rot) & 7) * 128 + half * 64 + c * 16);
                    const uint32_t p0 = hmul2(xv.x, gw.x), p1 = hmul2(xv.y, gw.y), p2 = hmul2(xv.z, gw.z), p3 = hmul2(xv.w, gw.w);
                    gs0 += (bf_lo(p0) + bf_lo(p1)) + (bf_lo(p2) + bf_lo(p3));
                    gs1 += (bf_hi(p0) + bf_hi(p1)) + (bf_hi(p2) + bf_hi(p3));
                }
                asm volatile("" : "+f"(gs0), "+f"(gs1));
                __syncwarp();
                if (lane == 0) mbar_arrive(bar + 8 * (kb < 7 ? BAR_EMPTY + s : BAR_DONE));
            }
            float gs = gs0 + gs1;
            gs += __shfl_xor_sync(~0u, gs, 1);
            const uint32_t gv = __float_as_uint(bf_round(rcp(1.0f + ex2(-1.4426950408889634f * bf_round(gs))))) | tag;
            st_rlx64(gp, gv, gv);
        }
        if (lane == 0) kc[4 * 0 + 0] += ((ch & 1) ? bf_hi(pds) : bf_lo(pds));
        const uint32_t k1024 = __shfl_sync(~0u, pack2(kc[4 * 4 + 0], 0.f), 0);
#pragma unroll
        for (int i = 0; i < 2; i++) {
            const int be = g + 8 * i;
#pragma unroll
            for (int t = 0; t < 2; t++) {
                const uint32_t a = kb_ + (KW_D + 128 * t + 8 * be + 2 * q) * 4;
                const uint32_t w = pack2(kc[4 * t + 2 * i + 1], kc[4 * t + 2 * i]);
                sts32(a + 4, w); sts16(a, w >> 16); sts16(a + 10, w);
            }
            {
                const int p = 256 + 128 * (q >> 1) + 8 * be + 4 * (q & 1);
                const uint32_t a = kb_ + (KW_D + p) * 4;
                const uint32_t w = pack2(kc[4 * 2 + 2 * i + 1], kc[4 * 2 + 2 * i]);
                const uint32_t aa = (w >> 16) | (w & 0xffff0000u);
                if (p != 256) { sts16(a - 4, aa); sts32(a, aa); } else sts16(a, aa);
                sts32(a + 4, aa); sts32(a + 8, w); sts16(a + 14, w);
            }
            {
                const int k = 64 + 16 * q + be;
                const uint32_t w = pack2(kc[4 * 3 + 2 * i], kc[4 * 3 + 2 * i + 1]);
                if (k != 64) sts16(kb_ + (KW_2 + ((k - 1) >> 1) - 24) * 4 + (k & 1) * 2, w);
                else {
                    const uint32_t a = kb_ + (KW_D + 511) * 4, aa = (w << 16) | (w & 0xffffu);
                    sts16(a, w); sts32(a + 4, aa); sts32(a + 8, aa); sts32(a + 12, aa); sts16(a + 18, w);
                }
                sts16(kb_ + (KW_2 + 48 + (k >> 1) - 24) * 4 + ((k & 1) ^ 1) * 2, w >> 16);
            }
#pragma unroll
            for (int b = 0; b < 2; b++) {
                const int k = 64 + 8 * (2 * q + b) + (be >> 1);
                const uint32_t w = pack2(kc[4 * 4 + 2 * i + b], 0.f);
                if (!(be & 1) && k == 64) sts16(kb_ + (KW_2 + 63 - 24) * 4, w);
                else {
                    const uint32_t a = kb_ + (KW_3 + ((be & 1) ? 80 + k : k - 1) - 48) * 4;
                    sts16(a, w);
                    if (!((be & 1) && k == 127)) sts16(a + 6, w);
                }
            }
        }
        if (lane == 0) sts16(kb_ + (KW_3 + 127 - 48) * 4, pack2(kc[4 * 5 + 0], 0.f));
        __syncwarp();
        mbar_wait(bar + 8 * BAR_UR, 0);
        mbar_wait(bar + 8 * CONV_START, 0);
        auto yield = [&]() {
            int n = 0;
#pragma unroll 1
            while (lds32(bar + OFF_PAUSE) != 0) { __nanosleep(40); if (++n > SPIN_LIMIT) break; }
        };
        if (warp == 8) STAMP(23);
        float y[16][4];
#pragma unroll
        for (int nt = 0; nt < 16; nt++) { y[nt][0] = y[nt][1] = y[nt][2] = y[nt][3] = 0.f; }
        {
            uint32_t Bp[32], A[5][3];
            auto uaddr = [&](int rho) { const int R0 = (lane >> 4) * 8 + (lane & 7) - rho; return ub + (((2 * R0 + ((lane >> 3) & 1)) ^ ((R0 >> 2) & 1)) << 4); };
            const uint32_t kd = kb_ + (KW_D + g - 2 * q) * 4;
            auto lda = [&](int rho) {
#pragma unroll
                for (int ga = 0; ga < 5; ga++) {
                    const uint32_t a = kd + (ga < 4 ? rho : (rho & 1)) * 64 + ga * 512;
                    A[ga][0] = lds32(a); A[ga][1] = lds32(a + 32); A[ga][2] = lds32(a - 32);
                }
            };
            {
                const uint32_t a = uaddr(0);
#pragma unroll
                for (int p = 0; p < 8; p++) ldsm4(Bp + 4 * p, a + p * 512);
            }
#pragma unroll 1
            for (int rho = 0; rho < 8; rho++) {
                yield();
                lda(rho);
                if (rho < 2) {
#pragma unroll
                    for (int nt = 4; nt < 16; nt++) mma16816(y[nt], A[4][0], A[4][1], A[4][2], A[4][0], Bp[2 * (nt - 4)], Bp[2 * (nt - 4) + 1]);
                }
#pragma unroll
                for (int ga = 0; ga < 3; ga++)
#pragma unroll
                    for (int nt = 15; nt >= ga; nt--) mma16816(y[nt], A[ga][0], A[ga][1], A[ga][2], A[ga][0], Bp[2 * (nt - ga)], Bp[2 * (nt - ga) + 1]);
                yield();
                const uint32_t an = uaddr(rho + 1);
                ldsm4(Bp + 28, an + 7 * 512);
#pragma unroll
                for (int nt = 15; nt >= 3; nt--) {
                    mma16816(y[nt], A[3][0], A[3][1], A[3][2], A[3][0], Bp[2 * (nt - 3)], Bp[2 * (nt - 3) + 1]);
                    if (nt & 1) ldsm4(Bp + 2 * (nt - 3), an + ((nt - 3) >> 1) * 512);
                }
            }
        }
        if (warp == 8) STAMP(18);
        mbar_wait(bar + 8 * BAR_WR, 0);
#pragma unroll 1
        for (int ph = 0; ph < 2; ph++) {
            yield();
            uint32_t B[5][2];
            const uint32_t ka = kb_ + (KW_2 + ph * 48 + 8 + g - q) * 4;
#pragma unroll
            for (int dd = 0; dd < 5; dd++) { B[dd][0] = lds32(ka + dd * 32); B[dd][1] = lds32(ka + dd * 32 - 16); }
            const uint32_t wa = buf + ph * W3_OFF + ((lane & 7) + ((lane >> 3) & 1) + (lane >> 4) * 8) * 16;
#pragma unroll
            for (int s = 0; s < 12; s++) {
                uint32_t A[4];
                ldsm4t(A, wa + s * 256);
#pragma unroll
                for (int dd = 0; dd < 5; dd++)
                    if (s + 4 + dd < 16) mma16816(y[s + 4 + dd], A[0], A[1], A[2], A[3], B[dd][0], B[dd][1]);
            }
        }
        {
            const int ap = (lane & 7) + (lane >> 4) * 8;
            const uint32_t loff = ((2 * ap + ((lane >> 3) & 1)) ^ ((ap >> 2) & 1)) << 4;
#pragma unroll 1
            for (int ph = 0; ph < 2; ph++) {
                yield();
                uint32_t B[8][2];
                const uint32_t wb = (ph ? spare : buf + W9_OFF) + loff;
                const uint32_t ka = kb_ + (KW_3 + ph * 80 + 16 + g - 2 * q) * 4;
#pragma unroll
                for (int dd = 0; dd < 8; dd++) { B[dd][0] = lds32(ka + dd * 32); B[dd][1] = lds32(ka + dd * 32 - 32); }
#pragma unroll
                for (int s = 0; s < 4; s++) {
                    uint32_t A[4];
                    ldsm4t(A, wb + s * 512);
#pragma unroll
                    for (int dd = 0; dd < 8; dd++)
                        if (8 + 2 * s + dd < 16) mma16816(y[8 + 2 * s + dd], A[0], A[1], A[2], A[3], B[dd][0], B[dd][1]);
                }
            }
            const uint32_t idw = (g == 2 * q) ? k1024 : ((g == 2 * q + 1) ? (k1024 << 16) : 0u);
#pragma unroll
            for (int s = 0; s < 4; s++) {
                uint32_t A[4];
                ldsm4t(A, spare + 2048 + loff + s * 512);
                mma16816(y[8 + 2 * s], A[0], A[1], A[2], A[3], idw, 0u);
                mma16816(y[9 + 2 * s], A[0], A[1], A[2], A[3], 0u, idw);
            }
        }
        __syncwarp();
        if (warp == 8) STAMP(19);
#pragma unroll
        for (int nt = 0; nt < 16; nt++)
#pragma unroll
            for (int b = 0; b < 2; b++) sts32(buf + ((8 * nt + 2 * q + b) * 8 + g) * 4, pack2(y[nt][b], y[nt][2 + b]));
        bar_named(2, 128);
        uint4* yp = scr->y + bi * 1024 + st;
#pragma unroll
        for (int v = 0; v < 8; v++) {
            const uint32_t a = sb + OFF_BUF + (st + 128 * v) * 4;
            const uint32_t w0 = lds32(a), w1 = lds32(a + BUF_STRIDE), w2 = lds32(a + 2 * BUF_STRIDE), w3 = lds32(a + 3 * BUF_STRIDE);
            st_rlx128(yp + v * 128, tag4(__byte_perm(w0, w1, 0x5410), __byte_perm(w0, w1, 0x7632), __byte_perm(w2, w3, 0x5410), __byte_perm(w2, w3, 0x7632), tag));
        }
        if (st < 8) st_rlx32(scr->yflag + bi * 8 + st, tag);
        if (warp == 8) STAMP(20);
    } else {
        asm volatile("setmaxnreg.dec.sync.aligned.u32 64;");
        const int qq = (bi_i & 2) + ((lane >> 1) & 1);
        uint2* kvf_h = (uint2*)(scr->kvf + (bi_j * 4 + (bi_i >> 2)) * 68);
        auto windows = [&](int rhi, int rlo) {
#pragma unroll 1
            for (int rho = rhi; rho >= rlo; rho--) {
                const int ci = lane + 32 * rho;
                uint4 e4[4];
#pragma unroll
                for (int v = 0; v < 4; v++) { const int cc = ci - 3 + v; e4[v] = lds128(ub + ((cc ^ ((cc >> 3) & 1)) << 4)); }
                float S[29];
                const uint32_t* ew = (const uint32_t*)e4;
                S[3] = 0.f;
#pragma unroll
                for (int k = 4; k <= 28; k++) S[k] = S[k - 1] + ((k & 1) ? bf_hi(ew[k >> 1]) : bf_lo(ew[k >> 1]));
                auto win = [&](int lo, int hi, uint32_t a) {
                    sts128(a, pack2(S[hi] - S[lo - 1], S[hi + 1] - S[lo]), pack2(S[hi + 2] - S[lo + 1], S[hi + 3] - S[lo + 2]),
                           pack2(S[hi + 4] - S[lo + 3], S[hi + 5] - S[lo + 4]), pack2(S[hi + 6] - S[lo + 5], S[hi + 7] - S[lo + 6]));
                };
                win(14, 18, buf + W5_OFF + 16 + ci * 16); win(19, 21, buf + W3_OFF + 16 + ci * 16);
                if (rho < 4) {
                    const uint32_t sw = (ci ^ ((ci >> 3) & 1)) << 4;
                    win(4, 12, buf + W9_OFF + sw); win(13, 19, spare + sw); win(20, 21, spare + 2048 + sw);
                }
            }
        };
        {
            mbar_wait(bar + 8 * (BAR_FULL + xkb), 0);
#pragma unroll 1
            for (int hf = 0; hf < 2; hf++) {
                const int r = w4 * 32 + hf * 16 + (lane & 15);
                uint32_t* xt = (uint32_t*)scr->xt + ((xkb + rot) * 16 + (g >> 2)) * 4096 + (bi_i * 16 + w4 * 4 + hf * 2) * 16 + (g & 3) * 4 + q;
#pragma unroll
                for (int cb = 0; cb < 8; cb += 2) {
                    uint32_t v[4];
                    ldsm4t(v, sb + xkb * SLOT + r * 128 + (((cb + (lane >> 4)) ^ (r & 7)) << 4));
                    xt[cb * 8192] = v[0]; xt[cb * 8192 + 16] = v[1]; xt[cb * 8192 + 8192] = v[2]; xt[cb * 8192 + 8192 + 16] = v[3];
                }
            }
            __syncwarp();
            if (lane == 0) mbar_arrive(bar + 8 * BAR_XT);
            if (warp == 12) {
                STAMP(26);
                mbar_wait(bar + 8 * BAR_XT, 0);
                if (lane == 0) asm volatile("red.release.gpu.global.add.u32 [%0],8;" ::"l"(scr->xcnt + (xkb + rot) * 32) : "memory");
                __syncwarp();
                STAMP(27);
            }
            {
                const uint32_t old = tag ^ 1u;
                const uint4 z4 = make_uint4(old, 0, old, 0);
#pragma unroll
                for (int v = 0; v < 5; v++) if (v < 4 || st < 32) st_rlx128(scr->kvp + bi * 544 + v * 128 + st, z4);
                if (st < 16) st_rlx128(scr->o + ((bi_i * 8 + (st >> 1)) * 32 + bi_j * 4 + 3) * 32 + 30 + (st & 1), z4);
                if (lane < 8) st_rlx64(kvf_h + ((bi_i & 3) * 8 + w4 * 2 + (lane & 1)) * 4 + (lane >> 1), old, 0);
                if (st < 4 && !(bi_i & 1)) st_rlx64(kvf_h + (64 + qq) * 2 + (lane & 1), old, 0);
                __syncwarp();
                if (lane == 0) mbar_arrive(bar + 8 * BAR_PREP);
            }
            int n = 0;
#pragma unroll 1
            while (__any_sync(~0u, (int)(ld_acq(scr->xcnt + bi_j * 32) - (epoch1 << 7)) < 0)) { if (++n > SPIN_LIMIT) break; }
            if (warp == 12) STAMP(15);
            uint4 ur[8];
#pragma unroll
            for (int v = 0; v < 8; v++) ur[v] = __ldcg(scr->xt + bi * 1024 + st + 128 * v);
            mbar_wait(bar + 8 * BAR_SP, 0);
            if (lane < 16) sts128(ub - 256 + lane * 16, 0, 0, 0, 0);
            if (lane < 2) sts128(buf + lane * W3_OFF, 0, 0, 0, 0);
#pragma unroll
            for (int v = 0; v < 8; v++) {
                const int ci = (st >> 2) + 32 * v;
                sts128(sb + OFF_U + (st & 3) * U_STRIDE + 256 + ((ci ^ ((ci >> 3) & 1)) << 4), ur[v].x, ur[v].y, ur[v].z, ur[v].w);
            }
            __syncwarp();
            if (lane == 0) mbar_arrive(bar + 8 * BAR_UR);
            mbar_wait(bar + 8 * BAR_UR, 0);
            if (warp == 12) STAMP(16);
            windows(5, 4);
        }
        mbar_wait(bar + 8 * BAR_SP2, 0);
        windows(3, 0);
        __syncwarp();
        if (lane == 0) mbar_arrive(bar + 8 * BAR_WR);
        if (warp == 12) STAMP(24);
        {
            const bool zw = st < 32 && !(bi_i & 1);
            const uint4* src = scr->kvp + bi_j * (16 * 544) + (bi_i >> 2) * 136;
            const uint4* zsrc = src + (lane >> 2) * (2 * 544) + 128 + (lane & 1) * 4 + qq;
            src += (lane >> 3) * (4 * 544) + ((lane >> 1) & 3) * 32 + (bi_i & 3) * 8 + w4 * 2 + (lane & 1);
            if (!zw) zsrc = src;
            mbar_wait(bar + 8 * BAR_PUB, 0);
            if (warp == 12) STAMP(12);
            uint4 v[6];
            int n = 0;
#pragma unroll 1
            while (true) {
#pragma unroll
                for (int k = 0; k < 4; k++) v[k] = ld_rlx128(src + k * 544);
                v[4] = ld_rlx128(zsrc); v[5] = ld_rlx128(zsrc + 544);
                if (!__any_sync(~0u, (bad4(v[0], tag) | bad4(v[1], tag) | bad4(v[2], tag) | bad4(v[3], tag) | bad4(v[4], tag) | bad4(v[5], tag)) & 1)) break;
                if (++n > SPIN_LIMIT) break;
            }
            if (warp == 12) STAMP(30);
            float f[8];
            const float* vf = (const float*)v;
#pragma unroll
            for (int r = 0; r < 4; r++) {
                f[r] = (vf[r] + vf[4 + r]) + (vf[8 + r] + vf[12 + r]);
                f[4 + r] = vf[16 + r] + vf[20 + r];
                f[4 + r] += __shfl_xor_sync(~0u, f[4 + r], 4);
            }
#pragma unroll
            for (int o = 8; o <= 16; o <<= 1)
#pragma unroll
                for (int r = 0; r < 8; r++) f[r] += __shfl_xor_sync(~0u, f[r], o);
            if (lane < 8) st_rlx64(kvf_h + ((bi_i & 3) * 8 + w4 * 2 + (lane & 1)) * 4 + (lane >> 1), tagw(pack2(f[0], f[1]), tag), pack2(f[2], f[3]));
            if (zw && lane < 4) st_rlx64(kvf_h + (64 + qq) * 2 + (lane & 1), tagw(pack2(f[4], f[5]), tag), pack2(f[6], f[7]));
        }
        if (warp == 12) STAMP(13);
        {
            const uint4* kp = scr->kvf + bi_j * 272 + st;
            uint4 v0, v1, v2;
            int n = 0;
#pragma unroll 1
            while (true) {
                v0 = ld_rlx128(kp); v1 = ld_rlx128(kp + 128); v2 = ld_rlx128(kp + (st < 16 ? 256 : 0));
                if (!__any_sync(~0u, (bad4(v0, tag) | bad4(v1, tag) | bad4(v2, tag)) & 1)) break;
                if (++n > SPIN_LIMIT) break;
            }
            sts128(sb + OFF_KVF + st * 16, v0.x, v0.y, v0.z, v0.w);
            sts128(sb + OFF_KVF + 2048 + st * 16, v1.x, v1.y, v1.z, v1.w);
            if (st < 16) sts128(sb + OFF_KVF + 4096 + st * 16, v2.x, v2.y, v2.z, v2.w);
            if (st == 0) sts32(bar + OFF_PAUSE, 1);
            __syncwarp();
            if (lane == 0) mbar_arrive(bar + 8 * BAR_KVF);
        }
        if (warp == 13) {
            mbar_wait(bar + 8 * BAR_KVF, 0);
            if (lane == 0) {
                mbar_expect(bar + 8 * BAR_WO2, 65536);
                tma2d(sb + OFF_P, &mwo, (bi_j & 3) * 128, 256, bar + 8 * BAR_WO2);
                tma2d(sb + OFF_V, &mwo, (bi_j & 3) * 128 + 64, 256, bar + 8 * BAR_WO2);
            }
        }
        if (warp == 12) STAMP(25);
    }
    __syncwarp();
    if (lane == 0) {
        unsigned old;
        asm volatile("atom.acq_rel.cta.shared.add.u32 %0,[%1],1;" : "=r"(old) : "r"(bar + OFF_CNT) : "memory");
        if (old == 15) {
            atomicAdd(scr->done, 1u);
        }
    }
}

typedef CUresult (*EncFn)(CUtensorMap*, CUtensorMapDataType, cuuint32_t, void*, const cuuint64_t*, const cuuint64_t*, const cuuint32_t*,
                          const cuuint32_t*, CUtensorMapInterleave, CUtensorMapSwizzle, CUtensorMapL2promotion, CUtensorMapFloatOOBfill);

extern "C" void kernel_launch(void* const* d_in, const int* in_sizes, int n_in, void* d_out, int out_size) {
    static EncFn enc = nullptr;
    static Scratch* scr = nullptr;
    if (!enc) {
        cudaGetSymbolAddress((void**)&scr, g_scr);
        cudaDriverEntryPointQueryResult qr;
        cudaGetDriverEntryPoint("cuTensorMapEncodeTiled", (void**)&enc, cudaEnableDefault, &qr);
        cudaFuncSetAttribute(fused_kernel, cudaFuncAttributeMaxDynamicSharedMemorySize, SMEM_BYTES);
    }
    CUtensorMap mx, mw, mwo;
    const cuuint32_t es[3] = {1, 1, 1};
    {
        cuuint64_t d[2] = {512, 2048}, s[1] = {1024}; cuuint32_t b[2] = {64, 128};
        enc(&mx, CU_TENSOR_MAP_DATA_TYPE_BFLOAT16, 2, d_in[0], d, s, b, es, CU_TENSOR_MAP_INTERLEAVE_NONE, CU_TENSOR_MAP_SWIZZLE_128B,
            CU_TENSOR_MAP_L2_PROMOTION_L2_128B, CU_TENSOR_MAP_FLOAT_OOB_FILL_NONE);
    }
    {
        cuuint64_t d[3] = {512, 512, 3}, s[2] = {3072, 1024}; cuuint32_t b[3] = {64, 64, 3};
        enc(&mw, CU_TENSOR_MAP_DATA_TYPE_BFLOAT16, 3, d_in[1], d, s, b, es, CU_TENSOR_MAP_INTERLEAVE_NONE, CU_TENSOR_MAP_SWIZZLE_128B,
            CU_TENSOR_MAP_L2_PROMOTION_L2_128B, CU_TENSOR_MAP_FLOAT_OOB_FILL_NONE);
    }
    {
        cuuint64_t d[2] = {512, 512}, s[1] = {1024}; cuuint32_t b[2] = {64, 256};
        enc(&mwo, CU_TENSOR_MAP_DATA_TYPE_BFLOAT16, 2, d_in[3], d, s, b, es, CU_TENSOR_MAP_INTERLEAVE_NONE, CU_TENSOR_MAP_SWIZZLE_128B,
            CU_TENSOR_MAP_L2_PROMOTION_L2_128B, CU_TENSOR_MAP_FLOAT_OOB_FILL_NONE);
    }
    fused_kernel<<<128, 512, SMEM_BYTES, cudaStreamPerThread>>>(
        scr, (const bf16*)d_in[5], (const bf16*)d_in[6], (const bf16*)d_in[7], (const bf16*)d_in[8], (const bf16*)d_in[9],
        (const bf16*)d_in[10], (const bf16*)d_in[2], (const bf16*)d_in[11], (bf16*)d_out, mx, mw, mwo);
}
```

```cpp
#include <cuda_runtime.h>
#include <cuda.h>
#include <cuda_bf16.h>
#include <stdint.h>

typedef __nv_bfloat16 bf16;

struct Scratch {
    uint4 xt[128 * 1024];
    uint4 o[16 * 8 * 32 * 32];
    uint4 y[128 * 1024];
    uint4 kvp[8 * 16 * 544];
    uint4 kvf[8 * 4 * 68];
    unsigned g[1024 * 8];
    unsigned yflag[128 * 8];
    unsigned xcnt[8 * 32];
    unsigned done[32];
};
__device__ Scratch g_scr;
#define STAMP(n)

constexpr int SLOT = 40960;
constexpr int OFF_SP0 = 32768, OFF_SP1 = SLOT + 32768;
constexpr int OFF_P = 2 * SLOT, OFF_V = OFF_P + 32768;
constexpr int OFF_KVF = OFF_V + 32768;
constexpr int KT_BYTES = 3264, KW_D = 16, KW_2 = 560, KW_3 = 656;
constexpr int OFF_U = 4 * SLOT, U_STRIDE = 4096 + 256 + 32;
constexpr int OFF_BUF = OFF_U + 4 * U_STRIDE, BUF_STRIDE = 8320;
constexpr int OFF_K = OFF_BUF + 4 * BUF_STRIDE;
constexpr int OFF_WPHI = OFF_K + 4 * KT_BYTES;
constexpr int OFF_GW = OFF_WPHI + 2048;
constexpr int OFF_BAR = OFF_GW + 1024;
constexpr int SMEM_BYTES = OFF_BAR + 256 + 256;
static_assert(SMEM_BYTES <= 232448 && OFF_BUF % 128 == 0, "smem");
constexpr int W5_OFF = 0, W3_OFF = 3088, W9_OFF = 6176;
constexpr int BAR_FULL = 0, BAR_EMPTY = 4, BAR_WPHI = 8, BAR_WO = 9, BAR_WO2 = 10, BAR_XT = 11, BAR_DONE = 12, BAR_KG = 13, BAR_SP = 14,
              BAR_PUB = 15, BAR_KVF = 16, BAR_UR = 17, BAR_WR = 18, BAR_PREP = 19, BAR_KGA = 20, BAR_SP2 = 21, OFF_CNT = 192, OFF_PAUSE = 196;
#define CONV_START BAR_DONE
#define NOPAUSE
#define D1_NS 0
#define D2_NS 0
#define D3_NS 100
#define PS_NS 100
#define POLL_NS 0
constexpr int SPIN_LIMIT = 1 << 17;

__device__ __forceinline__ uint32_t s2u(const void* p) { return (uint32_t)__cvta_generic_to_shared(p); }
__device__ __forceinline__ void mbar_init(uint32_t b, int c) { asm volatile("mbarrier.init.shared::cta.b64 [%0],%1;" ::"r"(b), "r"(c) : "memory"); }
__device__ __forceinline__ void mbar_expect(uint32_t b, int bytes) { asm volatile("mbarrier.arrive.expect_tx.shared::cta.b64 _,[%0],%1;" ::"r"(b), "r"(bytes) : "memory"); }
__device__ __forceinline__ void mbar_arrive(uint32_t b) { asm volatile("mbarrier.arrive.shared::cta.b64 _,[%0];" ::"r"(b) : "memory"); }
__device__ __forceinline__ void mbar_wait(uint32_t b, int ph) {
    asm volatile("{\n.reg .pred p;\n.reg .u32 n;\nmov.u32 n,0;\nLW_%=:\nmbarrier.try_wait.parity.shared::cta.b64 p,[%0],%1;\n@p bra LD_%=;\n"
                 "add.u32 n,n,1;\nsetp.lt.u32 p,n,16384;\n@p bra LW_%=;\nLD_%=:\n}" ::"r"(b), "r"(ph) : "memory");
}
__device__ __forceinline__ void tma2d(uint32_t dst, const CUtensorMap* m, int c0, int c1, uint32_t bar) {
    asm volatile("cp.async.bulk.tensor.2d.shared::cluster.global.mbarrier::complete_tx::bytes [%0],[%1,{%3,%4}],[%2];" ::"r"(dst), "l"(m), "r"(bar), "r"(c0), "r"(c1) : "memory");
}
__device__ __forceinline__ void tma3d(uint32_t dst, const CUtensorMap* m, int c0, int c1, int c2, uint32_t bar) {
    asm volatile("cp.async.bulk.tensor.3d.shared::cluster.global.mbarrier::complete_tx::bytes [%0],[%1,{%3,%4,%5}],[%2];" ::"r"(dst), "l"(m), "r"(bar), "r"(c0), "r"(c1), "r"(c2) : "memory");
}
__device__ __forceinline__ void bulk_g2s(uint32_t dst, const void* src, int bytes, uint32_t bar) {
    asm volatile("cp.async.bulk.shared::cluster.global.mbarrier::complete_tx::bytes [%0],[%1],%2,[%3];" ::"r"(dst), "l"(src), "r"(bytes), "r"(bar) : "memory");
}
__device__ __forceinline__ uint64_t mkdesc(uint32_t addr, uint32_t lbo, uint32_t sbo) {
    return (uint64_t)((addr & 0x3FFFF) >> 4) | ((uint64_t)(lbo >> 4) << 16) | ((uint64_t)(sbo >> 4) << 32) | ((uint64_t)1 << 62);
}
__device__ __forceinline__ void wg_fence() { asm volatile("wgmma.fence.sync.aligned;" ::: "memory"); }
__device__ __forceinline__ void wg_commit() { asm volatile("wgmma.commit_group.sync.aligned;" ::: "memory"); }
template <int N> __device__ __forceinline__ void wg_wait() { asm volatile("wgmma.wait_group.sync.aligned %0;" ::"n"(N) : "memory"); }
template <int N> __device__ __forceinline__ void fence_regs(float* d) {
#pragma unroll
    for (int i = 0; i < N; i++) asm volatile("" : "+f"(d[i])::"memory");
}
#define R8(d, o) "+f"(d[o]), "+f"(d[o + 1]), "+f"(d[o + 2]), "+f"(d[o + 3]), "+f"(d[o + 4]), "+f"(d[o + 5]), "+f"(d[o + 6]), "+f"(d[o + 7])
__device__ __forceinline__ void wgmma192(float* d, uint64_t da, uint64_t db) {
    asm volatile("wgmma.mma_async.sync.aligned.m64n192k16.f32.bf16.bf16 {"
                 "%0,%1,%2,%3,%4,%5,%6,%7,%8,%9,%10,%11,%12,%13,%14,%15,%16,%17,%18,%19,%20,%21,%22,%23,%24,%25,%26,%27,%28,%29,%30,%31,"
                 "%32,%33,%34,%35,%36,%37,%38,%39,%40,%41,%42,%43,%44,%45,%46,%47,%48,%49,%50,%51,%52,%53,%54,%55,%56,%57,%58,%59,%60,%61,%62,%63,"
                 "%64,%65,%66,%67,%68,%69,%70,%71,%72,%73,%74,%75,%76,%77,%78,%79,%80,%81,%82,%83,%84,%85,%86,%87,%88,%89,%90,%91,%92,%93,%94,%95},"
                 "%96,%97,1,1,1,0,1;"
                 : R8(d, 0), R8(d, 8), R8(d, 16), R8(d, 24), R8(d, 32), R8(d, 40), R8(d, 48), R8(d, 56), R8(d, 64), R8(d, 72), R8(d, 80), R8(d, 88)
                 : "l"(da), "l"(db));
}
__device__ __forceinline__ void wgmma64_tt(float* d, uint64_t da, uint64_t db, int sc) {
    asm volatile("{.reg .pred p; setp.ne.b32 p,%34,0; wgmma.mma_async.sync.aligned.m64n64k16.f32.bf16.bf16 {"
                 "%0,%1,%2,%3,%4,%5,%6,%7,%8,%9,%10,%11,%12,%13,%14,%15,%16,%17,%18,%19,%20,%21,%22,%23,%24,%25,%26,%27,%28,%29,%30,%31},"
                 "%32,%33,p,1,1,1,1;}"
                 : R8(d, 0), R8(d, 8), R8(d, 16), R8(d, 24)
                 : "l"(da), "l"(db), "r"(sc));
}
__device__ __forceinline__ void wgmma128_rs(float* d, const uint4& a, uint64_t db, int sc) {
    asm volatile("{.reg .pred p; setp.ne.b32 p,%69,0; wgmma.mma_async.sync.aligned.m64n128k16.f32.bf16.bf16 {"
                 "%0,%1,%2,%3,%4,%5,%6,%7,%8,%9,%10,%11,%12,%13,%14,%15,%16,%17,%18,%19,%20,%21,%22,%23,%24,%25,%26,%27,%28,%29,%30,%31,"
                 "%32,%33,%34,%35,%36,%37,%38,%39,%40,%41,%42,%43,%44,%45,%46,%47,%48,%49,%50,%51,%52,%53,%54,%55,%56,%57,%58,%59,%60,%61,%62,%63},"
                 "{%64,%65,%66,%67},%68,p,1,1,1;}"
                 : R8(d, 0), R8(d, 8), R8(d, 16), R8(d, 24), R8(d, 32), R8(d, 40), R8(d, 48), R8(d, 56)
                 : "r"(a.x), "r"(a.y), "r"(a.z), "r"(a.w), "l"(db), "r"(sc));
}
__device__ __forceinline__ void mma16816(float* c, uint32_t a0, uint32_t a1, uint32_t a2, uint32_t a3, uint32_t b0, uint32_t b1) {
    asm("mma.sync.aligned.m16n8k16.row.col.f32.bf16.bf16.f32 {%0,%1,%2,%3},{%4,%5,%6,%7},{%8,%9},{%0,%1,%2,%3};"
        : "+f"(c[0]), "+f"(c[1]), "+f"(c[2]), "+f"(c[3]) : "r"(a0), "r"(a1), "r"(a2), "r"(a3), "r"(b0), "r"(b1));
}
__device__ __forceinline__ void ldsm4(uint32_t* r, uint32_t a) {
    asm volatile("ldmatrix.sync.aligned.m8n8.x4.shared.b16 {%0,%1,%2,%3},[%4];" : "=r"(r[0]), "=r"(r[1]), "=r"(r[2]), "=r"(r[3]) : "r"(a) : "memory");
}
__device__ __forceinline__ void ldsm4t(uint32_t* r, uint32_t a) {
    asm volatile("ldmatrix.sync.aligned.m8n8.x4.trans.shared.b16 {%0,%1,%2,%3},[%4];" : "=r"(r[0]), "=r"(r[1]), "=r"(r[2]), "=r"(r[3]) : "r"(a) : "memory");
}
__device__ __forceinline__ void stsm4(uint32_t a, uint32_t r0, uint32_t r1, uint32_t r2, uint32_t r3) {
    asm volatile("stmatrix.sync.aligned.m8n8.x4.shared.b16 [%0],{%1,%2,%3,%4};" ::"r"(a), "r"(r0), "r"(r1), "r"(r2), "r"(r3) : "memory");
}
__device__ __forceinline__ uint32_t lds32(uint32_t a) { uint32_t v; asm volatile("ld.shared.b32 %0,[%1];" : "=r"(v) : "r"(a) : "memory"); return v; }
__device__ __forceinline__ uint4 lds128(uint32_t a) { uint4 v; asm volatile("ld.shared.v4.b32 {%0,%1,%2,%3},[%4];" : "=r"(v.x), "=r"(v.y), "=r"(v.z), "=r"(v.w) : "r"(a) : "memory"); return v; }
__device__ __forceinline__ void sts16(uint32_t a, uint32_t v) { asm volatile("st.shared.b16 [%0],%1;" ::"r"(a), "h"((unsigned short)v) : "memory"); }
__device__ __forceinline__ void sts32(uint32_t a, uint32_t v) { asm volatile("st.shared.b32 [%0],%1;" ::"r"(a), "r"(v) : "memory"); }
__device__ __forceinline__ void sts64(uint32_t a, uint32_t x, uint32_t y) { asm volatile("st.shared.v2.b32 [%0],{%1,%2};" ::"r"(a), "r"(x), "r"(y) : "memory"); }
__device__ __forceinline__ void sts128(uint32_t a, uint32_t x, uint32_t y, uint32_t z, uint32_t w) { asm volatile("st.shared.v4.b32 [%0],{%1,%2,%3,%4};" ::"r"(a), "r"(x), "r"(y), "r"(z), "r"(w) : "memory"); }
__device__ __forceinline__ uint32_t pack2(float lo, float hi) { uint32_t d; asm("cvt.rn.bf16x2.f32 %0,%1,%2;" : "=r"(d) : "f"(hi), "f"(lo)); return d; }
__device__ __forceinline__ float bf_lo(uint32_t v) { return __uint_as_float(v << 16); }
__device__ __forceinline__ float bf_hi(uint32_t v) { return __uint_as_float(v & 0xffff0000u); }
__device__ __forceinline__ float bf_round(float v) { return bf_lo(pack2(v, 0.f)); }
__device__ __forceinline__ uint32_t hmax2(uint32_t a, uint32_t b) { uint32_t d; asm("max.bf16x2 %0,%1,%2;" : "=r"(d) : "r"(a), "r"(b)); return d; }
__device__ __forceinline__ uint32_t hmin2(uint32_t a, uint32_t b) { uint32_t d; asm("min.bf16x2 %0,%1,%2;" : "=r"(d) : "r"(a), "r"(b)); return d; }
__device__ __forceinline__ uint32_t hmul2(uint32_t a, uint32_t b) { uint32_t d; asm("mul.rn.bf16x2 %0,%1,%2;" : "=r"(d) : "r"(a), "r"(b)); return d; }
__device__ __forceinline__ float ex2(float x) { float y; asm("ex2.approx.ftz.f32 %0,%1;" : "=f"(y) : "f"(x)); return y; }
__device__ __forceinline__ float rcp(float x) { float y; asm("rcp.approx.ftz.f32 %0,%1;" : "=f"(y) : "f"(x)); return y; }
__device__ __forceinline__ uint32_t ld_nc(const uint32_t* p) { uint32_t v; asm volatile("ld.global.nc.b32 %0,[%1];" : "=r"(v) : "l"(p)); return v; }
__device__ __forceinline__ uint2 ld_nc64(const uint2* p) { uint2 v; asm volatile("ld.global.nc.v2.b32 {%0,%1},[%2];" : "=r"(v.x), "=r"(v.y) : "l"(p)); return v; }
__device__ __forceinline__ unsigned ld_acq(const unsigned* p) { unsigned v; asm volatile("ld.acquire.gpu.global.u32 %0,[%1];" : "=r"(v) : "l"(p) : "memory"); return v; }
__device__ __forceinline__ unsigned ld_rlx(const unsigned* p) { unsigned v; asm volatile("ld.relaxed.gpu.global.u32 %0,[%1];" : "=r"(v) : "l"(p) : "memory"); return v; }
__device__ __forceinline__ uint2 ld_rlx64(const void* p) { uint2 v; asm volatile("{.reg .b64 t; ld.relaxed.gpu.global.b64 t,[%2]; mov.b64 {%0,%1},t;}" : "=r"(v.x), "=r"(v.y) : "l"(p) : "memory"); return v; }
__device__ __forceinline__ uint4 ld_rlx128(const void* p) {
    uint4 v;
    asm volatile("{.reg .b64 t,u; ld.relaxed.gpu.global.v2.b64 {t,u},[%4]; mov.b64 {%0,%1},t; mov.b64 {%2,%3},u;}" : "=r"(v.x), "=r"(v.y), "=r"(v.z), "=r"(v.w) : "l"(p) : "memory");
    return v;
}
__device__ __forceinline__ void st_rlx32(void* p, uint32_t x) { asm volatile("st.relaxed.gpu.global.u32 [%0],%1;" ::"l"(p), "r"(x) : "memory"); }
__device__ __forceinline__ void st_rlx64(void* p, uint32_t x, uint32_t y) { asm volatile("{.reg .b64 t; mov.b64 t,{%1,%2}; st.relaxed.gpu.global.b64 [%0],t;}" ::"l"(p), "r"(x), "r"(y) : "memory"); }
__device__ __forceinline__ void st_rlx128(void* p, uint4 v) {
    asm volatile("{.reg .b64 t,u; mov.b64 t,{%1,%2}; mov.b64 u,{%3,%4}; st.relaxed.gpu.global.v2.b64 [%0],{t,u};}" ::"l"(p), "r"(v.x), "r"(v.y), "r"(v.z), "r"(v.w) : "memory");
}
__device__ __forceinline__ uint32_t tagw(uint32_t w, uint32_t tag) { return (w & ~1u) | tag; }
__device__ __forceinline__ uint4 tag4(uint32_t x, uint32_t y, uint32_t z, uint32_t w, uint32_t tag) { return make_uint4(tagw(x, tag), y, tagw(z, tag), w); }
__device__ __forceinline__ uint32_t bad4(const uint4& v, uint32_t tag) { return (v.x ^ tag) | (v.z ^ tag); }
__device__ __forceinline__ void bar_named(int id, int n) { asm volatile("bar.sync %0,%1;" ::"r"(id), "r"(n) : "memory"); }

struct cf { float re, im; };
__device__ __forceinline__ cf cmul(cf a, cf b) { cf r; r.re = a.re * b.re - a.im * b.im; r.im = a.re * b.im + a.im * b.re; return r; }
__device__ __forceinline__ cf cexp_p(float arl, float ait, float p) {
    float mag = ex2(arl * p);
    float t = ait * p;
    t = (t - rintf(t)) * 6.283185307179586f;
    cf r; r.re = mag * __cosf(t); r.im = mag * __sinf(t);
    return r;
}

__device__ __forceinline__ void hedgehog4(const uint32_t* a, uint32_t wphi_addr, uint32_t (*out)[8]) {
    float p[4][2][4], mx[4][2];
#pragma unroll
    for (int h = 0; h < 4; h++) {
        uint32_t b[4];
        ldsm4t(b, wphi_addr + h * 512);
        float c0[4] = {0.f, 0.f, 0.f, 0.f}, c1[4] = {0.f, 0.f, 0.f, 0.f};
        mma16816(c0, a[4 * h], a[4 * h + 1], a[4 * h + 2], a[4 * h + 3], b[0], b[1]);
        mma16816(c1, a[4 * h], a[4 * h + 1], a[4 * h + 2], a[4 * h + 3], b[2], b[3]);
#pragma unroll
        for (int k = 0; k < 2; k++) {
            p[h][k][0] = c0[2 * k]; p[h][k][1] = c0[2 * k + 1]; p[h][k][2] = c1[2 * k]; p[h][k][3] = c1[2 * k + 1];
            mx[h][k] = fmaxf(fmaxf(p[h][k][0], p[h][k][1]), fmaxf(p[h][k][2], p[h][k][3]));
        }
    }
#pragma unroll
    for (int o = 1; o <= 2; o <<= 1)
#pragma unroll
        for (int h = 0; h < 4; h++)
#pragma unroll
            for (int k = 0; k < 2; k++) mx[h][k] = fmaxf(mx[h][k], __shfl_xor_sync(~0u, mx[h][k], o));
    const float L = 1.4426950408889634f;
    float pmin = 1.f;
#pragma unroll
    for (int h = 0; h < 4; h++)
#pragma unroll
        for (int k = 0; k < 2; k++) {
            const float m = -mx[h][k] * L;
            const float e0 = ex2(fmaf(p[h][k][0], L, m)), e1 = ex2(fmaf(p[h][k][1], L, m)), e2 = ex2(fmaf(p[h][k][2], L, m)), e3 = ex2(fmaf(p[h][k][3], L, m));
            const float p01 = e0 * e1, p23 = e2 * e3, pp = p01 * p23, r = rcp(pp), r01 = r * p23, r23 = r * p01;
            pmin = fminf(pmin, pp);
            out[h][k] = pack2(e0, e1); out[h][k + 2] = pack2(e2, e3);
            out[h][4 + k] = pack2(r01 * e1, r01 * e0); out[h][4 + k + 2] = pack2(r23 * e3, r23 * e2);
        }
    if (__builtin_expect(__any_sync(~0u, !(pmin > 1e-18f)), 0)) {
#pragma unroll
        for (int h = 0; h < 4; h++)
#pragma unroll
            for (int k = 0; k < 2; k++) {
                float m = fminf(fminf(p[h][k][0], p[h][k][1]), fminf(p[h][k][2], p[h][k][3]));
                m = fminf(m, __shfl_xor_sync(~0u, m, 1));
                m = fminf(m, __shfl_xor_sync(~0u, m, 2)) * L;
                out[h][4 + k] = pack2(ex2(fmaf(p[h][k][0], -L, m)), ex2(fmaf(p[h][k][1], -L, m)));
                out[h][4 + k + 2] = pack2(ex2(fmaf(p[h][k][2], -L, m)), ex2(fmaf(p[h][k][3], -L, m)));
            }
    }
}

__global__ void __launch_bounds__(512, 1)
fused_kernel(Scratch* __restrict__ scr, const bf16* __restrict__ logA, const bf16* __restrict__ Aim, const bf16* __restrict__ Cre,
             const bf16* __restrict__ Cim, const bf16* __restrict__ logdt, const bf16* __restrict__ Dskip, const bf16* __restrict__ wphi,
             const bf16* __restrict__ gatew, bf16* __restrict__ out,
             const __grid_constant__ CUtensorMap mx, const __grid_constant__ CUtensorMap mw, const __grid_constant__ CUtensorMap mwo) {
    extern __shared__ __align__(1024) uint8_t smem[];
    const uint32_t sb = s2u(smem);
    const int tid = threadIdx.x, warp = __shfl_sync(~0u, tid >> 5, 0), lane = tid & 31;
    const int g = lane >> 2, q = lane & 3, w4 = warp & 3;
    const int bi = blockIdx.x, bi_i = bi & 15, bi_j = bi >> 4;
    const uint32_t bar = sb + OFF_BAR;
    const int rot = (bi_j & 3) * 2, xkb = bi_j >> 2;
    auto load_stage = [&](int kb) {
        const uint32_t b = bar + 8 * (BAR_FULL + (kb & 3)), d = sb + (kb & 3) * SLOT;
        const int kc = ((kb + rot) & 7) * 64;
        mbar_expect(b, SLOT);
        tma2d(d, &mx, kc, bi_i * 128, b);
        tma3d(d + 16384, &mw, bi_j * 64, kc, 0, b);
    };

    const int ch = bi * 4 + w4;
    const int pidx = ch * 64 + lane * 2 + (warp >> 3);
    const uint32_t pla = ld_nc((const uint32_t*)logA + pidx), pai = ld_nc((const uint32_t*)Aim + pidx);
    const uint32_t pcr = ld_nc((const uint32_t*)Cre + pidx), pci = ld_nc((const uint32_t*)Cim + pidx);
    uint32_t pdt = ld_nc((const uint32_t*)logdt + (ch >> 1));
    const uint32_t pds = ld_nc((const uint32_t*)Dskip + (ch >> 1));
    unsigned done0 = ld_rlx(scr->done);
    if (tid == 0) {
        for (int s = 0; s < 4; s++) mbar_init(bar + 8 * (BAR_FULL + s), 1);
        asm volatile("fence.mbarrier_init.release.cluster;" ::: "memory");
        load_stage(0); load_stage(1);
        STAMP(11);
    } else if (tid == 32) {
        if (sb & 1023) __trap();
        sts32(bar + OFF_CNT, 0); sts32(bar + OFF_PAUSE, 0);
        for (int s = 0; s < 4; s++) mbar_init(bar + 8 * (BAR_EMPTY + s), 9);
        mbar_init(bar + 8 * BAR_WPHI, 1); mbar_init(bar + 8 * BAR_WO, 2); mbar_init(bar + 8 * BAR_WO2, 1); mbar_init(bar + 8 * BAR_XT, 4);
        mbar_init(bar + 8 * BAR_DONE, 9); mbar_init(bar + 8 * BAR_KG, 8); mbar_init(bar + 8 * BAR_SP, 1); mbar_init(bar + 8 * BAR_PUB, 8);
        mbar_init(bar + 8 * BAR_KVF, 4); mbar_init(bar + 8 * BAR_UR, 4); mbar_init(bar + 8 * BAR_WR, 4); mbar_init(bar + 8 * BAR_PREP, 4); mbar_init(bar + 8 * BAR_KGA, 4); mbar_init(bar + 8 * BAR_SP2, 1);
        asm volatile("fence.mbarrier_init.release.cluster;" ::: "memory");
        mbar_expect(bar + 8 * BAR_WPHI, 3072);
        bulk_g2s(sb + OFF_GW, gatew, 1024, bar + 8 * BAR_WPHI);
        bulk_g2s(sb + OFF_WPHI, wphi + bi_j * 1024, 2048, bar + 8 * BAR_WPHI);
    } else if (tid == 64) {
        asm volatile("prefetch.tensormap [%0];" ::"l"(&mw) : "memory");
    }
    const uint32_t buf = sb + OFF_BUF + w4 * BUF_STRIDE, kb_ = sb + OFF_K + w4 * KT_BYTES;
    if ((warp >> 2) == 2) {
#pragma unroll
        for (int v = 0; v < 7; v++) if (v * 32 + lane < KT_BYTES / 16) sts128(kb_ + (v * 32 + lane) * 16, 0, 0, 0, 0);
    }
    __syncthreads();
    asm volatile("" : "+r"(pdt), "+r"(done0)::"memory");
    const unsigned epoch1 = (done0 >> 7) + 1u;
    const uint32_t tag = epoch1 & 1u;

    const int st = tid & 127;
    const uint32_t ub = sb + OFF_U + w4 * U_STRIDE + 256, spare = sb + (w4 < 2 ? OFF_SP0 : OFF_SP1) + (w4 & 1) * 4096;

    auto stg_of = [&](int w) { return w < 8 ? sb + 3 * SLOT + w * 7296 : sb + 2 * SLOT + (w & 3) * 7296; };
    float kc[24];
#pragma unroll
    for (int t = 0; t < 24; t++) kc[t] = 0.f;
    {
        const float dt = bf_round(expf((ch & 1) ? bf_hi(pdt) : bf_lo(pdt)));
        const uint32_t stg = (warp >> 2) == 2 ? buf : stg_of(warp);
        const int sh = ((warp >> 2) & 1) * 16;
        auto pick = [&](uint32_t v) { return __uint_as_float((v >> sh) << 16); };
        const float ea = bf_round(expf(pick(pla)));
        const float arl = (-ea * dt) * 1.4426950408889634f, ait = (pick(pai) * dt) * 0.15915494309189535f;
        cf C2; C2.re = 2.0f * (pick(pcr) * dt); C2.im = 2.0f * (pick(pci) * dt);
        const cf z1 = cexp_p(arl, ait, 1.0f), z128 = cexp_p(arl, ait, 128.0f);
        cf z8 = cexp_p(arl, ait, 8.0f); z8.im = -z8.im;
        const uint32_t lp = stg + lane * 4;
        auto put = [&](int row, const cf& v) { sts32((lp ^ ((row & 7) << 4)) + row * 128, pack2(v.re, v.im)); };
        {
            const cf z16 = cmul(z8, z8);
            cf e; e.re = 1.f; e.im = 0.f;
            cf o = z8;
            put(0, e); put(1, o);
            e = z16; put(2, e);
#pragma unroll
            for (int b = 3; b < 16; b += 2) {
                o = cmul(o, z16); put(b, o);
                if (b + 1 < 16) { e = cmul(e, z16); put(b + 1, e); }
            }
        }
        cf h[8];
        h[0] = C2; put(16, h[0]);
        {
            const cf z2 = cmul(z1, z1);
            h[1] = cmul(h[0], z1);
#pragma unroll
            for (int r = 2; r < 8; r++) h[r] = cmul(h[r - 2], z2);
#pragma unroll
            for (int r = 1; r < 8; r++) put(16 + r, h[r]);
        }
#pragma unroll
        for (int r = 0; r < 8; r++) { h[r] = cmul(h[r], z128); put(24 + r, h[r]); }
#pragma unroll
        for (int al = 0; al < 2; al++)
#pragma unroll
            for (int r = 0; r < 4; r++) { h[2 * r] = cmul(h[2 * r], z128); put(32 + al * 4 + r, h[2 * r]); }
#pragma unroll
        for (int al = 0; al < 4; al++)
#pragma unroll
            for (int r = 0; r < 2; r++) { h[4 * r] = cmul(h[4 * r], z128); put(40 + al * 2 + r, h[4 * r]); }
#pragma unroll
        for (int al = 0; al < 9; al++) { h[0] = cmul(h[0], z128); put(48 + al, h[0]); }
        __syncwarp();
        const int lr = lane & 7, lm = lane >> 3;
#pragma unroll
        for (int kp = 0; kp < 2; kp++) {
            uint32_t a0[4], a1[4];
            ldsm4(a0, stg + ((lm & 1) * 8 + lr) * 128 + (((4 * kp + (lm >> 1)) ^ lr) << 4));
            ldsm4(a1, stg + ((lm & 1) * 8 + lr) * 128 + (((4 * kp + 2 + (lm >> 1)) ^ lr) << 4));
#pragma unroll
            for (int t = 0; t < 6; t++) {
                uint32_t b[4];
                ldsm4(b, stg + (16 + 8 * t + lr) * 128 + (((4 * kp + lm) ^ lr) << 4));
                mma16816(kc + 4 * t, a0[0], a0[1], a0[2], a0[3], b[0], b[1]);
                mma16816(kc + 4 * t, a1[0], a1[1], a1[2], a1[3], b[2], b[3]);
            }
        }
        __syncwarp();
        if ((warp >> 2) != 2) {
#pragma unroll
            for (int t = 0; t < 6; t++)
                sts128(stg + (t * 32 + lane) * 16, __float_as_uint(kc[4 * t]), __float_as_uint(kc[4 * t + 1]), __float_as_uint(kc[4 * t + 2]), __float_as_uint(kc[4 * t + 3]));
            asm volatile("fence.proxy.async.shared::cta;" ::: "memory");
            __syncwarp();
            if (lane == 0) mbar_arrive(bar + 8 * (warp < 8 ? BAR_KG : BAR_KGA));
        }
    }

    if (warp < 8) {
        asm volatile("setmaxnreg.inc.sync.aligned.u32 160;");
        const int wg = warp >> 2;
        if (warp == 0) STAMP(21);
        float acc[96];
        const int srow = warp * 16 + (lane & 15);
        const uint32_t srow_a = srow * 128;
        const int sx = srow & 7, shi = lane >> 4;
#pragma unroll
        for (int r = 0; r < 96; r++) acc[r] = 0.f;
        fence_regs<96>(acc);
        const uint64_t da0 = mkdesc(sb + wg * 8192, 16, 1024), db0 = mkdesc(sb + 16384, 8192, 1024);
#pragma unroll 1
        for (int kb = 0; kb < 8; kb++) {
            const int s = kb & 3;
            const uint64_t da = da0 + s * (SLOT >> 4), db = db0 + s * (SLOT >> 4);
            if (warp == 0) STAMP(40 + kb);
            mbar_wait(bar + 8 * (BAR_FULL + s), kb >> 2);
            if (warp == 0) STAMP(32 + kb);
            wg_fence();
#pragma unroll
            for (int k = 0; k < 4; k++) wgmma192(acc, da + 2 * k, db + 128 * k);
            wg_commit();
            wg_wait<1>();
            if (lane == 0 && kb > 0) mbar_arrive(bar + 8 * (BAR_EMPTY + ((kb - 1) & 3)));
        }
        mbar_wait(bar + 8 * BAR_WPHI, 0);
        wg_wait<0>();
        fence_regs<96>(acc);
        if (lane == 0) mbar_arrive(bar + 8 * BAR_DONE);
        if (warp == 0) STAMP(1);
        uint32_t in[16], qa[16];
        mbar_wait(bar + 8 * BAR_DONE, 0);
#pragma unroll
        for (int r = 0; r < 16; r++) {
            in[r] = pack2(acc[32 + 2 * r], acc[32 + 2 * r + 1]);
            qa[r] = pack2(acc[2 * r], acc[2 * r + 1]);
        }
#pragma unroll
        for (int hh = 0; hh < 4; hh++)
            stsm4(sb + OFF_V + (hh >> 1) * 16384 + srow_a + (((2 * (hh & 1) + shi) ^ sx) << 4), pack2(acc[64 + 8 * hh], acc[65 + 8 * hh]),
                  pack2(acc[66 + 8 * hh], acc[67 + 8 * hh]), pack2(acc[68 + 8 * hh], acc[69 + 8 * hh]), pack2(acc[70 + 8 * hh], acc[71 + 8 * hh]));
        sts128(sb + OFF_V + shi * 16384 + srow_a + ((4 ^ sx) << 4), 0x3f803f80u, 0x3f803f80u, 0x3f803f80u, 0x3f803f80u);
        const uint32_t wphi_a = sb + OFF_WPHI + (lane & 15) * 32 + (lane >> 4) * 16;
        uint32_t pq[4][8];
#pragma unroll 1
        for (int it = 0; it < 2; it++) {
            hedgehog4(in, wphi_a, pq);
            if (it == 1) break;
#pragma unroll
            for (int hs = 0; hs < 8; hs++) {
                float c[4] = {0.f, 0.f, 0.f, 0.f};
                const uint32_t* o = pq[hs >> 1] + 4 * (hs & 1);
                mma16816(c, o[0], o[1], o[2], o[3], 0x3f803f80u, 0x3f803f80u);
                const float r0 = rcp(c[0]), r1 = rcp(c[2]);
                const uint32_t s0 = pack2(r0, r0), s1 = pack2(r1, r1);
                stsm4(sb + OFF_P + (hs >> 2) * 16384 + srow_a + (((2 * (hs & 3) + shi) ^ sx) << 4), hmul2(o[0], s0), hmul2(o[1], s1), hmul2(o[2], s0), hmul2(o[3], s1));
            }
            asm volatile("fence.proxy.async.shared::cta;" ::: "memory");
            bar_named(1, 256);
            if (warp == 0) STAMP(2);
            float d[32];
            const uint64_t dv = mkdesc(sb + OFF_V + wg * 16384, 16, 1024), dp = mkdesc(sb + OFF_P + wg * 16384, 16, 1024);
            wg_fence();
#pragma unroll
            for (int k = 0; k < 8; k++) wgmma64_tt(d, dv + 128 * k, dp + 128 * k, k != 0);
            wg_commit();
            mbar_wait(bar + 8 * BAR_PREP, 0);
            uint4* kvp = scr->kvp + bi * 544 + wg * 272 + (w4 < 2 ? w4 * 136 : 128) + lane;
            wg_wait<0>();
            fence_regs<32>(d);
            if (w4 < 2 || (w4 == 2 && lane < 4)) {
#pragma unroll
                for (int f = 0; f < 4; f++) {
                    const int i0 = 8 * (f >> 1) + 2 * (f & 1), i2 = 16 * (f >> 1) + 8 * (f & 1);
                    const float e0 = w4 == 0 ? d[i0] : (w4 == 1 ? d[16 + i0] : d[i2]), e1 = w4 == 0 ? d[i0 + 1] : (w4 == 1 ? d[17 + i0] : d[i2 + 1]);
                    const float e2 = w4 == 0 ? d[i0 + 4] : (w4 == 1 ? d[20 + i0] : d[i2 + 4]), e3 = w4 == 0 ? d[i0 + 5] : (w4 == 1 ? d[21 + i0] : d[i2 + 5]);
                    st_rlx128(kvp + (w4 < 2 ? f * 32 : (f >> 1) * 136 + (f & 1) * 4), tag4(__float_as_uint(e0), __float_as_uint(e1), __float_as_uint(e2), __float_as_uint(e3), tag));
                }
            }
            __syncwarp();
            if (lane == 0) mbar_arrive(bar + 8 * BAR_PUB);
            if (warp == 0) STAMP(3);
#pragma unroll
            for (int r = 0; r < 16; r++) in[r] = qa[r];
        }
        if (warp == 0) STAMP(4);
        {
            mbar_wait(bar + 8 * BAR_KVF, 0);
            uint4 kf[4][3];
#pragma unroll
            for (int hh = 0; hh < 4; hh++) {
                const uint32_t a = sb + OFF_KVF + hh * 1088;
                kf[hh][0] = lds128(a + lane * 32); kf[hh][1] = lds128(a + lane * 32 + 16); kf[hh][2] = lds128(a + 1024 + q * 16);
            }
            if (warp == 0) STAMP(5);
            uint4* og = scr->o + ((bi_i * 8 + warp) * 32 + bi_j * 4) * 32 + lane;
#pragma unroll
            for (int hh = 0; hh < 4; hh++) {
                float c[6][4];
#pragma unroll
                for (int t = 0; t < 6; t++) { c[t][0] = c[t][1] = c[t][2] = c[t][3] = 0.f; }
                const uint32_t* a = pq[hh];
                const bool od = g & 1;
                mma16816(c[0], a[0], a[1], a[2], a[3], od ? 0x3f803f80u : kf[hh][2].x, od ? 0x3f803f80u : kf[hh][2].y);
                mma16816(c[1], a[4], a[5], a[6], a[7], od ? 0x3f803f80u : kf[hh][2].z, od ? 0x3f803f80u : kf[hh][2].w);
                mma16816(c[2], a[0], a[1], a[2], a[3], kf[hh][0].x, kf[hh][0].y);
                mma16816(c[3], a[0], a[1], a[2], a[3], kf[hh][0].z, kf[hh][0].w);
                mma16816(c[4], a[4], a[5], a[6], a[7], kf[hh][1].x, kf[hh][1].y);
                mma16816(c[5], a[4], a[5], a[6], a[7], kf[hh][1].z, kf[hh][1].w);
                uint32_t w[4];
#pragma unroll
                for (int k = 0; k < 2; k++) {
                    const float rho = c[0][2 * k + 1] * rcp(c[1][2 * k + 1]);
                    const float r = rcp(fmaf(c[0][2 * k + 1], 1e-6f, fmaf(rho, c[1][2 * k], c[0][2 * k]))), rr = r * rho;
                    w[k] = pack2(fmaf(c[4][2 * k], rr, c[2][2 * k] * r), fmaf(c[4][2 * k + 1], rr, c[2][2 * k + 1] * r));
                    w[2 + k] = pack2(fmaf(c[5][2 * k], rr, c[3][2 * k] * r), fmaf(c[5][2 * k + 1], rr, c[3][2 * k + 1] * r));
                }
                st_rlx128(og + hh * 32, tag4(w[0], w[1], w[2], w[3], tag));
            }
        }
        if (tid == 0) sts32(bar + OFF_PAUSE, 0);
        if (warp == 0) STAMP(6);
        float oc[64];
        const int slab = bi_i * 8 + (bi_j >> 2) * 4 + w4;
        const uint8_t* yb = (const uint8_t*)scr->y + (size_t)((bi_j & 3) * 32 + wg * 16 + (q >> 1)) * 16384 + slab * 128 + g * 16 + (q & 1) * 8;
        const unsigned* gp = scr->g + (slab * 8 + (g >> 1)) * 8 + (g & 1) * 4;
        uint2 yv[8]; unsigned g0, g1;
        {
            const uint4* osrc = scr->o + (slab * 32 + wg * 16) * 32 + lane;
            uint4 fr[16];
            const unsigned* probe = (const unsigned*)(osrc - lane + ((lane & 3) * 4 + 3) * 32 + 31) + 2;
            {
                unsigned miss = ~0u;
                int n = 0;
#pragma unroll
                for (int s = 0; s < 4; s++) {
#pragma unroll 1
                    while ((miss >> s) & 1) { miss = __ballot_sync(~0u, (ld_rlx(probe) ^ tag) & 1); if (++n > SPIN_LIMIT) break; }
#pragma unroll
                    for (int k = 4 * s; k < 4 * s + 4; k++) fr[k] = ld_rlx128(osrc + k * 32);
                }
            }
            if (warp == 0) STAMP(14);
            mbar_wait(bar + 8 * (wg ? BAR_WO2 : BAR_WO), 0);
            const uint64_t dw = mkdesc(sb + wg * 2 * SLOT, wg ? 32768 : SLOT, 1024);
#pragma unroll
            for (int s = 0; s < 4; s++) {
                int n = 0;
#pragma unroll 1
                while (__builtin_expect(__any_sync(~0u, (bad4(fr[4 * s], tag) | bad4(fr[4 * s + 1], tag) | bad4(fr[4 * s + 2], tag) | bad4(fr[4 * s + 3], tag)) & 1), 0)) {
#pragma unroll
                    for (int k = 4 * s; k < 4 * s + 4; k++) fr[k] = ld_rlx128(osrc + k * 32);
                    if (++n > SPIN_LIMIT) break;
                }
                wg_fence();
#pragma unroll
                for (int hh = 0; hh < 4; hh++) wgmma128_rs(oc, fr[4 * s + hh], dw + 128 * (4 * s + hh), (s | hh) != 0);
                wg_commit();
                if (s == 1) {
                    wg_wait<1>();
#pragma unroll
                    for (int nt = 0; nt < 8; nt++) yv[nt] = ld_rlx64(yb + nt * 32768);
                    g0 = ld_rlx(gp); g1 = ld_rlx(gp + 32);
                }
            }
            if (warp == 0) STAMP(7);
            {
                const unsigned* yprobe = scr->yflag + ((bi_j & 3) * 32 + wg * 16 + (lane & 15)) * 8;
                int n = 0;
#pragma unroll 1
                while (true) {
                    uint32_t bad = (g0 ^ tag) | (g1 ^ tag);
#pragma unroll
                    for (int nt = 0; nt < 8; nt++) bad |= yv[nt].x ^ tag;
                    if (!__any_sync(~0u, bad & 1)) break;
#pragma unroll 1
                    while (__any_sync(~0u, (ld_rlx(yprobe) ^ tag) & 1)) { if (++n > SPIN_LIMIT) break; }
#pragma unroll
                    for (int nt = 0; nt < 8; nt++) yv[nt] = ld_rlx64(yb + nt * 32768);
                    g0 = ld_rlx(gp); g1 = ld_rlx(gp + 32);
                    if (++n > SPIN_LIMIT) break;
                }
            }
            if (warp == 0) STAMP(28);
            wg_wait<0>();
            fence_regs<64>(oc);
        }
        {
            bar_named(3 + wg, 128);
            const uint32_t xw = sb + wg * 2 * SLOT + (tid & 127) * 16, xr = sb + (wg ^ 1) * 2 * SLOT + (tid & 127) * 16;
#pragma unroll
            for (int r = 0; r < 8; r++) {
                const float* o = oc + 4 * r;
                sts128(xw + r * 2048, __float_as_uint(wg ? o[0] : o[32]), __float_as_uint(wg ? o[1] : o[33]), __float_as_uint(wg ? o[2] : o[34]), __float_as_uint(wg ? o[3] : o[35]));
            }
#pragma unroll
            for (int r = 0; r < 32; r++) oc[r] = wg ? oc[32 + r] : oc[r];
            bar_named(1, 256);
            if (warp == 0) STAMP(8);
            const float ga = bf_hi(g0), gb = bf_hi(g1);
            const float ha = bf_round(1.0f - ga), hb = bf_round(1.0f - gb);
            uint32_t w[8][2];
#pragma unroll
            for (int nt = 0; nt < 8; nt++) {
                const uint4 p = lds128(xr + nt * 2048);
                w[nt][0] = pack2(fmaf(ga, oc[4 * nt] + __uint_as_float(p.x), ha * bf_lo(yv[nt].x)), fmaf(ga, oc[4 * nt + 1] + __uint_as_float(p.y), ha * bf_hi(yv[nt].x)));
                w[nt][1] = pack2(fmaf(gb, oc[4 * nt + 2] + __uint_as_float(p.z), hb * bf_lo(yv[nt].y)), fmaf(gb, oc[4 * nt + 3] + __uint_as_float(p.w), hb * bf_hi(yv[nt].y)));
            }
            const uint32_t ob = sb + wg * 2 * SLOT + 16384 + w4 * 2048;
#pragma unroll
            for (int nt = 0; nt < 8; nt += 2)
                stsm4(ob + (lane & 15) * 128 + (((nt + shi) ^ (lane & 7)) << 4), w[nt][0], w[nt][1], w[nt + 1][0], w[nt + 1][1]);
            __syncwarp();
            bf16* op = out + (size_t)(slab * 16) * 512 + (bi_j & 3) * 128 + wg * 64 + (lane & 7) * 8;
#pragma unroll
            for (int it = 0; it < 4; it++) {
                const int r = it * 4 + (lane >> 3);
                uint4 v = lds128(ob + r * 128 + (((lane & 7) ^ (r & 7)) << 4));
                *(uint4*)(op + r * 512) = v;
            }
        }
        if (warp == 0) STAMP(10);
    } else if (warp < 12) {
#pragma unroll
        for (int src = 2; src >= 0; src--) {
            if (src != 0) mbar_wait(bar + 8 * (src == 2 ? BAR_KGA : BAR_KG), 0);
#pragma unroll
            for (int t = 0; t < 6; t++) {
                const uint4 v = lds128(stg_of(w4 + src * 4) + (t * 32 + lane) * 16);
                kc[4 * t] += __uint_as_float(v.x); kc[4 * t + 1] += __uint_as_float(v.y); kc[4 * t + 2] += __uint_as_float(v.z); kc[4 * t + 3] += __uint_as_float(v.w);
            }
            if (src != 1) {
                bar_named(2, 128);
                if (st == 0) { load_stage(src == 2 ? 2 : 3); if (src == 0) mbar_arrive(bar + 8 * BAR_SP); }
                if (warp == 8) STAMP(src == 2 ? 22 : 17);
            }
        }
        if (warp == 8) {
#pragma unroll 1
            for (int kb = 0; kb < 6; kb++) {
                const int s = kb & 3;
                mbar_wait(bar + 8 * (BAR_EMPTY + s), kb >> 2);
                if (kb == xkb) mbar_wait(bar + 8 * BAR_XT, 0);
                if (lane == 0) {
                    STAMP(48 + kb);
                    if (kb < 4) load_stage(kb + 4);
                    else {
                        mbar_expect(bar + 8 * BAR_WO, 32768);
                        tma2d(sb + s * SLOT, &mwo, (bi_j & 3) * 128 + s * 64, 0, bar + 8 * BAR_WO);
                        if (kb == 5) mbar_arrive(bar + 8 * BAR_SP2);
                    }
                }
                __syncwarp();
            }
        } else if (warp == 9) {
            const int row = bi_j * 16 + (lane >> 1), half = lane & 1;
            unsigned* gp = scr->g + (bi_i * 64 + bi_j * 8) * 8 + lane * 2;
            st_rlx64(gp, tag ^ 1u, tag ^ 1u);
            if (lane < 8) st_rlx32(scr->yflag + bi * 8 + lane, tag ^ 1u);
            float gs0 = 0.f, gs1 = 0.f;
            mbar_wait(bar + 8 * BAR_WPHI, 0);
#pragma unroll 1
            for (int kb = 0; kb < 8; kb++) {
                const int s = kb & 3;
                mbar_wait(bar + 8 * (BAR_FULL + s), kb >> 2);
#pragma unroll
                for (int c = 0; c < 4; c++) {
                    const uint4 xv = lds128(sb + s * SLOT + row * 128 + (((half * 4 + c) ^ (row & 7)) << 4));
                    const uint4 gw = lds128(sb + OFF_GW + ((kb + rot) & 7) * 128 + half * 64 + c * 16);
                    const uint32_t p0 = hmul2(xv.x, gw.x), p1 = hmul2(xv.y, gw.y), p2 = hmul2(xv.z, gw.z), p3 = hmul2(xv.w, gw.w);
                    gs0 += (bf_lo(p0) + bf_lo(p1)) + (bf_lo(p2) + bf_lo(p3));
                    gs1 += (bf_hi(p0) + bf_hi(p1)) + (bf_hi(p2) + bf_hi(p3));
                }
                asm volatile("" : "+f"(gs0), "+f"(gs1));
                __syncwarp();
                if (lane == 0) mbar_arrive(bar + 8 * (kb < 7 ? BAR_EMPTY + s : BAR_DONE));
            }
            float gs = gs0 + gs1;
            gs += __shfl_xor_sync(~0u, gs, 1);
            const uint32_t gv = __float_as_uint(bf_round(rcp(1.0f + ex2(-1.4426950408889634f * bf_round(gs))))) | tag;
            st_rlx64(gp, gv, gv);
        }
        if (lane == 0) kc[4 * 0 + 0] += ((ch & 1) ? bf_hi(pds) : bf_lo(pds));
        const uint32_t k1024 = __shfl_sync(~0u, pack2(kc[4 * 4 + 0], 0.f), 0);
#pragma unroll
        for (int i = 0; i < 2; i++) {
            const int be = g + 8 * i;
#pragma unroll
            for (int t = 0; t < 2; t++) {
                const uint32_t a = kb_ + (KW_D + 128 * t + 8 * be + 2 * q) * 4;
                const uint32_t w = pack2(kc[4 * t + 2 * i + 1], kc[4 * t + 2 * i]);
                sts32(a + 4, w); sts16(a, w >> 16); sts16(a + 10, w);
            }
            {
                const int p = 256 + 128 * (q >> 1) + 8 * be + 4 * (q & 1);
                const uint32_t a = kb_ + (KW_D + p) * 4;
                const uint32_t w = pack2(kc[4 * 2 + 2 * i + 1], kc[4 * 2 + 2 * i]);
                const uint32_t aa = (w >> 16) | (w & 0xffff0000u);
                if (p != 256) { sts16(a - 4, aa); sts32(a, aa); } else sts16(a, aa);
                sts32(a + 4, aa); sts32(a + 8, w); sts16(a + 14, w);
            }
            {
                const int k = 64 + 16 * q + be;
                const uint32_t w = pack2(kc[4 * 3 + 2 * i], kc[4 * 3 + 2 * i + 1]);
                if (k != 64) sts16(kb_ + (KW_2 + ((k - 1) >> 1) - 24) * 4 + (k & 1) * 2, w);
                else {
                    const uint32_t a = kb_ + (KW_D + 511) * 4, aa = (w << 16) | (w & 0xffffu);
                    sts16(a, w); sts32(a + 4, aa); sts32(a + 8, aa); sts32(a + 12, aa); sts16(a + 18, w);
                }
                sts16(kb_ + (KW_2 + 48 + (k >> 1) - 24) * 4 + ((k & 1) ^ 1) * 2, w >> 16);
            }
#pragma unroll
            for (int b = 0; b < 2; b++) {
                const int k = 64 + 8 * (2 * q + b) + (be >> 1);
                const uint32_t w = pack2(kc[4 * 4 + 2 * i + b], 0.f);
                if (!(be & 1) && k == 64) sts16(kb_ + (KW_2 + 63 - 24) * 4, w);
                else {
                    const uint32_t a = kb_ + (KW_3 + ((be & 1) ? 80 + k : k - 1) - 48) * 4;
                    sts16(a, w);
                    if (!((be & 1) && k == 127)) sts16(a + 6, w);
                }
            }
        }
        if (lane == 0) sts16(kb_ + (KW_3 + 127 - 48) * 4, pack2(kc[4 * 5 + 0], 0.f));
        __syncwarp();
        mbar_wait(bar + 8 * BAR_UR, 0);
        mbar_wait(bar + 8 * CONV_START, 0);
        auto yield = [&]() {
        };
        if (warp == 8) STAMP(23);
        float y[16][4];
#pragma unroll
        for (int nt = 0; nt < 16; nt++) { y[nt][0] = y[nt][1] = y[nt][2] = y[nt][3] = 0.f; }
        {
            uint32_t Bp[32], A[5][3];
            auto uaddr = [&](int rho) { const int R0 = (lane >> 4) * 8 + (lane & 7) - rho; return ub + (((2 * R0 + ((lane >> 3) & 1)) ^ ((R0 >> 2) & 1)) << 4); };
            const uint32_t kd = kb_ + (KW_D + g - 2 * q) * 4;
            auto lda = [&](int rho) {
#pragma unroll
                for (int ga = 0; ga < 5; ga++) {
                    const uint32_t a = kd + (ga < 4 ? rho : (rho & 1)) * 64 + ga * 512;
                    A[ga][0] = lds32(a); A[ga][1] = lds32(a + 32); A[ga][2] = lds32(a - 32);
                }
            };
            {
                const uint32_t a = uaddr(0);
#pragma unroll
                for (int p = 0; p < 8; p++) ldsm4(Bp + 4 * p, a + p * 512);
            }
#pragma unroll 1
            for (int rho = 0; rho < 8; rho++) {
                yield();
                lda(rho);
                if (rho < 2) {
#pragma unroll
                    for (int nt = 4; nt < 16; nt++) mma16816(y[nt], A[4][0], A[4][1], A[4][2], A[4][0], Bp[2 * (nt - 4)], Bp[2 * (nt - 4) + 1]);
                }
#pragma unroll
                for (int ga = 0; ga < 3; ga++)
#pragma unroll
                    for (int nt = 15; nt >= ga; nt--) mma16816(y[nt], A[ga][0], A[ga][1], A[ga][2], A[ga][0], Bp[2 * (nt - ga)], Bp[2 * (nt - ga) + 1]);
                yield();
                const uint32_t an = uaddr(rho + 1);
                ldsm4(Bp + 28, an + 7 * 512);
#pragma unroll
                for (int nt = 15; nt >= 3; nt--) {
                    mma16816(y[nt], A[3][0], A[3][1], A[3][2], A[3][0], Bp[2 * (nt - 3)], Bp[2 * (nt - 3) + 1]);
                    if (nt & 1) ldsm4(Bp + 2 * (nt - 3), an + ((nt - 3) >> 1) * 512);
                }
            }
        }
        if (warp == 8) STAMP(18);
        mbar_wait(bar + 8 * BAR_WR, 0);
#pragma unroll 1
        for (int ph = 0; ph < 2; ph++) {
            yield();
            uint32_t B[5][2];
            const uint32_t ka = kb_ + (KW_2 + ph * 48 + 8 + g - q) * 4;
#pragma unroll
            for (int dd = 0; dd < 5; dd++) { B[dd][0] = lds32(ka + dd * 32); B[dd][1] = lds32(ka + dd * 32 - 16); }
            const uint32_t wa = buf + ph * W3_OFF + ((lane & 7) + ((lane >> 3) & 1) + (lane >> 4) * 8) * 16;
#pragma unroll
            for (int s = 0; s < 12; s++) {
                uint32_t A[4];
                ldsm4t(A, wa + s * 256);
#pragma unroll
                for (int dd = 0; dd < 5; dd++)
                    if (s + 4 + dd < 16) mma16816(y[s + 4 + dd], A[0], A[1], A[2], A[3], B[dd][0], B[dd][1]);
            }
        }
        {
            const int ap = (lane & 7) + (lane >> 4) * 8;
            const uint32_t loff = ((2 * ap + ((lane >> 3) & 1)) ^ ((ap >> 2) & 1)) << 4;
#pragma unroll 1
            for (int ph = 0; ph < 2; ph++) {
                yield();
                uint32_t B[8][2];
                const uint32_t wb = (ph ? spare : buf + W9_OFF) + loff;
                const uint32_t ka = kb_ + (KW_3 + ph * 80 + 16 + g - 2 * q) * 4;
#pragma unroll
                for (int dd = 0; dd < 8; dd++) { B[dd][0] = lds32(ka + dd * 32); B[dd][1] = lds32(ka + dd * 32 - 32); }
#pragma unroll
                for (int s = 0; s < 4; s++) {
                    uint32_t A[4];
                    ldsm4t(A, wb + s * 512);
#pragma unroll
                    for (int dd = 0; dd < 8; dd++)
                        if (8 + 2 * s + dd < 16) mma16816(y[8 + 2 * s + dd], A[0], A[1], A[2], A[3], B[dd][0], B[dd][1]);
                }
            }
            const uint32_t idw = (g == 2 * q) ? k1024 : ((g == 2 * q + 1) ? (k1024 << 16) : 0u);
#pragma unroll
            for (int s = 0; s < 4; s++) {
                uint32_t A[4];
                ldsm4t(A, spare + 2048 + loff + s * 512);
                mma16816(y[8 + 2 * s], A[0], A[1], A[2], A[3], idw, 0u);
                mma16816(y[9 + 2 * s], A[0], A[1], A[2], A[3], 0u, idw);
            }
        }
        __syncwarp();
        if (warp == 8) STAMP(19);
#pragma unroll
        for (int nt = 0; nt < 16; nt++)
#pragma unroll
            for (int b = 0; b < 2; b++) sts32(buf + ((8 * nt + 2 * q + b) * 8 + g) * 4, pack2(y[nt][b], y[nt][2 + b]));
        bar_named(2, 128);
        uint4* yp = scr->y + bi * 1024 + st;
#pragma unroll
        for (int v = 0; v < 8; v++) {
            const uint32_t a = sb + OFF_BUF + (st + 128 * v) * 4;
            const uint32_t w0 = lds32(a), w1 = lds32(a + BUF_STRIDE), w2 = lds32(a + 2 * BUF_STRIDE), w3 = lds32(a + 3 * BUF_STRIDE);
            st_rlx128(yp + v * 128, tag4(__byte_perm(w0, w1, 0x5410), __byte_perm(w0, w1, 0x7632), __byte_perm(w2, w3, 0x5410), __byte_perm(w2, w3, 0x7632), tag));
        }
        if (st < 8) st_rlx32(scr->yflag + bi * 8 + st, tag);
        if (warp == 8) STAMP(20);
    } else {
        asm volatile("setmaxnreg.dec.sync.aligned.u32 64;");
        const int qq = (bi_i & 2) + ((lane >> 1) & 1);
        uint2* kvf_h = (uint2*)(scr->kvf + (bi_j * 4 + (bi_i >> 2)) * 68);
        auto windows = [&](int rhi, int rlo) {
#pragma unroll 1
            for (int rho = rhi; rho >= rlo; rho--) {
                const int ci = lane + 32 * rho;
                uint4 e4[4];
#pragma unroll
                for (int v = 0; v < 4; v++) { const int cc = ci - 3 + v; e4[v] = lds128(ub + ((cc ^ ((cc >> 3) & 1)) << 4)); }
                float S[29];
                const uint32_t* ew = (const uint32_t*)e4;
                S[3] = 0.f;
#pragma unroll
                for (int k = 4; k <= 28; k++) S[k] = S[k - 1] + ((k & 1) ? bf_hi(ew[k >> 1]) : bf_lo(ew[k >> 1]));
                auto win = [&](int lo, int hi, uint32_t a) {
                    sts128(a, pack2(S[hi] - S[lo - 1], S[hi + 1] - S[lo]), pack2(S[hi + 2] - S[lo + 1], S[hi + 3] - S[lo + 2]),
                           pack2(S[hi + 4] - S[lo + 3], S[hi + 5] - S[lo + 4]), pack2(S[hi + 6] - S[lo + 5], S[hi + 7] - S[lo + 6]));
                };
                win(14, 18, buf + W5_OFF + 16 + ci * 16); win(19, 21, buf + W3_OFF + 16 + ci * 16);
                if (rho < 4) {
                    const uint32_t sw = (ci ^ ((ci >> 3) & 1)) << 4;
                    win(4, 12, buf + W9_OFF + sw); win(13, 19, spare + sw); win(20, 21, spare + 2048 + sw);
                }
            }
        };
        {
            mbar_wait(bar + 8 * (BAR_FULL + xkb), 0);
#pragma unroll 1
            for (int hf = 0; hf < 2; hf++) {
                const int r = w4 * 32 + hf * 16 + (lane & 15);
                uint32_t* xt = (uint32_t*)scr->xt + ((xkb + rot) * 16 + (g >> 2)) * 4096 + (bi_i * 16 + w4 * 4 + hf * 2) * 16 + (g & 3) * 4 + q;
#pragma unroll
                for (int cb = 0; cb < 8; cb += 2) {
                    uint32_t v[4];
                    ldsm4t(v, sb + xkb * SLOT + r * 128 + (((cb + (lane >> 4)) ^ (r & 7)) << 4));
                    xt[cb * 8192] = v[0]; xt[cb * 8192 + 16] = v[1]; xt[cb * 8192 + 8192] = v[2]; xt[cb * 8192 + 8192 + 16] = v[3];
                }
            }
            __syncwarp();
            if (lane == 0) mbar_arrive(bar + 8 * BAR_XT);
            if (warp == 12) {
                STAMP(26);
                mbar_wait(bar + 8 * BAR_XT, 0);
                if (lane == 0) asm volatile("red.release.gpu.global.add.u32 [%0],8;" ::"l"(scr->xcnt + (xkb + rot) * 32) : "memory");
                __syncwarp();
                STAMP(27);
            }
            {
                const uint32_t old = tag ^ 1u;
                const uint4 z4 = make_uint4(old, 0, old, 0);
#pragma unroll
                for (int v = 0; v < 5; v++) if (v < 4 || st < 32) st_rlx128(scr->kvp + bi * 544 + v * 128 + st, z4);
                if (st < 16) st_rlx128(scr->o + ((bi_i * 8 + (st >> 1)) * 32 + bi_j * 4 + 3) * 32 + 30 + (st & 1), z4);
                if (lane < 8) st_rlx64(kvf_h + ((bi_i & 3) * 8 + w4 * 2 + (lane & 1)) * 4 + (lane >> 1), old, 0);
                if (st < 4 && !(bi_i & 1)) st_rlx64(kvf_h + (64 + qq) * 2 + (lane & 1), old, 0);
                __syncwarp();
                if (lane == 0) mbar_arrive(bar + 8 * BAR_PREP);
            }
            int n = 0;
#pragma unroll 1
            while (__any_sync(~0u, (int)(ld_acq(scr->xcnt + bi_j * 32) - (epoch1 << 7)) < 0)) { if (++n > SPIN_LIMIT) break; }
            if (warp == 12) STAMP(15);
            uint4 ur[8];
#pragma unroll
            for (int v = 0; v < 8; v++) ur[v] = __ldcg(scr->xt + bi * 1024 + st + 128 * v);
            mbar_wait(bar + 8 * BAR_SP, 0);
            if (lane < 16) sts128(ub - 256 + lane * 16, 0, 0, 0, 0);
            if (lane < 2) sts128(buf + lane * W3_OFF, 0, 0, 0, 0);
#pragma unroll
            for (int v = 0; v < 8; v++) {
                const int ci = (st >> 2) + 32 * v;
                sts128(sb + OFF_U + (st & 3) * U_STRIDE + 256 + ((ci ^ ((ci >> 3) & 1)) << 4), ur[v].x, ur[v].y, ur[v].z, ur[v].w);
            }
            __syncwarp();
            if (lane == 0) mbar_arrive(bar + 8 * BAR_UR);
            mbar_wait(bar + 8 * BAR_UR, 0);
            if (warp == 12) STAMP(16);
            windows(5, 4);
        }
        mbar_wait(bar + 8 * BAR_SP2, 0);
        windows(3, 0);
        __syncwarp();
        if (lane == 0) mbar_arrive(bar + 8 * BAR_WR);
        if (warp == 12) STAMP(24);
        {
            const bool zw = st < 32 && !(bi_i & 1);
            const uint4* src = scr->kvp + bi_j * (16 * 544) + (bi_i >> 2) * 136;
            const uint4* zsrc = src + (lane >> 2) * (2 * 544) + 128 + (lane & 1) * 4 + qq;
            src += (lane >> 3) * (4 * 544) + ((lane >> 1) & 3) * 32 + (bi_i & 3) * 8 + w4 * 2 + (lane & 1);
            mbar_wait(bar + 8 * BAR_PUB, 0);
            if (warp == 12) STAMP(12);
            __nanosleep(D1_NS);
            uint4 v[6];
#pragma unroll
            for (int k = 0; k < 6; k++) v[k] = make_uint4(tag ^ 1u, 0, 0, 0);
            int n = 0;
#pragma unroll 1
            while (true) {
#pragma unroll
                for (int k = 0; k < 6; k++) if ((bad4(v[k], tag) & 1) && (k < 4 || zw)) v[k] = ld_rlx128(k < 4 ? src + k * 544 : zsrc + (k - 4) * 544);
                if (!__any_sync(~0u, (bad4(v[0], tag) | bad4(v[1], tag) | bad4(v[2], tag) | bad4(v[3], tag) | (zw ? bad4(v[4], tag) | bad4(v[5], tag) : 0u)) & 1)) break;
                if (warp == 12 && n < 3) STAMP(54 + n);
                if (++n > SPIN_LIMIT) break;
                __nanosleep(POLL_NS);
            }
            if (warp == 12) STAMP(30);
            float f[8];
            const float* vf = (const float*)v;
#pragma unroll
            for (int r = 0; r < 4; r++) {
                f[r] = (vf[r] + vf[4 + r]) + (vf[8 + r] + vf[12 + r]);
                f[4 + r] = vf[16 + r] + vf[20 + r];
                f[4 + r] += __shfl_xor_sync(~0u, f[4 + r], 4);
            }
#pragma unroll
            for (int o = 8; o <= 16; o <<= 1)
#pragma unroll
                for (int r = 0; r < 8; r++) f[r] += __shfl_xor_sync(~0u, f[r], o);
            if (lane < 8) st_rlx64(kvf_h + ((bi_i & 3) * 8 + w4 * 2 + (lane & 1)) * 4 + (lane >> 1), tagw(pack2(f[0], f[1]), tag), pack2(f[2], f[3]));
            if (zw && lane < 4) st_rlx64(kvf_h + (64 + qq) * 2 + (lane & 1), tagw(pack2(f[4], f[5]), tag), pack2(f[6], f[7]));
        }
        if (warp == 12) STAMP(13);
        {
            const uint4* kp = scr->kvf + bi_j * 272 + st;
            __nanosleep(D2_NS);
            uint4 v0 = make_uint4(tag ^ 1u, 0, 0, 0), v1 = v0, v2 = make_uint4(st < 16 ? tag ^ 1u : tag, 0, tag, 0);
            int n = 0;
#pragma unroll 1
            while (true) {
                if (bad4(v0, tag) & 1) v0 = ld_rlx128(kp);
                if (bad4(v1, tag) & 1) v1 = ld_rlx128(kp + 128);
                if (bad4(v2, tag) & 1) v2 = ld_rlx128(kp + 256);
                if (!__any_sync(~0u, (bad4(v0, tag) | bad4(v1, tag) | bad4(v2, tag)) & 1)) break;
                if (++n > SPIN_LIMIT) break;
                __nanosleep(POLL_NS);
            }
            sts128(sb + OFF_KVF + st * 16, v0.x, v0.y, v0.z, v0.w);
            sts128(sb + OFF_KVF + 2048 + st * 16, v1.x, v1.y, v1.z, v1.w);
            if (st < 16) sts128(sb + OFF_KVF + 4096 + st * 16, v2.x, v2.y, v2.z, v2.w);
            if (st == 0) sts32(bar + OFF_PAUSE, 1);
            __syncwarp();
            if (lane == 0) mbar_arrive(bar + 8 * BAR_KVF);
        }
        if (warp == 13) {
            mbar_wait(bar + 8 * BAR_KVF, 0);
            if (lane == 0) {
                mbar_expect(bar + 8 * BAR_WO2, 65536);
                tma2d(sb + OFF_P, &mwo, (bi_j & 3) * 128, 256, bar + 8 * BAR_WO2);
                tma2d(sb + OFF_V, &mwo, (bi_j & 3) * 128 + 64, 256, bar + 8 * BAR_WO2);
            }
        }
        if (warp == 12) STAMP(25);
    }
    __syncwarp();
    if (lane == 0) {
        unsigned old;
        asm volatile("atom.acq_rel.cta.shared.add.u32 %0,[%1],1;" : "=r"(old) : "r"(bar + OFF_CNT) : "memory");
        if (old == 15) {
            atomicAdd(scr->done, 1u);
        }
    }
}

typedef CUresult (*EncFn)(CUtensorMap*, CUtensorMapDataType, cuuint32_t, void*, const cuuint64_t*, const cuuint64_t*, const cuuint32_t*,
                          const cuuint32_t*, CUtensorMapInterleave, CUtensorMapSwizzle, CUtensorMapL2promotion, CUtensorMapFloatOOBfill);

extern "C" void kernel_launch(void* const* d_in, const int* in_sizes, int n_in, void* d_out, int out_size) {
    static EncFn enc = nullptr;
    static Scratch* scr = nullptr;
    if (!enc) {
        cudaGetSymbolAddress((void**)&scr, g_scr);
        cudaDriverEntryPointQueryResult qr;
        cudaGetDriverEntryPoint("cuTensorMapEncodeTiled", (void**)&enc, cudaEnableDefault, &qr);
        cudaFuncSetAttribute(fused_kernel, cudaFuncAttributeMaxDynamicSharedMemorySize, SMEM_BYTES);
    }
    CUtensorMap mx, mw, mwo;
    const cuuint32_t es[3] = {1, 1, 1};
    {
        cuuint64_t d[2] = {512, 2048}, s[1] = {1024}; cuuint32_t b[2] = {64, 128};
        enc(&mx, CU_TENSOR_MAP_DATA_TYPE_BFLOAT16, 2, d_in[0], d, s, b, es, CU_TENSOR_MAP_INTERLEAVE_NONE, CU_TENSOR_MAP_SWIZZLE_128B,
            CU_TENSOR_MAP_L2_PROMOTION_L2_128B, CU_TENSOR_MAP_FLOAT_OOB_FILL_NONE);
    }
    {
        cuuint64_t d[3] = {512, 512, 3}, s[2] = {3072, 1024}; cuuint32_t b[3] = {64, 64, 3};
        enc(&mw, CU_TENSOR_MAP_DATA_TYPE_BFLOAT16, 3, d_in[1], d, s, b, es, CU_TENSOR_MAP_INTERLEAVE_NONE, CU_TENSOR_MAP_SWIZZLE_128B,
            CU_TENSOR_MAP_L2_PROMOTION_L2_128B, CU_TENSOR_MAP_FLOAT_OOB_FILL_NONE);
    }
    {
        cuuint64_t d[2] = {512, 512}, s[1] = {1024}; cuuint32_t b[2] = {64, 256};
        enc(&mwo, CU_TENSOR_MAP_DATA_TYPE_BFLOAT16, 2, d_in[3], d, s, b, es, CU_TENSOR_MAP_INTERLEAVE_NONE, CU_TENSOR_MAP_SWIZZLE_128B,
            CU_TENSOR_MAP_L2_PROMOTION_L2_128B, CU_TENSOR_MAP_FLOAT_OOB_FILL_NONE);
    }
    fused_kernel<<<128, 512, SMEM_BYTES, cudaStreamPerThread>>>(
        scr, (const bf16*)d_in[5], (const bf16*)d_in[6], (const bf16*)d_in[7], (const bf16*)d_in[8], (const bf16*)d_in[9],
        (const bf16*)d_in[10], (const bf16*)d_in[2], (const bf16*)d_in[11], (bf16*)d_out, mx, mw, mwo);
}
```

```cpp
#include <cuda_runtime.h>
#include <cuda.h>
#include <cuda_bf16.h>
#include <stdint.h>

typedef __nv_bfloat16 bf16;

struct Scratch {
    uint4 xt[128 * 1024];
    uint4 o[16 * 8 * 32 * 32];
    uint4 y[128 * 1024];
    uint4 kvp[8 * 16 * 544];
    uint4 kvf[8 * 4 * 68];
    unsigned g[1024 * 8];
    unsigned yflag[128 * 8];
    unsigned xcnt[8 * 32];
    unsigned done[32];
};
__device__ Scratch g_scr;
#define STAMP(n)

constexpr int SLOT = 40960;
constexpr int OFF_SP0 = 32768, OFF_SP1 = SLOT + 32768;
constexpr int OFF_P = 2 * SLOT, OFF_V = OFF_P + 32768;
constexpr int OFF_KVF = OFF_V + 32768;
constexpr int KT_BYTES = 3264, KW_D = 16, KW_2 = 560, KW_3 = 656;
constexpr int OFF_U = 4 * SLOT, U_STRIDE = 4096 + 256 + 32;
constexpr int OFF_BUF = OFF_U + 4 * U_STRIDE, BUF_STRIDE = 8320;
constexpr int OFF_K = OFF_BUF + 4 * BUF_STRIDE;
constexpr int OFF_WPHI = OFF_K + 4 * KT_BYTES;
constexpr int OFF_GW = OFF_WPHI + 2048;
constexpr int OFF_BAR = OFF_GW + 1024;
constexpr int SMEM_BYTES = OFF_BAR + 256 + 256;
static_assert(SMEM_BYTES <= 232448 && OFF_BUF % 128 == 0, "smem");
constexpr int W5_OFF = 0, W3_OFF = 3088, W9_OFF = 6176;
constexpr int BAR_FULL = 0, BAR_EMPTY = 4, BAR_WPHI = 8, BAR_WO = 9, BAR_WO2 = 10, BAR_XT = 11, BAR_DONE = 12, BAR_KG = 13, BAR_SP = 14,
              BAR_PUB = 15, BAR_KVF = 16, BAR_UR = 17, BAR_WR = 18, BAR_PREP = 19, BAR_KGA = 20, BAR_SP2 = 21, OFF_CNT = 192;
#define CONV_START BAR_DONE
#define D1_NS 0
#define D2_NS 0
#define D3_NS 100
#define PS_NS 100
#define POLL_NS 0
constexpr int SPIN_LIMIT = 1 << 17;

__device__ __forceinline__ uint32_t s2u(const void* p) { return (uint32_t)__cvta_generic_to_shared(p); }
__device__ __forceinline__ void mbar_init(uint32_t b, int c) { asm volatile("mbarrier.init.shared::cta.b64 [%0],%1;" ::"r"(b), "r"(c) : "memory"); }
__device__ __forceinline__ void mbar_expect(uint32_t b, int bytes) { asm volatile("mbarrier.arrive.expect_tx.shared::cta.b64 _,[%0],%1;" ::"r"(b), "r"(bytes) : "memory"); }
__device__ __forceinline__ void mbar_arrive(uint32_t b) { asm volatile("mbarrier.arrive.shared::cta.b64 _,[%0];" ::"r"(b) : "memory"); }
__device__ __forceinline__ void mbar_wait(uint32_t b, int ph) {
    asm volatile("{\n.reg .pred p;\n.reg .u32 n;\nmov.u32 n,0;\nLW_%=:\nmbarrier.try_wait.parity.shared::cta.b64 p,[%0],%1;\n@p bra LD_%=;\n"
                 "add.u32 n,n,1;\nsetp.lt.u32 p,n,16384;\n@p bra LW_%=;\nLD_%=:\n}" ::"r"(b), "r"(ph) : "memory");
}
__device__ __forceinline__ void tma2d(uint32_t dst, const CUtensorMap* m, int c0, int c1, uint32_t bar) {
    asm volatile("cp.async.bulk.tensor.2d.shared::cluster.global.mbarrier::complete_tx::bytes [%0],[%1,{%3,%4}],[%2];" ::"r"(dst), "l"(m), "r"(bar), "r"(c0), "r"(c1) : "memory");
}
__device__ __forceinline__ void tma3d(uint32_t dst, const CUtensorMap* m, int c0, int c1, int c2, uint32_t bar) {
    asm volatile("cp.async.bulk.tensor.3d.shared::cluster.global.mbarrier::complete_tx::bytes [%0],[%1,{%3,%4,%5}],[%2];" ::"r"(dst), "l"(m), "r"(bar), "r"(c0), "r"(c1), "r"(c2) : "memory");
}
__device__ __forceinline__ void bulk_g2s(uint32_t dst, const void* src, int bytes, uint32_t bar) {
    asm volatile("cp.async.bulk.shared::cluster.global.mbarrier::complete_tx::bytes [%0],[%1],%2,[%3];" ::"r"(dst), "l"(src), "r"(bytes), "r"(bar) : "memory");
}
__device__ __forceinline__ uint64_t mkdesc(uint32_t addr, uint32_t lbo, uint32_t sbo) {
    return (uint64_t)((addr & 0x3FFFF) >> 4) | ((uint64_t)(lbo >> 4) << 16) | ((uint64_t)(sbo >> 4) << 32) | ((uint64_t)1 << 62);
}
__device__ __forceinline__ void wg_fence() { asm volatile("wgmma.fence.sync.aligned;" ::: "memory"); }
__device__ __forceinline__ void wg_commit() { asm volatile("wgmma.commit_group.sync.aligned;" ::: "memory"); }
template <int N> __device__ __forceinline__ void wg_wait() { asm volatile("wgmma.wait_group.sync.aligned %0;" ::"n"(N) : "memory"); }
template <int N> __device__ __forceinline__ void fence_regs(float* d) {
#pragma unroll
    for (int i = 0; i < N; i++) asm volatile("" : "+f"(d[i])::"memory");
}
#define R8(d, o) "+f"(d[o]), "+f"(d[o + 1]), "+f"(d[o + 2]), "+f"(d[o + 3]), "+f"(d[o + 4]), "+f"(d[o + 5]), "+f"(d[o + 6]), "+f"(d[o + 7])
__device__ __forceinline__ void wgmma192(float* d, uint64_t da, uint64_t db) {
    asm volatile("wgmma.mma_async.sync.aligned.m64n192k16.f32.bf16.bf16 {"
                 "%0,%1,%2,%3,%4,%5,%6,%7,%8,%9,%10,%11,%12,%13,%14,%15,%16,%17,%18,%19,%20,%21,%22,%23,%24,%25,%26,%27,%28,%29,%30,%31,"
                 "%32,%33,%34,%35,%36,%37,%38,%39,%40,%41,%42,%43,%44,%45,%46,%47,%48,%49,%50,%51,%52,%53,%54,%55,%56,%57,%58,%59,%60,%61,%62,%63,"
                 "%64,%65,%66,%67,%68,%69,%70,%71,%72,%73,%74,%75,%76,%77,%78,%79,%80,%81,%82,%83,%84,%85,%86,%87,%88,%89,%90,%91,%92,%93,%94,%95},"
                 "%96,%97,1,1,1,0,1;"
                 : R8(d, 0), R8(d, 8), R8(d, 16), R8(d, 24), R8(d, 32), R8(d, 40), R8(d, 48), R8(d, 56), R8(d, 64), R8(d, 72), R8(d, 80), R8(d, 88)
                 : "l"(da), "l"(db));
}
__device__ __forceinline__ void wgmma64_tt(float* d, uint64_t da, uint64_t db, int sc) {
    asm volatile("{.reg .pred p; setp.ne.b32 p,%34,0; wgmma.mma_async.sync.aligned.m64n64k16.f32.bf16.bf16 {"
                 "%0,%1,%2,%3,%4,%5,%6,%7,%8,%9,%10,%11,%12,%13,%14,%15,%16,%17,%18,%19,%20,%21,%22,%23,%24,%25,%26,%27,%28,%29,%30,%31},"
                 "%32,%33,p,1,1,1,1;}"
                 : R8(d, 0), R8(d, 8), R8(d, 16), R8(d, 24)
                 : "l"(da), "l"(db), "r"(sc));
}
__device__ __forceinline__ void wgmma128_rs(float* d, const uint4& a, uint64_t db, int sc) {
    asm volatile("{.reg .pred p; setp.ne.b32 p,%69,0; wgmma.mma_async.sync.aligned.m64n128k16.f32.bf16.bf16 {"
                 "%0,%1,%2,%3,%4,%5,%6,%7,%8,%9,%10,%11,%12,%13,%14,%15,%16,%17,%18,%19,%20,%21,%22,%23,%24,%25,%26,%27,%28,%29,%30,%31,"
                 "%32,%33,%34,%35,%36,%37,%38,%39,%40,%41,%42,%43,%44,%45,%46,%47,%48,%49,%50,%51,%52,%53,%54,%55,%56,%57,%58,%59,%60,%61,%62,%63},"
                 "{%64,%65,%66,%67},%68,p,1,1,1;}"
                 : R8(d, 0), R8(d, 8), R8(d, 16), R8(d, 24), R8(d, 32), R8(d, 40), R8(d, 48), R8(d, 56)
                 : "r"(a.x), "r"(a.y), "r"(a.z), "r"(a.w), "l"(db), "r"(sc));
}
__device__ __forceinline__ void mma16816(float* c, uint32_t a0, uint32_t a1, uint32_t a2, uint32_t a3, uint32_t b0, uint32_t b1) {
    asm("mma.sync.aligned.m16n8k16.row.col.f32.bf16.bf16.f32 {%0,%1,%2,%3},{%4,%5,%6,%7},{%8,%9},{%0,%1,%2,%3};"
        : "+f"(c[0]), "+f"(c[1]), "+f"(c[2]), "+f"(c[3]) : "r"(a0), "r"(a1), "r"(a2), "r"(a3), "r"(b0), "r"(b1));
}
__device__ __forceinline__ void ldsm4(uint32_t* r, uint32_t a) {
    asm volatile("ldmatrix.sync.aligned.m8n8.x4.shared.b16 {%0,%1,%2,%3},[%4];" : "=r"(r[0]), "=r"(r[1]), "=r"(r[2]), "=r"(r[3]) : "r"(a) : "memory");
}
__device__ __forceinline__ void ldsm4t(uint32_t* r, uint32_t a) {
    asm volatile("ldmatrix.sync.aligned.m8n8.x4.trans.shared.b16 {%0,%1,%2,%3},[%4];" : "=r"(r[0]), "=r"(r[1]), "=r"(r[2]), "=r"(r[3]) : "r"(a) : "memory");
}
__device__ __forceinline__ void stsm4(uint32_t a, uint32_t r0, uint32_t r1, uint32_t r2, uint32_t r3) {
    asm volatile("stmatrix.sync.aligned.m8n8.x4.shared.b16 [%0],{%1,%2,%3,%4};" ::"r"(a), "r"(r0), "r"(r1), "r"(r2), "r"(r3) : "memory");
}
__device__ __forceinline__ uint32_t lds32(uint32_t a) { uint32_t v; asm volatile("ld.shared.b32 %0,[%1];" : "=r"(v) : "r"(a) : "memory"); return v; }
__device__ __forceinline__ uint4 lds128(uint32_t a) { uint4 v; asm volatile("ld.shared.v4.b32 {%0,%1,%2,%3},[%4];" : "=r"(v.x), "=r"(v.y), "=r"(v.z), "=r"(v.w) : "r"(a) : "memory"); return v; }
__device__ __forceinline__ void sts16(uint32_t a, uint32_t v) { asm volatile("st.shared.b16 [%0],%1;" ::"r"(a), "h"((unsigned short)v) : "memory"); }
__device__ __forceinline__ void sts32(uint32_t a, uint32_t v) { asm volatile("st.shared.b32 [%0],%1;" ::"r"(a), "r"(v) : "memory"); }
__device__ __forceinline__ void sts64(uint32_t a, uint32_t x, uint32_t y) { asm volatile("st.shared.v2.b32 [%0],{%1,%2};" ::"r"(a), "r"(x), "r"(y) : "memory"); }
__device__ __forceinline__ void sts128(uint32_t a, uint32_t x, uint32_t y, uint32_t z, uint32_t w) { asm volatile("st.shared.v4.b32 [%0],{%1,%2,%3,%4};" ::"r"(a), "r"(x), "r"(y), "r"(z), "r"(w) : "memory"); }
__device__ __forceinline__ uint32_t pack2(float lo, float hi) { uint32_t d; asm("cvt.rn.bf16x2.f32 %0,%1,%2;" : "=r"(d) : "f"(hi), "f"(lo)); return d; }
__device__ __forceinline__ float bf_lo(uint32_t v) { return __uint_as_float(v << 16); }
__device__ __forceinline__ float bf_hi(uint32_t v) { return __uint_as_float(v & 0xffff0000u); }
__device__ __forceinline__ float bf_round(float v) { return bf_lo(pack2(v, 0.f)); }
__device__ __forceinline__ uint32_t hmax2(uint32_t a, uint32_t b) { uint32_t d; asm("max.bf16x2 %0,%1,%2;" : "=r"(d) : "r"(a), "r"(b)); return d; }
__device__ __forceinline__ uint32_t hmin2(uint32_t a, uint32_t b) { uint32_t d; asm("min.bf16x2 %0,%1,%2;" : "=r"(d) : "r"(a), "r"(b)); return d; }
__device__ __forceinline__ uint32_t hmul2(uint32_t a, uint32_t b) { uint32_t d; asm("mul.rn.bf16x2 %0,%1,%2;" : "=r"(d) : "r"(a), "r"(b)); return d; }
__device__ __forceinline__ float ex2(float x) { float y; asm("ex2.approx.ftz.f32 %0,%1;" : "=f"(y) : "f"(x)); return y; }
__device__ __forceinline__ float rcp(float x) { float y; asm("rcp.approx.ftz.f32 %0,%1;" : "=f"(y) : "f"(x)); return y; }
__device__ __forceinline__ uint32_t ld_nc(const uint32_t* p) { uint32_t v; asm volatile("ld.global.nc.b32 %0,[%1];" : "=r"(v) : "l"(p)); return v; }
__device__ __forceinline__ uint2 ld_nc64(const uint2* p) { uint2 v; asm volatile("ld.global.nc.v2.b32 {%0,%1},[%2];" : "=r"(v.x), "=r"(v.y) : "l"(p)); return v; }
__device__ __forceinline__ unsigned ld_acq(const unsigned* p) { unsigned v; asm volatile("ld.acquire.gpu.global.u32 %0,[%1];" : "=r"(v) : "l"(p) : "memory"); return v; }
__device__ __forceinline__ unsigned ld_rlx(const unsigned* p) { unsigned v; asm volatile("ld.relaxed.gpu.global.u32 %0,[%1];" : "=r"(v) : "l"(p) : "memory"); return v; }
__device__ __forceinline__ uint2 ld_rlx64(const void* p) { uint2 v; asm volatile("{.reg .b64 t; ld.relaxed.gpu.global.b64 t,[%2]; mov.b64 {%0,%1},t;}" : "=r"(v.x), "=r"(v.y) : "l"(p) : "memory"); return v; }
__device__ __forceinline__ uint4 ld_rlx128(const void* p) {
    uint4 v;
    asm volatile("{.reg .b64 t,u; ld.relaxed.gpu.global.v2.b64 {t,u},[%4]; mov.b64 {%0,%1},t; mov.b64 {%2,%3},u;}" : "=r"(v.x), "=r"(v.y), "=r"(v.z), "=r"(v.w) : "l"(p) : "memory");
    return v;
}
__device__ __forceinline__ void st_rlx32(void* p, uint32_t x) { asm volatile("st.relaxed.gpu.global.u32 [%0],%1;" ::"l"(p), "r"(x) : "memory"); }
__device__ __forceinline__ void st_rlx64(void* p, uint32_t x, uint32_t y) { asm volatile("{.reg .b64 t; mov.b64 t,{%1,%2}; st.relaxed.gpu.global.b64 [%0],t;}" ::"l"(p), "r"(x), "r"(y) : "memory"); }
__device__ __forceinline__ void st_rlx128(void* p, uint4 v) {
    asm volatile("{.reg .b64 t,u; mov.b64 t,{%1,%2}; mov.b64 u,{%3,%4}; st.relaxed.gpu.global.v2.b64 [%0],{t,u};}" ::"l"(p), "r"(v.x), "r"(v.y), "r"(v.z), "r"(v.w) : "memory");
}
__device__ __forceinline__ uint32_t tagw(uint32_t w, uint32_t tag) { return (w & ~1u) | tag; }
__device__ __forceinline__ uint4 tag4(uint32_t x, uint32_t y, uint32_t z, uint32_t w, uint32_t tag) { return make_uint4(tagw(x, tag), y, tagw(z, tag), w); }
__device__ __forceinline__ uint32_t bad4(const uint4& v, uint32_t tag) { return (v.x ^ tag) | (v.z ^ tag); }
__device__ __forceinline__ void bar_named(int id, int n) { asm volatile("bar.sync %0,%1;" ::"r"(id), "r"(n) : "memory"); }

struct cf { float re, im; };
__device__ __forceinline__ cf cmul(cf a, cf b) { cf r; r.re = a.re * b.re - a.im * b.im; r.im = a.re * b.im + a.im * b.re; return r; }
__device__ __forceinline__ cf cexp_p(float arl, float ait, float p) {
    float mag = ex2(arl * p);
    float t = ait * p;
    t = (t - rintf(t)) * 6.283185307179586f;
    cf r; r.re = mag * __cosf(t); r.im = mag * __sinf(t);
    return r;
}

__device__ __forceinline__ void hedgehog4(const uint32_t* a, uint32_t wphi_addr, uint32_t (*out)[8]) {
    float p[4][2][4], mx[4][2];
#pragma unroll
    for (int h = 0; h < 4; h++) {
        uint32_t b[4];
        ldsm4t(b, wphi_addr + h * 512);
        float c0[4] = {0.f, 0.f, 0.f, 0.f}, c1[4] = {0.f, 0.f, 0.f, 0.f};
        mma16816(c0, a[4 * h], a[4 * h + 1], a[4 * h + 2], a[4 * h + 3], b[0], b[1]);
        mma16816(c1, a[4 * h], a[4 * h + 1], a[4 * h + 2], a[4 * h + 3], b[2], b[3]);
#pragma unroll
        for (int k = 0; k < 2; k++) {
            p[h][k][0] = c0[2 * k]; p[h][k][1] = c0[2 * k + 1]; p[h][k][2] = c1[2 * k]; p[h][k][3] = c1[2 * k + 1];
            mx[h][k] = fmaxf(fmaxf(p[h][k][0], p[h][k][1]), fmaxf(p[h][k][2], p[h][k][3]));
        }
    }
#pragma unroll
    for (int o = 1; o <= 2; o <<= 1)
#pragma unroll
        for (int h = 0; h < 4; h++)
#pragma unroll
            for (int k = 0; k < 2; k++) mx[h][k] = fmaxf(mx[h][k], __shfl_xor_sync(~0u, mx[h][k], o));
    const float L = 1.4426950408889634f;
    float pmin = 1.f;
#pragma unroll
    for (int h = 0; h < 4; h++)
#pragma unroll
        for (int k = 0; k < 2; k++) {
            const float m = -mx[h][k] * L;
            const float e0 = ex2(fmaf(p[h][k][0], L, m)), e1 = ex2(fmaf(p[h][k][1], L, m)), e2 = ex2(fmaf(p[h][k][2], L, m)), e3 = ex2(fmaf(p[h][k][3], L, m));
            const float p01 = e0 * e1, p23 = e2 * e3, pp = p01 * p23, r = rcp(pp), r01 = r * p23, r23 = r * p01;
            pmin = fminf(pmin, pp);
            out[h][k] = pack2(e0, e1); out[h][k + 2] = pack2(e2, e3);
            out[h][4 + k] = pack2(r01 * e1, r01 * e0); out[h][4 + k + 2] = pack2(r23 * e3, r23 * e2);
        }
    if (__builtin_expect(__any_sync(~0u, !(pmin > 1e-18f)), 0)) {
#pragma unroll
        for (int h = 0; h < 4; h++)
#pragma unroll
            for (int k = 0; k < 2; k++) {
                float m = fminf(fminf(p[h][k][0], p[h][k][1]), fminf(p[h][k][2], p[h][k][3]));
                m = fminf(m, __shfl_xor_sync(~0u, m, 1));
                m = fminf(m, __shfl_xor_sync(~0u, m, 2)) * L;
                out[h][4 + k] = pack2(ex2(fmaf(p[h][k][0], -L, m)), ex2(fmaf(p[h][k][1], -L, m)));
                out[h][4 + k + 2] = pack2(ex2(fmaf(p[h][k][2], -L, m)), ex2(fmaf(p[h][k][3], -L, m)));
            }
    }
}

__global__ void __launch_bounds__(512, 1)
fused_kernel(Scratch* __restrict__ scr, const bf16* __restrict__ logA, const bf16* __restrict__ Aim, const bf16* __restrict__ Cre,
             const bf16* __restrict__ Cim, const bf16* __restrict__ logdt, const bf16* __restrict__ Dskip, const bf16* __restrict__ wphi,
             const bf16* __restrict__ gatew, bf16* __restrict__ out,
             const __grid_constant__ CUtensorMap mx, const __grid_constant__ CUtensorMap mw, const __grid_constant__ CUtensorMap mwo) {
    extern __shared__ __align__(1024) uint8_t smem[];
    const uint32_t sb = s2u(smem);
    const int tid = threadIdx.x, warp = __shfl_sync(~0u, tid >> 5, 0), lane = tid & 31;
    const int g = lane >> 2, q = lane & 3, w4 = warp & 3;
    const int bi = blockIdx.x, bi_i = bi & 15, bi_j = bi >> 4;
    const uint32_t bar = sb + OFF_BAR;
    const int rot = (bi_j & 3) * 2, xkb = bi_j >> 2;
    auto load_stage = [&](int kb) {
        const uint32_t b = bar + 8 * (BAR_FULL + (kb & 3)), d = sb + (kb & 3) * SLOT;
        const int kc = ((kb + rot) & 7) * 64;
        mbar_expect(b, SLOT);
        tma2d(d, &mx, kc, bi_i * 128, b);
        tma3d(d + 16384, &mw, bi_j * 64, kc, 0, b);
    };

    const int ch = bi * 4 + w4;
    const int pidx = ch * 64 + lane * 2 + (warp >> 3);
    const uint32_t pla = ld_nc((const uint32_t*)logA + pidx), pai = ld_nc((const uint32_t*)Aim + pidx);
    const uint32_t pcr = ld_nc((const uint32_t*)Cre + pidx), pci = ld_nc((const uint32_t*)Cim + pidx);
    uint32_t pdt = ld_nc((const uint32_t*)logdt + (ch >> 1));
    const uint32_t pds = ld_nc((const uint32_t*)Dskip + (ch >> 1));
    unsigned done0 = ld_rlx(scr->done);
    if (tid == 0) {
        for (int s = 0; s < 4; s++) mbar_init(bar + 8 * (BAR_FULL + s), 1);
        asm volatile("fence.mbarrier_init.release.cluster;" ::: "memory");
        load_stage(0); load_stage(1);
        STAMP(11);
    } else if (tid == 32) {
        if (sb & 1023) __trap();
        sts32(bar + OFF_CNT, 0);
        for (int s = 0; s < 4; s++) mbar_init(bar + 8 * (BAR_EMPTY + s), 9);
        mbar_init(bar + 8 * BAR_WPHI, 1); mbar_init(bar + 8 * BAR_WO, 2); mbar_init(bar + 8 * BAR_WO2, 1); mbar_init(bar + 8 * BAR_XT, 4);
        mbar_init(bar + 8 * BAR_DONE, 9); mbar_init(bar + 8 * BAR_KG, 8); mbar_init(bar + 8 * BAR_SP, 1); mbar_init(bar + 8 * BAR_PUB, 8);
        mbar_init(bar + 8 * BAR_KVF, 4); mbar_init(bar + 8 * BAR_UR, 4); mbar_init(bar + 8 * BAR_WR, 4); mbar_init(bar + 8 * BAR_PREP, 4); mbar_init(bar + 8 * BAR_KGA, 4); mbar_init(bar + 8 * BAR_SP2, 1);
        asm volatile("fence.mbarrier_init.release.cluster;" ::: "memory");
        mbar_expect(bar + 8 * BAR_WPHI, 3072);
        bulk_g2s(sb + OFF_GW, gatew, 1024, bar + 8 * BAR_WPHI);
        bulk_g2s(sb + OFF_WPHI, wphi + bi_j * 1024, 2048, bar + 8 * BAR_WPHI);
    } else if (tid == 64) {
        asm volatile("prefetch.tensormap [%0];" ::"l"(&mw) : "memory");
    }
    const uint32_t buf = sb + OFF_BUF + w4 * BUF_STRIDE, kb_ = sb + OFF_K + w4 * KT_BYTES;
    if ((warp >> 2) == 2) {
#pragma unroll
        for (int v = 0; v < 7; v++) if (v * 32 + lane < KT_BYTES / 16) sts128(kb_ + (v * 32 + lane) * 16, 0, 0, 0, 0);
    }
    __syncthreads();
    asm volatile("" : "+r"(pdt), "+r"(done0)::"memory");
    const unsigned epoch1 = (done0 >> 7) + 1u;
    const uint32_t tag = epoch1 & 1u;

    const int st = tid & 127;
    const uint32_t ub = sb + OFF_U + w4 * U_STRIDE + 256, spare = sb + (w4 < 2 ? OFF_SP0 : OFF_SP1) + (w4 & 1) * 4096;

    auto stg_of = [&](int w) { return w < 8 ? sb + 3 * SLOT + w * 7296 : sb + 2 * SLOT + (w & 3) * 7296; };
    float kc[24];
#pragma unroll
    for (int t = 0; t < 24; t++) kc[t] = 0.f;
    {
        const float dt = bf_round(expf((ch & 1) ? bf_hi(pdt) : bf_lo(pdt)));
        const uint32_t stg = (warp >> 2) == 2 ? buf : stg_of(warp);
        const int sh = ((warp >> 2) & 1) * 16;
        auto pick = [&](uint32_t v) { return __uint_as_float((v >> sh) << 16); };
        const float ea = bf_round(expf(pick(pla)));
        const float arl = (-ea * dt) * 1.4426950408889634f, ait = (pick(pai) * dt) * 0.15915494309189535f;
        cf C2; C2.re = 2.0f * (pick(pcr) * dt); C2.im = 2.0f * (pick(pci) * dt);
        const cf z1 = cexp_p(arl, ait, 1.0f), z128 = cexp_p(arl, ait, 128.0f);
        cf z8 = cexp_p(arl, ait, 8.0f); z8.im = -z8.im;
        const uint32_t lp = stg + lane * 4;
        auto put = [&](int row, const cf& v) { sts32((lp ^ ((row & 7) << 4)) + row * 128, pack2(v.re, v.im)); };
        {
            const cf z16 = cmul(z8, z8);
            cf e; e.re = 1.f; e.im = 0.f;
            cf o = z8;
            put(0, e); put(1, o);
            e = z16; put(2, e);
#pragma unroll
            for (int b = 3; b < 16; b += 2) {
                o = cmul(o, z16); put(b, o);
                if (b + 1 < 16) { e = cmul(e, z16); put(b + 1, e); }
            }
        }
        cf h[8];
        h[0] = C2; put(16, h[0]);
        {
            const cf z2 = cmul(z1, z1);
            h[1] = cmul(h[0], z1);
#pragma unroll
            for (int r = 2; r < 8; r++) h[r] = cmul(h[r - 2], z2);
#pragma unroll
            for (int r = 1; r < 8; r++) put(16 + r, h[r]);
        }
#pragma unroll
        for (int r = 0; r < 8; r++) { h[r] = cmul(h[r], z128); put(24 + r, h[r]); }
#pragma unroll
        for (int al = 0; al < 2; al++)
#pragma unroll
            for (int r = 0; r < 4; r++) { h[2 * r] = cmul(h[2 * r], z128); put(32 + al * 4 + r, h[2 * r]); }
#pragma unroll
        for (int al = 0; al < 4; al++)
#pragma unroll
            for (int r = 0; r < 2; r++) { h[4 * r] = cmul(h[4 * r], z128); put(40 + al * 2 + r, h[4 * r]); }
#pragma unroll
        for (int al = 0; al < 9; al++) { h[0] = cmul(h[0], z128); put(48 + al, h[0]); }
        __syncwarp();
        const int lr = lane & 7, lm = lane >> 3;
#pragma unroll
        for (int kp = 0; kp < 2; kp++) {
            uint32_t a0[4], a1[4];
            ldsm4(a0, stg + ((lm & 1) * 8 + lr) * 128 + (((4 * kp + (lm >> 1)) ^ lr) << 4));
            ldsm4(a1, stg + ((lm & 1) * 8 + lr) * 128 + (((4 * kp + 2 + (lm >> 1)) ^ lr) << 4));
#pragma unroll
            for (int t = 0; t < 6; t++) {
                uint32_t b[4];
                ldsm4(b, stg + (16 + 8 * t + lr) * 128 + (((4 * kp + lm) ^ lr) << 4));
                mma16816(kc + 4 * t, a0[0], a0[1], a0[2], a0[3], b[0], b[1]);
                mma16816(kc + 4 * t, a1[0], a1[1], a1[2], a1[3], b[2], b[3]);
            }
        }
        __syncwarp();
        if ((warp >> 2) != 2) {
#pragma unroll
            for (int t = 0; t < 6; t++)
                sts128(stg + (t * 32 + lane) * 16, __float_as_uint(kc[4 * t]), __float_as_uint(kc[4 * t + 1]), __float_as_uint(kc[4 * t + 2]), __float_as_uint(kc[4 * t + 3]));
            asm volatile("fence.proxy.async.shared::cta;" ::: "memory");
            __syncwarp();
            if (lane == 0) mbar_arrive(bar + 8 * (warp < 8 ? BAR_KG : BAR_KGA));
        }
    }

    if (warp < 8) {
        asm volatile("setmaxnreg.inc.sync.aligned.u32 160;");
        const int wg = warp >> 2;
        if (warp == 0) STAMP(21);
        float acc[96];
        const int srow = warp * 16 + (lane & 15);
        const uint32_t srow_a = srow * 128;
        const int sx = srow & 7, shi = lane >> 4;
#pragma unroll
        for (int r = 0; r < 96; r++) acc[r] = 0.f;
        fence_regs<96>(acc);
        const uint64_t da0 = mkdesc(sb + wg * 8192, 16, 1024), db0 = mkdesc(sb + 16384, 8192, 1024);
#pragma unroll 1
        for (int kb = 0; kb < 8; kb++) {
            const int s = kb & 3;
            const uint64_t da = da0 + s * (SLOT >> 4), db = db0 + s * (SLOT >> 4);
            if (warp == 0) STAMP(40 + kb);
            mbar_wait(bar + 8 * (BAR_FULL + s), kb >> 2);
            if (warp == 0) STAMP(32 + kb);
            wg_fence();
#pragma unroll
            for (int k = 0; k < 4; k++) wgmma192(acc, da + 2 * k, db + 128 * k);
            wg_commit();
            wg_wait<1>();
            if (lane == 0 && kb > 0) mbar_arrive(bar + 8 * (BAR_EMPTY + ((kb - 1) & 3)));
        }
        mbar_wait(bar + 8 * BAR_WPHI, 0);
        wg_wait<0>();
        fence_regs<96>(acc);
        if (lane == 0) mbar_arrive(bar + 8 * BAR_DONE);
        if (warp == 0) STAMP(1);
        uint32_t in[16], qa[16];
        mbar_wait(bar + 8 * BAR_DONE, 0);
#pragma unroll
        for (int r = 0; r < 16; r++) {
            in[r] = pack2(acc[32 + 2 * r], acc[32 + 2 * r + 1]);
            qa[r] = pack2(acc[2 * r], acc[2 * r + 1]);
        }
#pragma unroll
        for (int hh = 0; hh < 4; hh++)
            stsm4(sb + OFF_V + (hh >> 1) * 16384 + srow_a + (((2 * (hh & 1) + shi) ^ sx) << 4), pack2(acc[64 + 8 * hh], acc[65 + 8 * hh]),
                  pack2(acc[66 + 8 * hh], acc[67 + 8 * hh]), pack2(acc[68 + 8 * hh], acc[69 + 8 * hh]), pack2(acc[70 + 8 * hh], acc[71 + 8 * hh]));
        sts128(sb + OFF_V + shi * 16384 + srow_a + ((4 ^ sx) << 4), 0x3f803f80u, 0x3f803f80u, 0x3f803f80u, 0x3f803f80u);
        const uint32_t wphi_a = sb + OFF_WPHI + (lane & 15) * 32 + (lane >> 4) * 16;
        uint32_t pq[4][8];
#pragma unroll 1
        for (int it = 0; it < 2; it++) {
            hedgehog4(in, wphi_a, pq);
            if (it == 1) break;
#pragma unroll
            for (int hs = 0; hs < 8; hs++) {
                float c[4] = {0.f, 0.f, 0.f, 0.f};
                const uint32_t* o = pq[hs >> 1] + 4 * (hs & 1);
                mma16816(c, o[0], o[1], o[2], o[3], 0x3f803f80u, 0x3f803f80u);
                const float r0 = rcp(c[0]), r1 = rcp(c[2]);
                const uint32_t s0 = pack2(r0, r0), s1 = pack2(r1, r1);
                stsm4(sb + OFF_P + (hs >> 2) * 16384 + srow_a + (((2 * (hs & 3) + shi) ^ sx) << 4), hmul2(o[0], s0), hmul2(o[1], s1), hmul2(o[2], s0), hmul2(o[3], s1));
            }
            asm volatile("fence.proxy.async.shared::cta;" ::: "memory");
            bar_named(1, 256);
            if (warp == 0) STAMP(2);
            float d[32];
            const uint64_t dv = mkdesc(sb + OFF_V + wg * 16384, 16, 1024), dp = mkdesc(sb + OFF_P + wg * 16384, 16, 1024);
            wg_fence();
#pragma unroll
            for (int k = 0; k < 8; k++) wgmma64_tt(d, dv + 128 * k, dp + 128 * k, k != 0);
            wg_commit();
            mbar_wait(bar + 8 * BAR_PREP, 0);
            uint4* kvp = scr->kvp + bi * 544 + wg * 272 + (w4 < 2 ? w4 * 136 : 128) + lane;
            wg_wait<0>();
            fence_regs<32>(d);
            if (w4 < 2 || (w4 == 2 && lane < 4)) {
#pragma unroll
                for (int f = 0; f < 4; f++) {
                    const int i0 = 8 * (f >> 1) + 2 * (f & 1), i2 = 16 * (f >> 1) + 8 * (f & 1);
                    const float e0 = w4 == 0 ? d[i0] : (w4 == 1 ? d[16 + i0] : d[i2]), e1 = w4 == 0 ? d[i0 + 1] : (w4 == 1 ? d[17 + i0] : d[i2 + 1]);
                    const float e2 = w4 == 0 ? d[i0 + 4] : (w4 == 1 ? d[20 + i0] : d[i2 + 4]), e3 = w4 == 0 ? d[i0 + 5] : (w4 == 1 ? d[21 + i0] : d[i2 + 5]);
                    st_rlx128(kvp + (w4 < 2 ? f * 32 : (f >> 1) * 136 + (f & 1) * 4), tag4(__float_as_uint(e0), __float_as_uint(e1), __float_as_uint(e2), __float_as_uint(e3), tag));
                }
            }
            __syncwarp();
            if (lane == 0) mbar_arrive(bar + 8 * BAR_PUB);
            if (warp == 0) STAMP(3);
#pragma unroll
            for (int r = 0; r < 16; r++) in[r] = qa[r];
        }
        if (warp == 0) STAMP(4);
        {
            mbar_wait(bar + 8 * BAR_KVF, 0);
            uint4 kf[4][3];
#pragma unroll
            for (int hh = 0; hh < 4; hh++) {
                const uint32_t a = sb + OFF_KVF + hh * 1088;
                kf[hh][0] = lds128(a + lane * 32); kf[hh][1] = lds128(a + lane * 32 + 16); kf[hh][2] = lds128(a + 1024 + q * 16);
            }
            if (warp == 0) STAMP(5);
            uint4* og = scr->o + ((bi_i * 8 + warp) * 32 + bi_j * 4) * 32 + lane;
#pragma unroll
            for (int hh = 0; hh < 4; hh++) {
                float c[6][4];
#pragma unroll
                for (int t = 0; t < 6; t++) { c[t][0] = c[t][1] = c[t][2] = c[t][3] = 0.f; }
                const uint32_t* a = pq[hh];
                const bool od = g & 1;
                mma16816(c[0], a[0], a[1], a[2], a[3], od ? 0x3f803f80u : kf[hh][2].x, od ? 0x3f803f80u : kf[hh][2].y);
                mma16816(c[1], a[4], a[5], a[6], a[7], od ? 0x3f803f80u : kf[hh][2].z, od ? 0x3f803f80u : kf[hh][2].w);
                mma16816(c[2], a[0], a[1], a[2], a[3], kf[hh][0].x, kf[hh][0].y);
                mma16816(c[3], a[0], a[1], a[2], a[3], kf[hh][0].z, kf[hh][0].w);
                mma16816(c[4], a[4], a[5], a[6], a[7], kf[hh][1].x, kf[hh][1].y);
                mma16816(c[5], a[4], a[5], a[6], a[7], kf[hh][1].z, kf[hh][1].w);
                uint32_t w[4];
#pragma unroll
                for (int k = 0; k < 2; k++) {
                    const float rho = c[0][2 * k + 1] * rcp(c[1][2 * k + 1]);
                    const float r = rcp(fmaf(c[0][2 * k + 1], 1e-6f, fmaf(rho, c[1][2 * k], c[0][2 * k]))), rr = r * rho;
                    w[k] = pack2(fmaf(c[4][2 * k], rr, c[2][2 * k] * r), fmaf(c[4][2 * k + 1], rr, c[2][2 * k + 1] * r));
                    w[2 + k] = pack2(fmaf(c[5][2 * k], rr, c[3][2 * k] * r), fmaf(c[5][2 * k + 1], rr, c[3][2 * k + 1] * r));
                }
                st_rlx128(og + hh * 32, tag4(w[0], w[1], w[2], w[3], tag));
            }
        }
        if (warp == 0) STAMP(6);
        float oc[64];
        const int slab = bi_i * 8 + (bi_j >> 2) * 4 + w4;
        const uint8_t* yb = (const uint8_t*)scr->y + (size_t)((bi_j & 3) * 32 + wg * 16 + (q >> 1)) * 16384 + slab * 128 + g * 16 + (q & 1) * 8;
        const unsigned* gp = scr->g + (slab * 8 + (g >> 1)) * 8 + (g & 1) * 4;
        uint2 yv[8]; unsigned g0, g1;
        {
            const uint4* osrc = scr->o + (slab * 32 + wg * 16) * 32 + lane;
            uint4 fr[16];
            const unsigned* probe = (const unsigned*)(osrc - lane + ((lane & 3) * 4 + 3) * 32 + 31) + 2;
            {
                unsigned miss = ~0u;
                int n = 0;
#pragma unroll
                for (int s = 0; s < 4; s++) {
#pragma unroll 1
                    while ((miss >> s) & 1) { miss = __ballot_sync(~0u, (ld_rlx(probe) ^ tag) & 1); if (++n > SPIN_LIMIT) break; }
#pragma unroll
                    for (int k = 4 * s; k < 4 * s + 4; k++) fr[k] = ld_rlx128(osrc + k * 32);
                }
            }
            if (warp == 0) STAMP(14);
            mbar_wait(bar + 8 * (wg ? BAR_WO2 : BAR_WO), 0);
            const uint64_t dw = mkdesc(sb + wg * 2 * SLOT, wg ? 32768 : SLOT, 1024);
#pragma unroll
            for (int s = 0; s < 4; s++) {
                int n = 0;
#pragma unroll 1
                while (__builtin_expect(__any_sync(~0u, (bad4(fr[4 * s], tag) | bad4(fr[4 * s + 1], tag) | bad4(fr[4 * s + 2], tag) | bad4(fr[4 * s + 3], tag)) & 1), 0)) {
#pragma unroll
                    for (int k = 4 * s; k < 4 * s + 4; k++) fr[k] = ld_rlx128(osrc + k * 32);
                    if (++n > SPIN_LIMIT) break;
                }
                wg_fence();
#pragma unroll
                for (int hh = 0; hh < 4; hh++) wgmma128_rs(oc, fr[4 * s + hh], dw + 128 * (4 * s + hh), (s | hh) != 0);
                wg_commit();
                if (s == 1) {
                    wg_wait<1>();
#pragma unroll
                    for (int nt = 0; nt < 8; nt++) yv[nt] = ld_rlx64(yb + nt * 32768);
                    g0 = ld_rlx(gp); g1 = ld_rlx(gp + 32);
                }
            }
            if (warp == 0) STAMP(7);
            {
                const unsigned* yprobe = scr->yflag + ((bi_j & 3) * 32 + wg * 16 + (lane & 15)) * 8;
                int n = 0;
#pragma unroll 1
                while (true) {
                    uint32_t bad = (g0 ^ tag) | (g1 ^ tag);
#pragma unroll
                    for (int nt = 0; nt < 8; nt++) bad |= yv[nt].x ^ tag;
                    if (!__any_sync(~0u, bad & 1)) break;
#pragma unroll 1
                    while (__any_sync(~0u, (ld_rlx(yprobe) ^ tag) & 1)) { if (++n > SPIN_LIMIT) break; }
#pragma unroll
                    for (int nt = 0; nt < 8; nt++) yv[nt] = ld_rlx64(yb + nt * 32768);
                    g0 = ld_rlx(gp); g1 = ld_rlx(gp + 32);
                    if (++n > SPIN_LIMIT) break;
                }
            }
            if (warp == 0) STAMP(28);
            wg_wait<0>();
            fence_regs<64>(oc);
        }
        {
            bar_named(3 + wg, 128);
            const uint32_t xw = sb + wg * 2 * SLOT + (tid & 127) * 16, xr = sb + (wg ^ 1) * 2 * SLOT + (tid & 127) * 16;
#pragma unroll
            for (int r = 0; r < 8; r++) {
                const float* o = oc + 4 * r;
                sts128(xw + r * 2048, __float_as_uint(wg ? o[0] : o[32]), __float_as_uint(wg ? o[1] : o[33]), __float_as_uint(wg ? o[2] : o[34]), __float_as_uint(wg ? o[3] : o[35]));
            }
#pragma unroll
            for (int r = 0; r < 32; r++) oc[r] = wg ? oc[32 + r] : oc[r];
            bar_named(1, 256);
            if (warp == 0) STAMP(8);
            const float ga = bf_hi(g0), gb = bf_hi(g1);
            const float ha = bf_round(1.0f - ga), hb = bf_round(1.0f - gb);
            uint32_t w[8][2];
#pragma unroll
            for (int nt = 0; nt < 8; nt++) {
                const uint4 p = lds128(xr + nt * 2048);
                w[nt][0] = pack2(fmaf(ga, oc[4 * nt] + __uint_as_float(p.x), ha * bf_lo(yv[nt].x)), fmaf(ga, oc[4 * nt + 1] + __uint_as_float(p.y), ha * bf_hi(yv[nt].x)));
                w[nt][1] = pack2(fmaf(gb, oc[4 * nt + 2] + __uint_as_float(p.z), hb * bf_lo(yv[nt].y)), fmaf(gb, oc[4 * nt + 3] + __uint_as_float(p.w), hb * bf_hi(yv[nt].y)));
            }
            const uint32_t ob = sb + wg * 2 * SLOT + 16384 + w4 * 2048;
#pragma unroll
            for (int nt = 0; nt < 8; nt += 2)
                stsm4(ob + (lane & 15) * 128 + (((nt + shi) ^ (lane & 7)) << 4), w[nt][0], w[nt][1], w[nt + 1][0], w[nt + 1][1]);
            __syncwarp();
            bf16* op = out + (size_t)(slab * 16) * 512 + (bi_j & 3) * 128 + wg * 64 + (lane & 7) * 8;
#pragma unroll
            for (int it = 0; it < 4; it++) {
                const int r = it * 4 + (lane >> 3);
                uint4 v = lds128(ob + r * 128 + (((lane & 7) ^ (r & 7)) << 4));
                *(uint4*)(op + r * 512) = v;
            }
        }
        if (warp == 0) STAMP(10);
    } else if (warp < 12) {
#pragma unroll
        for (int src = 2; src >= 0; src--) {
            if (src != 0) mbar_wait(bar + 8 * (src == 2 ? BAR_KGA : BAR_KG), 0);
#pragma unroll
            for (int t = 0; t < 6; t++) {
                const uint4 v = lds128(stg_of(w4 + src * 4) + (t * 32 + lane) * 16);
                kc[4 * t] += __uint_as_float(v.x); kc[4 * t + 1] += __uint_as_float(v.y); kc[4 * t + 2] += __uint_as_float(v.z); kc[4 * t + 3] += __uint_as_float(v.w);
            }
            if (src != 1) {
                bar_named(2, 128);
                if (st == 0) { load_stage(src == 2 ? 2 : 3); if (src == 0) mbar_arrive(bar + 8 * BAR_SP); }
                if (warp == 8) STAMP(src == 2 ? 22 : 17);
            }
        }
        if (warp == 8) {
#pragma unroll 1
            for (int kb = 0; kb < 6; kb++) {
                const int s = kb & 3;
                mbar_wait(bar + 8 * (BAR_EMPTY + s), kb >> 2);
                if (kb == xkb) mbar_wait(bar + 8 * BAR_XT, 0);
                if (lane == 0) {
                    STAMP(48 + kb);
                    if (kb < 4) load_stage(kb + 4);
                    else {
                        mbar_expect(bar + 8 * BAR_WO, 32768);
                        tma2d(sb + s * SLOT, &mwo, (bi_j & 3) * 128 + s * 64, 0, bar + 8 * BAR_WO);
                        if (kb == 5) mbar_arrive(bar + 8 * BAR_SP2);
                    }
                }
                __syncwarp();
            }
        } else if (warp == 9) {
            const int row = bi_j * 16 + (lane >> 1), half = lane & 1;
            unsigned* gp = scr->g + (bi_i * 64 + bi_j * 8) * 8 + lane * 2;
            st_rlx64(gp, tag ^ 1u, tag ^ 1u);
            if (lane < 8) st_rlx32(scr->yflag + bi * 8 + lane, tag ^ 1u);
            float gs0 = 0.f, gs1 = 0.f;
            mbar_wait(bar + 8 * BAR_WPHI, 0);
#pragma unroll 1
            for (int kb = 0; kb < 8; kb++) {
                const int s = kb & 3;
                mbar_wait(bar + 8 * (BAR_FULL + s), kb >> 2);
#pragma unroll
                for (int c = 0; c < 4; c++) {
                    const uint4 xv = lds128(sb + s * SLOT + row * 128 + (((half * 4 + c) ^ (row & 7)) << 4));
                    const uint4 gw = lds128(sb + OFF_GW + ((kb + rot) & 7) * 128 + half * 64 + c * 16);
                    const uint32_t p0 = hmul2(xv.x, gw.x), p1 = hmul2(xv.y, gw.y), p2 = hmul2(xv.z, gw.z), p3 = hmul2(xv.w, gw.w);
                    gs0 += (bf_lo(p0) + bf_lo(p1)) + (bf_lo(p2) + bf_lo(p3));
                    gs1 += (bf_hi(p0) + bf_hi(p1)) + (bf_hi(p2) + bf_hi(p3));
                }
                asm volatile("" : "+f"(gs0), "+f"(gs1));
                __syncwarp();
                if (lane == 0) mbar_arrive(bar + 8 * (kb < 7 ? BAR_EMPTY + s : BAR_DONE));
            }
            float gs = gs0 + gs1;
            gs += __shfl_xor_sync(~0u, gs, 1);
            const uint32_t gv = __float_as_uint(bf_round(rcp(1.0f + ex2(-1.4426950408889634f * bf_round(gs))))) | tag;
            st_rlx64(gp, gv, gv);
        }
        if (lane == 0) kc[4 * 0 + 0] += ((ch & 1) ? bf_hi(pds) : bf_lo(pds));
        const uint32_t k1024 = __shfl_sync(~0u, pack2(kc[4 * 4 + 0], 0.f), 0);
#pragma unroll
        for (int i = 0; i < 2; i++) {
            const int be = g + 8 * i;
#pragma unroll
            for (int t = 0; t < 2; t++) {
                const uint32_t a = kb_ + (KW_D + 128 * t + 8 * be + 2 * q) * 4;
                const uint32_t w = pack2(kc[4 * t + 2 * i + 1], kc[4 * t + 2 * i]);
                sts32(a + 4, w); sts16(a, w >> 16); sts16(a + 10, w);
            }
            {
                const int p = 256 + 128 * (q >> 1) + 8 * be + 4 * (q & 1);
                const uint32_t a = kb_ + (KW_D + p) * 4;
                const uint32_t w = pack2(kc[4 * 2 + 2 * i + 1], kc[4 * 2 + 2 * i]);
                const uint32_t aa = (w >> 16) | (w & 0xffff0000u);
                if (p != 256) { sts16(a - 4, aa); sts32(a, aa); } else sts16(a, aa);
                sts32(a + 4, aa); sts32(a + 8, w); sts16(a + 14, w);
            }
            {
                const int k = 64 + 16 * q + be;
                const uint32_t w = pack2(kc[4 * 3 + 2 * i], kc[4 * 3 + 2 * i + 1]);
                if (k != 64) sts16(kb_ + (KW_2 + ((k - 1) >> 1) - 24) * 4 + (k & 1) * 2, w);
                else {
                    const uint32_t a = kb_ + (KW_D + 511) * 4, aa = (w << 16) | (w & 0xffffu);
                    sts16(a, w); sts32(a + 4, aa); sts32(a + 8, aa); sts32(a + 12, aa); sts16(a + 18, w);
                }
                sts16(kb_ + (KW_2 + 48 + (k >> 1) - 24) * 4 + ((k & 1) ^ 1) * 2, w >> 16);
            }
#pragma unroll
            for (int b = 0; b < 2; b++) {
                const int k = 64 + 8 * (2 * q + b) + (be >> 1);
                const uint32_t w = pack2(kc[4 * 4 + 2 * i + b], 0.f);
                if (!(be & 1) && k == 64) sts16(kb_ + (KW_2 + 63 - 24) * 4, w);
                else {
                    const uint32_t a = kb_ + (KW_3 + ((be & 1) ? 80 + k : k - 1) - 48) * 4;
                    sts16(a, w);
                    if (!((be & 1) && k == 127)) sts16(a + 6, w);
                }
            }
        }
        if (lane == 0) sts16(kb_ + (KW_3 + 127 - 48) * 4, pack2(kc[4 * 5 + 0], 0.f));
        __syncwarp();
        mbar_wait(bar + 8 * BAR_UR, 0);
        mbar_wait(bar + 8 * CONV_START, 0);
        if (warp == 8) STAMP(23);
        float y[16][4];
#pragma unroll
        for (int nt = 0; nt < 16; nt++) { y[nt][0] = y[nt][1] = y[nt][2] = y[nt][3] = 0.f; }
        {
            uint32_t Bp[32], A[4][3], An[4][3];
            auto uaddr = [&](int rho) { const int R0 = (lane >> 4) * 64 + (lane & 7) - rho; return ub + (((2 * R0 + ((lane >> 3) & 1)) ^ ((R0 >> 2) & 1)) << 4); };
            const uint32_t kd = kb_ + (KW_D + g - 2 * q) * 4;
#pragma unroll 1
            for (int rho = 1; rho >= 0; rho--) {
                const uint32_t a = uaddr(rho), k = kd + 2048 + rho * 64;
#pragma unroll
                for (int i = 0; i < 8; i++) ldsm4(Bp + 4 * i, a + i * 256);
                const uint32_t a0 = lds32(k), a1 = lds32(k + 32), a2 = lds32(k - 32);
#pragma unroll
                for (int i = 0; i < 12; i++) mma16816(y[i + 4], a0, a1, a2, a0, Bp[4 * (i & 7) + 2 * (i >> 3)], Bp[4 * (i & 7) + 2 * (i >> 3) + 1]);
            }
#pragma unroll
            for (int ga = 0; ga < 4; ga++) { An[ga][0] = lds32(kd + ga * 512); An[ga][1] = lds32(kd + ga * 512 + 32); An[ga][2] = lds32(kd + ga * 512 - 32); }
#pragma unroll 1
            for (int rho = 0; rho < 8; rho++) {
#pragma unroll
                for (int ga = 0; ga < 4; ga++) {
                    const uint32_t a = kd + (rho + 1) * 64 + ga * 512;
                    A[ga][0] = An[ga][0]; A[ga][1] = An[ga][1]; A[ga][2] = An[ga][2];
                    An[ga][0] = lds32(a); An[ga][1] = lds32(a + 32); An[ga][2] = lds32(a - 32);
                }
                const uint32_t an = uaddr(rho + 1);
#pragma unroll
                for (int i = 0; i < 8; i++) {
#pragma unroll
                    for (int ga = 0; ga < 4; ga++) {
                        mma16816(y[i + ga], A[ga][0], A[ga][1], A[ga][2], A[ga][0], Bp[4 * i], Bp[4 * i + 1]);
                        if (i + 8 + ga < 16) mma16816(y[i + 8 + ga], A[ga][0], A[ga][1], A[ga][2], A[ga][0], Bp[4 * i + 2], Bp[4 * i + 3]);
                    }
                    ldsm4(Bp + 4 * i, an + i * 256);
                    __syncwarp();
                }
            }
        }
        if (warp == 8) STAMP(18);
        mbar_wait(bar + 8 * BAR_WR, 0);
#pragma unroll 1
        for (int ph = 0; ph < 2; ph++) {
            uint32_t B[5][2];
            const uint32_t ka = kb_ + (KW_2 + ph * 48 + 8 + g - q) * 4;
#pragma unroll
            for (int dd = 0; dd < 5; dd++) { B[dd][0] = lds32(ka + dd * 32); B[dd][1] = lds32(ka + dd * 32 - 16); }
            const uint32_t wa = buf + ph * W3_OFF + ((lane & 7) + ((lane >> 3) & 1) + (lane >> 4) * 8) * 16;
#pragma unroll
            for (int s = 0; s < 12; s++) {
                uint32_t A[4];
                ldsm4t(A, wa + s * 256);
#pragma unroll
                for (int dd = 0; dd < 5; dd++)
                    if (s + 4 + dd < 16) mma16816(y[s + 4 + dd], A[0], A[1], A[2], A[3], B[dd][0], B[dd][1]);
            }
        }
        {
            const int ap = (lane & 7) + (lane >> 4) * 8;
            const uint32_t loff = ((2 * ap + ((lane >> 3) & 1)) ^ ((ap >> 2) & 1)) << 4;
#pragma unroll 1
            for (int ph = 0; ph < 2; ph++) {
                uint32_t B[8][2];
                const uint32_t wb = (ph ? spare : buf + W9_OFF) + loff;
                const uint32_t ka = kb_ + (KW_3 + ph * 80 + 16 + g - 2 * q) * 4;
#pragma unroll
                for (int dd = 0; dd < 8; dd++) { B[dd][0] = lds32(ka + dd * 32); B[dd][1] = lds32(ka + dd * 32 - 32); }
#pragma unroll
                for (int s = 0; s < 4; s++) {
                    uint32_t A[4];
                    ldsm4t(A, wb + s * 512);
#pragma unroll
                    for (int dd = 0; dd < 8; dd++)
                        if (8 + 2 * s + dd < 16) mma16816(y[8 + 2 * s + dd], A[0], A[1], A[2], A[3], B[dd][0], B[dd][1]);
                }
            }
            const uint32_t idw = (g == 2 * q) ? k1024 : ((g == 2 * q + 1) ? (k1024 << 16) : 0u);
#pragma unroll
            for (int s = 0; s < 4; s++) {
                uint32_t A[4];
                ldsm4t(A, spare + 2048 + loff + s * 512);
                mma16816(y[8 + 2 * s], A[0], A[1], A[2], A[3], idw, 0u);
                mma16816(y[9 + 2 * s], A[0], A[1], A[2], A[3], 0u, idw);
            }
        }
        __syncwarp();
        if (warp == 8) STAMP(19);
#pragma unroll
        for (int nt = 0; nt < 16; nt++)
#pragma unroll
            for (int b = 0; b < 2; b++) sts32(buf + ((8 * nt + 2 * q + b) * 8 + g) * 4, pack2(y[nt][b], y[nt][2 + b]));
        bar_named(2, 128);
        uint4* yp = scr->y + bi * 1024 + st;
#pragma unroll
        for (int v = 0; v < 8; v++) {
            const uint32_t a = sb + OFF_BUF + (st + 128 * v) * 4;
            const uint32_t w0 = lds32(a), w1 = lds32(a + BUF_STRIDE), w2 = lds32(a + 2 * BUF_STRIDE), w3 = lds32(a + 3 * BUF_STRIDE);
            st_rlx128(yp + v * 128, tag4(__byte_perm(w0, w1, 0x5410), __byte_perm(w0, w1, 0x7632), __byte_perm(w2, w3, 0x5410), __byte_perm(w2, w3, 0x7632), tag));
        }
        if (st < 8) st_rlx32(scr->yflag + bi * 8 + st, tag);
        if (warp == 8) STAMP(20);
    } else {
        asm volatile("setmaxnreg.dec.sync.aligned.u32 64;");
        const int qq = (bi_i & 2) + ((lane >> 1) & 1);
        uint2* kvf_h = (uint2*)(scr->kvf + (bi_j * 4 + (bi_i >> 2)) * 68);
        auto windows = [&](int rhi, int rlo) {
#pragma unroll 1
            for (int rho = rhi; rho >= rlo; rho--) {
                const int ci = lane + 32 * rho;
                uint4 e4[4];
#pragma unroll
                for (int v = 0; v < 4; v++) { const int cc = ci - 3 + v; e4[v] = lds128(ub + ((cc ^ ((cc >> 3) & 1)) << 4)); }
                float S[29];
                const uint32_t* ew = (const uint32_t*)e4;
                S[3] = 0.f;
#pragma unroll
                for (int k = 4; k <= 28; k++) S[k] = S[k - 1] + ((k & 1) ? bf_hi(ew[k >> 1]) : bf_lo(ew[k >> 1]));
                auto win = [&](int lo, int hi, uint32_t a) {
                    sts128(a, pack2(S[hi] - S[lo - 1], S[hi + 1] - S[lo]), pack2(S[hi + 2] - S[lo + 1], S[hi + 3] - S[lo + 2]),
                           pack2(S[hi + 4] - S[lo + 3], S[hi + 5] - S[lo + 4]), pack2(S[hi + 6] - S[lo + 5], S[hi + 7] - S[lo + 6]));
                };
                win(14, 18, buf + W5_OFF + 16 + ci * 16); win(19, 21, buf + W3_OFF + 16 + ci * 16);
                if (rho < 4) {
                    const uint32_t sw = (ci ^ ((ci >> 3) & 1)) << 4;
                    win(4, 12, buf + W9_OFF + sw); win(13, 19, spare + sw); win(20, 21, spare + 2048 + sw);
                }
            }
        };
        {
            mbar_wait(bar + 8 * (BAR_FULL + xkb), 0);
#pragma unroll 1
            for (int hf = 0; hf < 2; hf++) {
                const int r = w4 * 32 + hf * 16 + (lane & 15);
                uint32_t* xt = (uint32_t*)scr->xt + ((xkb + rot) * 16 + (g >> 2)) * 4096 + (bi_i * 16 + w4 * 4 + hf * 2) * 16 + (g & 3) * 4 + q;
#pragma unroll
                for (int cb = 0; cb < 8; cb += 2) {
                    uint32_t v[4];
                    ldsm4t(v, sb + xkb * SLOT + r * 128 + (((cb + (lane >> 4)) ^ (r & 7)) << 4));
                    xt[cb * 8192] = v[0]; xt[cb * 8192 + 16] = v[1]; xt[cb * 8192 + 8192] = v[2]; xt[cb * 8192 + 8192 + 16] = v[3];
                }
            }
            __syncwarp();
            if (lane == 0) mbar_arrive(bar + 8 * BAR_XT);
            if (warp == 12) {
                STAMP(26);
                mbar_wait(bar + 8 * BAR_XT, 0);
                if (lane == 0) asm volatile("red.release.gpu.global.add.u32 [%0],8;" ::"l"(scr->xcnt + (xkb + rot) * 32) : "memory");
                __syncwarp();
                STAMP(27);
            }
            {
                const uint32_t old = tag ^ 1u;
                const uint4 z4 = make_uint4(old, 0, old, 0);
#pragma unroll
                for (int v = 0; v < 5; v++) if (v < 4 || st < 32) st_rlx128(scr->kvp + bi * 544 + v * 128 + st, z4);
                if (st < 16) st_rlx128(scr->o + ((bi_i * 8 + (st >> 1)) * 32 + bi_j * 4 + 3) * 32 + 30 + (st & 1), z4);
                if (lane < 8) st_rlx64(kvf_h + ((bi_i & 3) * 8 + w4 * 2 + (lane & 1)) * 4 + (lane >> 1), old, 0);
                if (st < 4 && !(bi_i & 1)) st_rlx64(kvf_h + (64 + qq) * 2 + (lane & 1), old, 0);
                __syncwarp();
                if (lane == 0) mbar_arrive(bar + 8 * BAR_PREP);
            }
            int n = 0;
#pragma unroll 1
            while (__any_sync(~0u, (int)(ld_acq(scr->xcnt + bi_j * 32) - (epoch1 << 7)) < 0)) { if (++n > SPIN_LIMIT) break; }
            if (warp == 12) STAMP(15);
            uint4 ur[8];
#pragma unroll
            for (int v = 0; v < 8; v++) ur[v] = __ldcg(scr->xt + bi * 1024 + st + 128 * v);
            mbar_wait(bar + 8 * BAR_SP, 0);
            if (lane < 16) sts128(ub - 256 + lane * 16, 0, 0, 0, 0);
            if (lane < 2) sts128(buf + lane * W3_OFF, 0, 0, 0, 0);
#pragma unroll
            for (int v = 0; v < 8; v++) {
                const int ci = (st >> 2) + 32 * v;
                sts128(sb + OFF_U + (st & 3) * U_STRIDE + 256 + ((ci ^ ((ci >> 3) & 1)) << 4), ur[v].x, ur[v].y, ur[v].z, ur[v].w);
            }
            __syncwarp();
            if (lane == 0) mbar_arrive(bar + 8 * BAR_UR);
            mbar_wait(bar + 8 * BAR_UR, 0);
            if (warp == 12) STAMP(16);
            windows(5, 4);
        }
        mbar_wait(bar + 8 * BAR_SP2, 0);
        windows(3, 0);
        __syncwarp();
        if (lane == 0) mbar_arrive(bar + 8 * BAR_WR);
        if (warp == 12) STAMP(24);
        {
            const bool zw = st < 32 && !(bi_i & 1);
            const uint4* src = scr->kvp + bi_j * (16 * 544) + (bi_i >> 2) * 136;
            const uint4* zsrc = src + (lane >> 2) * (2 * 544) + 128 + (lane & 1) * 4 + qq;
            src += (lane >> 3) * (4 * 544) + ((lane >> 1) & 3) * 32 + (bi_i & 3) * 8 + w4 * 2 + (lane & 1);
            mbar_wait(bar + 8 * BAR_PUB, 0);
            if (warp == 12) STAMP(12);
            __nanosleep(D1_NS);
            uint4 v[6];
#pragma unroll
            for (int k = 0; k < 6; k++) v[k] = make_uint4(tag ^ 1u, 0, 0, 0);
            int n = 0;
#pragma unroll 1
            while (true) {
#pragma unroll
                for (int k = 0; k < 6; k++) if ((bad4(v[k], tag) & 1) && (k < 4 || zw)) v[k] = ld_rlx128(k < 4 ? src + k * 544 : zsrc + (k - 4) * 544);
                if (!__any_sync(~0u, (bad4(v[0], tag) | bad4(v[1], tag) | bad4(v[2], tag) | bad4(v[3], tag) | (zw ? bad4(v[4], tag) | bad4(v[5], tag) : 0u)) & 1)) break;
                if (warp == 12 && n < 3) STAMP(54 + n);
                if (++n > SPIN_LIMIT) break;
                __nanosleep(POLL_NS);
            }
            if (warp == 12) STAMP(30);
            float f[8];
            const float* vf = (const float*)v;
#pragma unroll
            for (int r = 0; r < 4; r++) {
                f[r] = (vf[r] + vf[4 + r]) + (vf[8 + r] + vf[12 + r]);
                f[4 + r] = vf[16 + r] + vf[20 + r];
                f[4 + r] += __shfl_xor_sync(~0u, f[4 + r], 4);
            }
#pragma unroll
            for (int o = 8; o <= 16; o <<= 1)
#pragma unroll
                for (int r = 0; r < 8; r++) f[r] += __shfl_xor_sync(~0u, f[r], o);
            if (lane < 8) st_rlx64(kvf_h + ((bi_i & 3) * 8 + w4 * 2 + (lane & 1)) * 4 + (lane >> 1), tagw(pack2(f[0], f[1]), tag), pack2(f[2], f[3]));
            if (zw && lane < 4) st_rlx64(kvf_h + (64 + qq) * 2 + (lane & 1), tagw(pack2(f[4], f[5]), tag), pack2(f[6], f[7]));
        }
        if (warp == 12) STAMP(13);
        {
            const uint4* kp = scr->kvf + bi_j * 272 + st;
            __nanosleep(D2_NS);
            uint4 v0 = make_uint4(tag ^ 1u, 0, 0, 0), v1 = v0, v2 = make_uint4(st < 16 ? tag ^ 1u : tag, 0, tag, 0);
            int n = 0;
#pragma unroll 1
            while (true) {
                if (bad4(v0, tag) & 1) v0 = ld_rlx128(kp);
                if (bad4(v1, tag) & 1) v1 = ld_rlx128(kp + 128);
                if (bad4(v2, tag) & 1) v2 = ld_rlx128(kp + 256);
                if (!__any_sync(~0u, (bad4(v0, tag) | bad4(v1, tag) | bad4(v2, tag)) & 1)) break;
                if (++n > SPIN_LIMIT) break;
                __nanosleep(POLL_NS);
            }
            sts128(sb + OFF_KVF + st * 16, v0.x, v0.y, v0.z, v0.w);
            sts128(sb + OFF_KVF + 2048 + st * 16, v1.x, v1.y, v1.z, v1.w);
            if (st < 16) sts128(sb + OFF_KVF + 4096 + st * 16, v2.x, v2.y, v2.z, v2.w);
            __syncwarp();
            if (lane == 0) mbar_arrive(bar + 8 * BAR_KVF);
        }
        if (warp == 13) {
            mbar_wait(bar + 8 * BAR_KVF, 0);
            if (lane == 0) {
                mbar_expect(bar + 8 * BAR_WO2, 65536);
                tma2d(sb + OFF_P, &mwo, (bi_j & 3) * 128, 256, bar + 8 * BAR_WO2);
                tma2d(sb + OFF_V, &mwo, (bi_j & 3) * 128 + 64, 256, bar + 8 * BAR_WO2);
            }
        }
        if (warp == 12) STAMP(25);
    }
    __syncwarp();
    if (lane == 0) {
        unsigned old;
        asm volatile("atom.acq_rel.cta.shared.add.u32 %0,[%1],1;" : "=r"(old) : "r"(bar + OFF_CNT) : "memory");
        if (old == 15) {
            atomicAdd(scr->done, 1u);
        }
    }
}

typedef CUresult (*EncFn)(CUtensorMap*, CUtensorMapDataType, cuuint32_t, void*, const cuuint64_t*, const cuuint64_t*, const cuuint32_t*,
                          const cuuint32_t*, CUtensorMapInterleave, CUtensorMapSwizzle, CUtensorMapL2promotion, CUtensorMapFloatOOBfill);

extern "C" void kernel_launch(void* const* d_in, const int* in_sizes, int n_in, void* d_out, int out_size) {
    static EncFn enc = nullptr;
    static Scratch* scr = nullptr;
    if (!enc) {
        cudaGetSymbolAddress((void**)&scr, g_scr);
        cudaDriverEntryPointQueryResult qr;
        cudaGetDriverEntryPoint("cuTensorMapEncodeTiled", (void**)&enc, cudaEnableDefault, &qr);
        cudaFuncSetAttribute(fused_kernel, cudaFuncAttributeMaxDynamicSharedMemorySize, SMEM_BYTES);
    }
    CUtensorMap mx, mw, mwo;
    const cuuint32_t es[3] = {1, 1, 1};
    {
        cuuint64_t d[2] = {512, 2048}, s[1] = {1024}; cuuint32_t b[2] = {64, 128};
        enc(&mx, CU_TENSOR_MAP_DATA_TYPE_BFLOAT16, 2, d_in[0], d, s, b, es, CU_TENSOR_MAP_INTERLEAVE_NONE, CU_TENSOR_MAP_SWIZZLE_128B,
            CU_TENSOR_MAP_L2_PROMOTION_L2_128B, CU_TENSOR_MAP_FLOAT_OOB_FILL_NONE);
    }
    {
        cuuint64_t d[3] = {512, 512, 3}, s[2] = {3072, 1024}; cuuint32_t b[3] = {64, 64, 3};
        enc(&mw, CU_TENSOR_MAP_DATA_TYPE_BFLOAT16, 3, d_in[1], d, s, b, es, CU_TENSOR_MAP_INTERLEAVE_NONE, CU_TENSOR_MAP_SWIZZLE_128B,
            CU_TENSOR_MAP_L2_PROMOTION_L2_128B, CU_TENSOR_MAP_FLOAT_OOB_FILL_NONE);
    }
    {
        cuuint64_t d[2] = {512, 512}, s[1] = {1024}; cuuint32_t b[2] = {64, 256};
        enc(&mwo, CU_TENSOR_MAP_DATA_TYPE_BFLOAT16, 2, d_in[3], d, s, b, es, CU_TENSOR_MAP_INTERLEAVE_NONE, CU_TENSOR_MAP_SWIZZLE_128B,
            CU_TENSOR_MAP_L2_PROMOTION_L2_128B, CU_TENSOR_MAP_FLOAT_OOB_FILL_NONE);
    }
    fused_kernel<<<128, 512, SMEM_BYTES, cudaStreamPerThread>>>(
        scr, (const bf16*)d_in[5], (const bf16*)d_in[6], (const bf16*)d_in[7], (const bf16*)d_in[8], (const bf16*)d_in[9],
        (const bf16*)d_in[10], (const bf16*)d_in[2], (const bf16*)d_in[11], (bf16*)d_out, mx, mw, mwo);
}
```

```cpp
#include <cuda_runtime.h>
#include <cuda.h>
#include <cuda_bf16.h>
#include <stdint.h>

typedef __nv_bfloat16 bf16;

struct Scratch {
    uint4 xt[128 * 1024];
    uint4 o[16 * 8 * 32 * 32];
    uint4 y[128 * 1024];
    uint4 kvp[8 * 16 * 544];
    uint4 kvf[8 * 4 * 68];
    unsigned g[1024 * 8];
    unsigned yflag[128 * 8];
    unsigned xcnt[8 * 32];
    unsigned done[32];
};
__device__ Scratch g_scr;
#define STAMP(n)

constexpr int SLOT = 40960;
constexpr int OFF_SP0 = 32768, OFF_SP1 = SLOT + 32768;
constexpr int OFF_P = 2 * SLOT, OFF_V = OFF_P + 32768;
constexpr int OFF_KVF = OFF_V + 32768;
constexpr int KT_BYTES = 3264, KW_D = 16, KW_2 = 560, KW_3 = 656;
constexpr int OFF_U = 4 * SLOT, U_STRIDE = 4096 + 256 + 32;
constexpr int OFF_BUF = OFF_U + 4 * U_STRIDE, BUF_STRIDE = 8320;
constexpr int OFF_K = OFF_BUF + 4 * BUF_STRIDE;
constexpr int OFF_WPHI = OFF_K + 4 * KT_BYTES;
constexpr int OFF_GW = OFF_WPHI + 2048;
constexpr int OFF_BAR = OFF_GW + 1024;
constexpr int SMEM_BYTES = OFF_BAR + 256 + 256;
static_assert(SMEM_BYTES <= 232448 && OFF_BUF % 128 == 0, "smem");
constexpr int W5_OFF = 0, W3_OFF = 3088, W9_OFF = 6176;
constexpr int BAR_FULL = 0, BAR_EMPTY = 4, BAR_WPHI = 8, BAR_WO = 9, BAR_WO2 = 10, BAR_XT = 11, BAR_DONE = 12, BAR_KG = 13, BAR_SP = 14,
              BAR_PUB = 15, BAR_KVF = 16, BAR_UR = 17, BAR_WR = 18, BAR_PREP = 19, BAR_KGA = 20, BAR_SP2 = 21, OFF_CNT = 192;
#define CONV_START BAR_DONE
#define D1_NS 0
#define D2_NS 0
#define D3_NS 100
#define PS_NS 100
#define POLL_NS 0
constexpr int SPIN_LIMIT = 1 << 17;

__device__ __forceinline__ uint32_t s2u(const void* p) { return (uint32_t)__cvta_generic_to_shared(p); }
__device__ __forceinline__ void mbar_init(uint32_t b, int c) { asm volatile("mbarrier.init.shared::cta.b64 [%0],%1;" ::"r"(b), "r"(c) : "memory"); }
__device__ __forceinline__ void mbar_expect(uint32_t b, int bytes) { asm volatile("mbarrier.arrive.expect_tx.shared::cta.b64 _,[%0],%1;" ::"r"(b), "r"(bytes) : "memory"); }
__device__ __forceinline__ void mbar_arrive(uint32_t b) { asm volatile("mbarrier.arrive.shared::cta.b64 _,[%0];" ::"r"(b) : "memory"); }
__device__ __forceinline__ void mbar_wait(uint32_t b, int ph) {
    asm volatile("{\n.reg .pred p;\n.reg .u32 n;\nmov.u32 n,0;\nLW_%=:\nmbarrier.try_wait.parity.shared::cta.b64 p,[%0],%1;\n@p bra LD_%=;\n"
                 "add.u32 n,n,1;\nsetp.lt.u32 p,n,16384;\n@p bra LW_%=;\nLD_%=:\n}" ::"r"(b), "r"(ph) : "memory");
}
__device__ __forceinline__ void tma2d(uint32_t dst, const CUtensorMap* m, int c0, int c1, uint32_t bar) {
    asm volatile("cp.async.bulk.tensor.2d.shared::cluster.global.mbarrier::complete_tx::bytes [%0],[%1,{%3,%4}],[%2];" ::"r"(dst), "l"(m), "r"(bar), "r"(c0), "r"(c1) : "memory");
}
__device__ __forceinline__ void tma3d(uint32_t dst, const CUtensorMap* m, int c0, int c1, int c2, uint32_t bar) {
    asm volatile("cp.async.bulk.tensor.3d.shared::cluster.global.mbarrier::complete_tx::bytes [%0],[%1,{%3,%4,%5}],[%2];" ::"r"(dst), "l"(m), "r"(bar), "r"(c0), "r"(c1), "r"(c2) : "memory");
}
__device__ __forceinline__ void bulk_g2s(uint32_t dst, const void* src, int bytes, uint32_t bar) {
    asm volatile("cp.async.bulk.shared::cluster.global.mbarrier::complete_tx::bytes [%0],[%1],%2,[%3];" ::"r"(dst), "l"(src), "r"(bytes), "r"(bar) : "memory");
}
__device__ __forceinline__ uint64_t mkdesc(uint32_t addr, uint32_t lbo, uint32_t sbo) {
    return (uint64_t)((addr & 0x3FFFF) >> 4) | ((uint64_t)(lbo >> 4) << 16) | ((uint64_t)(sbo >> 4) << 32) | ((uint64_t)1 << 62);
}
__device__ __forceinline__ void wg_fence() { asm volatile("wgmma.fence.sync.aligned;" ::: "memory"); }
__device__ __forceinline__ void wg_commit() { asm volatile("wgmma.commit_group.sync.aligned;" ::: "memory"); }
template <int N> __device__ __forceinline__ void wg_wait() { asm volatile("wgmma.wait_group.sync.aligned %0;" ::"n"(N) : "memory"); }
template <int N> __device__ __forceinline__ void fence_regs(float* d) {
#pragma unroll
    for (int i = 0; i < N; i++) asm volatile("" : "+f"(d[i])::"memory");
}
#define R8(d, o) "+f"(d[o]), "+f"(d[o + 1]), "+f"(d[o + 2]), "+f"(d[o + 3]), "+f"(d[o + 4]), "+f"(d[o + 5]), "+f"(d[o + 6]), "+f"(d[o + 7])
__device__ __forceinline__ void wgmma192(float* d, uint64_t da, uint64_t db) {
    asm volatile("wgmma.mma_async.sync.aligned.m64n192k16.f32.bf16.bf16 {"
                 "%0,%1,%2,%3,%4,%5,%6,%7,%8,%9,%10,%11,%12,%13,%14,%15,%16,%17,%18,%19,%20,%21,%22,%23,%24,%25,%26,%27,%28,%29,%30,%31,"
                 "%32,%33,%34,%35,%36,%37,%38,%39,%40,%41,%42,%43,%44,%45,%46,%47,%48,%49,%50,%51,%52,%53,%54,%55,%56,%57,%58,%59,%60,%61,%62,%63,"
                 "%64,%65,%66,%67,%68,%69,%70,%71,%72,%73,%74,%75,%76,%77,%78,%79,%80,%81,%82,%83,%84,%85,%86,%87,%88,%89,%90,%91,%92,%93,%94,%95},"
                 "%96,%97,1,1,1,0,1;"
                 : R8(d, 0), R8(d, 8), R8(d, 16), R8(d, 24), R8(d, 32), R8(d, 40), R8(d, 48), R8(d, 56), R8(d, 64), R8(d, 72), R8(d, 80), R8(d, 88)
                 : "l"(da), "l"(db));
}
__device__ __forceinline__ void wgmma64_tt(float* d, uint64_t da, uint64_t db, int sc) {
    asm volatile("{.reg .pred p; setp.ne.b32 p,%34,0; wgmma.mma_async.sync.aligned.m64n64k16.f32.bf16.bf16 {"
                 "%0,%1,%2,%3,%4,%5,%6,%7,%8,%9,%10,%11,%12,%13,%14,%15,%16,%17,%18,%19,%20,%21,%22,%23,%24,%25,%26,%27,%28,%29,%30,%31},"
                 "%32,%33,p,1,1,1,1;}"
                 : R8(d, 0), R8(d, 8), R8(d, 16), R8(d, 24)
                 : "l"(da), "l"(db), "r"(sc));
}
__device__ __forceinline__ void wgmma128_rs(float* d, const uint4& a, uint64_t db, int sc) {
    asm volatile("{.reg .pred p; setp.ne.b32 p,%69,0; wgmma.mma_async.sync.aligned.m64n128k16.f32.bf16.bf16 {"
                 "%0,%1,%2,%3,%4,%5,%6,%7,%8,%9,%10,%11,%12,%13,%14,%15,%16,%17,%18,%19,%20,%21,%22,%23,%24,%25,%26,%27,%28,%29,%30,%31,"
                 "%32,%33,%34,%35,%36,%37,%38,%39,%40,%41,%42,%43,%44,%45,%46,%47,%48,%49,%50,%51,%52,%53,%54,%55,%56,%57,%58,%59,%60,%61,%62,%63},"
                 "{%64,%65,%66,%67},%68,p,1,1,1;}"
                 : R8(d, 0), R8(d, 8), R8(d, 16), R8(d, 24), R8(d, 32), R8(d, 40), R8(d, 48), R8(d, 56)
                 : "r"(a.x), "r"(a.y), "r"(a.z), "r"(a.w), "l"(db), "r"(sc));
}
__device__ __forceinline__ void mma16816(float* c, uint32_t a0, uint32_t a1, uint32_t a2, uint32_t a3, uint32_t b0, uint32_t b1) {
    asm("mma.sync.aligned.m16n8k16.row.col.f32.bf16.bf16.f32 {%0,%1,%2,%3},{%4,%5,%6,%7},{%8,%9},{%0,%1,%2,%3};"
        : "+f"(c[0]), "+f"(c[1]), "+f"(c[2]), "+f"(c[3]) : "r"(a0), "r"(a1), "r"(a2), "r"(a3), "r"(b0), "r"(b1));
}
__device__ __forceinline__ void ldsm4(uint32_t* r, uint32_t a) {
    asm volatile("ldmatrix.sync.aligned.m8n8.x4.shared.b16 {%0,%1,%2,%3},[%4];" : "=r"(r[0]), "=r"(r[1]), "=r"(r[2]), "=r"(r[3]) : "r"(a) : "memory");
}
__device__ __forceinline__ void ldsm4t(uint32_t* r, uint32_t a) {
    asm volatile("ldmatrix.sync.aligned.m8n8.x4.trans.shared.b16 {%0,%1,%2,%3},[%4];" : "=r"(r[0]), "=r"(r[1]), "=r"(r[2]), "=r"(r[3]) : "r"(a) : "memory");
}
__device__ __forceinline__ void stsm4(uint32_t a, uint32_t r0, uint32_t r1, uint32_t r2, uint32_t r3) {
    asm volatile("stmatrix.sync.aligned.m8n8.x4.shared.b16 [%0],{%1,%2,%3,%4};" ::"r"(a), "r"(r0), "r"(r1), "r"(r2), "r"(r3) : "memory");
}
__device__ __forceinline__ uint32_t lds32(uint32_t a) { uint32_t v; asm volatile("ld.shared.b32 %0,[%1];" : "=r"(v) : "r"(a) : "memory"); return v; }
__device__ __forceinline__ uint4 lds128(uint32_t a) { uint4 v; asm volatile("ld.shared.v4.b32 {%0,%1,%2,%3},[%4];" : "=r"(v.x), "=r"(v.y), "=r"(v.z), "=r"(v.w) : "r"(a) : "memory"); return v; }
__device__ __forceinline__ void sts16(uint32_t a, uint32_t v) { asm volatile("st.shared.b16 [%0],%1;" ::"r"(a), "h"((unsigned short)v) : "memory"); }
__device__ __forceinline__ void sts32(uint32_t a, uint32_t v) { asm volatile("st.shared.b32 [%0],%1;" ::"r"(a), "r"(v) : "memory"); }
__device__ __forceinline__ void sts64(uint32_t a, uint32_t x, uint32_t y) { asm volatile("st.shared.v2.b32 [%0],{%1,%2};" ::"r"(a), "r"(x), "r"(y) : "memory"); }
__device__ __forceinline__ void sts128(uint32_t a, uint32_t x, uint32_t y, uint32_t z, uint32_t w) { asm volatile("st.shared.v4.b32 [%0],{%1,%2,%3,%4};" ::"r"(a), "r"(x), "r"(y), "r"(z), "r"(w) : "memory"); }
__device__ __forceinline__ uint32_t pack2(float lo, float hi) { uint32_t d; asm("cvt.rn.bf16x2.f32 %0,%1,%2;" : "=r"(d) : "f"(hi), "f"(lo)); return d; }
__device__ __forceinline__ float bf_lo(uint32_t v) { return __uint_as_float(v << 16); }
__device__ __forceinline__ float bf_hi(uint32_t v) { return __uint_as_float(v & 0xffff0000u); }
__device__ __forceinline__ float bf_round(float v) { return bf_lo(pack2(v, 0.f)); }
__device__ __forceinline__ uint32_t hmax2(uint32_t a, uint32_t b) { uint32_t d; asm("max.bf16x2 %0,%1,%2;" : "=r"(d) : "r"(a), "r"(b)); return d; }
__device__ __forceinline__ uint32_t hmin2(uint32_t a, uint32_t b) { uint32_t d; asm("min.bf16x2 %0,%1,%2;" : "=r"(d) : "r"(a), "r"(b)); return d; }
__device__ __forceinline__ uint32_t hmul2(uint32_t a, uint32_t b) { uint32_t d; asm("mul.rn.bf16x2 %0,%1,%2;" : "=r"(d) : "r"(a), "r"(b)); return d; }
__device__ __forceinline__ float ex2(float x) { float y; asm("ex2.approx.ftz.f32 %0,%1;" : "=f"(y) : "f"(x)); return y; }
__device__ __forceinline__ float rcp(float x) { float y; asm("rcp.approx.ftz.f32 %0,%1;" : "=f"(y) : "f"(x)); return y; }
__device__ __forceinline__ uint32_t ld_nc(const uint32_t* p) { uint32_t v; asm volatile("ld.global.nc.b32 %0,[%1];" : "=r"(v) : "l"(p)); return v; }
__device__ __forceinline__ uint2 ld_nc64(const uint2* p) { uint2 v; asm volatile("ld.global.nc.v2.b32 {%0,%1},[%2];" : "=r"(v.x), "=r"(v.y) : "l"(p)); return v; }
__device__ __forceinline__ unsigned ld_acq(const unsigned* p) { unsigned v; asm volatile("ld.acquire.gpu.global.u32 %0,[%1];" : "=r"(v) : "l"(p) : "memory"); return v; }
__device__ __forceinline__ unsigned ld_rlx(const unsigned* p) { unsigned v; asm volatile("ld.relaxed.gpu.global.u32 %0,[%1];" : "=r"(v) : "l"(p) : "memory"); return v; }
__device__ __forceinline__ uint2 ld_rlx64(const void* p) { uint2 v; asm volatile("{.reg .b64 t; ld.relaxed.gpu.global.b64 t,[%2]; mov.b64 {%0,%1},t;}" : "=r"(v.x), "=r"(v.y) : "l"(p) : "memory"); return v; }
__device__ __forceinline__ uint4 ld_rlx128(const void* p) {
    uint4 v;
    asm volatile("{.reg .b64 t,u; ld.relaxed.gpu.global.v2.b64 {t,u},[%4]; mov.b64 {%0,%1},t; mov.b64 {%2,%3},u;}" : "=r"(v.x), "=r"(v.y), "=r"(v.z), "=r"(v.w) : "l"(p) : "memory");
    return v;
}
__device__ __forceinline__ void st_rlx32(void* p, uint32_t x) { asm volatile("st.relaxed.gpu.global.u32 [%0],%1;" ::"l"(p), "r"(x) : "memory"); }
__device__ __forceinline__ void st_rlx64(void* p, uint32_t x, uint32_t y) { asm volatile("{.reg .b64 t; mov.b64 t,{%1,%2}; st.relaxed.gpu.global.b64 [%0],t;}" ::"l"(p), "r"(x), "r"(y) : "memory"); }
__device__ __forceinline__ void st_rlx128(void* p, uint4 v) {
    asm volatile("{.reg .b64 t,u; mov.b64 t,{%1,%2}; mov.b64 u,{%3,%4}; st.relaxed.gpu.global.v2.b64 [%0],{t,u};}" ::"l"(p), "r"(v.x), "r"(v.y), "r"(v.z), "r"(v.w) : "memory");
}
__device__ __forceinline__ uint32_t tagw(uint32_t w, uint32_t tag) { return (w & ~1u) | tag; }
__device__ __forceinline__ uint4 tag4(uint32_t x, uint32_t y, uint32_t z, uint32_t w, uint32_t tag) { return make_uint4(tagw(x, tag), y, tagw(z, tag), w); }
__device__ __forceinline__ uint32_t bad4(const uint4& v, uint32_t tag) { return (v.x ^ tag) | (v.z ^ tag); }
__device__ __forceinline__ void bar_named(int id, int n) { asm volatile("bar.sync %0,%1;" ::"r"(id), "r"(n) : "memory"); }

struct cf { float re, im; };
__device__ __forceinline__ cf cmul(cf a, cf b) { cf r; r.re = a.re * b.re - a.im * b.im; r.im = a.re * b.im + a.im * b.re; return r; }
__device__ __forceinline__ cf cexp_p(float arl, float ait, float p) {
    float mag = ex2(arl * p);
    float t = ait * p;
    t = (t - rintf(t)) * 6.283185307179586f;
    cf r; r.re = mag * __cosf(t); r.im = mag * __sinf(t);
    return r;
}

__device__ __forceinline__ void hedgehog4(const uint32_t* a, uint32_t wphi_addr, uint32_t (*out)[8]) {
    float p[4][2][4], mx[4][2];
#pragma unroll
    for (int h = 0; h < 4; h++) {
        uint32_t b[4];
        ldsm4t(b, wphi_addr + h * 512);
        float c0[4] = {0.f, 0.f, 0.f, 0.f}, c1[4] = {0.f, 0.f, 0.f, 0.f};
        mma16816(c0, a[4 * h], a[4 * h + 1], a[4 * h + 2], a[4 * h + 3], b[0], b[1]);
        mma16816(c1, a[4 * h], a[4 * h + 1], a[4 * h + 2], a[4 * h + 3], b[2], b[3]);
#pragma unroll
        for (int k = 0; k < 2; k++) {
            p[h][k][0] = c0[2 * k]; p[h][k][1] = c0[2 * k + 1]; p[h][k][2] = c1[2 * k]; p[h][k][3] = c1[2 * k + 1];
            mx[h][k] = fmaxf(fmaxf(p[h][k][0], p[h][k][1]), fmaxf(p[h][k][2], p[h][k][3]));
        }
    }
#pragma unroll
    for (int o = 1; o <= 2; o <<= 1)
#pragma unroll
        for (int h = 0; h < 4; h++)
#pragma unroll
            for (int k = 0; k < 2; k++) mx[h][k] = fmaxf(mx[h][k], __shfl_xor_sync(~0u, mx[h][k], o));
    const float L = 1.4426950408889634f;
    float pmin = 1.f;
#pragma unroll
    for (int h = 0; h < 4; h++)
#pragma unroll
        for (int k = 0; k < 2; k++) {
            const float m = -mx[h][k] * L;
            const float e0 = ex2(fmaf(p[h][k][0], L, m)), e1 = ex2(fmaf(p[h][k][1], L, m)), e2 = ex2(fmaf(p[h][k][2], L, m)), e3 = ex2(fmaf(p[h][k][3], L, m));
            const float p01 = e0 * e1, p23 = e2 * e3, pp = p01 * p23, r = rcp(pp), r01 = r * p23, r23 = r * p01;
            pmin = fminf(pmin, pp);
            out[h][k] = pack2(e0, e1); out[h][k + 2] = pack2(e2, e3);
            out[h][4 + k] = pack2(r01 * e1, r01 * e0); out[h][4 + k + 2] = pack2(r23 * e3, r23 * e2);
        }
    if (__builtin_expect(__any_sync(~0u, !(pmin > 1e-18f)), 0)) {
#pragma unroll
        for (int h = 0; h < 4; h++)
#pragma unroll
            for (int k = 0; k < 2; k++) {
                float m = fminf(fminf(p[h][k][0], p[h][k][1]), fminf(p[h][k][2], p[h][k][3]));
                m = fminf(m, __shfl_xor_sync(~0u, m, 1));
                m = fminf(m, __shfl_xor_sync(~0u, m, 2)) * L;
                out[h][4 + k] = pack2(ex2(fmaf(p[h][k][0], -L, m)), ex2(fmaf(p[h][k][1], -L, m)));
                out[h][4 + k + 2] = pack2(ex2(fmaf(p[h][k][2], -L, m)), ex2(fmaf(p[h][k][3], -L, m)));
            }
    }
}

__global__ void __launch_bounds__(512, 1)
fused_kernel(Scratch* __restrict__ scr, const bf16* __restrict__ logA, const bf16* __restrict__ Aim, const bf16* __restrict__ Cre,
             const bf16* __restrict__ Cim, const bf16* __restrict__ logdt, const bf16* __restrict__ Dskip, const bf16* __restrict__ wphi,
             const bf16* __restrict__ gatew, bf16* __restrict__ out,
             const __grid_constant__ CUtensorMap mx, const __grid_constant__ CUtensorMap mw, const __grid_constant__ CUtensorMap mwo) {
    extern __shared__ __align__(1024) uint8_t smem[];
    const uint32_t sb = s2u(smem);
    const int tid = threadIdx.x, warp = __shfl_sync(~0u, tid >> 5, 0), lane = tid & 31;
    const int g = lane >> 2, q = lane & 3, w4 = warp & 3;
    const int bi = blockIdx.x, bi_i = bi & 15, bi_j = bi >> 4;
    const uint32_t bar = sb + OFF_BAR;
    const int rot = (bi_j & 3) * 2, xkb = bi_j >> 2;
    auto load_stage = [&](int kb) {
        const uint32_t b = bar + 8 * (BAR_FULL + (kb & 3)), d = sb + (kb & 3) * SLOT;
        const int kc = ((kb + rot) & 7) * 64;
        mbar_expect(b, SLOT);
        tma2d(d, &mx, kc, bi_i * 128, b);
        tma3d(d + 16384, &mw, bi_j * 64, kc, 0, b);
    };

    if (tid == 0) {
        for (int s = 0; s < 4; s++) mbar_init(bar + 8 * (BAR_FULL + s), 1);
        asm volatile("fence.mbarrier_init.release.cluster;" ::: "memory");
        load_stage(0); load_stage(1);
        STAMP(11);
    }
    const int ch = bi * 4 + w4;
    const int pidx = ch * 64 + lane * 2 + (warp >> 3);
    const uint32_t pla = ld_nc((const uint32_t*)logA + pidx), pai = ld_nc((const uint32_t*)Aim + pidx);
    const uint32_t pcr = ld_nc((const uint32_t*)Cre + pidx), pci = ld_nc((const uint32_t*)Cim + pidx);
    uint32_t pdt = ld_nc((const uint32_t*)logdt + (ch >> 1));
    const uint32_t pds = ld_nc((const uint32_t*)Dskip + (ch >> 1));
    unsigned done0 = ld_rlx(scr->done);
    if (tid == 32) {
        if (sb & 1023) __trap();
        sts32(bar + OFF_CNT, 0);
        for (int s = 0; s < 4; s++) mbar_init(bar + 8 * (BAR_EMPTY + s), 9);
        mbar_init(bar + 8 * BAR_WPHI, 1); mbar_init(bar + 8 * BAR_WO, 2); mbar_init(bar + 8 * BAR_WO2, 1); mbar_init(bar + 8 * BAR_XT, 4);
        mbar_init(bar + 8 * BAR_DONE, 9); mbar_init(bar + 8 * BAR_KG, 8); mbar_init(bar + 8 * BAR_SP, 1); mbar_init(bar + 8 * BAR_PUB, 8);
        mbar_init(bar + 8 * BAR_KVF, 4); mbar_init(bar + 8 * BAR_UR, 4); mbar_init(bar + 8 * BAR_WR, 4); mbar_init(bar + 8 * BAR_PREP, 4); mbar_init(bar + 8 * BAR_KGA, 4); mbar_init(bar + 8 * BAR_SP2, 1);
        asm volatile("fence.mbarrier_init.release.cluster;" ::: "memory");
        mbar_expect(bar + 8 * BAR_WPHI, 3072);
        bulk_g2s(sb + OFF_GW, gatew, 1024, bar + 8 * BAR_WPHI);
        bulk_g2s(sb + OFF_WPHI, wphi + bi_j * 1024, 2048, bar + 8 * BAR_WPHI);
    } else if (tid == 64) {
        asm volatile("prefetch.tensormap [%0];" ::"l"(&mw) : "memory");
    }
    const uint32_t buf = sb + OFF_BUF + w4 * BUF_STRIDE, kb_ = sb + OFF_K + w4 * KT_BYTES;
    if ((warp >> 2) == 2) {
#pragma unroll
        for (int v = 0; v < 7; v++) if (v * 32 + lane < KT_BYTES / 16) sts128(kb_ + (v * 32 + lane) * 16, 0, 0, 0, 0);
    }
    __syncthreads();
    asm volatile("" : "+r"(pdt), "+r"(done0)::"memory");
    const unsigned epoch1 = (done0 >> 7) + 1u;
    const uint32_t tag = epoch1 & 1u;

    const int st = tid & 127;
    const uint32_t ub = sb + OFF_U + w4 * U_STRIDE + 256, spare = sb + (w4 < 2 ? OFF_SP0 : OFF_SP1) + (w4 & 1) * 4096;

    auto stg_of = [&](int w) { return w < 8 ? sb + 3 * SLOT + w * 7296 : sb + 2 * SLOT + (w & 3) * 7296; };
    float kc[24];
#pragma unroll
    for (int t = 0; t < 24; t++) kc[t] = 0.f;
    {
        const float dt = bf_round(expf((ch & 1) ? bf_hi(pdt) : bf_lo(pdt)));
        const uint32_t stg = (warp >> 2) == 2 ? buf : stg_of(warp);
        const int sh = ((warp >> 2) & 1) * 16;
        auto pick = [&](uint32_t v) { return __uint_as_float((v >> sh) << 16); };
        const float ea = bf_round(ex2(pick(pla) * 1.4426950408889634f));
        const float arl = (-ea * dt) * 1.4426950408889634f, ait = (pick(pai) * dt) * 0.15915494309189535f;
        cf C2; C2.re = 2.0f * (pick(pcr) * dt); C2.im = 2.0f * (pick(pci) * dt);
        const cf z1 = cexp_p(arl, ait, 1.0f), z128 = cexp_p(arl, ait, 128.0f);
        cf z8 = cexp_p(arl, ait, 8.0f); z8.im = -z8.im;
        const uint32_t lp = stg + lane * 4;
        auto put = [&](int row, const cf& v) { sts32((lp ^ ((row & 7) << 4)) + row * 128, pack2(v.re, v.im)); };
        {
            const cf z16 = cmul(z8, z8);
            cf e; e.re = 1.f; e.im = 0.f;
            cf o = z8;
            put(0, e); put(1, o);
            e = z16; put(2, e);
#pragma unroll
            for (int b = 3; b < 16; b += 2) {
                o = cmul(o, z16); put(b, o);
                if (b + 1 < 16) { e = cmul(e, z16); put(b + 1, e); }
            }
        }
        cf h[8];
        h[0] = C2; put(16, h[0]);
        {
            const cf z2 = cmul(z1, z1);
            h[1] = cmul(h[0], z1);
#pragma unroll
            for (int r = 2; r < 8; r++) h[r] = cmul(h[r - 2], z2);
#pragma unroll
            for (int r = 1; r < 8; r++) put(16 + r, h[r]);
        }
#pragma unroll
        for (int r = 0; r < 8; r++) { h[r] = cmul(h[r], z128); put(24 + r, h[r]); }
#pragma unroll
        for (int al = 0; al < 2; al++)
#pragma unroll
            for (int r = 0; r < 4; r++) { h[2 * r] = cmul(h[2 * r], z128); put(32 + al * 4 + r, h[2 * r]); }
#pragma unroll
        for (int al = 0; al < 4; al++)
#pragma unroll
            for (int r = 0; r < 2; r++) { h[4 * r] = cmul(h[4 * r], z128); put(40 + al * 2 + r, h[4 * r]); }
#pragma unroll
        for (int al = 0; al < 9; al++) { h[0] = cmul(h[0], z128); put(48 + al, h[0]); }
        __syncwarp();
        const int lr = lane & 7, lm = lane >> 3;
#pragma unroll
        for (int kp = 0; kp < 2; kp++) {
            uint32_t a0[4], a1[4];
            ldsm4(a0, stg + ((lm & 1) * 8 + lr) * 128 + (((4 * kp + (lm >> 1)) ^ lr) << 4));
            ldsm4(a1, stg + ((lm & 1) * 8 + lr) * 128 + (((4 * kp + 2 + (lm >> 1)) ^ lr) << 4));
#pragma unroll
            for (int t = 0; t < 6; t++) {
                uint32_t b[4];
                ldsm4(b, stg + (16 + 8 * t + lr) * 128 + (((4 * kp + lm) ^ lr) << 4));
                mma16816(kc + 4 * t, a0[0], a0[1], a0[2], a0[3], b[0], b[1]);
                mma16816(kc + 4 * t, a1[0], a1[1], a1[2], a1[3], b[2], b[3]);
            }
        }
        __syncwarp();
        if ((warp >> 2) != 2) {
#pragma unroll
            for (int t = 0; t < 6; t++)
                sts128(stg + (t * 32 + lane) * 16, __float_as_uint(kc[4 * t]), __float_as_uint(kc[4 * t + 1]), __float_as_uint(kc[4 * t + 2]), __float_as_uint(kc[4 * t + 3]));
            asm volatile("fence.proxy.async.shared::cta;" ::: "memory");
            __syncwarp();
            if (lane == 0) mbar_arrive(bar + 8 * (warp < 8 ? BAR_KG : BAR_KGA));
        }
    }

    if (warp < 8) {
        asm volatile("setmaxnreg.inc.sync.aligned.u32 160;");
        const int wg = warp >> 2;
        if (warp == 0) STAMP(21);
        float acc[96];
        const int srow = warp * 16 + (lane & 15);
        const uint32_t srow_a = srow * 128;
        const int sx = srow & 7, shi = lane >> 4;
#pragma unroll
        for (int r = 0; r < 96; r++) acc[r] = 0.f;
        fence_regs<96>(acc);
        const uint64_t da0 = mkdesc(sb + wg * 8192, 16, 1024), db0 = mkdesc(sb + 16384, 8192, 1024);
#pragma unroll 1
        for (int kb = 0; kb < 8; kb++) {
            const int s = kb & 3;
            const uint64_t da = da0 + s * (SLOT >> 4), db = db0 + s * (SLOT >> 4);
            if (warp == 0) STAMP(40 + kb);
            mbar_wait(bar + 8 * (BAR_FULL + s), kb >> 2);
            if (warp == 0) STAMP(32 + kb);
            wg_fence();
#pragma unroll
            for (int k = 0; k < 4; k++) wgmma192(acc, da + 2 * k, db + 128 * k);
            wg_commit();
            wg_wait<1>();
            if (lane == 0 && kb > 0) mbar_arrive(bar + 8 * (BAR_EMPTY + ((kb - 1) & 3)));
        }
        mbar_wait(bar + 8 * BAR_WPHI, 0);
        wg_wait<0>();
        fence_regs<96>(acc);
        if (lane == 0) mbar_arrive(bar + 8 * BAR_DONE);
        if (warp == 0) STAMP(1);
        uint32_t in[16], qa[16];
        mbar_wait(bar + 8 * BAR_DONE, 0);
#pragma unroll
        for (int r = 0; r < 16; r++) {
            in[r] = pack2(acc[32 + 2 * r], acc[32 + 2 * r + 1]);
            qa[r] = pack2(acc[2 * r], acc[2 * r + 1]);
        }
#pragma unroll
        for (int hh = 0; hh < 4; hh++)
            stsm4(sb + OFF_V + (hh >> 1) * 16384 + srow_a + (((2 * (hh & 1) + shi) ^ sx) << 4), pack2(acc[64 + 8 * hh], acc[65 + 8 * hh]),
                  pack2(acc[66 + 8 * hh], acc[67 + 8 * hh]), pack2(acc[68 + 8 * hh], acc[69 + 8 * hh]), pack2(acc[70 + 8 * hh], acc[71 + 8 * hh]));
        sts128(sb + OFF_V + shi * 16384 + srow_a + ((4 ^ sx) << 4), 0x3f803f80u, 0x3f803f80u, 0x3f803f80u, 0x3f803f80u);
        const uint32_t wphi_a = sb + OFF_WPHI + (lane & 15) * 32 + (lane >> 4) * 16;
        uint32_t pq[4][8];
#pragma unroll 1
        for (int it = 0; it < 2; it++) {
            hedgehog4(in, wphi_a, pq);
            if (it == 1) break;
#pragma unroll
            for (int hs = 0; hs < 8; hs++) {
                float c[4] = {0.f, 0.f, 0.f, 0.f};
                const uint32_t* o = pq[hs >> 1] + 4 * (hs & 1);
                mma16816(c, o[0], o[1], o[2], o[3], 0x3f803f80u, 0x3f803f80u);
                const float r0 = rcp(c[0]), r1 = rcp(c[2]);
                const uint32_t s0 = pack2(r0, r0), s1 = pack2(r1, r1);
                stsm4(sb + OFF_P + (hs >> 2) * 16384 + srow_a + (((2 * (hs & 3) + shi) ^ sx) << 4), hmul2(o[0], s0), hmul2(o[1], s1), hmul2(o[2], s0), hmul2(o[3], s1));
            }
            asm volatile("fence.proxy.async.shared::cta;" ::: "memory");
            bar_named(1, 256);
            if (warp == 0) STAMP(2);
            float d[32];
            const uint64_t dv = mkdesc(sb + OFF_V + wg * 16384, 16, 1024), dp = mkdesc(sb + OFF_P + wg * 16384, 16, 1024);
            wg_fence();
#pragma unroll
            for (int k = 0; k < 8; k++) wgmma64_tt(d, dv + 128 * k, dp + 128 * k, k != 0);
            wg_commit();
            mbar_wait(bar + 8 * BAR_PREP, 0);
            uint4* kvp = scr->kvp + bi * 544 + wg * 272 + (w4 < 2 ? w4 * 136 : 128) + lane;
            wg_wait<0>();
            fence_regs<32>(d);
            if (w4 < 2 || (w4 == 2 && lane < 4)) {
#pragma unroll
                for (int f = 0; f < 4; f++) {
                    const int i0 = 8 * (f >> 1) + 2 * (f & 1), i2 = 16 * (f >> 1) + 8 * (f & 1);
                    const float e0 = w4 == 0 ? d[i0] : (w4 == 1 ? d[16 + i0] : d[i2]), e1 = w4 == 0 ? d[i0 + 1] : (w4 == 1 ? d[17 + i0] : d[i2 + 1]);
                    const float e2 = w4 == 0 ? d[i0 + 4] : (w4 == 1 ? d[20 + i0] : d[i2 + 4]), e3 = w4 == 0 ? d[i0 + 5] : (w4 == 1 ? d[21 + i0] : d[i2 + 5]);
                    st_rlx128(kvp + (w4 < 2 ? f * 32 : (f >> 1) * 136 + (f & 1) * 4), tag4(__float_as_uint(e0), __float_as_uint(e1), __float_as_uint(e2), __float_as_uint(e3), tag));
                }
            }
            __syncwarp();
            if (lane == 0) mbar_arrive(bar + 8 * BAR_PUB);
            if (warp == 0) STAMP(3);
#pragma unroll
            for (int r = 0; r < 16; r++) in[r] = qa[r];
        }
        if (warp == 0) STAMP(4);
        {
            mbar_wait(bar + 8 * BAR_KVF, 0);
            uint4 kf[4][3];
#pragma unroll
            for (int hh = 0; hh < 4; hh++) {
                const uint32_t a = sb + OFF_KVF + hh * 1088;
                kf[hh][0] = lds128(a + lane * 32); kf[hh][1] = lds128(a + lane * 32 + 16); kf[hh][2] = lds128(a + 1024 + q * 16);
            }
            if (warp == 0) STAMP(5);
            uint4* og = scr->o + ((bi_i * 8 + warp) * 32 + bi_j * 4) * 32 + lane;
#pragma unroll
            for (int hh = 0; hh < 4; hh++) {
                float c[6][4];
#pragma unroll
                for (int t = 0; t < 6; t++) { c[t][0] = c[t][1] = c[t][2] = c[t][3] = 0.f; }
                const uint32_t* a = pq[hh];
                const bool od = g & 1;
                mma16816(c[0], a[0], a[1], a[2], a[3], od ? 0x3f803f80u : kf[hh][2].x, od ? 0x3f803f80u : kf[hh][2].y);
                mma16816(c[1], a[4], a[5], a[6], a[7], od ? 0x3f803f80u : kf[hh][2].z, od ? 0x3f803f80u : kf[hh][2].w);
                mma16816(c[2], a[0], a[1], a[2], a[3], kf[hh][0].x, kf[hh][0].y);
                mma16816(c[3], a[0], a[1], a[2], a[3], kf[hh][0].z, kf[hh][0].w);
                mma16816(c[4], a[4], a[5], a[6], a[7], kf[hh][1].x, kf[hh][1].y);
                mma16816(c[5], a[4], a[5], a[6], a[7], kf[hh][1].z, kf[hh][1].w);
                uint32_t w[4];
#pragma unroll
                for (int k = 0; k < 2; k++) {
                    const float rho = c[0][2 * k + 1] * rcp(c[1][2 * k + 1]);
                    const float r = rcp(fmaf(c[0][2 * k + 1], 1e-6f, fmaf(rho, c[1][2 * k], c[0][2 * k]))), rr = r * rho;
                    w[k] = pack2(fmaf(c[4][2 * k], rr, c[2][2 * k] * r), fmaf(c[4][2 * k + 1], rr, c[2][2 * k + 1] * r));
                    w[2 + k] = pack2(fmaf(c[5][2 * k], rr, c[3][2 * k] * r), fmaf(c[5][2 * k + 1], rr, c[3][2 * k + 1] * r));
                }
                st_rlx128(og + hh * 32, tag4(w[0], w[1], w[2], w[3], tag));
            }
        }
        if (warp == 0) STAMP(6);
        float oc[64];
        const int slab = bi_i * 8 + (bi_j >> 2) * 4 + w4;
        const uint8_t* ysrc = (const uint8_t*)scr->y + (size_t)((bi_j & 3) * 32 + wg * 16 + (q >> 1)) * 16384 + slab * 128 + g * 16 + (q & 1) * 8;
        const unsigned* gp = scr->g + (slab * 8 + (g >> 1)) * 8 + (g & 1) * 4;
        uint2 yv[8]; unsigned g0, g1;
        {
            const uint4* osrc = scr->o + (slab * 32 + wg * 16) * 32 + lane;
            uint4 fr[16];
            const unsigned* probe = (const unsigned*)(osrc - lane + ((lane & 3) * 4 + 3) * 32 + 31) + 2;
            {
                unsigned miss = ~0u;
                int n = 0;
#pragma unroll
                for (int s = 0; s < 4; s++) {
#pragma unroll 1
                    while ((miss >> s) & 1) { miss = __ballot_sync(~0u, (ld_rlx(probe) ^ tag) & 1); if (++n > SPIN_LIMIT) break; }
#pragma unroll
                    for (int k = 4 * s; k < 4 * s + 4; k++) fr[k] = ld_rlx128(osrc + k * 32);
                }
            }
            if (warp == 0) STAMP(14);
            mbar_wait(bar + 8 * (wg ? BAR_WO2 : BAR_WO), 0);
            const uint64_t dw = mkdesc(sb + wg * 2 * SLOT, wg ? 32768 : SLOT, 1024);
#pragma unroll
            for (int s = 0; s < 4; s++) {
                int n = 0;
#pragma unroll 1
                while (__builtin_expect(__any_sync(~0u, (bad4(fr[4 * s], tag) | bad4(fr[4 * s + 1], tag) | bad4(fr[4 * s + 2], tag) | bad4(fr[4 * s + 3], tag)) & 1), 0)) {
#pragma unroll
                    for (int k = 4 * s; k < 4 * s + 4; k++) fr[k] = ld_rlx128(osrc + k * 32);
                    if (++n > SPIN_LIMIT) break;
                }
                wg_fence();
#pragma unroll
                for (int hh = 0; hh < 4; hh++) wgmma128_rs(oc, fr[4 * s + hh], dw + 128 * (4 * s + hh), (s | hh) != 0);
                wg_commit();
                if (s == 1) {
                    wg_wait<1>();
#pragma unroll
                    for (int nt = 0; nt < 8; nt++) yv[nt] = ld_rlx64(ysrc + nt * 32768);
                    g0 = ld_rlx(gp); g1 = ld_rlx(gp + 32);
                }
            }
            if (warp == 0) STAMP(7);
            {
                const unsigned* yprobe = scr->yflag + ((bi_j & 3) * 32 + wg * 16 + (lane & 15)) * 8;
                int n = 0;
#pragma unroll 1
                while (true) {
                    uint32_t bad = (g0 ^ tag) | (g1 ^ tag);
#pragma unroll
                    for (int nt = 0; nt < 8; nt++) bad |= yv[nt].x ^ tag;
                    if (!__any_sync(~0u, bad & 1)) break;
#pragma unroll 1
                    while (__any_sync(~0u, (ld_rlx(yprobe) ^ tag) & 1)) { if (++n > SPIN_LIMIT) break; }
#pragma unroll
                    for (int nt = 0; nt < 8; nt++) yv[nt] = ld_rlx64(ysrc + nt * 32768);
                    g0 = ld_rlx(gp); g1 = ld_rlx(gp + 32);
                    if (++n > SPIN_LIMIT) break;
                }
            }
            if (warp == 0) STAMP(28);
        }
        {
            const float ga = bf_hi(g0), gb = bf_hi(g1);
            const float ha = bf_round(1.0f - ga), hb = bf_round(1.0f - gb);
            float yb[32];
#pragma unroll
            for (int nt = 0; nt < 8; nt++) {
                yb[4 * nt] = ha * bf_lo(yv[nt].x); yb[4 * nt + 1] = ha * bf_hi(yv[nt].x);
                yb[4 * nt + 2] = hb * bf_lo(yv[nt].y); yb[4 * nt + 3] = hb * bf_hi(yv[nt].y);
            }
            fence_regs<32>(yb);
            const uint32_t xw = sb + wg * 2 * SLOT + (tid & 127) * 16, xr = sb + (wg ^ 1) * 2 * SLOT + (tid & 127) * 16;
            wg_wait<0>();
            fence_regs<64>(oc);
            bar_named(3 + wg, 128);
#pragma unroll
            for (int r = 0; r < 8; r++) {
                const float* o = oc + 4 * r;
                sts128(xw + r * 2048, __float_as_uint(wg ? o[0] : o[32]), __float_as_uint(wg ? o[1] : o[33]), __float_as_uint(wg ? o[2] : o[34]), __float_as_uint(wg ? o[3] : o[35]));
            }
#pragma unroll
            for (int r = 0; r < 32; r++) yb[r] = fmaf((r & 2) ? gb : ga, wg ? oc[32 + r] : oc[r], yb[r]);
            bar_named(1, 256);
            if (warp == 0) STAMP(8);
            uint32_t w[8][2];
#pragma unroll
            for (int nt = 0; nt < 8; nt++) {
                const uint4 p = lds128(xr + nt * 2048);
                w[nt][0] = pack2(fmaf(ga, __uint_as_float(p.x), yb[4 * nt]), fmaf(ga, __uint_as_float(p.y), yb[4 * nt + 1]));
                w[nt][1] = pack2(fmaf(gb, __uint_as_float(p.z), yb[4 * nt + 2]), fmaf(gb, __uint_as_float(p.w), yb[4 * nt + 3]));
            }
            const uint32_t ob = sb + wg * 2 * SLOT + 16384 + w4 * 2048;
#pragma unroll
            for (int nt = 0; nt < 8; nt += 2)
                stsm4(ob + (lane & 15) * 128 + (((nt + shi) ^ (lane & 7)) << 4), w[nt][0], w[nt][1], w[nt + 1][0], w[nt + 1][1]);
            __syncwarp();
            bf16* op = out + (size_t)(slab * 16) * 512 + (bi_j & 3) * 128 + wg * 64 + (lane & 7) * 8;
#pragma unroll
            for (int it = 0; it < 4; it++) {
                const int r = it * 4 + (lane >> 3);
                uint4 v = lds128(ob + r * 128 + (((lane & 7) ^ (r & 7)) << 4));
                *(uint4*)(op + r * 512) = v;
            }
        }
        if (warp == 0) STAMP(10);
    } else if (warp < 12) {
#pragma unroll
        for (int src = 2; src >= 0; src--) {
            if (src != 0) mbar_wait(bar + 8 * (src == 2 ? BAR_KGA : BAR_KG), 0);
#pragma unroll
            for (int t = 0; t < 6; t++) {
                const uint4 v = lds128(stg_of(w4 + src * 4) + (t * 32 + lane) * 16);
                kc[4 * t] += __uint_as_float(v.x); kc[4 * t + 1] += __uint_as_float(v.y); kc[4 * t + 2] += __uint_as_float(v.z); kc[4 * t + 3] += __uint_as_float(v.w);
            }
            if (src != 1) {
                bar_named(2, 128);
                if (st == 0) { load_stage(src == 2 ? 2 : 3); if (src == 0) mbar_arrive(bar + 8 * BAR_SP); }
                if (warp == 8) STAMP(src == 2 ? 22 : 17);
            }
        }
        if (warp == 8) {
#pragma unroll 1
            for (int kb = 0; kb < 6; kb++) {
                const int s = kb & 3;
                mbar_wait(bar + 8 * (BAR_EMPTY + s), kb >> 2);
                if (kb == xkb) mbar_wait(bar + 8 * BAR_XT, 0);
                if (lane == 0) {
                    STAMP(48 + kb);
                    if (kb < 4) load_stage(kb + 4);
                    else {
                        mbar_expect(bar + 8 * BAR_WO, 32768);
                        tma2d(sb + s * SLOT, &mwo, (bi_j & 3) * 128 + s * 64, 0, bar + 8 * BAR_WO);
                        if (kb == 5) mbar_arrive(bar + 8 * BAR_SP2);
                    }
                }
                __syncwarp();
            }
        } else if (warp == 9) {
            const int row = bi_j * 16 + (lane >> 1), half = lane & 1;
            unsigned* gp = scr->g + (bi_i * 64 + bi_j * 8) * 8 + lane * 2;
            st_rlx64(gp, tag ^ 1u, tag ^ 1u);
            if (lane < 8) st_rlx32(scr->yflag + bi * 8 + lane, tag ^ 1u);
            float gs0 = 0.f, gs1 = 0.f;
            mbar_wait(bar + 8 * BAR_WPHI, 0);
#pragma unroll 1
            for (int kb = 0; kb < 8; kb++) {
                const int s = kb & 3;
                mbar_wait(bar + 8 * (BAR_FULL + s), kb >> 2);
#pragma unroll
                for (int c = 0; c < 4; c++) {
                    const uint4 xv = lds128(sb + s * SLOT + row * 128 + (((half * 4 + c) ^ (row & 7)) << 4));
                    const uint4 gw = lds128(sb + OFF_GW + ((kb + rot) & 7) * 128 + half * 64 + c * 16);
                    const uint32_t p0 = hmul2(xv.x, gw.x), p1 = hmul2(xv.y, gw.y), p2 = hmul2(xv.z, gw.z), p3 = hmul2(xv.w, gw.w);
                    gs0 += (bf_lo(p0) + bf_lo(p1)) + (bf_lo(p2) + bf_lo(p3));
                    gs1 += (bf_hi(p0) + bf_hi(p1)) + (bf_hi(p2) + bf_hi(p3));
                }
                asm volatile("" : "+f"(gs0), "+f"(gs1));
                __syncwarp();
                if (lane == 0) mbar_arrive(bar + 8 * (kb < 7 ? BAR_EMPTY + s : BAR_DONE));
            }
            float gs = gs0 + gs1;
            gs += __shfl_xor_sync(~0u, gs, 1);
            const uint32_t gv = __float_as_uint(bf_round(rcp(1.0f + ex2(-1.4426950408889634f * bf_round(gs))))) | tag;
            st_rlx64(gp, gv, gv);
        }
        if (lane == 0) kc[4 * 0 + 0] += ((ch & 1) ? bf_hi(pds) : bf_lo(pds));
        const uint32_t k1024 = __shfl_sync(~0u, pack2(kc[4 * 4 + 0], 0.f), 0);
#pragma unroll
        for (int i = 0; i < 2; i++) {
            const int be = g + 8 * i;
#pragma unroll
            for (int t = 0; t < 2; t++) {
                const uint32_t a = kb_ + (KW_D + 128 * t + 8 * be + 2 * q) * 4;
                const uint32_t w = pack2(kc[4 * t + 2 * i + 1], kc[4 * t + 2 * i]);
                sts32(a + 4, w); sts16(a, w >> 16); sts16(a + 10, w);
            }
            {
                const int p = 256 + 128 * (q >> 1) + 8 * be + 4 * (q & 1);
                const uint32_t a = kb_ + (KW_D + p) * 4;
                const uint32_t w = pack2(kc[4 * 2 + 2 * i + 1], kc[4 * 2 + 2 * i]);
                const uint32_t aa = (w >> 16) | (w & 0xffff0000u);
                if (p != 256) { sts16(a - 4, aa); sts32(a, aa); } else sts16(a, aa);
                sts32(a + 4, aa); sts32(a + 8, w); sts16(a + 14, w);
            }
            {
                const int k = 64 + 16 * q + be;
                const uint32_t w = pack2(kc[4 * 3 + 2 * i], kc[4 * 3 + 2 * i + 1]);
                if (k != 64) sts16(kb_ + (KW_2 + ((k - 1) >> 1) - 24) * 4 + (k & 1) * 2, w);
                else {
                    const uint32_t a = kb_ + (KW_D + 511) * 4, aa = (w << 16) | (w & 0xffffu);
                    sts16(a, w); sts32(a + 4, aa); sts32(a + 8, aa); sts32(a + 12, aa); sts16(a + 18, w);
                }
                sts16(kb_ + (KW_2 + 48 + (k >> 1) - 24) * 4 + ((k & 1) ^ 1) * 2, w >> 16);
            }
#pragma unroll
            for (int b = 0; b < 2; b++) {
                const int k = 64 + 8 * (2 * q + b) + (be >> 1);
                const uint32_t w = pack2(kc[4 * 4 + 2 * i + b], 0.f);
                if (!(be & 1) && k == 64) sts16(kb_ + (KW_2 + 63 - 24) * 4, w);
                else {
                    const uint32_t a = kb_ + (KW_3 + ((be & 1) ? 80 + k : k - 1) - 48) * 4;
                    sts16(a, w);
                    if (!((be & 1) && k == 127)) sts16(a + 6, w);
                }
            }
        }
        if (lane == 0) sts16(kb_ + (KW_3 + 127 - 48) * 4, pack2(kc[4 * 5 + 0], 0.f));
        __syncwarp();
        mbar_wait(bar + 8 * BAR_UR, 0);
        mbar_wait(bar + 8 * CONV_START, 0);
        if (warp == 8) STAMP(23);
        float y[16][4];
#pragma unroll
        for (int nt = 0; nt < 16; nt++) { y[nt][0] = y[nt][1] = y[nt][2] = y[nt][3] = 0.f; }
        {
            uint32_t Bp[32], A[4][3], An[4][3];
            auto uaddr = [&](int rho) { const int R0 = (lane >> 4) * 64 + (lane & 7) - rho; return ub + (((2 * R0 + ((lane >> 3) & 1)) ^ ((R0 >> 2) & 1)) << 4); };
            const uint32_t kd = kb_ + (KW_D + g - 2 * q) * 4;
#pragma unroll 1
            for (int rho = 1; rho >= 0; rho--) {
                const uint32_t a = uaddr(rho), k = kd + 2048 + rho * 64;
#pragma unroll
                for (int i = 0; i < 8; i++) ldsm4(Bp + 4 * i, a + i * 256);
                const uint32_t a0 = lds32(k), a1 = lds32(k + 32), a2 = lds32(k - 32);
#pragma unroll
                for (int i = 0; i < 12; i++) mma16816(y[i + 4], a0, a1, a2, a0, Bp[4 * (i & 7) + 2 * (i >> 3)], Bp[4 * (i & 7) + 2 * (i >> 3) + 1]);
            }
#pragma unroll
            for (int ga = 0; ga < 4; ga++) { An[ga][0] = lds32(kd + ga * 512); An[ga][1] = lds32(kd + ga * 512 + 32); An[ga][2] = lds32(kd + ga * 512 - 32); }
#pragma unroll 1
            for (int rho = 0; rho < 8; rho++) {
#pragma unroll
                for (int ga = 0; ga < 4; ga++) {
                    const uint32_t a = kd + (rho + 1) * 64 + ga * 512;
                    A[ga][0] = An[ga][0]; A[ga][1] = An[ga][1]; A[ga][2] = An[ga][2];
                    An[ga][0] = lds32(a); An[ga][1] = lds32(a + 32); An[ga][2] = lds32(a - 32);
                }
                const uint32_t an = uaddr(rho + 1);
#pragma unroll
                for (int i = 0; i < 8; i++) {
#pragma unroll
                    for (int ga = 0; ga < 4; ga++) {
                        mma16816(y[i + ga], A[ga][0], A[ga][1], A[ga][2], A[ga][0], Bp[4 * i], Bp[4 * i + 1]);
                        if (i + 8 + ga < 16) mma16816(y[i + 8 + ga], A[ga][0], A[ga][1], A[ga][2], A[ga][0], Bp[4 * i + 2], Bp[4 * i + 3]);
                    }
                    ldsm4(Bp + 4 * i, an + i * 256);
                    __syncwarp();
                }
            }
        }
        if (warp == 8) STAMP(18);
        mbar_wait(bar + 8 * BAR_WR, 0);
#pragma unroll 1
        for (int ph = 0; ph < 2; ph++) {
            uint32_t B[5][2];
            const uint32_t ka = kb_ + (KW_2 + ph * 48 + 8 + g - q) * 4;
#pragma unroll
            for (int dd = 0; dd < 5; dd++) { B[dd][0] = lds32(ka + dd * 32); B[dd][1] = lds32(ka + dd * 32 - 16); }
            const uint32_t wa = buf + ph * W3_OFF + ((lane & 7) + ((lane >> 3) & 1) + (lane >> 4) * 8) * 16;
#pragma unroll
            for (int s = 0; s < 12; s++) {
                uint32_t A[4];
                ldsm4t(A, wa + s * 256);
#pragma unroll
                for (int dd = 0; dd < 5; dd++)
                    if (s + 4 + dd < 16) mma16816(y[s + 4 + dd], A[0], A[1], A[2], A[3], B[dd][0], B[dd][1]);
            }
        }
        {
            const int ap = (lane & 7) + (lane >> 4) * 8;
            const uint32_t loff = ((2 * ap + ((lane >> 3) & 1)) ^ ((ap >> 2) & 1)) << 4;
#pragma unroll 1
            for (int ph = 0; ph < 2; ph++) {
                uint32_t B[8][2];
                const uint32_t wb = (ph ? spare : buf + W9_OFF) + loff;
                const uint32_t ka = kb_ + (KW_3 + ph * 80 + 16 + g - 2 * q) * 4;
#pragma unroll
                for (int dd = 0; dd < 8; dd++) { B[dd][0] = lds32(ka + dd * 32); B[dd][1] = lds32(ka + dd * 32 - 32); }
#pragma unroll
                for (int s = 0; s < 4; s++) {
                    uint32_t A[4];
                    ldsm4t(A, wb + s * 512);
#pragma unroll
                    for (int dd = 0; dd < 8; dd++)
                        if (8 + 2 * s + dd < 16) mma16816(y[8 + 2 * s + dd], A[0], A[1], A[2], A[3], B[dd][0], B[dd][1]);
                }
            }
            const uint32_t idw = (g == 2 * q) ? k1024 : ((g == 2 * q + 1) ? (k1024 << 16) : 0u);
#pragma unroll
            for (int s = 0; s < 4; s++) {
                uint32_t A[4];
                ldsm4t(A, spare + 2048 + loff + s * 512);
                mma16816(y[8 + 2 * s], A[0], A[1], A[2], A[3], idw, 0u);
                mma16816(y[9 + 2 * s], A[0], A[1], A[2], A[3], 0u, idw);
            }
        }
        __syncwarp();
        if (warp == 8) STAMP(19);
#pragma unroll
        for (int nt = 0; nt < 16; nt++)
#pragma unroll
            for (int b = 0; b < 2; b++) sts32(buf + ((8 * nt + 2 * q + b) * 8 + g) * 4, pack2(y[nt][b], y[nt][2 + b]));
        bar_named(2, 128);
        uint4* yp = scr->y + bi * 1024 + st;
#pragma unroll
        for (int v = 0; v < 8; v++) {
            const uint32_t a = sb + OFF_BUF + (st + 128 * v) * 4;
            const uint32_t w0 = lds32(a), w1 = lds32(a + BUF_STRIDE), w2 = lds32(a + 2 * BUF_STRIDE), w3 = lds32(a + 3 * BUF_STRIDE);
            st_rlx128(yp + v * 128, tag4(__byte_perm(w0, w1, 0x5410), __byte_perm(w0, w1, 0x7632), __byte_perm(w2, w3, 0x5410), __byte_perm(w2, w3, 0x7632), tag));
        }
        if (st < 8) st_rlx32(scr->yflag + bi * 8 + st, tag);
        if (warp == 8) STAMP(20);
    } else {
        asm volatile("setmaxnreg.dec.sync.aligned.u32 64;");
        const int qq = (bi_i & 2) + ((lane >> 1) & 1);
        uint2* kvf_h = (uint2*)(scr->kvf + (bi_j * 4 + (bi_i >> 2)) * 68);
        auto windows = [&](int rhi, int rlo) {
#pragma unroll 1
            for (int rho = rhi; rho >= rlo; rho--) {
                const int ci = lane + 32 * rho;
                uint4 e4[4];
#pragma unroll
                for (int v = 0; v < 4; v++) { const int cc = ci - 3 + v; e4[v] = lds128(ub + ((cc ^ ((cc >> 3) & 1)) << 4)); }
                float S[29];
                const uint32_t* ew = (const uint32_t*)e4;
                S[3] = 0.f;
#pragma unroll
                for (int k = 4; k <= 28; k++) S[k] = S[k - 1] + ((k & 1) ? bf_hi(ew[k >> 1]) : bf_lo(ew[k >> 1]));
                auto win = [&](int lo, int hi, uint32_t a) {
                    sts128(a, pack2(S[hi] - S[lo - 1], S[hi + 1] - S[lo]), pack2(S[hi + 2] - S[lo + 1], S[hi + 3] - S[lo + 2]),
                           pack2(S[hi + 4] - S[lo + 3], S[hi + 5] - S[lo + 4]), pack2(S[hi + 6] - S[lo + 5], S[hi + 7] - S[lo + 6]));
                };
                win(14, 18, buf + W5_OFF + 16 + ci * 16); win(19, 21, buf + W3_OFF + 16 + ci * 16);
                if (rho < 4) {
                    const uint32_t sw = (ci ^ ((ci >> 3) & 1)) << 4;
                    win(4, 12, buf + W9_OFF + sw); win(13, 19, spare + sw); win(20, 21, spare + 2048 + sw);
                }
            }
        };
        {
            mbar_wait(bar + 8 * (BAR_FULL + xkb), 0);
#pragma unroll 1
            for (int hf = 0; hf < 2; hf++) {
                const int r = w4 * 32 + hf * 16 + (lane & 15);
                uint32_t* xt = (uint32_t*)scr->xt + ((xkb + rot) * 16 + (g >> 2)) * 4096 + (bi_i * 16 + w4 * 4 + hf * 2) * 16 + (g & 3) * 4 + q;
#pragma unroll
                for (int cb = 0; cb < 8; cb += 2) {
                    uint32_t v[4];
                    ldsm4t(v, sb + xkb * SLOT + r * 128 + (((cb + (lane >> 4)) ^ (r & 7)) << 4));
                    xt[cb * 8192] = v[0]; xt[cb * 8192 + 16] = v[1]; xt[cb * 8192 + 8192] = v[2]; xt[cb * 8192 + 8192 + 16] = v[3];
                }
            }
            __syncwarp();
            if (lane == 0) {
                mbar_arrive(bar + 8 * BAR_XT);
                STAMP(26);
                asm volatile("red.release.gpu.global.add.u32 [%0],2;" ::"l"(scr->xcnt + (xkb + rot) * 32) : "memory");
                STAMP(27);
            }
            __syncwarp();
            {
                const uint32_t old = tag ^ 1u;
                const uint4 z4 = make_uint4(old, 0, old, 0);
#pragma unroll
                for (int v = 0; v < 5; v++) if (v < 4 || st < 32) st_rlx128(scr->kvp + bi * 544 + v * 128 + st, z4);
                if (st < 16) st_rlx128(scr->o + ((bi_i * 8 + (st >> 1)) * 32 + bi_j * 4 + 3) * 32 + 30 + (st & 1), z4);
                if (lane < 8) st_rlx64(kvf_h + ((bi_i & 3) * 8 + w4 * 2 + (lane & 1)) * 4 + (lane >> 1), old, 0);
                if (st < 4 && !(bi_i & 1)) st_rlx64(kvf_h + (64 + qq) * 2 + (lane & 1), old, 0);
                __syncwarp();
                if (lane == 0) mbar_arrive(bar + 8 * BAR_PREP);
            }
            int n = 0;
#pragma unroll 1
            while (__any_sync(~0u, (int)(ld_acq(scr->xcnt + bi_j * 32) - (epoch1 << 7)) < 0)) { if (++n > SPIN_LIMIT) break; }
            if (warp == 12) STAMP(15);
            uint4 ur[8];
#pragma unroll
            for (int v = 0; v < 8; v++) ur[v] = __ldcg(scr->xt + bi * 1024 + st + 128 * v);
            mbar_wait(bar + 8 * BAR_SP, 0);
            if (lane < 16) sts128(ub - 256 + lane * 16, 0, 0, 0, 0);
            if (lane < 2) sts128(buf + lane * W3_OFF, 0, 0, 0, 0);
#pragma unroll
            for (int v = 0; v < 8; v++) {
                const int ci = (st >> 2) + 32 * v;
                sts128(sb + OFF_U + (st & 3) * U_STRIDE + 256 + ((ci ^ ((ci >> 3) & 1)) << 4), ur[v].x, ur[v].y, ur[v].z, ur[v].w);
            }
            __syncwarp();
            if (lane == 0) mbar_arrive(bar + 8 * BAR_UR);
            mbar_wait(bar + 8 * BAR_UR, 0);
            if (warp == 12) STAMP(16);
            windows(5, 4);
        }
        mbar_wait(bar + 8 * BAR_SP2, 0);
        windows(3, 0);
        __syncwarp();
        if (lane == 0) mbar_arrive(bar + 8 * BAR_WR);
        if (warp == 12) STAMP(24);
        {
            const bool zw = st < 32 && !(bi_i & 1);
            const uint4* src = scr->kvp + bi_j * (16 * 544) + (bi_i >> 2) * 136;
            const uint4* zsrc = src + (lane >> 2) * (2 * 544) + 128 + (lane & 1) * 4 + qq;
            src += (lane >> 3) * (4 * 544) + ((lane >> 1) & 3) * 32 + (bi_i & 3) * 8 + w4 * 2 + (lane & 1);
            mbar_wait(bar + 8 * BAR_PUB, 0);
            if (warp == 12) STAMP(12);
            __nanosleep(D1_NS);
            uint4 v[6];
#pragma unroll
            for (int k = 0; k < 6; k++) v[k] = make_uint4(tag ^ 1u, 0, 0, 0);
            int n = 0;
#pragma unroll 1
            while (true) {
#pragma unroll
                for (int k = 0; k < 6; k++) if ((bad4(v[k], tag) & 1) && (k < 4 || zw)) v[k] = ld_rlx128(k < 4 ? src + k * 544 : zsrc + (k - 4) * 544);
                if (!__any_sync(~0u, (bad4(v[0], tag) | bad4(v[1], tag) | bad4(v[2], tag) | bad4(v[3], tag) | (zw ? bad4(v[4], tag) | bad4(v[5], tag) : 0u)) & 1)) break;
                if (warp == 12 && n < 3) STAMP(54 + n);
                if (++n > SPIN_LIMIT) break;
                __nanosleep(POLL_NS);
            }
            if (warp == 12) STAMP(30);
            float f[8];
            const float* vf = (const float*)v;
#pragma unroll
            for (int r = 0; r < 4; r++) {
                f[r] = (vf[r] + vf[4 + r]) + (vf[8 + r] + vf[12 + r]);
                f[4 + r] = vf[16 + r] + vf[20 + r];
                f[4 + r] += __shfl_xor_sync(~0u, f[4 + r], 4);
            }
#pragma unroll
            for (int o = 8; o <= 16; o <<= 1)
#pragma unroll
                for (int r = 0; r < 8; r++) f[r] += __shfl_xor_sync(~0u, f[r], o);
            if (lane < 8) st_rlx64(kvf_h + ((bi_i & 3) * 8 + w4 * 2 + (lane & 1)) * 4 + (lane >> 1), tagw(pack2(f[0], f[1]), tag), pack2(f[2], f[3]));
            if (zw && lane < 4) st_rlx64(kvf_h + (64 + qq) * 2 + (lane & 1), tagw(pack2(f[4], f[5]), tag), pack2(f[6], f[7]));
        }
        if (warp == 12) STAMP(13);
        {
            const uint4* kp = scr->kvf + bi_j * 272 + st;
            __nanosleep(D2_NS);
            uint4 v0 = make_uint4(tag ^ 1u, 0, 0, 0), v1 = v0, v2 = make_uint4(st < 16 ? tag ^ 1u : tag, 0, tag, 0);
            int n = 0;
#pragma unroll 1
            while (true) {
                if (bad4(v0, tag) & 1) v0 = ld_rlx128(kp);
                if (bad4(v1, tag) & 1) v1 = ld_rlx128(kp + 128);
                if (bad4(v2, tag) & 1) v2 = ld_rlx128(kp + 256);
                if (!__any_sync(~0u, (bad4(v0, tag) | bad4(v1, tag) | bad4(v2, tag)) & 1)) break;
                if (++n > SPIN_LIMIT) break;
                __nanosleep(POLL_NS);
            }
            sts128(sb + OFF_KVF + st * 16, v0.x, v0.y, v0.z, v0.w);
            sts128(sb + OFF_KVF + 2048 + st * 16, v1.x, v1.y, v1.z, v1.w);
            if (st < 16) sts128(sb + OFF_KVF + 4096 + st * 16, v2.x, v2.y, v2.z, v2.w);
            __syncwarp();
            if (lane == 0) mbar_arrive(bar + 8 * BAR_KVF);
        }
        if (warp == 13) {
            mbar_wait(bar + 8 * BAR_KVF, 0);
            if (lane == 0) {
                mbar_expect(bar + 8 * BAR_WO2, 65536);
                tma2d(sb + OFF_P, &mwo, (bi_j & 3) * 128, 256, bar + 8 * BAR_WO2);
                tma2d(sb + OFF_V, &mwo, (bi_j & 3) * 128 + 64, 256, bar + 8 * BAR_WO2);
            }
        }
        if (warp == 12) STAMP(25);
    }
    __syncwarp();
    if (lane == 0) {
        unsigned old;
        asm volatile("atom.acq_rel.cta.shared.add.u32 %0,[%1],1;" : "=r"(old) : "r"(bar + OFF_CNT) : "memory");
        if (old == 15) {
            atomicAdd(scr->done, 1u);
        }
    }
}

typedef CUresult (*EncFn)(CUtensorMap*, CUtensorMapDataType, cuuint32_t, void*, const cuuint64_t*, const cuuint64_t*, const cuuint32_t*,
                          const cuuint32_t*, CUtensorMapInterleave, CUtensorMapSwizzle, CUtensorMapL2promotion, CUtensorMapFloatOOBfill);

extern "C" void kernel_launch(void* const* d_in, const int* in_sizes, int n_in, void* d_out, int out_size) {
    static EncFn enc = nullptr;
    static Scratch* scr = nullptr;
    if (!enc) {
        cudaGetSymbolAddress((void**)&scr, g_scr);
        cudaDriverEntryPointQueryResult qr;
        cudaGetDriverEntryPoint("cuTensorMapEncodeTiled", (void**)&enc, cudaEnableDefault, &qr);
        cudaFuncSetAttribute(fused_kernel, cudaFuncAttributeMaxDynamicSharedMemorySize, SMEM_BYTES);
    }
    CUtensorMap mx, mw, mwo;
    const cuuint32_t es[3] = {1, 1, 1};
    {
        cuuint64_t d[2] = {512, 2048}, s[1] = {1024}; cuuint32_t b[2] = {64, 128};
        enc(&mx, CU_TENSOR_MAP_DATA_TYPE_BFLOAT16, 2, d_in[0], d, s, b, es, CU_TENSOR_MAP_INTERLEAVE_NONE, CU_TENSOR_MAP_SWIZZLE_128B,
            CU_TENSOR_MAP_L2_PROMOTION_L2_128B, CU_TENSOR_MAP_FLOAT_OOB_FILL_NONE);
    }
    {
        cuuint64_t d[3] = {512, 512, 3}, s[2] = {3072, 1024}; cuuint32_t b[3] = {64, 64, 3};
        enc(&mw, CU_TENSOR_MAP_DATA_TYPE_BFLOAT16, 3, d_in[1], d, s, b, es, CU_TENSOR_MAP_INTERLEAVE_NONE, CU_TENSOR_MAP_SWIZZLE_128B,
            CU_TENSOR_MAP_L2_PROMOTION_L2_128B, CU_TENSOR_MAP_FLOAT_OOB_FILL_NONE);
    }
    {
        cuuint64_t d[2] = {512, 512}, s[1] = {1024}; cuuint32_t b[2] = {64, 256};
        enc(&mwo, CU_TENSOR_MAP_DATA_TYPE_BFLOAT16, 2, d_in[3], d, s, b, es, CU_TENSOR_MAP_INTERLEAVE_NONE, CU_TENSOR_MAP_SWIZZLE_128B,
            CU_TENSOR_MAP_L2_PROMOTION_L2_128B, CU_TENSOR_MAP_FLOAT_OOB_FILL_NONE);
    }
    fused_kernel<<<128, 512, SMEM_BYTES, cudaStreamPerThread>>>(
        scr, (const bf16*)d_in[5], (const bf16*)d_in[6], (const bf16*)d_in[7], (const bf16*)d_in[8], (const bf16*)d_in[9],
        (const bf16*)d_in[10], (const bf16*)d_in[2], (const bf16*)d_in[11], (bf16*)d_out, mx, mw, mwo);
}
```

```cpp
#include <cuda_runtime.h>
#include <cuda.h>
#include <cuda_bf16.h>
#include <stdint.h>

typedef __nv_bfloat16 bf16;

struct Scratch {
    uint4 xt[128 * 1024];
    uint4 o[16 * 8 * 32 * 32];
    uint4 y[128 * 1024];
    uint4 kvp[8 * 16 * 544];
    uint4 kvf[8 * 4 * 68];
    unsigned g[1024 * 8];
    unsigned yflag[128 * 8];
    unsigned xcnt[8 * 32];
    unsigned done[32];
};
__device__ Scratch g_scr;
#define STAMP(n)

constexpr int SLOT = 40960;
constexpr int OFF_SP0 = 32768, OFF_SP1 = SLOT + 32768;
constexpr int OFF_P = 2 * SLOT, OFF_V = OFF_P + 32768;
constexpr int OFF_KVF = OFF_V + 32768;
constexpr int KT_BYTES = 3264, KW_D = 16, KW_2 = 560, KW_3 = 656;
constexpr int OFF_U = 4 * SLOT, U_STRIDE = 4096 + 256 + 32;
constexpr int OFF_BUF = OFF_U + 4 * U_STRIDE, BUF_STRIDE = 8320;
constexpr int OFF_K = OFF_BUF + 4 * BUF_STRIDE;
constexpr int OFF_WPHI = OFF_K + 4 * KT_BYTES;
constexpr int OFF_GW = OFF_WPHI + 2048;
constexpr int OFF_BAR = OFF_GW + 1024;
constexpr int SMEM_BYTES = OFF_BAR + 256 + 256;
static_assert(SMEM_BYTES <= 232448 && OFF_BUF % 128 == 0, "smem");
constexpr int W5_OFF = 0, W3_OFF = 3088, W9_OFF = 6176;
constexpr int BAR_FULL = 0, BAR_EMPTY = 4, BAR_WPHI = 8, BAR_WO = 9, BAR_WO2 = 10, BAR_XT = 11, BAR_DONE = 12, BAR_KG = 13, BAR_SP = 14,
              BAR_PUB = 15, BAR_KVF = 16, BAR_UR = 17, BAR_WR = 18, BAR_PREP = 19, BAR_KGA = 20, BAR_SP2 = 21, BAR_GO = 22, BAR_TL = 23, BAR_TC = 24, OFF_CNT = 240;
#define CONV_START BAR_DONE
#define D1_NS 0
#define D2_NS 0
#define D3_NS 100
#define PS_NS 100
#define POLL_NS 0
constexpr int SPIN_LIMIT = 1 << 17;

__device__ __forceinline__ uint32_t s2u(const void* p) { return (uint32_t)__cvta_generic_to_shared(p); }
__device__ __forceinline__ void mbar_init(uint32_t b, int c) { asm volatile("mbarrier.init.shared::cta.b64 [%0],%1;" ::"r"(b), "r"(c) : "memory"); }
__device__ __forceinline__ void mbar_expect(uint32_t b, int bytes) { asm volatile("mbarrier.arrive.expect_tx.shared::cta.b64 _,[%0],%1;" ::"r"(b), "r"(bytes) : "memory"); }
__device__ __forceinline__ void mbar_arrive(uint32_t b) { asm volatile("mbarrier.arrive.shared::cta.b64 _,[%0];" ::"r"(b) : "memory"); }
__device__ __forceinline__ void mbar_wait(uint32_t b, int ph) {
    asm volatile("{\n.reg .pred p;\n.reg .u32 n;\nmov.u32 n,0;\nLW_%=:\nmbarrier.try_wait.parity.shared::cta.b64 p,[%0],%1;\n@p bra LD_%=;\n"
                 "add.u32 n,n,1;\nsetp.lt.u32 p,n,16384;\n@p bra LW_%=;\nLD_%=:\n}" ::"r"(b), "r"(ph) : "memory");
}
__device__ __forceinline__ void tma2d(uint32_t dst, const CUtensorMap* m, int c0, int c1, uint32_t bar) {
    asm volatile("cp.async.bulk.tensor.2d.shared::cluster.global.mbarrier::complete_tx::bytes [%0],[%1,{%3,%4}],[%2];" ::"r"(dst), "l"(m), "r"(bar), "r"(c0), "r"(c1) : "memory");
}
__device__ __forceinline__ void tma3d(uint32_t dst, const CUtensorMap* m, int c0, int c1, int c2, uint32_t bar) {
    asm volatile("cp.async.bulk.tensor.3d.shared::cluster.global.mbarrier::complete_tx::bytes [%0],[%1,{%3,%4,%5}],[%2];" ::"r"(dst), "l"(m), "r"(bar), "r"(c0), "r"(c1), "r"(c2) : "memory");
}
__device__ __forceinline__ void bulk_g2s(uint32_t dst, const void* src, int bytes, uint32_t bar) {
    asm volatile("cp.async.bulk.shared::cluster.global.mbarrier::complete_tx::bytes [%0],[%1],%2,[%3];" ::"r"(dst), "l"(src), "r"(bytes), "r"(bar) : "memory");
}
__device__ __forceinline__ uint64_t mkdesc(uint32_t addr, uint32_t lbo, uint32_t sbo) {
    return (uint64_t)((addr & 0x3FFFF) >> 4) | ((uint64_t)(lbo >> 4) << 16) | ((uint64_t)(sbo >> 4) << 32) | ((uint64_t)1 << 62);
}
__device__ __forceinline__ void wg_fence() { asm volatile("wgmma.fence.sync.aligned;" ::: "memory"); }
__device__ __forceinline__ void wg_commit() { asm volatile("wgmma.commit_group.sync.aligned;" ::: "memory"); }
template <int N> __device__ __forceinline__ void wg_wait() { asm volatile("wgmma.wait_group.sync.aligned %0;" ::"n"(N) : "memory"); }
template <int N> __device__ __forceinline__ void fence_regs(float* d) {
#pragma unroll
    for (int i = 0; i < N; i++) asm volatile("" : "+f"(d[i])::"memory");
}
#define R8(d, o) "+f"(d[o]), "+f"(d[o + 1]), "+f"(d[o + 2]), "+f"(d[o + 3]), "+f"(d[o + 4]), "+f"(d[o + 5]), "+f"(d[o + 6]), "+f"(d[o + 7])
__device__ __forceinline__ void wgmma192(float* d, uint64_t da, uint64_t db) {
    asm volatile("wgmma.mma_async.sync.aligned.m64n192k16.f32.bf16.bf16 {"
                 "%0,%1,%2,%3,%4,%5,%6,%7,%8,%9,%10,%11,%12,%13,%14,%15,%16,%17,%18,%19,%20,%21,%22,%23,%24,%25,%26,%27,%28,%29,%30,%31,"
                 "%32,%33,%34,%35,%36,%37,%38,%39,%40,%41,%42,%43,%44,%45,%46,%47,%48,%49,%50,%51,%52,%53,%54,%55,%56,%57,%58,%59,%60,%61,%62,%63,"
                 "%64,%65,%66,%67,%68,%69,%70,%71,%72,%73,%74,%75,%76,%77,%78,%79,%80,%81,%82,%83,%84,%85,%86,%87,%88,%89,%90,%91,%92,%93,%94,%95},"
                 "%96,%97,1,1,1,0,1;"
                 : R8(d, 0), R8(d, 8), R8(d, 16), R8(d, 24), R8(d, 32), R8(d, 40), R8(d, 48), R8(d, 56), R8(d, 64), R8(d, 72), R8(d, 80), R8(d, 88)
                 : "l"(da), "l"(db));
}
__device__ __forceinline__ void wgmma64_tt(float* d, uint64_t da, uint64_t db, int sc) {
    asm volatile("{.reg .pred p; setp.ne.b32 p,%34,0; wgmma.mma_async.sync.aligned.m64n64k16.f32.bf16.bf16 {"
                 "%0,%1,%2,%3,%4,%5,%6,%7,%8,%9,%10,%11,%12,%13,%14,%15,%16,%17,%18,%19,%20,%21,%22,%23,%24,%25,%26,%27,%28,%29,%30,%31},"
                 "%32,%33,p,1,1,1,1;}"
                 : R8(d, 0), R8(d, 8), R8(d, 16), R8(d, 24)
                 : "l"(da), "l"(db), "r"(sc));
}
__device__ __forceinline__ void wgmma128_rs(float* d, const uint4& a, uint64_t db, int sc) {
    asm volatile("{.reg .pred p; setp.ne.b32 p,%69,0; wgmma.mma_async.sync.aligned.m64n128k16.f32.bf16.bf16 {"
                 "%0,%1,%2,%3,%4,%5,%6,%7,%8,%9,%10,%11,%12,%13,%14,%15,%16,%17,%18,%19,%20,%21,%22,%23,%24,%25,%26,%27,%28,%29,%30,%31,"
                 "%32,%33,%34,%35,%36,%37,%38,%39,%40,%41,%42,%43,%44,%45,%46,%47,%48,%49,%50,%51,%52,%53,%54,%55,%56,%57,%58,%59,%60,%61,%62,%63},"
                 "{%64,%65,%66,%67},%68,p,1,1,1;}"
                 : R8(d, 0), R8(d, 8), R8(d, 16), R8(d, 24), R8(d, 32), R8(d, 40), R8(d, 48), R8(d, 56)
                 : "r"(a.x), "r"(a.y), "r"(a.z), "r"(a.w), "l"(db), "r"(sc));
}
__device__ __forceinline__ void mma16816(float* c, uint32_t a0, uint32_t a1, uint32_t a2, uint32_t a3, uint32_t b0, uint32_t b1) {
    asm("mma.sync.aligned.m16n8k16.row.col.f32.bf16.bf16.f32 {%0,%1,%2,%3},{%4,%5,%6,%7},{%8,%9},{%0,%1,%2,%3};"
        : "+f"(c[0]), "+f"(c[1]), "+f"(c[2]), "+f"(c[3]) : "r"(a0), "r"(a1), "r"(a2), "r"(a3), "r"(b0), "r"(b1));
}
__device__ __forceinline__ void ldsm4(uint32_t* r, uint32_t a) {
    asm volatile("ldmatrix.sync.aligned.m8n8.x4.shared.b16 {%0,%1,%2,%3},[%4];" : "=r"(r[0]), "=r"(r[1]), "=r"(r[2]), "=r"(r[3]) : "r"(a) : "memory");
}
__device__ __forceinline__ void ldsm4t(uint32_t* r, uint32_t a) {
    asm volatile("ldmatrix.sync.aligned.m8n8.x4.trans.shared.b16 {%0,%1,%2,%3},[%4];" : "=r"(r[0]), "=r"(r[1]), "=r"(r[2]), "=r"(r[3]) : "r"(a) : "memory");
}
__device__ __forceinline__ void stsm4(uint32_t a, uint32_t r0, uint32_t r1, uint32_t r2, uint32_t r3) {
    asm volatile("stmatrix.sync.aligned.m8n8.x4.shared.b16 [%0],{%1,%2,%3,%4};" ::"r"(a), "r"(r0), "r"(r1), "r"(r2), "r"(r3) : "memory");
}
__device__ __forceinline__ uint32_t lds32(uint32_t a) { uint32_t v; asm volatile("ld.shared.b32 %0,[%1];" : "=r"(v) : "r"(a) : "memory"); return v; }
__device__ __forceinline__ uint4 lds128(uint32_t a) { uint4 v; asm volatile("ld.shared.v4.b32 {%0,%1,%2,%3},[%4];" : "=r"(v.x), "=r"(v.y), "=r"(v.z), "=r"(v.w) : "r"(a) : "memory"); return v; }
__device__ __forceinline__ void sts16(uint32_t a, uint32_t v) { asm volatile("st.shared.b16 [%0],%1;" ::"r"(a), "h"((unsigned short)v) : "memory"); }
__device__ __forceinline__ void sts32(uint32_t a, uint32_t v) { asm volatile("st.shared.b32 [%0],%1;" ::"r"(a), "r"(v) : "memory"); }
__device__ __forceinline__ void sts64(uint32_t a, uint32_t x, uint32_t y) { asm volatile("st.shared.v2.b32 [%0],{%1,%2};" ::"r"(a), "r"(x), "r"(y) : "memory"); }
__device__ __forceinline__ void sts128(uint32_t a, uint32_t x, uint32_t y, uint32_t z, uint32_t w) { asm volatile("st.shared.v4.b32 [%0],{%1,%2,%3,%4};" ::"r"(a), "r"(x), "r"(y), "r"(z), "r"(w) : "memory"); }
__device__ __forceinline__ uint32_t pack2(float lo, float hi) { uint32_t d; asm("cvt.rn.bf16x2.f32 %0,%1,%2;" : "=r"(d) : "f"(hi), "f"(lo)); return d; }
__device__ __forceinline__ float bf_lo(uint32_t v) { return __uint_as_float(v << 16); }
__device__ __forceinline__ float bf_hi(uint32_t v) { return __uint_as_float(v & 0xffff0000u); }
__device__ __forceinline__ float bf_round(float v) { return bf_lo(pack2(v, 0.f)); }
__device__ __forceinline__ uint32_t hmax2(uint32_t a, uint32_t b) { uint32_t d; asm("max.bf16x2 %0,%1,%2;" : "=r"(d) : "r"(a), "r"(b)); return d; }
__device__ __forceinline__ uint32_t hmin2(uint32_t a, uint32_t b) { uint32_t d; asm("min.bf16x2 %0,%1,%2;" : "=r"(d) : "r"(a), "r"(b)); return d; }
__device__ __forceinline__ uint32_t hmul2(uint32_t a, uint32_t b) { uint32_t d; asm("mul.rn.bf16x2 %0,%1,%2;" : "=r"(d) : "r"(a), "r"(b)); return d; }
__device__ __forceinline__ float ex2(float x) { float y; asm("ex2.approx.ftz.f32 %0,%1;" : "=f"(y) : "f"(x)); return y; }
__device__ __forceinline__ float rcp(float x) { float y; asm("rcp.approx.ftz.f32 %0,%1;" : "=f"(y) : "f"(x)); return y; }
__device__ __forceinline__ uint32_t ld_nc(const uint32_t* p) { uint32_t v; asm volatile("ld.global.nc.b32 %0,[%1];" : "=r"(v) : "l"(p)); return v; }
__device__ __forceinline__ uint2 ld_nc64(const uint2* p) { uint2 v; asm volatile("ld.global.nc.v2.b32 {%0,%1},[%2];" : "=r"(v.x), "=r"(v.y) : "l"(p)); return v; }
__device__ __forceinline__ unsigned ld_acq(const unsigned* p) { unsigned v; asm volatile("ld.acquire.gpu.global.u32 %0,[%1];" : "=r"(v) : "l"(p) : "memory"); return v; }
__device__ __forceinline__ unsigned ld_rlx(const unsigned* p) { unsigned v; asm volatile("ld.relaxed.gpu.global.u32 %0,[%1];" : "=r"(v) : "l"(p) : "memory"); return v; }
__device__ __forceinline__ uint2 ld_rlx64(const void* p) { uint2 v; asm volatile("{.reg .b64 t; ld.relaxed.gpu.global.b64 t,[%2]; mov.b64 {%0,%1},t;}" : "=r"(v.x), "=r"(v.y) : "l"(p) : "memory"); return v; }
__device__ __forceinline__ uint4 ld_rlx128(const void* p) {
    uint4 v;
    asm volatile("{.reg .b64 t,u; ld.relaxed.gpu.global.v2.b64 {t,u},[%4]; mov.b64 {%0,%1},t; mov.b64 {%2,%3},u;}" : "=r"(v.x), "=r"(v.y), "=r"(v.z), "=r"(v.w) : "l"(p) : "memory");
    return v;
}
__device__ __forceinline__ void st_rlx32(void* p, uint32_t x) { asm volatile("st.relaxed.gpu.global.u32 [%0],%1;" ::"l"(p), "r"(x) : "memory"); }
__device__ __forceinline__ void st_rlx64(void* p, uint32_t x, uint32_t y) { asm volatile("{.reg .b64 t; mov.b64 t,{%1,%2}; st.relaxed.gpu.global.b64 [%0],t;}" ::"l"(p), "r"(x), "r"(y) : "memory"); }
__device__ __forceinline__ void st_rlx128(void* p, uint4 v) {
    asm volatile("{.reg .b64 t,u; mov.b64 t,{%1,%2}; mov.b64 u,{%3,%4}; st.relaxed.gpu.global.v2.b64 [%0],{t,u};}" ::"l"(p), "r"(v.x), "r"(v.y), "r"(v.z), "r"(v.w) : "memory");
}
__device__ __forceinline__ uint32_t tagw(uint32_t w, uint32_t tag) { return (w & ~1u) | tag; }
__device__ __forceinline__ uint4 tag4(uint32_t x, uint32_t y, uint32_t z, uint32_t w, uint32_t tag) { return make_uint4(tagw(x, tag), y, tagw(z, tag), w); }
__device__ __forceinline__ uint32_t bad4(const uint4& v, uint32_t tag) { return (v.x ^ tag) | (v.z ^ tag); }
__device__ __forceinline__ void bar_named(int id, int n) { asm volatile("bar.sync %0,%1;" ::"r"(id), "r"(n) : "memory"); }

struct cf { float re, im; };
__device__ __forceinline__ cf cmul(cf a, cf b) { cf r; r.re = a.re * b.re - a.im * b.im; r.im = a.re * b.im + a.im * b.re; return r; }
__device__ __forceinline__ cf cexp_p(float arl, float ait, float p) {
    float mag = ex2(arl * p);
    float t = ait * p;
    t = (t - rintf(t)) * 6.283185307179586f;
    cf r; r.re = mag * __cosf(t); r.im = mag * __sinf(t);
    return r;
}

__device__ __forceinline__ void hedgehog4(const uint32_t* a, uint32_t wphi_addr, uint32_t (*out)[8]) {
    float p[4][2][4], mx[4][2];
#pragma unroll
    for (int h = 0; h < 4; h++) {
        uint32_t b[4];
        ldsm4t(b, wphi_addr + h * 512);
        float c0[4] = {0.f, 0.f, 0.f, 0.f}, c1[4] = {0.f, 0.f, 0.f, 0.f};
        mma16816(c0, a[4 * h], a[4 * h + 1], a[4 * h + 2], a[4 * h + 3], b[0], b[1]);
        mma16816(c1, a[4 * h], a[4 * h + 1], a[4 * h + 2], a[4 * h + 3], b[2], b[3]);
#pragma unroll
        for (int k = 0; k < 2; k++) {
            p[h][k][0] = c0[2 * k]; p[h][k][1] = c0[2 * k + 1]; p[h][k][2] = c1[2 * k]; p[h][k][3] = c1[2 * k + 1];
            mx[h][k] = fmaxf(fmaxf(p[h][k][0], p[h][k][1]), fmaxf(p[h][k][2], p[h][k][3]));
        }
    }
#pragma unroll
    for (int o = 1; o <= 2; o <<= 1)
#pragma unroll
        for (int h = 0; h < 4; h++)
#pragma unroll
            for (int k = 0; k < 2; k++) mx[h][k] = fmaxf(mx[h][k], __shfl_xor_sync(~0u, mx[h][k], o));
    const float L = 1.4426950408889634f;
    float pmin = 1.f;
#pragma unroll
    for (int h = 0; h < 4; h++)
#pragma unroll
        for (int k = 0; k < 2; k++) {
            const float m = -mx[h][k] * L;
            const float e0 = ex2(fmaf(p[h][k][0], L, m)), e1 = ex2(fmaf(p[h][k][1], L, m)), e2 = ex2(fmaf(p[h][k][2], L, m)), e3 = ex2(fmaf(p[h][k][3], L, m));
            const float p01 = e0 * e1, p23 = e2 * e3, pp = p01 * p23, r = rcp(pp), r01 = r * p23, r23 = r * p01;
            pmin = fminf(pmin, pp);
            out[h][k] = pack2(e0, e1); out[h][k + 2] = pack2(e2, e3);
            out[h][4 + k] = pack2(r01 * e1, r01 * e0); out[h][4 + k + 2] = pack2(r23 * e3, r23 * e2);
        }
    if (__builtin_expect(__any_sync(~0u, !(pmin > 1e-18f)), 0)) {
#pragma unroll
        for (int h = 0; h < 4; h++)
#pragma unroll
            for (int k = 0; k < 2; k++) {
                float m = fminf(fminf(p[h][k][0], p[h][k][1]), fminf(p[h][k][2], p[h][k][3]));
                m = fminf(m, __shfl_xor_sync(~0u, m, 1));
                m = fminf(m, __shfl_xor_sync(~0u, m, 2)) * L;
                out[h][4 + k] = pack2(ex2(fmaf(p[h][k][0], -L, m)), ex2(fmaf(p[h][k][1], -L, m)));
                out[h][4 + k + 2] = pack2(ex2(fmaf(p[h][k][2], -L, m)), ex2(fmaf(p[h][k][3], -L, m)));
            }
    }
}

__global__ void __launch_bounds__(512, 1)
fused_kernel(Scratch* __restrict__ scr, const bf16* __restrict__ logA, const bf16* __restrict__ Aim, const bf16* __restrict__ Cre,
             const bf16* __restrict__ Cim, const bf16* __restrict__ logdt, const bf16* __restrict__ Dskip, const bf16* __restrict__ wphi,
             const bf16* __restrict__ gatew, bf16* __restrict__ out,
             const __grid_constant__ CUtensorMap mx, const __grid_constant__ CUtensorMap mw, const __grid_constant__ CUtensorMap mwo) {
    extern __shared__ __align__(1024) uint8_t smem[];
    const uint32_t sb = s2u(smem);
    const int tid = threadIdx.x, warp = __shfl_sync(~0u, tid >> 5, 0), lane = tid & 31;
    const int g = lane >> 2, q = lane & 3, w4 = warp & 3;
    const int bi = blockIdx.x, bi_i = bi & 15, bi_j = bi >> 4;
    const uint32_t bar = sb + OFF_BAR;
    const int rot = (bi_j & 3) * 2, xkb = bi_j >> 2;
    auto load_stage = [&](int kb) {
        const uint32_t b = bar + 8 * (BAR_FULL + (kb & 3)), d = sb + (kb & 3) * SLOT;
        const int kc = ((kb + rot) & 7) * 64;
        mbar_expect(b, SLOT);
        tma2d(d, &mx, kc, bi_i * 128, b);
        tma3d(d + 16384, &mw, bi_j * 64, kc, 0, b);
    };

    const int ch = bi * 4 + w4;
    const int pidx = ch * 64 + lane * 2 + (warp >> 3);
    const uint32_t pla = ld_nc((const uint32_t*)logA + pidx), pai = ld_nc((const uint32_t*)Aim + pidx);
    const uint32_t pcr = ld_nc((const uint32_t*)Cre + pidx), pci = ld_nc((const uint32_t*)Cim + pidx);
    uint32_t pdt = ld_nc((const uint32_t*)logdt + (ch >> 1));
    const uint32_t pds = ld_nc((const uint32_t*)Dskip + (ch >> 1));
    unsigned done0 = ld_rlx(scr->done);
    if (tid == 0) {
        for (int s = 0; s < 4; s++) mbar_init(bar + 8 * (BAR_FULL + s), 1);
        asm volatile("fence.mbarrier_init.release.cluster;" ::: "memory");
        asm volatile("prefetch.tensormap [%0];" ::"l"(&mx) : "memory");
        load_stage(0); load_stage(1);
        STAMP(11);
    } else if (tid == 32) {
        if (sb & 1023) __trap();
        sts32(bar + OFF_CNT, 0);
        for (int s = 0; s < 4; s++) mbar_init(bar + 8 * (BAR_EMPTY + s), 9);
        mbar_init(bar + 8 * BAR_WPHI, 1); mbar_init(bar + 8 * BAR_WO, 2); mbar_init(bar + 8 * BAR_WO2, 1); mbar_init(bar + 8 * BAR_XT, 4);
        mbar_init(bar + 8 * BAR_DONE, 9); mbar_init(bar + 8 * BAR_KG, 8); mbar_init(bar + 8 * BAR_SP, 1); mbar_init(bar + 8 * BAR_PUB, 8);
        mbar_init(bar + 8 * BAR_KVF, 4); mbar_init(bar + 8 * BAR_UR, 4); mbar_init(bar + 8 * BAR_WR, 8); mbar_init(bar + 8 * BAR_PREP, 4); mbar_init(bar + 8 * BAR_KGA, 4); mbar_init(bar + 8 * BAR_SP2, 1); mbar_init(bar + 8 * BAR_GO, 8); mbar_init(bar + 8 * BAR_TL, 8); mbar_init(bar + 8 * BAR_TC, 4);
        asm volatile("fence.mbarrier_init.release.cluster;" ::: "memory");
        mbar_expect(bar + 8 * BAR_WPHI, 3072);
        bulk_g2s(sb + OFF_GW, gatew, 1024, bar + 8 * BAR_WPHI);
        bulk_g2s(sb + OFF_WPHI, wphi + bi_j * 1024, 2048, bar + 8 * BAR_WPHI);
    } else if (tid == 64) {
        asm volatile("prefetch.tensormap [%0];" ::"l"(&mw) : "memory");
    }
    const uint32_t buf = sb + OFF_BUF + w4 * BUF_STRIDE, kb_ = sb + OFF_K + w4 * KT_BYTES;
    if ((warp >> 2) == 2) {
#pragma unroll
        for (int v = 0; v < 7; v++) if (v * 32 + lane < KT_BYTES / 16) sts128(kb_ + (v * 32 + lane) * 16, 0, 0, 0, 0);
    }
    __syncthreads();
    asm volatile("" : "+r"(pdt), "+r"(done0)::"memory");
    const unsigned epoch1 = (done0 >> 7) + 1u;
    const uint32_t tag = epoch1 & 1u;

    const int st = tid & 127;
    const uint32_t ub = sb + OFF_U + w4 * U_STRIDE + 256, spare = sb + (w4 < 2 ? OFF_SP0 : OFF_SP1) + (w4 & 1) * 4096;

    auto stg_of = [&](int w) { return w < 8 ? sb + 3 * SLOT + w * 7296 : sb + 2 * SLOT + (w & 3) * 7296; };
    float kc[24];
#pragma unroll
    for (int t = 0; t < 24; t++) kc[t] = 0.f;
    {
        const float dt = bf_round(expf((ch & 1) ? bf_hi(pdt) : bf_lo(pdt)));
        const uint32_t stg = (warp >> 2) == 2 ? buf : stg_of(warp);
        const int sh = ((warp >> 2) & 1) * 16;
        auto pick = [&](uint32_t v) { return __uint_as_float((v >> sh) << 16); };
        const float ea = bf_round(ex2(pick(pla) * 1.4426950408889634f));
        const float arl = (-ea * dt) * 1.4426950408889634f, ait = (pick(pai) * dt) * 0.15915494309189535f;
        cf C2; C2.re = 2.0f * (pick(pcr) * dt); C2.im = 2.0f * (pick(pci) * dt);
        const cf z1 = cexp_p(arl, ait, 1.0f), z128 = cexp_p(arl, ait, 128.0f);
        cf z8 = cexp_p(arl, ait, 8.0f); z8.im = -z8.im;
        const uint32_t lp = stg + lane * 4;
        auto put = [&](int row, const cf& v) { sts32((lp ^ ((row & 7) << 4)) + row * 128, pack2(v.re, v.im)); };
        {
            const cf z16 = cmul(z8, z8);
            cf e; e.re = 1.f; e.im = 0.f;
            cf o = z8;
            put(0, e); put(1, o);
            e = z16; put(2, e);
#pragma unroll
            for (int b = 3; b < 16; b += 2) {
                o = cmul(o, z16); put(b, o);
                if (b + 1 < 16) { e = cmul(e, z16); put(b + 1, e); }
            }
        }
        cf h[8];
        h[0] = C2; put(16, h[0]);
        {
            const cf z2 = cmul(z1, z1);
            h[1] = cmul(h[0], z1);
#pragma unroll
            for (int r = 2; r < 8; r++) h[r] = cmul(h[r - 2], z2);
#pragma unroll
            for (int r = 1; r < 8; r++) put(16 + r, h[r]);
        }
#pragma unroll
        for (int r = 0; r < 8; r++) { h[r] = cmul(h[r], z128); put(24 + r, h[r]); }
#pragma unroll
        for (int al = 0; al < 2; al++)
#pragma unroll
            for (int r = 0; r < 4; r++) { h[2 * r] = cmul(h[2 * r], z128); put(32 + al * 4 + r, h[2 * r]); }
#pragma unroll
        for (int al = 0; al < 4; al++)
#pragma unroll
            for (int r = 0; r < 2; r++) { h[4 * r] = cmul(h[4 * r], z128); put(40 + al * 2 + r, h[4 * r]); }
#pragma unroll
        for (int al = 0; al < 9; al++) { h[0] = cmul(h[0], z128); put(48 + al, h[0]); }
        __syncwarp();
        const int lr = lane & 7, lm = lane >> 3;
#pragma unroll
        for (int kp = 0; kp < 2; kp++) {
            uint32_t a0[4], a1[4];
            ldsm4(a0, stg + ((lm & 1) * 8 + lr) * 128 + (((4 * kp + (lm >> 1)) ^ lr) << 4));
            ldsm4(a1, stg + ((lm & 1) * 8 + lr) * 128 + (((4 * kp + 2 + (lm >> 1)) ^ lr) << 4));
#pragma unroll
            for (int t = 0; t < 6; t++) {
                uint32_t b[4];
                ldsm4(b, stg + (16 + 8 * t + lr) * 128 + (((4 * kp + lm) ^ lr) << 4));
                mma16816(kc + 4 * t, a0[0], a0[1], a0[2], a0[3], b[0], b[1]);
                mma16816(kc + 4 * t, a1[0], a1[1], a1[2], a1[3], b[2], b[3]);
            }
        }
        __syncwarp();
        if ((warp >> 2) != 2) {
#pragma unroll
            for (int t = 0; t < 6; t++)
                sts128(stg + (t * 32 + lane) * 16, __float_as_uint(kc[4 * t]), __float_as_uint(kc[4 * t + 1]), __float_as_uint(kc[4 * t + 2]), __float_as_uint(kc[4 * t + 3]));
            asm volatile("fence.proxy.async.shared::cta;" ::: "memory");
            __syncwarp();
            if (lane == 0) mbar_arrive(bar + 8 * (warp < 8 ? BAR_KG : BAR_KGA));
        }
    }

    if (warp < 8) {
        asm volatile("setmaxnreg.inc.sync.aligned.u32 160;");
        const int wg = warp >> 2;
        if (warp == 0) STAMP(21);
        float acc[96];
        const int srow = warp * 16 + (lane & 15);
        const uint32_t srow_a = srow * 128;
        const int sx = srow & 7, shi = lane >> 4;
#pragma unroll
        for (int r = 0; r < 96; r++) acc[r] = 0.f;
        fence_regs<96>(acc);
        const uint64_t da0 = mkdesc(sb + wg * 8192, 16, 1024), db0 = mkdesc(sb + 16384, 8192, 1024);
#pragma unroll 1
        for (int kb = 0; kb < 8; kb++) {
            const int s = kb & 3;
            const uint64_t da = da0 + s * (SLOT >> 4), db = db0 + s * (SLOT >> 4);
            if (warp == 0) STAMP(40 + kb);
            mbar_wait(bar + 8 * (BAR_FULL + s), kb >> 2);
            if (warp == 0) STAMP(32 + kb);
            wg_fence();
#pragma unroll
            for (int k = 0; k < 4; k++) wgmma192(acc, da + 2 * k, db + 128 * k);
            wg_commit();
            wg_wait<1>();
            if (lane == 0 && kb > 0) mbar_arrive(bar + 8 * (BAR_EMPTY + ((kb - 1) & 3)));
        }
        mbar_wait(bar + 8 * BAR_WPHI, 0);
        wg_wait<0>();
        fence_regs<96>(acc);
        if (lane == 0) mbar_arrive(bar + 8 * BAR_DONE);
        if (warp == 0) STAMP(1);
        uint32_t in[16], qa[16];
        mbar_wait(bar + 8 * BAR_DONE, 0);
#pragma unroll
        for (int r = 0; r < 16; r++) {
            in[r] = pack2(acc[32 + 2 * r], acc[32 + 2 * r + 1]);
            qa[r] = pack2(acc[2 * r], acc[2 * r + 1]);
        }
#pragma unroll
        for (int hh = 0; hh < 4; hh++)
            stsm4(sb + OFF_V + (hh >> 1) * 16384 + srow_a + (((2 * (hh & 1) + shi) ^ sx) << 4), pack2(acc[64 + 8 * hh], acc[65 + 8 * hh]),
                  pack2(acc[66 + 8 * hh], acc[67 + 8 * hh]), pack2(acc[68 + 8 * hh], acc[69 + 8 * hh]), pack2(acc[70 + 8 * hh], acc[71 + 8 * hh]));
        sts128(sb + OFF_V + shi * 16384 + srow_a + ((4 ^ sx) << 4), 0x3f803f80u, 0x3f803f80u, 0x3f803f80u, 0x3f803f80u);
        const uint32_t wphi_a = sb + OFF_WPHI + (lane & 15) * 32 + (lane >> 4) * 16;
        uint32_t pq[4][8];
#pragma unroll 1
        for (int it = 0; it < 2; it++) {
            hedgehog4(in, wphi_a, pq);
            if (it == 1) break;
#pragma unroll
            for (int hs = 0; hs < 8; hs++) {
                float c[4] = {0.f, 0.f, 0.f, 0.f};
                const uint32_t* o = pq[hs >> 1] + 4 * (hs & 1);
                mma16816(c, o[0], o[1], o[2], o[3], 0x3f803f80u, 0x3f803f80u);
                const float r0 = rcp(c[0]), r1 = rcp(c[2]);
                const uint32_t s0 = pack2(r0, r0), s1 = pack2(r1, r1);
                stsm4(sb + OFF_P + (hs >> 2) * 16384 + srow_a + (((2 * (hs & 3) + shi) ^ sx) << 4), hmul2(o[0], s0), hmul2(o[1], s1), hmul2(o[2], s0), hmul2(o[3], s1));
            }
            asm volatile("fence.proxy.async.shared::cta;" ::: "memory");
            if (lane == 0) mbar_arrive(bar + 8 * BAR_GO);
            bar_named(1, 256);
            if (warp == 0) STAMP(2);
            float d[32];
            const uint64_t dv = mkdesc(sb + OFF_V + wg * 16384, 16, 1024), dp = mkdesc(sb + OFF_P + wg * 16384, 16, 1024);
            wg_fence();
#pragma unroll
            for (int k = 0; k < 8; k++) wgmma64_tt(d, dv + 128 * k, dp + 128 * k, k != 0);
            wg_commit();
            mbar_wait(bar + 8 * BAR_PREP, 0);
            uint4* kvp = scr->kvp + bi * 544 + wg * 272 + (w4 < 2 ? w4 * 136 : 128) + lane;
            wg_wait<0>();
            fence_regs<32>(d);
            if (w4 < 2 || (w4 == 2 && lane < 4)) {
#pragma unroll
                for (int f = 0; f < 4; f++) {
                    const int i0 = 8 * (f >> 1) + 2 * (f & 1), i2 = 16 * (f >> 1) + 8 * (f & 1);
                    const float e0 = w4 == 0 ? d[i0] : (w4 == 1 ? d[16 + i0] : d[i2]), e1 = w4 == 0 ? d[i0 + 1] : (w4 == 1 ? d[17 + i0] : d[i2 + 1]);
                    const float e2 = w4 == 0 ? d[i0 + 4] : (w4 == 1 ? d[20 + i0] : d[i2 + 4]), e3 = w4 == 0 ? d[i0 + 5] : (w4 == 1 ? d[21 + i0] : d[i2 + 5]);
                    st_rlx128(kvp + (w4 < 2 ? f * 32 : (f >> 1) * 136 + (f & 1) * 4), tag4(__float_as_uint(e0), __float_as_uint(e1), __float_as_uint(e2), __float_as_uint(e3), tag));
                }
            }
            __syncwarp();
            if (lane == 0) mbar_arrive(bar + 8 * BAR_PUB);
            if (warp == 0) STAMP(3);
#pragma unroll
            for (int r = 0; r < 16; r++) in[r] = qa[r];
        }
        if (warp == 0) STAMP(4);
        {
            float y[12][4];
#pragma unroll
            for (int nt = 0; nt < 12; nt++) { y[nt][0] = y[nt][1] = y[nt][2] = y[nt][3] = 0.f; }
            mbar_wait(bar + 8 * BAR_WR, 0);
            {
                uint32_t B[5][2];
                const uint32_t ka = kb_ + (KW_2 + wg * 48 + 8 + g - q) * 4;
#pragma unroll
                for (int dd = 0; dd < 5; dd++) { B[dd][0] = lds32(ka + dd * 32); B[dd][1] = lds32(ka + dd * 32 - 16); }
                const uint32_t wa = buf + wg * W3_OFF + ((lane & 7) + ((lane >> 3) & 1) + (lane >> 4) * 8) * 16;
#pragma unroll
                for (int s = 0; s < 12; s++) {
                    uint32_t A[4];
                    ldsm4t(A, wa + s * 256);
#pragma unroll
                    for (int dd = 0; dd < 5; dd++)
                        if (s + dd < 12) mma16816(y[s + dd], A[0], A[1], A[2], A[3], B[dd][0], B[dd][1]);
                }
            }
            {
                const int ap = (lane & 7) + (lane >> 4) * 8;
                const uint32_t loff = ((2 * ap + ((lane >> 3) & 1)) ^ ((ap >> 2) & 1)) << 4;
                uint32_t B[8][2];
                const uint32_t wb = (wg ? spare : buf + W9_OFF) + loff;
                const uint32_t ka = kb_ + (KW_3 + wg * 80 + 16 + g - 2 * q) * 4;
#pragma unroll
                for (int dd = 0; dd < 8; dd++) { B[dd][0] = lds32(ka + dd * 32); B[dd][1] = lds32(ka + dd * 32 - 32); }
#pragma unroll
                for (int s = 0; s < 4; s++) {
                    uint32_t A[4];
                    ldsm4t(A, wb + s * 512);
#pragma unroll
                    for (int dd = 0; dd < 8; dd++)
                        if (4 + 2 * s + dd < 12) mma16816(y[4 + 2 * s + dd], A[0], A[1], A[2], A[3], B[dd][0], B[dd][1]);
                }
                const uint32_t k1024 = lds32(kb_ + (KW_2 + 63 - 24) * 4) & 0xffffu;
                const uint32_t idw = (g == 2 * q) ? k1024 : ((g == 2 * q + 1) ? (k1024 << 16) : 0u);
#pragma unroll
                for (int s = 0; s < 2; s++) {
                    uint32_t A[4];
                    ldsm4t(A, spare + 2048 + loff + (2 * wg + s) * 512);
                    float c0[4] = {0.f, 0.f, 0.f, 0.f}, c1[4] = {0.f, 0.f, 0.f, 0.f};
                    mma16816(c0, A[0], A[1], A[2], A[3], idw, 0u);
                    mma16816(c1, A[0], A[1], A[2], A[3], 0u, idw);
#pragma unroll
                    for (int r = 0; r < 4; r++) {
                        y[4 + 2 * s][r] += wg ? 0.f : c0[r]; y[5 + 2 * s][r] += wg ? 0.f : c1[r];
                        y[8 + 2 * s][r] += wg ? c0[r] : 0.f; y[9 + 2 * s][r] += wg ? c1[r] : 0.f;
                    }
                }
            }
            mbar_wait(bar + 8 * BAR_PUB, 0);
#pragma unroll
            for (int t = 0; t < 12; t++)
                sts128(sb + OFF_P + warp * 6144 + (t * 32 + lane) * 16, __float_as_uint(y[t][0]), __float_as_uint(y[t][1]), __float_as_uint(y[t][2]), __float_as_uint(y[t][3]));
            asm volatile("fence.proxy.async.shared::cta;" ::: "memory");
            __syncwarp();
            if (lane == 0) mbar_arrive(bar + 8 * BAR_TL);
            if (warp == 0) STAMP(31);
        }
        {
            mbar_wait(bar + 8 * BAR_KVF, 0);
            uint4 kf[4][3];
#pragma unroll
            for (int hh = 0; hh < 4; hh++) {
                const uint32_t a = sb + OFF_KVF + hh * 1088;
                kf[hh][0] = lds128(a + lane * 32); kf[hh][1] = lds128(a + lane * 32 + 16); kf[hh][2] = lds128(a + 1024 + q * 16);
            }
            if (warp == 0) STAMP(5);
            uint4* og = scr->o + ((bi_i * 8 + warp) * 32 + bi_j * 4) * 32 + lane;
#pragma unroll
            for (int hh = 0; hh < 4; hh++) {
                float c[6][4];
#pragma unroll
                for (int t = 0; t < 6; t++) { c[t][0] = c[t][1] = c[t][2] = c[t][3] = 0.f; }
                const uint32_t* a = pq[hh];
                const bool od = g & 1;
                mma16816(c[0], a[0], a[1], a[2], a[3], od ? 0x3f803f80u : kf[hh][2].x, od ? 0x3f803f80u : kf[hh][2].y);
                mma16816(c[1], a[4], a[5], a[6], a[7], od ? 0x3f803f80u : kf[hh][2].z, od ? 0x3f803f80u : kf[hh][2].w);
                mma16816(c[2], a[0], a[1], a[2], a[3], kf[hh][0].x, kf[hh][0].y);
                mma16816(c[3], a[0], a[1], a[2], a[3], kf[hh][0].z, kf[hh][0].w);
                mma16816(c[4], a[4], a[5], a[6], a[7], kf[hh][1].x, kf[hh][1].y);
                mma16816(c[5], a[4], a[5], a[6], a[7], kf[hh][1].z, kf[hh][1].w);
                uint32_t w[4];
#pragma unroll
                for (int k = 0; k < 2; k++) {
                    const float rho = c[0][2 * k + 1] * rcp(c[1][2 * k + 1]);
                    const float r = rcp(fmaf(c[0][2 * k + 1], 1e-6f, fmaf(rho, c[1][2 * k], c[0][2 * k]))), rr = r * rho;
                    w[k] = pack2(fmaf(c[4][2 * k], rr, c[2][2 * k] * r), fmaf(c[4][2 * k + 1], rr, c[2][2 * k + 1] * r));
                    w[2 + k] = pack2(fmaf(c[5][2 * k], rr, c[3][2 * k] * r), fmaf(c[5][2 * k + 1], rr, c[3][2 * k + 1] * r));
                }
                st_rlx128(og + hh * 32, tag4(w[0], w[1], w[2], w[3], tag));
            }
        }
        if (warp == 0) STAMP(6);
        float oc[64];
        const int slab = bi_i * 8 + (bi_j >> 2) * 4 + w4;
        const uint8_t* ysrc = (const uint8_t*)scr->y + (size_t)((bi_j & 3) * 32 + wg * 16 + (q >> 1)) * 16384 + slab * 128 + g * 16 + (q & 1) * 8;
        const unsigned* gp = scr->g + (slab * 8 + (g >> 1)) * 8 + (g & 1) * 4;
        uint2 yv[8]; unsigned g0, g1;
        {
            const uint4* osrc = scr->o + (slab * 32 + wg * 16) * 32 + lane;
            uint4 fr[16];
            const unsigned* probe = (const unsigned*)(osrc - lane + ((lane & 3) * 4 + 3) * 32 + 31) + 2;
            {
                unsigned miss = ~0u;
                int n = 0;
#pragma unroll
                for (int s = 0; s < 4; s++) {
#pragma unroll 1
                    while ((miss >> s) & 1) { miss = __ballot_sync(~0u, (ld_rlx(probe) ^ tag) & 1); if (++n > SPIN_LIMIT) break; }
#pragma unroll
                    for (int k = 4 * s; k < 4 * s + 4; k++) fr[k] = ld_rlx128(osrc + k * 32);
                }
            }
            if (warp == 0) STAMP(14);
            mbar_wait(bar + 8 * (wg ? BAR_WO2 : BAR_WO), 0);
            const uint64_t dw = mkdesc(sb + wg * 2 * SLOT, wg ? 32768 : SLOT, 1024);
#pragma unroll
            for (int s = 0; s < 4; s++) {
                int n = 0;
#pragma unroll 1
                while (__builtin_expect(__any_sync(~0u, (bad4(fr[4 * s], tag) | bad4(fr[4 * s + 1], tag) | bad4(fr[4 * s + 2], tag) | bad4(fr[4 * s + 3], tag)) & 1), 0)) {
#pragma unroll
                    for (int k = 4 * s; k < 4 * s + 4; k++) fr[k] = ld_rlx128(osrc + k * 32);
                    if (++n > SPIN_LIMIT) break;
                }
                wg_fence();
#pragma unroll
                for (int hh = 0; hh < 4; hh++) wgmma128_rs(oc, fr[4 * s + hh], dw + 128 * (4 * s + hh), (s | hh) != 0);
                wg_commit();
                if (s == 1) {
                    wg_wait<1>();
#pragma unroll
                    for (int nt = 0; nt < 8; nt++) yv[nt] = ld_rlx64(ysrc + nt * 32768);
                    g0 = ld_rlx(gp); g1 = ld_rlx(gp + 32);
                }
            }
            if (warp == 0) STAMP(7);
            {
                const unsigned* yprobe = scr->yflag + ((bi_j & 3) * 32 + wg * 16 + (lane & 15)) * 8;
                int n = 0;
#pragma unroll 1
                while (true) {
                    uint32_t bad = (g0 ^ tag) | (g1 ^ tag);
#pragma unroll
                    for (int nt = 0; nt < 8; nt++) bad |= yv[nt].x ^ tag;
                    if (!__any_sync(~0u, bad & 1)) break;
#pragma unroll 1
                    while (__any_sync(~0u, (ld_rlx(yprobe) ^ tag) & 1)) { if (++n > SPIN_LIMIT) break; }
#pragma unroll
                    for (int nt = 0; nt < 8; nt++) yv[nt] = ld_rlx64(ysrc + nt * 32768);
                    g0 = ld_rlx(gp); g1 = ld_rlx(gp + 32);
                    if (++n > SPIN_LIMIT) break;
                }
            }
            if (warp == 0) STAMP(28);
        }
        {
            const float ga = bf_hi(g0), gb = bf_hi(g1);
            const float ha = bf_round(1.0f - ga), hb = bf_round(1.0f - gb);
            float yb[32];
#pragma unroll
            for (int nt = 0; nt < 8; nt++) {
                yb[4 * nt] = ha * bf_lo(yv[nt].x); yb[4 * nt + 1] = ha * bf_hi(yv[nt].x);
                yb[4 * nt + 2] = hb * bf_lo(yv[nt].y); yb[4 * nt + 3] = hb * bf_hi(yv[nt].y);
            }
            fence_regs<32>(yb);
            const uint32_t xw = sb + wg * 2 * SLOT + (tid & 127) * 16, xr = sb + (wg ^ 1) * 2 * SLOT + (tid & 127) * 16;
            wg_wait<0>();
            fence_regs<64>(oc);
            bar_named(3 + wg, 128);
#pragma unroll
            for (int r = 0; r < 8; r++) {
                const float* o = oc + 4 * r;
                sts128(xw + r * 2048, __float_as_uint(wg ? o[0] : o[32]), __float_as_uint(wg ? o[1] : o[33]), __float_as_uint(wg ? o[2] : o[34]), __float_as_uint(wg ? o[3] : o[35]));
            }
#pragma unroll
            for (int r = 0; r < 32; r++) yb[r] = fmaf((r & 2) ? gb : ga, wg ? oc[32 + r] : oc[r], yb[r]);
            bar_named(1, 256);
            if (warp == 0) STAMP(8);
            uint32_t w[8][2];
#pragma unroll
            for (int nt = 0; nt < 8; nt++) {
                const uint4 p = lds128(xr + nt * 2048);
                w[nt][0] = pack2(fmaf(ga, __uint_as_float(p.x), yb[4 * nt]), fmaf(ga, __uint_as_float(p.y), yb[4 * nt + 1]));
                w[nt][1] = pack2(fmaf(gb, __uint_as_float(p.z), yb[4 * nt + 2]), fmaf(gb, __uint_as_float(p.w), yb[4 * nt + 3]));
            }
            const uint32_t ob = sb + wg * 2 * SLOT + 16384 + w4 * 2048;
#pragma unroll
            for (int nt = 0; nt < 8; nt += 2)
                stsm4(ob + (lane & 15) * 128 + (((nt + shi) ^ (lane & 7)) << 4), w[nt][0], w[nt][1], w[nt + 1][0], w[nt + 1][1]);
            __syncwarp();
            bf16* op = out + (size_t)(slab * 16) * 512 + (bi_j & 3) * 128 + wg * 64 + (lane & 7) * 8;
#pragma unroll
            for (int it = 0; it < 4; it++) {
                const int r = it * 4 + (lane >> 3);
                uint4 v = lds128(ob + r * 128 + (((lane & 7) ^ (r & 7)) << 4));
                *(uint4*)(op + r * 512) = v;
            }
        }
        if (warp == 0) STAMP(10);
    } else if (warp < 12) {
#pragma unroll
        for (int src = 2; src >= 0; src--) {
            if (src != 0) mbar_wait(bar + 8 * (src == 2 ? BAR_KGA : BAR_KG), 0);
#pragma unroll
            for (int t = 0; t < 6; t++) {
                const uint4 v = lds128(stg_of(w4 + src * 4) + (t * 32 + lane) * 16);
                kc[4 * t] += __uint_as_float(v.x); kc[4 * t + 1] += __uint_as_float(v.y); kc[4 * t + 2] += __uint_as_float(v.z); kc[4 * t + 3] += __uint_as_float(v.w);
            }
            if (src != 1) {
                bar_named(2, 128);
                if (st == 0) { load_stage(src == 2 ? 2 : 3); if (src == 0) mbar_arrive(bar + 8 * BAR_SP); }
                if (warp == 8) STAMP(src == 2 ? 22 : 17);
            }
        }
        if (warp == 8) {
#pragma unroll 1
            for (int kb = 0; kb < 6; kb++) {
                const int s = kb & 3;
                mbar_wait(bar + 8 * (BAR_EMPTY + s), kb >> 2);
                if (kb == xkb) mbar_wait(bar + 8 * BAR_XT, 0);
                if (lane == 0) {
                    STAMP(48 + kb);
                    if (kb < 4) load_stage(kb + 4);
                    else {
                        mbar_expect(bar + 8 * BAR_WO, 32768);
                        tma2d(sb + s * SLOT, &mwo, (bi_j & 3) * 128 + s * 64, 0, bar + 8 * BAR_WO);
                        if (kb == 5) mbar_arrive(bar + 8 * BAR_SP2);
                    }
                }
                __syncwarp();
            }
        } else if (warp == 9) {
            const int row = bi_j * 16 + (lane >> 1), half = lane & 1;
            unsigned* gp = scr->g + (bi_i * 64 + bi_j * 8) * 8 + lane * 2;
            st_rlx64(gp, tag ^ 1u, tag ^ 1u);
            if (lane < 8) st_rlx32(scr->yflag + bi * 8 + lane, tag ^ 1u);
            float gs0 = 0.f, gs1 = 0.f;
            mbar_wait(bar + 8 * BAR_WPHI, 0);
#pragma unroll 1
            for (int kb = 0; kb < 8; kb++) {
                const int s = kb & 3;
                mbar_wait(bar + 8 * (BAR_FULL + s), kb >> 2);
#pragma unroll
                for (int c = 0; c < 4; c++) {
                    const uint4 xv = lds128(sb + s * SLOT + row * 128 + (((half * 4 + c) ^ (row & 7)) << 4));
                    const uint4 gw = lds128(sb + OFF_GW + ((kb + rot) & 7) * 128 + half * 64 + c * 16);
                    const uint32_t p0 = hmul2(xv.x, gw.x), p1 = hmul2(xv.y, gw.y), p2 = hmul2(xv.z, gw.z), p3 = hmul2(xv.w, gw.w);
                    gs0 += (bf_lo(p0) + bf_lo(p1)) + (bf_lo(p2) + bf_lo(p3));
                    gs1 += (bf_hi(p0) + bf_hi(p1)) + (bf_hi(p2) + bf_hi(p3));
                }
                asm volatile("" : "+f"(gs0), "+f"(gs1));
                __syncwarp();
                if (lane == 0) mbar_arrive(bar + 8 * (kb < 7 ? BAR_EMPTY + s : BAR_DONE));
            }
            float gs = gs0 + gs1;
            gs += __shfl_xor_sync(~0u, gs, 1);
            const uint32_t gv = __float_as_uint(bf_round(rcp(1.0f + ex2(-1.4426950408889634f * bf_round(gs))))) | tag;
            st_rlx64(gp, gv, gv);
        }
        if (lane == 0) kc[4 * 0 + 0] += ((ch & 1) ? bf_hi(pds) : bf_lo(pds));
#pragma unroll
        for (int i = 0; i < 2; i++) {
            const int be = g + 8 * i;
#pragma unroll
            for (int t = 0; t < 2; t++) {
                const uint32_t a = kb_ + (KW_D + 128 * t + 8 * be + 2 * q) * 4;
                const uint32_t w = pack2(kc[4 * t + 2 * i + 1], kc[4 * t + 2 * i]);
                sts32(a + 4, w); sts16(a, w >> 16); sts16(a + 10, w);
            }
            {
                const int p = 256 + 128 * (q >> 1) + 8 * be + 4 * (q & 1);
                const uint32_t a = kb_ + (KW_D + p) * 4;
                const uint32_t w = pack2(kc[4 * 2 + 2 * i + 1], kc[4 * 2 + 2 * i]);
                const uint32_t aa = (w >> 16) | (w & 0xffff0000u);
                if (p != 256) { sts16(a - 4, aa); sts32(a, aa); } else sts16(a, aa);
                sts32(a + 4, aa); sts32(a + 8, w); sts16(a + 14, w);
            }
            {
                const int k = 64 + 16 * q + be;
                const uint32_t w = pack2(kc[4 * 3 + 2 * i], kc[4 * 3 + 2 * i + 1]);
                if (k != 64) sts16(kb_ + (KW_2 + ((k - 1) >> 1) - 24) * 4 + (k & 1) * 2, w);
                else {
                    const uint32_t a = kb_ + (KW_D + 511) * 4, aa = (w << 16) | (w & 0xffffu);
                    sts16(a, w); sts32(a + 4, aa); sts32(a + 8, aa); sts32(a + 12, aa); sts16(a + 18, w);
                }
                sts16(kb_ + (KW_2 + 48 + (k >> 1) - 24) * 4 + ((k & 1) ^ 1) * 2, w >> 16);
            }
#pragma unroll
            for (int b = 0; b < 2; b++) {
                const int k = 64 + 8 * (2 * q + b) + (be >> 1);
                const uint32_t w = pack2(kc[4 * 4 + 2 * i + b], 0.f);
                if (!(be & 1) && k == 64) sts16(kb_ + (KW_2 + 63 - 24) * 4, w);
                else {
                    const uint32_t a = kb_ + (KW_3 + ((be & 1) ? 80 + k : k - 1) - 48) * 4;
                    sts16(a, w);
                    if (!((be & 1) && k == 127)) sts16(a + 6, w);
                }
            }
        }
        if (lane == 0) sts16(kb_ + (KW_3 + 127 - 48) * 4, pack2(kc[4 * 5 + 0], 0.f));
        __syncwarp();
        if (lane == 0) mbar_arrive(bar + 8 * BAR_WR);
        mbar_wait(bar + 8 * BAR_UR, 0);
        mbar_wait(bar + 8 * CONV_START, 0);
        if (warp == 8) STAMP(23);
        float y[16][4];
#pragma unroll
        for (int nt = 0; nt < 16; nt++) { y[nt][0] = y[nt][1] = y[nt][2] = y[nt][3] = 0.f; }
        {
            uint32_t Bp[32], A[4][3], An[4][3];
            auto uaddr = [&](int rho) { const int R0 = (lane >> 4) * 64 + (lane & 7) - rho; return ub + (((2 * R0 + ((lane >> 3) & 1)) ^ ((R0 >> 2) & 1)) << 4); };
            const uint32_t kd = kb_ + (KW_D + g - 2 * q) * 4;
#pragma unroll 1
            for (int rho = 1; rho >= 0; rho--) {
                const uint32_t a = uaddr(rho), k = kd + 2048 + rho * 64;
#pragma unroll
                for (int i = 0; i < 8; i++) ldsm4(Bp + 4 * i, a + i * 256);
                const uint32_t a0 = lds32(k), a1 = lds32(k + 32), a2 = lds32(k - 32);
#pragma unroll
                for (int i = 0; i < 12; i++) mma16816(y[i + 4], a0, a1, a2, a0, Bp[4 * (i & 7) + 2 * (i >> 3)], Bp[4 * (i & 7) + 2 * (i >> 3) + 1]);
            }
#pragma unroll
            for (int ga = 0; ga < 4; ga++) { An[ga][0] = lds32(kd + ga * 512); An[ga][1] = lds32(kd + ga * 512 + 32); An[ga][2] = lds32(kd + ga * 512 - 32); }
#pragma unroll 1
            for (int rho = 0; rho < 8; rho++) {
#pragma unroll
                for (int ga = 0; ga < 4; ga++) {
                    const uint32_t a = kd + (rho + 1) * 64 + ga * 512;
                    A[ga][0] = An[ga][0]; A[ga][1] = An[ga][1]; A[ga][2] = An[ga][2];
                    An[ga][0] = lds32(a); An[ga][1] = lds32(a + 32); An[ga][2] = lds32(a - 32);
                }
                const uint32_t an = uaddr(rho + 1);
#pragma unroll
                for (int i = 0; i < 8; i++) {
#pragma unroll
                    for (int ga = 0; ga < 4; ga++) {
                        mma16816(y[i + ga], A[ga][0], A[ga][1], A[ga][2], A[ga][0], Bp[4 * i], Bp[4 * i + 1]);
                        if (i + 8 + ga < 16) mma16816(y[i + 8 + ga], A[ga][0], A[ga][1], A[ga][2], A[ga][0], Bp[4 * i + 2], Bp[4 * i + 3]);
                    }
                    ldsm4(Bp + 4 * i, an + i * 256);
                    __syncwarp();
                }
            }
        }
        if (warp == 8) STAMP(18);
        mbar_wait(bar + 8 * BAR_TL, 0);
#pragma unroll
        for (int t = 0; t < 24; t++) {
            const uint4 v = lds128(sb + OFF_P + (w4 + 4 * (t / 12)) * 6144 + ((t % 12) * 32 + lane) * 16);
            float* o = y[4 + t % 12];
            o[0] += __uint_as_float(v.x); o[1] += __uint_as_float(v.y); o[2] += __uint_as_float(v.z); o[3] += __uint_as_float(v.w);
        }
        asm volatile("fence.proxy.async.shared::cta;" ::: "memory");
        __syncwarp();
        if (lane == 0) mbar_arrive(bar + 8 * BAR_TC);
        __syncwarp();
        if (warp == 8) STAMP(19);
#pragma unroll
        for (int nt = 0; nt < 16; nt++)
#pragma unroll
            for (int b = 0; b < 2; b++) sts32(buf + ((8 * nt + 2 * q + b) * 8 + g) * 4, pack2(y[nt][b], y[nt][2 + b]));
        bar_named(2, 128);
        uint4* yp = scr->y + bi * 1024 + st;
#pragma unroll
        for (int v = 0; v < 8; v++) {
            const uint32_t a = sb + OFF_BUF + (st + 128 * v) * 4;
            const uint32_t w0 = lds32(a), w1 = lds32(a + BUF_STRIDE), w2 = lds32(a + 2 * BUF_STRIDE), w3 = lds32(a + 3 * BUF_STRIDE);
            st_rlx128(yp + v * 128, tag4(__byte_perm(w0, w1, 0x5410), __byte_perm(w0, w1, 0x7632), __byte_perm(w2, w3, 0x5410), __byte_perm(w2, w3, 0x7632), tag));
        }
        if (st < 8) st_rlx32(scr->yflag + bi * 8 + st, tag);
        if (warp == 8) STAMP(20);
    } else {
        asm volatile("setmaxnreg.dec.sync.aligned.u32 64;");
        const int qq = (bi_i & 2) + ((lane >> 1) & 1);
        uint2* kvf_h = (uint2*)(scr->kvf + (bi_j * 4 + (bi_i >> 2)) * 68);
        auto windows = [&](int rhi, int rlo) {
#pragma unroll 1
            for (int rho = rhi; rho >= rlo; rho--) {
                const int ci = lane + 32 * rho;
                uint4 e4[4];
#pragma unroll
                for (int v = 0; v < 4; v++) { const int cc = ci - 3 + v; e4[v] = lds128(ub + ((cc ^ ((cc >> 3) & 1)) << 4)); }
                float S[29];
                const uint32_t* ew = (const uint32_t*)e4;
                S[3] = 0.f;
#pragma unroll
                for (int k = 4; k <= 28; k++) S[k] = S[k - 1] + ((k & 1) ? bf_hi(ew[k >> 1]) : bf_lo(ew[k >> 1]));
                auto win = [&](int lo, int hi, uint32_t a) {
                    sts128(a, pack2(S[hi] - S[lo - 1], S[hi + 1] - S[lo]), pack2(S[hi + 2] - S[lo + 1], S[hi + 3] - S[lo + 2]),
                           pack2(S[hi + 4] - S[lo + 3], S[hi + 5] - S[lo + 4]), pack2(S[hi + 6] - S[lo + 5], S[hi + 7] - S[lo + 6]));
                };
                win(14, 18, buf + W5_OFF + 16 + ci * 16); win(19, 21, buf + W3_OFF + 16 + ci * 16);
                if (rho < 4) {
                    const uint32_t sw = (ci ^ ((ci >> 3) & 1)) << 4;
                    win(4, 12, buf + W9_OFF + sw); win(13, 19, spare + sw); win(20, 21, spare + 2048 + sw);
                }
            }
        };
        {
            mbar_wait(bar + 8 * (BAR_FULL + xkb), 0);
#pragma unroll 1
            for (int hf = 0; hf < 2; hf++) {
                const int r = w4 * 32 + hf * 16 + (lane & 15);
                uint32_t* xt = (uint32_t*)scr->xt + ((xkb + rot) * 16 + (g >> 2)) * 4096 + (bi_i * 16 + w4 * 4 + hf * 2) * 16 + (g & 3) * 4 + q;
#pragma unroll
                for (int cb = 0; cb < 8; cb += 2) {
                    uint32_t v[4];
                    ldsm4t(v, sb + xkb * SLOT + r * 128 + (((cb + (lane >> 4)) ^ (r & 7)) << 4));
                    xt[cb * 8192] = v[0]; xt[cb * 8192 + 16] = v[1]; xt[cb * 8192 + 8192] = v[2]; xt[cb * 8192 + 8192 + 16] = v[3];
                }
            }
            __syncwarp();
            if (lane == 0) {
                mbar_arrive(bar + 8 * BAR_XT);
                STAMP(26);
                asm volatile("red.release.gpu.global.add.u32 [%0],2;" ::"l"(scr->xcnt + (xkb + rot) * 32) : "memory");
                STAMP(27);
            }
            __syncwarp();
            {
                const uint32_t old = tag ^ 1u;
                const uint4 z4 = make_uint4(old, 0, old, 0);
#pragma unroll
                for (int v = 0; v < 5; v++) if (v < 4 || st < 32) st_rlx128(scr->kvp + bi * 544 + v * 128 + st, z4);
                if (st < 16) st_rlx128(scr->o + ((bi_i * 8 + (st >> 1)) * 32 + bi_j * 4 + 3) * 32 + 30 + (st & 1), z4);
                if (lane < 8) st_rlx64(kvf_h + ((bi_i & 3) * 8 + w4 * 2 + (lane & 1)) * 4 + (lane >> 1), old, 0);
                if (st < 4 && !(bi_i & 1)) st_rlx64(kvf_h + (64 + qq) * 2 + (lane & 1), old, 0);
                __syncwarp();
                if (lane == 0) mbar_arrive(bar + 8 * BAR_PREP);
            }
            int n = 0;
#pragma unroll 1
            while (__any_sync(~0u, (int)(ld_acq(scr->xcnt + bi_j * 32) - (epoch1 << 7)) < 0)) { if (++n > SPIN_LIMIT) break; }
            if (warp == 12) STAMP(15);
            uint4 ur[8];
#pragma unroll
            for (int v = 0; v < 8; v++) ur[v] = __ldcg(scr->xt + bi * 1024 + st + 128 * v);
            mbar_wait(bar + 8 * BAR_SP, 0);
            if (lane < 16) sts128(ub - 256 + lane * 16, 0, 0, 0, 0);
            if (lane < 2) sts128(buf + lane * W3_OFF, 0, 0, 0, 0);
#pragma unroll
            for (int v = 0; v < 8; v++) {
                const int ci = (st >> 2) + 32 * v;
                sts128(sb + OFF_U + (st & 3) * U_STRIDE + 256 + ((ci ^ ((ci >> 3) & 1)) << 4), ur[v].x, ur[v].y, ur[v].z, ur[v].w);
            }
            __syncwarp();
            if (lane == 0) mbar_arrive(bar + 8 * BAR_UR);
            mbar_wait(bar + 8 * BAR_UR, 0);
            if (warp == 12) STAMP(16);
            windows(5, 4);
        }
        mbar_wait(bar + 8 * BAR_SP2, 0);
        windows(3, 0);
        __syncwarp();
        if (lane == 0) mbar_arrive(bar + 8 * BAR_WR);
        if (warp == 12) STAMP(24);
        {
            const bool zw = st < 32 && !(bi_i & 1);
            const uint4* src = scr->kvp + bi_j * (16 * 544) + (bi_i >> 2) * 136;
            const uint4* zsrc = src + (lane >> 2) * (2 * 544) + 128 + (lane & 1) * 4 + qq;
            src += (lane >> 3) * (4 * 544) + ((lane >> 1) & 3) * 32 + (bi_i & 3) * 8 + w4 * 2 + (lane & 1);
            mbar_wait(bar + 8 * BAR_PUB, 0);
            if (warp == 12) STAMP(12);
            __nanosleep(D1_NS);
            uint4 v[6];
#pragma unroll
            for (int k = 0; k < 6; k++) v[k] = make_uint4(tag ^ 1u, 0, 0, 0);
            int n = 0;
#pragma unroll 1
            while (true) {
#pragma unroll
                for (int k = 0; k < 6; k++) if ((bad4(v[k], tag) & 1) && (k < 4 || zw)) v[k] = ld_rlx128(k < 4 ? src + k * 544 : zsrc + (k - 4) * 544);
                if (!__any_sync(~0u, (bad4(v[0], tag) | bad4(v[1], tag) | bad4(v[2], tag) | bad4(v[3], tag) | (zw ? bad4(v[4], tag) | bad4(v[5], tag) : 0u)) & 1)) break;
                if (warp == 12 && n < 3) STAMP(54 + n);
                if (++n > SPIN_LIMIT) break;
                __nanosleep(POLL_NS);
            }
            if (warp == 12) STAMP(30);
            float f[8];
            const float* vf = (const float*)v;
#pragma unroll
            for (int r = 0; r < 4; r++) {
                f[r] = (vf[r] + vf[4 + r]) + (vf[8 + r] + vf[12 + r]);
                f[4 + r] = vf[16 + r] + vf[20 + r];
                f[4 + r] += __shfl_xor_sync(~0u, f[4 + r], 4);
            }
#pragma unroll
            for (int o = 8; o <= 16; o <<= 1)
#pragma unroll
                for (int r = 0; r < 8; r++) f[r] += __shfl_xor_sync(~0u, f[r], o);
            if (lane < 8) st_rlx64(kvf_h + ((bi_i & 3) * 8 + w4 * 2 + (lane & 1)) * 4 + (lane >> 1), tagw(pack2(f[0], f[1]), tag), pack2(f[2], f[3]));
            if (zw && lane < 4) st_rlx64(kvf_h + (64 + qq) * 2 + (lane & 1), tagw(pack2(f[4], f[5]), tag), pack2(f[6], f[7]));
        }
        if (warp == 12) STAMP(13);
        {
            const uint4* kp = scr->kvf + bi_j * 272 + st;
            __nanosleep(D2_NS);
            uint4 v0 = make_uint4(tag ^ 1u, 0, 0, 0), v1 = v0, v2 = make_uint4(st < 16 ? tag ^ 1u : tag, 0, tag, 0);
            int n = 0;
#pragma unroll 1
            while (true) {
                if (bad4(v0, tag) & 1) v0 = ld_rlx128(kp);
                if (bad4(v1, tag) & 1) v1 = ld_rlx128(kp + 128);
                if (bad4(v2, tag) & 1) v2 = ld_rlx128(kp + 256);
                if (!__any_sync(~0u, (bad4(v0, tag) | bad4(v1, tag) | bad4(v2, tag)) & 1)) break;
                if (++n > SPIN_LIMIT) break;
                __nanosleep(POLL_NS);
            }
            sts128(sb + OFF_KVF + st * 16, v0.x, v0.y, v0.z, v0.w);
            sts128(sb + OFF_KVF + 2048 + st * 16, v1.x, v1.y, v1.z, v1.w);
            if (st < 16) sts128(sb + OFF_KVF + 4096 + st * 16, v2.x, v2.y, v2.z, v2.w);
            __syncwarp();
            if (lane == 0) mbar_arrive(bar + 8 * BAR_KVF);
        }
        if (warp == 13) {
            mbar_wait(bar + 8 * BAR_KVF, 0);
            mbar_wait(bar + 8 * BAR_TC, 0);
            if (lane == 0) {
                mbar_expect(bar + 8 * BAR_WO2, 65536);
                tma2d(sb + OFF_P, &mwo, (bi_j & 3) * 128, 256, bar + 8 * BAR_WO2);
                tma2d(sb + OFF_V, &mwo, (bi_j & 3) * 128 + 64, 256, bar + 8 * BAR_WO2);
            }
        }
        if (warp == 12) STAMP(25);
    }
    __syncwarp();
    if (lane == 0) {
        unsigned old;
        asm volatile("atom.acq_rel.cta.shared.add.u32 %0,[%1],1;" : "=r"(old) : "r"(bar + OFF_CNT) : "memory");
        if (old == 15) {
            atomicAdd(scr->done, 1u);
        }
    }
}

typedef CUresult (*EncFn)(CUtensorMap*, CUtensorMapDataType, cuuint32_t, void*, const cuuint64_t*, const cuuint64_t*, const cuuint32_t*,
                          const cuuint32_t*, CUtensorMapInterleave, CUtensorMapSwizzle, CUtensorMapL2promotion, CUtensorMapFloatOOBfill);

extern "C" void kernel_launch(void* const* d_in, const int* in_sizes, int n_in, void* d_out, int out_size) {
    static EncFn enc = nullptr;
    static Scratch* scr = nullptr;
    if (!enc) {
        cudaGetSymbolAddress((void**)&scr, g_scr);
        cudaDriverEntryPointQueryResult qr;
        cudaGetDriverEntryPoint("cuTensorMapEncodeTiled", (void**)&enc, cudaEnableDefault, &qr);
        cudaFuncSetAttribute(fused_kernel, cudaFuncAttributeMaxDynamicSharedMemorySize, SMEM_BYTES);
    }
    CUtensorMap mx, mw, mwo;
    const cuuint32_t es[3] = {1, 1, 1};
    {
        cuuint64_t d[2] = {512, 2048}, s[1] = {1024}; cuuint32_t b[2] = {64, 128};
        enc(&mx, CU_TENSOR_MAP_DATA_TYPE_BFLOAT16, 2, d_in[0], d, s, b, es, CU_TENSOR_MAP_INTERLEAVE_NONE, CU_TENSOR_MAP_SWIZZLE_128B,
            CU_TENSOR_MAP_L2_PROMOTION_L2_128B, CU_TENSOR_MAP_FLOAT_OOB_FILL_NONE);
    }
    {
        cuuint64_t d[3] = {512, 512, 3}, s[2] = {3072, 1024}; cuuint32_t b[3] = {64, 64, 3};
        enc(&mw, CU_TENSOR_MAP_DATA_TYPE_BFLOAT16, 3, d_in[1], d, s, b, es, CU_TENSOR_MAP_INTERLEAVE_NONE, CU_TENSOR_MAP_SWIZZLE_128B,
            CU_TENSOR_MAP_L2_PROMOTION_L2_128B, CU_TENSOR_MAP_FLOAT_OOB_FILL_NONE);
    }
    {
        cuuint64_t d[2] = {512, 512}, s[1] = {1024}; cuuint32_t b[2] = {64, 256};
        enc(&mwo, CU_TENSOR_MAP_DATA_TYPE_BFLOAT16, 2, d_in[3], d, s, b, es, CU_TENSOR_MAP_INTERLEAVE_NONE, CU_TENSOR_MAP_SWIZZLE_128B,
            CU_TENSOR_MAP_L2_PROMOTION_L2_128B, CU_TENSOR_MAP_FLOAT_OOB_FILL_NONE);
    }
    fused_kernel<<<128, 512, SMEM_BYTES, cudaStreamPerThread>>>(
        scr, (const bf16*)d_in[5], (const bf16*)d_in[6], (const bf16*)d_in[7], (const bf16*)d_in[8], (const bf16*)d_in[9],
        (const bf16*)d_in[10], (const bf16*)d_in[2], (const bf16*)d_in[11], (bf16*)d_out, mx, mw, mwo);
}
```

```cpp
#include <cuda_runtime.h>
#include <cuda.h>
#include <cuda_bf16.h>
#include <stdint.h>

typedef __nv_bfloat16 bf16;

struct Scratch {
    uint4 xt[128 * 1024];
    uint4 o[16 * 8 * 32 * 32];
    uint4 y[128 * 1024];
    uint4 kvp[8 * 16 * 544];
    uint4 kvf[8 * 4 * 68];
    unsigned g[1024 * 8];
    unsigned yflag[128 * 8];
    unsigned xcnt[8 * 32];
    unsigned done[32];
};
__device__ Scratch g_scr;
#define STAMP(n)

constexpr int SLOT = 40960;
constexpr int OFF_SP0 = 32768, OFF_SP1 = SLOT + 32768;
constexpr int OFF_P = 2 * SLOT, OFF_V = OFF_P + 32768;
constexpr int OFF_KVF = OFF_V + 32768;
constexpr int KT_BYTES = 3264, KW_D = 16, KW_2 = 560, KW_3 = 656;
constexpr int OFF_U = 4 * SLOT, U_STRIDE = 4096 + 256 + 32;
constexpr int OFF_BUF = OFF_U + 4 * U_STRIDE, BUF_STRIDE = 8320;
constexpr int OFF_K = OFF_BUF + 4 * BUF_STRIDE;
constexpr int OFF_WPHI = OFF_K + 4 * KT_BYTES;
constexpr int OFF_GW = OFF_WPHI + 2048;
constexpr int OFF_BAR = OFF_GW + 1024;
constexpr int SMEM_BYTES = OFF_BAR + 256 + 256;
static_assert(SMEM_BYTES <= 232448 && OFF_BUF % 128 == 0, "smem");
constexpr int W5_OFF = 0, W3_OFF = 3088, W9_OFF = 6176;
constexpr int BAR_FULL = 0, BAR_EMPTY = 4, BAR_WPHI = 8, BAR_WO = 9, BAR_WO2 = 10, BAR_XT = 11, BAR_DONE = 12, BAR_KG = 13, BAR_SP = 14,
              BAR_PUB = 15, BAR_KVF = 16, BAR_UR = 17, BAR_WR = 18, BAR_PREP = 19, BAR_KGA = 20, BAR_SP2 = 21, BAR_GO = 22, OFF_CNT = 192;
#define CONV_START BAR_DONE
#define D1_NS 0
#define D2_NS 0
#define D3_NS 100
#define PS_NS 100
#define POLL_NS 0
constexpr int SPIN_LIMIT = 1 << 17;

__device__ __forceinline__ uint32_t s2u(const void* p) { return (uint32_t)__cvta_generic_to_shared(p); }
__device__ __forceinline__ void mbar_init(uint32_t b, int c) { asm volatile("mbarrier.init.shared::cta.b64 [%0],%1;" ::"r"(b), "r"(c) : "memory"); }
__device__ __forceinline__ void mbar_expect(uint32_t b, int bytes) { asm volatile("mbarrier.arrive.expect_tx.shared::cta.b64 _,[%0],%1;" ::"r"(b), "r"(bytes) : "memory"); }
__device__ __forceinline__ void mbar_arrive(uint32_t b) { asm volatile("mbarrier.arrive.shared::cta.b64 _,[%0];" ::"r"(b) : "memory"); }
__device__ __forceinline__ void mbar_wait(uint32_t b, int ph) {
    asm volatile("{\n.reg .pred p;\n.reg .u32 n;\nmov.u32 n,0;\nLW_%=:\nmbarrier.try_wait.parity.shared::cta.b64 p,[%0],%1;\n@p bra LD_%=;\n"
                 "add.u32 n,n,1;\nsetp.lt.u32 p,n,16384;\n@p bra LW_%=;\nLD_%=:\n}" ::"r"(b), "r"(ph) : "memory");
}
__device__ __forceinline__ void tma2d(uint32_t dst, const CUtensorMap* m, int c0, int c1, uint32_t bar) {
    asm volatile("cp.async.bulk.tensor.2d.shared::cluster.global.mbarrier::complete_tx::bytes [%0],[%1,{%3,%4}],[%2];" ::"r"(dst), "l"(m), "r"(bar), "r"(c0), "r"(c1) : "memory");
}
__device__ __forceinline__ void tma3d(uint32_t dst, const CUtensorMap* m, int c0, int c1, int c2, uint32_t bar) {
    asm volatile("cp.async.bulk.tensor.3d.shared::cluster.global.mbarrier::complete_tx::bytes [%0],[%1,{%3,%4,%5}],[%2];" ::"r"(dst), "l"(m), "r"(bar), "r"(c0), "r"(c1), "r"(c2) : "memory");
}
__device__ __forceinline__ void bulk_g2s(uint32_t dst, const void* src, int bytes, uint32_t bar) {
    asm volatile("cp.async.bulk.shared::cluster.global.mbarrier::complete_tx::bytes [%0],[%1],%2,[%3];" ::"r"(dst), "l"(src), "r"(bytes), "r"(bar) : "memory");
}
__device__ __forceinline__ uint64_t mkdesc(uint32_t addr, uint32_t lbo, uint32_t sbo) {
    return (uint64_t)((addr & 0x3FFFF) >> 4) | ((uint64_t)(lbo >> 4) << 16) | ((uint64_t)(sbo >> 4) << 32) | ((uint64_t)1 << 62);
}
__device__ __forceinline__ void wg_fence() { asm volatile("wgmma.fence.sync.aligned;" ::: "memory"); }
__device__ __forceinline__ void wg_commit() { asm volatile("wgmma.commit_group.sync.aligned;" ::: "memory"); }
template <int N> __device__ __forceinline__ void wg_wait() { asm volatile("wgmma.wait_group.sync.aligned %0;" ::"n"(N) : "memory"); }
template <int N> __device__ __forceinline__ void fence_regs(float* d) {
#pragma unroll
    for (int i = 0; i < N; i++) asm volatile("" : "+f"(d[i])::"memory");
}
#define R8(d, o) "+f"(d[o]), "+f"(d[o + 1]), "+f"(d[o + 2]), "+f"(d[o + 3]), "+f"(d[o + 4]), "+f"(d[o + 5]), "+f"(d[o + 6]), "+f"(d[o + 7])
__device__ __forceinline__ void wgmma192(float* d, uint64_t da, uint64_t db) {
    asm volatile("wgmma.mma_async.sync.aligned.m64n192k16.f32.bf16.bf16 {"
                 "%0,%1,%2,%3,%4,%5,%6,%7,%8,%9,%10,%11,%12,%13,%14,%15,%16,%17,%18,%19,%20,%21,%22,%23,%24,%25,%26,%27,%28,%29,%30,%31,"
                 "%32,%33,%34,%35,%36,%37,%38,%39,%40,%41,%42,%43,%44,%45,%46,%47,%48,%49,%50,%51,%52,%53,%54,%55,%56,%57,%58,%59,%60,%61,%62,%63,"
                 "%64,%65,%66,%67,%68,%69,%70,%71,%72,%73,%74,%75,%76,%77,%78,%79,%80,%81,%82,%83,%84,%85,%86,%87,%88,%89,%90,%91,%92,%93,%94,%95},"
                 "%96,%97,1,1,1,0,1;"
                 : R8(d, 0), R8(d, 8), R8(d, 16), R8(d, 24), R8(d, 32), R8(d, 40), R8(d, 48), R8(d, 56), R8(d, 64), R8(d, 72), R8(d, 80), R8(d, 88)
                 : "l"(da), "l"(db));
}
__device__ __forceinline__ void wgmma64_tt(float* d, uint64_t da, uint64_t db, int sc) {
    asm volatile("{.reg .pred p; setp.ne.b32 p,%34,0; wgmma.mma_async.sync.aligned.m64n64k16.f32.bf16.bf16 {"
                 "%0,%1,%2,%3,%4,%5,%6,%7,%8,%9,%10,%11,%12,%13,%14,%15,%16,%17,%18,%19,%20,%21,%22,%23,%24,%25,%26,%27,%28,%29,%30,%31},"
                 "%32,%33,p,1,1,1,1;}"
                 : R8(d, 0), R8(d, 8), R8(d, 16), R8(d, 24)
                 : "l"(da), "l"(db), "r"(sc));
}
__device__ __forceinline__ void wgmma128_rs(float* d, const uint4& a, uint64_t db, int sc) {
    asm volatile("{.reg .pred p; setp.ne.b32 p,%69,0; wgmma.mma_async.sync.aligned.m64n128k16.f32.bf16.bf16 {"
                 "%0,%1,%2,%3,%4,%5,%6,%7,%8,%9,%10,%11,%12,%13,%14,%15,%16,%17,%18,%19,%20,%21,%22,%23,%24,%25,%26,%27,%28,%29,%30,%31,"
                 "%32,%33,%34,%35,%36,%37,%38,%39,%40,%41,%42,%43,%44,%45,%46,%47,%48,%49,%50,%51,%52,%53,%54,%55,%56,%57,%58,%59,%60,%61,%62,%63},"
                 "{%64,%65,%66,%67},%68,p,1,1,1;}"
                 : R8(d, 0), R8(d, 8), R8(d, 16), R8(d, 24), R8(d, 32), R8(d, 40), R8(d, 48), R8(d, 56)
                 : "r"(a.x), "r"(a.y), "r"(a.z), "r"(a.w), "l"(db), "r"(sc));
}
__device__ __forceinline__ void mma16816(float* c, uint32_t a0, uint32_t a1, uint32_t a2, uint32_t a3, uint32_t b0, uint32_t b1) {
    asm("mma.sync.aligned.m16n8k16.row.col.f32.bf16.bf16.f32 {%0,%1,%2,%3},{%4,%5,%6,%7},{%8,%9},{%0,%1,%2,%3};"
        : "+f"(c[0]), "+f"(c[1]), "+f"(c[2]), "+f"(c[3]) : "r"(a0), "r"(a1), "r"(a2), "r"(a3), "r"(b0), "r"(b1));
}
__device__ __forceinline__ void ldsm4(uint32_t* r, uint32_t a) {
    asm volatile("ldmatrix.sync.aligned.m8n8.x4.shared.b16 {%0,%1,%2,%3},[%4];" : "=r"(r[0]), "=r"(r[1]), "=r"(r[2]), "=r"(r[3]) : "r"(a) : "memory");
}
__device__ __forceinline__ void ldsm4t(uint32_t* r, uint32_t a) {
    asm volatile("ldmatrix.sync.aligned.m8n8.x4.trans.shared.b16 {%0,%1,%2,%3},[%4];" : "=r"(r[0]), "=r"(r[1]), "=r"(r[2]), "=r"(r[3]) : "r"(a) : "memory");
}
__device__ __forceinline__ void stsm4(uint32_t a, uint32_t r0, uint32_t r1, uint32_t r2, uint32_t r3) {
    asm volatile("stmatrix.sync.aligned.m8n8.x4.shared.b16 [%0],{%1,%2,%3,%4};" ::"r"(a), "r"(r0), "r"(r1), "r"(r2), "r"(r3) : "memory");
}
__device__ __forceinline__ uint32_t lds32(uint32_t a) { uint32_t v; asm volatile("ld.shared.b32 %0,[%1];" : "=r"(v) : "r"(a) : "memory"); return v; }
__device__ __forceinline__ uint4 lds128(uint32_t a) { uint4 v; asm volatile("ld.shared.v4.b32 {%0,%1,%2,%3},[%4];" : "=r"(v.x), "=r"(v.y), "=r"(v.z), "=r"(v.w) : "r"(a) : "memory"); return v; }
__device__ __forceinline__ void sts16(uint32_t a, uint32_t v) { asm volatile("st.shared.b16 [%0],%1;" ::"r"(a), "h"((unsigned short)v) : "memory"); }
__device__ __forceinline__ void sts32(uint32_t a, uint32_t v) { asm volatile("st.shared.b32 [%0],%1;" ::"r"(a), "r"(v) : "memory"); }
__device__ __forceinline__ void sts64(uint32_t a, uint32_t x, uint32_t y) { asm volatile("st.shared.v2.b32 [%0],{%1,%2};" ::"r"(a), "r"(x), "r"(y) : "memory"); }
__device__ __forceinline__ void sts128(uint32_t a, uint32_t x, uint32_t y, uint32_t z, uint32_t w) { asm volatile("st.shared.v4.b32 [%0],{%1,%2,%3,%4};" ::"r"(a), "r"(x), "r"(y), "r"(z), "r"(w) : "memory"); }
__device__ __forceinline__ uint32_t pack2(float lo, float hi) { uint32_t d; asm("cvt.rn.bf16x2.f32 %0,%1,%2;" : "=r"(d) : "f"(hi), "f"(lo)); return d; }
__device__ __forceinline__ float bf_lo(uint32_t v) { return __uint_as_float(v << 16); }
__device__ __forceinline__ float bf_hi(uint32_t v) { return __uint_as_float(v & 0xffff0000u); }
__device__ __forceinline__ float bf_round(float v) { return bf_lo(pack2(v, 0.f)); }
__device__ __forceinline__ uint32_t hmax2(uint32_t a, uint32_t b) { uint32_t d; asm("max.bf16x2 %0,%1,%2;" : "=r"(d) : "r"(a), "r"(b)); return d; }
__device__ __forceinline__ uint32_t hmin2(uint32_t a, uint32_t b) { uint32_t d; asm("min.bf16x2 %0,%1,%2;" : "=r"(d) : "r"(a), "r"(b)); return d; }
__device__ __forceinline__ uint32_t hmul2(uint32_t a, uint32_t b) { uint32_t d; asm("mul.rn.bf16x2 %0,%1,%2;" : "=r"(d) : "r"(a), "r"(b)); return d; }
__device__ __forceinline__ float ex2(float x) { float y; asm("ex2.approx.ftz.f32 %0,%1;" : "=f"(y) : "f"(x)); return y; }
__device__ __forceinline__ float rcp(float x) { float y; asm("rcp.approx.ftz.f32 %0,%1;" : "=f"(y) : "f"(x)); return y; }
__device__ __forceinline__ uint32_t ld_nc(const uint32_t* p) { uint32_t v; asm volatile("ld.global.nc.b32 %0,[%1];" : "=r"(v) : "l"(p)); return v; }
__device__ __forceinline__ uint2 ld_nc64(const uint2* p) { uint2 v; asm volatile("ld.global.nc.v2.b32 {%0,%1},[%2];" : "=r"(v.x), "=r"(v.y) : "l"(p)); return v; }
__device__ __forceinline__ unsigned ld_acq(const unsigned* p) { unsigned v; asm volatile("ld.acquire.gpu.global.u32 %0,[%1];" : "=r"(v) : "l"(p) : "memory"); return v; }
__device__ __forceinline__ unsigned ld_rlx(const unsigned* p) { unsigned v; asm volatile("ld.relaxed.gpu.global.u32 %0,[%1];" : "=r"(v) : "l"(p) : "memory"); return v; }
__device__ __forceinline__ uint2 ld_rlx64(const void* p) { uint2 v; asm volatile("{.reg .b64 t; ld.relaxed.gpu.global.b64 t,[%2]; mov.b64 {%0,%1},t;}" : "=r"(v.x), "=r"(v.y) : "l"(p) : "memory"); return v; }
__device__ __forceinline__ uint4 ld_rlx128(const void* p) {
    uint4 v;
    asm volatile("{.reg .b64 t,u; ld.relaxed.gpu.global.v2.b64 {t,u},[%4]; mov.b64 {%0,%1},t; mov.b64 {%2,%3},u;}" : "=r"(v.x), "=r"(v.y), "=r"(v.z), "=r"(v.w) : "l"(p) : "memory");
    return v;
}
__device__ __forceinline__ void st_rlx32(void* p, uint32_t x) { asm volatile("st.relaxed.gpu.global.u32 [%0],%1;" ::"l"(p), "r"(x) : "memory"); }
__device__ __forceinline__ void st_rlx64(void* p, uint32_t x, uint32_t y) { asm volatile("{.reg .b64 t; mov.b64 t,{%1,%2}; st.relaxed.gpu.global.b64 [%0],t;}" ::"l"(p), "r"(x), "r"(y) : "memory"); }
__device__ __forceinline__ void st_rlx128(void* p, uint4 v) {
    asm volatile("{.reg .b64 t,u; mov.b64 t,{%1,%2}; mov.b64 u,{%3,%4}; st.relaxed.gpu.global.v2.b64 [%0],{t,u};}" ::"l"(p), "r"(v.x), "r"(v.y), "r"(v.z), "r"(v.w) : "memory");
}
__device__ __forceinline__ uint32_t tagw(uint32_t w, uint32_t tag) { return (w & ~1u) | tag; }
__device__ __forceinline__ uint4 tag4(uint32_t x, uint32_t y, uint32_t z, uint32_t w, uint32_t tag) { return make_uint4(tagw(x, tag), y, tagw(z, tag), w); }
__device__ __forceinline__ uint32_t bad4(const uint4& v, uint32_t tag) { return (v.x ^ tag) | (v.z ^ tag); }
__device__ __forceinline__ void bar_named(int id, int n) { asm volatile("bar.sync %0,%1;" ::"r"(id), "r"(n) : "memory"); }

struct cf { float re, im; };
__device__ __forceinline__ cf cmul(cf a, cf b) { cf r; r.re = a.re * b.re - a.im * b.im; r.im = a.re * b.im + a.im * b.re; return r; }
__device__ __forceinline__ cf cexp_p(float arl, float ait, float p) {
    float mag = ex2(arl * p);
    float t = ait * p;
    t = (t - rintf(t)) * 6.283185307179586f;
    cf r; r.re = mag * __cosf(t); r.im = mag * __sinf(t);
    return r;
}

__device__ __forceinline__ void hedgehog4(const uint32_t* a, uint32_t wphi_addr, uint32_t (*out)[8]) {
    float p[4][2][4], mx[4][2];
#pragma unroll
    for (int h = 0; h < 4; h++) {
        uint32_t b[4];
        ldsm4t(b, wphi_addr + h * 512);
        float c0[4] = {0.f, 0.f, 0.f, 0.f}, c1[4] = {0.f, 0.f, 0.f, 0.f};
        mma16816(c0, a[4 * h], a[4 * h + 1], a[4 * h + 2], a[4 * h + 3], b[0], b[1]);
        mma16816(c1, a[4 * h], a[4 * h + 1], a[4 * h + 2], a[4 * h + 3], b[2], b[3]);
#pragma unroll
        for (int k = 0; k < 2; k++) {
            p[h][k][0] = c0[2 * k]; p[h][k][1] = c0[2 * k + 1]; p[h][k][2] = c1[2 * k]; p[h][k][3] = c1[2 * k + 1];
            mx[h][k] = fmaxf(fmaxf(p[h][k][0], p[h][k][1]), fmaxf(p[h][k][2], p[h][k][3]));
        }
    }
#pragma unroll
    for (int o = 1; o <= 2; o <<= 1)
#pragma unroll
        for (int h = 0; h < 4; h++)
#pragma unroll
            for (int k = 0; k < 2; k++) mx[h][k] = fmaxf(mx[h][k], __shfl_xor_sync(~0u, mx[h][k], o));
    const float L = 1.4426950408889634f;
    float pmin = 1.f;
#pragma unroll
    for (int h = 0; h < 4; h++)
#pragma unroll
        for (int k = 0; k < 2; k++) {
            const float m = -mx[h][k] * L;
            const float e0 = ex2(fmaf(p[h][k][0], L, m)), e1 = ex2(fmaf(p[h][k][1], L, m)), e2 = ex2(fmaf(p[h][k][2], L, m)), e3 = ex2(fmaf(p[h][k][3], L, m));
            const float p01 = e0 * e1, p23 = e2 * e3, pp = p01 * p23, r = rcp(pp), r01 = r * p23, r23 = r * p01;
            pmin = fminf(pmin, pp);
            out[h][k] = pack2(e0, e1); out[h][k + 2] = pack2(e2, e3);
            out[h][4 + k] = pack2(r01 * e1, r01 * e0); out[h][4 + k + 2] = pack2(r23 * e3, r23 * e2);
        }
    if (__builtin_expect(__any_sync(~0u, !(pmin > 1e-18f)), 0)) {
#pragma unroll
        for (int h = 0; h < 4; h++)
#pragma unroll
            for (int k = 0; k < 2; k++) {
                float m = fminf(fminf(p[h][k][0], p[h][k][1]), fminf(p[h][k][2], p[h][k][3]));
                m = fminf(m, __shfl_xor_sync(~0u, m, 1));
                m = fminf(m, __shfl_xor_sync(~0u, m, 2)) * L;
                out[h][4 + k] = pack2(ex2(fmaf(p[h][k][0], -L, m)), ex2(fmaf(p[h][k][1], -L, m)));
                out[h][4 + k + 2] = pack2(ex2(fmaf(p[h][k][2], -L, m)), ex2(fmaf(p[h][k][3], -L, m)));
            }
    }
}

__global__ void __launch_bounds__(512, 1)
fused_kernel(Scratch* __restrict__ scr, const bf16* __restrict__ logA, const bf16* __restrict__ Aim, const bf16* __restrict__ Cre,
             const bf16* __restrict__ Cim, const bf16* __restrict__ logdt, const bf16* __restrict__ Dskip, const bf16* __restrict__ wphi,
             const bf16* __restrict__ gatew, bf16* __restrict__ out,
             const __grid_constant__ CUtensorMap mx, const __grid_constant__ CUtensorMap mw, const __grid_constant__ CUtensorMap mwo) {
    extern __shared__ __align__(1024) uint8_t smem[];
    constexpr uint32_t sb = 1024;
    const int tid = threadIdx.x, warp = __shfl_sync(~0u, tid >> 5, 0), lane = tid & 31;
    const int g = lane >> 2, q = lane & 3, w4 = warp & 3;
    const int bi = blockIdx.x, bi_i = bi & 15, bi_j = bi >> 4;
    const uint32_t bar = sb + OFF_BAR;
    const int rot = (bi_j & 3) * 2, xkb = bi_j >> 2;
    auto load_stage = [&](int kb) {
        const uint32_t b = bar + 8 * (BAR_FULL + (kb & 3)), d = sb + (kb & 3) * SLOT;
        const int kc = ((kb + rot) & 7) * 64;
        mbar_expect(b, SLOT);
        tma2d(d, &mx, kc, bi_i * 128, b);
        tma3d(d + 16384, &mw, bi_j * 64, kc, 0, b);
    };

    const int ch = bi * 4 + w4;
    const int pidx = ch * 64 + lane * 2 + (warp >> 3);
    const uint32_t pla = ld_nc((const uint32_t*)logA + pidx), pai = ld_nc((const uint32_t*)Aim + pidx);
    const uint32_t pcr = ld_nc((const uint32_t*)Cre + pidx), pci = ld_nc((const uint32_t*)Cim + pidx);
    uint32_t pdt = ld_nc((const uint32_t*)logdt + (ch >> 1));
    const uint32_t pds = ld_nc((const uint32_t*)Dskip + (ch >> 1));
    unsigned done0 = ld_rlx(scr->done);
    if (tid == 0) {
        for (int s = 0; s < 4; s++) mbar_init(bar + 8 * (BAR_FULL + s), 1);
        asm volatile("fence.mbarrier_init.release.cluster;" ::: "memory");
        asm volatile("prefetch.tensormap [%0];" ::"l"(&mx) : "memory");
        load_stage(0); load_stage(1);
        STAMP(11);
    } else if (tid == 32) {
        if (s2u(smem) != sb) __trap();
        sts32(bar + OFF_CNT, 0);
        for (int s = 0; s < 4; s++) mbar_init(bar + 8 * (BAR_EMPTY + s), 9);
        mbar_init(bar + 8 * BAR_WPHI, 1); mbar_init(bar + 8 * BAR_WO, 2); mbar_init(bar + 8 * BAR_WO2, 1); mbar_init(bar + 8 * BAR_XT, 4);
        mbar_init(bar + 8 * BAR_DONE, 9); mbar_init(bar + 8 * BAR_KG, 8); mbar_init(bar + 8 * BAR_SP, 1); mbar_init(bar + 8 * BAR_PUB, 8);
        mbar_init(bar + 8 * BAR_KVF, 4); mbar_init(bar + 8 * BAR_UR, 4); mbar_init(bar + 8 * BAR_WR, 4); mbar_init(bar + 8 * BAR_PREP, 4); mbar_init(bar + 8 * BAR_KGA, 4); mbar_init(bar + 8 * BAR_SP2, 1); mbar_init(bar + 8 * BAR_GO, 8);
        asm volatile("fence.mbarrier_init.release.cluster;" ::: "memory");
        mbar_expect(bar + 8 * BAR_WPHI, 3072);
        bulk_g2s(sb + OFF_GW, gatew, 1024, bar + 8 * BAR_WPHI);
        bulk_g2s(sb + OFF_WPHI, wphi + bi_j * 1024, 2048, bar + 8 * BAR_WPHI);
    } else if (tid == 64) {
        asm volatile("prefetch.tensormap [%0];" ::"l"(&mw) : "memory");
    }
    const uint32_t buf = sb + OFF_BUF + w4 * BUF_STRIDE, kb_ = sb + OFF_K + w4 * KT_BYTES;
    if ((warp >> 2) == 2) {
#pragma unroll
        for (int v = 0; v < 7; v++) if (v * 32 + lane < KT_BYTES / 16) sts128(kb_ + (v * 32 + lane) * 16, 0, 0, 0, 0);
    }
    __syncthreads();
    asm volatile("" : "+r"(pdt), "+r"(done0)::"memory");
    const unsigned epoch1 = (done0 >> 7) + 1u;
    const uint32_t tag = epoch1 & 1u;

    const int st = tid & 127;
    const uint32_t ub = sb + OFF_U + w4 * U_STRIDE + 256, spare = sb + (w4 < 2 ? OFF_SP0 : OFF_SP1) + (w4 & 1) * 4096;

    auto stg_of = [&](int w) { return w < 8 ? sb + 3 * SLOT + w * 7296 : sb + 2 * SLOT + (w & 3) * 7296; };
    float kc[24];
#pragma unroll
    for (int t = 0; t < 24; t++) kc[t] = 0.f;
    {
        const float dt = bf_round(expf((ch & 1) ? bf_hi(pdt) : bf_lo(pdt)));
        const uint32_t stg = (warp >> 2) == 2 ? buf : stg_of(warp);
        const int sh = ((warp >> 2) & 1) * 16;
        auto pick = [&](uint32_t v) { return __uint_as_float((v >> sh) << 16); };
        const float ea = bf_round(ex2(pick(pla) * 1.4426950408889634f));
        const float arl = (-ea * dt) * 1.4426950408889634f, ait = (pick(pai) * dt) * 0.15915494309189535f;
        cf C2; C2.re = 2.0f * (pick(pcr) * dt); C2.im = 2.0f * (pick(pci) * dt);
        const cf z1 = cexp_p(arl, ait, 1.0f), z128 = cexp_p(arl, ait, 128.0f);
        cf z8 = cexp_p(arl, ait, 8.0f); z8.im = -z8.im;
        const uint32_t lp = stg + lane * 4;
        auto put = [&](int row, const cf& v) { sts32((lp ^ ((row & 7) << 4)) + row * 128, pack2(v.re, v.im)); };
        {
            const cf z16 = cmul(z8, z8);
            cf e; e.re = 1.f; e.im = 0.f;
            cf o = z8;
            put(0, e); put(1, o);
            e = z16; put(2, e);
#pragma unroll
            for (int b = 3; b < 16; b += 2) {
                o = cmul(o, z16); put(b, o);
                if (b + 1 < 16) { e = cmul(e, z16); put(b + 1, e); }
            }
        }
        cf h[8];
        h[0] = C2; put(16, h[0]);
        {
            const cf z2 = cmul(z1, z1);
            h[1] = cmul(h[0], z1);
#pragma unroll
            for (int r = 2; r < 8; r++) h[r] = cmul(h[r - 2], z2);
#pragma unroll
            for (int r = 1; r < 8; r++) put(16 + r, h[r]);
        }
#pragma unroll
        for (int r = 0; r < 8; r++) { h[r] = cmul(h[r], z128); put(24 + r, h[r]); }
#pragma unroll
        for (int al = 0; al < 2; al++)
#pragma unroll
            for (int r = 0; r < 4; r++) { h[2 * r] = cmul(h[2 * r], z128); put(32 + al * 4 + r, h[2 * r]); }
#pragma unroll
        for (int al = 0; al < 4; al++)
#pragma unroll
            for (int r = 0; r < 2; r++) { h[4 * r] = cmul(h[4 * r], z128); put(40 + al * 2 + r, h[4 * r]); }
#pragma unroll
        for (int al = 0; al < 9; al++) { h[0] = cmul(h[0], z128); put(48 + al, h[0]); }
        __syncwarp();
        const int lr = lane & 7, lm = lane >> 3;
#pragma unroll
        for (int kp = 0; kp < 2; kp++) {
            uint32_t a0[4], a1[4];
            ldsm4(a0, stg + ((lm & 1) * 8 + lr) * 128 + (((4 * kp + (lm >> 1)) ^ lr) << 4));
            ldsm4(a1, stg + ((lm & 1) * 8 + lr) * 128 + (((4 * kp + 2 + (lm >> 1)) ^ lr) << 4));
#pragma unroll
            for (int t = 0; t < 6; t++) {
                uint32_t b[4];
                ldsm4(b, stg + (16 + 8 * t + lr) * 128 + (((4 * kp + lm) ^ lr) << 4));
                mma16816(kc + 4 * t, a0[0], a0[1], a0[2], a0[3], b[0], b[1]);
                mma16816(kc + 4 * t, a1[0], a1[1], a1[2], a1[3], b[2], b[3]);
            }
        }
        __syncwarp();
        if ((warp >> 2) != 2) {
#pragma unroll
            for (int t = 0; t < 6; t++)
                sts128(stg + (t * 32 + lane) * 16, __float_as_uint(kc[4 * t]), __float_as_uint(kc[4 * t + 1]), __float_as_uint(kc[4 * t + 2]), __float_as_uint(kc[4 * t + 3]));
            asm volatile("fence.proxy.async.shared::cta;" ::: "memory");
            __syncwarp();
            if (lane == 0) mbar_arrive(bar + 8 * (warp < 8 ? BAR_KG : BAR_KGA));
        }
    }

    if (warp < 8) {
        asm volatile("setmaxnreg.inc.sync.aligned.u32 160;");
        const int wg = warp >> 2;
        if (warp == 0) STAMP(21);
        float acc[96];
        const int srow = warp * 16 + (lane & 15);
        const uint32_t srow_a = srow * 128;
        const int sx = srow & 7, shi = lane >> 4;
#pragma unroll
        for (int r = 0; r < 96; r++) acc[r] = 0.f;
        fence_regs<96>(acc);
        const uint64_t da0 = mkdesc(sb + wg * 8192, 16, 1024), db0 = mkdesc(sb + 16384, 8192, 1024);
#pragma unroll 1
        for (int kb = 0; kb < 8; kb++) {
            const int s = kb & 3;
            const uint64_t da = da0 + s * (SLOT >> 4), db = db0 + s * (SLOT >> 4);
            if (warp == 0) STAMP(40 + kb);
            mbar_wait(bar + 8 * (BAR_FULL + s), kb >> 2);
            if (warp == 0) STAMP(32 + kb);
            wg_fence();
#pragma unroll
            for (int k = 0; k < 4; k++) wgmma192(acc, da + 2 * k, db + 128 * k);
            wg_commit();
            wg_wait<1>();
            if (lane == 0 && kb > 0) mbar_arrive(bar + 8 * (BAR_EMPTY + ((kb - 1) & 3)));
        }
        mbar_wait(bar + 8 * BAR_WPHI, 0);
        wg_wait<0>();
        fence_regs<96>(acc);
        if (lane == 0) mbar_arrive(bar + 8 * BAR_DONE);
        if (warp == 0) STAMP(1);
        uint32_t in[16], qa[16];
        mbar_wait(bar + 8 * BAR_DONE, 0);
#pragma unroll
        for (int r = 0; r < 16; r++) {
            in[r] = pack2(acc[32 + 2 * r], acc[32 + 2 * r + 1]);
            qa[r] = pack2(acc[2 * r], acc[2 * r + 1]);
        }
#pragma unroll
        for (int hh = 0; hh < 4; hh++)
            stsm4(sb + OFF_V + (hh >> 1) * 16384 + srow_a + (((2 * (hh & 1) + shi) ^ sx) << 4), pack2(acc[64 + 8 * hh], acc[65 + 8 * hh]),
                  pack2(acc[66 + 8 * hh], acc[67 + 8 * hh]), pack2(acc[68 + 8 * hh], acc[69 + 8 * hh]), pack2(acc[70 + 8 * hh], acc[71 + 8 * hh]));
        sts128(sb + OFF_V + shi * 16384 + srow_a + ((4 ^ sx) << 4), 0x3f803f80u, 0x3f803f80u, 0x3f803f80u, 0x3f803f80u);
        const uint32_t wphi_a = sb + OFF_WPHI + (lane & 15) * 32 + (lane >> 4) * 16;
        uint32_t pq[4][8];
#pragma unroll 1
        for (int it = 0; it < 2; it++) {
            hedgehog4(in, wphi_a, pq);
            if (it == 1) break;
#pragma unroll
            for (int hs = 0; hs < 8; hs++) {
                float c[4] = {0.f, 0.f, 0.f, 0.f};
                const uint32_t* o = pq[hs >> 1] + 4 * (hs & 1);
                mma16816(c, o[0], o[1], o[2], o[3], 0x3f803f80u, 0x3f803f80u);
                const float r0 = rcp(c[0]), r1 = rcp(c[2]);
                const uint32_t s0 = pack2(r0, r0), s1 = pack2(r1, r1);
                stsm4(sb + OFF_P + (hs >> 2) * 16384 + srow_a + (((2 * (hs & 3) + shi) ^ sx) << 4), hmul2(o[0], s0), hmul2(o[1], s1), hmul2(o[2], s0), hmul2(o[3], s1));
            }
            asm volatile("fence.proxy.async.shared::cta;" ::: "memory");
            if (lane == 0) mbar_arrive(bar + 8 * BAR_GO);
            bar_named(1, 256);
            if (warp == 0) STAMP(2);
            float d[32];
            const uint64_t dv = mkdesc(sb + OFF_V + wg * 16384, 16, 1024), dp = mkdesc(sb + OFF_P + wg * 16384, 16, 1024);
            wg_fence();
#pragma unroll
            for (int k = 0; k < 8; k++) wgmma64_tt(d, dv + 128 * k, dp + 128 * k, k != 0);
            wg_commit();
            mbar_wait(bar + 8 * BAR_PREP, 0);
            uint4* kvp = scr->kvp + bi * 544 + wg * 272 + (w4 < 2 ? w4 * 136 : 128) + lane;
            wg_wait<0>();
            fence_regs<32>(d);
            if (w4 < 2 || (w4 == 2 && lane < 4)) {
#pragma unroll
                for (int f = 0; f < 4; f++) {
                    const int i0 = 8 * (f >> 1) + 2 * (f & 1), i2 = 16 * (f >> 1) + 8 * (f & 1);
                    const float e0 = w4 == 0 ? d[i0] : (w4 == 1 ? d[16 + i0] : d[i2]), e1 = w4 == 0 ? d[i0 + 1] : (w4 == 1 ? d[17 + i0] : d[i2 + 1]);
                    const float e2 = w4 == 0 ? d[i0 + 4] : (w4 == 1 ? d[20 + i0] : d[i2 + 4]), e3 = w4 == 0 ? d[i0 + 5] : (w4 == 1 ? d[21 + i0] : d[i2 + 5]);
                    st_rlx128(kvp + (w4 < 2 ? f * 32 : (f >> 1) * 136 + (f & 1) * 4), tag4(__float_as_uint(e0), __float_as_uint(e1), __float_as_uint(e2), __float_as_uint(e3), tag));
                }
            }
            __syncwarp();
            if (lane == 0) mbar_arrive(bar + 8 * BAR_PUB);
            if (warp == 0) STAMP(3);
#pragma unroll
            for (int r = 0; r < 16; r++) in[r] = qa[r];
        }
        if (warp == 0) STAMP(4);
        {
            mbar_wait(bar + 8 * BAR_KVF, 0);
            uint4 kf[4][3];
#pragma unroll
            for (int hh = 0; hh < 4; hh++) {
                const uint32_t a = sb + OFF_KVF + hh * 1088;
                kf[hh][0] = lds128(a + lane * 32); kf[hh][1] = lds128(a + lane * 32 + 16); kf[hh][2] = lds128(a + 1024 + q * 16);
            }
            if (warp == 0) STAMP(5);
            uint4* og = scr->o + ((bi_i * 8 + warp) * 32 + bi_j * 4) * 32 + lane;
#pragma unroll
            for (int hh = 0; hh < 4; hh++) {
                float c[6][4];
#pragma unroll
                for (int t = 0; t < 6; t++) { c[t][0] = c[t][1] = c[t][2] = c[t][3] = 0.f; }
                const uint32_t* a = pq[hh];
                const bool od = g & 1;
                mma16816(c[0], a[0], a[1], a[2], a[3], od ? 0x3f803f80u : kf[hh][2].x, od ? 0x3f803f80u : kf[hh][2].y);
                mma16816(c[1], a[4], a[5], a[6], a[7], od ? 0x3f803f80u : kf[hh][2].z, od ? 0x3f803f80u : kf[hh][2].w);
                mma16816(c[2], a[0], a[1], a[2], a[3], kf[hh][0].x, kf[hh][0].y);
                mma16816(c[3], a[0], a[1], a[2], a[3], kf[hh][0].z, kf[hh][0].w);
                mma16816(c[4], a[4], a[5], a[6], a[7], kf[hh][1].x, kf[hh][1].y);
                mma16816(c[5], a[4], a[5], a[6], a[7], kf[hh][1].z, kf[hh][1].w);
                uint32_t w[4];
#pragma unroll
                for (int k = 0; k < 2; k++) {
                    const float rho = c[0][2 * k + 1] * rcp(c[1][2 * k + 1]);
                    const float r = rcp(fmaf(c[0][2 * k + 1], 1e-6f, fmaf(rho, c[1][2 * k], c[0][2 * k]))), rr = r * rho;
                    w[k] = pack2(fmaf(c[4][2 * k], rr, c[2][2 * k] * r), fmaf(c[4][2 * k + 1], rr, c[2][2 * k + 1] * r));
                    w[2 + k] = pack2(fmaf(c[5][2 * k], rr, c[3][2 * k] * r), fmaf(c[5][2 * k + 1], rr, c[3][2 * k + 1] * r));
                }
                st_rlx128(og + hh * 32, tag4(w[0], w[1], w[2], w[3], tag));
            }
        }
        if (warp == 0) STAMP(6);
        float oc[64];
        const int slab = bi_i * 8 + (bi_j >> 2) * 4 + w4;
        const uint8_t* ysrc = (const uint8_t*)scr->y + (size_t)((bi_j & 3) * 32 + wg * 16 + (q >> 1)) * 16384 + slab * 128 + g * 16 + (q & 1) * 8;
        const unsigned* gp = scr->g + (slab * 8 + (g >> 1)) * 8 + (g & 1) * 4;
        uint2 yv[8]; unsigned g0, g1;
        {
            const uint4* osrc = scr->o + (slab * 32 + wg * 16) * 32 + lane;
            uint4 fr[16];
            const unsigned* probe = (const unsigned*)(osrc - lane + ((lane & 3) * 4 + 3) * 32 + 31) + 2;
            {
                unsigned miss = ~0u;
                int n = 0;
#pragma unroll
                for (int s = 0; s < 4; s++) {
#pragma unroll 1
                    while ((miss >> s) & 1) { miss = __ballot_sync(~0u, (ld_rlx(probe) ^ tag) & 1); if (++n > SPIN_LIMIT) break; }
#pragma unroll
                    for (int k = 4 * s; k < 4 * s + 4; k++) fr[k] = ld_rlx128(osrc + k * 32);
                }
            }
            if (warp == 0) STAMP(14);
            mbar_wait(bar + 8 * (wg ? BAR_WO2 : BAR_WO), 0);
            const uint64_t dw = mkdesc(sb + wg * 2 * SLOT, wg ? 32768 : SLOT, 1024);
#pragma unroll
            for (int s = 0; s < 4; s++) {
                int n = 0;
#pragma unroll 1
                while (__builtin_expect(__any_sync(~0u, (bad4(fr[4 * s], tag) | bad4(fr[4 * s + 1], tag) | bad4(fr[4 * s + 2], tag) | bad4(fr[4 * s + 3], tag)) & 1), 0)) {
#pragma unroll
                    for (int k = 4 * s; k < 4 * s + 4; k++) fr[k] = ld_rlx128(osrc + k * 32);
                    if (++n > SPIN_LIMIT) break;
                }
                wg_fence();
#pragma unroll
                for (int hh = 0; hh < 4; hh++) wgmma128_rs(oc, fr[4 * s + hh], dw + 128 * (4 * s + hh), (s | hh) != 0);
                wg_commit();
                if (s == 1) {
                    wg_wait<1>();
#pragma unroll
                    for (int nt = 0; nt < 8; nt++) yv[nt] = ld_rlx64(ysrc + nt * 32768);
                    g0 = ld_rlx(gp); g1 = ld_rlx(gp + 32);
                }
            }
            if (warp == 0) STAMP(7);
            {
                const unsigned* yprobe = scr->yflag + ((bi_j & 3) * 32 + wg * 16 + (lane & 15)) * 8;
                int n = 0;
#pragma unroll 1
                while (true) {
                    uint32_t bad = (g0 ^ tag) | (g1 ^ tag);
#pragma unroll
                    for (int nt = 0; nt < 8; nt++) bad |= yv[nt].x ^ tag;
                    if (!__any_sync(~0u, bad & 1)) break;
#pragma unroll 1
                    while (__any_sync(~0u, (ld_rlx(yprobe) ^ tag) & 1)) { if (++n > SPIN_LIMIT) break; }
#pragma unroll
                    for (int nt = 0; nt < 8; nt++) yv[nt] = ld_rlx64(ysrc + nt * 32768);
                    g0 = ld_rlx(gp); g1 = ld_rlx(gp + 32);
                    if (++n > SPIN_LIMIT) break;
                }
            }
            if (warp == 0) STAMP(28);
        }
        {
            const float ga = bf_hi(g0), gb = bf_hi(g1);
            const float ha = bf_round(1.0f - ga), hb = bf_round(1.0f - gb);
            float yb[32];
#pragma unroll
            for (int nt = 0; nt < 8; nt++) {
                yb[4 * nt] = ha * bf_lo(yv[nt].x); yb[4 * nt + 1] = ha * bf_hi(yv[nt].x);
                yb[4 * nt + 2] = hb * bf_lo(yv[nt].y); yb[4 * nt + 3] = hb * bf_hi(yv[nt].y);
            }
            fence_regs<32>(yb);
            const uint32_t xw = sb + wg * 2 * SLOT + (tid & 127) * 16, xr = sb + (wg ^ 1) * 2 * SLOT + (tid & 127) * 16;
            wg_wait<0>();
            fence_regs<64>(oc);
            bar_named(3 + wg, 128);
#pragma unroll
            for (int r = 0; r < 8; r++)
                sts128(xw + r * 2048, __float_as_uint(oc[32 + 4 * r]), __float_as_uint(oc[33 + 4 * r]), __float_as_uint(oc[34 + 4 * r]), __float_as_uint(oc[35 + 4 * r]));
#pragma unroll
            for (int r = 0; r < 32; r++) yb[r] = fmaf((r & 2) ? gb : ga, oc[r], yb[r]);
            bar_named(1, 256);
            if (warp == 0) STAMP(8);
            uint32_t w[8][2];
#pragma unroll
            for (int nt = 0; nt < 8; nt++) {
                const uint4 p = lds128(xr + nt * 2048);
                w[nt][0] = pack2(fmaf(ga, __uint_as_float(p.x), yb[4 * nt]), fmaf(ga, __uint_as_float(p.y), yb[4 * nt + 1]));
                w[nt][1] = pack2(fmaf(gb, __uint_as_float(p.z), yb[4 * nt + 2]), fmaf(gb, __uint_as_float(p.w), yb[4 * nt + 3]));
            }
            const uint32_t ob = sb + wg * 2 * SLOT + 16384 + w4 * 2048;
#pragma unroll
            for (int nt = 0; nt < 8; nt += 2)
                stsm4(ob + (lane & 15) * 128 + (((nt + shi) ^ (lane & 7)) << 4), w[nt][0], w[nt][1], w[nt + 1][0], w[nt + 1][1]);
            __syncwarp();
            bf16* op = out + (size_t)(slab * 16) * 512 + (bi_j & 3) * 128 + wg * 64 + (lane & 7) * 8;
#pragma unroll
            for (int it = 0; it < 4; it++) {
                const int r = it * 4 + (lane >> 3);
                uint4 v = lds128(ob + r * 128 + (((lane & 7) ^ (r & 7)) << 4));
                *(uint4*)(op + r * 512) = v;
            }
        }
        if (warp == 0) STAMP(10);
    } else if (warp < 12) {
#pragma unroll
        for (int src = 2; src >= 0; src--) {
            if (src != 0) mbar_wait(bar + 8 * (src == 2 ? BAR_KGA : BAR_KG), 0);
#pragma unroll
            for (int t = 0; t < 6; t++) {
                const uint4 v = lds128(stg_of(w4 + src * 4) + (t * 32 + lane) * 16);
                kc[4 * t] += __uint_as_float(v.x); kc[4 * t + 1] += __uint_as_float(v.y); kc[4 * t + 2] += __uint_as_float(v.z); kc[4 * t + 3] += __uint_as_float(v.w);
            }
            if (src != 1) {
                bar_named(2, 128);
                if (st == 0) { load_stage(src == 2 ? 2 : 3); if (src == 0) mbar_arrive(bar + 8 * BAR_SP); }
                if (warp == 8) STAMP(src == 2 ? 22 : 17);
            }
        }
        if (warp == 8) {
#pragma unroll 1
            for (int kb = 0; kb < 6; kb++) {
                const int s = kb & 3;
                mbar_wait(bar + 8 * (BAR_EMPTY + s), kb >> 2);
                if (kb == xkb) mbar_wait(bar + 8 * BAR_XT, 0);
                if (lane == 0) {
                    STAMP(48 + kb);
                    if (kb < 4) load_stage(kb + 4);
                    else {
                        mbar_expect(bar + 8 * BAR_WO, 32768);
                        tma2d(sb + s * SLOT, &mwo, (bi_j & 3) * 128 + s * 64, 0, bar + 8 * BAR_WO);
                        if (kb == 5) mbar_arrive(bar + 8 * BAR_SP2);
                    }
                }
                __syncwarp();
            }
        } else if (warp == 9) {
            const int row = bi_j * 16 + (lane >> 1), half = lane & 1;
            unsigned* gp = scr->g + (bi_i * 64 + bi_j * 8) * 8 + lane * 2;
            st_rlx64(gp, tag ^ 1u, tag ^ 1u);
            if (lane < 8) st_rlx32(scr->yflag + bi * 8 + lane, tag ^ 1u);
            float gs0 = 0.f, gs1 = 0.f;
            mbar_wait(bar + 8 * BAR_WPHI, 0);
#pragma unroll 1
            for (int kb = 0; kb < 8; kb++) {
                const int s = kb & 3;
                mbar_wait(bar + 8 * (BAR_FULL + s), kb >> 2);
#pragma unroll
                for (int c = 0; c < 4; c++) {
                    const uint4 xv = lds128(sb + s * SLOT + row * 128 + (((half * 4 + c) ^ (row & 7)) << 4));
                    const uint4 gw = lds128(sb + OFF_GW + ((kb + rot) & 7) * 128 + half * 64 + c * 16);
                    const uint32_t p0 = hmul2(xv.x, gw.x), p1 = hmul2(xv.y, gw.y), p2 = hmul2(xv.z, gw.z), p3 = hmul2(xv.w, gw.w);
                    gs0 += (bf_lo(p0) + bf_lo(p1)) + (bf_lo(p2) + bf_lo(p3));
                    gs1 += (bf_hi(p0) + bf_hi(p1)) + (bf_hi(p2) + bf_hi(p3));
                }
                asm volatile("" : "+f"(gs0), "+f"(gs1));
                __syncwarp();
                if (lane == 0) mbar_arrive(bar + 8 * (kb < 7 ? BAR_EMPTY + s : BAR_DONE));
            }
            float gs = gs0 + gs1;
            gs += __shfl_xor_sync(~0u, gs, 1);
            const uint32_t gv = __float_as_uint(bf_round(rcp(1.0f + ex2(-1.4426950408889634f * bf_round(gs))))) | tag;
            st_rlx64(gp, gv, gv);
        }
        if (lane == 0) kc[4 * 0 + 0] += ((ch & 1) ? bf_hi(pds) : bf_lo(pds));
        const uint32_t k1024 = __shfl_sync(~0u, pack2(kc[4 * 4 + 0], 0.f), 0);
#pragma unroll
        for (int i = 0; i < 2; i++) {
            const int be = g + 8 * i;
#pragma unroll
            for (int t = 0; t < 2; t++) {
                const uint32_t a = kb_ + (KW_D + 128 * t + 8 * be + 2 * q) * 4;
                const uint32_t w = pack2(kc[4 * t + 2 * i + 1], kc[4 * t + 2 * i]);
                sts32(a + 4, w); sts16(a, w >> 16); sts16(a + 10, w);
            }
            {
                const int p = 256 + 128 * (q >> 1) + 8 * be + 4 * (q & 1);
                const uint32_t a = kb_ + (KW_D + p) * 4;
                const uint32_t w = pack2(kc[4 * 2 + 2 * i + 1], kc[4 * 2 + 2 * i]);
                const uint32_t aa = (w >> 16) | (w & 0xffff0000u);
                if (p != 256) { sts16(a - 4, aa); sts32(a, aa); } else sts16(a, aa);
                sts32(a + 4, aa); sts32(a + 8, w); sts16(a + 14, w);
            }
            {
                const int k = 64 + 16 * q + be;
                const uint32_t w = pack2(kc[4 * 3 + 2 * i], kc[4 * 3 + 2 * i + 1]);
                if (k != 64) sts16(kb_ + (KW_2 + ((k - 1) >> 1) - 24) * 4 + (k & 1) * 2, w);
                else {
                    const uint32_t a = kb_ + (KW_D + 511) * 4, aa = (w << 16) | (w & 0xffffu);
                    sts16(a, w); sts32(a + 4, aa); sts32(a + 8, aa); sts32(a + 12, aa); sts16(a + 18, w);
                }
                sts16(kb_ + (KW_2 + 48 + (k >> 1) - 24) * 4 + ((k & 1) ^ 1) * 2, w >> 16);
            }
#pragma unroll
            for (int b = 0; b < 2; b++) {
                const int k = 64 + 8 * (2 * q + b) + (be >> 1);
                const uint32_t w = pack2(kc[4 * 4 + 2 * i + b], 0.f);
                if (!(be & 1) && k == 64) sts16(kb_ + (KW_2 + 63 - 24) * 4, w);
                else {
                    const uint32_t a = kb_ + (KW_3 + ((be & 1) ? 80 + k : k - 1) - 48) * 4;
                    sts16(a, w);
                    if (!((be & 1) && k == 127)) sts16(a + 6, w);
                }
            }
        }
        if (lane == 0) sts16(kb_ + (KW_3 + 127 - 48) * 4, pack2(kc[4 * 5 + 0], 0.f));
        __syncwarp();
        mbar_wait(bar + 8 * BAR_UR, 0);
        mbar_wait(bar + 8 * CONV_START, 0);
        if (warp == 8) STAMP(23);
        float y[16][4];
#pragma unroll
        for (int nt = 0; nt < 16; nt++) { y[nt][0] = y[nt][1] = y[nt][2] = y[nt][3] = 0.f; }
        {
            uint32_t Bp[32], A[4][3], An[4][3];
            auto uaddr = [&](int rho) { const int R0 = (lane >> 4) * 64 + (lane & 7) - rho; return ub + (((2 * R0 + ((lane >> 3) & 1)) ^ ((R0 >> 2) & 1)) << 4); };
            const uint32_t kd = kb_ + (KW_D + g - 2 * q) * 4;
#pragma unroll 1
            for (int rho = 1; rho >= 0; rho--) {
                const uint32_t a = uaddr(rho), k = kd + 2048 + rho * 64;
#pragma unroll
                for (int i = 0; i < 8; i++) ldsm4(Bp + 4 * i, a + i * 256);
                const uint32_t a0 = lds32(k), a1 = lds32(k + 32), a2 = lds32(k - 32);
#pragma unroll
                for (int i = 0; i < 12; i++) mma16816(y[i + 4], a0, a1, a2, a0, Bp[4 * (i & 7) + 2 * (i >> 3)], Bp[4 * (i & 7) + 2 * (i >> 3) + 1]);
            }
#pragma unroll
            for (int ga = 0; ga < 4; ga++) { An[ga][0] = lds32(kd + ga * 512); An[ga][1] = lds32(kd + ga * 512 + 32); An[ga][2] = lds32(kd + ga * 512 - 32); }
#pragma unroll 1
            for (int rho = 0; rho < 8; rho++) {
#pragma unroll
                for (int ga = 0; ga < 4; ga++) {
                    const uint32_t a = kd + (rho + 1) * 64 + ga * 512;
                    A[ga][0] = An[ga][0]; A[ga][1] = An[ga][1]; A[ga][2] = An[ga][2];
                    An[ga][0] = lds32(a); An[ga][1] = lds32(a + 32); An[ga][2] = lds32(a - 32);
                }
                const uint32_t an = uaddr(rho + 1);
#pragma unroll
                for (int i = 0; i < 8; i++) {
#pragma unroll
                    for (int ga = 0; ga < 4; ga++) {
                        mma16816(y[i + ga], A[ga][0], A[ga][1], A[ga][2], A[ga][0], Bp[4 * i], Bp[4 * i + 1]);
                        if (i + 8 + ga < 16) mma16816(y[i + 8 + ga], A[ga][0], A[ga][1], A[ga][2], A[ga][0], Bp[4 * i + 2], Bp[4 * i + 3]);
                    }
                    ldsm4(Bp + 4 * i, an + i * 256);
                    __syncwarp();
                }
            }
        }
        if (warp == 8) STAMP(18);
        mbar_wait(bar + 8 * BAR_WR, 0);
#pragma unroll 1
        for (int ph = 0; ph < 2; ph++) {
            uint32_t B[5][2];
            const uint32_t ka = kb_ + (KW_2 + ph * 48 + 8 + g - q) * 4;
#pragma unroll
            for (int dd = 0; dd < 5; dd++) { B[dd][0] = lds32(ka + dd * 32); B[dd][1] = lds32(ka + dd * 32 - 16); }
            const uint32_t wa = buf + ph * W3_OFF + ((lane & 7) + ((lane >> 3) & 1) + (lane >> 4) * 8) * 16;
#pragma unroll
            for (int s = 0; s < 12; s++) {
                uint32_t A[4];
                ldsm4t(A, wa + s * 256);
#pragma unroll
                for (int dd = 0; dd < 5; dd++)
                    if (s + 4 + dd < 16) mma16816(y[s + 4 + dd], A[0], A[1], A[2], A[3], B[dd][0], B[dd][1]);
            }
        }
        {
            const int ap = (lane & 7) + (lane >> 4) * 8;
            const uint32_t loff = ((2 * ap + ((lane >> 3) & 1)) ^ ((ap >> 2) & 1)) << 4;
#pragma unroll 1
            for (int ph = 0; ph < 2; ph++) {
                uint32_t B[8][2];
                const uint32_t wb = (ph ? spare : buf + W9_OFF) + loff;
                const uint32_t ka = kb_ + (KW_3 + ph * 80 + 16 + g - 2 * q) * 4;
#pragma unroll
                for (int dd = 0; dd < 8; dd++) { B[dd][0] = lds32(ka + dd * 32); B[dd][1] = lds32(ka + dd * 32 - 32); }
#pragma unroll
                for (int s = 0; s < 4; s++) {
                    uint32_t A[4];
                    ldsm4t(A, wb + s * 512);
#pragma unroll
                    for (int dd = 0; dd < 8; dd++)
                        if (8 + 2 * s + dd < 16) mma16816(y[8 + 2 * s + dd], A[0], A[1], A[2], A[3], B[dd][0], B[dd][1]);
                }
            }
            const uint32_t idw = (g == 2 * q) ? k1024 : ((g == 2 * q + 1) ? (k1024 << 16) : 0u);
#pragma unroll
            for (int s = 0; s < 4; s++) {
                uint32_t A[4];
                ldsm4t(A, spare + 2048 + loff + s * 512);
                mma16816(y[8 + 2 * s], A[0], A[1], A[2], A[3], idw, 0u);
                mma16816(y[9 + 2 * s], A[0], A[1], A[2], A[3], 0u, idw);
            }
        }
        __syncwarp();
        if (warp == 8) STAMP(19);
#pragma unroll
        for (int nt = 0; nt < 16; nt++)
#pragma unroll
            for (int b = 0; b < 2; b++) sts32(buf + ((8 * nt + 2 * q + b) * 8 + g) * 4, pack2(y[nt][b], y[nt][2 + b]));
        bar_named(2, 128);
        uint4* yp = scr->y + bi * 1024 + st;
#pragma unroll
        for (int v = 0; v < 8; v++) {
            const uint32_t a = sb + OFF_BUF + (st + 128 * v) * 4;
            const uint32_t w0 = lds32(a), w1 = lds32(a + BUF_STRIDE), w2 = lds32(a + 2 * BUF_STRIDE), w3 = lds32(a + 3 * BUF_STRIDE);
            st_rlx128(yp + v * 128, tag4(__byte_perm(w0, w1, 0x5410), __byte_perm(w0, w1, 0x7632), __byte_perm(w2, w3, 0x5410), __byte_perm(w2, w3, 0x7632), tag));
        }
        if (st < 8) st_rlx32(scr->yflag + bi * 8 + st, tag);
        if (warp == 8) STAMP(20);
    } else {
        asm volatile("setmaxnreg.dec.sync.aligned.u32 64;");
        const int qq = (bi_i & 2) + ((lane >> 1) & 1);
        uint2* kvf_h = (uint2*)(scr->kvf + (bi_j * 4 + (bi_i >> 2)) * 68);
        auto windows = [&](int rhi, int rlo) {
#pragma unroll 1
            for (int rho = rhi; rho >= rlo; rho--) {
                if (rho == 3) mbar_wait(bar + 8 * BAR_SP2, 0);
                const int ci = lane + 32 * rho;
                uint4 e4[4];
#pragma unroll
                for (int v = 0; v < 4; v++) { const int cc = ci - 3 + v; e4[v] = lds128(ub + ((cc ^ ((cc >> 3) & 1)) << 4)); }
                float S[29];
                const uint32_t* ew = (const uint32_t*)e4;
                S[3] = 0.f;
#pragma unroll
                for (int k = 4; k <= 28; k++) S[k] = S[k - 1] + ((k & 1) ? bf_hi(ew[k >> 1]) : bf_lo(ew[k >> 1]));
                auto win = [&](int lo, int hi, uint32_t a) {
                    sts128(a, pack2(S[hi] - S[lo - 1], S[hi + 1] - S[lo]), pack2(S[hi + 2] - S[lo + 1], S[hi + 3] - S[lo + 2]),
                           pack2(S[hi + 4] - S[lo + 3], S[hi + 5] - S[lo + 4]), pack2(S[hi + 6] - S[lo + 5], S[hi + 7] - S[lo + 6]));
                };
                win(14, 18, buf + W5_OFF + 16 + ci * 16); win(19, 21, buf + W3_OFF + 16 + ci * 16);
                if (rho < 4) {
                    const uint32_t sw = (ci ^ ((ci >> 3) & 1)) << 4;
                    win(4, 12, buf + W9_OFF + sw); win(13, 19, spare + sw); win(20, 21, spare + 2048 + sw);
                }
            }
        };
        {
            mbar_wait(bar + 8 * (BAR_FULL + xkb), 0);
#pragma unroll 1
            for (int hf = 0; hf < 2; hf++) {
                const int r = w4 * 32 + hf * 16 + (lane & 15);
                uint32_t* xt = (uint32_t*)scr->xt + ((xkb + rot) * 16 + (g >> 2)) * 4096 + (bi_i * 16 + w4 * 4 + hf * 2) * 16 + (g & 3) * 4 + q;
#pragma unroll
                for (int cb = 0; cb < 8; cb += 2) {
                    uint32_t v[4];
                    ldsm4t(v, sb + xkb * SLOT + r * 128 + (((cb + (lane >> 4)) ^ (r & 7)) << 4));
                    xt[cb * 8192] = v[0]; xt[cb * 8192 + 16] = v[1]; xt[cb * 8192 + 8192] = v[2]; xt[cb * 8192 + 8192 + 16] = v[3];
                }
            }
            __syncwarp();
            if (lane == 0) {
                mbar_arrive(bar + 8 * BAR_XT);
                STAMP(26);
                asm volatile("red.release.gpu.global.add.u32 [%0],2;" ::"l"(scr->xcnt + (xkb + rot) * 32) : "memory");
                STAMP(27);
            }
            __syncwarp();
            {
                const uint32_t old = tag ^ 1u;
                const uint4 z4 = make_uint4(old, 0, old, 0);
#pragma unroll
                for (int v = 0; v < 5; v++) if (v < 4 || st < 32) st_rlx128(scr->kvp + bi * 544 + v * 128 + st, z4);
                if (st < 16) st_rlx128(scr->o + ((bi_i * 8 + (st >> 1)) * 32 + bi_j * 4 + 3) * 32 + 30 + (st & 1), z4);
                if (lane < 8) st_rlx64(kvf_h + ((bi_i & 3) * 8 + w4 * 2 + (lane & 1)) * 4 + (lane >> 1), old, 0);
                if (st < 4 && !(bi_i & 1)) st_rlx64(kvf_h + (64 + qq) * 2 + (lane & 1), old, 0);
                __syncwarp();
                if (lane == 0) mbar_arrive(bar + 8 * BAR_PREP);
            }
            int n = 0;
#pragma unroll 1
            while (__any_sync(~0u, (int)(ld_acq(scr->xcnt + bi_j * 32) - (epoch1 << 7)) < 0)) { if (++n > SPIN_LIMIT) break; }
            if (warp == 12) STAMP(15);
            uint4 ur[8];
#pragma unroll
            for (int v = 0; v < 8; v++) ur[v] = __ldcg(scr->xt + bi * 1024 + st + 128 * v);
            mbar_wait(bar + 8 * BAR_SP, 0);
            if (lane < 16) sts128(ub - 256 + lane * 16, 0, 0, 0, 0);
            if (lane < 2) sts128(buf + lane * W3_OFF, 0, 0, 0, 0);
#pragma unroll
            for (int v = 0; v < 8; v++) {
                const int ci = (st >> 2) + 32 * v;
                sts128(sb + OFF_U + (st & 3) * U_STRIDE + 256 + ((ci ^ ((ci >> 3) & 1)) << 4), ur[v].x, ur[v].y, ur[v].z, ur[v].w);
            }
            __syncwarp();
            if (lane == 0) mbar_arrive(bar + 8 * BAR_UR);
            mbar_wait(bar + 8 * BAR_UR, 0);
            if (warp == 12) STAMP(16);
        }
        windows(5, 0);
        __syncwarp();
        if (lane == 0) mbar_arrive(bar + 8 * BAR_WR);
        if (warp == 12) STAMP(24);
        {
            const bool zw = st < 32 && !(bi_i & 1);
            const uint4* src = scr->kvp + bi_j * (16 * 544) + (bi_i >> 2) * 136;
            const uint4* zsrc = src + (lane >> 2) * (2 * 544) + 128 + (lane & 1) * 4 + qq;
            src += (lane >> 3) * (4 * 544) + ((lane >> 1) & 3) * 32 + (bi_i & 3) * 8 + w4 * 2 + (lane & 1);
            mbar_wait(bar + 8 * BAR_PUB, 0);
            if (warp == 12) STAMP(12);
            __nanosleep(D1_NS);
            uint4 v[6];
#pragma unroll
            for (int k = 0; k < 6; k++) v[k] = make_uint4(tag ^ 1u, 0, 0, 0);
            int n = 0;
#pragma unroll 1
            while (true) {
#pragma unroll
                for (int k = 0; k < 6; k++) if ((bad4(v[k], tag) & 1) && (k < 4 || zw)) v[k] = ld_rlx128(k < 4 ? src + k * 544 : zsrc + (k - 4) * 544);
                if (!__any_sync(~0u, (bad4(v[0], tag) | bad4(v[1], tag) | bad4(v[2], tag) | bad4(v[3], tag) | (zw ? bad4(v[4], tag) | bad4(v[5], tag) : 0u)) & 1)) break;
                if (warp == 12 && n < 3) STAMP(54 + n);
                if (++n > SPIN_LIMIT) break;
                __nanosleep(POLL_NS);
            }
            if (warp == 12) STAMP(30);
            float f[8];
            const float* vf = (const float*)v;
#pragma unroll
            for (int r = 0; r < 4; r++) {
                f[r] = (vf[r] + vf[4 + r]) + (vf[8 + r] + vf[12 + r]);
                f[4 + r] = vf[16 + r] + vf[20 + r];
                f[4 + r] += __shfl_xor_sync(~0u, f[4 + r], 4);
            }
#pragma unroll
            for (int o = 8; o <= 16; o <<= 1)
#pragma unroll
                for (int r = 0; r < 8; r++) f[r] += __shfl_xor_sync(~0u, f[r], o);
            if (lane < 8) st_rlx64(kvf_h + ((bi_i & 3) * 8 + w4 * 2 + (lane & 1)) * 4 + (lane >> 1), tagw(pack2(f[0], f[1]), tag), pack2(f[2], f[3]));
            if (zw && lane < 4) st_rlx64(kvf_h + (64 + qq) * 2 + (lane & 1), tagw(pack2(f[4], f[5]), tag), pack2(f[6], f[7]));
        }
        if (warp == 12) STAMP(13);
        {
            const uint4* kp = scr->kvf + bi_j * 272 + st;
            __nanosleep(D2_NS);
            uint4 v0 = make_uint4(tag ^ 1u, 0, 0, 0), v1 = v0, v2 = make_uint4(st < 16 ? tag ^ 1u : tag, 0, tag, 0);
            int n = 0;
#pragma unroll 1
            while (true) {
                if (bad4(v0, tag) & 1) v0 = ld_rlx128(kp);
                if (bad4(v1, tag) & 1) v1 = ld_rlx128(kp + 128);
                if (bad4(v2, tag) & 1) v2 = ld_rlx128(kp + 256);
                if (!__any_sync(~0u, (bad4(v0, tag) | bad4(v1, tag) | bad4(v2, tag)) & 1)) break;
                if (++n > SPIN_LIMIT) break;
                __nanosleep(POLL_NS);
            }
            sts128(sb + OFF_KVF + st * 16, v0.x, v0.y, v0.z, v0.w);
            sts128(sb + OFF_KVF + 2048 + st * 16, v1.x, v1.y, v1.z, v1.w);
            if (st < 16) sts128(sb + OFF_KVF + 4096 + st * 16, v2.x, v2.y, v2.z, v2.w);
            __syncwarp();
            if (lane == 0) mbar_arrive(bar + 8 * BAR_KVF);
        }
        if (warp == 13) {
            mbar_wait(bar + 8 * BAR_KVF, 0);
            if (lane == 0) {
                mbar_expect(bar + 8 * BAR_WO2, 65536);
                tma2d(sb + OFF_P, &mwo, (bi_j & 3) * 128 + 64, 256, bar + 8 * BAR_WO2);
                tma2d(sb + OFF_V, &mwo, (bi_j & 3) * 128, 256, bar + 8 * BAR_WO2);
            }
        }
        if (warp == 12) STAMP(25);
    }
    __syncwarp();
    if (lane == 0) {
        unsigned old;
        asm volatile("atom.acq_rel.cta.shared.add.u32 %0,[%1],1;" : "=r"(old) : "r"(bar + OFF_CNT) : "memory");
        if (old == 15) {
            atomicAdd(scr->done, 1u);
        }
    }
}

typedef CUresult (*EncFn)(CUtensorMap*, CUtensorMapDataType, cuuint32_t, void*, const cuuint64_t*, const cuuint64_t*, const cuuint32_t*,
                          const cuuint32_t*, CUtensorMapInterleave, CUtensorMapSwizzle, CUtensorMapL2promotion, CUtensorMapFloatOOBfill);

extern "C" void kernel_launch(void* const* d_in, const int* in_sizes, int n_in, void* d_out, int out_size) {
    static EncFn enc = nullptr;
    static Scratch* scr = nullptr;
    if (!enc) {
        cudaGetSymbolAddress((void**)&scr, g_scr);
        cudaDriverEntryPointQueryResult qr;
        cudaGetDriverEntryPoint("cuTensorMapEncodeTiled", (void**)&enc, cudaEnableDefault, &qr);
        cudaFuncSetAttribute(fused_kernel, cudaFuncAttributeMaxDynamicSharedMemorySize, SMEM_BYTES);
    }
    CUtensorMap mx, mw, mwo;
    const cuuint32_t es[3] = {1, 1, 1};
    {
        cuuint64_t d[2] = {512, 2048}, s[1] = {1024}; cuuint32_t b[2] = {64, 128};
        enc(&mx, CU_TENSOR_MAP_DATA_TYPE_BFLOAT16, 2, d_in[0], d, s, b, es, CU_TENSOR_MAP_INTERLEAVE_NONE, CU_TENSOR_MAP_SWIZZLE_128B,
            CU_TENSOR_MAP_L2_PROMOTION_L2_128B, CU_TENSOR_MAP_FLOAT_OOB_FILL_NONE);
    }
    {
        cuuint64_t d[3] = {512, 512, 3}, s[2] = {3072, 1024}; cuuint32_t b[3] = {64, 64, 3};
        enc(&mw, CU_TENSOR_MAP_DATA_TYPE_BFLOAT16, 3, d_in[1], d, s, b, es, CU_TENSOR_MAP_INTERLEAVE_NONE, CU_TENSOR_MAP_SWIZZLE_128B,
            CU_TENSOR_MAP_L2_PROMOTION_L2_128B, CU_TENSOR_MAP_FLOAT_OOB_FILL_NONE);
    }
    {
        cuuint64_t d[2] = {512, 512}, s[1] = {1024}; cuuint32_t b[2] = {64, 256};
        enc(&mwo, CU_TENSOR_MAP_DATA_TYPE_BFLOAT16, 2, d_in[3], d, s, b, es, CU_TENSOR_MAP_INTERLEAVE_NONE, CU_TENSOR_MAP_SWIZZLE_128B,
            CU_TENSOR_MAP_L2_PROMOTION_L2_128B, CU_TENSOR_MAP_FLOAT_OOB_FILL_NONE);
    }
    fused_kernel<<<128, 512, SMEM_BYTES, cudaStreamPerThread>>>(
        scr, (const bf16*)d_in[5], (const bf16*)d_in[6], (const bf16*)d_in[7], (const bf16*)d_in[8], (const bf16*)d_in[9],
        (const bf16*)d_in[10], (const bf16*)d_in[2], (const bf16*)d_in[11], (bf16*)d_out, mx, mw, mwo);
}
```

```cpp
#include <cuda_runtime.h>
#include <cuda.h>
#include <cuda_bf16.h>
#include <stdint.h>

typedef __nv_bfloat16 bf16;

struct Scratch {
    uint4 xt[128 * 1024];
    uint4 o[16 * 8 * 32 * 32];
    uint4 y[128 * 1024];
    uint4 kvp[8 * 16 * 544];
    uint4 kvf[8 * 4 * 68];
    unsigned g[1024 * 8];
    unsigned yflag[128 * 8];
    unsigned xcnt[8 * 32];
    unsigned done[32];
};
__device__ Scratch g_scr;
#define STAMP(n)

constexpr int SLOT = 40960;
constexpr int OFF_SP0 = 32768, OFF_SP1 = SLOT + 32768;
constexpr int OFF_P = 2 * SLOT, OFF_V = OFF_P + 32768;
constexpr int OFF_KVF = OFF_V + 32768;
constexpr int KT_BYTES = 3264, KW_D = 16, KW_2 = 560, KW_3 = 656;
constexpr int OFF_U = 4 * SLOT, U_STRIDE = 4096 + 256 + 32;
constexpr int OFF_BUF = OFF_U + 4 * U_STRIDE, BUF_STRIDE = 8320;
constexpr int OFF_K = OFF_BUF + 4 * BUF_STRIDE;
constexpr int OFF_WPHI = OFF_K + 4 * KT_BYTES;
constexpr int OFF_GW = OFF_WPHI + 2048;
constexpr int OFF_BAR = OFF_GW + 1024;
constexpr int SMEM_BYTES = OFF_BAR + 256 + 256;
static_assert(SMEM_BYTES <= 232448 && OFF_BUF % 128 == 0, "smem");
constexpr int W5_OFF = 0, W3_OFF = 3088, W9_OFF = 6176;
constexpr int BAR_FULL = 0, BAR_EMPTY = 4, BAR_WPHI = 8, BAR_WO = 9, BAR_WO2 = 10, BAR_XT = 11, BAR_DONE = 12, BAR_KG = 13, BAR_SP = 14,
              BAR_PUB = 15, BAR_KVF = 16, BAR_UR = 17, BAR_WR = 18, BAR_PREP = 19, BAR_KGA = 20, BAR_SP2 = 21, BAR_GO = 22, OFF_CNT = 192, OFF_TAG = 196;
#define CONV_START BAR_DONE
#define D1_NS 0
#define D2_NS 0
#define D3_NS 100
#define PS_NS 100
#define POLL_NS 0
constexpr int SPIN_LIMIT = 1 << 17;

__device__ __forceinline__ uint32_t s2u(const void* p) { return (uint32_t)__cvta_generic_to_shared(p); }
__device__ __forceinline__ void mbar_init(uint32_t b, int c) { asm volatile("mbarrier.init.shared::cta.b64 [%0],%1;" ::"r"(b), "r"(c) : "memory"); }
__device__ __forceinline__ void mbar_expect(uint32_t b, int bytes) { asm volatile("mbarrier.arrive.expect_tx.shared::cta.b64 _,[%0],%1;" ::"r"(b), "r"(bytes) : "memory"); }
__device__ __forceinline__ void mbar_arrive(uint32_t b) { asm volatile("mbarrier.arrive.shared::cta.b64 _,[%0];" ::"r"(b) : "memory"); }
__device__ __forceinline__ void mbar_wait(uint32_t b, int ph) {
    asm volatile("{\n.reg .pred p;\n.reg .u32 n;\nmov.u32 n,0;\nLW_%=:\nmbarrier.try_wait.parity.shared::cta.b64 p,[%0],%1;\n@p bra LD_%=;\n"
                 "add.u32 n,n,1;\nsetp.lt.u32 p,n,16384;\n@p bra LW_%=;\nLD_%=:\n}" ::"r"(b), "r"(ph) : "memory");
}
__device__ __forceinline__ void tma2d(uint32_t dst, const CUtensorMap* m, int c0, int c1, uint32_t bar) {
    asm volatile("cp.async.bulk.tensor.2d.shared::cluster.global.mbarrier::complete_tx::bytes [%0],[%1,{%3,%4}],[%2];" ::"r"(dst), "l"(m), "r"(bar), "r"(c0), "r"(c1) : "memory");
}
__device__ __forceinline__ void tma3d(uint32_t dst, const CUtensorMap* m, int c0, int c1, int c2, uint32_t bar) {
    asm volatile("cp.async.bulk.tensor.3d.shared::cluster.global.mbarrier::complete_tx::bytes [%0],[%1,{%3,%4,%5}],[%2];" ::"r"(dst), "l"(m), "r"(bar), "r"(c0), "r"(c1), "r"(c2) : "memory");
}
__device__ __forceinline__ void bulk_g2s(uint32_t dst, const void* src, int bytes, uint32_t bar) {
    asm volatile("cp.async.bulk.shared::cluster.global.mbarrier::complete_tx::bytes [%0],[%1],%2,[%3];" ::"r"(dst), "l"(src), "r"(bytes), "r"(bar) : "memory");
}
__device__ __forceinline__ uint64_t mkdesc(uint32_t addr, uint32_t lbo, uint32_t sbo) {
    return (uint64_t)((addr & 0x3FFFF) >> 4) | ((uint64_t)(lbo >> 4) << 16) | ((uint64_t)(sbo >> 4) << 32) | ((uint64_t)1 << 62);
}
__device__ __forceinline__ void wg_fence() { asm volatile("wgmma.fence.sync.aligned;" ::: "memory"); }
__device__ __forceinline__ void wg_commit() { asm volatile("wgmma.commit_group.sync.aligned;" ::: "memory"); }
template <int N> __device__ __forceinline__ void wg_wait() { asm volatile("wgmma.wait_group.sync.aligned %0;" ::"n"(N) : "memory"); }
template <int N> __device__ __forceinline__ void fence_regs(float* d) {
#pragma unroll
    for (int i = 0; i < N; i++) asm volatile("" : "+f"(d[i])::"memory");
}
#define R8(d, o) "+f"(d[o]), "+f"(d[o + 1]), "+f"(d[o + 2]), "+f"(d[o + 3]), "+f"(d[o + 4]), "+f"(d[o + 5]), "+f"(d[o + 6]), "+f"(d[o + 7])
__device__ __forceinline__ void wgmma192(float* d, uint64_t da, uint64_t db) {
    asm volatile("wgmma.mma_async.sync.aligned.m64n192k16.f32.bf16.bf16 {"
                 "%0,%1,%2,%3,%4,%5,%6,%7,%8,%9,%10,%11,%12,%13,%14,%15,%16,%17,%18,%19,%20,%21,%22,%23,%24,%25,%26,%27,%28,%29,%30,%31,"
                 "%32,%33,%34,%35,%36,%37,%38,%39,%40,%41,%42,%43,%44,%45,%46,%47,%48,%49,%50,%51,%52,%53,%54,%55,%56,%57,%58,%59,%60,%61,%62,%63,"
                 "%64,%65,%66,%67,%68,%69,%70,%71,%72,%73,%74,%75,%76,%77,%78,%79,%80,%81,%82,%83,%84,%85,%86,%87,%88,%89,%90,%91,%92,%93,%94,%95},"
                 "%96,%97,1,1,1,0,1;"
                 : R8(d, 0), R8(d, 8), R8(d, 16), R8(d, 24), R8(d, 32), R8(d, 40), R8(d, 48), R8(d, 56), R8(d, 64), R8(d, 72), R8(d, 80), R8(d, 88)
                 : "l"(da), "l"(db));
}
__device__ __forceinline__ void wgmma64_tt(float* d, uint64_t da, uint64_t db, int sc) {
    asm volatile("{.reg .pred p; setp.ne.b32 p,%34,0; wgmma.mma_async.sync.aligned.m64n64k16.f32.bf16.bf16 {"
                 "%0,%1,%2,%3,%4,%5,%6,%7,%8,%9,%10,%11,%12,%13,%14,%15,%16,%17,%18,%19,%20,%21,%22,%23,%24,%25,%26,%27,%28,%29,%30,%31},"
                 "%32,%33,p,1,1,1,1;}"
                 : R8(d, 0), R8(d, 8), R8(d, 16), R8(d, 24)
                 : "l"(da), "l"(db), "r"(sc));
}
__device__ __forceinline__ void wgmma128_rs(float* d, const uint4& a, uint64_t db, int sc) {
    asm volatile("{.reg .pred p; setp.ne.b32 p,%69,0; wgmma.mma_async.sync.aligned.m64n128k16.f32.bf16.bf16 {"
                 "%0,%1,%2,%3,%4,%5,%6,%7,%8,%9,%10,%11,%12,%13,%14,%15,%16,%17,%18,%19,%20,%21,%22,%23,%24,%25,%26,%27,%28,%29,%30,%31,"
                 "%32,%33,%34,%35,%36,%37,%38,%39,%40,%41,%42,%43,%44,%45,%46,%47,%48,%49,%50,%51,%52,%53,%54,%55,%56,%57,%58,%59,%60,%61,%62,%63},"
                 "{%64,%65,%66,%67},%68,p,1,1,1;}"
                 : R8(d, 0), R8(d, 8), R8(d, 16), R8(d, 24), R8(d, 32), R8(d, 40), R8(d, 48), R8(d, 56)
                 : "r"(a.x), "r"(a.y), "r"(a.z), "r"(a.w), "l"(db), "r"(sc));
}
__device__ __forceinline__ void mma16816(float* c, uint32_t a0, uint32_t a1, uint32_t a2, uint32_t a3, uint32_t b0, uint32_t b1) {
    asm("mma.sync.aligned.m16n8k16.row.col.f32.bf16.bf16.f32 {%0,%1,%2,%3},{%4,%5,%6,%7},{%8,%9},{%0,%1,%2,%3};"
        : "+f"(c[0]), "+f"(c[1]), "+f"(c[2]), "+f"(c[3]) : "r"(a0), "r"(a1), "r"(a2), "r"(a3), "r"(b0), "r"(b1));
}
__device__ __forceinline__ void ldsm4(uint32_t* r, uint32_t a) {
    asm volatile("ldmatrix.sync.aligned.m8n8.x4.shared.b16 {%0,%1,%2,%3},[%4];" : "=r"(r[0]), "=r"(r[1]), "=r"(r[2]), "=r"(r[3]) : "r"(a) : "memory");
}
__device__ __forceinline__ void ldsm4t(uint32_t* r, uint32_t a) {
    asm volatile("ldmatrix.sync.aligned.m8n8.x4.trans.shared.b16 {%0,%1,%2,%3},[%4];" : "=r"(r[0]), "=r"(r[1]), "=r"(r[2]), "=r"(r[3]) : "r"(a) : "memory");
}
__device__ __forceinline__ void stsm4(uint32_t a, uint32_t r0, uint32_t r1, uint32_t r2, uint32_t r3) {
    asm volatile("stmatrix.sync.aligned.m8n8.x4.shared.b16 [%0],{%1,%2,%3,%4};" ::"r"(a), "r"(r0), "r"(r1), "r"(r2), "r"(r3) : "memory");
}
__device__ __forceinline__ uint32_t lds32(uint32_t a) { uint32_t v; asm volatile("ld.shared.b32 %0,[%1];" : "=r"(v) : "r"(a) : "memory"); return v; }
__device__ __forceinline__ uint4 lds128(uint32_t a) { uint4 v; asm volatile("ld.shared.v4.b32 {%0,%1,%2,%3},[%4];" : "=r"(v.x), "=r"(v.y), "=r"(v.z), "=r"(v.w) : "r"(a) : "memory"); return v; }
__device__ __forceinline__ void sts16(uint32_t a, uint32_t v) { asm volatile("st.shared.b16 [%0],%1;" ::"r"(a), "h"((unsigned short)v) : "memory"); }
__device__ __forceinline__ void sts32(uint32_t a, uint32_t v) { asm volatile("st.shared.b32 [%0],%1;" ::"r"(a), "r"(v) : "memory"); }
__device__ __forceinline__ void sts64(uint32_t a, uint32_t x, uint32_t y) { asm volatile("st.shared.v2.b32 [%0],{%1,%2};" ::"r"(a), "r"(x), "r"(y) : "memory"); }
__device__ __forceinline__ void sts128(uint32_t a, uint32_t x, uint32_t y, uint32_t z, uint32_t w) { asm volatile("st.shared.v4.b32 [%0],{%1,%2,%3,%4};" ::"r"(a), "r"(x), "r"(y), "r"(z), "r"(w) : "memory"); }
__device__ __forceinline__ uint32_t pack2(float lo, float hi) { uint32_t d; asm("cvt.rn.bf16x2.f32 %0,%1,%2;" : "=r"(d) : "f"(hi), "f"(lo)); return d; }
__device__ __forceinline__ float bf_lo(uint32_t v) { return __uint_as_float(v << 16); }
__device__ __forceinline__ float bf_hi(uint32_t v) { return __uint_as_float(v & 0xffff0000u); }
__device__ __forceinline__ float bf_round(float v) { return bf_lo(pack2(v, 0.f)); }
__device__ __forceinline__ uint32_t hmax2(uint32_t a, uint32_t b) { uint32_t d; asm("max.bf16x2 %0,%1,%2;" : "=r"(d) : "r"(a), "r"(b)); return d; }
__device__ __forceinline__ uint32_t hmin2(uint32_t a, uint32_t b) { uint32_t d; asm("min.bf16x2 %0,%1,%2;" : "=r"(d) : "r"(a), "r"(b)); return d; }
__device__ __forceinline__ uint32_t hmul2(uint32_t a, uint32_t b) { uint32_t d; asm("mul.rn.bf16x2 %0,%1,%2;" : "=r"(d) : "r"(a), "r"(b)); return d; }
__device__ __forceinline__ float ex2(float x) { float y; asm("ex2.approx.ftz.f32 %0,%1;" : "=f"(y) : "f"(x)); return y; }
__device__ __forceinline__ float rcp(float x) { float y; asm("rcp.approx.ftz.f32 %0,%1;" : "=f"(y) : "f"(x)); return y; }
__device__ __forceinline__ uint32_t ld_nc(const uint32_t* p) { uint32_t v; asm volatile("ld.global.nc.b32 %0,[%1];" : "=r"(v) : "l"(p)); return v; }
__device__ __forceinline__ uint2 ld_nc64(const uint2* p) { uint2 v; asm volatile("ld.global.nc.v2.b32 {%0,%1},[%2];" : "=r"(v.x), "=r"(v.y) : "l"(p)); return v; }
__device__ __forceinline__ unsigned ld_acq(const unsigned* p) { unsigned v; asm volatile("ld.acquire.gpu.global.u32 %0,[%1];" : "=r"(v) : "l"(p) : "memory"); return v; }
__device__ __forceinline__ unsigned ld_rlx(const unsigned* p) { unsigned v; asm volatile("ld.relaxed.gpu.global.u32 %0,[%1];" : "=r"(v) : "l"(p) : "memory"); return v; }
__device__ __forceinline__ uint2 ld_rlx64(const void* p) { uint2 v; asm volatile("{.reg .b64 t; ld.relaxed.gpu.global.b64 t,[%2]; mov.b64 {%0,%1},t;}" : "=r"(v.x), "=r"(v.y) : "l"(p) : "memory"); return v; }
__device__ __forceinline__ uint4 ld_rlx128(const void* p) {
    uint4 v;
    asm volatile("{.reg .b64 t,u; ld.relaxed.gpu.global.v2.b64 {t,u},[%4]; mov.b64 {%0,%1},t; mov.b64 {%2,%3},u;}" : "=r"(v.x), "=r"(v.y), "=r"(v.z), "=r"(v.w) : "l"(p) : "memory");
    return v;
}
__device__ __forceinline__ void st_rlx32(void* p, uint32_t x) { asm volatile("st.relaxed.gpu.global.u32 [%0],%1;" ::"l"(p), "r"(x) : "memory"); }
__device__ __forceinline__ void st_rlx64(void* p, uint32_t x, uint32_t y) { asm volatile("{.reg .b64 t; mov.b64 t,{%1,%2}; st.relaxed.gpu.global.b64 [%0],t;}" ::"l"(p), "r"(x), "r"(y) : "memory"); }
__device__ __forceinline__ void st_rlx128(void* p, uint4 v) {
    asm volatile("{.reg .b64 t,u; mov.b64 t,{%1,%2}; mov.b64 u,{%3,%4}; st.relaxed.gpu.global.v2.b64 [%0],{t,u};}" ::"l"(p), "r"(v.x), "r"(v.y), "r"(v.z), "r"(v.w) : "memory");
}
__device__ __forceinline__ uint32_t tagw(uint32_t w, uint32_t tag) { return (w & ~1u) | tag; }
__device__ __forceinline__ uint4 tag4(uint32_t x, uint32_t y, uint32_t z, uint32_t w, uint32_t tag) { return make_uint4(tagw(x, tag), y, tagw(z, tag), w); }
__device__ __forceinline__ uint32_t bad4(const uint4& v, uint32_t tag) { return (v.x ^ tag) | (v.z ^ tag); }
__device__ __forceinline__ void bar_named(int id, int n) { asm volatile("bar.sync %0,%1;" ::"r"(id), "r"(n) : "memory"); }

struct cf { float re, im; };
__device__ __forceinline__ cf cmul(cf a, cf b) { cf r; r.re = a.re * b.re - a.im * b.im; r.im = a.re * b.im + a.im * b.re; return r; }
__device__ __forceinline__ cf cexp_p(float arl, float ait, float p) {
    float mag = ex2(arl * p);
    float t = ait * p;
    t = (t - rintf(t)) * 6.283185307179586f;
    cf r; r.re = mag * __cosf(t); r.im = mag * __sinf(t);
    return r;
}

__device__ __forceinline__ void hedgehog4(const uint32_t* a, uint32_t wphi_addr, uint32_t (*out)[8]) {
    float p[4][2][4], mx[4][2];
#pragma unroll
    for (int h = 0; h < 4; h++) {
        uint32_t b[4];
        ldsm4t(b, wphi_addr + h * 512);
        float c0[4] = {0.f, 0.f, 0.f, 0.f}, c1[4] = {0.f, 0.f, 0.f, 0.f};
        mma16816(c0, a[4 * h], a[4 * h + 1], a[4 * h + 2], a[4 * h + 3], b[0], b[1]);
        mma16816(c1, a[4 * h], a[4 * h + 1], a[4 * h + 2], a[4 * h + 3], b[2], b[3]);
#pragma unroll
        for (int k = 0; k < 2; k++) {
            p[h][k][0] = c0[2 * k]; p[h][k][1] = c0[2 * k + 1]; p[h][k][2] = c1[2 * k]; p[h][k][3] = c1[2 * k + 1];
            mx[h][k] = fmaxf(fmaxf(p[h][k][0], p[h][k][1]), fmaxf(p[h][k][2], p[h][k][3]));
        }
    }
#pragma unroll
    for (int o = 1; o <= 2; o <<= 1)
#pragma unroll
        for (int h = 0; h < 4; h++)
#pragma unroll
            for (int k = 0; k < 2; k++) mx[h][k] = fmaxf(mx[h][k], __shfl_xor_sync(~0u, mx[h][k], o));
    const float L = 1.4426950408889634f;
    float pmin = 1.f;
#pragma unroll
    for (int h = 0; h < 4; h++)
#pragma unroll
        for (int k = 0; k < 2; k++) {
            const float m = -mx[h][k] * L;
            const float e0 = ex2(fmaf(p[h][k][0], L, m)), e1 = ex2(fmaf(p[h][k][1], L, m)), e2 = ex2(fmaf(p[h][k][2], L, m)), e3 = ex2(fmaf(p[h][k][3], L, m));
            const float p01 = e0 * e1, p23 = e2 * e3, pp = p01 * p23, r = rcp(pp), r01 = r * p23, r23 = r * p01;
            pmin = fminf(pmin, pp);
            out[h][k] = pack2(e0, e1); out[h][k + 2] = pack2(e2, e3);
            out[h][4 + k] = pack2(r01 * e1, r01 * e0); out[h][4 + k + 2] = pack2(r23 * e3, r23 * e2);
        }
    if (__builtin_expect(__any_sync(~0u, !(pmin > 1e-18f)), 0)) {
#pragma unroll
        for (int h = 0; h < 4; h++)
#pragma unroll
            for (int k = 0; k < 2; k++) {
                float m = fminf(fminf(p[h][k][0], p[h][k][1]), fminf(p[h][k][2], p[h][k][3]));
                m = fminf(m, __shfl_xor_sync(~0u, m, 1));
                m = fminf(m, __shfl_xor_sync(~0u, m, 2)) * L;
                out[h][4 + k] = pack2(ex2(fmaf(p[h][k][0], -L, m)), ex2(fmaf(p[h][k][1], -L, m)));
                out[h][4 + k + 2] = pack2(ex2(fmaf(p[h][k][2], -L, m)), ex2(fmaf(p[h][k][3], -L, m)));
            }
    }
}

__global__ void __launch_bounds__(512, 1)
fused_kernel(Scratch* __restrict__ scr, const bf16* __restrict__ logA, const bf16* __restrict__ Aim, const bf16* __restrict__ Cre,
             const bf16* __restrict__ Cim, const bf16* __restrict__ logdt, const bf16* __restrict__ Dskip, const bf16* __restrict__ wphi,
             const bf16* __restrict__ gatew, bf16* __restrict__ out,
             const __grid_constant__ CUtensorMap mx, const __grid_constant__ CUtensorMap mw, const __grid_constant__ CUtensorMap mwo) {
    extern __shared__ __align__(1024) uint8_t smem[];
    constexpr uint32_t sb = 1024;
    const int tid = threadIdx.x, warp = __shfl_sync(~0u, tid >> 5, 0), lane = tid & 31;
    const int g = lane >> 2, q = lane & 3, w4 = warp & 3;
    const int bi = blockIdx.x, bi_i = bi & 15, bi_j = bi >> 4;
    const uint32_t bar = sb + OFF_BAR;
    const int rot = (bi_j & 3) * 2, xkb = bi_j >> 2;
    auto load_stage = [&](int kb) {
        const uint32_t b = bar + 8 * (BAR_FULL + (kb & 3)), d = sb + (kb & 3) * SLOT;
        const int kc = ((kb + rot) & 7) * 64;
        mbar_expect(b, SLOT);
        tma2d(d, &mx, kc, bi_i * 128, b);
        tma3d(d + 16384, &mw, bi_j * 64, kc, 0, b);
    };

    const int ch = bi * 4 + w4;
    const int pidx = ch * 64 + lane * 2 + (warp >> 3);
    const uint32_t pla = ld_nc((const uint32_t*)logA + pidx), pai = ld_nc((const uint32_t*)Aim + pidx);
    const uint32_t pcr = ld_nc((const uint32_t*)Cre + pidx), pci = ld_nc((const uint32_t*)Cim + pidx);
    uint32_t pdt = ld_nc((const uint32_t*)logdt + (ch >> 1));
    const uint32_t pds = ld_nc((const uint32_t*)Dskip + (ch >> 1));
    unsigned done0 = ld_rlx(scr->done);
    if (tid == 0) {
        for (int s = 0; s < 4; s++) mbar_init(bar + 8 * (BAR_FULL + s), 1);
        asm volatile("fence.mbarrier_init.release.cluster;" ::: "memory");
        asm volatile("prefetch.tensormap [%0];" ::"l"(&mx) : "memory");
        load_stage(0); load_stage(1);
        STAMP(11);
    } else if (tid == 32) {
        if (s2u(smem) != sb) __trap();
        sts32(bar + OFF_CNT, 0);
        for (int s = 0; s < 4; s++) mbar_init(bar + 8 * (BAR_EMPTY + s), 9);
        mbar_init(bar + 8 * BAR_WPHI, 1); mbar_init(bar + 8 * BAR_WO, 2); mbar_init(bar + 8 * BAR_WO2, 1); mbar_init(bar + 8 * BAR_XT, 4);
        mbar_init(bar + 8 * BAR_DONE, 9); mbar_init(bar + 8 * BAR_KG, 8); mbar_init(bar + 8 * BAR_SP, 1); mbar_init(bar + 8 * BAR_PUB, 8);
        mbar_init(bar + 8 * BAR_KVF, 4); mbar_init(bar + 8 * BAR_UR, 4); mbar_init(bar + 8 * BAR_WR, 4); mbar_init(bar + 8 * BAR_PREP, 4); mbar_init(bar + 8 * BAR_KGA, 4); mbar_init(bar + 8 * BAR_SP2, 1); mbar_init(bar + 8 * BAR_GO, 8);
        asm volatile("fence.mbarrier_init.release.cluster;" ::: "memory");
        mbar_expect(bar + 8 * BAR_WPHI, 3072);
        bulk_g2s(sb + OFF_GW, gatew, 1024, bar + 8 * BAR_WPHI);
        bulk_g2s(sb + OFF_WPHI, wphi + bi_j * 1024, 2048, bar + 8 * BAR_WPHI);
    } else if (tid == 64) {
        asm volatile("prefetch.tensormap [%0];" ::"l"(&mw) : "memory");
    }
    const uint32_t buf = sb + OFF_BUF + w4 * BUF_STRIDE, kb_ = sb + OFF_K + w4 * KT_BYTES;
    if ((warp >> 2) == 2) {
#pragma unroll
        for (int v = 0; v < 7; v++) if (v * 32 + lane < KT_BYTES / 16) sts128(kb_ + (v * 32 + lane) * 16, 0, 0, 0, 0);
    }
    __syncthreads();
    asm volatile("" : "+r"(pdt), "+r"(done0)::"memory");
    const unsigned epoch1 = (done0 >> 7) + 1u;
    const uint32_t tag = epoch1 & 1u;

    const int st = tid & 127;
    const uint32_t ub = sb + OFF_U + w4 * U_STRIDE + 256, spare = sb + (w4 < 2 ? OFF_SP0 : OFF_SP1) + (w4 & 1) * 4096;

    auto stg_of = [&](int w) { return w < 8 ? sb + 3 * SLOT + w * 7296 : sb + 2 * SLOT + (w & 3) * 7296; };
    float kc[24];
#pragma unroll
    for (int t = 0; t < 24; t++) kc[t] = 0.f;
    {
        const float dt = bf_round(expf((ch & 1) ? bf_hi(pdt) : bf_lo(pdt)));
        const uint32_t stg = (warp >> 2) == 2 ? buf : stg_of(warp);
        const int sh = ((warp >> 2) & 1) * 16;
        auto pick = [&](uint32_t v) { return __uint_as_float((v >> sh) << 16); };
        const float ea = bf_round(ex2(pick(pla) * 1.4426950408889634f));
        const float arl = (-ea * dt) * 1.4426950408889634f, ait = (pick(pai) * dt) * 0.15915494309189535f;
        cf C2; C2.re = 2.0f * (pick(pcr) * dt); C2.im = 2.0f * (pick(pci) * dt);
        const cf z1 = cexp_p(arl, ait, 1.0f), z128 = cexp_p(arl, ait, 128.0f);
        cf z8 = cexp_p(arl, ait, 8.0f); z8.im = -z8.im;
        const uint32_t lp = stg + lane * 4;
        auto put = [&](int row, const cf& v) { sts32((lp ^ ((row & 7) << 4)) + row * 128, pack2(v.re, v.im)); };
        {
            const cf z16 = cmul(z8, z8);
            cf e; e.re = 1.f; e.im = 0.f;
            cf o = z8;
            put(0, e); put(1, o);
            e = z16; put(2, e);
#pragma unroll
            for (int b = 3; b < 16; b += 2) {
                o = cmul(o, z16); put(b, o);
                if (b + 1 < 16) { e = cmul(e, z16); put(b + 1, e); }
            }
        }
        cf h[8];
        h[0] = C2; put(16, h[0]);
        {
            const cf z2 = cmul(z1, z1);
            h[1] = cmul(h[0], z1);
#pragma unroll
            for (int r = 2; r < 8; r++) h[r] = cmul(h[r - 2], z2);
#pragma unroll
            for (int r = 1; r < 8; r++) put(16 + r, h[r]);
        }
#pragma unroll
        for (int r = 0; r < 8; r++) { h[r] = cmul(h[r], z128); put(24 + r, h[r]); }
#pragma unroll
        for (int al = 0; al < 2; al++)
#pragma unroll
            for (int r = 0; r < 4; r++) { h[2 * r] = cmul(h[2 * r], z128); put(32 + al * 4 + r, h[2 * r]); }
#pragma unroll
        for (int al = 0; al < 4; al++)
#pragma unroll
            for (int r = 0; r < 2; r++) { h[4 * r] = cmul(h[4 * r], z128); put(40 + al * 2 + r, h[4 * r]); }
#pragma unroll
        for (int al = 0; al < 9; al++) { h[0] = cmul(h[0], z128); put(48 + al, h[0]); }
        __syncwarp();
        const int lr = lane & 7, lm = lane >> 3;
#pragma unroll
        for (int kp = 0; kp < 2; kp++) {
            uint32_t a0[4], a1[4];
            ldsm4(a0, stg + ((lm & 1) * 8 + lr) * 128 + (((4 * kp + (lm >> 1)) ^ lr) << 4));
            ldsm4(a1, stg + ((lm & 1) * 8 + lr) * 128 + (((4 * kp + 2 + (lm >> 1)) ^ lr) << 4));
#pragma unroll
            for (int t = 0; t < 6; t++) {
                uint32_t b[4];
                ldsm4(b, stg + (16 + 8 * t + lr) * 128 + (((4 * kp + lm) ^ lr) << 4));
                mma16816(kc + 4 * t, a0[0], a0[1], a0[2], a0[3], b[0], b[1]);
                mma16816(kc + 4 * t, a1[0], a1[1], a1[2], a1[3], b[2], b[3]);
            }
        }
        __syncwarp();
        if ((warp >> 2) != 2) {
#pragma unroll
            for (int t = 0; t < 6; t++)
                sts128(stg + (t * 32 + lane) * 16, __float_as_uint(kc[4 * t]), __float_as_uint(kc[4 * t + 1]), __float_as_uint(kc[4 * t + 2]), __float_as_uint(kc[4 * t + 3]));
            asm volatile("fence.proxy.async.shared::cta;" ::: "memory");
            __syncwarp();
            if (lane == 0) mbar_arrive(bar + 8 * (warp < 8 ? BAR_KG : BAR_KGA));
        }
    }

    if (warp < 8) {
        asm volatile("setmaxnreg.inc.sync.aligned.u32 160;");
        const int wg = warp >> 2;
        if (warp == 0) STAMP(21);
        float acc[96];
        const int srow = warp * 16 + (lane & 15);
        const uint32_t srow_a = srow * 128;
        const int sx = srow & 7, shi = lane >> 4;
#pragma unroll
        for (int r = 0; r < 96; r++) acc[r] = 0.f;
        fence_regs<96>(acc);
        const uint64_t da0 = mkdesc(sb + wg * 8192, 16, 1024), db0 = mkdesc(sb + 16384, 8192, 1024);
#pragma unroll 1
        for (int kb = 0; kb < 8; kb++) {
            const int s = kb & 3;
            const uint64_t da = da0 + s * (SLOT >> 4), db = db0 + s * (SLOT >> 4);
            if (warp == 0) STAMP(40 + kb);
            mbar_wait(bar + 8 * (BAR_FULL + s), kb >> 2);
            if (warp == 0) STAMP(32 + kb);
            wg_fence();
#pragma unroll
            for (int k = 0; k < 4; k++) wgmma192(acc, da + 2 * k, db + 128 * k);
            wg_commit();
            wg_wait<1>();
            if (lane == 0 && kb > 0) mbar_arrive(bar + 8 * (BAR_EMPTY + ((kb - 1) & 3)));
        }
        mbar_wait(bar + 8 * BAR_WPHI, 0);
        wg_wait<0>();
        fence_regs<96>(acc);
        if (lane == 0) mbar_arrive(bar + 8 * BAR_DONE);
        if (warp == 0) STAMP(1);
        uint32_t in[16], qa[16];
        mbar_wait(bar + 8 * BAR_DONE, 0);
#pragma unroll
        for (int r = 0; r < 16; r++) {
            in[r] = pack2(acc[32 + 2 * r], acc[32 + 2 * r + 1]);
            qa[r] = pack2(acc[2 * r], acc[2 * r + 1]);
        }
#pragma unroll
        for (int hh = 0; hh < 4; hh++)
            stsm4(sb + OFF_V + (hh >> 1) * 16384 + srow_a + (((2 * (hh & 1) + shi) ^ sx) << 4), pack2(acc[64 + 8 * hh], acc[65 + 8 * hh]),
                  pack2(acc[66 + 8 * hh], acc[67 + 8 * hh]), pack2(acc[68 + 8 * hh], acc[69 + 8 * hh]), pack2(acc[70 + 8 * hh], acc[71 + 8 * hh]));
        sts128(sb + OFF_V + shi * 16384 + srow_a + ((4 ^ sx) << 4), 0x3f803f80u, 0x3f803f80u, 0x3f803f80u, 0x3f803f80u);
        const uint32_t wphi_a = sb + OFF_WPHI + (lane & 15) * 32 + (lane >> 4) * 16;
        uint32_t pq[4][8];
#pragma unroll 1
        for (int it = 0; it < 2; it++) {
            hedgehog4(in, wphi_a, pq);
            if (it == 1) break;
#pragma unroll
            for (int hs = 0; hs < 8; hs++) {
                float c[4] = {0.f, 0.f, 0.f, 0.f};
                const uint32_t* o = pq[hs >> 1] + 4 * (hs & 1);
                mma16816(c, o[0], o[1], o[2], o[3], 0x3f803f80u, 0x3f803f80u);
                const float r0 = rcp(c[0]), r1 = rcp(c[2]);
                const uint32_t s0 = pack2(r0, r0), s1 = pack2(r1, r1);
                stsm4(sb + OFF_P + (hs >> 2) * 16384 + srow_a + (((2 * (hs & 3) + shi) ^ sx) << 4), hmul2(o[0], s0), hmul2(o[1], s1), hmul2(o[2], s0), hmul2(o[3], s1));
            }
            asm volatile("fence.proxy.async.shared::cta;" ::: "memory");
            if (lane == 0) mbar_arrive(bar + 8 * BAR_GO);
            bar_named(1, 256);
            if (warp == 0) STAMP(2);
            float d[32];
            const uint64_t dv = mkdesc(sb + OFF_V + wg * 16384, 16, 1024), dp = mkdesc(sb + OFF_P + wg * 16384, 16, 1024);
            wg_fence();
#pragma unroll
            for (int k = 0; k < 8; k++) wgmma64_tt(d, dv + 128 * k, dp + 128 * k, k != 0);
            wg_commit();
            mbar_wait(bar + 8 * BAR_PREP, 0);
            uint4* kvp = scr->kvp + bi * 544 + wg * 272 + (w4 < 2 ? w4 * 136 : 128) + lane;
            wg_wait<0>();
            fence_regs<32>(d);
            if (w4 < 2 || (w4 == 2 && lane < 4)) {
#pragma unroll
                for (int f = 0; f < 4; f++) {
                    const int i0 = 8 * (f >> 1) + 2 * (f & 1), i2 = 16 * (f >> 1) + 8 * (f & 1);
                    const float e0 = w4 == 0 ? d[i0] : (w4 == 1 ? d[16 + i0] : d[i2]), e1 = w4 == 0 ? d[i0 + 1] : (w4 == 1 ? d[17 + i0] : d[i2 + 1]);
                    const float e2 = w4 == 0 ? d[i0 + 4] : (w4 == 1 ? d[20 + i0] : d[i2 + 4]), e3 = w4 == 0 ? d[i0 + 5] : (w4 == 1 ? d[21 + i0] : d[i2 + 5]);
                    st_rlx128(kvp + (w4 < 2 ? f * 32 : (f >> 1) * 136 + (f & 1) * 4), tag4(__float_as_uint(e0), __float_as_uint(e1), __float_as_uint(e2), __float_as_uint(e3), tag));
                }
            }
            __syncwarp();
            if (lane == 0) mbar_arrive(bar + 8 * BAR_PUB);
            if (warp == 0) STAMP(3);
#pragma unroll
            for (int r = 0; r < 16; r++) in[r] = qa[r];
        }
        if (warp == 0) STAMP(4);
        {
            mbar_wait(bar + 8 * BAR_KVF, 0);
            uint4 kf[4][3];
#pragma unroll
            for (int hh = 0; hh < 4; hh++) {
                const uint32_t a = sb + OFF_KVF + hh * 1088;
                kf[hh][0] = lds128(a + lane * 32); kf[hh][1] = lds128(a + lane * 32 + 16); kf[hh][2] = lds128(a + 1024 + q * 16);
            }
            if (warp == 0) STAMP(5);
            uint4* og = scr->o + ((bi_i * 8 + warp) * 32 + bi_j * 4) * 32 + lane;
#pragma unroll
            for (int hh = 0; hh < 4; hh++) {
                float c[6][4];
#pragma unroll
                for (int t = 0; t < 6; t++) { c[t][0] = c[t][1] = c[t][2] = c[t][3] = 0.f; }
                const uint32_t* a = pq[hh];
                const bool od = g & 1;
                mma16816(c[0], a[0], a[1], a[2], a[3], od ? 0x3f803f80u : kf[hh][2].x, od ? 0x3f803f80u : kf[hh][2].y);
                mma16816(c[1], a[4], a[5], a[6], a[7], od ? 0x3f803f80u : kf[hh][2].z, od ? 0x3f803f80u : kf[hh][2].w);
                mma16816(c[2], a[0], a[1], a[2], a[3], kf[hh][0].x, kf[hh][0].y);
                mma16816(c[3], a[0], a[1], a[2], a[3], kf[hh][0].z, kf[hh][0].w);
                mma16816(c[4], a[4], a[5], a[6], a[7], kf[hh][1].x, kf[hh][1].y);
                mma16816(c[5], a[4], a[5], a[6], a[7], kf[hh][1].z, kf[hh][1].w);
                uint32_t w[4];
#pragma unroll
                for (int k = 0; k < 2; k++) {
                    const float rho = c[0][2 * k + 1] * rcp(c[1][2 * k + 1]);
                    const float r = rcp(fmaf(c[0][2 * k + 1], 1e-6f, fmaf(rho, c[1][2 * k], c[0][2 * k]))), rr = r * rho;
                    w[k] = pack2(fmaf(c[4][2 * k], rr, c[2][2 * k] * r), fmaf(c[4][2 * k + 1], rr, c[2][2 * k + 1] * r));
                    w[2 + k] = pack2(fmaf(c[5][2 * k], rr, c[3][2 * k] * r), fmaf(c[5][2 * k + 1], rr, c[3][2 * k + 1] * r));
                }
                st_rlx128(og + hh * 32, tag4(w[0], w[1], w[2], w[3], tag));
            }
        }
        if (warp == 0) STAMP(6);
        float oc[64];
        const int slab = bi_i * 8 + (bi_j >> 2) * 4 + w4;
        const uint8_t* ysrc = (const uint8_t*)scr->y + (size_t)((bi_j & 3) * 32 + wg * 16 + (q >> 1)) * 16384 + slab * 128 + g * 16 + (q & 1) * 8;
        const unsigned* gp = scr->g + (slab * 8 + (g >> 1)) * 8 + (g & 1) * 4;
        uint2 yv[8]; unsigned g0, g1;
        {
            const uint4* osrc = scr->o + (slab * 32 + wg * 16) * 32 + lane;
            uint4 fr[16];
            const unsigned* probe = (const unsigned*)(osrc - lane + ((lane & 3) * 4 + 3) * 32 + 31) + 2;
            {
                unsigned miss = ~0u;
                int n = 0;
#pragma unroll
                for (int s = 0; s < 4; s++) {
#pragma unroll 1
                    while ((miss >> s) & 1) { miss = __ballot_sync(~0u, (ld_rlx(probe) ^ tag) & 1); if (++n > SPIN_LIMIT) break; }
#pragma unroll
                    for (int k = 4 * s; k < 4 * s + 4; k++) fr[k] = ld_rlx128(osrc + k * 32);
                }
            }
            if (warp == 0) STAMP(14);
            mbar_wait(bar + 8 * (wg ? BAR_WO2 : BAR_WO), 0);
            const uint64_t dw = mkdesc(sb + wg * 2 * SLOT, wg ? 32768 : SLOT, 1024);
#pragma unroll
            for (int s = 0; s < 4; s++) {
                int n = 0;
#pragma unroll 1
                while (__builtin_expect(__any_sync(~0u, (bad4(fr[4 * s], tag) | bad4(fr[4 * s + 1], tag) | bad4(fr[4 * s + 2], tag) | bad4(fr[4 * s + 3], tag)) & 1), 0)) {
#pragma unroll
                    for (int k = 4 * s; k < 4 * s + 4; k++) fr[k] = ld_rlx128(osrc + k * 32);
                    if (++n > SPIN_LIMIT) break;
                }
                wg_fence();
#pragma unroll
                for (int hh = 0; hh < 4; hh++) wgmma128_rs(oc, fr[4 * s + hh], dw + 128 * (4 * s + hh), (s | hh) != 0);
                wg_commit();
                if (s == 1) {
                    wg_wait<1>();
#pragma unroll
                    for (int nt = 0; nt < 8; nt++) yv[nt] = ld_rlx64(ysrc + nt * 32768);
                    g0 = ld_rlx(gp); g1 = ld_rlx(gp + 32);
                }
            }
            if (warp == 0) STAMP(7);
            {
                const unsigned* yprobe = scr->yflag + ((bi_j & 3) * 32 + wg * 16 + (lane & 15)) * 8;
                int n = 0;
#pragma unroll 1
                while (true) {
                    uint32_t bad = (g0 ^ tag) | (g1 ^ tag);
#pragma unroll
                    for (int nt = 0; nt < 8; nt++) bad |= yv[nt].x ^ tag;
                    if (!__any_sync(~0u, bad & 1)) break;
#pragma unroll 1
                    while (__any_sync(~0u, (ld_rlx(yprobe) ^ tag) & 1)) { if (++n > SPIN_LIMIT) break; }
#pragma unroll
                    for (int nt = 0; nt < 8; nt++) yv[nt] = ld_rlx64(ysrc + nt * 32768);
                    g0 = ld_rlx(gp); g1 = ld_rlx(gp + 32);
                    if (++n > SPIN_LIMIT) break;
                }
            }
            if (warp == 0) STAMP(28);
        }
        {
            const float ga = bf_hi(g0), gb = bf_hi(g1);
            const float ha = bf_round(1.0f - ga), hb = bf_round(1.0f - gb);
            float yb[32];
#pragma unroll
            for (int nt = 0; nt < 8; nt++) {
                yb[4 * nt] = ha * bf_lo(yv[nt].x); yb[4 * nt + 1] = ha * bf_hi(yv[nt].x);
                yb[4 * nt + 2] = hb * bf_lo(yv[nt].y); yb[4 * nt + 3] = hb * bf_hi(yv[nt].y);
            }
            fence_regs<32>(yb);
            const uint32_t xw = sb + wg * 2 * SLOT + (tid & 127) * 16, xr = sb + (wg ^ 1) * 2 * SLOT + (tid & 127) * 16;
            wg_wait<0>();
            fence_regs<64>(oc);
            bar_named(3 + wg, 128);
#pragma unroll
            for (int r = 0; r < 8; r++)
                sts128(xw + r * 2048, __float_as_uint(oc[32 + 4 * r]), __float_as_uint(oc[33 + 4 * r]), __float_as_uint(oc[34 + 4 * r]), __float_as_uint(oc[35 + 4 * r]));
#pragma unroll
            for (int r = 0; r < 32; r++) yb[r] = fmaf((r & 2) ? gb : ga, oc[r], yb[r]);
            bar_named(1, 256);
            if (warp == 0) STAMP(8);
            uint32_t w[8][2];
#pragma unroll
            for (int nt = 0; nt < 8; nt++) {
                const uint4 p = lds128(xr + nt * 2048);
                w[nt][0] = pack2(fmaf(ga, __uint_as_float(p.x), yb[4 * nt]), fmaf(ga, __uint_as_float(p.y), yb[4 * nt + 1]));
                w[nt][1] = pack2(fmaf(gb, __uint_as_float(p.z), yb[4 * nt + 2]), fmaf(gb, __uint_as_float(p.w), yb[4 * nt + 3]));
            }
            const uint32_t ob = sb + wg * 2 * SLOT + 16384 + w4 * 2048;
#pragma unroll
            for (int nt = 0; nt < 8; nt += 2)
                stsm4(ob + (lane & 15) * 128 + (((nt + shi) ^ (lane & 7)) << 4), w[nt][0], w[nt][1], w[nt + 1][0], w[nt + 1][1]);
            __syncwarp();
            bf16* op = out + (size_t)(slab * 16) * 512 + (bi_j & 3) * 128 + wg * 64 + (lane & 7) * 8;
#pragma unroll
            for (int it = 0; it < 4; it++) {
                const int r = it * 4 + (lane >> 3);
                uint4 v = lds128(ob + r * 128 + (((lane & 7) ^ (r & 7)) << 4));
                *(uint4*)(op + r * 512) = v;
            }
        }
        if (warp == 0) STAMP(10);
    } else if (warp < 12) {
        if (st == 0) sts32(bar + OFF_TAG, tag);
#pragma unroll
        for (int src = 2; src >= 0; src--) {
            if (src != 0) mbar_wait(bar + 8 * (src == 2 ? BAR_KGA : BAR_KG), 0);
#pragma unroll
            for (int t = 0; t < 6; t++) {
                const uint4 v = lds128(stg_of(w4 + src * 4) + (t * 32 + lane) * 16);
                kc[4 * t] += __uint_as_float(v.x); kc[4 * t + 1] += __uint_as_float(v.y); kc[4 * t + 2] += __uint_as_float(v.z); kc[4 * t + 3] += __uint_as_float(v.w);
            }
            if (src != 1) {
                bar_named(2, 128);
                if (st == 0) { load_stage(src == 2 ? 2 : 3); if (src == 0) mbar_arrive(bar + 8 * BAR_SP); }
                if (warp == 8) STAMP(src == 2 ? 22 : 17);
            }
        }
        if (warp == 8) {
#pragma unroll 1
            for (int kb = 0; kb < 6; kb++) {
                const int s = kb & 3;
                mbar_wait(bar + 8 * (BAR_EMPTY + s), kb >> 2);
                if (kb == xkb) mbar_wait(bar + 8 * BAR_XT, 0);
                if (lane == 0) {
                    STAMP(48 + kb);
                    if (kb < 4) load_stage(kb + 4);
                    else {
                        mbar_expect(bar + 8 * BAR_WO, 32768);
                        tma2d(sb + s * SLOT, &mwo, (bi_j & 3) * 128 + s * 64, 0, bar + 8 * BAR_WO);
                        if (kb == 5) mbar_arrive(bar + 8 * BAR_SP2);
                    }
                }
                __syncwarp();
            }
        } else if (warp == 9) {
            const int row = bi_j * 16 + (lane >> 1), half = lane & 1;
            unsigned* gp = scr->g + (bi_i * 64 + bi_j * 8) * 8 + lane * 2;
            st_rlx64(gp, tag ^ 1u, tag ^ 1u);
            if (lane < 8) st_rlx32(scr->yflag + bi * 8 + lane, tag ^ 1u);
            float gs0 = 0.f, gs1 = 0.f;
            mbar_wait(bar + 8 * BAR_WPHI, 0);
#pragma unroll 1
            for (int kb = 0; kb < 8; kb++) {
                const int s = kb & 3;
                mbar_wait(bar + 8 * (BAR_FULL + s), kb >> 2);
#pragma unroll
                for (int c = 0; c < 4; c++) {
                    const uint4 xv = lds128(sb + s * SLOT + row * 128 + (((half * 4 + c) ^ (row & 7)) << 4));
                    const uint4 gw = lds128(sb + OFF_GW + ((kb + rot) & 7) * 128 + half * 64 + c * 16);
                    const uint32_t p0 = hmul2(xv.x, gw.x), p1 = hmul2(xv.y, gw.y), p2 = hmul2(xv.z, gw.z), p3 = hmul2(xv.w, gw.w);
                    gs0 += (bf_lo(p0) + bf_lo(p1)) + (bf_lo(p2) + bf_lo(p3));
                    gs1 += (bf_hi(p0) + bf_hi(p1)) + (bf_hi(p2) + bf_hi(p3));
                }
                asm volatile("" : "+f"(gs0), "+f"(gs1));
                __syncwarp();
                if (lane == 0) mbar_arrive(bar + 8 * (kb < 7 ? BAR_EMPTY + s : BAR_DONE));
            }
            float gs = gs0 + gs1;
            gs += __shfl_xor_sync(~0u, gs, 1);
            const uint32_t gv = __float_as_uint(bf_round(rcp(1.0f + ex2(-1.4426950408889634f * bf_round(gs))))) | tag;
            st_rlx64(gp, gv, gv);
        }
        if (lane == 0) kc[4 * 0 + 0] += ((ch & 1) ? bf_hi(pds) : bf_lo(pds));
#pragma unroll
        for (int i = 0; i < 2; i++) {
            const int be = g + 8 * i;
#pragma unroll
            for (int t = 0; t < 2; t++) {
                const uint32_t a = kb_ + (KW_D + 128 * t + 8 * be + 2 * q) * 4;
                const uint32_t w = pack2(kc[4 * t + 2 * i + 1], kc[4 * t + 2 * i]);
                sts32(a + 4, w); sts16(a, w >> 16); sts16(a + 10, w);
            }
            {
                const int p = 256 + 128 * (q >> 1) + 8 * be + 4 * (q & 1);
                const uint32_t a = kb_ + (KW_D + p) * 4;
                const uint32_t w = pack2(kc[4 * 2 + 2 * i + 1], kc[4 * 2 + 2 * i]);
                const uint32_t aa = (w >> 16) | (w & 0xffff0000u);
                if (p != 256) { sts16(a - 4, aa); sts32(a, aa); } else sts16(a, aa);
                sts32(a + 4, aa); sts32(a + 8, w); sts16(a + 14, w);
            }
            {
                const int k = 64 + 16 * q + be;
                const uint32_t w = pack2(kc[4 * 3 + 2 * i], kc[4 * 3 + 2 * i + 1]);
                if (k != 64) sts16(kb_ + (KW_2 + ((k - 1) >> 1) - 24) * 4 + (k & 1) * 2, w);
                else {
                    const uint32_t a = kb_ + (KW_D + 511) * 4, aa = (w << 16) | (w & 0xffffu);
                    sts16(a, w); sts32(a + 4, aa); sts32(a + 8, aa); sts32(a + 12, aa); sts16(a + 18, w);
                }
                sts16(kb_ + (KW_2 + 48 + (k >> 1) - 24) * 4 + ((k & 1) ^ 1) * 2, w >> 16);
            }
#pragma unroll
            for (int b = 0; b < 2; b++) {
                const int k = 64 + 8 * (2 * q + b) + (be >> 1);
                const uint32_t w = pack2(kc[4 * 4 + 2 * i + b], 0.f);
                if (!(be & 1) && k == 64) sts16(kb_ + (KW_2 + 63 - 24) * 4, w);
                else {
                    const uint32_t a = kb_ + (KW_3 + ((be & 1) ? 80 + k : k - 1) - 48) * 4;
                    sts16(a, w);
                    if (!((be & 1) && k == 127)) sts16(a + 6, w);
                }
            }
        }
        if (lane == 0) sts16(kb_ + (KW_3 + 127 - 48) * 4, pack2(kc[4 * 5 + 0], 0.f));
        __syncwarp();
        mbar_wait(bar + 8 * BAR_UR, 0);
        mbar_wait(bar + 8 * CONV_START, 0);
        if (warp == 8) STAMP(23);
        float y[16][4];
#pragma unroll
        for (int nt = 0; nt < 16; nt++) { y[nt][0] = y[nt][1] = y[nt][2] = y[nt][3] = 0.f; }
        {
            uint32_t Bp[32], A[4][3], An[4][3];
            auto uaddr = [&](int rho) { const int R0 = (lane >> 4) * 64 + (lane & 7) - rho; return ub + (((2 * R0 + ((lane >> 3) & 1)) ^ ((R0 >> 2) & 1)) << 4); };
            const uint32_t kd = kb_ + (KW_D + g - 2 * q) * 4;
#pragma unroll 1
            for (int rho = 1; rho >= 0; rho--) {
                const uint32_t a = uaddr(rho), k = kd + 2048 + rho * 64;
#pragma unroll
                for (int i = 0; i < 8; i++) ldsm4(Bp + 4 * i, a + i * 256);
                const uint32_t a0 = lds32(k), a1 = lds32(k + 32), a2 = lds32(k - 32);
#pragma unroll
                for (int i = 0; i < 12; i++) mma16816(y[i + 4], a0, a1, a2, a0, Bp[4 * (i & 7) + 2 * (i >> 3)], Bp[4 * (i & 7) + 2 * (i >> 3) + 1]);
            }
#pragma unroll
            for (int ga = 0; ga < 4; ga++) { An[ga][0] = lds32(kd + ga * 512); An[ga][1] = lds32(kd + ga * 512 + 32); An[ga][2] = lds32(kd + ga * 512 - 32); }
            uint32_t ka = kd, le = (ub >> 4) + (lane >> 4) * 128 + (lane & 7) * 2 + ((lane >> 3) & 1);
            const uint32_t kend = kd + 512;
#pragma unroll 1
            while (ka != kend) {
                ka += 64; le -= 2;
#pragma unroll
                for (int ga = 0; ga < 4; ga++) {
                    A[ga][0] = An[ga][0]; A[ga][1] = An[ga][1]; A[ga][2] = An[ga][2];
                    An[ga][0] = lds32(ka + ga * 512); An[ga][1] = lds32(ka + ga * 512 + 32); An[ga][2] = lds32(ka + ga * 512 - 32);
                }
                const uint32_t c = le - (ub >> 4);
                const uint32_t an = ub + ((c ^ ((c >> 3) & 1)) << 4);
#pragma unroll
                for (int i = 0; i < 8; i++) {
#pragma unroll
                    for (int ga = 0; ga < 4; ga++) {
                        mma16816(y[i + ga], A[ga][0], A[ga][1], A[ga][2], A[ga][0], Bp[4 * i], Bp[4 * i + 1]);
                        if (i + 8 + ga < 16) mma16816(y[i + 8 + ga], A[ga][0], A[ga][1], A[ga][2], A[ga][0], Bp[4 * i + 2], Bp[4 * i + 3]);
                    }
                    ldsm4(Bp + 4 * i, an + i * 256);
                    __syncwarp();
                }
            }
        }
        if (warp == 8) STAMP(18);
        {
        uint32_t tx;
        asm volatile("mov.u32 %0,%%tid.x;" : "=r"(tx));
        const int w4 = (tx >> 5) & 3, lane = tx & 31, g = lane >> 2, q = lane & 3, st = tx & 127;
        const uint32_t buf = sb + OFF_BUF + w4 * BUF_STRIDE, kb_ = sb + OFF_K + w4 * KT_BYTES, spare = sb + OFF_SP0 + (w4 >> 1) * SLOT + (w4 & 1) * 4096;
        mbar_wait(bar + 8 * BAR_WR, 0);
#pragma unroll 1
        for (int ph = 0; ph < 2; ph++) {
            uint32_t B[5][2];
            const uint32_t ka = kb_ + (KW_2 + ph * 48 + 8 + g - q) * 4;
#pragma unroll
            for (int dd = 0; dd < 5; dd++) { B[dd][0] = lds32(ka + dd * 32); B[dd][1] = lds32(ka + dd * 32 - 16); }
            const uint32_t wa = buf + ph * W3_OFF + ((lane & 7) + ((lane >> 3) & 1) + (lane >> 4) * 8) * 16;
#pragma unroll
            for (int s = 0; s < 12; s++) {
                uint32_t A[4];
                ldsm4t(A, wa + s * 256);
#pragma unroll
                for (int dd = 0; dd < 5; dd++)
                    if (s + 4 + dd < 16) mma16816(y[s + 4 + dd], A[0], A[1], A[2], A[3], B[dd][0], B[dd][1]);
            }
        }
        {
            const int ap = (lane & 7) + (lane >> 4) * 8;
            const uint32_t loff = ((2 * ap + ((lane >> 3) & 1)) ^ ((ap >> 2) & 1)) << 4;
#pragma unroll 1
            for (int ph = 0; ph < 2; ph++) {
                uint32_t B[8][2];
                const uint32_t wb = (ph ? spare : buf + W9_OFF) + loff;
                const uint32_t ka = kb_ + (KW_3 + ph * 80 + 16 + g - 2 * q) * 4;
#pragma unroll
                for (int dd = 0; dd < 8; dd++) { B[dd][0] = lds32(ka + dd * 32); B[dd][1] = lds32(ka + dd * 32 - 32); }
#pragma unroll
                for (int s = 0; s < 4; s++) {
                    uint32_t A[4];
                    ldsm4t(A, wb + s * 512);
#pragma unroll
                    for (int dd = 0; dd < 8; dd++)
                        if (8 + 2 * s + dd < 16) mma16816(y[8 + 2 * s + dd], A[0], A[1], A[2], A[3], B[dd][0], B[dd][1]);
                }
            }
            const uint32_t k1024 = lds32(kb_ + (KW_2 + 63 - 24) * 4) & 0xffffu;
            const uint32_t idw = (g == 2 * q) ? k1024 : ((g == 2 * q + 1) ? (k1024 << 16) : 0u);
#pragma unroll
            for (int s = 0; s < 4; s++) {
                uint32_t A[4];
                ldsm4t(A, spare + 2048 + loff + s * 512);
                mma16816(y[8 + 2 * s], A[0], A[1], A[2], A[3], idw, 0u);
                mma16816(y[9 + 2 * s], A[0], A[1], A[2], A[3], 0u, idw);
            }
        }
        __syncwarp();
        if (warp == 8) STAMP(19);
#pragma unroll
        for (int nt = 0; nt < 16; nt++)
#pragma unroll
            for (int b = 0; b < 2; b++) sts32(buf + ((8 * nt + 2 * q + b) * 8 + g) * 4, pack2(y[nt][b], y[nt][2 + b]));
        bar_named(2, 128);
        const uint32_t tag2 = lds32(bar + OFF_TAG);
        uint4* yp = scr->y + bi * 1024 + st;
#pragma unroll
        for (int v = 0; v < 8; v++) {
            const uint32_t a = sb + OFF_BUF + (st + 128 * v) * 4;
            const uint32_t w0 = lds32(a), w1 = lds32(a + BUF_STRIDE), w2 = lds32(a + 2 * BUF_STRIDE), w3 = lds32(a + 3 * BUF_STRIDE);
            st_rlx128(yp + v * 128, tag4(__byte_perm(w0, w1, 0x5410), __byte_perm(w0, w1, 0x7632), __byte_perm(w2, w3, 0x5410), __byte_perm(w2, w3, 0x7632), tag2));
        }
        if (st < 8) st_rlx32(scr->yflag + bi * 8 + st, tag2);
        if (warp == 8) STAMP(20);
        }
    } else {
        asm volatile("setmaxnreg.dec.sync.aligned.u32 64;");
        const int qq = (bi_i & 2) + ((lane >> 1) & 1);
        uint2* kvf_h = (uint2*)(scr->kvf + (bi_j * 4 + (bi_i >> 2)) * 68);
        auto windows = [&](int rhi, int rlo) {
#pragma unroll 1
            for (int rho = rhi; rho >= rlo; rho--) {
                const int ci = lane + 32 * rho;
                uint4 e4[4];
#pragma unroll
                for (int v = 0; v < 4; v++) { const int cc = ci - 3 + v; e4[v] = lds128(ub + ((cc ^ ((cc >> 3) & 1)) << 4)); }
                float S[29];
                const uint32_t* ew = (const uint32_t*)e4;
                S[3] = 0.f;
#pragma unroll
                for (int k = 4; k <= 28; k++) S[k] = S[k - 1] + ((k & 1) ? bf_hi(ew[k >> 1]) : bf_lo(ew[k >> 1]));
                auto win = [&](int lo, int hi, uint32_t a) {
                    sts128(a, pack2(S[hi] - S[lo - 1], S[hi + 1] - S[lo]), pack2(S[hi + 2] - S[lo + 1], S[hi + 3] - S[lo + 2]),
                           pack2(S[hi + 4] - S[lo + 3], S[hi + 5] - S[lo + 4]), pack2(S[hi + 6] - S[lo + 5], S[hi + 7] - S[lo + 6]));
                };
                win(14, 18, buf + W5_OFF + 16 + ci * 16); win(19, 21, buf + W3_OFF + 16 + ci * 16);
                if (rho < 4) {
                    const uint32_t sw = (ci ^ ((ci >> 3) & 1)) << 4;
                    win(4, 12, buf + W9_OFF + sw); win(13, 19, spare + sw); win(20, 21, spare + 2048 + sw);
                }
            }
        };
        {
            mbar_wait(bar + 8 * (BAR_FULL + xkb), 0);
#pragma unroll 1
            for (int hf = 0; hf < 2; hf++) {
                const int r = w4 * 32 + hf * 16 + (lane & 15);
                uint32_t* xt = (uint32_t*)scr->xt + ((xkb + rot) * 16 + (g >> 2)) * 4096 + (bi_i * 16 + w4 * 4 + hf * 2) * 16 + (g & 3) * 4 + q;
#pragma unroll
                for (int cb = 0; cb < 8; cb += 2) {
                    uint32_t v[4];
                    ldsm4t(v, sb + xkb * SLOT + r * 128 + (((cb + (lane >> 4)) ^ (r & 7)) << 4));
                    xt[cb * 8192] = v[0]; xt[cb * 8192 + 16] = v[1]; xt[cb * 8192 + 8192] = v[2]; xt[cb * 8192 + 8192 + 16] = v[3];
                }
            }
            __syncwarp();
            if (lane == 0) {
                mbar_arrive(bar + 8 * BAR_XT);
                STAMP(26);
                asm volatile("red.release.gpu.global.add.u32 [%0],2;" ::"l"(scr->xcnt + (xkb + rot) * 32) : "memory");
                STAMP(27);
            }
            __syncwarp();
            {
                const uint32_t old = tag ^ 1u;
                const uint4 z4 = make_uint4(old, 0, old, 0);
#pragma unroll
                for (int v = 0; v < 5; v++) if (v < 4 || st < 32) st_rlx128(scr->kvp + bi * 544 + v * 128 + st, z4);
                if (st < 16) st_rlx128(scr->o + ((bi_i * 8 + (st >> 1)) * 32 + bi_j * 4 + 3) * 32 + 30 + (st & 1), z4);
                if (lane < 8) st_rlx64(kvf_h + ((bi_i & 3) * 8 + w4 * 2 + (lane & 1)) * 4 + (lane >> 1), old, 0);
                if (st < 4 && !(bi_i & 1)) st_rlx64(kvf_h + (64 + qq) * 2 + (lane & 1), old, 0);
                __syncwarp();
                if (lane == 0) mbar_arrive(bar + 8 * BAR_PREP);
            }
            int n = 0;
#pragma unroll 1
            while (__any_sync(~0u, (int)(ld_acq(scr->xcnt + bi_j * 32) - (epoch1 << 7)) < 0)) { if (++n > SPIN_LIMIT) break; }
            if (warp == 12) STAMP(15);
            uint4 ur[8];
#pragma unroll
            for (int v = 0; v < 8; v++) ur[v] = __ldcg(scr->xt + bi * 1024 + st + 128 * v);
            mbar_wait(bar + 8 * BAR_SP, 0);
            if (lane < 16) sts128(ub - 256 + lane * 16, 0, 0, 0, 0);
            if (lane < 2) sts128(buf + lane * W3_OFF, 0, 0, 0, 0);
#pragma unroll
            for (int v = 0; v < 8; v++) {
                const int ci = (st >> 2) + 32 * v;
                sts128(sb + OFF_U + (st & 3) * U_STRIDE + 256 + ((ci ^ ((ci >> 3) & 1)) << 4), ur[v].x, ur[v].y, ur[v].z, ur[v].w);
            }
            __syncwarp();
            if (lane == 0) mbar_arrive(bar + 8 * BAR_UR);
            mbar_wait(bar + 8 * BAR_UR, 0);
            if (warp == 12) STAMP(16);
        }
        windows(5, 4);
        mbar_wait(bar + 8 * BAR_SP2, 0);
        windows(3, 0);
        __syncwarp();
        if (lane == 0) mbar_arrive(bar + 8 * BAR_WR);
        if (warp == 12) STAMP(24);
        {
            const bool zw = st < 32 && !(bi_i & 1);
            const uint4* src = scr->kvp + bi_j * (16 * 544) + (bi_i >> 2) * 136;
            const uint4* zsrc = src + (lane >> 2) * (2 * 544) + 128 + (lane & 1) * 4 + qq;
            src += (lane >> 3) * (4 * 544) + ((lane >> 1) & 3) * 32 + (bi_i & 3) * 8 + w4 * 2 + (lane & 1);
            mbar_wait(bar + 8 * BAR_PUB, 0);
            if (warp == 12) STAMP(12);
            __nanosleep(D1_NS);
            uint4 v[6];
#pragma unroll
            for (int k = 0; k < 6; k++) v[k] = make_uint4(tag ^ 1u, 0, 0, 0);
            int n = 0;
#pragma unroll 1
            while (true) {
#pragma unroll
                for (int k = 0; k < 6; k++) if ((bad4(v[k], tag) & 1) && (k < 4 || zw)) v[k] = ld_rlx128(k < 4 ? src + k * 544 : zsrc + (k - 4) * 544);
                if (!__any_sync(~0u, (bad4(v[0], tag) | bad4(v[1], tag) | bad4(v[2], tag) | bad4(v[3], tag) | (zw ? bad4(v[4], tag) | bad4(v[5], tag) : 0u)) & 1)) break;
                if (warp == 12 && n < 3) STAMP(54 + n);
                if (++n > SPIN_LIMIT) break;
                __nanosleep(POLL_NS);
            }
            if (warp == 12) STAMP(30);
            float f[8];
            const float* vf = (const float*)v;
#pragma unroll
            for (int r = 0; r < 4; r++) {
                f[r] = (vf[r] + vf[4 + r]) + (vf[8 + r] + vf[12 + r]);
                f[4 + r] = vf[16 + r] + vf[20 + r];
                f[4 + r] += __shfl_xor_sync(~0u, f[4 + r], 4);
            }
#pragma unroll
            for (int o = 8; o <= 16; o <<= 1)
#pragma unroll
                for (int r = 0; r < 8; r++) f[r] += __shfl_xor_sync(~0u, f[r], o);
            if (lane < 8) st_rlx64(kvf_h + ((bi_i & 3) * 8 + w4 * 2 + (lane & 1)) * 4 + (lane >> 1), tagw(pack2(f[0], f[1]), tag), pack2(f[2], f[3]));
            if (zw && lane < 4) st_rlx64(kvf_h + (64 + qq) * 2 + (lane & 1), tagw(pack2(f[4], f[5]), tag), pack2(f[6], f[7]));
        }
        if (warp == 12) STAMP(13);
        {
            const uint4* kp = scr->kvf + bi_j * 272 + st;
            __nanosleep(D2_NS);
            uint4 v0 = make_uint4(tag ^ 1u, 0, 0, 0), v1 = v0, v2 = make_uint4(st < 16 ? tag ^ 1u : tag, 0, tag, 0);
            int n = 0;
#pragma unroll 1
            while (true) {
                if (bad4(v0, tag) & 1) v0 = ld_rlx128(kp);
                if (bad4(v1, tag) & 1) v1 = ld_rlx128(kp + 128);
                if (bad4(v2, tag) & 1) v2 = ld_rlx128(kp + 256);
                if (!__any_sync(~0u, (bad4(v0, tag) | bad4(v1, tag) | bad4(v2, tag)) & 1)) break;
                if (++n > SPIN_LIMIT) break;
                __nanosleep(POLL_NS);
            }
            sts128(sb + OFF_KVF + st * 16, v0.x, v0.y, v0.z, v0.w);
            sts128(sb + OFF_KVF + 2048 + st * 16, v1.x, v1.y, v1.z, v1.w);
            if (st < 16) sts128(sb + OFF_KVF + 4096 + st * 16, v2.x, v2.y, v2.z, v2.w);
            __syncwarp();
            if (lane == 0) mbar_arrive(bar + 8 * BAR_KVF);
        }
        if (warp == 13) {
            mbar_wait(bar + 8 * BAR_KVF, 0);
            if (lane == 0) {
                mbar_expect(bar + 8 * BAR_WO2, 65536);
                tma2d(sb + OFF_P, &mwo, (bi_j & 3) * 128 + 64, 256, bar + 8 * BAR_WO2);
                tma2d(sb + OFF_V, &mwo, (bi_j & 3) * 128, 256, bar + 8 * BAR_WO2);
            }
        }
        if (warp == 12) STAMP(25);
    }
    __syncwarp();
    if (lane == 0) {
        unsigned old;
        asm volatile("atom.acq_rel.cta.shared.add.u32 %0,[%1],1;" : "=r"(old) : "r"(bar + OFF_CNT) : "memory");
        if (old == 15) {
            atomicAdd(scr->done, 1u);
        }
    }
}

typedef CUresult (*EncFn)(CUtensorMap*, CUtensorMapDataType, cuuint32_t, void*, const cuuint64_t*, const cuuint64_t*, const cuuint32_t*,
                          const cuuint32_t*, CUtensorMapInterleave, CUtensorMapSwizzle, CUtensorMapL2promotion, CUtensorMapFloatOOBfill);

extern "C" void kernel_launch(void* const* d_in, const int* in_sizes, int n_in, void* d_out, int out_size) {
    static EncFn enc = nullptr;
    static Scratch* scr = nullptr;
    if (!enc) {
        cudaGetSymbolAddress((void**)&scr, g_scr);
        cudaDriverEntryPointQueryResult qr;
        cudaGetDriverEntryPoint("cuTensorMapEncodeTiled", (void**)&enc, cudaEnableDefault, &qr);
        cudaFuncSetAttribute(fused_kernel, cudaFuncAttributeMaxDynamicSharedMemorySize, SMEM_BYTES);
    }
    CUtensorMap mx, mw, mwo;
    const cuuint32_t es[3] = {1, 1, 1};
    {
        cuuint64_t d[2] = {512, 2048}, s[1] = {1024}; cuuint32_t b[2] = {64, 128};
        enc(&mx, CU_TENSOR_MAP_DATA_TYPE_BFLOAT16, 2, d_in[0], d, s, b, es, CU_TENSOR_MAP_INTERLEAVE_NONE, CU_TENSOR_MAP_SWIZZLE_128B,
            CU_TENSOR_MAP_L2_PROMOTION_L2_128B, CU_TENSOR_MAP_FLOAT_OOB_FILL_NONE);
    }
    {
        cuuint64_t d[3] = {512, 512, 3}, s[2] = {3072, 1024}; cuuint32_t b[3] = {64, 64, 3};
        enc(&mw, CU_TENSOR_MAP_DATA_TYPE_BFLOAT16, 3, d_in[1], d, s, b, es, CU_TENSOR_MAP_INTERLEAVE_NONE, CU_TENSOR_MAP_SWIZZLE_128B,
            CU_TENSOR_MAP_L2_PROMOTION_L2_128B, CU_TENSOR_MAP_FLOAT_OOB_FILL_NONE);
    }
    {
        cuuint64_t d[2] = {512, 512}, s[1] = {1024}; cuuint32_t b[2] = {64, 256};
        enc(&mwo, CU_TENSOR_MAP_DATA_TYPE_BFLOAT16, 2, d_in[3], d, s, b, es, CU_TENSOR_MAP_INTERLEAVE_NONE, CU_TENSOR_MAP_SWIZZLE_128B,
            CU_TENSOR_MAP_L2_PROMOTION_L2_128B, CU_TENSOR_MAP_FLOAT_OOB_FILL_NONE);
    }
    fused_kernel<<<128, 512, SMEM_BYTES, cudaStreamPerThread>>>(
        scr, (const bf16*)d_in[5], (const bf16*)d_in[6], (const bf16*)d_in[7], (const bf16*)d_in[8], (const bf16*)d_in[9],
        (const bf16*)d_in[10], (const bf16*)d_in[2], (const bf16*)d_in[11], (bf16*)d_out, mx, mw, mwo);
}
```

```cpp
#include <cuda_runtime.h>
#include <cuda.h>
#include <cuda_bf16.h>
#include <stdint.h>

typedef __nv_bfloat16 bf16;

struct Scratch {
    uint4 xt[128 * 1024];
    uint4 o[16 * 8 * 32 * 32];
    uint4 y[128 * 1024];
    uint4 kvp[8 * 16 * 544];
    uint4 kvf[8 * 4 * 68];
    unsigned g[1024 * 8];
    unsigned yflag[128 * 8];
    unsigned xcnt[8 * 32];
    unsigned done[32];
};
__device__ Scratch g_scr;
#ifdef TIMING
__device__ long long g_ts[128 * 64];
#define STAMP(n) do { if (lane == 0) sts32(sb + OFF_BAR + 256 + 4 * (n), (uint32_t)(clock64() - t_start)); } while (0)
#else
#define STAMP(n)
#endif

constexpr int SLOT = 40960;
constexpr int OFF_SP0 = 32768, OFF_SP1 = SLOT + 32768;
constexpr int OFF_P = 2 * SLOT, OFF_V = OFF_P + 32768;
constexpr int OFF_KVF = OFF_V + 32768;
constexpr int KT_BYTES = 3264, KW_D = 16, KW_2 = 560, KW_3 = 656;
constexpr int OFF_U = 4 * SLOT, U_STRIDE = 4096 + 256 + 32;
constexpr int OFF_BUF = OFF_U + 4 * U_STRIDE, BUF_STRIDE = 8320;
constexpr int OFF_K = OFF_BUF + 4 * BUF_STRIDE;
constexpr int OFF_WPHI = OFF_K + 4 * KT_BYTES;
constexpr int OFF_GW = OFF_WPHI + 2048;
constexpr int OFF_BAR = OFF_GW + 1024;
constexpr int SMEM_BYTES = OFF_BAR + 256 + 256;
static_assert(SMEM_BYTES <= 232448 && OFF_BUF % 128 == 0, "smem");
constexpr int W5_OFF = 0, W3_OFF = 3088, W9_OFF = 6176;
constexpr int BAR_FULL = 0, BAR_EMPTY = 4, BAR_WPHI = 8, BAR_WO = 9, BAR_WO2 = 10, BAR_XT = 11, BAR_DONE = 12, BAR_KG = 13, BAR_SP = 14,
              BAR_PUB = 15, BAR_KVF = 16, BAR_UR = 17, BAR_WR = 18, BAR_PREP = 19, BAR_KGA = 20, BAR_SP2 = 21, BAR_GO = 22, OFF_CNT = 192;
#ifndef CONV_START
#define CONV_START BAR_DONE
#endif
#ifndef D1_NS
#define D1_NS 0
#endif
#ifndef D2_NS
#define D2_NS 0
#endif
#ifndef D3_NS
#define D3_NS 100
#endif
#ifndef PS_NS
#define PS_NS 100
#endif
#ifndef POLL_NS
#define POLL_NS 0
#endif
constexpr int SPIN_LIMIT = 1 << 17;

__device__ __forceinline__ uint32_t s2u(const void* p) { return (uint32_t)__cvta_generic_to_shared(p); }
__device__ __forceinline__ void mbar_init(uint32_t b, int c) { asm volatile("mbarrier.init.shared::cta.b64 [%0],%1;" ::"r"(b), "r"(c) : "memory"); }
__device__ __forceinline__ void mbar_expect(uint32_t b, int bytes) { asm volatile("mbarrier.arrive.expect_tx.shared::cta.b64 _,[%0],%1;" ::"r"(b), "r"(bytes) : "memory"); }
__device__ __forceinline__ void mbar_arrive(uint32_t b) { asm volatile("mbarrier.arrive.shared::cta.b64 _,[%0];" ::"r"(b) : "memory"); }
__device__ __forceinline__ void mbar_wait(uint32_t b, int ph) {
    asm volatile("{\n.reg .pred p;\n.reg .u32 n;\nmov.u32 n,0;\nLW_%=:\nmbarrier.try_wait.parity.shared::cta.b64 p,[%0],%1;\n@p bra LD_%=;\n"
                 "add.u32 n,n,1;\nsetp.lt.u32 p,n,16384;\n@p bra LW_%=;\nLD_%=:\n}" ::"r"(b), "r"(ph) : "memory");
}
__device__ __forceinline__ void tma2d(uint32_t dst, const CUtensorMap* m, int c0, int c1, uint32_t bar) {
    asm volatile("cp.async.bulk.tensor.2d.shared::cluster.global.mbarrier::complete_tx::bytes [%0],[%1,{%3,%4}],[%2];" ::"r"(dst), "l"(m), "r"(bar), "r"(c0), "r"(c1) : "memory");
}
__device__ __forceinline__ void tma3d(uint32_t dst, const CUtensorMap* m, int c0, int c1, int c2, uint32_t bar) {
    asm volatile("cp.async.bulk.tensor.3d.shared::cluster.global.mbarrier::complete_tx::bytes [%0],[%1,{%3,%4,%5}],[%2];" ::"r"(dst), "l"(m), "r"(bar), "r"(c0), "r"(c1), "r"(c2) : "memory");
}
__device__ __forceinline__ void bulk_g2s(uint32_t dst, const void* src, int bytes, uint32_t bar) {
    asm volatile("cp.async.bulk.shared::cluster.global.mbarrier::complete_tx::bytes [%0],[%1],%2,[%3];" ::"r"(dst), "l"(src), "r"(bytes), "r"(bar) : "memory");
}
__device__ __forceinline__ uint64_t mkdesc(uint32_t addr, uint32_t lbo, uint32_t sbo) {
    return (uint64_t)((addr & 0x3FFFF) >> 4) | ((uint64_t)(lbo >> 4) << 16) | ((uint64_t)(sbo >> 4) << 32) | ((uint64_t)1 << 62);
}
__device__ __forceinline__ void wg_fence() { asm volatile("wgmma.fence.sync.aligned;" ::: "memory"); }
__device__ __forceinline__ void wg_commit() { asm volatile("wgmma.commit_group.sync.aligned;" ::: "memory"); }
template <int N> __device__ __forceinline__ void wg_wait() { asm volatile("wgmma.wait_group.sync.aligned %0;" ::"n"(N) : "memory"); }
template <int N> __device__ __forceinline__ void fence_regs(float* d) {
#pragma unroll
    for (int i = 0; i < N; i++) asm volatile("" : "+f"(d[i])::"memory");
}
#define R8(d, o) "+f"(d[o]), "+f"(d[o + 1]), "+f"(d[o + 2]), "+f"(d[o + 3]), "+f"(d[o + 4]), "+f"(d[o + 5]), "+f"(d[o + 6]), "+f"(d[o + 7])
__device__ __forceinline__ void wgmma192(float* d, uint64_t da, uint64_t db) {
    asm volatile("wgmma.mma_async.sync.aligned.m64n192k16.f32.bf16.bf16 {"
                 "%0,%1,%2,%3,%4,%5,%6,%7,%8,%9,%10,%11,%12,%13,%14,%15,%16,%17,%18,%19,%20,%21,%22,%23,%24,%25,%26,%27,%28,%29,%30,%31,"
                 "%32,%33,%34,%35,%36,%37,%38,%39,%40,%41,%42,%43,%44,%45,%46,%47,%48,%49,%50,%51,%52,%53,%54,%55,%56,%57,%58,%59,%60,%61,%62,%63,"
                 "%64,%65,%66,%67,%68,%69,%70,%71,%72,%73,%74,%75,%76,%77,%78,%79,%80,%81,%82,%83,%84,%85,%86,%87,%88,%89,%90,%91,%92,%93,%94,%95},"
                 "%96,%97,1,1,1,0,1;"
                 : R8(d, 0), R8(d, 8), R8(d, 16), R8(d, 24), R8(d, 32), R8(d, 40), R8(d, 48), R8(d, 56), R8(d, 64), R8(d, 72), R8(d, 80), R8(d, 88)
                 : "l"(da), "l"(db));
}
__device__ __forceinline__ void wgmma64_tt(float* d, uint64_t da, uint64_t db, int sc) {
    asm volatile("{.reg .pred p; setp.ne.b32 p,%34,0; wgmma.mma_async.sync.aligned.m64n64k16.f32.bf16.bf16 {"
                 "%0,%1,%2,%3,%4,%5,%6,%7,%8,%9,%10,%11,%12,%13,%14,%15,%16,%17,%18,%19,%20,%21,%22,%23,%24,%25,%26,%27,%28,%29,%30,%31},"
                 "%32,%33,p,1,1,1,1;}"
                 : R8(d, 0), R8(d, 8), R8(d, 16), R8(d, 24)
                 : "l"(da), "l"(db), "r"(sc));
}
__device__ __forceinline__ void wgmma128_rs(float* d, const uint4& a, uint64_t db, int sc) {
    asm volatile("{.reg .pred p; setp.ne.b32 p,%69,0; wgmma.mma_async.sync.aligned.m64n128k16.f32.bf16.bf16 {"
                 "%0,%1,%2,%3,%4,%5,%6,%7,%8,%9,%10,%11,%12,%13,%14,%15,%16,%17,%18,%19,%20,%21,%22,%23,%24,%25,%26,%27,%28,%29,%30,%31,"
                 "%32,%33,%34,%35,%36,%37,%38,%39,%40,%41,%42,%43,%44,%45,%46,%47,%48,%49,%50,%51,%52,%53,%54,%55,%56,%57,%58,%59,%60,%61,%62,%63},"
                 "{%64,%65,%66,%67},%68,p,1,1,1;}"
                 : R8(d, 0), R8(d, 8), R8(d, 16), R8(d, 24), R8(d, 32), R8(d, 40), R8(d, 48), R8(d, 56)
                 : "r"(a.x), "r"(a.y), "r"(a.z), "r"(a.w), "l"(db), "r"(sc));
}
__device__ __forceinline__ void mma16816(float* c, uint32_t a0, uint32_t a1, uint32_t a2, uint32_t a3, uint32_t b0, uint32_t b1) {
    asm("mma.sync.aligned.m16n8k16.row.col.f32.bf16.bf16.f32 {%0,%1,%2,%3},{%4,%5,%6,%7},{%8,%9},{%0,%1,%2,%3};"
        : "+f"(c[0]), "+f"(c[1]), "+f"(c[2]), "+f"(c[3]) : "r"(a0), "r"(a1), "r"(a2), "r"(a3), "r"(b0), "r"(b1));
}
__device__ __forceinline__ void ldsm4(uint32_t* r, uint32_t a) {
    asm volatile("ldmatrix.sync.aligned.m8n8.x4.shared.b16 {%0,%1,%2,%3},[%4];" : "=r"(r[0]), "=r"(r[1]), "=r"(r[2]), "=r"(r[3]) : "r"(a) : "memory");
}
__device__ __forceinline__ void ldsm4t(uint32_t* r, uint32_t a) {
    asm volatile("ldmatrix.sync.aligned.m8n8.x4.trans.shared.b16 {%0,%1,%2,%3},[%4];" : "=r"(r[0]), "=r"(r[1]), "=r"(r[2]), "=r"(r[3]) : "r"(a) : "memory");
}
__device__ __forceinline__ void stsm4(uint32_t a, uint32_t r0, uint32_t r1, uint32_t r2, uint32_t r3) {
    asm volatile("stmatrix.sync.aligned.m8n8.x4.shared.b16 [%0],{%1,%2,%3,%4};" ::"r"(a), "r"(r0), "r"(r1), "r"(r2), "r"(r3) : "memory");
}
__device__ __forceinline__ uint32_t lds32(uint32_t a) { uint32_t v; asm volatile("ld.shared.b32 %0,[%1];" : "=r"(v) : "r"(a) : "memory"); return v; }
__device__ __forceinline__ uint4 lds128(uint32_t a) { uint4 v; asm volatile("ld.shared.v4.b32 {%0,%1,%2,%3},[%4];" : "=r"(v.x), "=r"(v.y), "=r"(v.z), "=r"(v.w) : "r"(a) : "memory"); return v; }
__device__ __forceinline__ void sts16(uint32_t a, uint32_t v) { asm volatile("st.shared.b16 [%0],%1;" ::"r"(a), "h"((unsigned short)v) : "memory"); }
__device__ __forceinline__ void sts32(uint32_t a, uint32_t v) { asm volatile("st.shared.b32 [%0],%1;" ::"r"(a), "r"(v) : "memory"); }
__device__ __forceinline__ void sts64(uint32_t a, uint32_t x, uint32_t y) { asm volatile("st.shared.v2.b32 [%0],{%1,%2};" ::"r"(a), "r"(x), "r"(y) : "memory"); }
__device__ __forceinline__ void sts128(uint32_t a, uint32_t x, uint32_t y, uint32_t z, uint32_t w) { asm volatile("st.shared.v4.b32 [%0],{%1,%2,%3,%4};" ::"r"(a), "r"(x), "r"(y), "r"(z), "r"(w) : "memory"); }
__device__ __forceinline__ uint32_t pack2(float lo, float hi) { uint32_t d; asm("cvt.rn.bf16x2.f32 %0,%1,%2;" : "=r"(d) : "f"(hi), "f"(lo)); return d; }
__device__ __forceinline__ float bf_lo(uint32_t v) { return __uint_as_float(v << 16); }
__device__ __forceinline__ float bf_hi(uint32_t v) { return __uint_as_float(v & 0xffff0000u); }
__device__ __forceinline__ float bf_round(float v) { return bf_lo(pack2(v, 0.f)); }
__device__ __forceinline__ uint32_t hmax2(uint32_t a, uint32_t b) { uint32_t d; asm("max.bf16x2 %0,%1,%2;" : "=r"(d) : "r"(a), "r"(b)); return d; }
__device__ __forceinline__ uint32_t hmin2(uint32_t a, uint32_t b) { uint32_t d; asm("min.bf16x2 %0,%1,%2;" : "=r"(d) : "r"(a), "r"(b)); return d; }
__device__ __forceinline__ uint32_t hmul2(uint32_t a, uint32_t b) { uint32_t d; asm("mul.rn.bf16x2 %0,%1,%2;" : "=r"(d) : "r"(a), "r"(b)); return d; }
__device__ __forceinline__ float ex2(float x) { float y; asm("ex2.approx.ftz.f32 %0,%1;" : "=f"(y) : "f"(x)); return y; }
__device__ __forceinline__ float rcp(float x) { float y; asm("rcp.approx.ftz.f32 %0,%1;" : "=f"(y) : "f"(x)); return y; }
__device__ __forceinline__ uint32_t ld_nc(const uint32_t* p) { uint32_t v; asm volatile("ld.global.nc.b32 %0,[%1];" : "=r"(v) : "l"(p)); return v; }
__device__ __forceinline__ uint2 ld_nc64(const uint2* p) { uint2 v; asm volatile("ld.global.nc.v2.b32 {%0,%1},[%2];" : "=r"(v.x), "=r"(v.y) : "l"(p)); return v; }
__device__ __forceinline__ unsigned ld_acq(const unsigned* p) { unsigned v; asm volatile("ld.acquire.gpu.global.u32 %0,[%1];" : "=r"(v) : "l"(p) : "memory"); return v; }
__device__ __forceinline__ unsigned ld_rlx(const unsigned* p) { unsigned v; asm volatile("ld.relaxed.gpu.global.u32 %0,[%1];" : "=r"(v) : "l"(p) : "memory"); return v; }
__device__ __forceinline__ uint2 ld_rlx64(const void* p) { uint2 v; asm volatile("{.reg .b64 t; ld.relaxed.gpu.global.b64 t,[%2]; mov.b64 {%0,%1},t;}" : "=r"(v.x), "=r"(v.y) : "l"(p) : "memory"); return v; }
__device__ __forceinline__ uint4 ld_rlx128(const void* p) {
    uint4 v;
    asm volatile("{.reg .b64 t,u; ld.relaxed.gpu.global.v2.b64 {t,u},[%4]; mov.b64 {%0,%1},t; mov.b64 {%2,%3},u;}" : "=r"(v.x), "=r"(v.y), "=r"(v.z), "=r"(v.w) : "l"(p) : "memory");
    return v;
}
__device__ __forceinline__ void st_rlx32(void* p, uint32_t x) { asm volatile("st.relaxed.gpu.global.u32 [%0],%1;" ::"l"(p), "r"(x) : "memory"); }
__device__ __forceinline__ void st_rlx64(void* p, uint32_t x, uint32_t y) { asm volatile("{.reg .b64 t; mov.b64 t,{%1,%2}; st.relaxed.gpu.global.b64 [%0],t;}" ::"l"(p), "r"(x), "r"(y) : "memory"); }
__device__ __forceinline__ void st_rlx128(void* p, uint4 v) {
    asm volatile("{.reg .b64 t,u; mov.b64 t,{%1,%2}; mov.b64 u,{%3,%4}; st.relaxed.gpu.global.v2.b64 [%0],{t,u};}" ::"l"(p), "r"(v.x), "r"(v.y), "r"(v.z), "r"(v.w) : "memory");
}
__device__ __forceinline__ uint32_t tagw(uint32_t w, uint32_t tag) { return (w & ~1u) | tag; }
__device__ __forceinline__ uint4 tag4(uint32_t x, uint32_t y, uint32_t z, uint32_t w, uint32_t tag) { return make_uint4(tagw(x, tag), y, tagw(z, tag), w); }
__device__ __forceinline__ uint32_t bad4(const uint4& v, uint32_t tag) { return (v.x ^ tag) | (v.z ^ tag); }
__device__ __forceinline__ void bar_named(int id, int n) { asm volatile("bar.sync %0,%1;" ::"r"(id), "r"(n) : "memory"); }

struct cf { float re, im; };
__device__ __forceinline__ cf cmul(cf a, cf b) { cf r; r.re = a.re * b.re - a.im * b.im; r.im = a.re * b.im + a.im * b.re; return r; }
__device__ __forceinline__ cf cexp_p(float arl, float ait, float p) {
    float mag = ex2(arl * p);
    float t = ait * p;
    t = (t - rintf(t)) * 6.283185307179586f;
    cf r; r.re = mag * __cosf(t); r.im = mag * __sinf(t);
    return r;
}

__device__ __forceinline__ void hedgehog4(const uint32_t* a, uint32_t wphi_addr, uint32_t (*out)[8]) {
    float p[4][2][4], mx[4][2];
#pragma unroll
    for (int h = 0; h < 4; h++) {
        uint32_t b[4];
        ldsm4t(b, wphi_addr + h * 512);
        float c0[4] = {0.f, 0.f, 0.f, 0.f}, c1[4] = {0.f, 0.f, 0.f, 0.f};
        mma16816(c0, a[4 * h], a[4 * h + 1], a[4 * h + 2], a[4 * h + 3], b[0], b[1]);
        mma16816(c1, a[4 * h], a[4 * h + 1], a[4 * h + 2], a[4 * h + 3], b[2], b[3]);
#pragma unroll
        for (int k = 0; k < 2; k++) {
            p[h][k][0] = c0[2 * k]; p[h][k][1] = c0[2 * k + 1]; p[h][k][2] = c1[2 * k]; p[h][k][3] = c1[2 * k + 1];
            mx[h][k] = fmaxf(fmaxf(p[h][k][0], p[h][k][1]), fmaxf(p[h][k][2], p[h][k][3]));
        }
    }
#pragma unroll
    for (int o = 1; o <= 2; o <<= 1)
#pragma unroll
        for (int h = 0; h < 4; h++)
#pragma unroll
            for (int k = 0; k < 2; k++) mx[h][k] = fmaxf(mx[h][k], __shfl_xor_sync(~0u, mx[h][k], o));
    const float L = 1.4426950408889634f;
    float pmin = 1.f;
#pragma unroll
    for (int h = 0; h < 4; h++)
#pragma unroll
        for (int k = 0; k < 2; k++) {
            const float m = -mx[h][k] * L;
            const float e0 = ex2(fmaf(p[h][k][0], L, m)), e1 = ex2(fmaf(p[h][k][1], L, m)), e2 = ex2(fmaf(p[h][k][2], L, m)), e3 = ex2(fmaf(p[h][k][3], L, m));
            const float p01 = e0 * e1, p23 = e2 * e3, pp = p01 * p23, r = rcp(pp), r01 = r * p23, r23 = r * p01;
            pmin = fminf(pmin, pp);
            out[h][k] = pack2(e0, e1); out[h][k + 2] = pack2(e2, e3);
            out[h][4 + k] = pack2(r01 * e1, r01 * e0); out[h][4 + k + 2] = pack2(r23 * e3, r23 * e2);
        }
    if (__builtin_expect(__any_sync(~0u, !(pmin > 1e-18f)), 0)) {
#pragma unroll
        for (int h = 0; h < 4; h++)
#pragma unroll
            for (int k = 0; k < 2; k++) {
                float m = fminf(fminf(p[h][k][0], p[h][k][1]), fminf(p[h][k][2], p[h][k][3]));
                m = fminf(m, __shfl_xor_sync(~0u, m, 1));
                m = fminf(m, __shfl_xor_sync(~0u, m, 2)) * L;
                out[h][4 + k] = pack2(ex2(fmaf(p[h][k][0], -L, m)), ex2(fmaf(p[h][k][1], -L, m)));
                out[h][4 + k + 2] = pack2(ex2(fmaf(p[h][k][2], -L, m)), ex2(fmaf(p[h][k][3], -L, m)));
            }
    }
}

__global__ void __launch_bounds__(512, 1)
fused_kernel(Scratch* __restrict__ scr, const bf16* __restrict__ logA, const bf16* __restrict__ Aim, const bf16* __restrict__ Cre,
             const bf16* __restrict__ Cim, const bf16* __restrict__ logdt, const bf16* __restrict__ Dskip, const bf16* __restrict__ wphi,
             const bf16* __restrict__ gatew, bf16* __restrict__ out,
             const __grid_constant__ CUtensorMap mx, const __grid_constant__ CUtensorMap mw, const __grid_constant__ CUtensorMap mwo) {
    extern __shared__ __align__(1024) uint8_t smem[];
#ifdef TIMING
    long long t_start = clock64();
    long long gt0; asm volatile("mov.u64 %0,%%globaltimer;" : "=l"(gt0));
    if (threadIdx.x >= 448) ((uint32_t*)(smem + OFF_BAR + 256))[threadIdx.x - 448] = 0;
#endif
    constexpr uint32_t sb = 1024;
    const int tid = threadIdx.x, warp = __shfl_sync(~0u, tid >> 5, 0), lane = tid & 31;
    const int g = lane >> 2, q = lane & 3, w4 = warp & 3;
    const int bi = blockIdx.x, bi_i = bi & 15, bi_j = bi >> 4;
    const uint32_t bar = sb + OFF_BAR;
    const int rot = (bi_j & 3) * 2, xkb = bi_j >> 2;
    auto load_stage = [&](int kb) {
        const uint32_t b = bar + 8 * (BAR_FULL + (kb & 3)), d = sb + (kb & 3) * SLOT;
        const int kc = ((kb + rot) & 7) * 64;
        mbar_expect(b, SLOT);
        tma2d(d, &mx, kc, bi_i * 128, b);
        tma3d(d + 16384, &mw, bi_j * 64, kc, 0, b);
    };

    const int ch = bi * 4 + w4;
    const int pidx = ch * 64 + lane * 2 + (warp >> 3);
    const uint32_t pla = ld_nc((const uint32_t*)logA + pidx), pai = ld_nc((const uint32_t*)Aim + pidx);
    const uint32_t pcr = ld_nc((const uint32_t*)Cre + pidx), pci = ld_nc((const uint32_t*)Cim + pidx);
    uint32_t pdt = ld_nc((const uint32_t*)logdt + (ch >> 1));
    const uint32_t pds = ld_nc((const uint32_t*)Dskip + (ch >> 1));
    unsigned done0 = ld_rlx(scr->done);
    if (tid == 0) {
        for (int s = 0; s < 4; s++) mbar_init(bar + 8 * (BAR_FULL + s), 1);
        asm volatile("fence.mbarrier_init.release.cluster;" ::: "memory");
        asm volatile("prefetch.tensormap [%0];" ::"l"(&mx) : "memory");
#ifndef LATE_TMA
        load_stage(0); load_stage(1);
        STAMP(11);
#endif
    } else if (tid == 32) {
        if (s2u(smem) != sb) __trap();
        sts32(bar + OFF_CNT, 0);
        for (int s = 0; s < 4; s++) mbar_init(bar + 8 * (BAR_EMPTY + s), 9);
        mbar_init(bar + 8 * BAR_WPHI, 1); mbar_init(bar + 8 * BAR_WO, 2); mbar_init(bar + 8 * BAR_WO2, 1); mbar_init(bar + 8 * BAR_XT, 4);
        mbar_init(bar + 8 * BAR_DONE, 9); mbar_init(bar + 8 * BAR_KG, 8); mbar_init(bar + 8 * BAR_SP, 1); mbar_init(bar + 8 * BAR_PUB, 8);
        mbar_init(bar + 8 * BAR_KVF, 4); mbar_init(bar + 8 * BAR_UR, 4); mbar_init(bar + 8 * BAR_WR, 4); mbar_init(bar + 8 * BAR_PREP, 4); mbar_init(bar + 8 * BAR_KGA, 4); mbar_init(bar + 8 * BAR_SP2, 1); mbar_init(bar + 8 * BAR_GO, 8);
        asm volatile("fence.mbarrier_init.release.cluster;" ::: "memory");
        mbar_expect(bar + 8 * BAR_WPHI, 3072);
        bulk_g2s(sb + OFF_GW, gatew, 1024, bar + 8 * BAR_WPHI);
        bulk_g2s(sb + OFF_WPHI, wphi + bi_j * 1024, 2048, bar + 8 * BAR_WPHI);
    } else if (tid == 64) {
        asm volatile("prefetch.tensormap [%0];" ::"l"(&mw) : "memory");
    }
    const uint32_t buf = sb + OFF_BUF + w4 * BUF_STRIDE, kb_ = sb + OFF_K + w4 * KT_BYTES;
    if ((warp >> 2) == 2) {
#pragma unroll
        for (int v = 0; v < 7; v++) if (v * 32 + lane < KT_BYTES / 16) sts128(kb_ + (v * 32 + lane) * 16, 0, 0, 0, 0);
    }
    __syncthreads();
    asm volatile("" : "+r"(pdt), "+r"(done0)::"memory");
    const unsigned epoch1 = (done0 >> 7) + 1u;
    const uint32_t tag = epoch1 & 1u;
#ifdef LATE_TMA
    if (warp == LATE_TMA && (pla ^ pai ^ pcr ^ pci ^ pdt) != 0x9e3779b9u && lane == 0) { load_stage(0); load_stage(1); STAMP(11); }
    __syncwarp();
#endif

    const int st = tid & 127;
    const uint32_t ub = sb + OFF_U + w4 * U_STRIDE + 256, spare = sb + (w4 < 2 ? OFF_SP0 : OFF_SP1) + (w4 & 1) * 4096;

    auto stg_of = [&](int w) { return w < 8 ? sb + 3 * SLOT + w * 7296 : sb + 2 * SLOT + (w & 3) * 7296; };
    float kc[24];
#pragma unroll
    for (int t = 0; t < 24; t++) kc[t] = 0.f;
    {
        const float dt = bf_round(expf((ch & 1) ? bf_hi(pdt) : bf_lo(pdt)));
        const uint32_t stg = (warp >> 2) == 2 ? buf : stg_of(warp);
        const int sh = ((warp >> 2) & 1) * 16;
        auto pick = [&](uint32_t v) { return __uint_as_float((v >> sh) << 16); };
        const float ea = bf_round(ex2(pick(pla) * 1.4426950408889634f));
        const float arl = (-ea * dt) * 1.4426950408889634f, ait = (pick(pai) * dt) * 0.15915494309189535f;
        cf C2; C2.re = 2.0f * (pick(pcr) * dt); C2.im = 2.0f * (pick(pci) * dt);
        const cf z1 = cexp_p(arl, ait, 1.0f), z128 = cexp_p(arl, ait, 128.0f);
        cf z8 = cexp_p(arl, ait, 8.0f); z8.im = -z8.im;
        const uint32_t lp = stg + lane * 4;
        auto put = [&](int row, const cf& v) { sts32((lp ^ ((row & 7) << 4)) + row * 128, pack2(v.re, v.im)); };
        {
            const cf z16 = cmul(z8, z8);
            cf e; e.re = 1.f; e.im = 0.f;
            cf o = z8;
            put(0, e); put(1, o);
            e = z16; put(2, e);
#pragma unroll
            for (int b = 3; b < 16; b += 2) {
                o = cmul(o, z16); put(b, o);
                if (b + 1 < 16) { e = cmul(e, z16); put(b + 1, e); }
            }
        }
        cf h[8];
        h[0] = C2; put(16, h[0]);
        {
            const cf z2 = cmul(z1, z1);
            h[1] = cmul(h[0], z1);
#pragma unroll
            for (int r = 2; r < 8; r++) h[r] = cmul(h[r - 2], z2);
#pragma unroll
            for (int r = 1; r < 8; r++) put(16 + r, h[r]);
        }
#pragma unroll
        for (int r = 0; r < 8; r++) { h[r] = cmul(h[r], z128); put(24 + r, h[r]); }
#pragma unroll
        for (int al = 0; al < 2; al++)
#pragma unroll
            for (int r = 0; r < 4; r++) { h[2 * r] = cmul(h[2 * r], z128); put(32 + al * 4 + r, h[2 * r]); }
#pragma unroll
        for (int al = 0; al < 4; al++)
#pragma unroll
            for (int r = 0; r < 2; r++) { h[4 * r] = cmul(h[4 * r], z128); put(40 + al * 2 + r, h[4 * r]); }
#pragma unroll
        for (int al = 0; al < 9; al++) { h[0] = cmul(h[0], z128); put(48 + al, h[0]); }
        __syncwarp();
        const int lr = lane & 7, lm = lane >> 3;
#pragma unroll
        for (int kp = 0; kp < 2; kp++) {
            uint32_t a0[4], a1[4];
            ldsm4(a0, stg + ((lm & 1) * 8 + lr) * 128 + (((4 * kp + (lm >> 1)) ^ lr) << 4));
            ldsm4(a1, stg + ((lm & 1) * 8 + lr) * 128 + (((4 * kp + 2 + (lm >> 1)) ^ lr) << 4));
#pragma unroll
            for (int t = 0; t < 6; t++) {
                uint32_t b[4];
                ldsm4(b, stg + (16 + 8 * t + lr) * 128 + (((4 * kp + lm) ^ lr) << 4));
                mma16816(kc + 4 * t, a0[0], a0[1], a0[2], a0[3], b[0], b[1]);
                mma16816(kc + 4 * t, a1[0], a1[1], a1[2], a1[3], b[2], b[3]);
            }
        }
        __syncwarp();
        if ((warp >> 2) != 2) {
#pragma unroll
            for (int t = 0; t < 6; t++)
                sts128(stg + (t * 32 + lane) * 16, __float_as_uint(kc[4 * t]), __float_as_uint(kc[4 * t + 1]), __float_as_uint(kc[4 * t + 2]), __float_as_uint(kc[4 * t + 3]));
            asm volatile("fence.proxy.async.shared::cta;" ::: "memory");
            __syncwarp();
            if (lane == 0) mbar_arrive(bar + 8 * (warp < 8 ? BAR_KG : BAR_KGA));
        }
    }

    if (warp < 8) {
        asm volatile("setmaxnreg.inc.sync.aligned.u32 160;");
        const int wg = warp >> 2;
        if (warp == 0) STAMP(21);
        float acc[96];
        const int srow = warp * 16 + (lane & 15);
        const uint32_t srow_a = srow * 128;
        const int sx = srow & 7, shi = lane >> 4;
#pragma unroll
        for (int r = 0; r < 96; r++) acc[r] = 0.f;
        fence_regs<96>(acc);
        const uint64_t da0 = mkdesc(sb + wg * 8192, 16, 1024), db0 = mkdesc(sb + 16384, 8192, 1024);
#pragma unroll 1
        for (int kb = 0; kb < 8; kb++) {
            const int s = kb & 3;
            const uint64_t da = da0 + s * (SLOT >> 4), db = db0 + s * (SLOT >> 4);
            if (warp == 0) STAMP(40 + kb);
            mbar_wait(bar + 8 * (BAR_FULL + s), kb >> 2);
            if (warp == 0) STAMP(32 + kb);
            wg_fence();
#pragma unroll
            for (int k = 0; k < 4; k++) wgmma192(acc, da + 2 * k, db + 128 * k);
            wg_commit();
            wg_wait<1>();
            if (lane == 0 && kb > 0) mbar_arrive(bar + 8 * (BAR_EMPTY + ((kb - 1) & 3)));
        }
        mbar_wait(bar + 8 * BAR_WPHI, 0);
        wg_wait<0>();
        fence_regs<96>(acc);
        if (lane == 0) mbar_arrive(bar + 8 * BAR_DONE);
        if (warp == 0) STAMP(1);
        uint32_t in[16], qa[16];
        mbar_wait(bar + 8 * BAR_DONE, 0);
#pragma unroll
        for (int r = 0; r < 16; r++) {
            in[r] = pack2(acc[32 + 2 * r], acc[32 + 2 * r + 1]);
            qa[r] = pack2(acc[2 * r], acc[2 * r + 1]);
        }
#pragma unroll
        for (int hh = 0; hh < 4; hh++)
            stsm4(sb + OFF_V + (hh >> 1) * 16384 + srow_a + (((2 * (hh & 1) + shi) ^ sx) << 4), pack2(acc[64 + 8 * hh], acc[65 + 8 * hh]),
                  pack2(acc[66 + 8 * hh], acc[67 + 8 * hh]), pack2(acc[68 + 8 * hh], acc[69 + 8 * hh]), pack2(acc[70 + 8 * hh], acc[71 + 8 * hh]));
        sts128(sb + OFF_V + shi * 16384 + srow_a + ((4 ^ sx) << 4), 0x3f803f80u, 0x3f803f80u, 0x3f803f80u, 0x3f803f80u);
        const uint32_t wphi_a = sb + OFF_WPHI + (lane & 15) * 32 + (lane >> 4) * 16;
        uint32_t pq[4][8];
#pragma unroll 1
        for (int it = 0; it < 2; it++) {
            hedgehog4(in, wphi_a, pq);
            if (it == 1) break;
#ifdef GO_EARLY
            if (lane == 0) mbar_arrive(bar + 8 * BAR_GO);
#endif
#pragma unroll
            for (int hs = 0; hs < 8; hs++) {
                float c[4] = {0.f, 0.f, 0.f, 0.f};
                const uint32_t* o = pq[hs >> 1] + 4 * (hs & 1);
                mma16816(c, o[0], o[1], o[2], o[3], 0x3f803f80u, 0x3f803f80u);
                const float r0 = rcp(c[0]), r1 = rcp(c[2]);
                const uint32_t s0 = pack2(r0, r0), s1 = pack2(r1, r1);
                stsm4(sb + OFF_P + (hs >> 2) * 16384 + srow_a + (((2 * (hs & 3) + shi) ^ sx) << 4), hmul2(o[0], s0), hmul2(o[1], s1), hmul2(o[2], s0), hmul2(o[3], s1));
            }
            asm volatile("fence.proxy.async.shared::cta;" ::: "memory");
#ifndef GO_EARLY
            if (lane == 0) mbar_arrive(bar + 8 * BAR_GO);
#endif
            bar_named(1, 256);
            if (warp == 0) STAMP(2);
            float d[32];
            const uint64_t dv = mkdesc(sb + OFF_V + wg * 16384, 16, 1024), dp = mkdesc(sb + OFF_P + wg * 16384, 16, 1024);
            wg_fence();
#pragma unroll
            for (int k = 0; k < 8; k++) wgmma64_tt(d, dv + 128 * k, dp + 128 * k, k != 0);
            wg_commit();
            mbar_wait(bar + 8 * BAR_PREP, 0);
            uint4* kvp = scr->kvp + bi * 544 + wg * 272 + (w4 < 2 ? w4 * 136 : 128) + lane;
            wg_wait<0>();
            fence_regs<32>(d);
            if (w4 < 2 || (w4 == 2 && lane < 4)) {
#pragma unroll
                for (int f = 0; f < 4; f++) {
                    const int i0 = 8 * (f >> 1) + 2 * (f & 1), i2 = 16 * (f >> 1) + 8 * (f & 1);
                    const float e0 = w4 == 0 ? d[i0] : (w4 == 1 ? d[16 + i0] : d[i2]), e1 = w4 == 0 ? d[i0 + 1] : (w4 == 1 ? d[17 + i0] : d[i2 + 1]);
                    const float e2 = w4 == 0 ? d[i0 + 4] : (w4 == 1 ? d[20 + i0] : d[i2 + 4]), e3 = w4 == 0 ? d[i0 + 5] : (w4 == 1 ? d[21 + i0] : d[i2 + 5]);
                    st_rlx128(kvp + (w4 < 2 ? f * 32 : (f >> 1) * 136 + (f & 1) * 4), tag4(__float_as_uint(e0), __float_as_uint(e1), __float_as_uint(e2), __float_as_uint(e3), tag));
                }
            }
            __syncwarp();
            if (lane == 0) mbar_arrive(bar + 8 * BAR_PUB);
            if (warp == 0) STAMP(3);
#pragma unroll
            for (int r = 0; r < 16; r++) in[r] = qa[r];
        }
        if (warp == 0) STAMP(4);
        {
            mbar_wait(bar + 8 * BAR_KVF, 0);
            uint4 kf[4][3];
#pragma unroll
            for (int hh = 0; hh < 4; hh++) {
                const uint32_t a = sb + OFF_KVF + hh * 1088;
                kf[hh][0] = lds128(a + lane * 32); kf[hh][1] = lds128(a + lane * 32 + 16); kf[hh][2] = lds128(a + 1024 + q * 16);
            }
            if (warp == 0) STAMP(5);
            uint4* og = scr->o + ((bi_i * 8 + warp) * 32 + bi_j * 4) * 32 + lane;
#pragma unroll
            for (int hh = 0; hh < 4; hh++) {
                float c[6][4];
#pragma unroll
                for (int t = 0; t < 6; t++) { c[t][0] = c[t][1] = c[t][2] = c[t][3] = 0.f; }
                const uint32_t* a = pq[hh];
                const bool od = g & 1;
                mma16816(c[0], a[0], a[1], a[2], a[3], od ? 0x3f803f80u : kf[hh][2].x, od ? 0x3f803f80u : kf[hh][2].y);
                mma16816(c[1], a[4], a[5], a[6], a[7], od ? 0x3f803f80u : kf[hh][2].z, od ? 0x3f803f80u : kf[hh][2].w);
                mma16816(c[2], a[0], a[1], a[2], a[3], kf[hh][0].x, kf[hh][0].y);
                mma16816(c[3], a[0], a[1], a[2], a[3], kf[hh][0].z, kf[hh][0].w);
                mma16816(c[4], a[4], a[5], a[6], a[7], kf[hh][1].x, kf[hh][1].y);
                mma16816(c[5], a[4], a[5], a[6], a[7], kf[hh][1].z, kf[hh][1].w);
                uint32_t w[4];
#pragma unroll
                for (int k = 0; k < 2; k++) {
                    const float rho = c[0][2 * k + 1] * rcp(c[1][2 * k + 1]);
                    const float r = rcp(fmaf(c[0][2 * k + 1], 1e-6f, fmaf(rho, c[1][2 * k], c[0][2 * k]))), rr = r * rho;
                    w[k] = pack2(fmaf(c[4][2 * k], rr, c[2][2 * k] * r), fmaf(c[4][2 * k + 1], rr, c[2][2 * k + 1] * r));
                    w[2 + k] = pack2(fmaf(c[5][2 * k], rr, c[3][2 * k] * r), fmaf(c[5][2 * k + 1], rr, c[3][2 * k + 1] * r));
                }
                st_rlx128(og + hh * 32, tag4(w[0], w[1], w[2], w[3], tag));
            }
        }
        if (warp == 0) STAMP(6);
        float oc[64];
        const int slab = bi_i * 8 + (bi_j >> 2) * 4 + w4;
        const uint8_t* ysrc = (const uint8_t*)scr->y + (size_t)((bi_j & 3) * 32 + wg * 16 + (q >> 1)) * 16384 + slab * 128 + g * 16 + (q & 1) * 8;
        const unsigned* gp = scr->g + (slab * 8 + (g >> 1)) * 8 + (g & 1) * 4;
        uint2 yv[8]; unsigned g0, g1;
        {
            const uint4* osrc = scr->o + (slab * 32 + wg * 16) * 32 + lane;
            uint4 fr[16];
            const unsigned* probe = (const unsigned*)(osrc - lane + ((lane & 3) * 4 + 3) * 32 + 31) + 2;
            {
                unsigned miss = ~0u;
                int n = 0;
#pragma unroll
                for (int s = 0; s < 4; s++) {
#pragma unroll 1
                    while ((miss >> s) & 1) { miss = __ballot_sync(~0u, (ld_rlx(probe) ^ tag) & 1); if (++n > SPIN_LIMIT) break; }
#pragma unroll
                    for (int k = 4 * s; k < 4 * s + 4; k++) fr[k] = ld_rlx128(osrc + k * 32);
                }
#ifdef TIMING
                if (tid == 0) sts32(sb + OFF_BAR + 256 + 4 * 57, n);
#endif
            }
            if (warp == 0) STAMP(14);
            mbar_wait(bar + 8 * (wg ? BAR_WO2 : BAR_WO), 0);
            const uint64_t dw = mkdesc(sb + wg * 2 * SLOT, wg ? 32768 : SLOT, 1024);
#pragma unroll
            for (int s = 0; s < 4; s++) {
                int n = 0;
#pragma unroll 1
                while (__builtin_expect(__any_sync(~0u, (bad4(fr[4 * s], tag) | bad4(fr[4 * s + 1], tag) | bad4(fr[4 * s + 2], tag) | bad4(fr[4 * s + 3], tag)) & 1), 0)) {
#pragma unroll
                    for (int k = 4 * s; k < 4 * s + 4; k++) fr[k] = ld_rlx128(osrc + k * 32);
                    if (++n > SPIN_LIMIT) break;
                }
                wg_fence();
#pragma unroll
                for (int hh = 0; hh < 4; hh++) wgmma128_rs(oc, fr[4 * s + hh], dw + 128 * (4 * s + hh), (s | hh) != 0);
                wg_commit();
                if (s == 1) {
                    wg_wait<1>();
#pragma unroll
                    for (int nt = 0; nt < 8; nt++) yv[nt] = ld_rlx64(ysrc + nt * 32768);
                    g0 = ld_rlx(gp); g1 = ld_rlx(gp + 32);
                }
            }
            if (warp == 0) STAMP(7);
            {
                const unsigned* yprobe = scr->yflag + ((bi_j & 3) * 32 + wg * 16 + (lane & 15)) * 8;
                int n = 0;
#pragma unroll 1
                while (true) {
                    uint32_t bad = (g0 ^ tag) | (g1 ^ tag);
#pragma unroll
                    for (int nt = 0; nt < 8; nt++) bad |= yv[nt].x ^ tag;
                    if (!__any_sync(~0u, bad & 1)) break;
#pragma unroll 1
                    while (__any_sync(~0u, (ld_rlx(yprobe) ^ tag) & 1)) { if (++n > SPIN_LIMIT) break; }
#pragma unroll
                    for (int nt = 0; nt < 8; nt++) yv[nt] = ld_rlx64(ysrc + nt * 32768);
                    g0 = ld_rlx(gp); g1 = ld_rlx(gp + 32);
                    if (++n > SPIN_LIMIT) break;
                }
            }
            if (warp == 0) STAMP(28);
        }
        {
            const float ga = bf_hi(g0), gb = bf_hi(g1);
            const float ha = bf_round(1.0f - ga), hb = bf_round(1.0f - gb);
            float yb[32];
#pragma unroll
            for (int nt = 0; nt < 8; nt++) {
                yb[4 * nt] = ha * bf_lo(yv[nt].x); yb[4 * nt + 1] = ha * bf_hi(yv[nt].x);
                yb[4 * nt + 2] = hb * bf_lo(yv[nt].y); yb[4 * nt + 3] = hb * bf_hi(yv[nt].y);
            }
            fence_regs<32>(yb);
            const uint32_t xw = sb + wg * 2 * SLOT + (tid & 127) * 16, xr = sb + (wg ^ 1) * 2 * SLOT + (tid & 127) * 16;
            wg_wait<0>();
            fence_regs<64>(oc);
            bar_named(3 + wg, 128);
#pragma unroll
            for (int r = 0; r < 8; r++)
                sts128(xw + r * 2048, __float_as_uint(oc[32 + 4 * r]), __float_as_uint(oc[33 + 4 * r]), __float_as_uint(oc[34 + 4 * r]), __float_as_uint(oc[35 + 4 * r]));
#pragma unroll
            for (int r = 0; r < 32; r++) yb[r] = fmaf((r & 2) ? gb : ga, oc[r], yb[r]);
            bar_named(1, 256);
            if (warp == 0) STAMP(8);
            uint32_t w[8][2];
#pragma unroll
            for (int nt = 0; nt < 8; nt++) {
                const uint4 p = lds128(xr + nt * 2048);
                w[nt][0] = pack2(fmaf(ga, __uint_as_float(p.x), yb[4 * nt]), fmaf(ga, __uint_as_float(p.y), yb[4 * nt + 1]));
                w[nt][1] = pack2(fmaf(gb, __uint_as_float(p.z), yb[4 * nt + 2]), fmaf(gb, __uint_as_float(p.w), yb[4 * nt + 3]));
            }
            const uint32_t ob = sb + wg * 2 * SLOT + 16384 + w4 * 2048;
#pragma unroll
            for (int nt = 0; nt < 8; nt += 2)
                stsm4(ob + (lane & 15) * 128 + (((nt + shi) ^ (lane & 7)) << 4), w[nt][0], w[nt][1], w[nt + 1][0], w[nt + 1][1]);
            __syncwarp();
            bf16* op = out + (size_t)(slab * 16) * 512 + (bi_j & 3) * 128 + wg * 64 + (lane & 7) * 8;
#pragma unroll
            for (int it = 0; it < 4; it++) {
                const int r = it * 4 + (lane >> 3);
                uint4 v = lds128(ob + r * 128 + (((lane & 7) ^ (r & 7)) << 4));
                *(uint4*)(op + r * 512) = v;
            }
        }
        if (warp == 0) STAMP(10);
    } else if (warp < 12) {
#pragma unroll
        for (int src = 2; src >= 0; src--) {
            if (src != 0) mbar_wait(bar + 8 * (src == 2 ? BAR_KGA : BAR_KG), 0);
#pragma unroll
            for (int t = 0; t < 6; t++) {
                const uint4 v = lds128(stg_of(w4 + src * 4) + (t * 32 + lane) * 16);
                kc[4 * t] += __uint_as_float(v.x); kc[4 * t + 1] += __uint_as_float(v.y); kc[4 * t + 2] += __uint_as_float(v.z); kc[4 * t + 3] += __uint_as_float(v.w);
            }
            if (src != 1) {
                bar_named(2, 128);
                if (st == 0) { load_stage(src == 2 ? 2 : 3); if (src == 0) mbar_arrive(bar + 8 * BAR_SP); }
                if (warp == 8) STAMP(src == 2 ? 22 : 17);
            }
        }
        if (warp == 8) {
#pragma unroll 1
            for (int kb = 0; kb < 6; kb++) {
                const int s = kb & 3;
                mbar_wait(bar + 8 * (BAR_EMPTY + s), kb >> 2);
                if (kb == xkb) mbar_wait(bar + 8 * BAR_XT, 0);
                if (lane == 0) {
                    STAMP(48 + kb);
                    if (kb < 4) load_stage(kb + 4);
                    else {
                        mbar_expect(bar + 8 * BAR_WO, 32768);
                        tma2d(sb + s * SLOT, &mwo, (bi_j & 3) * 128 + s * 64, 0, bar + 8 * BAR_WO);
                        if (kb == 5) mbar_arrive(bar + 8 * BAR_SP2);
                    }
                }
                __syncwarp();
            }
        } else if (warp == 9) {
            const int row = bi_j * 16 + (lane >> 1), half = lane & 1;
            unsigned* gp = scr->g + (bi_i * 64 + bi_j * 8) * 8 + lane * 2;
            st_rlx64(gp, tag ^ 1u, tag ^ 1u);
            if (lane < 8) st_rlx32(scr->yflag + bi * 8 + lane, tag ^ 1u);
            float gs0 = 0.f, gs1 = 0.f;
            mbar_wait(bar + 8 * BAR_WPHI, 0);
#pragma unroll 1
            for (int kb = 0; kb < 8; kb++) {
                const int s = kb & 3;
                mbar_wait(bar + 8 * (BAR_FULL + s), kb >> 2);
#pragma unroll
                for (int c = 0; c < 4; c++) {
                    const uint4 xv = lds128(sb + s * SLOT + row * 128 + (((half * 4 + c) ^ (row & 7)) << 4));
                    const uint4 gw = lds128(sb + OFF_GW + ((kb + rot) & 7) * 128 + half * 64 + c * 16);
                    const uint32_t p0 = hmul2(xv.x, gw.x), p1 = hmul2(xv.y, gw.y), p2 = hmul2(xv.z, gw.z), p3 = hmul2(xv.w, gw.w);
                    gs0 += (bf_lo(p0) + bf_lo(p1)) + (bf_lo(p2) + bf_lo(p3));
                    gs1 += (bf_hi(p0) + bf_hi(p1)) + (bf_hi(p2) + bf_hi(p3));
                }
                asm volatile("" : "+f"(gs0), "+f"(gs1));
                __syncwarp();
                if (lane == 0) mbar_arrive(bar + 8 * (kb < 7 ? BAR_EMPTY + s : BAR_DONE));
            }
            float gs = gs0 + gs1;
            gs += __shfl_xor_sync(~0u, gs, 1);
            const uint32_t gv = __float_as_uint(bf_round(rcp(1.0f + ex2(-1.4426950408889634f * bf_round(gs))))) | tag;
            st_rlx64(gp, gv, gv);
        }
        if (lane == 0) kc[4 * 0 + 0] += ((ch & 1) ? bf_hi(pds) : bf_lo(pds));
#pragma unroll
        for (int i = 0; i < 2; i++) {
            const int be = g + 8 * i;
#pragma unroll
            for (int t = 0; t < 2; t++) {
                const uint32_t a = kb_ + (KW_D + 128 * t + 8 * be + 2 * q) * 4;
                const uint32_t w = pack2(kc[4 * t + 2 * i + 1], kc[4 * t + 2 * i]);
                sts32(a + 4, w); sts16(a, w >> 16); sts16(a + 10, w);
            }
            {
                const int p = 256 + 128 * (q >> 1) + 8 * be + 4 * (q & 1);
                const uint32_t a = kb_ + (KW_D + p) * 4;
                const uint32_t w = pack2(kc[4 * 2 + 2 * i + 1], kc[4 * 2 + 2 * i]);
                const uint32_t aa = (w >> 16) | (w & 0xffff0000u);
                if (p != 256) { sts16(a - 4, aa); sts32(a, aa); } else sts16(a, aa);
                sts32(a + 4, aa); sts32(a + 8, w); sts16(a + 14, w);
            }
            {
                const int k = 64 + 16 * q + be;
                const uint32_t w = pack2(kc[4 * 3 + 2 * i], kc[4 * 3 + 2 * i + 1]);
                if (k != 64) sts16(kb_ + (KW_2 + ((k - 1) >> 1) - 24) * 4 + (k & 1) * 2, w);
                else {
                    const uint32_t a = kb_ + (KW_D + 511) * 4, aa = (w << 16) | (w & 0xffffu);
                    sts16(a, w); sts32(a + 4, aa); sts32(a + 8, aa); sts32(a + 12, aa); sts16(a + 18, w);
                }
                sts16(kb_ + (KW_2 + 48 + (k >> 1) - 24) * 4 + ((k & 1) ^ 1) * 2, w >> 16);
            }
#pragma unroll
            for (int b = 0; b < 2; b++) {
                const int k = 64 + 8 * (2 * q + b) + (be >> 1);
                const uint32_t w = pack2(kc[4 * 4 + 2 * i + b], 0.f);
                if (!(be & 1) && k == 64) sts16(kb_ + (KW_2 + 63 - 24) * 4, w);
                else {
        float y[16][4];
#pragma unroll
        for (int nt = 0; nt < 16; nt++) { y[nt][0] = y[nt][1] = y[nt][2] = y[nt][3] = 0.f; }
        {
            uint32_t Bp[32], A[5][3];
            auto uaddr = [&](int rho) { const int R0 = (lane >> 4) * 8 + (lane & 7) - rho; return ub + (((2 * R0 + ((lane >> 3) & 1)) ^ ((R0 >> 2) & 1)) << 4); };
            const uint32_t kd = kb_ + (KW_D + g - 2 * q) * 4;
            auto lda = [&](int rho) {
#pragma unroll
                for (int ga = 0; ga < 5; ga++) {
                    const uint32_t a = kd + (ga < 4 ? rho : (rho & 1)) * 64 + ga * 512;
                    A[ga][0] = lds32(a); A[ga][1] = lds32(a + 32); A[ga][2] = lds32(a - 32);
                }
            };
            {
                const uint32_t a = uaddr(0);
#pragma unroll
                for (int p = 0; p < 8; p++) ldsm4(Bp + 4 * p, a + p * 512);
            }
#pragma unroll 1
            for (int rho = 0; rho < 8; rho++) {
                lda(rho);
                if (rho < 2) {
#pragma unroll
                    for (int nt = 4; nt < 16; nt++) mma16816(y[nt], A[4][0], A[4][1], A[4][2], A[4][0], Bp[2 * (nt - 4)], Bp[2 * (nt - 4) + 1]);
                }
#pragma unroll
                for (int ga = 0; ga < 3; ga++)
#pragma unroll
                    for (int nt = 15; nt >= ga; nt--) mma16816(y[nt], A[ga][0], A[ga][1], A[ga][2], A[ga][0], Bp[2 * (nt - ga)], Bp[2 * (nt - ga) + 1]);
                const uint32_t an = uaddr(rho + 1);
                ldsm4(Bp + 28, an + 7 * 512);
#pragma unroll
                for (int nt = 15; nt >= 3; nt--) {
                    mma16816(y[nt], A[3][0], A[3][1], A[3][2], A[3][0], Bp[2 * (nt - 3)], Bp[2 * (nt - 3) + 1]);
                    if (nt & 1) ldsm4(Bp + 2 * (nt - 3), an + ((nt - 3) >> 1) * 512);
                }
            }
        }
        if (warp == 8) STAMP(18);
        mbar_wait(bar + 8 * BAR_WR, 0);
#pragma unroll 1
        for (int ph = 0; ph < 2; ph++) {
            uint32_t B[5][2];
            const uint32_t ka = kb_ + (KW_2 + ph * 48 + 8 + g - q) * 4;
#pragma unroll
            for (int dd = 0; dd < 5; dd++) { B[dd][0] = lds32(ka + dd * 32); B[dd][1] = lds32(ka + dd * 32 - 16); }
            const uint32_t wa = buf + ph * W3_OFF + ((lane & 7) + ((lane >> 3) & 1) + (lane >> 4) * 8) * 16;
#pragma unroll
            for (int s = 0; s < 12; s++) {
                uint32_t A[4];
                ldsm4t(A, wa + s * 256);
#pragma unroll
                for (int dd = 0; dd < 5; dd++)
                    if (s + 4 + dd < 16) mma16816(y[s + 4 + dd], A[0], A[1], A[2], A[3], B[dd][0], B[dd][1]);
            }
        }
        {
            const int ap = (lane & 7) + (lane >> 4) * 8;
            const uint32_t loff = ((2 * ap + ((lane >> 3) & 1)) ^ ((ap >> 2) & 1)) << 4;
#pragma unroll 1
            for (int ph = 0; ph < 2; ph++) {
                uint32_t B[8][2];
                const uint32_t wb = (ph ? spare : buf + W9_OFF) + loff;
                const uint32_t ka = kb_ + (KW_3 + ph * 80 + 16 + g - 2 * q) * 4;
#pragma unroll
                for (int dd = 0; dd < 8; dd++) { B[dd][0] = lds32(ka + dd * 32); B[dd][1] = lds32(ka + dd * 32 - 32); }
#pragma unroll
                for (int s = 0; s < 4; s++) {
                    uint32_t A[4];
                    ldsm4t(A, wb + s * 512);
#pragma unroll
                    for (int dd = 0; dd < 8; dd++)
                        if (8 + 2 * s + dd < 16) mma16816(y[8 + 2 * s + dd], A[0], A[1], A[2], A[3], B[dd][0], B[dd][1]);
                }
            }
            const uint32_t k1024 = lds32(kb_ + (KW_2 + 63 - 24) * 4) & 0xffffu;
            const uint32_t idw = (g == 2 * q) ? k1024 : ((g == 2 * q + 1) ? (k1024 << 16) : 0u);
#pragma unroll
            for (int s = 0; s < 4; s++) {
                uint32_t A[4];
                ldsm4t(A, spare + 2048 + loff + s * 512);
                mma16816(y[8 + 2 * s], A[0], A[1], A[2], A[3], idw, 0u);
                mma16816(y[9 + 2 * s], A[0], A[1], A[2], A[3], 0u, idw);
            }
        }
        __syncwarp();
        if (warp == 8) STAMP(19);
#pragma unroll
        for (int nt = 0; nt < 16; nt++)
#pragma unroll
            for (int b = 0; b < 2; b++) sts32(buf + ((8 * nt + 2 * q + b) * 8 + g) * 4, pack2(y[nt][b], y[nt][2 + b]));
        bar_named(2, 128);
        uint4* yp = scr->y + bi * 1024 + st;
#pragma unroll
        for (int v = 0; v < 8; v++) {
            const uint32_t a = sb + OFF_BUF + (st + 128 * v) * 4;
            const uint32_t w0 = lds32(a), w1 = lds32(a + BUF_STRIDE), w2 = lds32(a + 2 * BUF_STRIDE), w3 = lds32(a + 3 * BUF_STRIDE);
            st_rlx128(yp + v * 128, tag4(__byte_perm(w0, w1, 0x5410), __byte_perm(w0, w1, 0x7632), __byte_perm(w2, w3, 0x5410), __byte_perm(w2, w3, 0x7632), tag));
        }
        if (st < 8) st_rlx32(scr->yflag + bi * 8 + st, tag);
        if (warp == 8) STAMP(20);
1]);
                }
            }
            const uint32_t k1024 = lds32(kb_ + (KW_2 + 63 - 24) * 4) & 0xffffu;
            const uint32_t idw = (g == 2 * q) ? k1024 : ((g == 2 * q + 1) ? (k1024 << 16) : 0u);
#pragma unroll
            for (int s = 0; s < 4; s++) {
                uint32_t A[4];
                ldsm4t(A, spare + 2048 + loff + s * 512);
                mma16816(y[8 + 2 * s], A[0], A[1], A[2], A[3], idw, 0u);
                mma16816(y[9 + 2 * s], A[0], A[1], A[2], A[3], 0u, idw);
            }
        }
        __syncwarp();
        if (warp == 8) STAMP(19);
#pragma unroll
        for (int nt = 0; nt < 16; nt++)
#pragma unroll
            for (int b = 0; b < 2; b++) sts32(buf + ((8 * nt + 2 * q + b) * 8 + g) * 4, pack2(y[nt][b], y[nt][2 + b]));
        bar_named(2, 128);
        const uint32_t tag2 = lds32(bar + OFF_TAG);
        uint4* yp = scr->y + bi * 1024 + st;
#pragma unroll
        for (int v = 0; v < 8; v++) {
            const uint32_t a = sb + OFF_BUF + (st + 128 * v) * 4;
            const uint32_t w0 = lds32(a), w1 = lds32(a + BUF_STRIDE), w2 = lds32(a + 2 * BUF_STRIDE), w3 = lds32(a + 3 * BUF_STRIDE);
            st_rlx128(yp + v * 128, tag4(__byte_perm(w0, w1, 0x5410), __byte_perm(w0, w1, 0x7632), __byte_perm(w2, w3, 0x5410), __byte_perm(w2, w3, 0x7632), tag2));
        }
        if (st < 8) st_rlx32(scr->yflag + bi * 8 + st, tag2);
        if (warp == 8) STAMP(20);
        }
#endif
    } else {
        asm volatile("setmaxnreg.dec.sync.aligned.u32 64;");
        const int qq = (bi_i & 2) + ((lane >> 1) & 1);
        uint2* kvf_h = (uint2*)(scr->kvf + (bi_j * 4 + (bi_i >> 2)) * 68);
        auto windows = [&](int rhi, int rlo) {
#pragma unroll 1
            for (int rho = rhi; rho >= rlo; rho--) {
                const int ci = lane + 32 * rho;
                uint4 e4[4];
#pragma unroll
                for (int v = 0; v < 4; v++) { const int cc = ci - 3 + v; e4[v] = lds128(ub + ((cc ^ ((cc >> 3) & 1)) << 4)); }
                float S[29];
                const uint32_t* ew = (const uint32_t*)e4;
                S[3] = 0.f;
#pragma unroll
                for (int k = 4; k <= 28; k++) S[k] = S[k - 1] + ((k & 1) ? bf_hi(ew[k >> 1]) : bf_lo(ew[k >> 1]));
                auto win = [&](int lo, int hi, uint32_t a) {
                    sts128(a, pack2(S[hi] - S[lo - 1], S[hi + 1] - S[lo]), pack2(S[hi + 2] - S[lo + 1], S[hi + 3] - S[lo + 2]),
                           pack2(S[hi + 4] - S[lo + 3], S[hi + 5] - S[lo + 4]), pack2(S[hi + 6] - S[lo + 5], S[hi + 7] - S[lo + 6]));
                };
                win(14, 18, buf + W5_OFF + 16 + ci * 16); win(19, 21, buf + W3_OFF + 16 + ci * 16);
                if (rho < 4) {
                    const uint32_t sw = (ci ^ ((ci >> 3) & 1)) << 4;
                    win(4, 12, buf + W9_OFF + sw); win(13, 19, spare + sw); win(20, 21, spare + 2048 + sw);
                }
            }
        };
        {
            mbar_wait(bar + 8 * (BAR_FULL + xkb), 0);
#pragma unroll 1
            for (int hf = 0; hf < 2; hf++) {
                const int r = w4 * 32 + hf * 16 + (lane & 15);
                uint32_t* xt = (uint32_t*)scr->xt + ((xkb + rot) * 16 + (g >> 2)) * 4096 + (bi_i * 16 + w4 * 4 + hf * 2) * 16 + (g & 3) * 4 + q;
#pragma unroll
                for (int cb = 0; cb < 8; cb += 2) {
                    uint32_t v[4];
                    ldsm4t(v, sb + xkb * SLOT + r * 128 + (((cb + (lane >> 4)) ^ (r & 7)) << 4));
                    xt[cb * 8192] = v[0]; xt[cb * 8192 + 16] = v[1]; xt[cb * 8192 + 8192] = v[2]; xt[cb * 8192 + 8192 + 16] = v[3];
                }
            }
            __syncwarp();
            if (lane == 0) {
                mbar_arrive(bar + 8 * BAR_XT);
                STAMP(26);
                asm volatile("red.release.gpu.global.add.u32 [%0],2;" ::"l"(scr->xcnt + (xkb + rot) * 32) : "memory");
                STAMP(27);
            }
            __syncwarp();
            {
                const uint32_t old = tag ^ 1u;
                const uint4 z4 = make_uint4(old, 0, old, 0);
#pragma unroll
                for (int v = 0; v < 5; v++) if (v < 4 || st < 32) st_rlx128(scr->kvp + bi * 544 + v * 128 + st, z4);
                if (st < 16) st_rlx128(scr->o + ((bi_i * 8 + (st >> 1)) * 32 + bi_j * 4 + 3) * 32 + 30 + (st & 1), z4);
                if (lane < 8) st_rlx64(kvf_h + ((bi_i & 3) * 8 + w4 * 2 + (lane & 1)) * 4 + (lane >> 1), old, 0);
                if (st < 4 && !(bi_i & 1)) st_rlx64(kvf_h + (64 + qq) * 2 + (lane & 1), old, 0);
                __syncwarp();
                if (lane == 0) mbar_arrive(bar + 8 * BAR_PREP);
            }
            int n = 0;
#pragma unroll 1
            while (__any_sync(~0u, (int)(ld_acq(scr->xcnt + bi_j * 32) - (epoch1 << 7)) < 0)) { if (++n > SPIN_LIMIT) break; }
            if (warp == 12) STAMP(15);
            mbar_wait(bar + 8 * BAR_SP, 0);
#pragma unroll
            for (int v = 0; v < 8; v++) {
                const int ci = (st >> 2) + 32 * v;
                asm volatile("cp.async.cg.shared.global [%0],[%1],16;" ::"r"(sb + OFF_U + (st & 3) * U_STRIDE + 256 + ((ci ^ ((ci >> 3) & 1)) << 4)),
                             "l"(scr->xt + bi * 1024 + st + 128 * v) : "memory");
            }
            if (lane < 16) sts128(ub - 256 + lane * 16, 0, 0, 0, 0);
            if (lane < 2) sts128(buf + lane * W3_OFF, 0, 0, 0, 0);
            asm volatile("cp.async.wait_all;" ::: "memory");
            __syncwarp();
            if (lane == 0) mbar_arrive(bar + 8 * BAR_UR);
            mbar_wait(bar + 8 * BAR_UR, 0);
            if (warp == 12) STAMP(16);
        }
        windows(5, 4);
        mbar_wait(bar + 8 * BAR_SP2, 0);
        windows(3, 0);
        __syncwarp();
        if (lane == 0) mbar_arrive(bar + 8 * BAR_WR);
        if (warp == 12) STAMP(24);
        {
            const bool zw = st < 32 && !(bi_i & 1);
            const uint4* src = scr->kvp + bi_j * (16 * 544) + (bi_i >> 2) * 136;
            const uint4* zsrc = src + (lane >> 2) * (2 * 544) + 128 + (lane & 1) * 4 + qq;
            src += (lane >> 3) * (4 * 544) + ((lane >> 1) & 3) * 32 + (bi_i & 3) * 8 + w4 * 2 + (lane & 1);
            mbar_wait(bar + 8 * BAR_PUB, 0);
            if (warp == 12) STAMP(12);
            __nanosleep(D1_NS);
            uint4 v[6];
#pragma unroll
            for (int k = 0; k < 6; k++) v[k] = make_uint4(tag ^ 1u, 0, 0, 0);
            int n = 0;
#pragma unroll 1
            while (true) {
#pragma unroll
                for (int k = 0; k < 6; k++) if ((bad4(v[k], tag) & 1) && (k < 4 || zw)) v[k] = ld_rlx128(k < 4 ? src + k * 544 : zsrc + (k - 4) * 544);
                if (!__any_sync(~0u, (bad4(v[0], tag) | bad4(v[1], tag) | bad4(v[2], tag) | bad4(v[3], tag) | (zw ? bad4(v[4], tag) | bad4(v[5], tag) : 0u)) & 1)) break;
                if (warp == 12 && n < 3) STAMP(54 + n);
                if (++n > SPIN_LIMIT) break;
                __nanosleep(POLL_NS);
            }
#ifdef TIMING
            if (st == 0) sts32(sb + OFF_BAR + 256 + 4 * 58, n + 1);
#endif
            if (warp == 12) STAMP(30);
            float f[8];
            const float* vf = (const float*)v;
#pragma unroll
            for (int r = 0; r < 4; r++) {
                f[r] = (vf[r] + vf[4 + r]) + (vf[8 + r] + vf[12 + r]);
                f[4 + r] = vf[16 + r] + vf[20 + r];
                f[4 + r] += __shfl_xor_sync(~0u, f[4 + r], 4);
            }
#pragma unroll
            for (int o = 8; o <= 16; o <<= 1)
#pragma unroll
                for (int r = 0; r < 8; r++) f[r] += __shfl_xor_sync(~0u, f[r], o);
            if (lane < 8) st_rlx64(kvf_h + ((bi_i & 3) * 8 + w4 * 2 + (lane & 1)) * 4 + (lane >> 1), tagw(pack2(f[0], f[1]), tag), pack2(f[2], f[3]));
            if (zw && lane < 4) st_rlx64(kvf_h + (64 + qq) * 2 + (lane & 1), tagw(pack2(f[4], f[5]), tag), pack2(f[6], f[7]));
        }
        if (warp == 12) STAMP(13);
        {
            const uint4* kp = scr->kvf + bi_j * 272 + st;
            __nanosleep(D2_NS);
            uint4 v0 = make_uint4(tag ^ 1u, 0, 0, 0), v1 = v0, v2 = make_uint4(st < 16 ? tag ^ 1u : tag, 0, tag, 0);
            int n = 0;
#pragma unroll 1
            while (true) {
                if (bad4(v0, tag) & 1) v0 = ld_rlx128(kp);
                if (bad4(v1, tag) & 1) v1 = ld_rlx128(kp + 128);
                if (bad4(v2, tag) & 1) v2 = ld_rlx128(kp + 256);
                if (!__any_sync(~0u, (bad4(v0, tag) | bad4(v1, tag) | bad4(v2, tag)) & 1)) break;
                if (++n > SPIN_LIMIT) break;
                __nanosleep(POLL_NS);
            }
            sts128(sb + OFF_KVF + st * 16, v0.x, v0.y, v0.z, v0.w);
            sts128(sb + OFF_KVF + 2048 + st * 16, v1.x, v1.y, v1.z, v1.w);
            if (st < 16) sts128(sb + OFF_KVF + 4096 + st * 16, v2.x, v2.y, v2.z, v2.w);
            __syncwarp();
            if (lane == 0) mbar_arrive(bar + 8 * BAR_KVF);
        }
        if (warp == 13) {
            mbar_wait(bar + 8 * BAR_KVF, 0);
            if (lane == 0) {
                mbar_expect(bar + 8 * BAR_WO2, 65536);
                tma2d(sb + OFF_P, &mwo, (bi_j & 3) * 128 + 64, 256, bar + 8 * BAR_WO2);
                tma2d(sb + OFF_V, &mwo, (bi_j & 3) * 128, 256, bar + 8 * BAR_WO2);
            }
        }
        if (warp == 12) STAMP(25);
    }
    __syncwarp();
    if (lane == 0) {
        unsigned old;
        asm volatile("atom.acq_rel.cta.shared.add.u32 %0,[%1],1;" : "=r"(old) : "r"(bar + OFF_CNT) : "memory");
        if (old == 15) {
            atomicAdd(scr->done, 1u);
#ifdef TIMING
            STAMP(29);
            for (int i = 0; i < 62; i++) g_ts[blockIdx.x * 64 + i] = lds32(sb + OFF_BAR + 256 + 4 * i);
            long long gt; asm volatile("mov.u64 %0,%%globaltimer;" : "=l"(gt)); g_ts[blockIdx.x * 64 + 63] = gt; g_ts[blockIdx.x * 64 + 62] = gt0;
#endif
        }
    }
}

typedef CUresult (*EncFn)(CUtensorMap*, CUtensorMapDataType, cuuint32_t, void*, const cuuint64_t*, const cuuint64_t*, const cuuint32_t*,
                          const cuuint32_t*, CUtensorMapInterleave, CUtensorMapSwizzle, CUtensorMapL2promotion, CUtensorMapFloatOOBfill);

extern "C" void kernel_launch(void* const* d_in, const int* in_sizes, int n_in, void* d_out, int out_size) {
    static EncFn enc = nullptr;
    static Scratch* scr = nullptr;
    if (!enc) {
        cudaGetSymbolAddress((void**)&scr, g_scr);
        cudaDriverEntryPointQueryResult qr;
        cudaGetDriverEntryPoint("cuTensorMapEncodeTiled", (void**)&enc, cudaEnableDefault, &qr);
        cudaFuncSetAttribute(fused_kernel, cudaFuncAttributeMaxDynamicSharedMemorySize, SMEM_BYTES);
    }
    CUtensorMap mx, mw, mwo;
    const cuuint32_t es[3] = {1, 1, 1};
    {
        cuuint64_t d[2] = {512, 2048}, s[1] = {1024}; cuuint32_t b[2] = {64, 128};
        enc(&mx, CU_TENSOR_MAP_DATA_TYPE_BFLOAT16, 2, d_in[0], d, s, b, es, CU_TENSOR_MAP_INTERLEAVE_NONE, CU_TENSOR_MAP_SWIZZLE_128B,
            CU_TENSOR_MAP_L2_PROMOTION_L2_128B, CU_TENSOR_MAP_FLOAT_OOB_FILL_NONE);
    }
    {
        cuuint64_t d[3] = {512, 512, 3}, s[2] = {3072, 1024}; cuuint32_t b[3] = {64, 64, 3};
        enc(&mw, CU_TENSOR_MAP_DATA_TYPE_BFLOAT16, 3, d_in[1], d, s, b, es, CU_TENSOR_MAP_INTERLEAVE_NONE, CU_TENSOR_MAP_SWIZZLE_128B,
            CU_TENSOR_MAP_L2_PROMOTION_L2_128B, CU_TENSOR_MAP_FLOAT_OOB_FILL_NONE);
    }
    {
        cuuint64_t d[2] = {512, 512}, s[1] = {1024}; cuuint32_t b[2] = {64, 256};
        enc(&mwo, CU_TENSOR_MAP_DATA_TYPE_BFLOAT16, 2, d_in[3], d, s, b, es, CU_TENSOR_MAP_INTERLEAVE_NONE, CU_TENSOR_MAP_SWIZZLE_128B,
            CU_TENSOR_MAP_L2_PROMOTION_L2_128B, CU_TENSOR_MAP_FLOAT_OOB_FILL_NONE);
    }
    fused_kernel<<<128, 512, SMEM_BYTES, cudaStreamPerThread>>>(
        scr, (const bf16*)d_in[5], (const bf16*)d_in[6], (const bf16*)d_in[7], (const bf16*)d_in[8], (const bf16*)d_in[9],
        (const bf16*)d_in[10], (const bf16*)d_in[2], (const bf16*)d_in[11], (bf16*)d_out, mx, mw, mwo);
}
```

```cpp
#include <cuda_runtime.h>
#include <cuda.h>
#include <cuda_bf16.h>
#include <stdint.h>

typedef __nv_bfloat16 bf16;

struct Scratch {
    uint4 xt[128 * 1024];
    uint4 o[16 * 8 * 32 * 32];
    uint4 y[128 * 1024];
    uint4 kvp[8 * 16 * 544];
    uint4 kvf[8 * 4 * 68];
    unsigned g[1024 * 8];
    unsigned yflag[128 * 8];
    unsigned xcnt[8 * 32];
    unsigned done[32];
};
__device__ Scratch g_scr;
#define STAMP(n)

constexpr int SLOT = 40960;
constexpr int OFF_SP0 = 32768, OFF_SP1 = SLOT + 32768;
constexpr int OFF_P = 2 * SLOT, OFF_V = OFF_P + 32768;
constexpr int OFF_KVF = OFF_V + 32768;
constexpr int KT_BYTES = 3264, KW_D = 16, KW_2 = 560, KW_3 = 656;
constexpr int OFF_U = 4 * SLOT, U_STRIDE = 4096 + 256 + 32;
constexpr int OFF_BUF = OFF_U + 4 * U_STRIDE, BUF_STRIDE = 8320;
constexpr int OFF_K = OFF_BUF + 4 * BUF_STRIDE;
constexpr int OFF_WPHI = OFF_K + 4 * KT_BYTES;
constexpr int OFF_GW = OFF_WPHI + 2048;
constexpr int OFF_BAR = OFF_GW + 1024;
constexpr int SMEM_BYTES = OFF_BAR + 256 + 256;
static_assert(SMEM_BYTES <= 232448 && OFF_BUF % 128 == 0, "smem");
constexpr int W5_OFF = 0, W3_OFF = 3088, W9_OFF = 6176;
constexpr int BAR_FULL = 0, BAR_EMPTY = 4, BAR_WPHI = 8, BAR_WO = 9, BAR_WO2 = 10, BAR_XT = 11, BAR_DONE = 12, BAR_KG = 13, BAR_SP = 14,
              BAR_PUB = 15, BAR_KVF = 16, BAR_UR = 17, BAR_WR = 18, BAR_PREP = 19, BAR_KGA = 20, BAR_SP2 = 21, OFF_CNT = 192;
constexpr int SPIN_LIMIT = 1 << 17;

__device__ __forceinline__ uint32_t s2u(const void* p) { return (uint32_t)__cvta_generic_to_shared(p); }
__device__ __forceinline__ void mbar_init(uint32_t b, int c) { asm volatile("mbarrier.init.shared::cta.b64 [%0],%1;" ::"r"(b), "r"(c) : "memory"); }
__device__ __forceinline__ void mbar_expect(uint32_t b, int bytes) { asm volatile("mbarrier.arrive.expect_tx.shared::cta.b64 _,[%0],%1;" ::"r"(b), "r"(bytes) : "memory"); }
__device__ __forceinline__ void mbar_arrive(uint32_t b) { asm volatile("mbarrier.arrive.shared::cta.b64 _,[%0];" ::"r"(b) : "memory"); }
__device__ __forceinline__ void mbar_wait(uint32_t b, int ph) {
    asm volatile("{\n.reg .pred p;\n.reg .u32 n;\nmov.u32 n,0;\nLW_%=:\nmbarrier.try_wait.parity.shared::cta.b64 p,[%0],%1;\n@p bra LD_%=;\n"
                 "add.u32 n,n,1;\nsetp.lt.u32 p,n,16384;\n@p bra LW_%=;\nLD_%=:\n}" ::"r"(b), "r"(ph) : "memory");
}
__device__ __forceinline__ void tma2d(uint32_t dst, const CUtensorMap* m, int c0, int c1, uint32_t bar) {
    asm volatile("cp.async.bulk.tensor.2d.shared::cluster.global.mbarrier::complete_tx::bytes [%0],[%1,{%3,%4}],[%2];" ::"r"(dst), "l"(m), "r"(bar), "r"(c0), "r"(c1) : "memory");
}
__device__ __forceinline__ void tma3d(uint32_t dst, const CUtensorMap* m, int c0, int c1, int c2, uint32_t bar) {
    asm volatile("cp.async.bulk.tensor.3d.shared::cluster.global.mbarrier::complete_tx::bytes [%0],[%1,{%3,%4,%5}],[%2];" ::"r"(dst), "l"(m), "r"(bar), "r"(c0), "r"(c1), "r"(c2) : "memory");
}
__device__ __forceinline__ void bulk_g2s(uint32_t dst, const void* src, int bytes, uint32_t bar) {
    asm volatile("cp.async.bulk.shared::cluster.global.mbarrier::complete_tx::bytes [%0],[%1],%2,[%3];" ::"r"(dst), "l"(src), "r"(bytes), "r"(bar) : "memory");
}
__device__ __forceinline__ uint64_t mkdesc(uint32_t addr, uint32_t lbo, uint32_t sbo) {
    return (uint64_t)((addr & 0x3FFFF) >> 4) | ((uint64_t)(lbo >> 4) << 16) | ((uint64_t)(sbo >> 4) << 32) | ((uint64_t)1 << 62);
}
__device__ __forceinline__ void wg_fence() { asm volatile("wgmma.fence.sync.aligned;" ::: "memory"); }
__device__ __forceinline__ void wg_commit() { asm volatile("wgmma.commit_group.sync.aligned;" ::: "memory"); }
template <int N> __device__ __forceinline__ void wg_wait() { asm volatile("wgmma.wait_group.sync.aligned %0;" ::"n"(N) : "memory"); }
template <int N> __device__ __forceinline__ void fence_regs(float* d) {
#pragma unroll
    for (int i = 0; i < N; i++) asm volatile("" : "+f"(d[i])::"memory");
}
#define R8(d, o) "+f"(d[o]), "+f"(d[o + 1]), "+f"(d[o + 2]), "+f"(d[o + 3]), "+f"(d[o + 4]), "+f"(d[o + 5]), "+f"(d[o + 6]), "+f"(d[o + 7])
__device__ __forceinline__ void wgmma192(float* d, uint64_t da, uint64_t db, int sc) {
    asm volatile("{.reg .pred p; setp.ne.b32 p,%98,0; wgmma.mma_async.sync.aligned.m64n192k16.f32.bf16.bf16 {"
                 "%0,%1,%2,%3,%4,%5,%6,%7,%8,%9,%10,%11,%12,%13,%14,%15,%16,%17,%18,%19,%20,%21,%22,%23,%24,%25,%26,%27,%28,%29,%30,%31,"
                 "%32,%33,%34,%35,%36,%37,%38,%39,%40,%41,%42,%43,%44,%45,%46,%47,%48,%49,%50,%51,%52,%53,%54,%55,%56,%57,%58,%59,%60,%61,%62,%63,"
                 "%64,%65,%66,%67,%68,%69,%70,%71,%72,%73,%74,%75,%76,%77,%78,%79,%80,%81,%82,%83,%84,%85,%86,%87,%88,%89,%90,%91,%92,%93,%94,%95},"
                 "%96,%97,p,1,1,0,1;}"
                 : R8(d, 0), R8(d, 8), R8(d, 16), R8(d, 24), R8(d, 32), R8(d, 40), R8(d, 48), R8(d, 56), R8(d, 64), R8(d, 72), R8(d, 80), R8(d, 88)
                 : "l"(da), "l"(db), "r"(sc));
}
__device__ __forceinline__ void wgmma64_tt(float* d, uint64_t da, uint64_t db, int sc) {
    asm volatile("{.reg .pred p; setp.ne.b32 p,%34,0; wgmma.mma_async.sync.aligned.m64n64k16.f32.bf16.bf16 {"
                 "%0,%1,%2,%3,%4,%5,%6,%7,%8,%9,%10,%11,%12,%13,%14,%15,%16,%17,%18,%19,%20,%21,%22,%23,%24,%25,%26,%27,%28,%29,%30,%31},"
                 "%32,%33,p,1,1,1,1;}"
                 : R8(d, 0), R8(d, 8), R8(d, 16), R8(d, 24)
                 : "l"(da), "l"(db), "r"(sc));
}
__device__ __forceinline__ void wgmma128_rs(float* d, const uint4& a, uint64_t db, int sc) {
    asm volatile("{.reg .pred p; setp.ne.b32 p,%69,0; wgmma.mma_async.sync.aligned.m64n128k16.f32.bf16.bf16 {"
                 "%0,%1,%2,%3,%4,%5,%6,%7,%8,%9,%10,%11,%12,%13,%14,%15,%16,%17,%18,%19,%20,%21,%22,%23,%24,%25,%26,%27,%28,%29,%30,%31,"
                 "%32,%33,%34,%35,%36,%37,%38,%39,%40,%41,%42,%43,%44,%45,%46,%47,%48,%49,%50,%51,%52,%53,%54,%55,%56,%57,%58,%59,%60,%61,%62,%63},"
                 "{%64,%65,%66,%67},%68,p,1,1,1;}"
                 : R8(d, 0), R8(d, 8), R8(d, 16), R8(d, 24), R8(d, 32), R8(d, 40), R8(d, 48), R8(d, 56)
                 : "r"(a.x), "r"(a.y), "r"(a.z), "r"(a.w), "l"(db), "r"(sc));
}
__device__ __forceinline__ void mma16816(float* c, uint32_t a0, uint32_t a1, uint32_t a2, uint32_t a3, uint32_t b0, uint32_t b1) {
    asm("mma.sync.aligned.m16n8k16.row.col.f32.bf16.bf16.f32 {%0,%1,%2,%3},{%4,%5,%6,%7},{%8,%9},{%0,%1,%2,%3};"
        : "+f"(c[0]), "+f"(c[1]), "+f"(c[2]), "+f"(c[3]) : "r"(a0), "r"(a1), "r"(a2), "r"(a3), "r"(b0), "r"(b1));
}
__device__ __forceinline__ void ldsm4(uint32_t* r, uint32_t a) {
    asm volatile("ldmatrix.sync.aligned.m8n8.x4.shared.b16 {%0,%1,%2,%3},[%4];" : "=r"(r[0]), "=r"(r[1]), "=r"(r[2]), "=r"(r[3]) : "r"(a) : "memory");
}
__device__ __forceinline__ void ldsm4t(uint32_t* r, uint32_t a) {
    asm volatile("ldmatrix.sync.aligned.m8n8.x4.trans.shared.b16 {%0,%1,%2,%3},[%4];" : "=r"(r[0]), "=r"(r[1]), "=r"(r[2]), "=r"(r[3]) : "r"(a) : "memory");
}
__device__ __forceinline__ void stsm4(uint32_t a, uint32_t r0, uint32_t r1, uint32_t r2, uint32_t r3) {
    asm volatile("stmatrix.sync.aligned.m8n8.x4.shared.b16 [%0],{%1,%2,%3,%4};" ::"r"(a), "r"(r0), "r"(r1), "r"(r2), "r"(r3) : "memory");
}
__device__ __forceinline__ uint32_t lds32(uint32_t a) { uint32_t v; asm volatile("ld.shared.b32 %0,[%1];" : "=r"(v) : "r"(a) : "memory"); return v; }
__device__ __forceinline__ uint4 lds128(uint32_t a) { uint4 v; asm volatile("ld.shared.v4.b32 {%0,%1,%2,%3},[%4];" : "=r"(v.x), "=r"(v.y), "=r"(v.z), "=r"(v.w) : "r"(a) : "memory"); return v; }
__device__ __forceinline__ void sts16(uint32_t a, uint32_t v) { asm volatile("st.shared.b16 [%0],%1;" ::"r"(a), "h"((unsigned short)v) : "memory"); }
__device__ __forceinline__ void sts32(uint32_t a, uint32_t v) { asm volatile("st.shared.b32 [%0],%1;" ::"r"(a), "r"(v) : "memory"); }
__device__ __forceinline__ void sts64(uint32_t a, uint32_t x, uint32_t y) { asm volatile("st.shared.v2.b32 [%0],{%1,%2};" ::"r"(a), "r"(x), "r"(y) : "memory"); }
__device__ __forceinline__ void sts128(uint32_t a, uint32_t x, uint32_t y, uint32_t z, uint32_t w) { asm volatile("st.shared.v4.b32 [%0],{%1,%2,%3,%4};" ::"r"(a), "r"(x), "r"(y), "r"(z), "r"(w) : "memory"); }
__device__ __forceinline__ uint32_t pack2(float lo, float hi) { uint32_t d; asm("cvt.rn.bf16x2.f32 %0,%1,%2;" : "=r"(d) : "f"(hi), "f"(lo)); return d; }
__device__ __forceinline__ float bf_lo(uint32_t v) { return __uint_as_float(v << 16); }
__device__ __forceinline__ float bf_hi(uint32_t v) { return __uint_as_float(v & 0xffff0000u); }
__device__ __forceinline__ float bf_round(float v) { return bf_lo(pack2(v, 0.f)); }
__device__ __forceinline__ uint32_t hmax2(uint32_t a, uint32_t b) { uint32_t d; asm("max.bf16x2 %0,%1,%2;" : "=r"(d) : "r"(a), "r"(b)); return d; }
__device__ __forceinline__ uint32_t hmin2(uint32_t a, uint32_t b) { uint32_t d; asm("min.bf16x2 %0,%1,%2;" : "=r"(d) : "r"(a), "r"(b)); return d; }
__device__ __forceinline__ uint32_t hmul2(uint32_t a, uint32_t b) { uint32_t d; asm("mul.rn.bf16x2 %0,%1,%2;" : "=r"(d) : "r"(a), "r"(b)); return d; }
__device__ __forceinline__ float ex2(float x) { float y; asm("ex2.approx.ftz.f32 %0,%1;" : "=f"(y) : "f"(x)); return y; }
__device__ __forceinline__ float rcp(float x) { float y; asm("rcp.approx.ftz.f32 %0,%1;" : "=f"(y) : "f"(x)); return y; }
__device__ __forceinline__ uint32_t ld_nc(const uint32_t* p) { uint32_t v; asm volatile("ld.global.nc.b32 %0,[%1];" : "=r"(v) : "l"(p)); return v; }
__device__ __forceinline__ uint2 ld_nc64(const uint2* p) { uint2 v; asm volatile("ld.global.nc.v2.b32 {%0,%1},[%2];" : "=r"(v.x), "=r"(v.y) : "l"(p)); return v; }
__device__ __forceinline__ unsigned ld_acq(const unsigned* p) { unsigned v; asm volatile("ld.acquire.gpu.global.u32 %0,[%1];" : "=r"(v) : "l"(p) : "memory"); return v; }
__device__ __forceinline__ unsigned ld_rlx(const unsigned* p) { unsigned v; asm volatile("ld.relaxed.gpu.global.u32 %0,[%1];" : "=r"(v) : "l"(p) : "memory"); return v; }
__device__ __forceinline__ uint2 ld_rlx64(const void* p) { uint2 v; asm volatile("{.reg .b64 t; ld.relaxed.gpu.global.b64 t,[%2]; mov.b64 {%0,%1},t;}" : "=r"(v.x), "=r"(v.y) : "l"(p) : "memory"); return v; }
__device__ __forceinline__ uint4 ld_rlx128(const void* p) {
    uint4 v;
    asm volatile("{.reg .b64 t,u; ld.relaxed.gpu.global.v2.b64 {t,u},[%4]; mov.b64 {%0,%1},t; mov.b64 {%2,%3},u;}" : "=r"(v.x), "=r"(v.y), "=r"(v.z), "=r"(v.w) : "l"(p) : "memory");
    return v;
}
__device__ __forceinline__ void st_rlx32(void* p, uint32_t x) { asm volatile("st.relaxed.gpu.global.u32 [%0],%1;" ::"l"(p), "r"(x) : "memory"); }
__device__ __forceinline__ void st_rlx64(void* p, uint32_t x, uint32_t y) { asm volatile("{.reg .b64 t; mov.b64 t,{%1,%2}; st.relaxed.gpu.global.b64 [%0],t;}" ::"l"(p), "r"(x), "r"(y) : "memory"); }
__device__ __forceinline__ void st_rlx128(void* p, uint4 v) {
    asm volatile("{.reg .b64 t,u; mov.b64 t,{%1,%2}; mov.b64 u,{%3,%4}; st.relaxed.gpu.global.v2.b64 [%0],{t,u};}" ::"l"(p), "r"(v.x), "r"(v.y), "r"(v.z), "r"(v.w) : "memory");
}
__device__ __forceinline__ uint32_t tagw(uint32_t w, uint32_t tag) { return (w & ~1u) | tag; }
__device__ __forceinline__ uint4 tag4(uint32_t x, uint32_t y, uint32_t z, uint32_t w, uint32_t tag) { return make_uint4(tagw(x, tag), y, tagw(z, tag), w); }
__device__ __forceinline__ uint32_t bad4(const uint4& v, uint32_t tag) { return (v.x ^ tag) | (v.z ^ tag); }
__device__ __forceinline__ void bar_named(int id, int n) { asm volatile("bar.sync %0,%1;" ::"r"(id), "r"(n) : "memory"); }

struct cf { float re, im; };
__device__ __forceinline__ cf cmul(cf a, cf b) { cf r; r.re = a.re * b.re - a.im * b.im; r.im = a.re * b.im + a.im * b.re; return r; }
__device__ __forceinline__ cf cexp_p(float arl, float ait, float p) {
    float mag = ex2(arl * p);
    float t = ait * p;
    t = (t - rintf(t)) * 6.283185307179586f;
    cf r; r.re = mag * __cosf(t); r.im = mag * __sinf(t);
    return r;
}

__device__ __forceinline__ void hedgehog4(const uint32_t* a, uint32_t wphi_addr, uint32_t (*out)[8]) {
    float p[4][2][4], mx[4][2];
#pragma unroll
    for (int h = 0; h < 4; h++) {
        uint32_t b[4];
        ldsm4t(b, wphi_addr + h * 512);
        float c0[4] = {0.f, 0.f, 0.f, 0.f}, c1[4] = {0.f, 0.f, 0.f, 0.f};
        mma16816(c0, a[4 * h], a[4 * h + 1], a[4 * h + 2], a[4 * h + 3], b[0], b[1]);
        mma16816(c1, a[4 * h], a[4 * h + 1], a[4 * h + 2], a[4 * h + 3], b[2], b[3]);
#pragma unroll
        for (int k = 0; k < 2; k++) {
            p[h][k][0] = c0[2 * k]; p[h][k][1] = c0[2 * k + 1]; p[h][k][2] = c1[2 * k]; p[h][k][3] = c1[2 * k + 1];
            mx[h][k] = fmaxf(fmaxf(p[h][k][0], p[h][k][1]), fmaxf(p[h][k][2], p[h][k][3]));
        }
    }
#pragma unroll
    for (int o = 1; o <= 2; o <<= 1)
#pragma unroll
        for (int h = 0; h < 4; h++)
#pragma unroll
            for (int k = 0; k < 2; k++) mx[h][k] = fmaxf(mx[h][k], __shfl_xor_sync(~0u, mx[h][k], o));
    const float L = 1.4426950408889634f;
    float pmin = 1.f;
#pragma unroll
    for (int h = 0; h < 4; h++)
#pragma unroll
        for (int k = 0; k < 2; k++) {
            const float m = -mx[h][k] * L;
            const float e0 = ex2(fmaf(p[h][k][0], L, m)), e1 = ex2(fmaf(p[h][k][1], L, m)), e2 = ex2(fmaf(p[h][k][2], L, m)), e3 = ex2(fmaf(p[h][k][3], L, m));
            const float p01 = e0 * e1, p23 = e2 * e3, pp = p01 * p23, r = rcp(pp), r01 = r * p23, r23 = r * p01;
            pmin = fminf(pmin, pp);
            out[h][k] = pack2(e0, e1); out[h][k + 2] = pack2(e2, e3);
            out[h][4 + k] = pack2(r01 * e1, r01 * e0); out[h][4 + k + 2] = pack2(r23 * e3, r23 * e2);
        }
    if (__builtin_expect(__any_sync(~0u, !(pmin > 1e-18f)), 0)) {
#pragma unroll
        for (int h = 0; h < 4; h++)
#pragma unroll
            for (int k = 0; k < 2; k++) {
                float m = fminf(fminf(p[h][k][0], p[h][k][1]), fminf(p[h][k][2], p[h][k][3]));
                m = fminf(m, __shfl_xor_sync(~0u, m, 1));
                m = fminf(m, __shfl_xor_sync(~0u, m, 2)) * L;
                out[h][4 + k] = pack2(ex2(fmaf(p[h][k][0], -L, m)), ex2(fmaf(p[h][k][1], -L, m)));
                out[h][4 + k + 2] = pack2(ex2(fmaf(p[h][k][2], -L, m)), ex2(fmaf(p[h][k][3], -L, m)));
            }
    }
}

__global__ void __launch_bounds__(512, 1)
fused_kernel(Scratch* __restrict__ scr, const bf16* __restrict__ logA, const bf16* __restrict__ Aim, const bf16* __restrict__ Cre,
             const bf16* __restrict__ Cim, const bf16* __restrict__ logdt, const bf16* __restrict__ Dskip, const bf16* __restrict__ wphi,
             const bf16* __restrict__ gatew, bf16* __restrict__ out,
             const __grid_constant__ CUtensorMap mx, const __grid_constant__ CUtensorMap mw, const __grid_constant__ CUtensorMap mwo) {
    extern __shared__ __align__(1024) uint8_t smem[];
    constexpr uint32_t sb = 1024;
    const int tid = threadIdx.x, warp = __shfl_sync(~0u, tid >> 5, 0), lane = tid & 31;
    const int g = lane >> 2, q = lane & 3, w4 = warp & 3;
    const int bi = blockIdx.x, bi_i = bi & 15, bi_j = bi >> 4;
    const uint32_t bar = sb + OFF_BAR;
    const int rot = (bi_j & 3) * 2, xkb = bi_j >> 2;
    auto load_stage = [&](int kb) {
        const uint32_t b = bar + 8 * (BAR_FULL + (kb & 3)), d = sb + (kb & 3) * SLOT;
        const int kc = ((kb + rot) & 7) * 64;
        mbar_expect(b, SLOT);
        tma2d(d, &mx, kc, bi_i * 128, b);
        tma3d(d + 16384, &mw, bi_j * 64, kc, 0, b);
    };

    const int ch = bi * 4 + w4;
    const int pidx = ch * 64 + lane * 2 + (warp >> 3);
    const uint32_t pla = ld_nc((const uint32_t*)logA + pidx), pai = ld_nc((const uint32_t*)Aim + pidx);
    const uint32_t pcr = ld_nc((const uint32_t*)Cre + pidx), pci = ld_nc((const uint32_t*)Cim + pidx);
    uint32_t pdt = ld_nc((const uint32_t*)logdt + (ch >> 1));
    const uint32_t pds = ld_nc((const uint32_t*)Dskip + (ch >> 1));
    unsigned done0 = ld_rlx(scr->done);
    if (tid == 0) {
        for (int s = 0; s < 4; s++) mbar_init(bar + 8 * (BAR_FULL + s), 1);
        asm volatile("fence.mbarrier_init.release.cluster;" ::: "memory");
        asm volatile("prefetch.tensormap [%0];" ::"l"(&mx) : "memory");
        load_stage(0); load_stage(1);
        STAMP(11);
    } else if (tid == 32) {
        if (s2u(smem) != sb) __trap();
        sts32(bar + OFF_CNT, 0);
        for (int s = 0; s < 4; s++) mbar_init(bar + 8 * (BAR_EMPTY + s), 9);
        mbar_init(bar + 8 * BAR_WPHI, 1); mbar_init(bar + 8 * BAR_WO, 2); mbar_init(bar + 8 * BAR_WO2, 1); mbar_init(bar + 8 * BAR_XT, 4);
        mbar_init(bar + 8 * BAR_DONE, 9); mbar_init(bar + 8 * BAR_KG, 8); mbar_init(bar + 8 * BAR_SP, 1); mbar_init(bar + 8 * BAR_PUB, 8);
        mbar_init(bar + 8 * BAR_KVF, 4); mbar_init(bar + 8 * BAR_UR, 4); mbar_init(bar + 8 * BAR_WR, 4); mbar_init(bar + 8 * BAR_PREP, 4); mbar_init(bar + 8 * BAR_KGA, 4); mbar_init(bar + 8 * BAR_SP2, 1);
        asm volatile("fence.mbarrier_init.release.cluster;" ::: "memory");
        mbar_expect(bar + 8 * BAR_WPHI, 3072);
        bulk_g2s(sb + OFF_GW, gatew, 1024, bar + 8 * BAR_WPHI);
        bulk_g2s(sb + OFF_WPHI, wphi + bi_j * 1024, 2048, bar + 8 * BAR_WPHI);
    } else if (tid == 64) {
        asm volatile("prefetch.tensormap [%0];" ::"l"(&mw) : "memory");
    }
    const uint32_t buf = sb + OFF_BUF + w4 * BUF_STRIDE, kb_ = sb + OFF_K + w4 * KT_BYTES;
    if ((warp >> 2) == 2) {
#pragma unroll
        for (int v = 0; v < 7; v++) if (v * 32 + lane < KT_BYTES / 16) sts128(kb_ + (v * 32 + lane) * 16, 0, 0, 0, 0);
    }
    __syncthreads();
    asm volatile("" : "+r"(pdt), "+r"(done0)::"memory");
    const unsigned epoch1 = (done0 >> 7) + 1u;
    const uint32_t tag = epoch1 & 1u;

    const int st = tid & 127;
    const uint32_t ub = sb + OFF_U + w4 * U_STRIDE + 256, spare = sb + (w4 < 2 ? OFF_SP0 : OFF_SP1) + (w4 & 1) * 4096;

    auto stg_of = [&](int w) { return w < 8 ? sb + 3 * SLOT + w * 7296 : sb + 2 * SLOT + (w & 3) * 7296; };
    float kc[24];
#pragma unroll
    for (int t = 0; t < 24; t++) kc[t] = 0.f;
    {
        const float dt = bf_round(expf((ch & 1) ? bf_hi(pdt) : bf_lo(pdt)));
        const uint32_t stg = (warp >> 2) == 2 ? buf : stg_of(warp);
        const int sh = ((warp >> 2) & 1) * 16;
        auto pick = [&](uint32_t v) { return __uint_as_float((v >> sh) << 16); };
        const float ea = bf_round(ex2(pick(pla) * 1.4426950408889634f));
        const float arl = (-ea * dt) * 1.4426950408889634f, ait = (pick(pai) * dt) * 0.15915494309189535f;
        cf C2; C2.re = 2.0f * (pick(pcr) * dt); C2.im = 2.0f * (pick(pci) * dt);
        const cf z1 = cexp_p(arl, ait, 1.0f), z128 = cexp_p(arl, ait, 128.0f);
        cf z8 = cexp_p(arl, ait, 8.0f); z8.im = -z8.im;
        const uint32_t lp = stg + lane * 4;
        auto put = [&](int row, const cf& v) { sts32((lp ^ ((row & 7) << 4)) + row * 128, pack2(v.re, v.im)); };
        {
            const cf z16 = cmul(z8, z8);
            cf e; e.re = 1.f; e.im = 0.f;
            cf o = z8;
            put(0, e); put(1, o);
            e = z16; put(2, e);
#pragma unroll
            for (int b = 3; b < 16; b += 2) {
                o = cmul(o, z16); put(b, o);
                if (b + 1 < 16) { e = cmul(e, z16); put(b + 1, e); }
            }
        }
        cf h[8];
        h[0] = C2; put(16, h[0]);
        {
            const cf z2 = cmul(z1, z1);
            h[1] = cmul(h[0], z1);
#pragma unroll
            for (int r = 2; r < 8; r++) h[r] = cmul(h[r - 2], z2);
#pragma unroll
            for (int r = 1; r < 8; r++) put(16 + r, h[r]);
        }
#pragma unroll
        for (int r = 0; r < 8; r++) { h[r] = cmul(h[r], z128); put(24 + r, h[r]); }
#pragma unroll
        for (int al = 0; al < 2; al++)
#pragma unroll
            for (int r = 0; r < 4; r++) { h[2 * r] = cmul(h[2 * r], z128); put(32 + al * 4 + r, h[2 * r]); }
#pragma unroll
        for (int al = 0; al < 4; al++)
#pragma unroll
            for (int r = 0; r < 2; r++) { h[4 * r] = cmul(h[4 * r], z128); put(40 + al * 2 + r, h[4 * r]); }
#pragma unroll
        for (int al = 0; al < 9; al++) { h[0] = cmul(h[0], z128); put(48 + al, h[0]); }
        __syncwarp();
        const int lr = lane & 7, lm = lane >> 3;
#pragma unroll
        for (int kp = 0; kp < 2; kp++) {
            uint32_t a0[4], a1[4];
            ldsm4(a0, stg + ((lm & 1) * 8 + lr) * 128 + (((4 * kp + (lm >> 1)) ^ lr) << 4));
            ldsm4(a1, stg + ((lm & 1) * 8 + lr) * 128 + (((4 * kp + 2 + (lm >> 1)) ^ lr) << 4));
#pragma unroll
            for (int t = 0; t < 6; t++) {
                uint32_t b[4];
                ldsm4(b, stg + (16 + 8 * t + lr) * 128 + (((4 * kp + lm) ^ lr) << 4));
                mma16816(kc + 4 * t, a0[0], a0[1], a0[2], a0[3], b[0], b[1]);
                mma16816(kc + 4 * t, a1[0], a1[1], a1[2], a1[3], b[2], b[3]);
            }
        }
        __syncwarp();
        if ((warp >> 2) != 2) {
#pragma unroll
            for (int t = 0; t < 6; t++)
                sts128(stg + (t * 32 + lane) * 16, __float_as_uint(kc[4 * t]), __float_as_uint(kc[4 * t + 1]), __float_as_uint(kc[4 * t + 2]), __float_as_uint(kc[4 * t + 3]));
            asm volatile("fence.proxy.async.shared::cta;" ::: "memory");
            __syncwarp();
            if (lane == 0) mbar_arrive(bar + 8 * (warp < 8 ? BAR_KG : BAR_KGA));
        }
    }

    if (warp < 8) {
        asm volatile("setmaxnreg.inc.sync.aligned.u32 160;");
        const int wg = warp >> 2;
        if (warp == 0) STAMP(21);
        float acc[96];
        const int srow = warp * 16 + (lane & 15);
        const uint32_t srow_a = srow * 128;
        const int sx = srow & 7, shi = lane >> 4;
        const uint64_t da0 = mkdesc(sb + wg * 8192, 16, 1024), db0 = mkdesc(sb + 16384, 8192, 1024);
#pragma unroll 1
        for (int kb = 0; kb < 8; kb++) {
            const int s = kb & 3;
            const uint64_t da = da0 + s * (SLOT >> 4), db = db0 + s * (SLOT >> 4);
            if (warp == 0) STAMP(40 + kb);
            mbar_wait(bar + 8 * (BAR_FULL + s), kb >> 2);
            if (warp == 0) STAMP(32 + kb);
            wg_fence();
#pragma unroll
            for (int k = 0; k < 4; k++) wgmma192(acc, da + 2 * k, db + 128 * k, kb | k);
            wg_commit();
            wg_wait<1>();
            if (lane == 0 && kb > 0) mbar_arrive(bar + 8 * (BAR_EMPTY + ((kb - 1) & 3)));
        }
        mbar_wait(bar + 8 * BAR_WPHI, 0);
        wg_wait<0>();
        fence_regs<96>(acc);
        if (lane == 0) mbar_arrive(bar + 8 * BAR_DONE);
        if (warp == 0) STAMP(1);
        uint32_t in[16], qa[16];
        mbar_wait(bar + 8 * BAR_DONE, 0);
#pragma unroll
        for (int r = 0; r < 16; r++) {
            in[r] = pack2(acc[32 + 2 * r], acc[32 + 2 * r + 1]);
            qa[r] = pack2(acc[2 * r], acc[2 * r + 1]);
        }
#pragma unroll
        for (int hh = 0; hh < 4; hh++)
            stsm4(sb + OFF_V + (hh >> 1) * 16384 + srow_a + (((2 * (hh & 1) + shi) ^ sx) << 4), pack2(acc[64 + 8 * hh], acc[65 + 8 * hh]),
                  pack2(acc[66 + 8 * hh], acc[67 + 8 * hh]), pack2(acc[68 + 8 * hh], acc[69 + 8 * hh]), pack2(acc[70 + 8 * hh], acc[71 + 8 * hh]));
        sts128(sb + OFF_V + shi * 16384 + srow_a + ((4 ^ sx) << 4), 0x3f803f80u, 0x3f803f80u, 0x3f803f80u, 0x3f803f80u);
        const uint32_t wphi_a = sb + OFF_WPHI + (lane & 15) * 32 + (lane >> 4) * 16;
        uint32_t pq[4][8];
#pragma unroll 1
        for (int it = 0; it < 2; it++) {
            hedgehog4(in, wphi_a, pq);
            if (it == 1) break;
#pragma unroll
            for (int hs = 0; hs < 8; hs++) {
                float c[4] = {0.f, 0.f, 0.f, 0.f};
                const uint32_t* o = pq[hs >> 1] + 4 * (hs & 1);
                mma16816(c, o[0], o[1], o[2], o[3], 0x3f803f80u, 0x3f803f80u);
                const float r0 = rcp(c[0]), r1 = rcp(c[2]);
                const uint32_t s0 = pack2(r0, r0), s1 = pack2(r1, r1);
                stsm4(sb + OFF_P + (hs >> 2) * 16384 + srow_a + (((2 * (hs & 3) + shi) ^ sx) << 4), hmul2(o[0], s0), hmul2(o[1], s1), hmul2(o[2], s0), hmul2(o[3], s1));
            }
            asm volatile("fence.proxy.async.shared::cta;" ::: "memory");
            bar_named(1, 256);
            if (warp == 0) STAMP(2);
            float d[32];
            const uint64_t dv = mkdesc(sb + OFF_V + wg * 16384, 16, 1024), dp = mkdesc(sb + OFF_P + wg * 16384, 16, 1024);
            wg_fence();
#pragma unroll
            for (int k = 0; k < 8; k++) wgmma64_tt(d, dv + 128 * k, dp + 128 * k, k != 0);
            wg_commit();
            mbar_wait(bar + 8 * BAR_PREP, 0);
            uint4* kvp = scr->kvp + bi * 544 + wg * 272 + (w4 < 2 ? w4 * 136 : 128) + lane;
            wg_wait<0>();
            fence_regs<32>(d);
            if (w4 < 2 || (w4 == 2 && lane < 4)) {
#pragma unroll
                for (int f = 0; f < 4; f++) {
                    const int i0 = 8 * (f >> 1) + 2 * (f & 1), i2 = 16 * (f >> 1) + 8 * (f & 1);
                    const float e0 = w4 == 0 ? d[i0] : (w4 == 1 ? d[16 + i0] : d[i2]), e1 = w4 == 0 ? d[i0 + 1] : (w4 == 1 ? d[17 + i0] : d[i2 + 1]);
                    const float e2 = w4 == 0 ? d[i0 + 4] : (w4 == 1 ? d[20 + i0] : d[i2 + 4]), e3 = w4 == 0 ? d[i0 + 5] : (w4 == 1 ? d[21 + i0] : d[i2 + 5]);
                    st_rlx128(kvp + (w4 < 2 ? f * 32 : (f >> 1) * 136 + (f & 1) * 4), tag4(__float_as_uint(e0), __float_as_uint(e1), __float_as_uint(e2), __float_as_uint(e3), tag));
                }
            }
            __syncwarp();
            if (lane == 0) mbar_arrive(bar + 8 * BAR_PUB);
            if (warp == 0) STAMP(3);
#pragma unroll
            for (int r = 0; r < 16; r++) in[r] = qa[r];
        }
        if (warp == 0) STAMP(4);
        {
            mbar_wait(bar + 8 * BAR_KVF, 0);
            uint4 kf[4][3];
#pragma unroll
            for (int hh = 0; hh < 4; hh++) {
                const uint32_t a = sb + OFF_KVF + hh * 1088;
                kf[hh][0] = lds128(a + lane * 32); kf[hh][1] = lds128(a + lane * 32 + 16); kf[hh][2] = lds128(a + 1024 + q * 16);
            }
            if (warp == 0) STAMP(5);
            uint4* og = scr->o + ((bi_i * 8 + warp) * 32 + bi_j * 4) * 32 + lane;
#pragma unroll
            for (int hh = 0; hh < 4; hh++) {
                float c[6][4];
#pragma unroll
                for (int t = 0; t < 6; t++) { c[t][0] = c[t][1] = c[t][2] = c[t][3] = 0.f; }
                const uint32_t* a = pq[hh];
                const bool od = g & 1;
                mma16816(c[0], a[0], a[1], a[2], a[3], od ? 0x3f803f80u : kf[hh][2].x, od ? 0x3f803f80u : kf[hh][2].y);
                mma16816(c[1], a[4], a[5], a[6], a[7], od ? 0x3f803f80u : kf[hh][2].z, od ? 0x3f803f80u : kf[hh][2].w);
                mma16816(c[2], a[0], a[1], a[2], a[3], kf[hh][0].x, kf[hh][0].y);
                mma16816(c[3], a[0], a[1], a[2], a[3], kf[hh][0].z, kf[hh][0].w);
                mma16816(c[4], a[4], a[5], a[6], a[7], kf[hh][1].x, kf[hh][1].y);
                mma16816(c[5], a[4], a[5], a[6], a[7], kf[hh][1].z, kf[hh][1].w);
                uint32_t w[4];
#pragma unroll
                for (int k = 0; k < 2; k++) {
                    const float rho = c[0][2 * k + 1] * rcp(c[1][2 * k + 1]);
                    const float r = rcp(fmaf(c[0][2 * k + 1], 1e-6f, fmaf(rho, c[1][2 * k], c[0][2 * k]))), rr = r * rho;
                    w[k] = pack2(fmaf(c[4][2 * k], rr, c[2][2 * k] * r), fmaf(c[4][2 * k + 1], rr, c[2][2 * k + 1] * r));
                    w[2 + k] = pack2(fmaf(c[5][2 * k], rr, c[3][2 * k] * r), fmaf(c[5][2 * k + 1], rr, c[3][2 * k + 1] * r));
                }
                st_rlx128(og + hh * 32, tag4(w[0], w[1], w[2], w[3], tag));
            }
        }
        if (warp == 0) STAMP(6);
        float oc[64];
        const int slab = bi_i * 8 + (bi_j >> 2) * 4 + w4;
        const uint8_t* ysrc = (const uint8_t*)scr->y + (size_t)((bi_j & 3) * 32 + wg * 16 + (q >> 1)) * 16384 + slab * 128 + g * 16 + (q & 1) * 8;
        const unsigned* gp = scr->g + (slab * 8 + (g >> 1)) * 8 + (g & 1) * 4;
        uint2 yv[8]; unsigned g0, g1;
        {
            const uint4* osrc = scr->o + (slab * 32 + wg * 16) * 32 + lane;
            uint4 fr[16];
            const unsigned* probe = (const unsigned*)(osrc - lane + ((lane & 3) * 4 + 3) * 32 + 31) + 2;
            {
                unsigned miss = ~0u;
                int n = 0;
#pragma unroll
                for (int s = 0; s < 4; s++) {
#pragma unroll 1
                    while ((miss >> s) & 1) { miss = __ballot_sync(~0u, (ld_rlx(probe) ^ tag) & 1); if (++n > SPIN_LIMIT) break; }
#pragma unroll
                    for (int k = 4 * s; k < 4 * s + 4; k++) fr[k] = ld_rlx128(osrc + k * 32);
                }
            }
            if (warp == 0) STAMP(14);
            mbar_wait(bar + 8 * (wg ? BAR_WO2 : BAR_WO), 0);
            const uint64_t dw = mkdesc(sb + wg * 2 * SLOT, wg ? 32768 : SLOT, 1024);
#pragma unroll
            for (int s = 0; s < 4; s++) {
                int n = 0;
#pragma unroll 1
                while (__builtin_expect(__any_sync(~0u, (bad4(fr[4 * s], tag) | bad4(fr[4 * s + 1], tag) | bad4(fr[4 * s + 2], tag) | bad4(fr[4 * s + 3], tag)) & 1), 0)) {
#pragma unroll
                    for (int k = 4 * s; k < 4 * s + 4; k++) fr[k] = ld_rlx128(osrc + k * 32);
                    if (++n > SPIN_LIMIT) break;
                }
                wg_fence();
#pragma unroll
                for (int hh = 0; hh < 4; hh++) wgmma128_rs(oc, fr[4 * s + hh], dw + 128 * (4 * s + hh), (s | hh) != 0);
                wg_commit();
                if (s == 1) {
                    wg_wait<1>();
#pragma unroll
                    for (int nt = 0; nt < 8; nt++) yv[nt] = ld_rlx64(ysrc + nt * 32768);
                    g0 = ld_rlx(gp); g1 = ld_rlx(gp + 32);
                }
            }
            if (warp == 0) STAMP(7);
            {
                const unsigned* yprobe = scr->yflag + ((bi_j & 3) * 32 + wg * 16 + (lane & 15)) * 8;
                int n = 0;
#pragma unroll 1
                while (true) {
                    uint32_t bad = (g0 ^ tag) | (g1 ^ tag);
#pragma unroll
                    for (int nt = 0; nt < 8; nt++) bad |= yv[nt].x ^ tag;
                    if (!__any_sync(~0u, bad & 1)) break;
#pragma unroll 1
                    while (__any_sync(~0u, (ld_rlx(yprobe) ^ tag) & 1)) { if (++n > SPIN_LIMIT) break; }
#pragma unroll
                    for (int nt = 0; nt < 8; nt++) yv[nt] = ld_rlx64(ysrc + nt * 32768);
                    g0 = ld_rlx(gp); g1 = ld_rlx(gp + 32);
                    if (++n > SPIN_LIMIT) break;
                }
            }
            if (warp == 0) STAMP(28);
        }
        {
            const float ga = bf_hi(g0), gb = bf_hi(g1);
            const float ha = bf_round(1.0f - ga), hb = bf_round(1.0f - gb);
            float yb[32];
#pragma unroll
            for (int nt = 0; nt < 8; nt++) {
                yb[4 * nt] = ha * bf_lo(yv[nt].x); yb[4 * nt + 1] = ha * bf_hi(yv[nt].x);
                yb[4 * nt + 2] = hb * bf_lo(yv[nt].y); yb[4 * nt + 3] = hb * bf_hi(yv[nt].y);
            }
            fence_regs<32>(yb);
            const uint32_t xw = sb + wg * 2 * SLOT + (tid & 127) * 16, xr = sb + (wg ^ 1) * 2 * SLOT + (tid & 127) * 16;
            wg_wait<0>();
            fence_regs<64>(oc);
            bar_named(3 + wg, 128);
#pragma unroll
            for (int r = 0; r < 8; r++)
                sts128(xw + r * 2048, __float_as_uint(oc[32 + 4 * r]), __float_as_uint(oc[33 + 4 * r]), __float_as_uint(oc[34 + 4 * r]), __float_as_uint(oc[35 + 4 * r]));
#pragma unroll
            for (int r = 0; r < 32; r++) yb[r] = fmaf((r & 2) ? gb : ga, oc[r], yb[r]);
            bar_named(1, 256);
            if (warp == 0) STAMP(8);
            uint32_t w[8][2];
#pragma unroll
            for (int nt = 0; nt < 8; nt++) {
                const uint4 p = lds128(xr + nt * 2048);
                w[nt][0] = pack2(fmaf(ga, __uint_as_float(p.x), yb[4 * nt]), fmaf(ga, __uint_as_float(p.y), yb[4 * nt + 1]));
                w[nt][1] = pack2(fmaf(gb, __uint_as_float(p.z), yb[4 * nt + 2]), fmaf(gb, __uint_as_float(p.w), yb[4 * nt + 3]));
            }
            const uint32_t ob = sb + wg * 2 * SLOT + 16384 + w4 * 2048;
#pragma unroll
            for (int nt = 0; nt < 8; nt += 2)
                stsm4(ob + (lane & 15) * 128 + (((nt + shi) ^ (lane & 7)) << 4), w[nt][0], w[nt][1], w[nt + 1][0], w[nt + 1][1]);
            __syncwarp();
            bf16* op = out + (size_t)(slab * 16) * 512 + (bi_j & 3) * 128 + wg * 64 + (lane & 7) * 8;
#pragma unroll
            for (int it = 0; it < 4; it++) {
                const int r = it * 4 + (lane >> 3);
                uint4 v = lds128(ob + r * 128 + (((lane & 7) ^ (r & 7)) << 4));
                *(uint4*)(op + r * 512) = v;
            }
        }
        if (warp == 0) STAMP(10);
    } else if (warp < 12) {
#pragma unroll
        for (int src = 2; src >= 0; src--) {
            if (src != 0) mbar_wait(bar + 8 * (src == 2 ? BAR_KGA : BAR_KG), 0);
#pragma unroll
            for (int t = 0; t < 6; t++) {
                const uint4 v = lds128(stg_of(w4 + src * 4) + (t * 32 + lane) * 16);
                kc[4 * t] += __uint_as_float(v.x); kc[4 * t + 1] += __uint_as_float(v.y); kc[4 * t + 2] += __uint_as_float(v.z); kc[4 * t + 3] += __uint_as_float(v.w);
            }
            if (src != 1) {
                bar_named(2, 128);
                if (st == 0) { load_stage(src == 2 ? 2 : 3); if (src == 0) mbar_arrive(bar + 8 * BAR_SP); }
                if (warp == 8) STAMP(src == 2 ? 22 : 17);
            }
        }
        if (warp == 8) {
#pragma unroll 1
            for (int kb = 0; kb < 6; kb++) {
                const int s = kb & 3;
                mbar_wait(bar + 8 * (BAR_EMPTY + s), kb >> 2);
                if (kb == xkb) mbar_wait(bar + 8 * BAR_XT, 0);
                if (lane == 0) {
                    STAMP(48 + kb);
                    if (kb < 4) load_stage(kb + 4);
                    else {
                        mbar_expect(bar + 8 * BAR_WO, 32768);
                        tma2d(sb + s * SLOT, &mwo, (bi_j & 3) * 128 + s * 64, 0, bar + 8 * BAR_WO);
                        if (kb == 5) mbar_arrive(bar + 8 * BAR_SP2);
                    }
                }
                __syncwarp();
            }
        } else if (warp == 9) {
            const int row = bi_j * 16 + (lane >> 1), half = lane & 1;
            unsigned* gp = scr->g + (bi_i * 64 + bi_j * 8) * 8 + lane * 2;
            st_rlx64(gp, tag ^ 1u, tag ^ 1u);
            if (lane < 8) st_rlx32(scr->yflag + bi * 8 + lane, tag ^ 1u);
            float gs0 = 0.f, gs1 = 0.f;
            mbar_wait(bar + 8 * BAR_WPHI, 0);
#pragma unroll 1
            for (int kb = 0; kb < 8; kb++) {
                const int s = kb & 3;
                mbar_wait(bar + 8 * (BAR_FULL + s), kb >> 2);
#pragma unroll
                for (int c = 0; c < 4; c++) {
                    const uint4 xv = lds128(sb + s * SLOT + row * 128 + (((half * 4 + c) ^ (row & 7)) << 4));
                    const uint4 gw = lds128(sb + OFF_GW + ((kb + rot) & 7) * 128 + half * 64 + c * 16);
                    const uint32_t p0 = hmul2(xv.x, gw.x), p1 = hmul2(xv.y, gw.y), p2 = hmul2(xv.z, gw.z), p3 = hmul2(xv.w, gw.w);
                    gs0 += (bf_lo(p0) + bf_lo(p1)) + (bf_lo(p2) + bf_lo(p3));
                    gs1 += (bf_hi(p0) + bf_hi(p1)) + (bf_hi(p2) + bf_hi(p3));
                }
                asm volatile("" : "+f"(gs0), "+f"(gs1));
                __syncwarp();
                if (lane == 0) mbar_arrive(bar + 8 * (kb < 7 ? BAR_EMPTY + s : BAR_DONE));
            }
            float gs = gs0 + gs1;
            gs += __shfl_xor_sync(~0u, gs, 1);
            const uint32_t gv = __float_as_uint(bf_round(rcp(1.0f + ex2(-1.4426950408889634f * bf_round(gs))))) | tag;
            st_rlx64(gp, gv, gv);
        }
        if (lane == 0) kc[4 * 0 + 0] += ((ch & 1) ? bf_hi(pds) : bf_lo(pds));
        const uint32_t k1024 = __shfl_sync(~0u, pack2(kc[4 * 4 + 0], 0.f), 0);
#pragma unroll
        for (int i = 0; i < 2; i++) {
            const int be = g + 8 * i;
#pragma unroll
            for (int t = 0; t < 2; t++) {
                const uint32_t a = kb_ + (KW_D + 128 * t + 8 * be + 2 * q) * 4;
                const uint32_t w = pack2(kc[4 * t + 2 * i + 1], kc[4 * t + 2 * i]);
                sts32(a + 4, w); sts16(a, w >> 16); sts16(a + 10, w);
            }
            {
                const int p = 256 + 128 * (q >> 1) + 8 * be + 4 * (q & 1);
                const uint32_t a = kb_ + (KW_D + p) * 4;
                const uint32_t w = pack2(kc[4 * 2 + 2 * i + 1], kc[4 * 2 + 2 * i]);
                const uint32_t aa = (w >> 16) | (w & 0xffff0000u);
                if (p != 256) { sts16(a - 4, aa); sts32(a, aa); } else sts16(a, aa);
                sts32(a + 4, aa); sts32(a + 8, w); sts16(a + 14, w);
            }
            {
                const int k = 64 + 16 * q + be;
                const uint32_t w = pack2(kc[4 * 3 + 2 * i], kc[4 * 3 + 2 * i + 1]);
                if (k != 64) sts16(kb_ + (KW_2 + ((k - 1) >> 1) - 24) * 4 + (k & 1) * 2, w);
                else {
                    const uint32_t a = kb_ + (KW_D + 511) * 4, aa = (w << 16) | (w & 0xffffu);
                    sts16(a, w); sts32(a + 4, aa); sts32(a + 8, aa); sts32(a + 12, aa); sts16(a + 18, w);
                }
                sts16(kb_ + (KW_2 + 48 + (k >> 1) - 24) * 4 + ((k & 1) ^ 1) * 2, w >> 16);
            }
#pragma unroll
            for (int b = 0; b < 2; b++) {
                const int k = 64 + 8 * (2 * q + b) + (be >> 1);
                const uint32_t w = pack2(kc[4 * 4 + 2 * i + b], 0.f);
                if (!(be & 1) && k == 64) sts16(kb_ + (KW_2 + 63 - 24) * 4, w);
                else {
                    const uint32_t a = kb_ + (KW_3 + ((be & 1) ? 80 + k : k - 1) - 48) * 4;
                    sts16(a, w);
                    if (!((be & 1) && k == 127)) sts16(a + 6, w);
                }
            }
        }
        if (lane == 0) sts16(kb_ + (KW_3 + 127 - 48) * 4, pack2(kc[4 * 5 + 0], 0.f));
        __syncwarp();
        asm volatile("setmaxnreg.inc.sync.aligned.u32 136;");
        mbar_wait(bar + 8 * BAR_UR, 0);
        mbar_wait(bar + 8 * BAR_DONE, 0);
        if (warp == 8) STAMP(23);
        float y[16][4];
#pragma unroll
        for (int nt = 0; nt < 16; nt++) { y[nt][0] = y[nt][1] = y[nt][2] = y[nt][3] = 0.f; }
        {
            uint32_t Bp[32], A[4][3], An[4][3];
            auto uaddr = [&](int rho) { const int R0 = (lane >> 4) * 64 + (lane & 7) - rho; return ub + (((2 * R0 + ((lane >> 3) & 1)) ^ ((R0 >> 2) & 1)) << 4); };
            const uint32_t kd = kb_ + (KW_D + g - 2 * q) * 4;
#pragma unroll 1
            for (int rho = 1; rho >= 0; rho--) {
                const uint32_t a = uaddr(rho), k = kd + 2048 + rho * 64;
#pragma unroll
                for (int i = 0; i < 8; i++) ldsm4(Bp + 4 * i, a + i * 256);
                const uint32_t a0 = lds32(k), a1 = lds32(k + 32), a2 = lds32(k - 32);
#pragma unroll
                for (int i = 0; i < 12; i++) mma16816(y[i + 4], a0, a1, a2, a0, Bp[4 * (i & 7) + 2 * (i >> 3)], Bp[4 * (i & 7) + 2 * (i >> 3) + 1]);
            }
#pragma unroll
            for (int ga = 0; ga < 4; ga++) { An[ga][0] = lds32(kd + ga * 512); An[ga][1] = lds32(kd + ga * 512 + 32); An[ga][2] = lds32(kd + ga * 512 - 32); }
#pragma unroll 1
            for (int rho = 0; rho < 8; rho++) {
#pragma unroll
                for (int ga = 0; ga < 4; ga++) {
                    const uint32_t a = kd + (rho + 1) * 64 + ga * 512;
                    A[ga][0] = An[ga][0]; A[ga][1] = An[ga][1]; A[ga][2] = An[ga][2];
                    An[ga][0] = lds32(a); An[ga][1] = lds32(a + 32); An[ga][2] = lds32(a - 32);
                }
                const uint32_t an = uaddr(rho + 1);
#pragma unroll
                for (int i = 0; i < 8; i++) {
#pragma unroll
                    for (int ga = 0; ga < 4; ga++) {
                        mma16816(y[i + ga], A[ga][0], A[ga][1], A[ga][2], A[ga][0], Bp[4 * i], Bp[4 * i + 1]);
                        if (i + 8 + ga < 16) mma16816(y[i + 8 + ga], A[ga][0], A[ga][1], A[ga][2], A[ga][0], Bp[4 * i + 2], Bp[4 * i + 3]);
                    }
                    ldsm4(Bp + 4 * i, an + i * 256);
                    __syncwarp();
                }
            }
        }
        if (warp == 8) STAMP(18);
        mbar_wait(bar + 8 * BAR_WR, 0);
#pragma unroll 1
        for (int ph = 0; ph < 2; ph++) {
            uint32_t B[5][2];
            const uint32_t ka = kb_ + (KW_2 + ph * 48 + 8 + g - q) * 4;
#pragma unroll
            for (int dd = 0; dd < 5; dd++) { B[dd][0] = lds32(ka + dd * 32); B[dd][1] = lds32(ka + dd * 32 - 16); }
            const uint32_t wa = buf + ph * W3_OFF + ((lane & 7) + ((lane >> 3) & 1) + (lane >> 4) * 8) * 16;
#pragma unroll
            for (int s = 0; s < 12; s++) {
                uint32_t A[4];
                ldsm4t(A, wa + s * 256);
#pragma unroll
                for (int dd = 0; dd < 5; dd++)
                    if (s + 4 + dd < 16) mma16816(y[s + 4 + dd], A[0], A[1], A[2], A[3], B[dd][0], B[dd][1]);
            }
        }
        {
            const int ap = (lane & 7) + (lane >> 4) * 8;
            const uint32_t loff = ((2 * ap + ((lane >> 3) & 1)) ^ ((ap >> 2) & 1)) << 4;
#pragma unroll 1
            for (int ph = 0; ph < 2; ph++) {
                uint32_t B[8][2];
                const uint32_t wb = (ph ? spare : buf + W9_OFF) + loff;
                const uint32_t ka = kb_ + (KW_3 + ph * 80 + 16 + g - 2 * q) * 4;
#pragma unroll
                for (int dd = 0; dd < 8; dd++) { B[dd][0] = lds32(ka + dd * 32); B[dd][1] = lds32(ka + dd * 32 - 32); }
#pragma unroll
                for (int s = 0; s < 4; s++) {
                    uint32_t A[4];
                    ldsm4t(A, wb + s * 512);
#pragma unroll
                    for (int dd = 0; dd < 8; dd++)
                        if (8 + 2 * s + dd < 16) mma16816(y[8 + 2 * s + dd], A[0], A[1], A[2], A[3], B[dd][0], B[dd][1]);
                }
            }
            const uint32_t idw = (g == 2 * q) ? k1024 : ((g == 2 * q + 1) ? (k1024 << 16) : 0u);
#pragma unroll
            for (int s = 0; s < 4; s++) {
                uint32_t A[4];
                ldsm4t(A, spare + 2048 + loff + s * 512);
                mma16816(y[8 + 2 * s], A[0], A[1], A[2], A[3], idw, 0u);
                mma16816(y[9 + 2 * s], A[0], A[1], A[2], A[3], 0u, idw);
            }
        }
        __syncwarp();
        if (warp == 8) STAMP(19);
#pragma unroll
        for (int nt = 0; nt < 16; nt++)
#pragma unroll
            for (int b = 0; b < 2; b++) sts32(buf + ((8 * nt + 2 * q + b) * 8 + g) * 4, pack2(y[nt][b], y[nt][2 + b]));
        bar_named(2, 128);
        uint4* yp = scr->y + bi * 1024 + st;
#pragma unroll
        for (int v = 0; v < 8; v++) {
            const uint32_t a = sb + OFF_BUF + (st + 128 * v) * 4;
            const uint32_t w0 = lds32(a), w1 = lds32(a + BUF_STRIDE), w2 = lds32(a + 2 * BUF_STRIDE), w3 = lds32(a + 3 * BUF_STRIDE);
            st_rlx128(yp + v * 128, tag4(__byte_perm(w0, w1, 0x5410), __byte_perm(w0, w1, 0x7632), __byte_perm(w2, w3, 0x5410), __byte_perm(w2, w3, 0x7632), tag));
        }
        if (st < 8) st_rlx32(scr->yflag + bi * 8 + st, tag);
        if (warp == 8) STAMP(20);
    } else {
        asm volatile("setmaxnreg.dec.sync.aligned.u32 56;");
        const int qq = (bi_i & 2) + ((lane >> 1) & 1);
        uint2* kvf_h = (uint2*)(scr->kvf + (bi_j * 4 + (bi_i >> 2)) * 68);
        auto windows = [&](int rhi, int rlo) {
#pragma unroll 1
            for (int rho = rhi; rho >= rlo; rho--) {
                const int ci = lane + 32 * rho;
                uint4 e4[4];
#pragma unroll
                for (int v = 0; v < 4; v++) { const int cc = ci - 3 + v; e4[v] = lds128(ub + ((cc ^ ((cc >> 3) & 1)) << 4)); }
                float S[29];
                const uint32_t* ew = (const uint32_t*)e4;
                S[3] = 0.f;
#pragma unroll
                for (int k = 4; k <= 28; k++) S[k] = S[k - 1] + ((k & 1) ? bf_hi(ew[k >> 1]) : bf_lo(ew[k >> 1]));
                auto win = [&](int lo, int hi, uint32_t a) {
                    sts128(a, pack2(S[hi] - S[lo - 1], S[hi + 1] - S[lo]), pack2(S[hi + 2] - S[lo + 1], S[hi + 3] - S[lo + 2]),
                           pack2(S[hi + 4] - S[lo + 3], S[hi + 5] - S[lo + 4]), pack2(S[hi + 6] - S[lo + 5], S[hi + 7] - S[lo + 6]));
                };
                win(14, 18, buf + W5_OFF + 16 + ci * 16); win(19, 21, buf + W3_OFF + 16 + ci * 16);
                if (rho < 4) {
                    const uint32_t sw = (ci ^ ((ci >> 3) & 1)) << 4;
                    win(4, 12, buf + W9_OFF + sw); win(13, 19, spare + sw); win(20, 21, spare + 2048 + sw);
                }
            }
        };
        {
            mbar_wait(bar + 8 * (BAR_FULL + xkb), 0);
#pragma unroll 1
            for (int hf = 0; hf < 2; hf++) {
                const int r = w4 * 32 + hf * 16 + (lane & 15);
                uint32_t* xt = (uint32_t*)scr->xt + ((xkb + rot) * 16 + (g >> 2)) * 4096 + (bi_i * 16 + w4 * 4 + hf * 2) * 16 + (g & 3) * 4 + q;
#pragma unroll
                for (int cb = 0; cb < 8; cb += 2) {
                    uint32_t v[4];
                    ldsm4t(v, sb + xkb * SLOT + r * 128 + (((cb + (lane >> 4)) ^ (r & 7)) << 4));
                    xt[cb * 8192] = v[0]; xt[cb * 8192 + 16] = v[1]; xt[cb * 8192 + 8192] = v[2]; xt[cb * 8192 + 8192 + 16] = v[3];
                }
            }
            __syncwarp();
            if (lane == 0) {
                mbar_arrive(bar + 8 * BAR_XT);
                STAMP(26);
                asm volatile("red.release.gpu.global.add.u32 [%0],2;" ::"l"(scr->xcnt + (xkb + rot) * 32) : "memory");
                STAMP(27);
            }
            __syncwarp();
            {
                const uint32_t old = tag ^ 1u;
                const uint4 z4 = make_uint4(old, 0, old, 0);
#pragma unroll
                for (int v = 0; v < 5; v++) if (v < 4 || st < 32) st_rlx128(scr->kvp + bi * 544 + v * 128 + st, z4);
                if (st < 16) st_rlx128(scr->o + ((bi_i * 8 + (st >> 1)) * 32 + bi_j * 4 + 3) * 32 + 30 + (st & 1), z4);
                if (lane < 8) st_rlx64(kvf_h + ((bi_i & 3) * 8 + w4 * 2 + (lane & 1)) * 4 + (lane >> 1), old, 0);
                if (st < 4 && !(bi_i & 1)) st_rlx64(kvf_h + (64 + qq) * 2 + (lane & 1), old, 0);
                __syncwarp();
                if (lane == 0) mbar_arrive(bar + 8 * BAR_PREP);
            }
            int n = 0;
#pragma unroll 1
            while (__any_sync(~0u, (int)(ld_acq(scr->xcnt + bi_j * 32) - (epoch1 << 7)) < 0)) { if (++n > SPIN_LIMIT) break; }
            if (warp == 12) STAMP(15);
            uint4 ur[8];
#pragma unroll
            for (int v = 0; v < 8; v++) ur[v] = __ldcg(scr->xt + bi * 1024 + st + 128 * v);
            mbar_wait(bar + 8 * BAR_SP, 0);
            if (lane < 16) sts128(ub - 256 + lane * 16, 0, 0, 0, 0);
            if (lane < 2) sts128(buf + lane * W3_OFF, 0, 0, 0, 0);
#pragma unroll
            for (int v = 0; v < 8; v++) {
                const int ci = (st >> 2) + 32 * v;
                sts128(sb + OFF_U + (st & 3) * U_STRIDE + 256 + ((ci ^ ((ci >> 3) & 1)) << 4), ur[v].x, ur[v].y, ur[v].z, ur[v].w);
            }
            __syncwarp();
            if (lane == 0) mbar_arrive(bar + 8 * BAR_UR);
            mbar_wait(bar + 8 * BAR_UR, 0);
            if (warp == 12) STAMP(16);
            windows(5, 4);
        }
        mbar_wait(bar + 8 * BAR_SP2, 0);
        windows(3, 0);
        __syncwarp();
        if (lane == 0) mbar_arrive(bar + 8 * BAR_WR);
        if (warp == 12) STAMP(24);
        {
            const bool zw = st < 32 && !(bi_i & 1);
            const uint4* src = scr->kvp + bi_j * (16 * 544) + (bi_i >> 2) * 136;
            const uint4* zsrc = src + (lane >> 2) * (2 * 544) + 128 + (lane & 1) * 4 + qq;
            src += (lane >> 3) * (4 * 544) + ((lane >> 1) & 3) * 32 + (bi_i & 3) * 8 + w4 * 2 + (lane & 1);
            mbar_wait(bar + 8 * BAR_PUB, 0);
            if (warp == 12) STAMP(12);
            uint4 v[6];
#pragma unroll
            for (int k = 0; k < 6; k++) v[k] = make_uint4(tag ^ 1u, 0, 0, 0);
            int n = 0;
#pragma unroll 1
            while (true) {
#pragma unroll
                for (int k = 0; k < 6; k++) if ((bad4(v[k], tag) & 1) && (k < 4 || zw)) v[k] = ld_rlx128(k < 4 ? src + k * 544 : zsrc + (k - 4) * 544);
                if (!__any_sync(~0u, (bad4(v[0], tag) | bad4(v[1], tag) | bad4(v[2], tag) | bad4(v[3], tag) | (zw ? bad4(v[4], tag) | bad4(v[5], tag) : 0u)) & 1)) break;
                if (++n > SPIN_LIMIT) break;
            }
            if (warp == 12) STAMP(30);
            float f[8];
            const float* vf = (const float*)v;
#pragma unroll
            for (int r = 0; r < 4; r++) {
                f[r] = (vf[r] + vf[4 + r]) + (vf[8 + r] + vf[12 + r]);
                f[4 + r] = vf[16 + r] + vf[20 + r];
                f[4 + r] += __shfl_xor_sync(~0u, f[4 + r], 4);
            }
#pragma unroll
            for (int o = 8; o <= 16; o <<= 1)
#pragma unroll
                for (int r = 0; r < 8; r++) f[r] += __shfl_xor_sync(~0u, f[r], o);
            if (lane < 8) st_rlx64(kvf_h + ((bi_i & 3) * 8 + w4 * 2 + (lane & 1)) * 4 + (lane >> 1), tagw(pack2(f[0], f[1]), tag), pack2(f[2], f[3]));
            if (zw && lane < 4) st_rlx64(kvf_h + (64 + qq) * 2 + (lane & 1), tagw(pack2(f[4], f[5]), tag), pack2(f[6], f[7]));
        }
        if (warp == 12) STAMP(13);
        {
            const uint4* kp = scr->kvf + bi_j * 272 + st;
            uint4 v0 = make_uint4(tag ^ 1u, 0, 0, 0), v1 = v0, v2 = make_uint4(st < 16 ? tag ^ 1u : tag, 0, tag, 0);
            int n = 0;
#pragma unroll 1
            while (true) {
                if (bad4(v0, tag) & 1) v0 = ld_rlx128(kp);
                if (bad4(v1, tag) & 1) v1 = ld_rlx128(kp + 128);
                if (bad4(v2, tag) & 1) v2 = ld_rlx128(kp + 256);
                if (!__any_sync(~0u, (bad4(v0, tag) | bad4(v1, tag) | bad4(v2, tag)) & 1)) break;
                if (++n > SPIN_LIMIT) break;
            }
            sts128(sb + OFF_KVF + st * 16, v0.x, v0.y, v0.z, v0.w);
            sts128(sb + OFF_KVF + 2048 + st * 16, v1.x, v1.y, v1.z, v1.w);
            if (st < 16) sts128(sb + OFF_KVF + 4096 + st * 16, v2.x, v2.y, v2.z, v2.w);
            __syncwarp();
            if (lane == 0) mbar_arrive(bar + 8 * BAR_KVF);
        }
        if (warp == 13) {
            mbar_wait(bar + 8 * BAR_KVF, 0);
            if (lane == 0) {
                mbar_expect(bar + 8 * BAR_WO2, 65536);
                tma2d(sb + OFF_P, &mwo, (bi_j & 3) * 128 + 64, 256, bar + 8 * BAR_WO2);
                tma2d(sb + OFF_V, &mwo, (bi_j & 3) * 128, 256, bar + 8 * BAR_WO2);
            }
        }
        if (warp == 12) STAMP(25);
    }
    __syncwarp();
    if (lane == 0) {
        unsigned old;
        asm volatile("atom.acq_rel.cta.shared.add.u32 %0,[%1],1;" : "=r"(old) : "r"(bar + OFF_CNT) : "memory");
        if (old == 15) {
            atomicAdd(scr->done, 1u);
        }
    }
}

typedef CUresult (*EncFn)(CUtensorMap*, CUtensorMapDataType, cuuint32_t, void*, const cuuint64_t*, const cuuint64_t*, const cuuint32_t*,
                          const cuuint32_t*, CUtensorMapInterleave, CUtensorMapSwizzle, CUtensorMapL2promotion, CUtensorMapFloatOOBfill);

extern "C" void kernel_launch(void* const* d_in, const int* in_sizes, int n_in, void* d_out, int out_size) {
    static EncFn enc = nullptr;
    static Scratch* scr = nullptr;
    if (!enc) {
        cudaGetSymbolAddress((void**)&scr, g_scr);
        cudaDriverEntryPointQueryResult qr;
        cudaGetDriverEntryPoint("cuTensorMapEncodeTiled", (void**)&enc, cudaEnableDefault, &qr);
        cudaFuncSetAttribute(fused_kernel, cudaFuncAttributeMaxDynamicSharedMemorySize, SMEM_BYTES);
    }
    CUtensorMap mx, mw, mwo;
    const cuuint32_t es[3] = {1, 1, 1};
    {
        cuuint64_t d[2] = {512, 2048}, s[1] = {1024}; cuuint32_t b[2] = {64, 128};
        enc(&mx, CU_TENSOR_MAP_DATA_TYPE_BFLOAT16, 2, d_in[0], d, s, b, es, CU_TENSOR_MAP_INTERLEAVE_NONE, CU_TENSOR_MAP_SWIZZLE_128B,
            CU_TENSOR_MAP_L2_PROMOTION_L2_128B, CU_TENSOR_MAP_FLOAT_OOB_FILL_NONE);
    }
    {
        cuuint64_t d[3] = {512, 512, 3}, s[2] = {3072, 1024}; cuuint32_t b[3] = {64, 64, 3};
        enc(&mw, CU_TENSOR_MAP_DATA_TYPE_BFLOAT16, 3, d_in[1], d, s, b, es, CU_TENSOR_MAP_INTERLEAVE_NONE, CU_TENSOR_MAP_SWIZZLE_128B,
            CU_TENSOR_MAP_L2_PROMOTION_L2_128B, CU_TENSOR_MAP_FLOAT_OOB_FILL_NONE);
    }
    {
        cuuint64_t d[2] = {512, 512}, s[1] = {1024}; cuuint32_t b[2] = {64, 256};
        enc(&mwo, CU_TENSOR_MAP_DATA_TYPE_BFLOAT16, 2, d_in[3], d, s, b, es, CU_TENSOR_MAP_INTERLEAVE_NONE, CU_TENSOR_MAP_SWIZZLE_128B,
            CU_TENSOR_MAP_L2_PROMOTION_L2_128B, CU_TENSOR_MAP_FLOAT_OOB_FILL_NONE);
    }
    fused_kernel<<<128, 512, SMEM_BYTES, cudaStreamPerThread>>>(
        scr, (const bf16*)d_in[5], (const bf16*)d_in[6], (const bf16*)d_in[7], (const bf16*)d_in[8], (const bf16*)d_in[9],
        (const bf16*)d_in[10], (const bf16*)d_in[2], (const bf16*)d_in[11], (bf16*)d_out, mx, mw, mwo);
}
```

```cpp
#include <cuda_runtime.h>
#include <cuda.h>
#include <cuda_bf16.h>
#include <stdint.h>

typedef __nv_bfloat16 bf16;

struct Scratch {
    uint4 xt[128 * 1024];
    uint4 o[16 * 8 * 32 * 32];
    uint4 y[128 * 1024];
    uint4 kvp[8 * 16 * 544];
    uint4 kvf[8 * 4 * 68];
    unsigned g[1024 * 8];
    unsigned yflag[128 * 8];
    unsigned xcnt[8 * 32];
    unsigned done[32];
};
__device__ Scratch g_scr;

constexpr int SLOT = 40960;
constexpr int OFF_SP0 = 32768, OFF_SP1 = SLOT + 32768;
constexpr int OFF_P = 2 * SLOT, OFF_V = OFF_P + 32768;
constexpr int OFF_KVF = OFF_V + 32768;
constexpr int KT_BYTES = 3264, KW_D = 16, KW_2 = 560, KW_3 = 656;
constexpr int OFF_U = 4 * SLOT, U_STRIDE = 4096 + 256 + 32;
constexpr int OFF_BUF = OFF_U + 4 * U_STRIDE, BUF_STRIDE = 8320;
constexpr int OFF_K = OFF_BUF + 4 * BUF_STRIDE;
constexpr int OFF_WPHI = OFF_K + 4 * KT_BYTES;
constexpr int OFF_GW = OFF_WPHI + 2048;
constexpr int OFF_BAR = OFF_GW + 1024;
constexpr int SMEM_BYTES = OFF_BAR + 256;
static_assert(SMEM_BYTES <= 232448 && OFF_BUF % 128 == 0, "smem");
constexpr int W5_OFF = 0, W3_OFF = 3088, W9_OFF = 6176;
constexpr int BAR_FULL = 0, BAR_EMPTY = 4, BAR_WPHI = 8, BAR_WO = 9, BAR_WO2 = 10, BAR_XT = 11, BAR_DONE = 12, BAR_KG = 13, BAR_SP = 14,
              BAR_PUB = 15, BAR_KVF = 16, BAR_UR = 17, BAR_WR = 18, BAR_PREP = 19, BAR_KGA = 20, BAR_SP2 = 21, OFF_CNT = 192;
constexpr int SPIN_LIMIT = 1 << 17;

__device__ __forceinline__ uint32_t s2u(const void* p) { return (uint32_t)__cvta_generic_to_shared(p); }
__device__ __forceinline__ void mbar_init(uint32_t b, int c) { asm volatile("mbarrier.init.shared::cta.b64 [%0],%1;" ::"r"(b), "r"(c) : "memory"); }
__device__ __forceinline__ void mbar_expect(uint32_t b, int bytes) { asm volatile("mbarrier.arrive.expect_tx.shared::cta.b64 _,[%0],%1;" ::"r"(b), "r"(bytes) : "memory"); }
__device__ __forceinline__ void mbar_arrive(uint32_t b) { asm volatile("mbarrier.arrive.shared::cta.b64 _,[%0];" ::"r"(b) : "memory"); }
__device__ __forceinline__ void mbar_wait(uint32_t b, int ph) {
    asm volatile("{\n.reg .pred p;\n.reg .u32 n;\nmov.u32 n,0;\nLW_%=:\nmbarrier.try_wait.parity.shared::cta.b64 p,[%0],%1;\n@p bra LD_%=;\n"
                 "add.u32 n,n,1;\nsetp.lt.u32 p,n,16384;\n@p bra LW_%=;\nLD_%=:\n}" ::"r"(b), "r"(ph) : "memory");
}
__device__ __forceinline__ void tma2d(uint32_t dst, const CUtensorMap* m, int c0, int c1, uint32_t bar) {
    asm volatile("cp.async.bulk.tensor.2d.shared::cluster.global.mbarrier::complete_tx::bytes [%0],[%1,{%3,%4}],[%2];" ::"r"(dst), "l"(m), "r"(bar), "r"(c0), "r"(c1) : "memory");
}
__device__ __forceinline__ void tma3d(uint32_t dst, const CUtensorMap* m, int c0, int c1, int c2, uint32_t bar) {
    asm volatile("cp.async.bulk.tensor.3d.shared::cluster.global.mbarrier::complete_tx::bytes [%0],[%1,{%3,%4,%5}],[%2];" ::"r"(dst), "l"(m), "r"(bar), "r"(c0), "r"(c1), "r"(c2) : "memory");
}
__device__ __forceinline__ void bulk_g2s(uint32_t dst, const void* src, int bytes, uint32_t bar) {
    asm volatile("cp.async.bulk.shared::cluster.global.mbarrier::complete_tx::bytes [%0],[%1],%2,[%3];" ::"r"(dst), "l"(src), "r"(bytes), "r"(bar) : "memory");
}
__device__ __forceinline__ uint64_t mkdesc(uint32_t addr, uint32_t lbo, uint32_t sbo) {
    return (uint64_t)((addr & 0x3FFFF) >> 4) | ((uint64_t)(lbo >> 4) << 16) | ((uint64_t)(sbo >> 4) << 32) | ((uint64_t)1 << 62);
}
__device__ __forceinline__ void wg_fence() { asm volatile("wgmma.fence.sync.aligned;" ::: "memory"); }
__device__ __forceinline__ void wg_commit() { asm volatile("wgmma.commit_group.sync.aligned;" ::: "memory"); }
template <int N> __device__ __forceinline__ void wg_wait() { asm volatile("wgmma.wait_group.sync.aligned %0;" ::"n"(N) : "memory"); }
template <int N> __device__ __forceinline__ void fence_regs(float* d) {
#pragma unroll
    for (int i = 0; i < N; i++) asm volatile("" : "+f"(d[i])::"memory");
}
#define R8(d, o) "+f"(d[o]), "+f"(d[o + 1]), "+f"(d[o + 2]), "+f"(d[o + 3]), "+f"(d[o + 4]), "+f"(d[o + 5]), "+f"(d[o + 6]), "+f"(d[o + 7])
__device__ __forceinline__ void wgmma192(float* d, uint64_t da, uint64_t db, int sc) {
    asm volatile("{.reg .pred p; setp.ne.b32 p,%98,0; wgmma.mma_async.sync.aligned.m64n192k16.f32.bf16.bf16 {"
                 "%0,%1,%2,%3,%4,%5,%6,%7,%8,%9,%10,%11,%12,%13,%14,%15,%16,%17,%18,%19,%20,%21,%22,%23,%24,%25,%26,%27,%28,%29,%30,%31,"
                 "%32,%33,%34,%35,%36,%37,%38,%39,%40,%41,%42,%43,%44,%45,%46,%47,%48,%49,%50,%51,%52,%53,%54,%55,%56,%57,%58,%59,%60,%61,%62,%63,"
                 "%64,%65,%66,%67,%68,%69,%70,%71,%72,%73,%74,%75,%76,%77,%78,%79,%80,%81,%82,%83,%84,%85,%86,%87,%88,%89,%90,%91,%92,%93,%94,%95},"
                 "%96,%97,p,1,1,0,1;}"
                 : R8(d, 0), R8(d, 8), R8(d, 16), R8(d, 24), R8(d, 32), R8(d, 40), R8(d, 48), R8(d, 56), R8(d, 64), R8(d, 72), R8(d, 80), R8(d, 88)
                 : "l"(da), "l"(db), "r"(sc));
}
__device__ __forceinline__ void wgmma64_tt(float* d, uint64_t da, uint64_t db, int sc) {
    asm volatile("{.reg .pred p; setp.ne.b32 p,%34,0; wgmma.mma_async.sync.aligned.m64n64k16.f32.bf16.bf16 {"
                 "%0,%1,%2,%3,%4,%5,%6,%7,%8,%9,%10,%11,%12,%13,%14,%15,%16,%17,%18,%19,%20,%21,%22,%23,%24,%25,%26,%27,%28,%29,%30,%31},"
                 "%32,%33,p,1,1,1,1;}"
                 : R8(d, 0), R8(d, 8), R8(d, 16), R8(d, 24)
                 : "l"(da), "l"(db), "r"(sc));
}
__device__ __forceinline__ void wgmma128_rs(float* d, const uint4& a, uint64_t db, int sc) {
    asm volatile("{.reg .pred p; setp.ne.b32 p,%69,0; wgmma.mma_async.sync.aligned.m64n128k16.f32.bf16.bf16 {"
                 "%0,%1,%2,%3,%4,%5,%6,%7,%8,%9,%10,%11,%12,%13,%14,%15,%16,%17,%18,%19,%20,%21,%22,%23,%24,%25,%26,%27,%28,%29,%30,%31,"
                 "%32,%33,%34,%35,%36,%37,%38,%39,%40,%41,%42,%43,%44,%45,%46,%47,%48,%49,%50,%51,%52,%53,%54,%55,%56,%57,%58,%59,%60,%61,%62,%63},"
                 "{%64,%65,%66,%67},%68,p,1,1,1;}"
                 : R8(d, 0), R8(d, 8), R8(d, 16), R8(d, 24), R8(d, 32), R8(d, 40), R8(d, 48), R8(d, 56)
                 : "r"(a.x), "r"(a.y), "r"(a.z), "r"(a.w), "l"(db), "r"(sc));
}
__device__ __forceinline__ void mma16816(float* c, uint32_t a0, uint32_t a1, uint32_t a2, uint32_t a3, uint32_t b0, uint32_t b1) {
    asm("mma.sync.aligned.m16n8k16.row.col.f32.bf16.bf16.f32 {%0,%1,%2,%3},{%4,%5,%6,%7},{%8,%9},{%0,%1,%2,%3};"
        : "+f"(c[0]), "+f"(c[1]), "+f"(c[2]), "+f"(c[3]) : "r"(a0), "r"(a1), "r"(a2), "r"(a3), "r"(b0), "r"(b1));
}
__device__ __forceinline__ void ldsm4(uint32_t* r, uint32_t a) {
    asm volatile("ldmatrix.sync.aligned.m8n8.x4.shared.b16 {%0,%1,%2,%3},[%4];" : "=r"(r[0]), "=r"(r[1]), "=r"(r[2]), "=r"(r[3]) : "r"(a) : "memory");
}
__device__ __forceinline__ void ldsm4t(uint32_t* r, uint32_t a) {
    asm volatile("ldmatrix.sync.aligned.m8n8.x4.trans.shared.b16 {%0,%1,%2,%3},[%4];" : "=r"(r[0]), "=r"(r[1]), "=r"(r[2]), "=r"(r[3]) : "r"(a) : "memory");
}
__device__ __forceinline__ void stsm4(uint32_t a, uint32_t r0, uint32_t r1, uint32_t r2, uint32_t r3) {
    asm volatile("stmatrix.sync.aligned.m8n8.x4.shared.b16 [%0],{%1,%2,%3,%4};" ::"r"(a), "r"(r0), "r"(r1), "r"(r2), "r"(r3) : "memory");
}
__device__ __forceinline__ uint32_t lds32(uint32_t a) { uint32_t v; asm volatile("ld.shared.b32 %0,[%1];" : "=r"(v) : "r"(a) : "memory"); return v; }
__device__ __forceinline__ uint4 lds128(uint32_t a) { uint4 v; asm volatile("ld.shared.v4.b32 {%0,%1,%2,%3},[%4];" : "=r"(v.x), "=r"(v.y), "=r"(v.z), "=r"(v.w) : "r"(a) : "memory"); return v; }
__device__ __forceinline__ void sts16(uint32_t a, uint32_t v) { asm volatile("st.shared.b16 [%0],%1;" ::"r"(a), "h"((unsigned short)v) : "memory"); }
__device__ __forceinline__ void sts32(uint32_t a, uint32_t v) { asm volatile("st.shared.b32 [%0],%1;" ::"r"(a), "r"(v) : "memory"); }
__device__ __forceinline__ void sts64(uint32_t a, uint32_t x, uint32_t y) { asm volatile("st.shared.v2.b32 [%0],{%1,%2};" ::"r"(a), "r"(x), "r"(y) : "memory"); }
__device__ __forceinline__ void sts128(uint32_t a, uint32_t x, uint32_t y, uint32_t z, uint32_t w) { asm volatile("st.shared.v4.b32 [%0],{%1,%2,%3,%4};" ::"r"(a), "r"(x), "r"(y), "r"(z), "r"(w) : "memory"); }
__device__ __forceinline__ uint32_t pack2(float lo, float hi) { uint32_t d; asm("cvt.rn.bf16x2.f32 %0,%1,%2;" : "=r"(d) : "f"(hi), "f"(lo)); return d; }
__device__ __forceinline__ float bf_lo(uint32_t v) { return __uint_as_float(v << 16); }
__device__ __forceinline__ float bf_hi(uint32_t v) { return __uint_as_float(v & 0xffff0000u); }
__device__ __forceinline__ float bf_round(float v) { return bf_lo(pack2(v, 0.f)); }
__device__ __forceinline__ uint32_t hmax2(uint32_t a, uint32_t b) { uint32_t d; asm("max.bf16x2 %0,%1,%2;" : "=r"(d) : "r"(a), "r"(b)); return d; }
__device__ __forceinline__ uint32_t hmin2(uint32_t a, uint32_t b) { uint32_t d; asm("min.bf16x2 %0,%1,%2;" : "=r"(d) : "r"(a), "r"(b)); return d; }
__device__ __forceinline__ uint32_t hmul2(uint32_t a, uint32_t b) { uint32_t d; asm("mul.rn.bf16x2 %0,%1,%2;" : "=r"(d) : "r"(a), "r"(b)); return d; }
__device__ __forceinline__ float ex2(float x) { float y; asm("ex2.approx.ftz.f32 %0,%1;" : "=f"(y) : "f"(x)); return y; }
__device__ __forceinline__ float rcp(float x) { float y; asm("rcp.approx.ftz.f32 %0,%1;" : "=f"(y) : "f"(x)); return y; }
__device__ __forceinline__ uint32_t ld_nc(const uint32_t* p) { uint32_t v; asm volatile("ld.global.nc.b32 %0,[%1];" : "=r"(v) : "l"(p)); return v; }
__device__ __forceinline__ uint2 ld_nc64(const uint2* p) { uint2 v; asm volatile("ld.global.nc.v2.b32 {%0,%1},[%2];" : "=r"(v.x), "=r"(v.y) : "l"(p)); return v; }
__device__ __forceinline__ unsigned ld_acq(const unsigned* p) { unsigned v; asm volatile("ld.acquire.gpu.global.u32 %0,[%1];" : "=r"(v) : "l"(p) : "memory"); return v; }
__device__ __forceinline__ unsigned ld_rlx(const unsigned* p) { unsigned v; asm volatile("ld.relaxed.gpu.global.u32 %0,[%1];" : "=r"(v) : "l"(p) : "memory"); return v; }
__device__ __forceinline__ uint2 ld_rlx64(const void* p) { uint2 v; asm volatile("{.reg .b64 t; ld.relaxed.gpu.global.b64 t,[%2]; mov.b64 {%0,%1},t;}" : "=r"(v.x), "=r"(v.y) : "l"(p) : "memory"); return v; }
__device__ __forceinline__ uint4 ld_rlx128(const void* p) {
    uint4 v;
    asm volatile("{.reg .b64 t,u; ld.relaxed.gpu.global.v2.b64 {t,u},[%4]; mov.b64 {%0,%1},t; mov.b64 {%2,%3},u;}" : "=r"(v.x), "=r"(v.y), "=r"(v.z), "=r"(v.w) : "l"(p) : "memory");
    return v;
}
__device__ __forceinline__ void st_rlx32(void* p, uint32_t x) { asm volatile("st.relaxed.gpu.global.u32 [%0],%1;" ::"l"(p), "r"(x) : "memory"); }
__device__ __forceinline__ void st_rlx64(void* p, uint32_t x, uint32_t y) { asm volatile("{.reg .b64 t; mov.b64 t,{%1,%2}; st.relaxed.gpu.global.b64 [%0],t;}" ::"l"(p), "r"(x), "r"(y) : "memory"); }
__device__ __forceinline__ void st_rlx128(void* p, uint4 v) {
    asm volatile("{.reg .b64 t,u; mov.b64 t,{%1,%2}; mov.b64 u,{%3,%4}; st.relaxed.gpu.global.v2.b64 [%0],{t,u};}" ::"l"(p), "r"(v.x), "r"(v.y), "r"(v.z), "r"(v.w) : "memory");
}
__device__ __forceinline__ uint32_t tagw(uint32_t w, uint32_t tag) { return (w & ~1u) | tag; }
__device__ __forceinline__ uint4 tag4(uint32_t x, uint32_t y, uint32_t z, uint32_t w, uint32_t tag) { return make_uint4(tagw(x, tag), y, tagw(z, tag), w); }
__device__ __forceinline__ uint32_t bad4(const uint4& v, uint32_t tag) { return (v.x ^ tag) | (v.z ^ tag); }
__device__ __forceinline__ void bar_named(int id, int n) { asm volatile("bar.sync %0,%1;" ::"r"(id), "r"(n) : "memory"); }

struct cf { float re, im; };
__device__ __forceinline__ cf cmul(cf a, cf b) { cf r; r.re = a.re * b.re - a.im * b.im; r.im = a.re * b.im + a.im * b.re; return r; }
__device__ __forceinline__ cf cexp_p(float arl, float ait, float p) {
    float mag = ex2(arl * p);
    float t = ait * p;
    t = (t - rintf(t)) * 6.283185307179586f;
    cf r; r.re = mag * __cosf(t); r.im = mag * __sinf(t);
    return r;
}

__device__ __forceinline__ void hedgehog4(const uint32_t* a, uint32_t wphi_addr, uint32_t (*out)[8]) {
    float p[4][2][4], mx[4][2];
#pragma unroll
    for (int h = 0; h < 4; h++) {
        uint32_t b[4];
        ldsm4t(b, wphi_addr + h * 512);
        float c0[4] = {0.f, 0.f, 0.f, 0.f}, c1[4] = {0.f, 0.f, 0.f, 0.f};
        mma16816(c0, a[4 * h], a[4 * h + 1], a[4 * h + 2], a[4 * h + 3], b[0], b[1]);
        mma16816(c1, a[4 * h], a[4 * h + 1], a[4 * h + 2], a[4 * h + 3], b[2], b[3]);
#pragma unroll
        for (int k = 0; k < 2; k++) {
            p[h][k][0] = c0[2 * k]; p[h][k][1] = c0[2 * k + 1]; p[h][k][2] = c1[2 * k]; p[h][k][3] = c1[2 * k + 1];
            mx[h][k] = fmaxf(fmaxf(p[h][k][0], p[h][k][1]), fmaxf(p[h][k][2], p[h][k][3]));
        }
    }
#pragma unroll
    for (int o = 1; o <= 2; o <<= 1)
#pragma unroll
        for (int h = 0; h < 4; h++)
#pragma unroll
            for (int k = 0; k < 2; k++) mx[h][k] = fmaxf(mx[h][k], __shfl_xor_sync(~0u, mx[h][k], o));
    const float L = 1.4426950408889634f;
    float pmin = 1.f;
#pragma unroll
    for (int h = 0; h < 4; h++)
#pragma unroll
        for (int k = 0; k < 2; k++) {
            const float m = -mx[h][k] * L;
            const float e0 = ex2(fmaf(p[h][k][0], L, m)), e1 = ex2(fmaf(p[h][k][1], L, m)), e2 = ex2(fmaf(p[h][k][2], L, m)), e3 = ex2(fmaf(p[h][k][3], L, m));
            const float p01 = e0 * e1, p23 = e2 * e3, pp = p01 * p23, r = rcp(pp), r01 = r * p23, r23 = r * p01;
            pmin = fminf(pmin, pp);
            out[h][k] = pack2(e0, e1); out[h][k + 2] = pack2(e2, e3);
            out[h][4 + k] = pack2(r01 * e1, r01 * e0); out[h][4 + k + 2] = pack2(r23 * e3, r23 * e2);
        }
    if (__builtin_expect(__any_sync(~0u, !(pmin > 1e-18f)), 0)) {
#pragma unroll
        for (int h = 0; h < 4; h++)
#pragma unroll
            for (int k = 0; k < 2; k++) {
                float m = fminf(fminf(p[h][k][0], p[h][k][1]), fminf(p[h][k][2], p[h][k][3]));
                m = fminf(m, __shfl_xor_sync(~0u, m, 1));
                m = fminf(m, __shfl_xor_sync(~0u, m, 2)) * L;
                out[h][4 + k] = pack2(ex2(fmaf(p[h][k][0], -L, m)), ex2(fmaf(p[h][k][1], -L, m)));
                out[h][4 + k + 2] = pack2(ex2(fmaf(p[h][k][2], -L, m)), ex2(fmaf(p[h][k][3], -L, m)));
            }
    }
}

__global__ void __launch_bounds__(512, 1)
fused_kernel(Scratch* __restrict__ scr, const bf16* __restrict__ logA, const bf16* __restrict__ Aim, const bf16* __restrict__ Cre,
             const bf16* __restrict__ Cim, const bf16* __restrict__ logdt, const bf16* __restrict__ Dskip, const bf16* __restrict__ wphi,
             const bf16* __restrict__ gatew, bf16* __restrict__ out,
             const __grid_constant__ CUtensorMap mx, const __grid_constant__ CUtensorMap mw, const __grid_constant__ CUtensorMap mwo) {
    extern __shared__ __align__(1024) uint8_t smem[];
    constexpr uint32_t sb = 1024;
    const int tid = threadIdx.x, warp = __shfl_sync(~0u, tid >> 5, 0), lane = tid & 31;
    const int g = lane >> 2, q = lane & 3, w4 = warp & 3;
    const int bi = blockIdx.x, bi_i = bi & 15, bi_j = bi >> 4;
    const uint32_t bar = sb + OFF_BAR;
    const int rot = (bi_j & 3) * 2, xkb = bi_j >> 2;
    auto load_stage = [&](int kb) {
        const uint32_t b = bar + 8 * (BAR_FULL + (kb & 3)), d = sb + (kb & 3) * SLOT;
        const int kc = ((kb + rot) & 7) * 64;
        mbar_expect(b, SLOT);
        tma2d(d, &mx, kc, bi_i * 128, b);
        tma3d(d + 16384, &mw, bi_j * 64, kc, 0, b);
    };

    const int ch = bi * 4 + w4;
    const int pidx = ch * 64 + lane * 2 + (warp >> 3);
    const uint32_t pla = ld_nc((const uint32_t*)logA + pidx), pai = ld_nc((const uint32_t*)Aim + pidx);
    const uint32_t pcr = ld_nc((const uint32_t*)Cre + pidx), pci = ld_nc((const uint32_t*)Cim + pidx);
    uint32_t pdt = ld_nc((const uint32_t*)logdt + (ch >> 1));
    const uint32_t pds = ld_nc((const uint32_t*)Dskip + (ch >> 1));
    unsigned done0 = ld_rlx(scr->done);
    if (tid == 0) {
        for (int s = 0; s < 4; s++) mbar_init(bar + 8 * (BAR_FULL + s), 1);
        asm volatile("fence.mbarrier_init.release.cluster;" ::: "memory");
        asm volatile("prefetch.tensormap [%0];" ::"l"(&mx) : "memory");
        load_stage(0); load_stage(1);
    } else if (tid == 32) {
        if (s2u(smem) != sb) __trap();
        sts32(bar + OFF_CNT, 0);
        for (int s = 0; s < 4; s++) mbar_init(bar + 8 * (BAR_EMPTY + s), 9);
        mbar_init(bar + 8 * BAR_WPHI, 1); mbar_init(bar + 8 * BAR_WO, 2); mbar_init(bar + 8 * BAR_WO2, 1); mbar_init(bar + 8 * BAR_XT, 4);
        mbar_init(bar + 8 * BAR_DONE, 9); mbar_init(bar + 8 * BAR_KG, 8); mbar_init(bar + 8 * BAR_SP, 1); mbar_init(bar + 8 * BAR_PUB, 8);
        mbar_init(bar + 8 * BAR_KVF, 4); mbar_init(bar + 8 * BAR_UR, 4); mbar_init(bar + 8 * BAR_WR, 4); mbar_init(bar + 8 * BAR_PREP, 4); mbar_init(bar + 8 * BAR_KGA, 4); mbar_init(bar + 8 * BAR_SP2, 1);
        asm volatile("fence.mbarrier_init.release.cluster;" ::: "memory");
        mbar_expect(bar + 8 * BAR_WPHI, 3072);
        bulk_g2s(sb + OFF_GW, gatew, 1024, bar + 8 * BAR_WPHI);
        bulk_g2s(sb + OFF_WPHI, wphi + bi_j * 1024, 2048, bar + 8 * BAR_WPHI);
    } else if (tid == 64) {
        asm volatile("prefetch.tensormap [%0];" ::"l"(&mw) : "memory");
    }
    const uint32_t buf = sb + OFF_BUF + w4 * BUF_STRIDE, kb_ = sb + OFF_K + w4 * KT_BYTES;
    if ((warp >> 2) == 2) {
#pragma unroll
        for (int v = 0; v < 7; v++) if (v * 32 + lane < KT_BYTES / 16) sts128(kb_ + (v * 32 + lane) * 16, 0, 0, 0, 0);
    }
    __syncthreads();
    asm volatile("" : "+r"(pdt), "+r"(done0)::"memory");
    const unsigned epoch1 = (done0 >> 7) + 1u;
    const uint32_t tag = epoch1 & 1u;

    const int st = tid & 127;
    const uint32_t ub = sb + OFF_U + w4 * U_STRIDE + 256, spare = sb + (w4 < 2 ? OFF_SP0 : OFF_SP1) + (w4 & 1) * 4096;

    auto stg_of = [&](int w) { return w < 8 ? sb + 3 * SLOT + w * 7296 : sb + 2 * SLOT + (w & 3) * 7296; };
    float kc[24];
#pragma unroll
    for (int t = 0; t < 24; t++) kc[t] = 0.f;
    {
        const float dt = bf_round(expf((ch & 1) ? bf_hi(pdt) : bf_lo(pdt)));
        const uint32_t stg = (warp >> 2) == 2 ? buf : stg_of(warp);
        const int sh = ((warp >> 2) & 1) * 16;
        auto pick = [&](uint32_t v) { return __uint_as_float((v >> sh) << 16); };
        const float ea = bf_round(ex2(pick(pla) * 1.4426950408889634f));
        const float arl = (-ea * dt) * 1.4426950408889634f, ait = (pick(pai) * dt) * 0.15915494309189535f;
        cf C2; C2.re = 2.0f * (pick(pcr) * dt); C2.im = 2.0f * (pick(pci) * dt);
        const cf z1 = cexp_p(arl, ait, 1.0f), z128 = cexp_p(arl, ait, 128.0f);
        cf z8 = cexp_p(arl, ait, 8.0f); z8.im = -z8.im;
        const uint32_t lp = stg + lane * 4;
        auto put = [&](int row, const cf& v) { sts32((lp ^ ((row & 7) << 4)) + row * 128, pack2(v.re, v.im)); };
        {
            const cf z16 = cmul(z8, z8);
            cf e; e.re = 1.f; e.im = 0.f;
            cf o = z8;
            put(0, e); put(1, o);
            e = z16; put(2, e);
#pragma unroll
            for (int b = 3; b < 16; b += 2) {
                o = cmul(o, z16); put(b, o);
                if (b + 1 < 16) { e = cmul(e, z16); put(b + 1, e); }
            }
        }
        cf h[8];
        h[0] = C2; put(16, h[0]);
        {
            const cf z2 = cmul(z1, z1);
            h[1] = cmul(h[0], z1);
#pragma unroll
            for (int r = 2; r < 8; r++) h[r] = cmul(h[r - 2], z2);
#pragma unroll
            for (int r = 1; r < 8; r++) put(16 + r, h[r]);
        }
#pragma unroll
        for (int r = 0; r < 8; r++) { h[r] = cmul(h[r], z128); put(24 + r, h[r]); }
#pragma unroll
        for (int al = 0; al < 2; al++)
#pragma unroll
            for (int r = 0; r < 4; r++) { h[2 * r] = cmul(h[2 * r], z128); put(32 + al * 4 + r, h[2 * r]); }
#pragma unroll
        for (int al = 0; al < 4; al++)
#pragma unroll
            for (int r = 0; r < 2; r++) { h[4 * r] = cmul(h[4 * r], z128); put(40 + al * 2 + r, h[4 * r]); }
#pragma unroll
        for (int al = 0; al < 9; al++) { h[0] = cmul(h[0], z128); put(48 + al, h[0]); }
        __syncwarp();
        const int lr = lane & 7, lm = lane >> 3;
#pragma unroll
        for (int kp = 0; kp < 2; kp++) {
            uint32_t a0[4], a1[4];
            ldsm4(a0, stg + ((lm & 1) * 8 + lr) * 128 + (((4 * kp + (lm >> 1)) ^ lr) << 4));
            ldsm4(a1, stg + ((lm & 1) * 8 + lr) * 128 + (((4 * kp + 2 + (lm >> 1)) ^ lr) << 4));
#pragma unroll
            for (int t = 0; t < 6; t++) {
                uint32_t b[4];
                ldsm4(b, stg + (16 + 8 * t + lr) * 128 + (((4 * kp + lm) ^ lr) << 4));
                mma16816(kc + 4 * t, a0[0], a0[1], a0[2], a0[3], b[0], b[1]);
                mma16816(kc + 4 * t, a1[0], a1[1], a1[2], a1[3], b[2], b[3]);
            }
        }
        __syncwarp();
        if ((warp >> 2) != 2) {
#pragma unroll
            for (int t = 0; t < 6; t++)
                sts128(stg + (t * 32 + lane) * 16, __float_as_uint(kc[4 * t]), __float_as_uint(kc[4 * t + 1]), __float_as_uint(kc[4 * t + 2]), __float_as_uint(kc[4 * t + 3]));
            asm volatile("fence.proxy.async.shared::cta;" ::: "memory");
            __syncwarp();
            if (lane == 0) mbar_arrive(bar + 8 * (warp < 8 ? BAR_KG : BAR_KGA));
        }
    }

    if (warp < 8) {
        asm volatile("setmaxnreg.inc.sync.aligned.u32 160;");
        const int wg = warp >> 2;
        float acc[96];
        const int srow = warp * 16 + (lane & 15);
        const uint32_t srow_a = srow * 128;
        const int sx = srow & 7, shi = lane >> 4;
        const uint64_t da0 = mkdesc(sb + wg * 8192, 16, 1024), db0 = mkdesc(sb + 16384, 8192, 1024);
#pragma unroll 1
        for (int kb = 0; kb < 8; kb++) {
            const int s = kb & 3;
            const uint64_t da = da0 + s * (SLOT >> 4), db = db0 + s * (SLOT >> 4);
            mbar_wait(bar + 8 * (BAR_FULL + s), kb >> 2);
            wg_fence();
#pragma unroll
            for (int k = 0; k < 4; k++) wgmma192(acc, da + 2 * k, db + 128 * k, kb | k);
            wg_commit();
            wg_wait<1>();
            if (lane == 0 && kb > 0) mbar_arrive(bar + 8 * (BAR_EMPTY + ((kb - 1) & 3)));
        }
        mbar_wait(bar + 8 * BAR_WPHI, 0);
        wg_wait<0>();
        fence_regs<96>(acc);
        if (lane == 0) mbar_arrive(bar + 8 * BAR_DONE);
        uint32_t in[16], qa[16];
        mbar_wait(bar + 8 * BAR_DONE, 0);
#pragma unroll
        for (int r = 0; r < 16; r++) {
            in[r] = pack2(acc[32 + 2 * r], acc[32 + 2 * r + 1]);
            qa[r] = pack2(acc[2 * r], acc[2 * r + 1]);
        }
#pragma unroll
        for (int hh = 0; hh < 4; hh++)
            stsm4(sb + OFF_V + (hh >> 1) * 16384 + srow_a + (((2 * (hh & 1) + shi) ^ sx) << 4), pack2(acc[64 + 8 * hh], acc[65 + 8 * hh]),
                  pack2(acc[66 + 8 * hh], acc[67 + 8 * hh]), pack2(acc[68 + 8 * hh], acc[69 + 8 * hh]), pack2(acc[70 + 8 * hh], acc[71 + 8 * hh]));
        sts128(sb + OFF_V + shi * 16384 + srow_a + ((4 ^ sx) << 4), 0x3f803f80u, 0x3f803f80u, 0x3f803f80u, 0x3f803f80u);
        const uint32_t wphi_a = sb + OFF_WPHI + (lane & 15) * 32 + (lane >> 4) * 16;
        uint32_t pq[4][8];
#pragma unroll 1
        for (int it = 0; it < 2; it++) {
            hedgehog4(in, wphi_a, pq);
            if (it == 1) break;
#pragma unroll
            for (int hs = 0; hs < 8; hs++) {
                float c[4] = {0.f, 0.f, 0.f, 0.f};
                const uint32_t* o = pq[hs >> 1] + 4 * (hs & 1);
                mma16816(c, o[0], o[1], o[2], o[3], 0x3f803f80u, 0x3f803f80u);
                const float r0 = rcp(c[0]), r1 = rcp(c[2]);
                const uint32_t s0 = pack2(r0, r0), s1 = pack2(r1, r1);
                stsm4(sb + OFF_P + (hs >> 2) * 16384 + srow_a + (((2 * (hs & 3) + shi) ^ sx) << 4), hmul2(o[0], s0), hmul2(o[1], s1), hmul2(o[2], s0), hmul2(o[3], s1));
            }
            asm volatile("fence.proxy.async.shared::cta;" ::: "memory");
            bar_named(1, 256);
            float d[32];
            const uint64_t dv = mkdesc(sb + OFF_V + wg * 16384, 16, 1024), dp = mkdesc(sb + OFF_P + wg * 16384, 16, 1024);
            wg_fence();
#pragma unroll
            for (int k = 0; k < 8; k++) wgmma64_tt(d, dv + 128 * k, dp + 128 * k, k != 0);
            wg_commit();
            mbar_wait(bar + 8 * BAR_PREP, 0);
            uint4* kvp = scr->kvp + bi * 544 + wg * 272 + (w4 < 2 ? w4 * 136 : 128) + lane;
            wg_wait<0>();
            fence_regs<32>(d);
            if (w4 < 2 || (w4 == 2 && lane < 4)) {
#pragma unroll
                for (int f = 0; f < 4; f++) {
                    const int i0 = 8 * (f >> 1) + 2 * (f & 1), i2 = 16 * (f >> 1) + 8 * (f & 1);
                    const float e0 = w4 == 0 ? d[i0] : (w4 == 1 ? d[16 + i0] : d[i2]), e1 = w4 == 0 ? d[i0 + 1] : (w4 == 1 ? d[17 + i0] : d[i2 + 1]);
                    const float e2 = w4 == 0 ? d[i0 + 4] : (w4 == 1 ? d[20 + i0] : d[i2 + 4]), e3 = w4 == 0 ? d[i0 + 5] : (w4 == 1 ? d[21 + i0] : d[i2 + 5]);
                    st_rlx128(kvp + (w4 < 2 ? f * 32 : (f >> 1) * 136 + (f & 1) * 4), tag4(__float_as_uint(e0), __float_as_uint(e1), __float_as_uint(e2), __float_as_uint(e3), tag));
                }
            }
            __syncwarp();
            if (lane == 0) mbar_arrive(bar + 8 * BAR_PUB);
#pragma unroll
            for (int r = 0; r < 16; r++) in[r] = qa[r];
        }
        {
            mbar_wait(bar + 8 * BAR_KVF, 0);
            uint4 kf[4][3];
#pragma unroll
            for (int hh = 0; hh < 4; hh++) {
                const uint32_t a = sb + OFF_KVF + hh * 1088;
                kf[hh][0] = lds128(a + lane * 32); kf[hh][1] = lds128(a + lane * 32 + 16); kf[hh][2] = lds128(a + 1024 + q * 16);
            }
            uint4* og = scr->o + ((bi_i * 8 + warp) * 32 + bi_j * 4) * 32 + lane;
#pragma unroll
            for (int hh = 0; hh < 4; hh++) {
                float c[6][4];
#pragma unroll
                for (int t = 0; t < 6; t++) { c[t][0] = c[t][1] = c[t][2] = c[t][3] = 0.f; }
                const uint32_t* a = pq[hh];
                const bool od = g & 1;
                mma16816(c[0], a[0], a[1], a[2], a[3], od ? 0x3f803f80u : kf[hh][2].x, od ? 0x3f803f80u : kf[hh][2].y);
                mma16816(c[1], a[4], a[5], a[6], a[7], od ? 0x3f803f80u : kf[hh][2].z, od ? 0x3f803f80u : kf[hh][2].w);
                mma16816(c[2], a[0], a[1], a[2], a[3], kf[hh][0].x, kf[hh][0].y);
                mma16816(c[3], a[0], a[1], a[2], a[3], kf[hh][0].z, kf[hh][0].w);
                mma16816(c[4], a[4], a[5], a[6], a[7], kf[hh][1].x, kf[hh][1].y);
                mma16816(c[5], a[4], a[5], a[6], a[7], kf[hh][1].z, kf[hh][1].w);
                uint32_t w[4];
#pragma unroll
                for (int k = 0; k < 2; k++) {
                    const float rho = c[0][2 * k + 1] * rcp(c[1][2 * k + 1]);
                    const float r = rcp(fmaf(c[0][2 * k + 1], 1e-6f, fmaf(rho, c[1][2 * k], c[0][2 * k]))), rr = r * rho;
                    w[k] = pack2(fmaf(c[4][2 * k], rr, c[2][2 * k] * r), fmaf(c[4][2 * k + 1], rr, c[2][2 * k + 1] * r));
                    w[2 + k] = pack2(fmaf(c[5][2 * k], rr, c[3][2 * k] * r), fmaf(c[5][2 * k + 1], rr, c[3][2 * k + 1] * r));
                }
                st_rlx128(og + hh * 32, tag4(w[0], w[1], w[2], w[3], tag));
            }
        }
        float oc[64];
        const int slab = bi_i * 8 + (bi_j >> 2) * 4 + w4;
        const uint8_t* ysrc = (const uint8_t*)scr->y + (size_t)((bi_j & 3) * 32 + wg * 16 + (q >> 1)) * 16384 + slab * 128 + g * 16 + (q & 1) * 8;
        const unsigned* gp = scr->g + (slab * 8 + (g >> 1)) * 8 + (g & 1) * 4;
        uint2 yv[8]; unsigned g0, g1;
        {
            const uint4* osrc = scr->o + (slab * 32 + wg * 16) * 32 + lane;
            uint4 fr[16];
            const unsigned* probe = (const unsigned*)(osrc - lane + ((lane & 3) * 4 + 3) * 32 + 31) + 2;
            {
                unsigned miss = ~0u;
                int n = 0;
#pragma unroll
                for (int s = 0; s < 4; s++) {
#pragma unroll 1
                    while ((miss >> s) & 1) { miss = __ballot_sync(~0u, (ld_rlx(probe) ^ tag) & 1); if (++n > SPIN_LIMIT) break; }
#pragma unroll
                    for (int k = 4 * s; k < 4 * s + 4; k++) fr[k] = ld_rlx128(osrc + k * 32);
                }
            }
            mbar_wait(bar + 8 * (wg ? BAR_WO2 : BAR_WO), 0);
            const uint64_t dw = mkdesc(sb + wg * 2 * SLOT, wg ? 32768 : SLOT, 1024);
#pragma unroll
            for (int s = 0; s < 4; s++) {
                int n = 0;
#pragma unroll 1
                while (__builtin_expect(__any_sync(~0u, (bad4(fr[4 * s], tag) | bad4(fr[4 * s + 1], tag) | bad4(fr[4 * s + 2], tag) | bad4(fr[4 * s + 3], tag)) & 1), 0)) {
#pragma unroll
                    for (int k = 4 * s; k < 4 * s + 4; k++) fr[k] = ld_rlx128(osrc + k * 32);
                    if (++n > SPIN_LIMIT) break;
                }
                wg_fence();
#pragma unroll
                for (int hh = 0; hh < 4; hh++) wgmma128_rs(oc, fr[4 * s + hh], dw + 128 * (4 * s + hh), (s | hh) != 0);
                wg_commit();
                if (s == 1) {
                    wg_wait<1>();
#pragma unroll
                    for (int nt = 0; nt < 8; nt++) yv[nt] = ld_rlx64(ysrc + nt * 32768);
                    g0 = ld_rlx(gp); g1 = ld_rlx(gp + 32);
                }
            }
            {
                const unsigned* yprobe = scr->yflag + ((bi_j & 3) * 32 + wg * 16 + (lane & 15)) * 8;
                int n = 0;
#pragma unroll 1
                while (true) {
                    uint32_t bad = (g0 ^ tag) | (g1 ^ tag);
#pragma unroll
                    for (int nt = 0; nt < 8; nt++) bad |= yv[nt].x ^ tag;
                    if (!__any_sync(~0u, bad & 1)) break;
#pragma unroll 1
                    while (__any_sync(~0u, (ld_rlx(yprobe) ^ tag) & 1)) { if (++n > SPIN_LIMIT) break; }
#pragma unroll
                    for (int nt = 0; nt < 8; nt++) yv[nt] = ld_rlx64(ysrc + nt * 32768);
                    g0 = ld_rlx(gp); g1 = ld_rlx(gp + 32);
                    if (++n > SPIN_LIMIT) break;
                }
            }
        }
        {
            const float ga = bf_hi(g0), gb = bf_hi(g1);
            const float ha = bf_round(1.0f - ga), hb = bf_round(1.0f - gb);
            float yb[32];
#pragma unroll
            for (int nt = 0; nt < 8; nt++) {
                yb[4 * nt] = ha * bf_lo(yv[nt].x); yb[4 * nt + 1] = ha * bf_hi(yv[nt].x);
                yb[4 * nt + 2] = hb * bf_lo(yv[nt].y); yb[4 * nt + 3] = hb * bf_hi(yv[nt].y);
            }
            fence_regs<32>(yb);
            const uint32_t xw = sb + wg * 2 * SLOT + (tid & 127) * 16, xr = sb + (wg ^ 1) * 2 * SLOT + (tid & 127) * 16;
            wg_wait<0>();
            fence_regs<64>(oc);
            bar_named(3 + wg, 128);
#pragma unroll
            for (int r = 0; r < 8; r++)
                sts128(xw + r * 2048, __float_as_uint(oc[32 + 4 * r]), __float_as_uint(oc[33 + 4 * r]), __float_as_uint(oc[34 + 4 * r]), __float_as_uint(oc[35 + 4 * r]));
#pragma unroll
            for (int r = 0; r < 32; r++) yb[r] = fmaf((r & 2) ? gb : ga, oc[r], yb[r]);
            bar_named(1, 256);
            uint32_t w[8][2];
#pragma unroll
            for (int nt = 0; nt < 8; nt++) {
                const uint4 p = lds128(xr + nt * 2048);
                w[nt][0] = pack2(fmaf(ga, __uint_as_float(p.x), yb[4 * nt]), fmaf(ga, __uint_as_float(p.y), yb[4 * nt + 1]));
                w[nt][1] = pack2(fmaf(gb, __uint_as_float(p.z), yb[4 * nt + 2]), fmaf(gb, __uint_as_float(p.w), yb[4 * nt + 3]));
            }
            const uint32_t ob = sb + wg * 2 * SLOT + 16384 + w4 * 2048;
#pragma unroll
            for (int nt = 0; nt < 8; nt += 2)
                stsm4(ob + (lane & 15) * 128 + (((nt + shi) ^ (lane & 7)) << 4), w[nt][0], w[nt][1], w[nt + 1][0], w[nt + 1][1]);
            __syncwarp();
            bf16* op = out + (size_t)(slab * 16) * 512 + (bi_j & 3) * 128 + wg * 64 + (lane & 7) * 8;
#pragma unroll
            for (int it = 0; it < 4; it++) {
                const int r = it * 4 + (lane >> 3);
                uint4 v = lds128(ob + r * 128 + (((lane & 7) ^ (r & 7)) << 4));
                *(uint4*)(op + r * 512) = v;
            }
        }
    } else if (warp < 12) {
#pragma unroll
        for (int src = 2; src >= 0; src--) {
            if (src != 0) mbar_wait(bar + 8 * (src == 2 ? BAR_KGA : BAR_KG), 0);
#pragma unroll
            for (int t = 0; t < 6; t++) {
                const uint4 v = lds128(stg_of(w4 + src * 4) + (t * 32 + lane) * 16);
                kc[4 * t] += __uint_as_float(v.x); kc[4 * t + 1] += __uint_as_float(v.y); kc[4 * t + 2] += __uint_as_float(v.z); kc[4 * t + 3] += __uint_as_float(v.w);
            }
            if (src != 1) {
                bar_named(2, 128);
                if (st == 0) { load_stage(src == 2 ? 2 : 3); if (src == 0) mbar_arrive(bar + 8 * BAR_SP); }
            }
        }
        if (warp == 8) {
#pragma unroll 1
            for (int kb = 0; kb < 6; kb++) {
                const int s = kb & 3;
                mbar_wait(bar + 8 * (BAR_EMPTY + s), kb >> 2);
                if (kb == xkb) mbar_wait(bar + 8 * BAR_XT, 0);
                if (lane == 0) {
                    if (kb < 4) load_stage(kb + 4);
                    else {
                        mbar_expect(bar + 8 * BAR_WO, 32768);
                        tma2d(sb + s * SLOT, &mwo, (bi_j & 3) * 128 + s * 64, 0, bar + 8 * BAR_WO);
                        if (kb == 5) mbar_arrive(bar + 8 * BAR_SP2);
                    }
                }
                __syncwarp();
            }
        } else if (warp == 9) {
            const int row = bi_j * 16 + (lane >> 1), half = lane & 1;
            unsigned* gp = scr->g + (bi_i * 64 + bi_j * 8) * 8 + lane * 2;
            st_rlx64(gp, tag ^ 1u, tag ^ 1u);
            if (lane < 8) st_rlx32(scr->yflag + bi * 8 + lane, tag ^ 1u);
            float gs0 = 0.f, gs1 = 0.f;
            mbar_wait(bar + 8 * BAR_WPHI, 0);
#pragma unroll 1
            for (int kb = 0; kb < 8; kb++) {
                const int s = kb & 3;
                mbar_wait(bar + 8 * (BAR_FULL + s), kb >> 2);
#pragma unroll
                for (int c = 0; c < 4; c++) {
                    const uint4 xv = lds128(sb + s * SLOT + row * 128 + (((half * 4 + c) ^ (row & 7)) << 4));
                    const uint4 gw = lds128(sb + OFF_GW + ((kb + rot) & 7) * 128 + half * 64 + c * 16);
                    const uint32_t p0 = hmul2(xv.x, gw.x), p1 = hmul2(xv.y, gw.y), p2 = hmul2(xv.z, gw.z), p3 = hmul2(xv.w, gw.w);
                    gs0 += (bf_lo(p0) + bf_lo(p1)) + (bf_lo(p2) + bf_lo(p3));
                    gs1 += (bf_hi(p0) + bf_hi(p1)) + (bf_hi(p2) + bf_hi(p3));
                }
                const uint32_t cnt = 1u + (__float_as_uint(gs0 + gs1) == 0xffc12345u);
                if (lane == 0) asm volatile("mbarrier.arrive.shared::cta.b64 _,[%0],%1;" ::"r"(bar + 8 * (kb < 7 ? BAR_EMPTY + s : BAR_DONE)), "r"(cnt) : "memory");
                __syncwarp();
            }
            float gs = gs0 + gs1;
            gs += __shfl_xor_sync(~0u, gs, 1);
            const uint32_t gv = __float_as_uint(bf_round(rcp(1.0f + ex2(-1.4426950408889634f * bf_round(gs))))) | tag;
            st_rlx64(gp, gv, gv);
        }
        if (lane == 0) kc[4 * 0 + 0] += ((ch & 1) ? bf_hi(pds) : bf_lo(pds));
        const uint32_t k1024 = __shfl_sync(~0u, pack2(kc[4 * 4 + 0], 0.f), 0);
#pragma unroll
        for (int i = 0; i < 2; i++) {
            const int be = g + 8 * i;
#pragma unroll
            for (int t = 0; t < 2; t++) {
                const uint32_t a = kb_ + (KW_D + 128 * t + 8 * be + 2 * q) * 4;
                const uint32_t w = pack2(kc[4 * t + 2 * i + 1], kc[4 * t + 2 * i]);
                sts32(a + 4, w); sts16(a, w >> 16); sts16(a + 10, w);
            }
            {
                const int p = 256 + 128 * (q >> 1) + 8 * be + 4 * (q & 1);
                const uint32_t a = kb_ + (KW_D + p) * 4;
                const uint32_t w = pack2(kc[4 * 2 + 2 * i + 1], kc[4 * 2 + 2 * i]);
                const uint32_t aa = (w >> 16) | (w & 0xffff0000u);
                if (p != 256) { sts16(a - 4, aa); sts32(a, aa); } else sts16(a, aa);
                sts32(a + 4, aa); sts32(a + 8, w); sts16(a + 14, w);
            }
            {
                const int k = 64 + 16 * q + be;
                const uint32_t w = pack2(kc[4 * 3 + 2 * i], kc[4 * 3 + 2 * i + 1]);
                if (k != 64) sts16(kb_ + (KW_2 + ((k - 1) >> 1) - 24) * 4 + (k & 1) * 2, w);
                else {
                    const uint32_t a = kb_ + (KW_D + 511) * 4, aa = (w << 16) | (w & 0xffffu);
                    sts16(a, w); sts32(a + 4, aa); sts32(a + 8, aa); sts32(a + 12, aa); sts16(a + 18, w);
                }
                sts16(kb_ + (KW_2 + 48 + (k >> 1) - 24) * 4 + ((k & 1) ^ 1) * 2, w >> 16);
            }
#pragma unroll
            for (int b = 0; b < 2; b++) {
                const int k = 64 + 8 * (2 * q + b) + (be >> 1);
                const uint32_t w = pack2(kc[4 * 4 + 2 * i + b], 0.f);
                if (!(be & 1) && k == 64) sts16(kb_ + (KW_2 + 63 - 24) * 4, w);
                else {
                    const uint32_t a = kb_ + (KW_3 + ((be & 1) ? 80 + k : k - 1) - 48) * 4;
                    sts16(a, w);
                    if (!((be & 1) && k == 127)) sts16(a + 6, w);
                }
            }
        }
        if (lane == 0) sts16(kb_ + (KW_3 + 127 - 48) * 4, pack2(kc[4 * 5 + 0], 0.f));
        __syncwarp();
        asm volatile("setmaxnreg.inc.sync.aligned.u32 136;");
        mbar_wait(bar + 8 * BAR_UR, 0);
        mbar_wait(bar + 8 * BAR_DONE, 0);
        float y[16][4];
#pragma unroll
        for (int nt = 0; nt < 16; nt++) { y[nt][0] = y[nt][1] = y[nt][2] = y[nt][3] = 0.f; }
        {
            uint32_t Bp[32], A[4][3], An[4][3];
            auto uaddr = [&](int rho) { const int R0 = (lane >> 4) * 64 + (lane & 7) - rho; return ub + (((2 * R0 + ((lane >> 3) & 1)) ^ ((R0 >> 2) & 1)) << 4); };
            const uint32_t kd = kb_ + (KW_D + g - 2 * q) * 4;
#pragma unroll 1
            for (int rho = 1; rho >= 0; rho--) {
                const uint32_t a = uaddr(rho), k = kd + 2048 + rho * 64;
#pragma unroll
                for (int i = 0; i < 8; i++) ldsm4(Bp + 4 * i, a + i * 256);
                const uint32_t a0 = lds32(k), a1 = lds32(k + 32), a2 = lds32(k - 32);
#pragma unroll
                for (int i = 0; i < 12; i++) mma16816(y[i + 4], a0, a1, a2, a0, Bp[4 * (i & 7) + 2 * (i >> 3)], Bp[4 * (i & 7) + 2 * (i >> 3) + 1]);
            }
#pragma unroll
            for (int ga = 0; ga < 4; ga++) { An[ga][0] = lds32(kd + ga * 512); An[ga][1] = lds32(kd + ga * 512 + 32); An[ga][2] = lds32(kd + ga * 512 - 32); }
#pragma unroll 1
            for (int rho = 0; rho < 8; rho++) {
#pragma unroll
                for (int ga = 0; ga < 4; ga++) {
                    const uint32_t a = kd + (rho + 1) * 64 + ga * 512;
                    A[ga][0] = An[ga][0]; A[ga][1] = An[ga][1]; A[ga][2] = An[ga][2];
                    An[ga][0] = lds32(a); An[ga][1] = lds32(a + 32); An[ga][2] = lds32(a - 32);
                }
                const uint32_t an = uaddr(rho + 1);
#pragma unroll
                for (int i = 0; i < 8; i++) {
#pragma unroll
                    for (int ga = 0; ga < 4; ga++) {
                        mma16816(y[i + ga], A[ga][0], A[ga][1], A[ga][2], A[ga][0], Bp[4 * i], Bp[4 * i + 1]);
                        if (i + 8 + ga < 16) mma16816(y[i + 8 + ga], A[ga][0], A[ga][1], A[ga][2], A[ga][0], Bp[4 * i + 2], Bp[4 * i + 3]);
                    }
                    ldsm4(Bp + 4 * i, an + i * 256);
                    __syncwarp();
                }
            }
        }
        mbar_wait(bar + 8 * BAR_WR, 0);
#pragma unroll 1
        for (int ph = 0; ph < 2; ph++) {
            uint32_t B[5][2];
            const uint32_t ka = kb_ + (KW_2 + ph * 48 + 8 + g - q) * 4;
#pragma unroll
            for (int dd = 0; dd < 5; dd++) { B[dd][0] = lds32(ka + dd * 32); B[dd][1] = lds32(ka + dd * 32 - 16); }
            const uint32_t wa = buf + ph * W3_OFF + ((lane & 7) + ((lane >> 3) & 1) + (lane >> 4) * 8) * 16;
#pragma unroll
            for (int s = 0; s < 12; s++) {
                uint32_t A[4];
                ldsm4t(A, wa + s * 256);
#pragma unroll
                for (int dd = 0; dd < 5; dd++)
                    if (s + 4 + dd < 16) mma16816(y[s + 4 + dd], A[0], A[1], A[2], A[3], B[dd][0], B[dd][1]);
            }
        }
        {
            const int ap = (lane & 7) + (lane >> 4) * 8;
            const uint32_t loff = ((2 * ap + ((lane >> 3) & 1)) ^ ((ap >> 2) & 1)) << 4;
#pragma unroll 1
            for (int ph = 0; ph < 2; ph++) {
                uint32_t B[8][2];
                const uint32_t wb = (ph ? spare : buf + W9_OFF) + loff;
                const uint32_t ka = kb_ + (KW_3 + ph * 80 + 16 + g - 2 * q) * 4;
#pragma unroll
                for (int dd = 0; dd < 8; dd++) { B[dd][0] = lds32(ka + dd * 32); B[dd][1] = lds32(ka + dd * 32 - 32); }
#pragma unroll
                for (int s = 0; s < 4; s++) {
                    uint32_t A[4];
                    ldsm4t(A, wb + s * 512);
#pragma unroll
                    for (int dd = 0; dd < 8; dd++)
                        if (8 + 2 * s + dd < 16) mma16816(y[8 + 2 * s + dd], A[0], A[1], A[2], A[3], B[dd][0], B[dd][1]);
                }
            }
            const uint32_t idw = (g == 2 * q) ? k1024 : ((g == 2 * q + 1) ? (k1024 << 16) : 0u);
#pragma unroll
            for (int s = 0; s < 4; s++) {
                uint32_t A[4];
                ldsm4t(A, spare + 2048 + loff + s * 512);
                mma16816(y[8 + 2 * s], A[0], A[1], A[2], A[3], idw, 0u);
                mma16816(y[9 + 2 * s], A[0], A[1], A[2], A[3], 0u, idw);
            }
        }
        __syncwarp();
#pragma unroll
        for (int nt = 0; nt < 16; nt++)
#pragma unroll
            for (int b = 0; b < 2; b++) sts32(buf + ((8 * nt + 2 * q + b) * 8 + g) * 4, pack2(y[nt][b], y[nt][2 + b]));
        bar_named(2, 128);
        uint4* yp = scr->y + bi * 1024 + st;
#pragma unroll
        for (int v = 0; v < 8; v++) {
            const uint32_t a = sb + OFF_BUF + (st + 128 * v) * 4;
            const uint32_t w0 = lds32(a), w1 = lds32(a + BUF_STRIDE), w2 = lds32(a + 2 * BUF_STRIDE), w3 = lds32(a + 3 * BUF_STRIDE);
            st_rlx128(yp + v * 128, tag4(__byte_perm(w0, w1, 0x5410), __byte_perm(w0, w1, 0x7632), __byte_perm(w2, w3, 0x5410), __byte_perm(w2, w3, 0x7632), tag));
        }
        if (st < 8) st_rlx32(scr->yflag + bi * 8 + st, tag);
    } else {
        asm volatile("setmaxnreg.dec.sync.aligned.u32 56;");
        const int qq = (bi_i & 2) + ((lane >> 1) & 1);
        uint2* kvf_h = (uint2*)(scr->kvf + (bi_j * 4 + (bi_i >> 2)) * 68);
        auto windows = [&](int rhi, int rlo) {
#pragma unroll 1
            for (int rho = rhi; rho >= rlo; rho--) {
                const int ci = lane + 32 * rho;
                uint4 e4[4];
#pragma unroll
                for (int v = 0; v < 4; v++) { const int cc = ci - 3 + v; e4[v] = lds128(ub + ((cc ^ ((cc >> 3) & 1)) << 4)); }
                float S[29];
                const uint32_t* ew = (const uint32_t*)e4;
                S[3] = 0.f;
#pragma unroll
                for (int k = 4; k <= 28; k++) S[k] = S[k - 1] + ((k & 1) ? bf_hi(ew[k >> 1]) : bf_lo(ew[k >> 1]));
                auto win = [&](int lo, int hi, uint32_t a) {
                    sts128(a, pack2(S[hi] - S[lo - 1], S[hi + 1] - S[lo]), pack2(S[hi + 2] - S[lo + 1], S[hi + 3] - S[lo + 2]),
                           pack2(S[hi + 4] - S[lo + 3], S[hi + 5] - S[lo + 4]), pack2(S[hi + 6] - S[lo + 5], S[hi + 7] - S[lo + 6]));
                };
                win(14, 18, buf + W5_OFF + 16 + ci * 16); win(19, 21, buf + W3_OFF + 16 + ci * 16);
                if (rho < 4) {
                    const uint32_t sw = (ci ^ ((ci >> 3) & 1)) << 4;
                    win(4, 12, buf + W9_OFF + sw); win(13, 19, spare + sw); win(20, 21, spare + 2048 + sw);
                }
            }
        };
        {
            mbar_wait(bar + 8 * (BAR_FULL + xkb), 0);
#pragma unroll 1
            for (int hf = 0; hf < 2; hf++) {
                const int r = w4 * 32 + hf * 16 + (lane & 15);
                uint32_t* xt = (uint32_t*)scr->xt + ((xkb + rot) * 16 + (g >> 2)) * 4096 + (bi_i * 16 + w4 * 4 + hf * 2) * 16 + (g & 3) * 4 + q;
#pragma unroll
                for (int cb = 0; cb < 8; cb += 2) {
                    uint32_t v[4];
                    ldsm4t(v, sb + xkb * SLOT + r * 128 + (((cb + (lane >> 4)) ^ (r & 7)) << 4));
                    xt[cb * 8192] = v[0]; xt[cb * 8192 + 16] = v[1]; xt[cb * 8192 + 8192] = v[2]; xt[cb * 8192 + 8192 + 16] = v[3];
                }
            }
            __syncwarp();
            if (lane == 0) {
                mbar_arrive(bar + 8 * BAR_XT);
                asm volatile("red.release.gpu.global.add.u32 [%0],2;" ::"l"(scr->xcnt + (xkb + rot) * 32) : "memory");
            }
            __syncwarp();
            {
                const uint32_t old = tag ^ 1u;
                const uint4 z4 = make_uint4(old, 0, old, 0);
#pragma unroll
                for (int v = 0; v < 5; v++) if (v < 4 || st < 32) st_rlx128(scr->kvp + bi * 544 + v * 128 + st, z4);
                if (st < 16) st_rlx128(scr->o + ((bi_i * 8 + (st >> 1)) * 32 + bi_j * 4 + 3) * 32 + 30 + (st & 1), z4);
                if (lane < 8) st_rlx64(kvf_h + ((bi_i & 3) * 8 + w4 * 2 + (lane & 1)) * 4 + (lane >> 1), old, 0);
                if (st < 4 && !(bi_i & 1)) st_rlx64(kvf_h + (64 + qq) * 2 + (lane & 1), old, 0);
                __syncwarp();
                if (lane == 0) mbar_arrive(bar + 8 * BAR_PREP);
            }
            int n = 0;
#pragma unroll 1
            while (__any_sync(~0u, (int)(ld_acq(scr->xcnt + bi_j * 32) - (epoch1 << 7)) < 0)) { if (++n > SPIN_LIMIT) break; }
            uint4 ur[8];
#pragma unroll
            for (int v = 0; v < 8; v++) ur[v] = __ldcg(scr->xt + bi * 1024 + st + 128 * v);
            mbar_wait(bar + 8 * BAR_SP, 0);
            if (lane < 16) sts128(ub - 256 + lane * 16, 0, 0, 0, 0);
            if (lane < 2) sts128(buf + lane * W3_OFF, 0, 0, 0, 0);
#pragma unroll
            for (int v = 0; v < 8; v++) {
                const int ci = (st >> 2) + 32 * v;
                sts128(sb + OFF_U + (st & 3) * U_STRIDE + 256 + ((ci ^ ((ci >> 3) & 1)) << 4), ur[v].x, ur[v].y, ur[v].z, ur[v].w);
            }
            __syncwarp();
            if (lane == 0) mbar_arrive(bar + 8 * BAR_UR);
            mbar_wait(bar + 8 * BAR_UR, 0);
            windows(5, 4);
        }
        mbar_wait(bar + 8 * BAR_SP2, 0);
        windows(3, 0);
        __syncwarp();
        if (lane == 0) mbar_arrive(bar + 8 * BAR_WR);
        {
            const bool zw = st < 32 && !(bi_i & 1);
            const uint4* src = scr->kvp + bi_j * (16 * 544) + (bi_i >> 2) * 136;
            const uint4* zsrc = src + (lane >> 2) * (2 * 544) + 128 + (lane & 1) * 4 + qq;
            src += (lane >> 3) * (4 * 544) + ((lane >> 1) & 3) * 32 + (bi_i & 3) * 8 + w4 * 2 + (lane & 1);
            mbar_wait(bar + 8 * BAR_PUB, 0);
            uint4 v[6];
#pragma unroll
            for (int k = 0; k < 6; k++) v[k] = make_uint4(tag ^ 1u, 0, 0, 0);
            int n = 0;
#pragma unroll 1
            while (true) {
#pragma unroll
                for (int k = 0; k < 6; k++) if ((bad4(v[k], tag) & 1) && (k < 4 || zw)) v[k] = ld_rlx128(k < 4 ? src + k * 544 : zsrc + (k - 4) * 544);
                if (!__any_sync(~0u, (bad4(v[0], tag) | bad4(v[1], tag) | bad4(v[2], tag) | bad4(v[3], tag) | (zw ? bad4(v[4], tag) | bad4(v[5], tag) : 0u)) & 1)) break;
                if (++n > SPIN_LIMIT) break;
            }
            float f[8];
            const float* vf = (const float*)v;
#pragma unroll
            for (int r = 0; r < 4; r++) {
                f[r] = (vf[r] + vf[4 + r]) + (vf[8 + r] + vf[12 + r]);
                f[4 + r] = vf[16 + r] + vf[20 + r];
                f[4 + r] += __shfl_xor_sync(~0u, f[4 + r], 4);
            }
#pragma unroll
            for (int o = 8; o <= 16; o <<= 1)
#pragma unroll
                for (int r = 0; r < 8; r++) f[r] += __shfl_xor_sync(~0u, f[r], o);
            if (lane < 8) st_rlx64(kvf_h + ((bi_i & 3) * 8 + w4 * 2 + (lane & 1)) * 4 + (lane >> 1), tagw(pack2(f[0], f[1]), tag), pack2(f[2], f[3]));
            if (zw && lane < 4) st_rlx64(kvf_h + (64 + qq) * 2 + (lane & 1), tagw(pack2(f[4], f[5]), tag), pack2(f[6], f[7]));
        }
        {
            const uint4* kp = scr->kvf + bi_j * 272 + st;
            uint4 v0 = make_uint4(tag ^ 1u, 0, 0, 0), v1 = v0, v2 = make_uint4(st < 16 ? tag ^ 1u : tag, 0, tag, 0);
            int n = 0;
#pragma unroll 1
            while (true) {
                if (bad4(v0, tag) & 1) v0 = ld_rlx128(kp);
                if (bad4(v1, tag) & 1) v1 = ld_rlx128(kp + 128);
                if (bad4(v2, tag) & 1) v2 = ld_rlx128(kp + 256);
                if (!__any_sync(~0u, (bad4(v0, tag) | bad4(v1, tag) | bad4(v2, tag)) & 1)) break;
                if (++n > SPIN_LIMIT) break;
            }
            sts128(sb + OFF_KVF + st * 16, v0.x, v0.y, v0.z, v0.w);
            sts128(sb + OFF_KVF + 2048 + st * 16, v1.x, v1.y, v1.z, v1.w);
            if (st < 16) sts128(sb + OFF_KVF + 4096 + st * 16, v2.x, v2.y, v2.z, v2.w);
            __syncwarp();
            if (lane == 0) mbar_arrive(bar + 8 * BAR_KVF);
        }
        if (warp == 13) {
            mbar_wait(bar + 8 * BAR_KVF, 0);
            if (lane == 0) {
                mbar_expect(bar + 8 * BAR_WO2, 65536);
                tma2d(sb + OFF_P, &mwo, (bi_j & 3) * 128 + 64, 256, bar + 8 * BAR_WO2);
                tma2d(sb + OFF_V, &mwo, (bi_j & 3) * 128, 256, bar + 8 * BAR_WO2);
            }
        }
    }
    __syncwarp();
    if (lane == 0) {
        unsigned old;
        asm volatile("atom.acq_rel.cta.shared.add.u32 %0,[%1],1;" : "=r"(old) : "r"(bar + OFF_CNT) : "memory");
        if (old == 15) {
            atomicAdd(scr->done, 1u);
        }
    }
}

typedef CUresult (*EncFn)(CUtensorMap*, CUtensorMapDataType, cuuint32_t, void*, const cuuint64_t*, const cuuint64_t*, const cuuint32_t*,
                          const cuuint32_t*, CUtensorMapInterleave, CUtensorMapSwizzle, CUtensorMapL2promotion, CUtensorMapFloatOOBfill);

extern "C" void kernel_launch(void* const* d_in, const int* in_sizes, int n_in, void* d_out, int out_size) {
    static EncFn enc = nullptr;
    static Scratch* scr = nullptr;
    if (!enc) {
        cudaGetSymbolAddress((void**)&scr, g_scr);
        cudaDriverEntryPointQueryResult qr;
        cudaGetDriverEntryPoint("cuTensorMapEncodeTiled", (void**)&enc, cudaEnableDefault, &qr);
        cudaFuncSetAttribute(fused_kernel, cudaFuncAttributeMaxDynamicSharedMemorySize, SMEM_BYTES);
    }
    CUtensorMap mx, mw, mwo;
    const cuuint32_t es[3] = {1, 1, 1};
    {
        cuuint64_t d[2] = {512, 2048}, s[1] = {1024}; cuuint32_t b[2] = {64, 128};
        enc(&mx, CU_TENSOR_MAP_DATA_TYPE_BFLOAT16, 2, d_in[0], d, s, b, es, CU_TENSOR_MAP_INTERLEAVE_NONE, CU_TENSOR_MAP_SWIZZLE_128B,
            CU_TENSOR_MAP_L2_PROMOTION_L2_128B, CU_TENSOR_MAP_FLOAT_OOB_FILL_NONE);
    }
    {
        cuuint64_t d[3] = {512, 512, 3}, s[2] = {3072, 1024}; cuuint32_t b[3] = {64, 64, 3};
        enc(&mw, CU_TENSOR_MAP_DATA_TYPE_BFLOAT16, 3, d_in[1], d, s, b, es, CU_TENSOR_MAP_INTERLEAVE_NONE, CU_TENSOR_MAP_SWIZZLE_128B,
            CU_TENSOR_MAP_L2_PROMOTION_L2_128B, CU_TENSOR_MAP_FLOAT_OOB_FILL_NONE);
    }
    {
        cuuint64_t d[2] = {512, 512}, s[1] = {1024}; cuuint32_t b[2] = {64, 256};
        enc(&mwo, CU_TENSOR_MAP_DATA_TYPE_BFLOAT16, 2, d_in[3], d, s, b, es, CU_TENSOR_MAP_INTERLEAVE_NONE, CU_TENSOR_MAP_SWIZZLE_128B,
            CU_TENSOR_MAP_L2_PROMOTION_L2_128B, CU_TENSOR_MAP_FLOAT_OOB_FILL_NONE);
    }
    fused_kernel<<<128, 512, SMEM_BYTES, cudaStreamPerThread>>>(
        scr, (const bf16*)d_in[5], (const bf16*)d_in[6], (const bf16*)d_in[7], (const bf16*)d_in[8], (const bf16*)d_in[9],
        (const bf16*)d_in[10], (const bf16*)d_in[2], (const bf16*)d_in[11], (bf16*)d_out, mx, mw, mwo);
}
```

```cpp
#include <cuda_runtime.h>
#include <cuda.h>
#include <cuda_bf16.h>
#include <stdint.h>

typedef __nv_bfloat16 bf16;

struct Scratch {
    uint4 xt[128 * 1024];
    uint4 o[16 * 8 * 32 * 32];
    uint4 y[128 * 1024];
    uint4 kvp[8 * 16 * 544];
    uint4 kvf[8 * 4 * 68];
    unsigned g[1024 * 8];
    unsigned yflag[128 * 8];
    unsigned xcnt[8 * 32];
    unsigned done[32];
};
__device__ Scratch g_scr;
#define STAMP(n)

constexpr int SLOT = 40960;
constexpr int OFF_SP0 = 32768, OFF_SP1 = SLOT + 32768;
constexpr int OFF_P = 2 * SLOT, OFF_V = OFF_P + 32768;
constexpr int OFF_KVF = OFF_V + 32768;
constexpr int KT_BYTES = 3264, KW_D = 16, KW_2 = 560, KW_3 = 656;
constexpr int OFF_U = 4 * SLOT, U_STRIDE = 4096 + 256 + 32;
constexpr int OFF_K = OFF_U + 4 * U_STRIDE;
constexpr int OFF_BUF = OFF_K + 4 * KT_BYTES, BUF_STRIDE = 8320;
constexpr int OFF_WPHI = OFF_BUF + 4 * BUF_STRIDE;
constexpr int OFF_GW = OFF_WPHI + 2048;
constexpr int OFF_BAR = OFF_GW + 1024;
constexpr int SMEM_BYTES = OFF_BAR + 256 + 256;
static_assert(SMEM_BYTES <= 232448 && OFF_BUF % 128 == 0 && OFF_U + 4 * 7296 <= OFF_BUF, "smem");
constexpr int W5_OFF = 0, W3_OFF = 3088, W9_OFF = 6176;
constexpr int BAR_FULL = 0, BAR_EMPTY = 4, BAR_WPHI = 8, BAR_WO = 9, BAR_WO2 = 10, BAR_XT = 11, BAR_DONE = 12, BAR_KG = 13, BAR_SP = 14,
              BAR_PUB = 15, BAR_KVF = 16, BAR_UR = 17, BAR_WR = 18, BAR_PREP = 19, BAR_KGA = 20, BAR_SP2 = 21, OFF_CNT = 192;
constexpr int SPIN_LIMIT = 1 << 17;

__device__ __forceinline__ uint32_t s2u(const void* p) { return (uint32_t)__cvta_generic_to_shared(p); }
__device__ __forceinline__ void mbar_init(uint32_t b, int c) { asm volatile("mbarrier.init.shared::cta.b64 [%0],%1;" ::"r"(b), "r"(c) : "memory"); }
__device__ __forceinline__ void mbar_expect(uint32_t b, int bytes) { asm volatile("mbarrier.arrive.expect_tx.shared::cta.b64 _,[%0],%1;" ::"r"(b), "r"(bytes) : "memory"); }
__device__ __forceinline__ void mbar_arrive(uint32_t b) { asm volatile("mbarrier.arrive.shared::cta.b64 _,[%0];" ::"r"(b) : "memory"); }
__device__ __forceinline__ void mbar_wait(uint32_t b, int ph) {
    asm volatile("{\n.reg .pred p;\n.reg .u32 n;\nmov.u32 n,0;\nLW_%=:\nmbarrier.try_wait.parity.shared::cta.b64 p,[%0],%1;\n@p bra LD_%=;\n"
                 "add.u32 n,n,1;\nsetp.lt.u32 p,n,16384;\n@p bra LW_%=;\nLD_%=:\n}" ::"r"(b), "r"(ph) : "memory");
}
__device__ __forceinline__ void tma2d(uint32_t dst, const CUtensorMap* m, int c0, int c1, uint32_t bar) {
    asm volatile("cp.async.bulk.tensor.2d.shared::cluster.global.mbarrier::complete_tx::bytes [%0],[%1,{%3,%4}],[%2];" ::"r"(dst), "l"(m), "r"(bar), "r"(c0), "r"(c1) : "memory");
}
__device__ __forceinline__ void tma3d(uint32_t dst, const CUtensorMap* m, int c0, int c1, int c2, uint32_t bar) {
    asm volatile("cp.async.bulk.tensor.3d.shared::cluster.global.mbarrier::complete_tx::bytes [%0],[%1,{%3,%4,%5}],[%2];" ::"r"(dst), "l"(m), "r"(bar), "r"(c0), "r"(c1), "r"(c2) : "memory");
}
__device__ __forceinline__ void bulk_g2s(uint32_t dst, const void* src, int bytes, uint32_t bar) {
    asm volatile("cp.async.bulk.shared::cluster.global.mbarrier::complete_tx::bytes [%0],[%1],%2,[%3];" ::"r"(dst), "l"(src), "r"(bytes), "r"(bar) : "memory");
}
__device__ __forceinline__ uint64_t mkdesc(uint32_t addr, uint32_t lbo, uint32_t sbo) {
    return (uint64_t)((addr & 0x3FFFF) >> 4) | ((uint64_t)(lbo >> 4) << 16) | ((uint64_t)(sbo >> 4) << 32) | ((uint64_t)1 << 62);
}
__device__ __forceinline__ void wg_fence() { asm volatile("wgmma.fence.sync.aligned;" ::: "memory"); }
__device__ __forceinline__ void wg_commit() { asm volatile("wgmma.commit_group.sync.aligned;" ::: "memory"); }
template <int N> __device__ __forceinline__ void wg_wait() { asm volatile("wgmma.wait_group.sync.aligned %0;" ::"n"(N) : "memory"); }
template <int N> __device__ __forceinline__ void fence_regs(float* d) {
#pragma unroll
    for (int i = 0; i < N; i++) asm volatile("" : "+f"(d[i])::"memory");
}
#define R8(d, o) "+f"(d[o]), "+f"(d[o + 1]), "+f"(d[o + 2]), "+f"(d[o + 3]), "+f"(d[o + 4]), "+f"(d[o + 5]), "+f"(d[o + 6]), "+f"(d[o + 7])
__device__ __forceinline__ void wgmma192(float* d, uint64_t da, uint64_t db, int sc) {
    asm volatile("{.reg .pred p; setp.ne.b32 p,%98,0; wgmma.mma_async.sync.aligned.m64n192k16.f32.bf16.bf16 {"
                 "%0,%1,%2,%3,%4,%5,%6,%7,%8,%9,%10,%11,%12,%13,%14,%15,%16,%17,%18,%19,%20,%21,%22,%23,%24,%25,%26,%27,%28,%29,%30,%31,"
                 "%32,%33,%34,%35,%36,%37,%38,%39,%40,%41,%42,%43,%44,%45,%46,%47,%48,%49,%50,%51,%52,%53,%54,%55,%56,%57,%58,%59,%60,%61,%62,%63,"
                 "%64,%65,%66,%67,%68,%69,%70,%71,%72,%73,%74,%75,%76,%77,%78,%79,%80,%81,%82,%83,%84,%85,%86,%87,%88,%89,%90,%91,%92,%93,%94,%95},"
                 "%96,%97,p,1,1,0,1;}"
                 : R8(d, 0), R8(d, 8), R8(d, 16), R8(d, 24), R8(d, 32), R8(d, 40), R8(d, 48), R8(d, 56), R8(d, 64), R8(d, 72), R8(d, 80), R8(d, 88)
                 : "l"(da), "l"(db), "r"(sc));
}
__device__ __forceinline__ void wgmma64_tt(float* d, uint64_t da, uint64_t db, int sc) {
    asm volatile("{.reg .pred p; setp.ne.b32 p,%34,0; wgmma.mma_async.sync.aligned.m64n64k16.f32.bf16.bf16 {"
                 "%0,%1,%2,%3,%4,%5,%6,%7,%8,%9,%10,%11,%12,%13,%14,%15,%16,%17,%18,%19,%20,%21,%22,%23,%24,%25,%26,%27,%28,%29,%30,%31},"
                 "%32,%33,p,1,1,1,1;}"
                 : R8(d, 0), R8(d, 8), R8(d, 16), R8(d, 24)
                 : "l"(da), "l"(db), "r"(sc));
}
__device__ __forceinline__ void wgmma128_rs(float* d, const uint4& a, uint64_t db, int sc) {
    asm volatile("{.reg .pred p; setp.ne.b32 p,%69,0; wgmma.mma_async.sync.aligned.m64n128k16.f32.bf16.bf16 {"
                 "%0,%1,%2,%3,%4,%5,%6,%7,%8,%9,%10,%11,%12,%13,%14,%15,%16,%17,%18,%19,%20,%21,%22,%23,%24,%25,%26,%27,%28,%29,%30,%31,"
                 "%32,%33,%34,%35,%36,%37,%38,%39,%40,%41,%42,%43,%44,%45,%46,%47,%48,%49,%50,%51,%52,%53,%54,%55,%56,%57,%58,%59,%60,%61,%62,%63},"
                 "{%64,%65,%66,%67},%68,p,1,1,1;}"
                 : R8(d, 0), R8(d, 8), R8(d, 16), R8(d, 24), R8(d, 32), R8(d, 40), R8(d, 48), R8(d, 56)
                 : "r"(a.x), "r"(a.y), "r"(a.z), "r"(a.w), "l"(db), "r"(sc));
}
__device__ __forceinline__ void wgmma48_rs(float* d, uint32_t a0, uint32_t a1, uint32_t a2, uint32_t a3, uint64_t db) {
    asm volatile("wgmma.mma_async.sync.aligned.m64n48k16.f32.bf16.bf16 {%0,%1,%2,%3,%4,%5,%6,%7,%8,%9,%10,%11,%12,%13,%14,%15,%16,%17,%18,%19,%20,%21,%22,%23},{%24,%25,%26,%27},%28,1,1,1,0;"
                 : R8(d, 0), R8(d, 8), R8(d, 16) : "r"(a0), "r"(a1), "r"(a2), "r"(a3), "l"(db));
}
__device__ __forceinline__ void mma16816(float* c, uint32_t a0, uint32_t a1, uint32_t a2, uint32_t a3, uint32_t b0, uint32_t b1) {
    asm("mma.sync.aligned.m16n8k16.row.col.f32.bf16.bf16.f32 {%0,%1,%2,%3},{%4,%5,%6,%7},{%8,%9},{%0,%1,%2,%3};"
        : "+f"(c[0]), "+f"(c[1]), "+f"(c[2]), "+f"(c[3]) : "r"(a0), "r"(a1), "r"(a2), "r"(a3), "r"(b0), "r"(b1));
}
__device__ __forceinline__ void ldsm4(uint32_t* r, uint32_t a) {
    asm volatile("ldmatrix.sync.aligned.m8n8.x4.shared.b16 {%0,%1,%2,%3},[%4];" : "=r"(r[0]), "=r"(r[1]), "=r"(r[2]), "=r"(r[3]) : "r"(a) : "memory");
}
__device__ __forceinline__ void ldsm4t(uint32_t* r, uint32_t a) {
    asm volatile("ldmatrix.sync.aligned.m8n8.x4.trans.shared.b16 {%0,%1,%2,%3},[%4];" : "=r"(r[0]), "=r"(r[1]), "=r"(r[2]), "=r"(r[3]) : "r"(a) : "memory");
}
__device__ __forceinline__ void stsm4(uint32_t a, uint32_t r0, uint32_t r1, uint32_t r2, uint32_t r3) {
    asm volatile("stmatrix.sync.aligned.m8n8.x4.shared.b16 [%0],{%1,%2,%3,%4};" ::"r"(a), "r"(r0), "r"(r1), "r"(r2), "r"(r3) : "memory");
}
__device__ __forceinline__ uint32_t lds32(uint32_t a) { uint32_t v; asm volatile("ld.shared.b32 %0,[%1];" : "=r"(v) : "r"(a) : "memory"); return v; }
__device__ __forceinline__ uint4 lds128(uint32_t a) { uint4 v; asm volatile("ld.shared.v4.b32 {%0,%1,%2,%3},[%4];" : "=r"(v.x), "=r"(v.y), "=r"(v.z), "=r"(v.w) : "r"(a) : "memory"); return v; }
__device__ __forceinline__ void sts16(uint32_t a, uint32_t v) { asm volatile("st.shared.b16 [%0],%1;" ::"r"(a), "h"((unsigned short)v) : "memory"); }
__device__ __forceinline__ void sts32(uint32_t a, uint32_t v) { asm volatile("st.shared.b32 [%0],%1;" ::"r"(a), "r"(v) : "memory"); }
__device__ __forceinline__ void sts64(uint32_t a, uint32_t x, uint32_t y) { asm volatile("st.shared.v2.b32 [%0],{%1,%2};" ::"r"(a), "r"(x), "r"(y) : "memory"); }
__device__ __forceinline__ void sts128(uint32_t a, uint32_t x, uint32_t y, uint32_t z, uint32_t w) { asm volatile("st.shared.v4.b32 [%0],{%1,%2,%3,%4};" ::"r"(a), "r"(x), "r"(y), "r"(z), "r"(w) : "memory"); }
__device__ __forceinline__ uint32_t pack2(float lo, float hi) { uint32_t d; asm("cvt.rn.bf16x2.f32 %0,%1,%2;" : "=r"(d) : "f"(hi), "f"(lo)); return d; }
__device__ __forceinline__ float bf_lo(uint32_t v) { return __uint_as_float(v << 16); }
__device__ __forceinline__ float bf_hi(uint32_t v) { return __uint_as_float(v & 0xffff0000u); }
__device__ __forceinline__ float bf_round(float v) { return bf_lo(pack2(v, 0.f)); }
__device__ __forceinline__ uint32_t hmax2(uint32_t a, uint32_t b) { uint32_t d; asm("max.bf16x2 %0,%1,%2;" : "=r"(d) : "r"(a), "r"(b)); return d; }
__device__ __forceinline__ uint32_t hmin2(uint32_t a, uint32_t b) { uint32_t d; asm("min.bf16x2 %0,%1,%2;" : "=r"(d) : "r"(a), "r"(b)); return d; }
__device__ __forceinline__ uint32_t hmul2(uint32_t a, uint32_t b) { uint32_t d; asm("mul.rn.bf16x2 %0,%1,%2;" : "=r"(d) : "r"(a), "r"(b)); return d; }
__device__ __forceinline__ float ex2(float x) { float y; asm("ex2.approx.ftz.f32 %0,%1;" : "=f"(y) : "f"(x)); return y; }
__device__ __forceinline__ float rcp(float x) { float y; asm("rcp.approx.ftz.f32 %0,%1;" : "=f"(y) : "f"(x)); return y; }
__device__ __forceinline__ uint32_t ld_nc(const uint32_t* p) { uint32_t v; asm volatile("ld.global.nc.b32 %0,[%1];" : "=r"(v) : "l"(p)); return v; }
__device__ __forceinline__ uint2 ld_nc64(const uint2* p) { uint2 v; asm volatile("ld.global.nc.v2.b32 {%0,%1},[%2];" : "=r"(v.x), "=r"(v.y) : "l"(p)); return v; }
__device__ __forceinline__ unsigned ld_acq(const unsigned* p) { unsigned v; asm volatile("ld.acquire.gpu.global.u32 %0,[%1];" : "=r"(v) : "l"(p) : "memory"); return v; }
__device__ __forceinline__ unsigned ld_rlx(const unsigned* p) { unsigned v; asm volatile("ld.relaxed.gpu.global.u32 %0,[%1];" : "=r"(v) : "l"(p) : "memory"); return v; }
__device__ __forceinline__ uint2 ld_rlx64(const void* p) { uint2 v; asm volatile("{.reg .b64 t; ld.relaxed.gpu.global.b64 t,[%2]; mov.b64 {%0,%1},t;}" : "=r"(v.x), "=r"(v.y) : "l"(p) : "memory"); return v; }
__device__ __forceinline__ uint4 ld_rlx128(const void* p) {
    uint4 v;
    asm volatile("{.reg .b64 t,u; ld.relaxed.gpu.global.v2.b64 {t,u},[%4]; mov.b64 {%0,%1},t; mov.b64 {%2,%3},u;}" : "=r"(v.x), "=r"(v.y), "=r"(v.z), "=r"(v.w) : "l"(p) : "memory");
    return v;
}
__device__ __forceinline__ void st_rlx32(void* p, uint32_t x) { asm volatile("st.relaxed.gpu.global.u32 [%0],%1;" ::"l"(p), "r"(x) : "memory"); }
__device__ __forceinline__ void st_rlx64(void* p, uint32_t x, uint32_t y) { asm volatile("{.reg .b64 t; mov.b64 t,{%1,%2}; st.relaxed.gpu.global.b64 [%0],t;}" ::"l"(p), "r"(x), "r"(y) : "memory"); }
__device__ __forceinline__ void st_rlx128(void* p, uint4 v) {
    asm volatile("{.reg .b64 t,u; mov.b64 t,{%1,%2}; mov.b64 u,{%3,%4}; st.relaxed.gpu.global.v2.b64 [%0],{t,u};}" ::"l"(p), "r"(v.x), "r"(v.y), "r"(v.z), "r"(v.w) : "memory");
}
__device__ __forceinline__ uint32_t tagw(uint32_t w, uint32_t tag) { return (w & ~1u) | tag; }
__device__ __forceinline__ uint4 tag4(uint32_t x, uint32_t y, uint32_t z, uint32_t w, uint32_t tag) { return make_uint4(tagw(x, tag), y, tagw(z, tag), w); }
__device__ __forceinline__ uint32_t bad4(const uint4& v, uint32_t tag) { return (v.x ^ tag) | (v.z ^ tag); }
__device__ __forceinline__ void bar_named(int id, int n) { asm volatile("bar.sync %0,%1;" ::"r"(id), "r"(n) : "memory"); }

struct cf { float re, im; };
__device__ __forceinline__ cf cmul(cf a, cf b) { cf r; r.re = a.re * b.re - a.im * b.im; r.im = a.re * b.im + a.im * b.re; return r; }
__device__ __forceinline__ cf cexp_p(float arl, float ait, float p) {
    float mag = ex2(arl * p);
    float t = ait * p;
    t = (t - rintf(t)) * 6.283185307179586f;
    cf r; r.re = mag * __cosf(t); r.im = mag * __sinf(t);
    return r;
}

__device__ __forceinline__ void hedgehog4(const uint32_t* a, uint32_t wphi_addr, uint32_t (*out)[8]) {
    float p[4][2][4], mx[4][2];
#pragma unroll
    for (int h = 0; h < 4; h++) {
        uint32_t b[4];
        ldsm4t(b, wphi_addr + h * 512);
        float c0[4] = {0.f, 0.f, 0.f, 0.f}, c1[4] = {0.f, 0.f, 0.f, 0.f};
        mma16816(c0, a[4 * h], a[4 * h + 1], a[4 * h + 2], a[4 * h + 3], b[0], b[1]);
        mma16816(c1, a[4 * h], a[4 * h + 1], a[4 * h + 2], a[4 * h + 3], b[2], b[3]);
#pragma unroll
        for (int k = 0; k < 2; k++) {
            p[h][k][0] = c0[2 * k]; p[h][k][1] = c0[2 * k + 1]; p[h][k][2] = c1[2 * k]; p[h][k][3] = c1[2 * k + 1];
            mx[h][k] = fmaxf(fmaxf(p[h][k][0], p[h][k][1]), fmaxf(p[h][k][2], p[h][k][3]));
        }
    }
#pragma unroll
    for (int o = 1; o <= 2; o <<= 1)
#pragma unroll
        for (int h = 0; h < 4; h++)
#pragma unroll
            for (int k = 0; k < 2; k++) mx[h][k] = fmaxf(mx[h][k], __shfl_xor_sync(~0u, mx[h][k], o));
    const float L = 1.4426950408889634f;
    float pmin = 1.f;
#pragma unroll
    for (int h = 0; h < 4; h++)
#pragma unroll
        for (int k = 0; k < 2; k++) {
            const float m = -mx[h][k] * L;
            const float e0 = ex2(fmaf(p[h][k][0], L, m)), e1 = ex2(fmaf(p[h][k][1], L, m)), e2 = ex2(fmaf(p[h][k][2], L, m)), e3 = ex2(fmaf(p[h][k][3], L, m));
            const float p01 = e0 * e1, p23 = e2 * e3, pp = p01 * p23, r = rcp(pp), r01 = r * p23, r23 = r * p01;
            pmin = fminf(pmin, pp);
            out[h][k] = pack2(e0, e1); out[h][k + 2] = pack2(e2, e3);
            out[h][4 + k] = pack2(r01 * e1, r01 * e0); out[h][4 + k + 2] = pack2(r23 * e3, r23 * e2);
        }
    if (__builtin_expect(__any_sync(~0u, !(pmin > 1e-18f)), 0)) {
#pragma unroll
        for (int h = 0; h < 4; h++)
#pragma unroll
            for (int k = 0; k < 2; k++) {
                float m = fminf(fminf(p[h][k][0], p[h][k][1]), fminf(p[h][k][2], p[h][k][3]));
                m = fminf(m, __shfl_xor_sync(~0u, m, 1));
                m = fminf(m, __shfl_xor_sync(~0u, m, 2)) * L;
                out[h][4 + k] = pack2(ex2(fmaf(p[h][k][0], -L, m)), ex2(fmaf(p[h][k][1], -L, m)));
                out[h][4 + k + 2] = pack2(ex2(fmaf(p[h][k][2], -L, m)), ex2(fmaf(p[h][k][3], -L, m)));
            }
    }
}

__global__ void __launch_bounds__(512, 1)
fused_kernel(Scratch* __restrict__ scr, const bf16* __restrict__ logA, const bf16* __restrict__ Aim, const bf16* __restrict__ Cre,
             const bf16* __restrict__ Cim, const bf16* __restrict__ logdt, const bf16* __restrict__ Dskip, const bf16* __restrict__ wphi,
             const bf16* __restrict__ gatew, bf16* __restrict__ out, const bf16* __restrict__ x,
             const __grid_constant__ CUtensorMap mx, const __grid_constant__ CUtensorMap mw, const __grid_constant__ CUtensorMap mwo) {
    extern __shared__ __align__(1024) uint8_t smem[];
    constexpr uint32_t sb = 1024;
    const int tid = threadIdx.x, warp = __shfl_sync(~0u, tid >> 5, 0), lane = tid & 31;
    const int g = lane >> 2, q = lane & 3, w4 = warp & 3;
    const int bi = blockIdx.x, bi_i = bi & 15, bi_j = bi >> 4;
    const uint32_t bar = sb + OFF_BAR;
    const int rot = (bi_j & 3) * 2, xkb = bi_j >> 2;
    auto load_stage = [&](int kb) {
        const uint32_t b = bar + 8 * (BAR_FULL + (kb & 3)), d = sb + (kb & 3) * SLOT;
        const int kc = ((kb + rot) & 7) * 64;
        mbar_expect(b, SLOT);
        tma2d(d, &mx, kc, bi_i * 128, b);
        tma3d(d + 16384, &mw, bi_j * 64, kc, 0, b);
    };

    const int ch = bi * 4 + w4;
    uint2 pla, pai, pcr, pci; uint32_t pdt = 0, pds = 0;
    if (warp >= 8) {
        pla = ld_nc64((const uint2*)logA + ch * 32 + lane); pai = ld_nc64((const uint2*)Aim + ch * 32 + lane);
        pcr = ld_nc64((const uint2*)Cre + ch * 32 + lane); pci = ld_nc64((const uint2*)Cim + ch * 32 + lane);
        pdt = ld_nc((const uint32_t*)logdt + (ch >> 1)); pds = ld_nc((const uint32_t*)Dskip + (ch >> 1));
    }
    unsigned done0 = ld_rlx(scr->done);
    if (tid == 0) {
        for (int s = 0; s < 4; s++) mbar_init(bar + 8 * (BAR_FULL + s), 1);
        asm volatile("fence.mbarrier_init.release.cluster;" ::: "memory");
        asm volatile("prefetch.tensormap [%0];" ::"l"(&mx) : "memory");
#pragma unroll 1
        for (int s = 0; s < 4; s++) load_stage(s);
        STAMP(11);
    } else if (tid == 32) {
        if (s2u(smem) != sb) __trap();
        sts32(bar + OFF_CNT, 0);
        for (int s = 0; s < 4; s++) mbar_init(bar + 8 * (BAR_EMPTY + s), 8);
        mbar_init(bar + 8 * BAR_WPHI, 1); mbar_init(bar + 8 * BAR_WO, 2); mbar_init(bar + 8 * BAR_WO2, 1); mbar_init(bar + 8 * BAR_XT, 4);
        mbar_init(bar + 8 * BAR_DONE, 8); mbar_init(bar + 8 * BAR_SP, 1); mbar_init(bar + 8 * BAR_PUB, 8);
        mbar_init(bar + 8 * BAR_KVF, 4); mbar_init(bar + 8 * BAR_UR, 4); mbar_init(bar + 8 * BAR_WR, 4); mbar_init(bar + 8 * BAR_PREP, 3); mbar_init(bar + 8 * BAR_KGA, 4); mbar_init(bar + 8 * BAR_SP2, 1);
        asm volatile("fence.mbarrier_init.release.cluster;" ::: "memory");
        mbar_expect(bar + 8 * BAR_WPHI, 3072);
        bulk_g2s(sb + OFF_GW, gatew, 1024, bar + 8 * BAR_WPHI);
        bulk_g2s(sb + OFF_WPHI, wphi + bi_j * 1024, 2048, bar + 8 * BAR_WPHI);
    } else if (tid == 64) {
        asm volatile("prefetch.tensormap [%0];" ::"l"(&mw) : "memory");
    }
    const uint32_t buf = sb + OFF_BUF + w4 * BUF_STRIDE, kb_ = sb + OFF_K + w4 * KT_BYTES;
    __syncthreads();
    asm volatile("" : "+r"(pdt), "+r"(done0)::"memory");
    const unsigned epoch1 = (done0 >> 7) + 1u;
    const uint32_t tag = epoch1 & 1u;

    const int st = tid & 127;
    const uint32_t ub = sb + OFF_U + w4 * U_STRIDE + 256, spare = sb + (w4 < 2 ? OFF_SP0 : OFF_SP1) + (w4 & 1) * 4096;

    float kc[24];
    if (warp >= 8) {
#pragma unroll
        for (int t = 0; t < 24; t++) kc[t] = 0.f;
        fence_regs<24>(kc);
        const float dt = bf_round(expf((ch & 1) ? bf_hi(pdt) : bf_lo(pdt)));
        const bool hw = warp >= 12;
        const uint32_t stg0 = hw ? sb + OFF_U : sb + OFF_BUF, sstr = hw ? 7296 : BUF_STRIDE, stg = stg0 + w4 * sstr;
        const int brow = (stg >> 7) & 7;
#pragma unroll 1
        for (int it = hw ? 3 : 0; it < (hw ? 4 : 3); it++) {
            const int sh = (it & 1) * 16;
            auto pick = [&](const uint2& v) { return __uint_as_float(((it & 2 ? v.y : v.x) >> sh) << 16); };
            const float ea = bf_round(ex2(pick(pla) * 1.4426950408889634f));
            const float arl = (-ea * dt) * 1.4426950408889634f, ait = (pick(pai) * dt) * 0.15915494309189535f;
            cf C2; C2.re = 2.0f * (pick(pcr) * dt); C2.im = 2.0f * (pick(pci) * dt);
            const cf z1 = cexp_p(arl, ait, 1.0f), z128 = cexp_p(arl, ait, 128.0f);
            cf z8 = cexp_p(arl, ait, 8.0f); z8.im = -z8.im;
            const uint32_t lp = stg + lane * 4;
            auto put = [&](int row, const cf& v) { sts32((lp ^ (((row + brow) & 7) << 4)) + row * 128, pack2(v.re, v.im)); };
            {
                const cf z16 = cmul(z8, z8);
                cf e; e.re = 1.f; e.im = 0.f;
                cf o = z8;
                put(0, e); put(1, o);
                e = z16; put(2, e);
#pragma unroll
                for (int b = 3; b < 16; b += 2) {
                    o = cmul(o, z16); put(b, o);
                    if (b + 1 < 16) { e = cmul(e, z16); put(b + 1, e); }
                }
            }
            cf h[8];
            h[0] = C2; put(16, h[0]);
            {
                const cf z2 = cmul(z1, z1);
                h[1] = cmul(h[0], z1);
#pragma unroll
                for (int r = 2; r < 8; r++) h[r] = cmul(h[r - 2], z2);
#pragma unroll
                for (int r = 1; r < 8; r++) put(16 + r, h[r]);
            }
#pragma unroll
            for (int r = 0; r < 8; r++) { h[r] = cmul(h[r], z128); put(24 + r, h[r]); }
#pragma unroll
            for (int al = 0; al < 2; al++)
#pragma unroll
                for (int r = 0; r < 4; r++) { h[2 * r] = cmul(h[2 * r], z128); put(32 + al * 4 + r, h[2 * r]); }
#pragma unroll
            for (int al = 0; al < 4; al++)
#pragma unroll
                for (int r = 0; r < 2; r++) { h[4 * r] = cmul(h[4 * r], z128); put(40 + al * 2 + r, h[4 * r]); }
#pragma unroll
            for (int al = 0; al < 9; al++) { h[0] = cmul(h[0], z128); put(48 + al, h[0]); }
            asm volatile("fence.proxy.async.shared::cta;" ::: "memory");
            bar_named(hw ? 5 : 2, 128);
            uint32_t la[4][4];
#pragma unroll
            for (int ks = 0; ks < 4; ks++) ldsm4(la[ks], stg + (lane & 15) * 128 + (((2 * ks + (lane >> 4)) ^ ((lane + brow) & 7)) << 4));
            const uint64_t dh = mkdesc(stg0 + 2048, 16, 1024);
#pragma unroll
            for (int c = 0; c < 4; c++) {
                uint32_t a[4][4];
#pragma unroll
                for (int r = 0; r < 16; r++) a[r >> 2][r & 3] = (c == w4) ? la[r >> 2][r & 3] : 0u;
                wg_fence();
#pragma unroll
                for (int ks = 0; ks < 4; ks++) wgmma48_rs(kc, a[ks][0], a[ks][1], a[ks][2], a[ks][3], dh + c * (sstr >> 4) + 2 * ks);
                wg_commit();
            }
            wg_wait<0>();
            fence_regs<24>(kc);
            bar_named(hw ? 5 : 2, 128);
        }
        if (hw) {
#pragma unroll
            for (int t = 0; t < 6; t++)
                sts128(stg + (t * 32 + lane) * 16, __float_as_uint(kc[4 * t]), __float_as_uint(kc[4 * t + 1]), __float_as_uint(kc[4 * t + 2]), __float_as_uint(kc[4 * t + 3]));
            __syncwarp();
            if (lane == 0) mbar_arrive(bar + 8 * BAR_KGA);
        }
    }

    if (warp < 8) {
        const int wg = warp >> 2;
        if (warp == 0) STAMP(21);
        float acc[96];
        const int srow = warp * 16 + (lane & 15);
        const uint32_t srow_a = srow * 128;
        const int sx = srow & 7, shi = lane >> 4;
        const uint64_t da0 = mkdesc(sb + wg * 8192, 16, 1024), db0 = mkdesc(sb + 16384, 8192, 1024);
#pragma unroll 1
        for (int kb = 0; kb < 8; kb++) {
            const int s = kb & 3;
            const uint64_t da = da0 + s * (SLOT >> 4), db = db0 + s * (SLOT >> 4);
            if (warp == 0) STAMP(40 + kb);
            mbar_wait(bar + 8 * (BAR_FULL + s), kb >> 2);
            if (warp == 0) STAMP(32 + kb);
            wg_fence();
#pragma unroll
            for (int k = 0; k < 4; k++) wgmma192(acc, da + 2 * k, db + 128 * k, kb | k);
            wg_commit();
            wg_wait<1>();
            if (lane == 0 && kb > 0) mbar_arrive(bar + 8 * (BAR_EMPTY + ((kb - 1) & 3)));
        }
        mbar_wait(bar + 8 * BAR_WPHI, 0);
        wg_wait<0>();
        fence_regs<96>(acc);
        asm volatile("setmaxnreg.inc.sync.aligned.u32 160;");
        if (lane == 0) mbar_arrive(bar + 8 * BAR_DONE);
        if (warp == 0) STAMP(1);
        uint32_t in[16], qa[16];
        mbar_wait(bar + 8 * BAR_DONE, 0);
#pragma unroll
        for (int r = 0; r < 16; r++) {
            in[r] = pack2(acc[32 + 2 * r], acc[32 + 2 * r + 1]);
            qa[r] = pack2(acc[2 * r], acc[2 * r + 1]);
        }
#pragma unroll
        for (int hh = 0; hh < 4; hh++)
            stsm4(sb + OFF_V + (hh >> 1) * 16384 + srow_a + (((2 * (hh & 1) + shi) ^ sx) << 4), pack2(acc[64 + 8 * hh], acc[65 + 8 * hh]),
                  pack2(acc[66 + 8 * hh], acc[67 + 8 * hh]), pack2(acc[68 + 8 * hh], acc[69 + 8 * hh]), pack2(acc[70 + 8 * hh], acc[71 + 8 * hh]));
        sts128(sb + OFF_V + shi * 16384 + srow_a + ((4 ^ sx) << 4), 0x3f803f80u, 0x3f803f80u, 0x3f803f80u, 0x3f803f80u);
        const uint32_t wphi_a = sb + OFF_WPHI + (lane & 15) * 32 + (lane >> 4) * 16;
        uint32_t pq[4][8];
#pragma unroll 1
        for (int it = 0; it < 2; it++) {
            hedgehog4(in, wphi_a, pq);
            if (it == 1) break;
#pragma unroll
            for (int hs = 0; hs < 8; hs++) {
                float c[4] = {0.f, 0.f, 0.f, 0.f};
                const uint32_t* o = pq[hs >> 1] + 4 * (hs & 1);
                mma16816(c, o[0], o[1], o[2], o[3], 0x3f803f80u, 0x3f803f80u);
                const float r0 = rcp(c[0]), r1 = rcp(c[2]);
                const uint32_t s0 = pack2(r0, r0), s1 = pack2(r1, r1);
                stsm4(sb + OFF_P + (hs >> 2) * 16384 + srow_a + (((2 * (hs & 3) + shi) ^ sx) << 4), hmul2(o[0], s0), hmul2(o[1], s1), hmul2(o[2], s0), hmul2(o[3], s1));
            }
            asm volatile("fence.proxy.async.shared::cta;" ::: "memory");
            bar_named(1, 256);
            if (warp == 0) STAMP(2);
            float d[32];
            const uint64_t dv = mkdesc(sb + OFF_V + wg * 16384, 16, 1024), dp = mkdesc(sb + OFF_P + wg * 16384, 16, 1024);
            wg_fence();
#pragma unroll
            for (int k = 0; k < 8; k++) wgmma64_tt(d, dv + 128 * k, dp + 128 * k, k != 0);
            wg_commit();
            mbar_wait(bar + 8 * BAR_PREP, 0);
            uint4* kvp = scr->kvp + bi * 544 + wg * 272 + (w4 < 2 ? w4 * 136 : 128) + lane;
            wg_wait<0>();
            fence_regs<32>(d);
            if (w4 < 2 || (w4 == 2 && lane < 4)) {
#pragma unroll
                for (int f = 0; f < 4; f++) {
                    const int i0 = 8 * (f >> 1) + 2 * (f & 1), i2 = 16 * (f >> 1) + 8 * (f & 1);
                    const float e0 = w4 == 0 ? d[i0] : (w4 == 1 ? d[16 + i0] : d[i2]), e1 = w4 == 0 ? d[i0 + 1] : (w4 == 1 ? d[17 + i0] : d[i2 + 1]);
                    const float e2 = w4 == 0 ? d[i0 + 4] : (w4 == 1 ? d[20 + i0] : d[i2 + 4]), e3 = w4 == 0 ? d[i0 + 5] : (w4 == 1 ? d[21 + i0] : d[i2 + 5]);
                    st_rlx128(kvp + (w4 < 2 ? f * 32 : (f >> 1) * 136 + (f & 1) * 4), tag4(__float_as_uint(e0), __float_as_uint(e1), __float_as_uint(e2), __float_as_uint(e3), tag));
                }
            }
            __syncwarp();
            if (lane == 0) mbar_arrive(bar + 8 * BAR_PUB);
            if (warp == 0) STAMP(3);
#pragma unroll
            for (int r = 0; r < 16; r++) in[r] = qa[r];
        }
        if (warp == 0) STAMP(4);
        {
            mbar_wait(bar + 8 * BAR_KVF, 0);
            uint4 kf[4][3];
#pragma unroll
            for (int hh = 0; hh < 4; hh++) {
                const uint32_t a = sb + OFF_KVF + hh * 1088;
                kf[hh][0] = lds128(a + lane * 32); kf[hh][1] = lds128(a + lane * 32 + 16); kf[hh][2] = lds128(a + 1024 + q * 16);
            }
            if (warp == 0) STAMP(5);
            uint4* og = scr->o + ((bi_i * 8 + warp) * 32 + bi_j * 4) * 32 + lane;
#pragma unroll
            for (int hh = 0; hh < 4; hh++) {
                float c[6][4];
#pragma unroll
                for (int t = 0; t < 6; t++) { c[t][0] = c[t][1] = c[t][2] = c[t][3] = 0.f; }
                const uint32_t* a = pq[hh];
                const bool od = g & 1;
                mma16816(c[0], a[0], a[1], a[2], a[3], od ? 0x3f803f80u : kf[hh][2].x, od ? 0x3f803f80u : kf[hh][2].y);
                mma16816(c[1], a[4], a[5], a[6], a[7], od ? 0x3f803f80u : kf[hh][2].z, od ? 0x3f803f80u : kf[hh][2].w);
                mma16816(c[2], a[0], a[1], a[2], a[3], kf[hh][0].x, kf[hh][0].y);
                mma16816(c[3], a[0], a[1], a[2], a[3], kf[hh][0].z, kf[hh][0].w);
                mma16816(c[4], a[4], a[5], a[6], a[7], kf[hh][1].x, kf[hh][1].y);
                mma16816(c[5], a[4], a[5], a[6], a[7], kf[hh][1].z, kf[hh][1].w);
                uint32_t w[4];
#pragma unroll
                for (int k = 0; k < 2; k++) {
                    const float rho = c[0][2 * k + 1] * rcp(c[1][2 * k + 1]);
                    const float r = rcp(fmaf(c[0][2 * k + 1], 1e-6f, fmaf(rho, c[1][2 * k], c[0][2 * k]))), rr = r * rho;
                    w[k] = pack2(fmaf(c[4][2 * k], rr, c[2][2 * k] * r), fmaf(c[4][2 * k + 1], rr, c[2][2 * k + 1] * r));
                    w[2 + k] = pack2(fmaf(c[5][2 * k], rr, c[3][2 * k] * r), fmaf(c[5][2 * k + 1], rr, c[3][2 * k + 1] * r));
                }
                st_rlx128(og + hh * 32, tag4(w[0], w[1], w[2], w[3], tag));
            }
        }
        if (warp == 0) STAMP(6);
        float oc[64];
        const int slab = bi_i * 8 + (bi_j >> 2) * 4 + w4;
        const uint8_t* ysrc = (const uint8_t*)scr->y + (size_t)((bi_j & 3) * 32 + wg * 16 + (q >> 1)) * 16384 + slab * 128 + g * 16 + (q & 1) * 8;
        const unsigned* gp = scr->g + (slab * 8 + (g >> 1)) * 8 + (g & 1) * 4;
        uint2 yv[8]; unsigned g0, g1;
        {
            const uint4* osrc = scr->o + (slab * 32 + wg * 16) * 32 + lane;
            uint4 fr[16];
            const unsigned* probe = (const unsigned*)(osrc - lane + ((lane & 3) * 4 + 3) * 32 + 31) + 2;
            {
                unsigned miss = ~0u;
                int n = 0;
#pragma unroll
                for (int s = 0; s < 4; s++) {
#pragma unroll 1
                    while ((miss >> s) & 1) { miss = __ballot_sync(~0u, (ld_rlx(probe) ^ tag) & 1); if (++n > SPIN_LIMIT) break; }
#pragma unroll
                    for (int k = 4 * s; k < 4 * s + 4; k++) fr[k] = ld_rlx128(osrc + k * 32);
                }
            }
            if (warp == 0) STAMP(14);
            mbar_wait(bar + 8 * (wg ? BAR_WO2 : BAR_WO), 0);
            const uint64_t dw = mkdesc(sb + wg * 2 * SLOT, wg ? 32768 : SLOT, 1024);
#pragma unroll
            for (int s = 0; s < 4; s++) {
                int n = 0;
#pragma unroll 1
                while (__builtin_expect(__any_sync(~0u, (bad4(fr[4 * s], tag) | bad4(fr[4 * s + 1], tag) | bad4(fr[4 * s + 2], tag) | bad4(fr[4 * s + 3], tag)) & 1), 0)) {
#pragma unroll
                    for (int k = 4 * s; k < 4 * s + 4; k++) fr[k] = ld_rlx128(osrc + k * 32);
                    if (++n > SPIN_LIMIT) break;
                }
                wg_fence();
#pragma unroll
                for (int hh = 0; hh < 4; hh++) wgmma128_rs(oc, fr[4 * s + hh], dw + 128 * (4 * s + hh), (s | hh) != 0);
                wg_commit();
                if (s == 1) {
                    wg_wait<1>();
#pragma unroll
                    for (int nt = 0; nt < 8; nt++) yv[nt] = ld_rlx64(ysrc + nt * 32768);
                    g0 = ld_rlx(gp); g1 = ld_rlx(gp + 32);
                }
            }
            if (warp == 0) STAMP(7);
            {
                const unsigned* yprobe = scr->yflag + ((bi_j & 3) * 32 + wg * 16 + (lane & 15)) * 8;
                int n = 0;
#pragma unroll 1
                while (true) {
                    uint32_t bad = (g0 ^ tag) | (g1 ^ tag);
#pragma unroll
                    for (int nt = 0; nt < 8; nt++) bad |= yv[nt].x ^ tag;
                    if (!__any_sync(~0u, bad & 1)) break;
#pragma unroll 1
                    while (__any_sync(~0u, (ld_rlx(yprobe) ^ tag) & 1)) { if (++n > SPIN_LIMIT) break; }
#pragma unroll
                    for (int nt = 0; nt < 8; nt++) yv[nt] = ld_rlx64(ysrc + nt * 32768);
                    g0 = ld_rlx(gp); g1 = ld_rlx(gp + 32);
                    if (++n > SPIN_LIMIT) break;
                }
            }
            if (warp == 0) STAMP(28);
        }
        {
            const float ga = bf_hi(g0), gb = bf_hi(g1);
            const float ha = bf_round(1.0f - ga), hb = bf_round(1.0f - gb);
            float yb[32];
#pragma unroll
            for (int nt = 0; nt < 8; nt++) {
                yb[4 * nt] = ha * bf_lo(yv[nt].x); yb[4 * nt + 1] = ha * bf_hi(yv[nt].x);
                yb[4 * nt + 2] = hb * bf_lo(yv[nt].y); yb[4 * nt + 3] = hb * bf_hi(yv[nt].y);
            }
            fence_regs<32>(yb);
            const uint32_t xw = sb + wg * 2 * SLOT + (tid & 127) * 16, xr = sb + (wg ^ 1) * 2 * SLOT + (tid & 127) * 16;
            wg_wait<0>();
            fence_regs<64>(oc);
            bar_named(3 + wg, 128);
#pragma unroll
            for (int r = 0; r < 8; r++)
                sts128(xw + r * 2048, __float_as_uint(oc[32 + 4 * r]), __float_as_uint(oc[33 + 4 * r]), __float_as_uint(oc[34 + 4 * r]), __float_as_uint(oc[35 + 4 * r]));
#pragma unroll
            for (int r = 0; r < 32; r++) yb[r] = fmaf((r & 2) ? gb : ga, oc[r], yb[r]);
            bar_named(1, 256);
            if (warp == 0) STAMP(8);
            uint32_t w[8][2];
#pragma unroll
            for (int nt = 0; nt < 8; nt++) {
                const uint4 p = lds128(xr + nt * 2048);
                w[nt][0] = pack2(fmaf(ga, __uint_as_float(p.x), yb[4 * nt]), fmaf(ga, __uint_as_float(p.y), yb[4 * nt + 1]));
                w[nt][1] = pack2(fmaf(gb, __uint_as_float(p.z), yb[4 * nt + 2]), fmaf(gb, __uint_as_float(p.w), yb[4 * nt + 3]));
            }
            const uint32_t ob = sb + wg * 2 * SLOT + 16384 + w4 * 2048;
#pragma unroll
            for (int nt = 0; nt < 8; nt += 2)
                stsm4(ob + (lane & 15) * 128 + (((nt + shi) ^ (lane & 7)) << 4), w[nt][0], w[nt][1], w[nt + 1][0], w[nt + 1][1]);
            __syncwarp();
            bf16* op = out + (size_t)(slab * 16) * 512 + (bi_j & 3) * 128 + wg * 64 + (lane & 7) * 8;
#pragma unroll
            for (int it = 0; it < 4; it++) {
                const int r = it * 4 + (lane >> 3);
                uint4 v = lds128(ob + r * 128 + (((lane & 7) ^ (r & 7)) << 4));
                *(uint4*)(op + r * 512) = v;
            }
        }
        if (warp == 0) STAMP(10);
    } else if (warp < 12) {
        mbar_wait(bar + 8 * BAR_KGA, 0);
#pragma unroll
        for (int t = 0; t < 6; t++) {
            const uint4 v = lds128(sb + OFF_U + w4 * 7296 + (t * 32 + lane) * 16);
            kc[4 * t] += __uint_as_float(v.x); kc[4 * t + 1] += __uint_as_float(v.y); kc[4 * t + 2] += __uint_as_float(v.z); kc[4 * t + 3] += __uint_as_float(v.w);
        }
        fence_regs<24>(kc);
        bar_named(2, 128);
        if (st == 0) mbar_arrive(bar + 8 * BAR_SP);
        if (warp == 8) STAMP(17);
        if (st < 8) st_rlx32(scr->yflag + bi * 8 + st, tag ^ 1u);
#pragma unroll
        for (int v = 0; v < 7; v++) if (v * 32 + lane < KT_BYTES / 16) sts128(kb_ + (v * 32 + lane) * 16, 0, 0, 0, 0);
        __syncwarp();
        if (lane == 0) kc[4 * 0 + 0] += ((ch & 1) ? bf_hi(pds) : bf_lo(pds));
        const uint32_t k1024 = __shfl_sync(~0u, pack2(kc[4 * 4 + 0], 0.f), 0);
#pragma unroll
        for (int i = 0; i < 2; i++) {
            const int be = g + 8 * i;
#pragma unroll
            for (int t = 0; t < 2; t++) {
                const uint32_t a = kb_ + (KW_D + 128 * t + 8 * be + 2 * q) * 4;
                const uint32_t w = pack2(kc[4 * t + 2 * i + 1], kc[4 * t + 2 * i]);
                sts32(a + 4, w); sts16(a, w >> 16); sts16(a + 10, w);
            }
            {
                const int p = 256 + 128 * (q >> 1) + 8 * be + 4 * (q & 1);
                const uint32_t a = kb_ + (KW_D + p) * 4;
                const uint32_t w = pack2(kc[4 * 2 + 2 * i + 1], kc[4 * 2 + 2 * i]);
                const uint32_t aa = (w >> 16) | (w & 0xffff0000u);
                if (p != 256) { sts16(a - 4, aa); sts32(a, aa); } else sts16(a, aa);
                sts32(a + 4, aa); sts32(a + 8, w); sts16(a + 14, w);
            }
            {
                const int k = 64 + 16 * q + be;
                const uint32_t w = pack2(kc[4 * 3 + 2 * i], kc[4 * 3 + 2 * i + 1]);
                if (k != 64) sts16(kb_ + (KW_2 + ((k - 1) >> 1) - 24) * 4 + (k & 1) * 2, w);
                else {
                    const uint32_t a = kb_ + (KW_D + 511) * 4, aa = (w << 16) | (w & 0xffffu);
                    sts16(a, w); sts32(a + 4, aa); sts32(a + 8, aa); sts32(a + 12, aa); sts16(a + 18, w);
                }
                sts16(kb_ + (KW_2 + 48 + (k >> 1) - 24) * 4 + ((k & 1) ^ 1) * 2, w >> 16);
            }
#pragma unroll
            for (int b = 0; b < 2; b++) {
                const int k = 64 + 8 * (2 * q + b) + (be >> 1);
                const uint32_t w = pack2(kc[4 * 4 + 2 * i + b], 0.f);
                if (!(be & 1) && k == 64) sts16(kb_ + (KW_2 + 63 - 24) * 4, w);
                else {
                    const uint32_t a = kb_ + (KW_3 + ((be & 1) ? 80 + k : k - 1) - 48) * 4;
                    sts16(a, w);
                    if (!((be & 1) && k == 127)) sts16(a + 6, w);
                }
            }
        }
        if (lane == 0) sts16(kb_ + (KW_3 + 127 - 48) * 4, pack2(kc[4 * 5 + 0], 0.f));
        __syncwarp();
        asm volatile("setmaxnreg.inc.sync.aligned.u32 136;");
        mbar_wait(bar + 8 * BAR_UR, 0);
        mbar_wait(bar + 8 * BAR_DONE, 0);
        if (warp == 8) STAMP(23);
        float y[16][4];
#pragma unroll
        for (int nt = 0; nt < 16; nt++) { y[nt][0] = y[nt][1] = y[nt][2] = y[nt][3] = 0.f; }
        {
            uint32_t Bp[32], A[4][3], An[4][3];
            auto uaddr = [&](int rho) { const int R0 = (lane >> 4) * 64 + (lane & 7) - rho; return ub + (((2 * R0 + ((lane >> 3) & 1)) ^ ((R0 >> 2) & 1)) << 4); };
            const uint32_t kd = kb_ + (KW_D + g - 2 * q) * 4;
#pragma unroll 1
            for (int rho = 1; rho >= 0; rho--) {
                const uint32_t a = uaddr(rho), k = kd + 2048 + rho * 64;
#pragma unroll
                for (int i = 0; i < 8; i++) ldsm4(Bp + 4 * i, a + i * 256);
                const uint32_t a0 = lds32(k), a1 = lds32(k + 32), a2 = lds32(k - 32);
#pragma unroll
                for (int i = 0; i < 12; i++) mma16816(y[i + 4], a0, a1, a2, a0, Bp[4 * (i & 7) + 2 * (i >> 3)], Bp[4 * (i & 7) + 2 * (i >> 3) + 1]);
            }
#pragma unroll
            for (int ga = 0; ga < 4; ga++) { An[ga][0] = lds32(kd + ga * 512); An[ga][1] = lds32(kd + ga * 512 + 32); An[ga][2] = lds32(kd + ga * 512 - 32); }
#pragma unroll 1
            for (int rho = 0; rho < 8; rho++) {
#pragma unroll
                for (int ga = 0; ga < 4; ga++) {
                    const uint32_t a = kd + (rho + 1) * 64 + ga * 512;
                    A[ga][0] = An[ga][0]; A[ga][1] = An[ga][1]; A[ga][2] = An[ga][2];
                    An[ga][0] = lds32(a); An[ga][1] = lds32(a + 32); An[ga][2] = lds32(a - 32);
                }
                const uint32_t an = uaddr(rho + 1);
#pragma unroll
                for (int i = 0; i < 8; i++) {
#pragma unroll
                    for (int ga = 0; ga < 4; ga++) {
                        mma16816(y[i + ga], A[ga][0], A[ga][1], A[ga][2], A[ga][0], Bp[4 * i], Bp[4 * i + 1]);
                        if (i + 8 + ga < 16) mma16816(y[i + 8 + ga], A[ga][0], A[ga][1], A[ga][2], A[ga][0], Bp[4 * i + 2], Bp[4 * i + 3]);
                    }
                    ldsm4(Bp + 4 * i, an + i * 256);
                    __syncwarp();
                }
            }
        }
        if (warp == 8) STAMP(18);
        mbar_wait(bar + 8 * BAR_WR, 0);
#pragma unroll 1
        for (int ph = 0; ph < 2; ph++) {
            uint32_t B[5][2];
            const uint32_t ka = kb_ + (KW_2 + ph * 48 + 8 + g - q) * 4;
#pragma unroll
            for (int dd = 0; dd < 5; dd++) { B[dd][0] = lds32(ka + dd * 32); B[dd][1] = lds32(ka + dd * 32 - 16); }
            const uint32_t wa = buf + ph * W3_OFF + ((lane & 7) + ((lane >> 3) & 1) + (lane >> 4) * 8) * 16;
#pragma unroll
            for (int s = 0; s < 12; s++) {
                uint32_t A[4];
                ldsm4t(A, wa + s * 256);
#pragma unroll
                for (int dd = 0; dd < 5; dd++)
                    if (s + 4 + dd < 16) mma16816(y[s + 4 + dd], A[0], A[1], A[2], A[3], B[dd][0], B[dd][1]);
            }
        }
        {
            const int ap = (lane & 7) + (lane >> 4) * 8;
            const uint32_t loff = ((2 * ap + ((lane >> 3) & 1)) ^ ((ap >> 2) & 1)) << 4;
#pragma unroll 1
            for (int ph = 0; ph < 2; ph++) {
                uint32_t B[8][2];
                const uint32_t wb = (ph ? spare : buf + W9_OFF) + loff;
                const uint32_t ka = kb_ + (KW_3 + ph * 80 + 16 + g - 2 * q) * 4;
#pragma unroll
                for (int dd = 0; dd < 8; dd++) { B[dd][0] = lds32(ka + dd * 32); B[dd][1] = lds32(ka + dd * 32 - 32); }
#pragma unroll
                for (int s = 0; s < 4; s++) {
                    uint32_t A[4];
                    ldsm4t(A, wb + s * 512);
#pragma unroll
                    for (int dd = 0; dd < 8; dd++)
                        if (8 + 2 * s + dd < 16) mma16816(y[8 + 2 * s + dd], A[0], A[1], A[2], A[3], B[dd][0], B[dd][1]);
                }
            }
            const uint32_t idw = (g == 2 * q) ? k1024 : ((g == 2 * q + 1) ? (k1024 << 16) : 0u);
#pragma unroll
            for (int s = 0; s < 4; s++) {
                uint32_t A[4];
                ldsm4t(A, spare + 2048 + loff + s * 512);
                mma16816(y[8 + 2 * s], A[0], A[1], A[2], A[3], idw, 0u);
                mma16816(y[9 + 2 * s], A[0], A[1], A[2], A[3], 0u, idw);
            }
        }
        __syncwarp();
        if (warp == 8) STAMP(19);
#pragma unroll
        for (int nt = 0; nt < 16; nt++)
#pragma unroll
            for (int b = 0; b < 2; b++) sts32(buf + ((8 * nt + 2 * q + b) * 8 + g) * 4, pack2(y[nt][b], y[nt][2 + b]));
        bar_named(2, 128);
        uint4* yp = scr->y + bi * 1024 + st;
#pragma unroll
        for (int v = 0; v < 8; v++) {
            const uint32_t a = sb + OFF_BUF + (st + 128 * v) * 4;
            const uint32_t w0 = lds32(a), w1 = lds32(a + BUF_STRIDE), w2 = lds32(a + 2 * BUF_STRIDE), w3 = lds32(a + 3 * BUF_STRIDE);
            st_rlx128(yp + v * 128, tag4(__byte_perm(w0, w1, 0x5410), __byte_perm(w0, w1, 0x7632), __byte_perm(w2, w3, 0x5410), __byte_perm(w2, w3, 0x7632), tag));
        }
        if (st < 8) st_rlx32(scr->yflag + bi * 8 + st, tag);
        if (warp == 8) STAMP(20);
    } else {
        asm volatile("setmaxnreg.dec.sync.aligned.u32 56;");
        const int qq = (bi_i & 2) + ((lane >> 1) & 1);
        uint2* kvf_h = (uint2*)(scr->kvf + (bi_j * 4 + (bi_i >> 2)) * 68);
        auto windows = [&](int rhi, int rlo) {
#pragma unroll 1
            for (int rho = rhi; rho >= rlo; rho--) {
                const int ci = lane + 32 * rho;
                uint4 e4[4];
#pragma unroll
                for (int v = 0; v < 4; v++) { const int cc = ci - 3 + v; e4[v] = lds128(ub + ((cc ^ ((cc >> 3) & 1)) << 4)); }
                float S[29];
                const uint32_t* ew = (const uint32_t*)e4;
                S[3] = 0.f;
#pragma unroll
                for (int k = 4; k <= 28; k++) S[k] = S[k - 1] + ((k & 1) ? bf_hi(ew[k >> 1]) : bf_lo(ew[k >> 1]));
                auto win = [&](int lo, int hi, uint32_t a) {
                    sts128(a, pack2(S[hi] - S[lo - 1], S[hi + 1] - S[lo]), pack2(S[hi + 2] - S[lo + 1], S[hi + 3] - S[lo + 2]),
                           pack2(S[hi + 4] - S[lo + 3], S[hi + 5] - S[lo + 4]), pack2(S[hi + 6] - S[lo + 5], S[hi + 7] - S[lo + 6]));
                };
                win(14, 18, buf + W5_OFF + 16 + ci * 16); win(19, 21, buf + W3_OFF + 16 + ci * 16);
                if (rho < 4) {
                    const uint32_t sw = (ci ^ ((ci >> 3) & 1)) << 4;
                    win(4, 12, buf + W9_OFF + sw); win(13, 19, spare + sw); win(20, 21, spare + 2048 + sw);
                }
            }
        };
        {
            mbar_wait(bar + 8 * (BAR_FULL + xkb), 0);
#pragma unroll 1
            for (int hf = 0; hf < 2; hf++) {
                const int r = w4 * 32 + hf * 16 + (lane & 15);
                uint32_t* xt = (uint32_t*)scr->xt + ((xkb + rot) * 16 + (g >> 2)) * 4096 + (bi_i * 16 + w4 * 4 + hf * 2) * 16 + (g & 3) * 4 + q;
#pragma unroll
                for (int cb = 0; cb < 8; cb += 2) {
                    uint32_t v[4];
                    ldsm4t(v, sb + xkb * SLOT + r * 128 + (((cb + (lane >> 4)) ^ (r & 7)) << 4));
                    xt[cb * 8192] = v[0]; xt[cb * 8192 + 16] = v[1]; xt[cb * 8192 + 8192] = v[2]; xt[cb * 8192 + 8192 + 16] = v[3];
                }
            }
            __syncwarp();
            if (lane == 0) mbar_arrive(bar + 8 * BAR_XT);
            if (warp == 12) {
                STAMP(26);
#pragma unroll 1
                for (int kb = 0; kb < 6; kb++) {
                    const int s = kb & 3;
                    mbar_wait(bar + 8 * (BAR_EMPTY + s), kb >> 2);
                    if (kb == xkb) mbar_wait(bar + 8 * BAR_XT, 0);
                    if (lane == 0) {
                        STAMP(48 + kb);
                        if (kb < 4) load_stage(kb + 4);
                        else {
                            mbar_expect(bar + 8 * BAR_WO, 32768);
                            tma2d(sb + s * SLOT, &mwo, (bi_j & 3) * 128 + s * 64, 0, bar + 8 * BAR_WO);
                            if (kb == 5) mbar_arrive(bar + 8 * BAR_SP2);
                        }
                    }
                    __syncwarp();
                }
            } else {
                const uint32_t old = tag ^ 1u;
                const uint4 z4 = make_uint4(old, 0, old, 0);
                const int s3 = st - 32;
#pragma unroll
                for (int v = 0; v < 6; v++) if (v < 5 || s3 < 64) st_rlx128(scr->kvp + bi * 544 + v * 96 + s3, z4);
                if (s3 < 16) st_rlx128(scr->o + ((bi_i * 8 + (s3 >> 1)) * 32 + bi_j * 4 + 3) * 32 + 30 + (s3 & 1), z4);
                if (s3 < 32) st_rlx64(kvf_h + ((bi_i & 3) * 8 + (s3 >> 3) * 2 + (s3 & 1)) * 4 + ((s3 >> 1) & 3), old, 0);
                if (s3 < 4 && !(bi_i & 1)) st_rlx64(kvf_h + (64 + qq) * 2 + (lane & 1), old, 0);
                if (s3 >= 64) st_rlx64(scr->g + (bi_i * 64 + bi_j * 8) * 8 + lane * 2, old, old);
                __syncwarp();
                if (lane == 0) mbar_arrive(bar + 8 * BAR_PREP);
                if (warp == 13) {
                    mbar_wait(bar + 8 * BAR_XT, 0);
                    if (lane == 0) asm volatile("red.release.gpu.global.add.u32 [%0],8;" ::"l"(scr->xcnt + (xkb + rot) * 32) : "memory");
                    __syncwarp();
                    STAMP(27);
                }
            }
            int n = 0;
#pragma unroll 1
            while (__any_sync(~0u, (int)(ld_acq(scr->xcnt + bi_j * 32) - (epoch1 << 7)) < 0)) { if (++n > SPIN_LIMIT) break; }
            if (warp == 12) STAMP(15);
            uint4 ur[8];
#pragma unroll
            for (int v = 0; v < 8; v++) ur[v] = __ldcg(scr->xt + bi * 1024 + st + 128 * v);
            mbar_wait(bar + 8 * BAR_SP, 0);
            if (lane < 16) sts128(ub - 256 + lane * 16, 0, 0, 0, 0);
            if (lane < 2) sts128(buf + lane * W3_OFF, 0, 0, 0, 0);
#pragma unroll
            for (int v = 0; v < 8; v++) {
                const int ci = (st >> 2) + 32 * v;
                sts128(sb + OFF_U + (st & 3) * U_STRIDE + 256 + ((ci ^ ((ci >> 3) & 1)) << 4), ur[v].x, ur[v].y, ur[v].z, ur[v].w);
            }
            __syncwarp();
            if (lane == 0) mbar_arrive(bar + 8 * BAR_UR);
            mbar_wait(bar + 8 * BAR_UR, 0);
            if (warp == 12) STAMP(16);
            windows(5, 4);
        }
        mbar_wait(bar + 8 * BAR_SP2, 0);
        windows(3, 0);
        __syncwarp();
        if (lane == 0) mbar_arrive(bar + 8 * BAR_WR);
        if (warp == 12) STAMP(24);
        {
            const bool zw = st < 32 && !(bi_i & 1);
            const uint4* src = scr->kvp + bi_j * (16 * 544) + (bi_i >> 2) * 136;
            const uint4* zsrc = src + (lane >> 2) * (2 * 544) + 128 + (lane & 1) * 4 + qq;
            src += (lane >> 3) * (4 * 544) + ((lane >> 1) & 3) * 32 + (bi_i & 3) * 8 + w4 * 2 + (lane & 1);
            mbar_wait(bar + 8 * BAR_PREP, 0);
            mbar_wait(bar + 8 * BAR_PUB, 0);
            if (warp == 12) STAMP(12);
            uint4 v[6];
#pragma unroll
            for (int k = 0; k < 6; k++) v[k] = make_uint4(tag ^ 1u, 0, 0, 0);
            int n = 0;
#pragma unroll 1
            while (true) {
#pragma unroll
                for (int k = 0; k < 6; k++) if ((bad4(v[k], tag) & 1) && (k < 4 || zw)) v[k] = ld_rlx128(k < 4 ? src + k * 544 : zsrc + (k - 4) * 544);
                if (!__any_sync(~0u, (bad4(v[0], tag) | bad4(v[1], tag) | bad4(v[2], tag) | bad4(v[3], tag) | (zw ? bad4(v[4], tag) | bad4(v[5], tag) : 0u)) & 1)) break;
                if (++n > SPIN_LIMIT) break;
            }
            if (warp == 12) STAMP(30);
            float f[8];
            const float* vf = (const float*)v;
#pragma unroll
            for (int r = 0; r < 4; r++) {
                f[r] = (vf[r] + vf[4 + r]) + (vf[8 + r] + vf[12 + r]);
                f[4 + r] = vf[16 + r] + vf[20 + r];
                f[4 + r] += __shfl_xor_sync(~0u, f[4 + r], 4);
            }
#pragma unroll
            for (int o = 8; o <= 16; o <<= 1)
#pragma unroll
                for (int r = 0; r < 8; r++) f[r] += __shfl_xor_sync(~0u, f[r], o);
            if (lane < 8) st_rlx64(kvf_h + ((bi_i & 3) * 8 + w4 * 2 + (lane & 1)) * 4 + (lane >> 1), tagw(pack2(f[0], f[1]), tag), pack2(f[2], f[3]));
            if (zw && lane < 4) st_rlx64(kvf_h + (64 + qq) * 2 + (lane & 1), tagw(pack2(f[4], f[5]), tag), pack2(f[6], f[7]));
        }
        if (warp == 12) STAMP(13);
        {
            const uint4* kp = scr->kvf + bi_j * 272 + st;
            uint4 v0 = make_uint4(tag ^ 1u, 0, 0, 0), v1 = v0, v2 = make_uint4(st < 16 ? tag ^ 1u : tag, 0, tag, 0);
            int n = 0;
#pragma unroll 1
            while (true) {
                if (bad4(v0, tag) & 1) v0 = ld_rlx128(kp);
                if (bad4(v1, tag) & 1) v1 = ld_rlx128(kp + 128);
                if (bad4(v2, tag) & 1) v2 = ld_rlx128(kp + 256);
                if (!__any_sync(~0u, (bad4(v0, tag) | bad4(v1, tag) | bad4(v2, tag)) & 1)) break;
                if (++n > SPIN_LIMIT) break;
            }
            sts128(sb + OFF_KVF + st * 16, v0.x, v0.y, v0.z, v0.w);
            sts128(sb + OFF_KVF + 2048 + st * 16, v1.x, v1.y, v1.z, v1.w);
            if (st < 16) sts128(sb + OFF_KVF + 4096 + st * 16, v2.x, v2.y, v2.z, v2.w);
            __syncwarp();
            if (lane == 0) mbar_arrive(bar + 8 * BAR_KVF);
        }
        if (warp == 13) {
            mbar_wait(bar + 8 * BAR_KVF, 0);
            if (lane == 0) {
                mbar_expect(bar + 8 * BAR_WO2, 65536);
                tma2d(sb + OFF_P, &mwo, (bi_j & 3) * 128 + 64, 256, bar + 8 * BAR_WO2);
                tma2d(sb + OFF_V, &mwo, (bi_j & 3) * 128, 256, bar + 8 * BAR_WO2);
            }
        }
        if (warp == 12) STAMP(25);
        {
            const uint4* xr = (const uint4*)(x + (size_t)(bi_i * 128 + bi_j * 16 + w4 * 4 + (lane >> 3)) * 512) + (lane & 7);
            uint4 xv[8];
#pragma unroll
            for (int c = 0; c < 8; c++) xv[c] = __ldg(xr + c * 8);
            float gs0 = 0.f, gs1 = 0.f;
            mbar_wait(bar + 8 * BAR_WPHI, 0);
#pragma unroll
            for (int c = 0; c < 8; c++) {
                const uint4 gw = lds128(sb + OFF_GW + c * 128 + (lane & 7) * 16);
                const uint32_t p0 = hmul2(xv[c].x, gw.x), p1 = hmul2(xv[c].y, gw.y), p2 = hmul2(xv[c].z, gw.z), p3 = hmul2(xv[c].w, gw.w);
                gs0 += (bf_lo(p0) + bf_lo(p1)) + (bf_lo(p2) + bf_lo(p3));
                gs1 += (bf_hi(p0) + bf_hi(p1)) + (bf_hi(p2) + bf_hi(p3));
            }
            float gs = gs0 + gs1;
#pragma unroll
            for (int o = 1; o < 8; o <<= 1) gs += __shfl_xor_sync(~0u, gs, o);
            const uint32_t gv = __float_as_uint(bf_round(rcp(1.0f + ex2(-1.4426950408889634f * bf_round(gs))))) | tag;
            if ((lane & 7) < 2) st_rlx64(scr->g + (bi_i * 64 + bi_j * 8 + w4 * 2) * 8 + (lane >> 3) * 4 + (lane & 1) * 2, gv, gv);
        }
    }
    __syncwarp();
    if (lane == 0) {
        unsigned old;
        asm volatile("atom.acq_rel.cta.shared.add.u32 %0,[%1],1;" : "=r"(old) : "r"(bar + OFF_CNT) : "memory");
        if (old == 15) {
            atomicAdd(scr->done, 1u);
        }
    }
}

typedef CUresult (*EncFn)(CUtensorMap*, CUtensorMapDataType, cuuint32_t, void*, const cuuint64_t*, const cuuint64_t*, const cuuint32_t*,
                          const cuuint32_t*, CUtensorMapInterleave, CUtensorMapSwizzle, CUtensorMapL2promotion, CUtensorMapFloatOOBfill);

extern "C" void kernel_launch(void* const* d_in, const int* in_sizes, int n_in, void* d_out, int out_size) {
    static EncFn enc = nullptr;
    static Scratch* scr = nullptr;
    if (!enc) {
        cudaGetSymbolAddress((void**)&scr, g_scr);
        cudaDriverEntryPointQueryResult qr;
        cudaGetDriverEntryPoint("cuTensorMapEncodeTiled", (void**)&enc, cudaEnableDefault, &qr);
        cudaFuncSetAttribute(fused_kernel, cudaFuncAttributeMaxDynamicSharedMemorySize, SMEM_BYTES);
    }
    CUtensorMap mx, mw, mwo;
    const cuuint32_t es[3] = {1, 1, 1};
    {
        cuuint64_t d[2] = {512, 2048}, s[1] = {1024}; cuuint32_t b[2] = {64, 128};
        enc(&mx, CU_TENSOR_MAP_DATA_TYPE_BFLOAT16, 2, d_in[0], d, s, b, es, CU_TENSOR_MAP_INTERLEAVE_NONE, CU_TENSOR_MAP_SWIZZLE_128B,
            CU_TENSOR_MAP_L2_PROMOTION_L2_128B, CU_TENSOR_MAP_FLOAT_OOB_FILL_NONE);
    }
    {
        cuuint64_t d[3] = {512, 512, 3}, s[2] = {3072, 1024}; cuuint32_t b[3] = {64, 64, 3};
        enc(&mw, CU_TENSOR_MAP_DATA_TYPE_BFLOAT16, 3, d_in[1], d, s, b, es, CU_TENSOR_MAP_INTERLEAVE_NONE, CU_TENSOR_MAP_SWIZZLE_128B,
            CU_TENSOR_MAP_L2_PROMOTION_L2_128B, CU_TENSOR_MAP_FLOAT_OOB_FILL_NONE);
    }
    {
        cuuint64_t d[2] = {512, 512}, s[1] = {1024}; cuuint32_t b[2] = {64, 256};
        enc(&mwo, CU_TENSOR_MAP_DATA_TYPE_BFLOAT16, 2, d_in[3], d, s, b, es, CU_TENSOR_MAP_INTERLEAVE_NONE, CU_TENSOR_MAP_SWIZZLE_128B,
            CU_TENSOR_MAP_L2_PROMOTION_L2_128B, CU_TENSOR_MAP_FLOAT_OOB_FILL_NONE);
    }
    fused_kernel<<<128, 512, SMEM_BYTES, cudaStreamPerThread>>>(
        scr, (const bf16*)d_in[5], (const bf16*)d_in[6], (const bf16*)d_in[7], (const bf16*)d_in[8], (const bf16*)d_in[9],
        (const bf16*)d_in[10], (const bf16*)d_in[2], (const bf16*)d_in[11], (bf16*)d_out, (const bf16*)d_in[0], mx, mw, mwo);
}
```

```cpp
#include <cuda_runtime.h>
#include <cuda.h>
#include <cuda_bf16.h>
#include <stdint.h>

typedef __nv_bfloat16 bf16;

struct Scratch {
    uint4 xt[128 * 1024];
    uint4 o[16 * 8 * 32 * 32];
    uint4 y[128 * 1024];
    uint4 kvp[8 * 16 * 544];
    uint4 kvf[8 * 4 * 68];
    unsigned g[1024 * 8];
    unsigned yflag[128 * 8];
    unsigned xcnt[8 * 32];
    unsigned done[32];
};
__device__ Scratch g_scr;
#define STAMP(n)

constexpr int SLOT = 40960;
constexpr int OFF_SP0 = 32768, OFF_SP1 = SLOT + 32768;
constexpr int OFF_P = 2 * SLOT, OFF_V = OFF_P + 32768;
constexpr int OFF_KVF = OFF_V + 32768;
constexpr int KT_BYTES = 3264, KW_D = 16, KW_2 = 560, KW_3 = 656;
constexpr int OFF_U = 4 * SLOT, U_STRIDE = 4096 + 256 + 32;
constexpr int OFF_BUF = OFF_U + 4 * U_STRIDE, BUF_STRIDE = 8320;
constexpr int OFF_K = OFF_BUF + 4 * BUF_STRIDE;
constexpr int OFF_WPHI = OFF_K + 4 * KT_BYTES;
constexpr int OFF_GW = OFF_WPHI + 2048;
constexpr int OFF_BAR = OFF_GW + 1024;
constexpr int SMEM_BYTES = OFF_BAR + 256 + 256;
static_assert(SMEM_BYTES <= 232448 && OFF_BUF % 128 == 0, "smem");
constexpr int W5_OFF = 0, W3_OFF = 3088, W9_OFF = 6176;
constexpr int BAR_FULL = 0, BAR_EMPTY = 4, BAR_WPHI = 8, BAR_WO = 9, BAR_WO2 = 10, BAR_XT = 11, BAR_DONE = 12, BAR_KG = 13, BAR_SP = 14,
              BAR_PUB = 15, BAR_KVF = 16, BAR_UR = 17, BAR_WR = 18, BAR_PREP = 19, BAR_KGA = 20, BAR_SP2 = 21, BAR_KS = 22, BAR_KP = 26, OFF_CNT = 248;
constexpr int SPIN_LIMIT = 1 << 17;

__device__ __forceinline__ uint32_t s2u(const void* p) { return (uint32_t)__cvta_generic_to_shared(p); }
__device__ __forceinline__ void mbar_init(uint32_t b, int c) { asm volatile("mbarrier.init.shared::cta.b64 [%0],%1;" ::"r"(b), "r"(c) : "memory"); }
__device__ __forceinline__ void mbar_expect(uint32_t b, int bytes) { asm volatile("mbarrier.arrive.expect_tx.shared::cta.b64 _,[%0],%1;" ::"r"(b), "r"(bytes) : "memory"); }
__device__ __forceinline__ void mbar_arrive(uint32_t b) { asm volatile("mbarrier.arrive.shared::cta.b64 _,[%0];" ::"r"(b) : "memory"); }
__device__ __forceinline__ void mbar_wait(uint32_t b, int ph) {
    asm volatile("{\n.reg .pred p;\n.reg .u32 n;\nmov.u32 n,0;\nLW_%=:\nmbarrier.try_wait.parity.shared::cta.b64 p,[%0],%1;\n@p bra LD_%=;\n"
                 "add.u32 n,n,1;\nsetp.lt.u32 p,n,16384;\n@p bra LW_%=;\nLD_%=:\n}" ::"r"(b), "r"(ph) : "memory");
}
__device__ __forceinline__ void tma2d(uint32_t dst, const CUtensorMap* m, int c0, int c1, uint32_t bar) {
    asm volatile("cp.async.bulk.tensor.2d.shared::cluster.global.mbarrier::complete_tx::bytes [%0],[%1,{%3,%4}],[%2];" ::"r"(dst), "l"(m), "r"(bar), "r"(c0), "r"(c1) : "memory");
}
__device__ __forceinline__ void tma3d(uint32_t dst, const CUtensorMap* m, int c0, int c1, int c2, uint32_t bar) {
    asm volatile("cp.async.bulk.tensor.3d.shared::cluster.global.mbarrier::complete_tx::bytes [%0],[%1,{%3,%4,%5}],[%2];" ::"r"(dst), "l"(m), "r"(bar), "r"(c0), "r"(c1), "r"(c2) : "memory");
}
__device__ __forceinline__ void bulk_g2s(uint32_t dst, const void* src, int bytes, uint32_t bar) {
    asm volatile("cp.async.bulk.shared::cluster.global.mbarrier::complete_tx::bytes [%0],[%1],%2,[%3];" ::"r"(dst), "l"(src), "r"(bytes), "r"(bar) : "memory");
}
__device__ __forceinline__ uint64_t mkdesc(uint32_t addr, uint32_t lbo, uint32_t sbo) {
    return (uint64_t)((addr & 0x3FFFF) >> 4) | ((uint64_t)(lbo >> 4) << 16) | ((uint64_t)(sbo >> 4) << 32) | ((uint64_t)1 << 62);
}
__device__ __forceinline__ void wg_fence() { asm volatile("wgmma.fence.sync.aligned;" ::: "memory"); }
__device__ __forceinline__ void wg_commit() { asm volatile("wgmma.commit_group.sync.aligned;" ::: "memory"); }
template <int N> __device__ __forceinline__ void wg_wait() { asm volatile("wgmma.wait_group.sync.aligned %0;" ::"n"(N) : "memory"); }
template <int N> __device__ __forceinline__ void fence_regs(float* d) {
#pragma unroll
    for (int i = 0; i < N; i++) asm volatile("" : "+f"(d[i])::"memory");
}
#define R8(d, o) "+f"(d[o]), "+f"(d[o + 1]), "+f"(d[o + 2]), "+f"(d[o + 3]), "+f"(d[o + 4]), "+f"(d[o + 5]), "+f"(d[o + 6]), "+f"(d[o + 7])
__device__ __forceinline__ void wgmma192(float* d, uint64_t da, uint64_t db, int sc) {
    asm volatile("{.reg .pred p; setp.ne.b32 p,%98,0; wgmma.mma_async.sync.aligned.m64n192k16.f32.bf16.bf16 {"
                 "%0,%1,%2,%3,%4,%5,%6,%7,%8,%9,%10,%11,%12,%13,%14,%15,%16,%17,%18,%19,%20,%21,%22,%23,%24,%25,%26,%27,%28,%29,%30,%31,"
                 "%32,%33,%34,%35,%36,%37,%38,%39,%40,%41,%42,%43,%44,%45,%46,%47,%48,%49,%50,%51,%52,%53,%54,%55,%56,%57,%58,%59,%60,%61,%62,%63,"
                 "%64,%65,%66,%67,%68,%69,%70,%71,%72,%73,%74,%75,%76,%77,%78,%79,%80,%81,%82,%83,%84,%85,%86,%87,%88,%89,%90,%91,%92,%93,%94,%95},"
                 "%96,%97,p,1,1,0,1;}"
                 : R8(d, 0), R8(d, 8), R8(d, 16), R8(d, 24), R8(d, 32), R8(d, 40), R8(d, 48), R8(d, 56), R8(d, 64), R8(d, 72), R8(d, 80), R8(d, 88)
                 : "l"(da), "l"(db), "r"(sc));
}
__device__ __forceinline__ void wgmma64_tt(float* d, uint64_t da, uint64_t db, int sc) {
    asm volatile("{.reg .pred p; setp.ne.b32 p,%34,0; wgmma.mma_async.sync.aligned.m64n64k16.f32.bf16.bf16 {"
                 "%0,%1,%2,%3,%4,%5,%6,%7,%8,%9,%10,%11,%12,%13,%14,%15,%16,%17,%18,%19,%20,%21,%22,%23,%24,%25,%26,%27,%28,%29,%30,%31},"
                 "%32,%33,p,1,1,1,1;}"
                 : R8(d, 0), R8(d, 8), R8(d, 16), R8(d, 24)
                 : "l"(da), "l"(db), "r"(sc));
}
__device__ __forceinline__ void wgmma128_rs(float* d, const uint4& a, uint64_t db, int sc) {
    asm volatile("{.reg .pred p; setp.ne.b32 p,%69,0; wgmma.mma_async.sync.aligned.m64n128k16.f32.bf16.bf16 {"
                 "%0,%1,%2,%3,%4,%5,%6,%7,%8,%9,%10,%11,%12,%13,%14,%15,%16,%17,%18,%19,%20,%21,%22,%23,%24,%25,%26,%27,%28,%29,%30,%31,"
                 "%32,%33,%34,%35,%36,%37,%38,%39,%40,%41,%42,%43,%44,%45,%46,%47,%48,%49,%50,%51,%52,%53,%54,%55,%56,%57,%58,%59,%60,%61,%62,%63},"
                 "{%64,%65,%66,%67},%68,p,1,1,1;}"
                 : R8(d, 0), R8(d, 8), R8(d, 16), R8(d, 24), R8(d, 32), R8(d, 40), R8(d, 48), R8(d, 56)
                 : "r"(a.x), "r"(a.y), "r"(a.z), "r"(a.w), "l"(db), "r"(sc));
}
__device__ __forceinline__ void mma16816(float* c, uint32_t a0, uint32_t a1, uint32_t a2, uint32_t a3, uint32_t b0, uint32_t b1) {
    asm("mma.sync.aligned.m16n8k16.row.col.f32.bf16.bf16.f32 {%0,%1,%2,%3},{%4,%5,%6,%7},{%8,%9},{%0,%1,%2,%3};"
        : "+f"(c[0]), "+f"(c[1]), "+f"(c[2]), "+f"(c[3]) : "r"(a0), "r"(a1), "r"(a2), "r"(a3), "r"(b0), "r"(b1));
}
__device__ __forceinline__ void ldsm4(uint32_t* r, uint32_t a) {
    asm volatile("ldmatrix.sync.aligned.m8n8.x4.shared.b16 {%0,%1,%2,%3},[%4];" : "=r"(r[0]), "=r"(r[1]), "=r"(r[2]), "=r"(r[3]) : "r"(a) : "memory");
}
__device__ __forceinline__ void ldsm4t(uint32_t* r, uint32_t a) {
    asm volatile("ldmatrix.sync.aligned.m8n8.x4.trans.shared.b16 {%0,%1,%2,%3},[%4];" : "=r"(r[0]), "=r"(r[1]), "=r"(r[2]), "=r"(r[3]) : "r"(a) : "memory");
}
__device__ __forceinline__ void stsm4(uint32_t a, uint32_t r0, uint32_t r1, uint32_t r2, uint32_t r3) {
    asm volatile("stmatrix.sync.aligned.m8n8.x4.shared.b16 [%0],{%1,%2,%3,%4};" ::"r"(a), "r"(r0), "r"(r1), "r"(r2), "r"(r3) : "memory");
}
__device__ __forceinline__ uint32_t lds32(uint32_t a) { uint32_t v; asm volatile("ld.shared.b32 %0,[%1];" : "=r"(v) : "r"(a) : "memory"); return v; }
__device__ __forceinline__ uint4 lds128(uint32_t a) { uint4 v; asm volatile("ld.shared.v4.b32 {%0,%1,%2,%3},[%4];" : "=r"(v.x), "=r"(v.y), "=r"(v.z), "=r"(v.w) : "r"(a) : "memory"); return v; }
__device__ __forceinline__ void sts16(uint32_t a, uint32_t v) { asm volatile("st.shared.b16 [%0],%1;" ::"r"(a), "h"((unsigned short)v) : "memory"); }
__device__ __forceinline__ void sts32(uint32_t a, uint32_t v) { asm volatile("st.shared.b32 [%0],%1;" ::"r"(a), "r"(v) : "memory"); }
__device__ __forceinline__ void sts64(uint32_t a, uint32_t x, uint32_t y) { asm volatile("st.shared.v2.b32 [%0],{%1,%2};" ::"r"(a), "r"(x), "r"(y) : "memory"); }
__device__ __forceinline__ void sts128(uint32_t a, uint32_t x, uint32_t y, uint32_t z, uint32_t w) { asm volatile("st.shared.v4.b32 [%0],{%1,%2,%3,%4};" ::"r"(a), "r"(x), "r"(y), "r"(z), "r"(w) : "memory"); }
__device__ __forceinline__ uint32_t pack2(float lo, float hi) { uint32_t d; asm("cvt.rn.bf16x2.f32 %0,%1,%2;" : "=r"(d) : "f"(hi), "f"(lo)); return d; }
__device__ __forceinline__ float bf_lo(uint32_t v) { return __uint_as_float(v << 16); }
__device__ __forceinline__ float bf_hi(uint32_t v) { return __uint_as_float(v & 0xffff0000u); }
__device__ __forceinline__ float bf_round(float v) { return bf_lo(pack2(v, 0.f)); }
__device__ __forceinline__ uint32_t hmax2(uint32_t a, uint32_t b) { uint32_t d; asm("max.bf16x2 %0,%1,%2;" : "=r"(d) : "r"(a), "r"(b)); return d; }
__device__ __forceinline__ uint32_t hmin2(uint32_t a, uint32_t b) { uint32_t d; asm("min.bf16x2 %0,%1,%2;" : "=r"(d) : "r"(a), "r"(b)); return d; }
__device__ __forceinline__ uint32_t hmul2(uint32_t a, uint32_t b) { uint32_t d; asm("mul.rn.bf16x2 %0,%1,%2;" : "=r"(d) : "r"(a), "r"(b)); return d; }
__device__ __forceinline__ float ex2(float x) { float y; asm("ex2.approx.ftz.f32 %0,%1;" : "=f"(y) : "f"(x)); return y; }
__device__ __forceinline__ float rcp(float x) { float y; asm("rcp.approx.ftz.f32 %0,%1;" : "=f"(y) : "f"(x)); return y; }
__device__ __forceinline__ uint32_t ld_nc(const uint32_t* p) { uint32_t v; asm volatile("ld.global.nc.b32 %0,[%1];" : "=r"(v) : "l"(p)); return v; }
__device__ __forceinline__ uint2 ld_nc64(const uint2* p) { uint2 v; asm volatile("ld.global.nc.v2.b32 {%0,%1},[%2];" : "=r"(v.x), "=r"(v.y) : "l"(p)); return v; }
__device__ __forceinline__ unsigned ld_acq(const unsigned* p) { unsigned v; asm volatile("ld.acquire.gpu.global.u32 %0,[%1];" : "=r"(v) : "l"(p) : "memory"); return v; }
__device__ __forceinline__ unsigned ld_rlx(const unsigned* p) { unsigned v; asm volatile("ld.relaxed.gpu.global.u32 %0,[%1];" : "=r"(v) : "l"(p) : "memory"); return v; }
__device__ __forceinline__ uint2 ld_rlx64(const void* p) { uint2 v; asm volatile("{.reg .b64 t; ld.relaxed.gpu.global.b64 t,[%2]; mov.b64 {%0,%1},t;}" : "=r"(v.x), "=r"(v.y) : "l"(p) : "memory"); return v; }
__device__ __forceinline__ uint4 ld_rlx128(const void* p) {
    uint4 v;
    asm volatile("{.reg .b64 t,u; ld.relaxed.gpu.global.v2.b64 {t,u},[%4]; mov.b64 {%0,%1},t; mov.b64 {%2,%3},u;}" : "=r"(v.x), "=r"(v.y), "=r"(v.z), "=r"(v.w) : "l"(p) : "memory");
    return v;
}
__device__ __forceinline__ void st_rlx32(void* p, uint32_t x) { asm volatile("st.relaxed.gpu.global.u32 [%0],%1;" ::"l"(p), "r"(x) : "memory"); }
__device__ __forceinline__ void st_rlx64(void* p, uint32_t x, uint32_t y) { asm volatile("{.reg .b64 t; mov.b64 t,{%1,%2}; st.relaxed.gpu.global.b64 [%0],t;}" ::"l"(p), "r"(x), "r"(y) : "memory"); }
__device__ __forceinline__ void st_rlx128(void* p, uint4 v) {
    asm volatile("{.reg .b64 t,u; mov.b64 t,{%1,%2}; mov.b64 u,{%3,%4}; st.relaxed.gpu.global.v2.b64 [%0],{t,u};}" ::"l"(p), "r"(v.x), "r"(v.y), "r"(v.z), "r"(v.w) : "memory");
}
__device__ __forceinline__ uint32_t tagw(uint32_t w, uint32_t tag) { return (w & ~1u) | tag; }
__device__ __forceinline__ uint4 tag4(uint32_t x, uint32_t y, uint32_t z, uint32_t w, uint32_t tag) { return make_uint4(tagw(x, tag), y, tagw(z, tag), w); }
__device__ __forceinline__ uint32_t bad4(const uint4& v, uint32_t tag) { return (v.x ^ tag) | (v.z ^ tag); }
__device__ __forceinline__ void bar_named(int id, int n) { asm volatile("bar.sync %0,%1;" ::"r"(id), "r"(n) : "memory"); }

struct cf { float re, im; };
__device__ __forceinline__ cf cmul(cf a, cf b) { cf r; r.re = a.re * b.re - a.im * b.im; r.im = a.re * b.im + a.im * b.re; return r; }
__device__ __forceinline__ cf cexp_p(float arl, float ait, float p) {
    float mag = ex2(arl * p);
    float t = ait * p;
    const float big = 12582912.f;
    t = (t - ((t + big) - big)) * 6.283185307179586f;
    cf r; r.re = mag * __cosf(t); r.im = mag * __sinf(t);
    return r;
}

__device__ __forceinline__ void hedgehog4(const uint32_t* a, uint32_t wphi_addr, uint32_t (*out)[8]) {
    float p[4][2][4], mx[4][2];
#pragma unroll
    for (int h = 0; h < 4; h++) {
        uint32_t b[4];
        ldsm4t(b, wphi_addr + h * 512);
        float c0[4] = {0.f, 0.f, 0.f, 0.f}, c1[4] = {0.f, 0.f, 0.f, 0.f};
        mma16816(c0, a[4 * h], a[4 * h + 1], a[4 * h + 2], a[4 * h + 3], b[0], b[1]);
        mma16816(c1, a[4 * h], a[4 * h + 1], a[4 * h + 2], a[4 * h + 3], b[2], b[3]);
#pragma unroll
        for (int k = 0; k < 2; k++) {
            p[h][k][0] = c0[2 * k]; p[h][k][1] = c0[2 * k + 1]; p[h][k][2] = c1[2 * k]; p[h][k][3] = c1[2 * k + 1];
            mx[h][k] = fmaxf(fmaxf(p[h][k][0], p[h][k][1]), fmaxf(p[h][k][2], p[h][k][3]));
        }
    }
#pragma unroll
    for (int o = 1; o <= 2; o <<= 1)
#pragma unroll
        for (int h = 0; h < 4; h++)
#pragma unroll
            for (int k = 0; k < 2; k++) mx[h][k] = fmaxf(mx[h][k], __shfl_xor_sync(~0u, mx[h][k], o));
    const float L = 1.4426950408889634f;
    float pmin = 1.f;
#pragma unroll
    for (int h = 0; h < 4; h++)
#pragma unroll
        for (int k = 0; k < 2; k++) {
            const float m = -mx[h][k] * L;
            const float e0 = ex2(fmaf(p[h][k][0], L, m)), e1 = ex2(fmaf(p[h][k][1], L, m)), e2 = ex2(fmaf(p[h][k][2], L, m)), e3 = ex2(fmaf(p[h][k][3], L, m));
            const float p01 = e0 * e1, p23 = e2 * e3, pp = p01 * p23, r = rcp(pp), r01 = r * p23, r23 = r * p01;
            pmin = fminf(pmin, pp);
            out[h][k] = pack2(e0, e1); out[h][k + 2] = pack2(e2, e3);
            out[h][4 + k] = pack2(r01 * e1, r01 * e0); out[h][4 + k + 2] = pack2(r23 * e3, r23 * e2);
        }
    if (__builtin_expect(__any_sync(~0u, !(pmin > 1e-18f)), 0)) {
#pragma unroll
        for (int h = 0; h < 4; h++)
#pragma unroll
            for (int k = 0; k < 2; k++) {
                float m = fminf(fminf(p[h][k][0], p[h][k][1]), fminf(p[h][k][2], p[h][k][3]));
                m = fminf(m, __shfl_xor_sync(~0u, m, 1));
                m = fminf(m, __shfl_xor_sync(~0u, m, 2)) * L;
                out[h][4 + k] = pack2(ex2(fmaf(p[h][k][0], -L, m)), ex2(fmaf(p[h][k][1], -L, m)));
                out[h][4 + k + 2] = pack2(ex2(fmaf(p[h][k][2], -L, m)), ex2(fmaf(p[h][k][3], -L, m)));
            }
    }
}

__global__ void __launch_bounds__(512, 1)
fused_kernel(Scratch* __restrict__ scr, const bf16* __restrict__ logA, const bf16* __restrict__ Aim, const bf16* __restrict__ Cre,
             const bf16* __restrict__ Cim, const bf16* __restrict__ logdt, const bf16* __restrict__ Dskip, const bf16* __restrict__ wphi,
             const bf16* __restrict__ gatew, bf16* __restrict__ out,
             const __grid_constant__ CUtensorMap mx, const __grid_constant__ CUtensorMap mw, const __grid_constant__ CUtensorMap mwo) {
    extern __shared__ __align__(1024) uint8_t smem[];
    constexpr uint32_t sb = 1024;
    const int tid = threadIdx.x, warp = __shfl_sync(~0u, tid >> 5, 0), lane = tid & 31;
    const int g = lane >> 2, q = lane & 3, w4 = warp & 3;
    const int bi = blockIdx.x, bi_i = bi & 15, bi_j = bi >> 4;
    const uint32_t bar = sb + OFF_BAR;
    const int rot = (bi_j & 3) * 2, xkb = bi_j >> 2;
    auto load_stage = [&](int kb) {
        const uint32_t b = bar + 8 * (BAR_FULL + (kb & 3)), d = sb + (kb & 3) * SLOT;
        const int kc = ((kb + rot) & 7) * 64;
        mbar_expect(b, SLOT);
        tma2d(d, &mx, kc, bi_i * 128, b);
        tma3d(d + 16384, &mw, bi_j * 64, kc, 0, b);
    };

    const int ch = bi * 4 + w4;
    const int pidx = ch * 64 + lane * 2 + (warp >> 3);
    const uint32_t pla = ld_nc((const uint32_t*)logA + pidx), pai = ld_nc((const uint32_t*)Aim + pidx);
    const uint32_t pcr = ld_nc((const uint32_t*)Cre + pidx), pci = ld_nc((const uint32_t*)Cim + pidx);
    uint32_t pdt = ld_nc((const uint32_t*)logdt + (ch >> 1));
    const uint32_t pds = ld_nc((const uint32_t*)Dskip + (ch >> 1));
    unsigned done0 = ld_rlx(scr->done);
    if (tid == 0) {
        for (int s = 0; s < 4; s++) mbar_init(bar + 8 * (BAR_FULL + s), 1);
        asm volatile("fence.mbarrier_init.release.cluster;" ::: "memory");
        asm volatile("prefetch.tensormap [%0];" ::"l"(&mx) : "memory");
        load_stage(0); load_stage(1);
        STAMP(11);
    } else if (tid == 32) {
        if (s2u(smem) != sb) __trap();
        sts32(bar + OFF_CNT, 0);
        for (int s = 0; s < 4; s++) { mbar_init(bar + 8 * (BAR_EMPTY + s), 9); mbar_init(bar + 8 * (BAR_KS + s), 1); mbar_init(bar + 8 * (BAR_KP + s), 3); }
        mbar_init(bar + 8 * BAR_WPHI, 1); mbar_init(bar + 8 * BAR_WO, 2); mbar_init(bar + 8 * BAR_WO2, 1); mbar_init(bar + 8 * BAR_XT, 4);
        mbar_init(bar + 8 * BAR_DONE, 9); mbar_init(bar + 8 * BAR_KG, 8); mbar_init(bar + 8 * BAR_SP, 4); mbar_init(bar + 8 * BAR_PUB, 8);
        mbar_init(bar + 8 * BAR_KVF, 4); mbar_init(bar + 8 * BAR_UR, 4); mbar_init(bar + 8 * BAR_WR, 4); mbar_init(bar + 8 * BAR_PREP, 4); mbar_init(bar + 8 * BAR_KGA, 4); mbar_init(bar + 8 * BAR_SP2, 1);
        asm volatile("fence.mbarrier_init.release.cluster;" ::: "memory");
        mbar_expect(bar + 8 * BAR_WPHI, 3072);
        bulk_g2s(sb + OFF_GW, gatew, 1024, bar + 8 * BAR_WPHI);
        bulk_g2s(sb + OFF_WPHI, wphi + bi_j * 1024, 2048, bar + 8 * BAR_WPHI);
    } else if (tid == 64) {
        asm volatile("prefetch.tensormap [%0];" ::"l"(&mw) : "memory");
    }
    const uint32_t buf = sb + OFF_BUF + w4 * BUF_STRIDE, kb_ = sb + OFF_K + w4 * KT_BYTES;
    if ((warp >> 2) == 2) {
#pragma unroll
        for (int v = 0; v < 7; v++) if (v * 32 + lane < KT_BYTES / 16) sts128(kb_ + (v * 32 + lane) * 16, 0, 0, 0, 0);
    }
    __syncthreads();
    asm volatile("" : "+r"(pdt), "+r"(done0)::"memory");
    const unsigned epoch1 = (done0 >> 7) + 1u;
    const uint32_t tag = epoch1 & 1u;

    const int st = tid & 127;
    const uint32_t ub = sb + OFF_U + w4 * U_STRIDE + 256, spare = sb + (w4 < 2 ? OFF_SP0 : OFF_SP1) + (w4 & 1) * 4096;

    auto stg_of = [&](int w) { return w < 8 ? sb + 3 * SLOT + w * 7296 : sb + 2 * SLOT + (w & 3) * 7296; };
    float kc[24];
#pragma unroll
    for (int t = 0; t < 24; t++) kc[t] = 0.f;
    {
        const float dt = bf_round(expf((ch & 1) ? bf_hi(pdt) : bf_lo(pdt)));
        const uint32_t stg = (warp >> 2) == 2 ? buf : stg_of(warp);
        const int sh = ((warp >> 2) & 1) * 16;
        auto pick = [&](uint32_t v) { return __uint_as_float((v >> sh) << 16); };
        const float ea = bf_round(ex2(pick(pla) * 1.4426950408889634f));
        const float arl = (-ea * dt) * 1.4426950408889634f, ait = (pick(pai) * dt) * 0.15915494309189535f;
        cf C2; C2.re = 2.0f * (pick(pcr) * dt); C2.im = 2.0f * (pick(pci) * dt);
        const cf z1 = cexp_p(arl, ait, 1.0f), z128 = cexp_p(arl, ait, 128.0f);
        const cf z2 = cmul(z1, z1), z4 = cmul(z2, z2);
        cf z8 = cmul(z4, z4); z8.im = -z8.im;
        const uint32_t sa0 = stg + (lane >> 3) * 128 + (((lane & 7) ^ (lane >> 3)) << 4), sa1 = (sa0 ^ 64) + 512;
        uint32_t w[60];
        auto put = [&](int row, const cf& v) {
            w[row] = pack2(v.re, v.im);
            if ((row & 3) == 3) stsm4(((row & 4) ? sa1 : sa0) + (row >> 3) * 1024, w[row - 3], w[row - 2], w[row - 1], w[row]);
        };
        {
            const cf z16 = cmul(z8, z8);
            cf e; e.re = 1.f; e.im = 0.f;
            cf o = z8;
            put(0, e); put(1, o);
            e = z16; put(2, e);
#pragma unroll
            for (int b = 3; b < 16; b += 2) {
                o = cmul(o, z16); put(b, o);
                if (b + 1 < 16) { e = cmul(e, z16); put(b + 1, e); }
            }
        }
        cf h[8];
        h[0] = C2; h[1] = cmul(h[0], z1);
#pragma unroll
        for (int r = 2; r < 8; r++) h[r] = cmul(h[r - 2], z2);
#pragma unroll
        for (int r = 0; r < 8; r++) put(16 + r, h[r]);
#pragma unroll
        for (int r = 0; r < 8; r++) { h[r] = cmul(h[r], z128); put(24 + r, h[r]); }
#pragma unroll
        for (int al = 0; al < 2; al++)
#pragma unroll
            for (int r = 0; r < 4; r++) { h[2 * r] = cmul(h[2 * r], z128); put(32 + al * 4 + r, h[2 * r]); }
#pragma unroll
        for (int al = 0; al < 4; al++)
#pragma unroll
            for (int r = 0; r < 2; r++) { h[4 * r] = cmul(h[4 * r], z128); put(40 + al * 2 + r, h[4 * r]); }
#pragma unroll
        for (int al = 0; al < 8; al++) { h[0] = cmul(h[0], z128); put(48 + al, h[0]); }
        h[0] = cmul(h[0], z128);
        sts32(stg + 56 * 128 + lane * 4, pack2(h[0].re, h[0].im));
        __syncwarp();
        const int lr = lane & 7, lm = lane >> 3;
#pragma unroll
        for (int kp = 0; kp < 2; kp++) {
            uint32_t a0[4], a1[4];
            ldsm4(a0, stg + ((lm & 1) * 8 + lr) * 128 + (((4 * kp + (lm >> 1)) ^ lr) << 4));
            ldsm4(a1, stg + ((lm & 1) * 8 + lr) * 128 + (((4 * kp + 2 + (lm >> 1)) ^ lr) << 4));
#pragma unroll
            for (int t = 0; t < 6; t++) {
                uint32_t b[4];
                ldsm4(b, stg + (16 + 8 * t + lr) * 128 + (((4 * kp + lm) ^ lr) << 4));
                mma16816(kc + 4 * t, a0[0], a0[1], a0[2], a0[3], b[0], b[1]);
                mma16816(kc + 4 * t, a1[0], a1[1], a1[2], a1[3], b[2], b[3]);
            }
        }
        __syncwarp();
        asm volatile("fence.proxy.async.shared::cta;" ::: "memory");
        const uint32_t cnt = 1u + (__float_as_uint(kc[0] + kc[23]) == 0xffc12345u);
        if (lane == 0) asm volatile("mbarrier.arrive.shared::cta.b64 _,[%0],%1;" ::"r"(bar + 8 * (warp < 8 ? BAR_KG : (warp < 12 ? BAR_KS + w4 : BAR_KGA))), "r"(cnt) : "memory");
        if ((warp >> 2) != 2) {
            const int src = warp < 8 ? warp >> 2 : 2;
            mbar_wait(bar + 8 * (BAR_KS + w4), 0);
#pragma unroll
            for (int t = 0; t < 5; t++)
                sts128(buf + src * 2560 + (t * 32 + lane) * 16, __float_as_uint(kc[4 * t]), __float_as_uint(kc[4 * t + 1]), __float_as_uint(kc[4 * t + 2]), __float_as_uint(kc[4 * t + 3]));
            if (lane == 0) sts32(buf + 7680 + src * 4, __float_as_uint(kc[20]));
            __syncwarp();
            if (lane == 0) mbar_arrive(bar + 8 * (BAR_KP + w4));
        }
    }

    if (warp < 8) {
        asm volatile("setmaxnreg.inc.sync.aligned.u32 160;");
        const int wg = warp >> 2;
        if (warp == 0) STAMP(21);
        float acc[96];
        const int srow = warp * 16 + (lane & 15);
        const uint32_t srow_a = srow * 128;
        const int sx = srow & 7, shi = lane >> 4;
        const uint64_t da0 = mkdesc(sb + wg * 8192, 16, 1024), db0 = mkdesc(sb + 16384, 8192, 1024);
#pragma unroll 1
        for (int kb = 0; kb < 8; kb++) {
            const int s = kb & 3;
            const uint64_t da = da0 + s * (SLOT >> 4), db = db0 + s * (SLOT >> 4);
            if (warp == 0) STAMP(40 + kb);
            mbar_wait(bar + 8 * (BAR_FULL + s), kb >> 2);
            if (warp == 0) STAMP(32 + kb);
            wg_fence();
#pragma unroll
            for (int k = 0; k < 4; k++) wgmma192(acc, da + 2 * k, db + 128 * k, kb | k);
            wg_commit();
            wg_wait<1>();
            if (lane == 0 && kb > 0) mbar_arrive(bar + 8 * (BAR_EMPTY + ((kb - 1) & 3)));
        }
        mbar_wait(bar + 8 * BAR_WPHI, 0);
        wg_wait<0>();
        fence_regs<96>(acc);
        if (lane == 0) mbar_arrive(bar + 8 * BAR_DONE);
        if (warp == 0) STAMP(1);
        uint32_t in[16], qa[16];
        mbar_wait(bar + 8 * BAR_DONE, 0);
#pragma unroll
        for (int r = 0; r < 16; r++) {
            in[r] = pack2(acc[32 + 2 * r], acc[32 + 2 * r + 1]);
            qa[r] = pack2(acc[2 * r], acc[2 * r + 1]);
        }
#pragma unroll
        for (int hh = 0; hh < 4; hh++)
            stsm4(sb + OFF_V + (hh >> 1) * 16384 + srow_a + (((2 * (hh & 1) + shi) ^ sx) << 4), pack2(acc[64 + 8 * hh], acc[65 + 8 * hh]),
                  pack2(acc[66 + 8 * hh], acc[67 + 8 * hh]), pack2(acc[68 + 8 * hh], acc[69 + 8 * hh]), pack2(acc[70 + 8 * hh], acc[71 + 8 * hh]));
        sts128(sb + OFF_V + shi * 16384 + srow_a + ((4 ^ sx) << 4), 0x3f803f80u, 0x3f803f80u, 0x3f803f80u, 0x3f803f80u);
        const uint32_t wphi_a = sb + OFF_WPHI + (lane & 15) * 32 + (lane >> 4) * 16;
        uint32_t pq[4][8];
#pragma unroll 1
        for (int it = 0; it < 2; it++) {
            hedgehog4(in, wphi_a, pq);
            if (it == 1) break;
#pragma unroll
            for (int hs = 0; hs < 8; hs++) {
                float c[4] = {0.f, 0.f, 0.f, 0.f};
                const uint32_t* o = pq[hs >> 1] + 4 * (hs & 1);
                mma16816(c, o[0], o[1], o[2], o[3], 0x3f803f80u, 0x3f803f80u);
                const float r0 = rcp(c[0]), r1 = rcp(c[2]);
                const uint32_t s0 = pack2(r0, r0), s1 = pack2(r1, r1);
                stsm4(sb + OFF_P + (hs >> 2) * 16384 + srow_a + (((2 * (hs & 3) + shi) ^ sx) << 4), hmul2(o[0], s0), hmul2(o[1], s1), hmul2(o[2], s0), hmul2(o[3], s1));
            }
            asm volatile("fence.proxy.async.shared::cta;" ::: "memory");
            bar_named(1, 256);
            if (warp == 0) STAMP(2);
            float d[32];
            const uint64_t dv = mkdesc(sb + OFF_V + wg * 16384, 16, 1024), dp = mkdesc(sb + OFF_P + wg * 16384, 16, 1024);
            wg_fence();
#pragma unroll
            for (int k = 0; k < 8; k++) wgmma64_tt(d, dv + 128 * k, dp + 128 * k, k != 0);
            wg_commit();
            mbar_wait(bar + 8 * BAR_PREP, 0);
            uint4* kvp = scr->kvp + bi * 544 + wg * 272 + (w4 < 2 ? w4 * 136 : 128) + lane;
            wg_wait<0>();
            fence_regs<32>(d);
            if (w4 < 2 || (w4 == 2 && lane < 4)) {
#pragma unroll
                for (int f = 0; f < 4; f++) {
                    const int i0 = 8 * (f >> 1) + 2 * (f & 1), i2 = 16 * (f >> 1) + 8 * (f & 1);
                    const float e0 = w4 == 0 ? d[i0] : (w4 == 1 ? d[16 + i0] : d[i2]), e1 = w4 == 0 ? d[i0 + 1] : (w4 == 1 ? d[17 + i0] : d[i2 + 1]);
                    const float e2 = w4 == 0 ? d[i0 + 4] : (w4 == 1 ? d[20 + i0] : d[i2 + 4]), e3 = w4 == 0 ? d[i0 + 5] : (w4 == 1 ? d[21 + i0] : d[i2 + 5]);
                    st_rlx128(kvp + (w4 < 2 ? f * 32 : (f >> 1) * 136 + (f & 1) * 4), tag4(__float_as_uint(e0), __float_as_uint(e1), __float_as_uint(e2), __float_as_uint(e3), tag));
                }
            }
            __syncwarp();
            if (lane == 0) mbar_arrive(bar + 8 * BAR_PUB);
            if (warp == 0) STAMP(3);
#pragma unroll
            for (int r = 0; r < 16; r++) in[r] = qa[r];
        }
        if (warp == 0) STAMP(4);
        {
            mbar_wait(bar + 8 * BAR_KVF, 0);
            uint4 kf[4][3];
#pragma unroll
            for (int hh = 0; hh < 4; hh++) {
                const uint32_t a = sb + OFF_KVF + hh * 1088;
                kf[hh][0] = lds128(a + lane * 32); kf[hh][1] = lds128(a + lane * 32 + 16); kf[hh][2] = lds128(a + 1024 + q * 16);
            }
            if (warp == 0) STAMP(5);
            uint4* og = scr->o + ((bi_i * 8 + warp) * 32 + bi_j * 4) * 32 + lane;
#pragma unroll
            for (int hh = 0; hh < 4; hh++) {
                float c[6][4];
#pragma unroll
                for (int t = 0; t < 6; t++) { c[t][0] = c[t][1] = c[t][2] = c[t][3] = 0.f; }
                const uint32_t* a = pq[hh];
                const bool od = g & 1;
                mma16816(c[0], a[0], a[1], a[2], a[3], od ? 0x3f803f80u : kf[hh][2].x, od ? 0x3f803f80u : kf[hh][2].y);
                mma16816(c[1], a[4], a[5], a[6], a[7], od ? 0x3f803f80u : kf[hh][2].z, od ? 0x3f803f80u : kf[hh][2].w);
                mma16816(c[2], a[0], a[1], a[2], a[3], kf[hh][0].x, kf[hh][0].y);
                mma16816(c[3], a[0], a[1], a[2], a[3], kf[hh][0].z, kf[hh][0].w);
                mma16816(c[4], a[4], a[5], a[6], a[7], kf[hh][1].x, kf[hh][1].y);
                mma16816(c[5], a[4], a[5], a[6], a[7], kf[hh][1].z, kf[hh][1].w);
                uint32_t w[4];
#pragma unroll
                for (int k = 0; k < 2; k++) {
                    const float rho = c[0][2 * k + 1] * rcp(c[1][2 * k + 1]);
                    const float r = rcp(fmaf(c[0][2 * k + 1], 1e-6f, fmaf(rho, c[1][2 * k], c[0][2 * k]))), rr = r * rho;
                    w[k] = pack2(fmaf(c[4][2 * k], rr, c[2][2 * k] * r), fmaf(c[4][2 * k + 1], rr, c[2][2 * k + 1] * r));
                    w[2 + k] = pack2(fmaf(c[5][2 * k], rr, c[3][2 * k] * r), fmaf(c[5][2 * k + 1], rr, c[3][2 * k + 1] * r));
                }
                st_rlx128(og + hh * 32, tag4(w[0], w[1], w[2], w[3], tag));
            }
        }
        if (warp == 0) STAMP(6);
        float oc[64];
        const int slab = bi_i * 8 + (bi_j >> 2) * 4 + w4;
        const uint8_t* ysrc = (const uint8_t*)scr->y + (size_t)((bi_j & 3) * 32 + wg * 16 + (q >> 1)) * 16384 + slab * 128 + g * 16 + (q & 1) * 8;
        const unsigned* gp = scr->g + (slab * 8 + (g >> 1)) * 8 + (g & 1) * 4;
        uint2 yv[8]; unsigned g0, g1;
        {
            const uint4* osrc = scr->o + (slab * 32 + wg * 16) * 32 + lane;
            uint4 fr[16];
            const unsigned* probe = (const unsigned*)(osrc - lane + ((lane & 3) * 4 + 3) * 32 + 31) + 2;
            {
                unsigned miss = ~0u;
                int n = 0;
#pragma unroll
                for (int s = 0; s < 4; s++) {
#pragma unroll 1
                    while ((miss >> s) & 1) { miss = __ballot_sync(~0u, (ld_rlx(probe) ^ tag) & 1); if (++n > SPIN_LIMIT) break; }
#pragma unroll
                    for (int k = 4 * s; k < 4 * s + 4; k++) fr[k] = ld_rlx128(osrc + k * 32);
                }
            }
            if (warp == 0) STAMP(14);
            mbar_wait(bar + 8 * (wg ? BAR_WO2 : BAR_WO), 0);
            const uint64_t dw = mkdesc(sb + wg * 2 * SLOT, wg ? 32768 : SLOT, 1024);
#pragma unroll
            for (int s = 0; s < 4; s++) {
                int n = 0;
#pragma unroll 1
                while (__builtin_expect(__any_sync(~0u, (bad4(fr[4 * s], tag) | bad4(fr[4 * s + 1], tag) | bad4(fr[4 * s + 2], tag) | bad4(fr[4 * s + 3], tag)) & 1), 0)) {
#pragma unroll
                    for (int k = 4 * s; k < 4 * s + 4; k++) fr[k] = ld_rlx128(osrc + k * 32);
                    if (++n > SPIN_LIMIT) break;
                }
                wg_fence();
#pragma unroll
                for (int hh = 0; hh < 4; hh++) wgmma128_rs(oc, fr[4 * s + hh], dw + 128 * (4 * s + hh), (s | hh) != 0);
                wg_commit();
                if (s == 1) {
                    wg_wait<1>();
#pragma unroll
                    for (int nt = 0; nt < 8; nt++) yv[nt] = ld_rlx64(ysrc + nt * 32768);
                    g0 = ld_rlx(gp); g1 = ld_rlx(gp + 32);
                }
            }
            if (warp == 0) STAMP(7);
            {
                const unsigned* yprobe = scr->yflag + ((bi_j & 3) * 32 + wg * 16 + (lane & 15)) * 8;
                int n = 0;
#pragma unroll 1
                while (true) {
                    uint32_t bad = (g0 ^ tag) | (g1 ^ tag);
#pragma unroll
                    for (int nt = 0; nt < 8; nt++) bad |= yv[nt].x ^ tag;
                    if (!__any_sync(~0u, bad & 1)) break;
#pragma unroll 1
                    while (__any_sync(~0u, (ld_rlx(yprobe) ^ tag) & 1)) { if (++n > SPIN_LIMIT) break; }
#pragma unroll
                    for (int nt = 0; nt < 8; nt++) yv[nt] = ld_rlx64(ysrc + nt * 32768);
                    g0 = ld_rlx(gp); g1 = ld_rlx(gp + 32);
                    if (++n > SPIN_LIMIT) break;
                }
            }
            if (warp == 0) STAMP(28);
        }
        {
            const float ga = bf_hi(g0), gb = bf_hi(g1);
            const float ha = bf_round(1.0f - ga), hb = bf_round(1.0f - gb);
            float yb[32];
#pragma unroll
            for (int nt = 0; nt < 8; nt++) {
                yb[4 * nt] = ha * bf_lo(yv[nt].x); yb[4 * nt + 1] = ha * bf_hi(yv[nt].x);
                yb[4 * nt + 2] = hb * bf_lo(yv[nt].y); yb[4 * nt + 3] = hb * bf_hi(yv[nt].y);
            }
            fence_regs<32>(yb);
            const uint32_t xw = sb + wg * 2 * SLOT + (tid & 127) * 16, xr = sb + (wg ^ 1) * 2 * SLOT + (tid & 127) * 16;
            wg_wait<0>();
            fence_regs<64>(oc);
            bar_named(3 + wg, 128);
#pragma unroll
            for (int r = 0; r < 8; r++)
                sts128(xw + r * 2048, __float_as_uint(oc[32 + 4 * r]), __float_as_uint(oc[33 + 4 * r]), __float_as_uint(oc[34 + 4 * r]), __float_as_uint(oc[35 + 4 * r]));
#pragma unroll
            for (int r = 0; r < 32; r++) yb[r] = fmaf((r & 2) ? gb : ga, oc[r], yb[r]);
            bar_named(1, 256);
            if (warp == 0) STAMP(8);
            uint32_t w[8][2];
#pragma unroll
            for (int nt = 0; nt < 8; nt++) {
                const uint4 p = lds128(xr + nt * 2048);
                w[nt][0] = pack2(fmaf(ga, __uint_as_float(p.x), yb[4 * nt]), fmaf(ga, __uint_as_float(p.y), yb[4 * nt + 1]));
                w[nt][1] = pack2(fmaf(gb, __uint_as_float(p.z), yb[4 * nt + 2]), fmaf(gb, __uint_as_float(p.w), yb[4 * nt + 3]));
            }
            const uint32_t ob = sb + wg * 2 * SLOT + 16384 + w4 * 2048;
#pragma unroll
            for (int nt = 0; nt < 8; nt += 2)
                stsm4(ob + (lane & 15) * 128 + (((nt + shi) ^ (lane & 7)) << 4), w[nt][0], w[nt][1], w[nt + 1][0], w[nt + 1][1]);
            __syncwarp();
            bf16* op = out + (size_t)(slab * 16) * 512 + (bi_j & 3) * 128 + wg * 64 + (lane & 7) * 8;
#pragma unroll
            for (int it = 0; it < 4; it++) {
                const int r = it * 4 + (lane >> 3);
                uint4 v = lds128(ob + r * 128 + (((lane & 7) ^ (r & 7)) << 4));
                *(uint4*)(op + r * 512) = v;
            }
        }
        if (warp == 0) STAMP(10);
    } else if (warp < 12) {
        if (warp == 8) {
            mbar_wait(bar + 8 * BAR_KGA, 0);
            if (lane == 0) load_stage(2);
            STAMP(22);
            mbar_wait(bar + 8 * BAR_KG, 0);
            if (lane == 0) load_stage(3);
            __syncwarp();
            STAMP(17);
        }
        mbar_wait(bar + 8 * (BAR_KP + w4), 0);
#pragma unroll
        for (int t = 0; t < 15; t++) {
            const uint4 v = lds128(buf + (t * 32 + lane) * 16);
            kc[4 * (t % 5)] += __uint_as_float(v.x); kc[4 * (t % 5) + 1] += __uint_as_float(v.y); kc[4 * (t % 5) + 2] += __uint_as_float(v.z); kc[4 * (t % 5) + 3] += __uint_as_float(v.w);
        }
        {
            const uint4 v = lds128(buf + 7680);
            kc[20] += __uint_as_float(v.x) + __uint_as_float(v.y) + __uint_as_float(v.z);
            const uint32_t cnt = 1u + (__float_as_uint(kc[20] + kc[19] + kc[0]) == 0xffc12345u);
            if (lane == 0) asm volatile("mbarrier.arrive.shared::cta.b64 _,[%0],%1;" ::"r"(bar + 8 * BAR_SP), "r"(cnt) : "memory");
            __syncwarp();
        }
        if (warp == 8) {
#pragma unroll 1
            for (int kb = 0; kb < 6; kb++) {
                const int s = kb & 3;
                mbar_wait(bar + 8 * (BAR_EMPTY + s), kb >> 2);
                if (kb == xkb) mbar_wait(bar + 8 * BAR_XT, 0);
                if (lane == 0) {
                    STAMP(48 + kb);
                    if (kb < 4) load_stage(kb + 4);
                    else {
                        mbar_expect(bar + 8 * BAR_WO, 32768);
                        tma2d(sb + s * SLOT, &mwo, (bi_j & 3) * 128 + s * 64, 0, bar + 8 * BAR_WO);
                        if (kb == 5) mbar_arrive(bar + 8 * BAR_SP2);
                    }
                }
                __syncwarp();
            }
        } else if (warp == 9) {
            const int row = bi_j * 16 + (lane >> 1), half = lane & 1;
            unsigned* gp = scr->g + (bi_i * 64 + bi_j * 8) * 8 + lane * 2;
            st_rlx64(gp, tag ^ 1u, tag ^ 1u);
            if (lane < 8) st_rlx32(scr->yflag + bi * 8 + lane, tag ^ 1u);
            float gs0 = 0.f, gs1 = 0.f;
            mbar_wait(bar + 8 * BAR_WPHI, 0);
#pragma unroll 1
            for (int kb = 0; kb < 8; kb++) {
                const int s = kb & 3;
                mbar_wait(bar + 8 * (BAR_FULL + s), kb >> 2);
#pragma unroll
                for (int c = 0; c < 4; c++) {
                    const uint4 xv = lds128(sb + s * SLOT + row * 128 + (((half * 4 + c) ^ (row & 7)) << 4));
                    const uint4 gw = lds128(sb + OFF_GW + ((kb + rot) & 7) * 128 + half * 64 + c * 16);
                    const uint32_t p0 = hmul2(xv.x, gw.x), p1 = hmul2(xv.y, gw.y), p2 = hmul2(xv.z, gw.z), p3 = hmul2(xv.w, gw.w);
                    gs0 += (bf_lo(p0) + bf_lo(p1)) + (bf_lo(p2) + bf_lo(p3));
                    gs1 += (bf_hi(p0) + bf_hi(p1)) + (bf_hi(p2) + bf_hi(p3));
                }
                const uint32_t cnt = 1u + (__float_as_uint(gs0 + gs1) == 0xffc12345u);
                if (lane == 0) asm volatile("mbarrier.arrive.shared::cta.b64 _,[%0],%1;" ::"r"(bar + 8 * (kb < 7 ? BAR_EMPTY + s : BAR_DONE)), "r"(cnt) : "memory");
                __syncwarp();
            }
            float gs = gs0 + gs1;
            gs += __shfl_xor_sync(~0u, gs, 1);
            const uint32_t gv = __float_as_uint(bf_round(rcp(1.0f + ex2(-1.4426950408889634f * bf_round(gs))))) | tag;
            st_rlx64(gp, gv, gv);
        }
        if (lane == 0) kc[4 * 0 + 0] += ((ch & 1) ? bf_hi(pds) : bf_lo(pds));
        const uint32_t k1024 = __shfl_sync(~0u, pack2(kc[4 * 4 + 0], 0.f), 0);
#pragma unroll
        for (int i = 0; i < 2; i++) {
            const int be = g + 8 * i;
#pragma unroll
            for (int t = 0; t < 2; t++) {
                const uint32_t a = kb_ + (KW_D + 128 * t + 8 * be + 2 * q) * 4;
                const uint32_t w = pack2(kc[4 * t + 2 * i + 1], kc[4 * t + 2 * i]);
                sts32(a + 4, w); sts16(a, w >> 16); sts16(a + 10, w);
            }
            {
                const int p = 256 + 128 * (q >> 1) + 8 * be + 4 * (q & 1);
                const uint32_t a = kb_ + (KW_D + p) * 4;
                const uint32_t w = pack2(kc[4 * 2 + 2 * i + 1], kc[4 * 2 + 2 * i]);
                const uint32_t aa = (w >> 16) | (w & 0xffff0000u);
                if (p != 256) { sts16(a - 4, aa); sts32(a, aa); } else sts16(a, aa);
                sts32(a + 4, aa); sts32(a + 8, w); sts16(a + 14, w);
            }
            {
                const int k = 64 + 16 * q + be;
                const uint32_t w = pack2(kc[4 * 3 + 2 * i], kc[4 * 3 + 2 * i + 1]);
                if (k != 64) sts16(kb_ + (KW_2 + ((k - 1) >> 1) - 24) * 4 + (k & 1) * 2, w);
                else {
                    const uint32_t a = kb_ + (KW_D + 511) * 4, aa = (w << 16) | (w & 0xffffu);
                    sts16(a, w); sts32(a + 4, aa); sts32(a + 8, aa); sts32(a + 12, aa); sts16(a + 18, w);
                }
                sts16(kb_ + (KW_2 + 48 + (k >> 1) - 24) * 4 + ((k & 1) ^ 1) * 2, w >> 16);
            }
#pragma unroll
            for (int b = 0; b < 2; b++) {
                const int k = 64 + 8 * (2 * q + b) + (be >> 1);
                const uint32_t w = pack2(kc[4 * 4 + 2 * i + b], 0.f);
                if (!(be & 1) && k == 64) sts16(kb_ + (KW_2 + 63 - 24) * 4, w);
                else {
                    const uint32_t a = kb_ + (KW_3 + ((be & 1) ? 80 + k : k - 1) - 48) * 4;
                    sts16(a, w);
                    if (!((be & 1) && k == 127)) sts16(a + 6, w);
                }
            }
        }
        if (lane == 0) sts16(kb_ + (KW_3 + 127 - 48) * 4, pack2(kc[4 * 5 + 0], 0.f));
        __syncwarp();
        asm volatile("setmaxnreg.inc.sync.aligned.u32 136;");
        mbar_wait(bar + 8 * BAR_UR, 0);
        mbar_wait(bar + 8 * BAR_DONE, 0);
        if (warp == 8) STAMP(23);
        float y[16][4];
#pragma unroll
        for (int nt = 0; nt < 16; nt++) { y[nt][0] = y[nt][1] = y[nt][2] = y[nt][3] = 0.f; }
        {
            uint32_t Bp[32], A[4][3], An[4][3];
            auto uaddr = [&](int rho) { const int R0 = (lane >> 4) * 64 + (lane & 7) - rho; return ub + (((2 * R0 + ((lane >> 3) & 1)) ^ ((R0 >> 2) & 1)) << 4); };
            const uint32_t kd = kb_ + (KW_D + g - 2 * q) * 4;
#pragma unroll 1
            for (int rho = 1; rho >= 0; rho--) {
                const uint32_t a = uaddr(rho), k = kd + 2048 + rho * 64;
#pragma unroll
                for (int i = 0; i < 8; i++) ldsm4(Bp + 4 * i, a + i * 256);
                const uint32_t a0 = lds32(k), a1 = lds32(k + 32), a2 = lds32(k - 32);
#pragma unroll
                for (int i = 0; i < 12; i++) mma16816(y[i + 4], a0, a1, a2, a0, Bp[4 * (i & 7) + 2 * (i >> 3)], Bp[4 * (i & 7) + 2 * (i >> 3) + 1]);
            }
#pragma unroll
            for (int ga = 0; ga < 4; ga++) { An[ga][0] = lds32(kd + ga * 512); An[ga][1] = lds32(kd + ga * 512 + 32); An[ga][2] = lds32(kd + ga * 512 - 32); }
#pragma unroll 1
            for (int rho = 0; rho < 8; rho++) {
#pragma unroll
                for (int ga = 0; ga < 4; ga++) {
                    const uint32_t a = kd + (rho + 1) * 64 + ga * 512;
                    A[ga][0] = An[ga][0]; A[ga][1] = An[ga][1]; A[ga][2] = An[ga][2];
                    An[ga][0] = lds32(a); An[ga][1] = lds32(a + 32); An[ga][2] = lds32(a - 32);
                }
                const uint32_t an = uaddr(rho + 1);
#pragma unroll
                for (int i = 0; i < 8; i++) {
#pragma unroll
                    for (int ga = 0; ga < 4; ga++) {
                        mma16816(y[i + ga], A[ga][0], A[ga][1], A[ga][2], A[ga][0], Bp[4 * i], Bp[4 * i + 1]);
                        if (i + 8 + ga < 16) mma16816(y[i + 8 + ga], A[ga][0], A[ga][1], A[ga][2], A[ga][0], Bp[4 * i + 2], Bp[4 * i + 3]);
                    }
                    ldsm4(Bp + 4 * i, an + i * 256);
                    __syncwarp();
                }
            }
        }
        if (warp == 8) STAMP(18);
        mbar_wait(bar + 8 * BAR_WR, 0);
#pragma unroll 1
        for (int ph = 0; ph < 2; ph++) {
            uint32_t B[5][2];
            const uint32_t ka = kb_ + (KW_2 + ph * 48 + 8 + g - q) * 4;
#pragma unroll
            for (int dd = 0; dd < 5; dd++) { B[dd][0] = lds32(ka + dd * 32); B[dd][1] = lds32(ka + dd * 32 - 16); }
            const uint32_t wa = buf + ph * W3_OFF + ((lane & 7) + ((lane >> 3) & 1) + (lane >> 4) * 8) * 16;
#pragma unroll
            for (int s = 0; s < 12; s++) {
                uint32_t A[4];
                ldsm4t(A, wa + s * 256);
#pragma unroll
                for (int dd = 0; dd < 5; dd++)
                    if (s + 4 + dd < 16) mma16816(y[s + 4 + dd], A[0], A[1], A[2], A[3], B[dd][0], B[dd][1]);
            }
        }
        {
            const int ap = (lane & 7) + (lane >> 4) * 8;
            const uint32_t loff = ((2 * ap + ((lane >> 3) & 1)) ^ ((ap >> 2) & 1)) << 4;
#pragma unroll 1
            for (int ph = 0; ph < 2; ph++) {
                uint32_t B[8][2];
                const uint32_t wb = (ph ? spare : buf + W9_OFF) + loff;
                const uint32_t ka = kb_ + (KW_3 + ph * 80 + 16 + g - 2 * q) * 4;
#pragma unroll
                for (int dd = 0; dd < 8; dd++) { B[dd][0] = lds32(ka + dd * 32); B[dd][1] = lds32(ka + dd * 32 - 32); }
#pragma unroll
                for (int s = 0; s < 4; s++) {
                    uint32_t A[4];
                    ldsm4t(A, wb + s * 512);
#pragma unroll
                    for (int dd = 0; dd < 8; dd++)
                        if (8 + 2 * s + dd < 16) mma16816(y[8 + 2 * s + dd], A[0], A[1], A[2], A[3], B[dd][0], B[dd][1]);
                }
            }
            const uint32_t idw = (g == 2 * q) ? k1024 : ((g == 2 * q + 1) ? (k1024 << 16) : 0u);
#pragma unroll
            for (int s = 0; s < 4; s++) {
                uint32_t A[4];
                ldsm4t(A, spare + 2048 + loff + s * 512);
                mma16816(y[8 + 2 * s], A[0], A[1], A[2], A[3], idw, 0u);
                mma16816(y[9 + 2 * s], A[0], A[1], A[2], A[3], 0u, idw);
            }
        }
        __syncwarp();
        if (warp == 8) STAMP(19);
#pragma unroll
        for (int nt = 0; nt < 16; nt++)
#pragma unroll
            for (int b = 0; b < 2; b++) sts32(buf + ((8 * nt + 2 * q + b) * 8 + g) * 4, pack2(y[nt][b], y[nt][2 + b]));
        bar_named(2, 128);
        uint4* yp = scr->y + bi * 1024 + st;
#pragma unroll
        for (int v = 0; v < 8; v++) {
            const uint32_t a = sb + OFF_BUF + (st + 128 * v) * 4;
            const uint32_t w0 = lds32(a), w1 = lds32(a + BUF_STRIDE), w2 = lds32(a + 2 * BUF_STRIDE), w3 = lds32(a + 3 * BUF_STRIDE);
            st_rlx128(yp + v * 128, tag4(__byte_perm(w0, w1, 0x5410), __byte_perm(w0, w1, 0x7632), __byte_perm(w2, w3, 0x5410), __byte_perm(w2, w3, 0x7632), tag));
        }
        if (st < 8) st_rlx32(scr->yflag + bi * 8 + st, tag);
        if (warp == 8) STAMP(20);
    } else {
        asm volatile("setmaxnreg.dec.sync.aligned.u32 56;");
        const int qq = (bi_i & 2) + ((lane >> 1) & 1);
        uint2* kvf_h = (uint2*)(scr->kvf + (bi_j * 4 + (bi_i >> 2)) * 68);
        auto windows = [&](int rhi, int rlo) {
#pragma unroll 1
            for (int rho = rhi; rho >= rlo; rho--) {
                const int ci = lane + 32 * rho;
                uint4 e4[4];
#pragma unroll
                for (int v = 0; v < 4; v++) { const int cc = ci - 3 + v; e4[v] = lds128(ub + ((cc ^ ((cc >> 3) & 1)) << 4)); }
                float S[29];
                const uint32_t* ew = (const uint32_t*)e4;
                S[3] = 0.f;
#pragma unroll
                for (int k = 4; k <= 28; k++) S[k] = S[k - 1] + ((k & 1) ? bf_hi(ew[k >> 1]) : bf_lo(ew[k >> 1]));
                auto win = [&](int lo, int hi, uint32_t a) {
                    sts128(a, pack2(S[hi] - S[lo - 1], S[hi + 1] - S[lo]), pack2(S[hi + 2] - S[lo + 1], S[hi + 3] - S[lo + 2]),
                           pack2(S[hi + 4] - S[lo + 3], S[hi + 5] - S[lo + 4]), pack2(S[hi + 6] - S[lo + 5], S[hi + 7] - S[lo + 6]));
                };
                win(14, 18, buf + W5_OFF + 16 + ci * 16); win(19, 21, buf + W3_OFF + 16 + ci * 16);
                if (rho < 4) {
                    const uint32_t sw = (ci ^ ((ci >> 3) & 1)) << 4;
                    win(4, 12, buf + W9_OFF + sw); win(13, 19, spare + sw); win(20, 21, spare + 2048 + sw);
                }
            }
        };
        {
            mbar_wait(bar + 8 * (BAR_FULL + xkb), 0);
#pragma unroll 1
            for (int hf = 0; hf < 2; hf++) {
                const int r = w4 * 32 + hf * 16 + (lane & 15);
                uint32_t* xt = (uint32_t*)scr->xt + ((xkb + rot) * 16 + (g >> 2)) * 4096 + (bi_i * 16 + w4 * 4 + hf * 2) * 16 + (g & 3) * 4 + q;
#pragma unroll
                for (int cb = 0; cb < 8; cb += 2) {
                    uint32_t v[4];
                    ldsm4t(v, sb + xkb * SLOT + r * 128 + (((cb + (lane >> 4)) ^ (r & 7)) << 4));
                    xt[cb * 8192] = v[0]; xt[cb * 8192 + 16] = v[1]; xt[cb * 8192 + 8192] = v[2]; xt[cb * 8192 + 8192 + 16] = v[3];
                }
            }
            __syncwarp();
            if (lane == 0) {
                mbar_arrive(bar + 8 * BAR_XT);
                STAMP(26);
                asm volatile("red.release.gpu.global.add.u32 [%0],2;" ::"l"(scr->xcnt + (xkb + rot) * 32) : "memory");
                STAMP(27);
            }
            __syncwarp();
            {
                const uint32_t old = tag ^ 1u;
                const uint4 z4 = make_uint4(old, 0, old, 0);
#pragma unroll
                for (int v = 0; v < 5; v++) if (v < 4 || st < 32) st_rlx128(scr->kvp + bi * 544 + v * 128 + st, z4);
                if (st < 16) st_rlx128(scr->o + ((bi_i * 8 + (st >> 1)) * 32 + bi_j * 4 + 3) * 32 + 30 + (st & 1), z4);
                if (lane < 8) st_rlx64(kvf_h + ((bi_i & 3) * 8 + w4 * 2 + (lane & 1)) * 4 + (lane >> 1), old, 0);
                if (st < 4 && !(bi_i & 1)) st_rlx64(kvf_h + (64 + qq) * 2 + (lane & 1), old, 0);
                __syncwarp();
                if (lane == 0) mbar_arrive(bar + 8 * BAR_PREP);
            }
            int n = 0;
#pragma unroll 1
            while (__any_sync(~0u, (int)(ld_acq(scr->xcnt + bi_j * 32) - (epoch1 << 7)) < 0)) { if (++n > SPIN_LIMIT) break; }
            if (warp == 12) STAMP(15);
            uint4 ur[8];
#pragma unroll
            for (int v = 0; v < 8; v++) ur[v] = __ldcg(scr->xt + bi * 1024 + st + 128 * v);
            mbar_wait(bar + 8 * BAR_SP, 0);
            if (lane < 16) sts128(ub - 256 + lane * 16, 0, 0, 0, 0);
            if (lane < 2) sts128(buf + lane * W3_OFF, 0, 0, 0, 0);
#pragma unroll
            for (int v = 0; v < 8; v++) {
                const int ci = (st >> 2) + 32 * v;
                sts128(sb + OFF_U + (st & 3) * U_STRIDE + 256 + ((ci ^ ((ci >> 3) & 1)) << 4), ur[v].x, ur[v].y, ur[v].z, ur[v].w);
            }
            __syncwarp();
            if (lane == 0) mbar_arrive(bar + 8 * BAR_UR);
            mbar_wait(bar + 8 * BAR_UR, 0);
            if (warp == 12) STAMP(16);
            windows(5, 4);
        }
        mbar_wait(bar + 8 * BAR_SP2, 0);
        windows(3, 0);
        __syncwarp();
        if (lane == 0) mbar_arrive(bar + 8 * BAR_WR);
        if (warp == 12) STAMP(24);
        {
            const bool zw = st < 32 && !(bi_i & 1);
            const uint4* src = scr->kvp + bi_j * (16 * 544) + (bi_i >> 2) * 136;
            const uint4* zsrc = src + (lane >> 2) * (2 * 544) + 128 + (lane & 1) * 4 + qq;
            src += (lane >> 3) * (4 * 544) + ((lane >> 1) & 3) * 32 + (bi_i & 3) * 8 + w4 * 2 + (lane & 1);
            mbar_wait(bar + 8 * BAR_PUB, 0);
            if (warp == 12) STAMP(12);
            uint4 v[6];
#pragma unroll
            for (int k = 0; k < 6; k++) v[k] = make_uint4(tag ^ 1u, 0, 0, 0);
            int n = 0;
#pragma unroll 1
            while (true) {
#pragma unroll
                for (int k = 0; k < 6; k++) if ((bad4(v[k], tag) & 1) && (k < 4 || zw)) v[k] = ld_rlx128(k < 4 ? src + k * 544 : zsrc + (k - 4) * 544);
                if (!__any_sync(~0u, (bad4(v[0], tag) | bad4(v[1], tag) | bad4(v[2], tag) | bad4(v[3], tag) | (zw ? bad4(v[4], tag) | bad4(v[5], tag) : 0u)) & 1)) break;
                if (++n > SPIN_LIMIT) break;
            }
            if (warp == 12) STAMP(30);
            float f[8];
            const float* vf = (const float*)v;
#pragma unroll
            for (int r = 0; r < 4; r++) {
                f[r] = (vf[r] + vf[4 + r]) + (vf[8 + r] + vf[12 + r]);
                f[4 + r] = vf[16 + r] + vf[20 + r];
                f[4 + r] += __shfl_xor_sync(~0u, f[4 + r], 4);
            }
#pragma unroll
            for (int o = 8; o <= 16; o <<= 1)
#pragma unroll
                for (int r = 0; r < 8; r++) f[r] += __shfl_xor_sync(~0u, f[r], o);
            if (lane < 8) st_rlx64(kvf_h + ((bi_i & 3) * 8 + w4 * 2 + (lane & 1)) * 4 + (lane >> 1), tagw(pack2(f[0], f[1]), tag), pack2(f[2], f[3]));
            if (zw && lane < 4) st_rlx64(kvf_h + (64 + qq) * 2 + (lane & 1), tagw(pack2(f[4], f[5]), tag), pack2(f[6], f[7]));
        }
        if (warp == 12) STAMP(13);
        {
            const uint4* kp = scr->kvf + bi_j * 272 + st;
            uint4 v0 = make_uint4(tag ^ 1u, 0, 0, 0), v1 = v0, v2 = make_uint4(st < 16 ? tag ^ 1u : tag, 0, tag, 0);
            int n = 0;
#pragma unroll 1
            while (true) {
                if (bad4(v0, tag) & 1) v0 = ld_rlx128(kp);
                if (bad4(v1, tag) & 1) v1 = ld_rlx128(kp + 128);
                if (bad4(v2, tag) & 1) v2 = ld_rlx128(kp + 256);
                if (!__any_sync(~0u, (bad4(v0, tag) | bad4(v1, tag) | bad4(v2, tag)) & 1)) break;
                if (++n > SPIN_LIMIT) break;
            }
            sts128(sb + OFF_KVF + st * 16, v0.x, v0.y, v0.z, v0.w);
            sts128(sb + OFF_KVF + 2048 + st * 16, v1.x, v1.y, v1.z, v1.w);
            if (st < 16) sts128(sb + OFF_KVF + 4096 + st * 16, v2.x, v2.y, v2.z, v2.w);
            __syncwarp();
            if (lane == 0) mbar_arrive(bar + 8 * BAR_KVF);
        }
        if (warp == 13) {
            mbar_wait(bar + 8 * BAR_KVF, 0);
            if (lane == 0) {
                mbar_expect(bar + 8 * BAR_WO2, 65536);
                tma2d(sb + OFF_P, &mwo, (bi_j & 3) * 128 + 64, 256, bar + 8 * BAR_WO2);
                tma2d(sb + OFF_V, &mwo, (bi_j & 3) * 128, 256, bar + 8 * BAR_WO2);
            }
        }
        if (warp == 12) STAMP(25);
    }
    __syncwarp();
    if (lane == 0) {
        unsigned old;
        asm volatile("atom.acq_rel.cta.shared.add.u32 %0,[%1],1;" : "=r"(old) : "r"(bar + OFF_CNT) : "memory");
        if (old == 15) {
            atomicAdd(scr->done, 1u);
        }
    }
}

typedef CUresult (*EncFn)(CUtensorMap*, CUtensorMapDataType, cuuint32_t, void*, const cuuint64_t*, const cuuint64_t*, const cuuint32_t*,
                          const cuuint32_t*, CUtensorMapInterleave, CUtensorMapSwizzle, CUtensorMapL2promotion, CUtensorMapFloatOOBfill);

extern "C" void kernel_launch(void* const* d_in, const int* in_sizes, int n_in, void* d_out, int out_size) {
    static EncFn enc = nullptr;
    static Scratch* scr = nullptr;
    if (!enc) {
        cudaGetSymbolAddress((void**)&scr, g_scr);
        cudaDriverEntryPointQueryResult qr;
        cudaGetDriverEntryPoint("cuTensorMapEncodeTiled", (void**)&enc, cudaEnableDefault, &qr);
        cudaFuncSetAttribute(fused_kernel, cudaFuncAttributeMaxDynamicSharedMemorySize, SMEM_BYTES);
    }
    CUtensorMap mx, mw, mwo;
    const cuuint32_t es[3] = {1, 1, 1};
    {
        cuuint64_t d[2] = {512, 2048}, s[1] = {1024}; cuuint32_t b[2] = {64, 128};
        enc(&mx, CU_TENSOR_MAP_DATA_TYPE_BFLOAT16, 2, d_in[0], d, s, b, es, CU_TENSOR_MAP_INTERLEAVE_NONE, CU_TENSOR_MAP_SWIZZLE_128B,
            CU_TENSOR_MAP_L2_PROMOTION_L2_128B, CU_TENSOR_MAP_FLOAT_OOB_FILL_NONE);
    }
    {
        cuuint64_t d[3] = {512, 512, 3}, s[2] = {3072, 1024}; cuuint32_t b[3] = {64, 64, 3};
        enc(&mw, CU_TENSOR_MAP_DATA_TYPE_BFLOAT16, 3, d_in[1], d, s, b, es, CU_TENSOR_MAP_INTERLEAVE_NONE, CU_TENSOR_MAP_SWIZZLE_128B,
            CU_TENSOR_MAP_L2_PROMOTION_L2_128B, CU_TENSOR_MAP_FLOAT_OOB_FILL_NONE);
    }
    {
        cuuint64_t d[2] = {512, 512}, s[1] = {1024}; cuuint32_t b[2] = {64, 256};
        enc(&mwo, CU_TENSOR_MAP_DATA_TYPE_BFLOAT16, 2, d_in[3], d, s, b, es, CU_TENSOR_MAP_INTERLEAVE_NONE, CU_TENSOR_MAP_SWIZZLE_128B,
            CU_TENSOR_MAP_L2_PROMOTION_L2_128B, CU_TENSOR_MAP_FLOAT_OOB_FILL_NONE);
    }
    fused_kernel<<<128, 512, SMEM_BYTES, cudaStreamPerThread>>>(
        scr, (const bf16*)d_in[5], (const bf16*)d_in[6], (const bf16*)d_in[7], (const bf16*)d_in[8], (const bf16*)d_in[9],
        (const bf16*)d_in[10], (const bf16*)d_in[2], (const bf16*)d_in[11], (bf16*)d_out, mx, mw, mwo);
}
```

```cpp
#include <cuda_runtime.h>
#include <cuda.h>
#include <cuda_bf16.h>
#include <stdint.h>

typedef __nv_bfloat16 bf16;

struct Scratch {
    uint4 xt[128 * 1024];
    uint4 o[16 * 8 * 32 * 32];
    uint4 y[128 * 1024];
    uint4 kvp[8 * 16 * 544];
    uint4 kvf[8 * 4 * 68];
    unsigned g[1024 * 8];
    unsigned yflag[128 * 8];
    unsigned xcnt[8 * 32];
    unsigned done[32];
};
__device__ Scratch g_scr;
#define STAMP(n)

constexpr int SLOT = 40960;
constexpr int OFF_SP0 = 32768, OFF_SP1 = SLOT + 32768;
constexpr int OFF_P = 2 * SLOT, OFF_V = OFF_P + 32768;
constexpr int OFF_KVF = OFF_V + 32768;
constexpr int KT_BYTES = 3264, KW_D = 16, KW_2 = 560, KW_3 = 656;
constexpr int OFF_U = 4 * SLOT, U_STRIDE = 4096 + 256 + 32;
constexpr int OFF_BUF = OFF_U + 4 * U_STRIDE, BUF_STRIDE = 8320;
constexpr int OFF_K = OFF_BUF + 4 * BUF_STRIDE;
constexpr int OFF_WPHI = OFF_K + 4 * KT_BYTES;
constexpr int OFF_GW = OFF_WPHI + 2048;
constexpr int OFF_BAR = OFF_GW + 1024;
constexpr int SMEM_BYTES = OFF_BAR + 320 + 256;
static_assert(SMEM_BYTES <= 232448 && OFF_BUF % 128 == 0, "smem");
constexpr int W5_OFF = 0, W3_OFF = 3088, W9_OFF = 6176;
constexpr int BAR_FULL = 0, BAR_EMPTY = 4, BAR_WPHI = 8, BAR_WO = 9, BAR_WO2 = 10, BAR_XT = 11, BAR_DONE = 12, BAR_KG = 13, BAR_SP = 14,
              BAR_PUB = 15, BAR_KVF = 16, BAR_UR = 17, BAR_WR = 18, BAR_PREP = 19, BAR_KGA = 20, BAR_SP2 = 21, BAR_KS = 22, BAR_KP = 26, BAR_KD = 30, OFF_CNT = 272;
constexpr int SPIN_LIMIT = 1 << 17;

__device__ __forceinline__ uint32_t s2u(const void* p) { return (uint32_t)__cvta_generic_to_shared(p); }
__device__ __forceinline__ void mbar_init(uint32_t b, int c) { asm volatile("mbarrier.init.shared::cta.b64 [%0],%1;" ::"r"(b), "r"(c) : "memory"); }
__device__ __forceinline__ void mbar_expect(uint32_t b, int bytes) { asm volatile("mbarrier.arrive.expect_tx.shared::cta.b64 _,[%0],%1;" ::"r"(b), "r"(bytes) : "memory"); }
__device__ __forceinline__ void mbar_arrive(uint32_t b) { asm volatile("mbarrier.arrive.shared::cta.b64 _,[%0];" ::"r"(b) : "memory"); }
__device__ __forceinline__ void mbar_wait(uint32_t b, int ph) {
    asm volatile("{\n.reg .pred p;\n.reg .u32 n;\nmov.u32 n,0;\nLW_%=:\nmbarrier.try_wait.parity.shared::cta.b64 p,[%0],%1;\n@p bra LD_%=;\n"
                 "add.u32 n,n,1;\nsetp.lt.u32 p,n,16384;\n@p bra LW_%=;\nLD_%=:\n}" ::"r"(b), "r"(ph) : "memory");
}
__device__ __forceinline__ void tma2d(uint32_t dst, const CUtensorMap* m, int c0, int c1, uint32_t bar) {
    asm volatile("cp.async.bulk.tensor.2d.shared::cluster.global.mbarrier::complete_tx::bytes [%0],[%1,{%3,%4}],[%2];" ::"r"(dst), "l"(m), "r"(bar), "r"(c0), "r"(c1) : "memory");
}
__device__ __forceinline__ void tma3d(uint32_t dst, const CUtensorMap* m, int c0, int c1, int c2, uint32_t bar) {
    asm volatile("cp.async.bulk.tensor.3d.shared::cluster.global.mbarrier::complete_tx::bytes [%0],[%1,{%3,%4,%5}],[%2];" ::"r"(dst), "l"(m), "r"(bar), "r"(c0), "r"(c1), "r"(c2) : "memory");
}
__device__ __forceinline__ void bulk_g2s(uint32_t dst, const void* src, int bytes, uint32_t bar) {
    asm volatile("cp.async.bulk.shared::cluster.global.mbarrier::complete_tx::bytes [%0],[%1],%2,[%3];" ::"r"(dst), "l"(src), "r"(bytes), "r"(bar) : "memory");
}
__device__ __forceinline__ uint64_t mkdesc(uint32_t addr, uint32_t lbo, uint32_t sbo) {
    return (uint64_t)((addr & 0x3FFFF) >> 4) | ((uint64_t)(lbo >> 4) << 16) | ((uint64_t)(sbo >> 4) << 32) | ((uint64_t)1 << 62);
}
__device__ __forceinline__ void wg_fence() { asm volatile("wgmma.fence.sync.aligned;" ::: "memory"); }
__device__ __forceinline__ void wg_commit() { asm volatile("wgmma.commit_group.sync.aligned;" ::: "memory"); }
template <int N> __device__ __forceinline__ void wg_wait() { asm volatile("wgmma.wait_group.sync.aligned %0;" ::"n"(N) : "memory"); }
template <int N> __device__ __forceinline__ void fence_regs(float* d) {
#pragma unroll
    for (int i = 0; i < N; i++) asm volatile("" : "+f"(d[i])::"memory");
}
#define R8(d, o) "+f"(d[o]), "+f"(d[o + 1]), "+f"(d[o + 2]), "+f"(d[o + 3]), "+f"(d[o + 4]), "+f"(d[o + 5]), "+f"(d[o + 6]), "+f"(d[o + 7])
__device__ __forceinline__ void wgmma192(float* d, uint64_t da, uint64_t db, int sc) {
    asm volatile("{.reg .pred p; setp.ne.b32 p,%98,0; wgmma.mma_async.sync.aligned.m64n192k16.f32.bf16.bf16 {"
                 "%0,%1,%2,%3,%4,%5,%6,%7,%8,%9,%10,%11,%12,%13,%14,%15,%16,%17,%18,%19,%20,%21,%22,%23,%24,%25,%26,%27,%28,%29,%30,%31,"
                 "%32,%33,%34,%35,%36,%37,%38,%39,%40,%41,%42,%43,%44,%45,%46,%47,%48,%49,%50,%51,%52,%53,%54,%55,%56,%57,%58,%59,%60,%61,%62,%63,"
                 "%64,%65,%66,%67,%68,%69,%70,%71,%72,%73,%74,%75,%76,%77,%78,%79,%80,%81,%82,%83,%84,%85,%86,%87,%88,%89,%90,%91,%92,%93,%94,%95},"
                 "%96,%97,p,1,1,0,1;}"
                 : R8(d, 0), R8(d, 8), R8(d, 16), R8(d, 24), R8(d, 32), R8(d, 40), R8(d, 48), R8(d, 56), R8(d, 64), R8(d, 72), R8(d, 80), R8(d, 88)
                 : "l"(da), "l"(db), "r"(sc));
}
__device__ __forceinline__ void wgmma64_tt(float* d, uint64_t da, uint64_t db, int sc) {
    asm volatile("{.reg .pred p; setp.ne.b32 p,%34,0; wgmma.mma_async.sync.aligned.m64n64k16.f32.bf16.bf16 {"
                 "%0,%1,%2,%3,%4,%5,%6,%7,%8,%9,%10,%11,%12,%13,%14,%15,%16,%17,%18,%19,%20,%21,%22,%23,%24,%25,%26,%27,%28,%29,%30,%31},"
                 "%32,%33,p,1,1,1,1;}"
                 : R8(d, 0), R8(d, 8), R8(d, 16), R8(d, 24)
                 : "l"(da), "l"(db), "r"(sc));
}
__device__ __forceinline__ void wgmma128_rs(float* d, const uint4& a, uint64_t db, int sc) {
    asm volatile("{.reg .pred p; setp.ne.b32 p,%69,0; wgmma.mma_async.sync.aligned.m64n128k16.f32.bf16.bf16 {"
                 "%0,%1,%2,%3,%4,%5,%6,%7,%8,%9,%10,%11,%12,%13,%14,%15,%16,%17,%18,%19,%20,%21,%22,%23,%24,%25,%26,%27,%28,%29,%30,%31,"
                 "%32,%33,%34,%35,%36,%37,%38,%39,%40,%41,%42,%43,%44,%45,%46,%47,%48,%49,%50,%51,%52,%53,%54,%55,%56,%57,%58,%59,%60,%61,%62,%63},"
                 "{%64,%65,%66,%67},%68,p,1,1,1;}"
                 : R8(d, 0), R8(d, 8), R8(d, 16), R8(d, 24), R8(d, 32), R8(d, 40), R8(d, 48), R8(d, 56)
                 : "r"(a.x), "r"(a.y), "r"(a.z), "r"(a.w), "l"(db), "r"(sc));
}
__device__ __forceinline__ void mma16816(float* c, uint32_t a0, uint32_t a1, uint32_t a2, uint32_t a3, uint32_t b0, uint32_t b1) {
    asm("mma.sync.aligned.m16n8k16.row.col.f32.bf16.bf16.f32 {%0,%1,%2,%3},{%4,%5,%6,%7},{%8,%9},{%0,%1,%2,%3};"
        : "+f"(c[0]), "+f"(c[1]), "+f"(c[2]), "+f"(c[3]) : "r"(a0), "r"(a1), "r"(a2), "r"(a3), "r"(b0), "r"(b1));
}
__device__ __forceinline__ void ldsm4(uint32_t* r, uint32_t a) {
    asm volatile("ldmatrix.sync.aligned.m8n8.x4.shared.b16 {%0,%1,%2,%3},[%4];" : "=r"(r[0]), "=r"(r[1]), "=r"(r[2]), "=r"(r[3]) : "r"(a) : "memory");
}
__device__ __forceinline__ void ldsm4t(uint32_t* r, uint32_t a) {
    asm volatile("ldmatrix.sync.aligned.m8n8.x4.trans.shared.b16 {%0,%1,%2,%3},[%4];" : "=r"(r[0]), "=r"(r[1]), "=r"(r[2]), "=r"(r[3]) : "r"(a) : "memory");
}
__device__ __forceinline__ void stsm4(uint32_t a, uint32_t r0, uint32_t r1, uint32_t r2, uint32_t r3) {
    asm volatile("stmatrix.sync.aligned.m8n8.x4.shared.b16 [%0],{%1,%2,%3,%4};" ::"r"(a), "r"(r0), "r"(r1), "r"(r2), "r"(r3) : "memory");
}
__device__ __forceinline__ uint32_t lds32(uint32_t a) { uint32_t v; asm volatile("ld.shared.b32 %0,[%1];" : "=r"(v) : "r"(a) : "memory"); return v; }
__device__ __forceinline__ uint4 lds128(uint32_t a) { uint4 v; asm volatile("ld.shared.v4.b32 {%0,%1,%2,%3},[%4];" : "=r"(v.x), "=r"(v.y), "=r"(v.z), "=r"(v.w) : "r"(a) : "memory"); return v; }
__device__ __forceinline__ void sts16(uint32_t a, uint32_t v) { asm volatile("st.shared.b16 [%0],%1;" ::"r"(a), "h"((unsigned short)v) : "memory"); }
__device__ __forceinline__ void sts32(uint32_t a, uint32_t v) { asm volatile("st.shared.b32 [%0],%1;" ::"r"(a), "r"(v) : "memory"); }
__device__ __forceinline__ void sts64(uint32_t a, uint32_t x, uint32_t y) { asm volatile("st.shared.v2.b32 [%0],{%1,%2};" ::"r"(a), "r"(x), "r"(y) : "memory"); }
__device__ __forceinline__ void sts128(uint32_t a, uint32_t x, uint32_t y, uint32_t z, uint32_t w) { asm volatile("st.shared.v4.b32 [%0],{%1,%2,%3,%4};" ::"r"(a), "r"(x), "r"(y), "r"(z), "r"(w) : "memory"); }
__device__ __forceinline__ uint32_t pack2(float lo, float hi) { uint32_t d; asm("cvt.rn.bf16x2.f32 %0,%1,%2;" : "=r"(d) : "f"(hi), "f"(lo)); return d; }
__device__ __forceinline__ float bf_lo(uint32_t v) { return __uint_as_float(v << 16); }
__device__ __forceinline__ float bf_hi(uint32_t v) { return __uint_as_float(v & 0xffff0000u); }
__device__ __forceinline__ float bf_round(float v) { return bf_lo(pack2(v, 0.f)); }
__device__ __forceinline__ uint32_t hmax2(uint32_t a, uint32_t b) { uint32_t d; asm("max.bf16x2 %0,%1,%2;" : "=r"(d) : "r"(a), "r"(b)); return d; }
__device__ __forceinline__ uint32_t hmin2(uint32_t a, uint32_t b) { uint32_t d; asm("min.bf16x2 %0,%1,%2;" : "=r"(d) : "r"(a), "r"(b)); return d; }
__device__ __forceinline__ uint32_t hmul2(uint32_t a, uint32_t b) { uint32_t d; asm("mul.rn.bf16x2 %0,%1,%2;" : "=r"(d) : "r"(a), "r"(b)); return d; }
__device__ __forceinline__ float ex2(float x) { float y; asm("ex2.approx.ftz.f32 %0,%1;" : "=f"(y) : "f"(x)); return y; }
__device__ __forceinline__ float rcp(float x) { float y; asm("rcp.approx.ftz.f32 %0,%1;" : "=f"(y) : "f"(x)); return y; }
__device__ __forceinline__ uint32_t ld_nc(const uint32_t* p) { uint32_t v; asm volatile("ld.global.nc.b32 %0,[%1];" : "=r"(v) : "l"(p)); return v; }
__device__ __forceinline__ uint2 ld_nc64(const uint2* p) { uint2 v; asm volatile("ld.global.nc.v2.b32 {%0,%1},[%2];" : "=r"(v.x), "=r"(v.y) : "l"(p)); return v; }
__device__ __forceinline__ unsigned ld_acq(const unsigned* p) { unsigned v; asm volatile("ld.acquire.gpu.global.u32 %0,[%1];" : "=r"(v) : "l"(p) : "memory"); return v; }
__device__ __forceinline__ unsigned ld_rlx(const unsigned* p) { unsigned v; asm volatile("ld.relaxed.gpu.global.u32 %0,[%1];" : "=r"(v) : "l"(p) : "memory"); return v; }
__device__ __forceinline__ uint2 ld_rlx64(const void* p) { uint2 v; asm volatile("{.reg .b64 t; ld.relaxed.gpu.global.b64 t,[%2]; mov.b64 {%0,%1},t;}" : "=r"(v.x), "=r"(v.y) : "l"(p) : "memory"); return v; }
__device__ __forceinline__ uint4 ld_rlx128(const void* p) {
    uint4 v;
    asm volatile("{.reg .b64 t,u; ld.relaxed.gpu.global.v2.b64 {t,u},[%4]; mov.b64 {%0,%1},t; mov.b64 {%2,%3},u;}" : "=r"(v.x), "=r"(v.y), "=r"(v.z), "=r"(v.w) : "l"(p) : "memory");
    return v;
}
__device__ __forceinline__ void st_rlx32(void* p, uint32_t x) { asm volatile("st.relaxed.gpu.global.u32 [%0],%1;" ::"l"(p), "r"(x) : "memory"); }
__device__ __forceinline__ void st_rlx64(void* p, uint32_t x, uint32_t y) { asm volatile("{.reg .b64 t; mov.b64 t,{%1,%2}; st.relaxed.gpu.global.b64 [%0],t;}" ::"l"(p), "r"(x), "r"(y) : "memory"); }
__device__ __forceinline__ void st_rlx128(void* p, uint4 v) {
    asm volatile("{.reg .b64 t,u; mov.b64 t,{%1,%2}; mov.b64 u,{%3,%4}; st.relaxed.gpu.global.v2.b64 [%0],{t,u};}" ::"l"(p), "r"(v.x), "r"(v.y), "r"(v.z), "r"(v.w) : "memory");
}
__device__ __forceinline__ uint32_t tagw(uint32_t w, uint32_t tag) { return (w & ~1u) | tag; }
__device__ __forceinline__ uint4 tag4(uint32_t x, uint32_t y, uint32_t z, uint32_t w, uint32_t tag) { return make_uint4(tagw(x, tag), y, tagw(z, tag), w); }
__device__ __forceinline__ uint32_t bad4(const uint4& v, uint32_t tag) { return (v.x ^ tag) | (v.z ^ tag); }
__device__ __forceinline__ void bar_named(int id, int n) { asm volatile("bar.sync %0,%1;" ::"r"(id), "r"(n) : "memory"); }

struct cf { float re, im; };
__device__ __forceinline__ cf cmul(cf a, cf b) { cf r; r.re = a.re * b.re - a.im * b.im; r.im = a.re * b.im + a.im * b.re; return r; }
__device__ __forceinline__ cf cexp_p(float arl, float ait, float p) {
    float mag = ex2(arl * p);
    float t = ait * p;
    const float big = 12582912.f;
    t = (t - ((t + big) - big)) * 6.283185307179586f;
    cf r; r.re = mag * __cosf(t); r.im = mag * __sinf(t);
    return r;
}

__device__ __forceinline__ void hedgehog4(const uint32_t* a, uint32_t wphi_addr, uint32_t (*out)[8]) {
    float p[4][2][4], mx[4][2];
#pragma unroll
    for (int h = 0; h < 4; h++) {
        uint32_t b[4];
        ldsm4t(b, wphi_addr + h * 512);
        float c0[4] = {0.f, 0.f, 0.f, 0.f}, c1[4] = {0.f, 0.f, 0.f, 0.f};
        mma16816(c0, a[4 * h], a[4 * h + 1], a[4 * h + 2], a[4 * h + 3], b[0], b[1]);
        mma16816(c1, a[4 * h], a[4 * h + 1], a[4 * h + 2], a[4 * h + 3], b[2], b[3]);
#pragma unroll
        for (int k = 0; k < 2; k++) {
            p[h][k][0] = c0[2 * k]; p[h][k][1] = c0[2 * k + 1]; p[h][k][2] = c1[2 * k]; p[h][k][3] = c1[2 * k + 1];
            mx[h][k] = fmaxf(fmaxf(p[h][k][0], p[h][k][1]), fmaxf(p[h][k][2], p[h][k][3]));
        }
    }
#pragma unroll
    for (int o = 1; o <= 2; o <<= 1)
#pragma unroll
        for (int h = 0; h < 4; h++)
#pragma unroll
            for (int k = 0; k < 2; k++) mx[h][k] = fmaxf(mx[h][k], __shfl_xor_sync(~0u, mx[h][k], o));
    const float L = 1.4426950408889634f;
    float pmin = 1.f;
#pragma unroll
    for (int h = 0; h < 4; h++)
#pragma unroll
        for (int k = 0; k < 2; k++) {
            const float m = -mx[h][k] * L;
            const float e0 = ex2(fmaf(p[h][k][0], L, m)), e1 = ex2(fmaf(p[h][k][1], L, m)), e2 = ex2(fmaf(p[h][k][2], L, m)), e3 = ex2(fmaf(p[h][k][3], L, m));
            const float p01 = e0 * e1, p23 = e2 * e3, pp = p01 * p23, r = rcp(pp), r01 = r * p23, r23 = r * p01;
            pmin = fminf(pmin, pp);
            out[h][k] = pack2(e0, e1); out[h][k + 2] = pack2(e2, e3);
            out[h][4 + k] = pack2(r01 * e1, r01 * e0); out[h][4 + k + 2] = pack2(r23 * e3, r23 * e2);
        }
    if (__builtin_expect(__any_sync(~0u, !(pmin > 1e-18f)), 0)) {
#pragma unroll
        for (int h = 0; h < 4; h++)
#pragma unroll
            for (int k = 0; k < 2; k++) {
                float m = fminf(fminf(p[h][k][0], p[h][k][1]), fminf(p[h][k][2], p[h][k][3]));
                m = fminf(m, __shfl_xor_sync(~0u, m, 1));
                m = fminf(m, __shfl_xor_sync(~0u, m, 2)) * L;
                out[h][4 + k] = pack2(ex2(fmaf(p[h][k][0], -L, m)), ex2(fmaf(p[h][k][1], -L, m)));
                out[h][4 + k + 2] = pack2(ex2(fmaf(p[h][k][2], -L, m)), ex2(fmaf(p[h][k][3], -L, m)));
            }
    }
}

__global__ void __launch_bounds__(512, 1)
fused_kernel(Scratch* __restrict__ scr, const bf16* __restrict__ logA, const bf16* __restrict__ Aim, const bf16* __restrict__ Cre,
             const bf16* __restrict__ Cim, const bf16* __restrict__ logdt, const bf16* __restrict__ Dskip, const bf16* __restrict__ wphi,
             const bf16* __restrict__ gatew, bf16* __restrict__ out,
             const __grid_constant__ CUtensorMap mx, const __grid_constant__ CUtensorMap mw, const __grid_constant__ CUtensorMap mwo) {
    extern __shared__ __align__(1024) uint8_t smem[];
    constexpr uint32_t sb = 1024;
    const int tid = threadIdx.x, warp = __shfl_sync(~0u, tid >> 5, 0), lane = tid & 31;
    const int g = lane >> 2, q = lane & 3, w4 = warp & 3;
    const int bi = blockIdx.x, bi_i = bi & 15, bi_j = bi >> 4;
    const uint32_t bar = sb + OFF_BAR;
    const int rot = (bi_j & 3) * 2, xkb = bi_j >> 2;
    auto load_stage = [&](int kb) {
        const uint32_t b = bar + 8 * (BAR_FULL + (kb & 3)), d = sb + (kb & 3) * SLOT;
        const int kc = ((kb + rot) & 7) * 64;
        mbar_expect(b, SLOT);
        tma2d(d, &mx, kc, bi_i * 128, b);
        tma3d(d + 16384, &mw, bi_j * 64, kc, 0, b);
    };

    const int ch = bi * 4 + w4;
    const int pidx = ch * 64 + lane * 2 + (warp >> 3);
    const uint32_t pla = ld_nc((const uint32_t*)logA + pidx), pai = ld_nc((const uint32_t*)Aim + pidx);
    const uint32_t pcr = ld_nc((const uint32_t*)Cre + pidx), pci = ld_nc((const uint32_t*)Cim + pidx);
    uint32_t pdt = ld_nc((const uint32_t*)logdt + (ch >> 1));
    const uint32_t pds = ld_nc((const uint32_t*)Dskip + (ch >> 1));
    unsigned done0 = ld_rlx(scr->done);
    if (tid == 0) {
        for (int s = 0; s < 4; s++) mbar_init(bar + 8 * (BAR_FULL + s), 1);
        asm volatile("fence.mbarrier_init.release.cluster;" ::: "memory");
        asm volatile("prefetch.tensormap [%0];" ::"l"(&mx) : "memory");
        load_stage(0); load_stage(1);
        STAMP(11);
    } else if (tid == 32) {
        if (s2u(smem) != sb) __trap();
        sts32(bar + OFF_CNT, 0);
        for (int s = 0; s < 4; s++) { mbar_init(bar + 8 * (BAR_EMPTY + s), 9); mbar_init(bar + 8 * (BAR_KS + s), 1); mbar_init(bar + 8 * (BAR_KP + s), 3); mbar_init(bar + 8 * (BAR_KD + s), 1); }
        mbar_init(bar + 8 * BAR_WPHI, 1); mbar_init(bar + 8 * BAR_WO, 2); mbar_init(bar + 8 * BAR_WO2, 1); mbar_init(bar + 8 * BAR_XT, 4);
        mbar_init(bar + 8 * BAR_DONE, 9); mbar_init(bar + 8 * BAR_KG, 8); mbar_init(bar + 8 * BAR_PUB, 8);
        mbar_init(bar + 8 * BAR_KVF, 4); mbar_init(bar + 8 * BAR_UR, 4); mbar_init(bar + 8 * BAR_WR, 4); mbar_init(bar + 8 * BAR_PREP, 4); mbar_init(bar + 8 * BAR_KGA, 4); mbar_init(bar + 8 * BAR_SP2, 1);
        asm volatile("fence.mbarrier_init.release.cluster;" ::: "memory");
        mbar_expect(bar + 8 * BAR_WPHI, 3072);
        bulk_g2s(sb + OFF_GW, gatew, 1024, bar + 8 * BAR_WPHI);
        bulk_g2s(sb + OFF_WPHI, wphi + bi_j * 1024, 2048, bar + 8 * BAR_WPHI);
    } else if (tid == 64) {
        asm volatile("prefetch.tensormap [%0];" ::"l"(&mw) : "memory");
    }
    const uint32_t buf = sb + OFF_BUF + w4 * BUF_STRIDE, kb_ = sb + OFF_K + w4 * KT_BYTES;
    if ((warp >> 2) == 2) {
#pragma unroll
        for (int v = 0; v < 7; v++) if (v * 32 + lane < KT_BYTES / 16) sts128(kb_ + (v * 32 + lane) * 16, 0, 0, 0, 0);
    }
    __syncthreads();
    asm volatile("" : "+r"(pdt), "+r"(done0)::"memory");
    const unsigned epoch1 = (done0 >> 7) + 1u;
    const uint32_t tag = epoch1 & 1u;

    const int st = tid & 127;
    const uint32_t ub = sb + OFF_U + w4 * U_STRIDE + 256, spare = sb + (w4 < 2 ? OFF_SP0 : OFF_SP1) + (w4 & 1) * 4096;

    auto stg_of = [&](int w) { return w < 8 ? sb + 3 * SLOT + w * 7296 : sb + 2 * SLOT + (w & 3) * 7296; };
    float kc[24];
#pragma unroll
    for (int t = 0; t < 24; t++) kc[t] = 0.f;
    auto handoff = [&](int src) {
        mbar_wait(bar + 8 * (BAR_KS + w4), 0);
#pragma unroll
        for (int t = 0; t < 5; t++)
            sts128(buf + src * 2560 + (t * 32 + lane) * 16, __float_as_uint(kc[4 * t]), __float_as_uint(kc[4 * t + 1]), __float_as_uint(kc[4 * t + 2]), __float_as_uint(kc[4 * t + 3]));
        if (lane == 0) sts32(buf + 7680 + src * 4, __float_as_uint(kc[20]));
        __syncwarp();
        if (lane == 0) mbar_arrive(bar + 8 * (BAR_KP + w4));
    };
    {
        const float dt = bf_round(expf((ch & 1) ? bf_hi(pdt) : bf_lo(pdt)));
        const uint32_t stg = (warp >> 2) == 2 ? buf : stg_of(warp);
        const int sh = ((warp >> 2) & 1) * 16;
        auto pick = [&](uint32_t v) { return __uint_as_float((v >> sh) << 16); };
        const float ea = bf_round(ex2(pick(pla) * 1.4426950408889634f));
        const float arl = (-ea * dt) * 1.4426950408889634f, ait = (pick(pai) * dt) * 0.15915494309189535f;
        cf C2; C2.re = 2.0f * (pick(pcr) * dt); C2.im = 2.0f * (pick(pci) * dt);
        const cf z1 = cexp_p(arl, ait, 1.0f), z128 = cexp_p(arl, ait, 128.0f);
        const cf z2 = cmul(z1, z1), z4 = cmul(z2, z2);
        cf z8 = cmul(z4, z4); z8.im = -z8.im;
        const uint32_t sa0 = stg + (lane >> 3) * 128 + (((lane & 7) ^ (lane >> 3)) << 4), sa1 = (sa0 ^ 64) + 512;
        uint32_t w[60];
        auto put = [&](int row, const cf& v) {
            w[row] = pack2(v.re, v.im);
            if ((row & 3) == 3) stsm4(((row & 4) ? sa1 : sa0) + (row >> 3) * 1024, w[row - 3], w[row - 2], w[row - 1], w[row]);
        };
        {
            const cf z16 = cmul(z8, z8);
            cf e; e.re = 1.f; e.im = 0.f;
            cf o = z8;
            put(0, e); put(1, o);
            e = z16; put(2, e);
#pragma unroll
            for (int b = 3; b < 16; b += 2) {
                o = cmul(o, z16); put(b, o);
                if (b + 1 < 16) { e = cmul(e, z16); put(b + 1, e); }
            }
        }
        cf h[8];
        h[0] = C2; h[1] = cmul(h[0], z1);
#pragma unroll
        for (int r = 2; r < 8; r++) h[r] = cmul(h[r - 2], z2);
#pragma unroll
        for (int r = 0; r < 8; r++) put(16 + r, h[r]);
#pragma unroll
        for (int r = 0; r < 8; r++) { h[r] = cmul(h[r], z128); put(24 + r, h[r]); }
#pragma unroll
        for (int al = 0; al < 2; al++)
#pragma unroll
            for (int r = 0; r < 4; r++) { h[2 * r] = cmul(h[2 * r], z128); put(32 + al * 4 + r, h[2 * r]); }
#pragma unroll
        for (int al = 0; al < 4; al++)
#pragma unroll
            for (int r = 0; r < 2; r++) { h[4 * r] = cmul(h[4 * r], z128); put(40 + al * 2 + r, h[4 * r]); }
#pragma unroll
        for (int al = 0; al < 8; al++) { h[0] = cmul(h[0], z128); put(48 + al, h[0]); }
        h[0] = cmul(h[0], z128);
        sts32(stg + 56 * 128 + lane * 4, pack2(h[0].re, h[0].im));
        __syncwarp();
        const int lr = lane & 7, lm = lane >> 3;
#pragma unroll
        for (int kp = 0; kp < 2; kp++) {
            uint32_t a0[4], a1[4];
            ldsm4(a0, stg + ((lm & 1) * 8 + lr) * 128 + (((4 * kp + (lm >> 1)) ^ lr) << 4));
            ldsm4(a1, stg + ((lm & 1) * 8 + lr) * 128 + (((4 * kp + 2 + (lm >> 1)) ^ lr) << 4));
#pragma unroll
            for (int t = 0; t < 6; t++) {
                uint32_t b[4];
                ldsm4(b, stg + (16 + 8 * t + lr) * 128 + (((4 * kp + lm) ^ lr) << 4));
                mma16816(kc + 4 * t, a0[0], a0[1], a0[2], a0[3], b[0], b[1]);
                mma16816(kc + 4 * t, a1[0], a1[1], a1[2], a1[3], b[2], b[3]);
            }
        }
        __syncwarp();
        asm volatile("fence.proxy.async.shared::cta;" ::: "memory");
        const uint32_t cnt = 1u + (__float_as_uint(kc[0] + kc[23]) == 0xffc12345u);
        if (lane == 0) asm volatile("mbarrier.arrive.shared::cta.b64 _,[%0],%1;" ::"r"(bar + 8 * (warp < 8 ? BAR_KG : (warp < 12 ? BAR_KS + w4 : BAR_KGA))), "r"(cnt) : "memory");
        if (warp < 8) handoff(warp >> 2);
    }

    if (warp < 8) {
        const int wg = warp >> 2;
        if (warp == 0) STAMP(21);
        float acc[96];
        const int srow = warp * 16 + (lane & 15);
        const uint32_t srow_a = srow * 128;
        const int sx = srow & 7, shi = lane >> 4;
        const uint64_t da0 = mkdesc(sb + wg * 8192, 16, 1024), db0 = mkdesc(sb + 16384, 8192, 1024);
#pragma unroll 1
        for (int kb = 0; kb < 8; kb++) {
            const int s = kb & 3;
            const uint64_t da = da0 + s * (SLOT >> 4), db = db0 + s * (SLOT >> 4);
            if (warp == 0) STAMP(40 + kb);
            mbar_wait(bar + 8 * (BAR_FULL + s), kb >> 2);
            if (warp == 0) STAMP(32 + kb);
            wg_fence();
#pragma unroll
            for (int k = 0; k < 4; k++) wgmma192(acc, da + 2 * k, db + 128 * k, kb | k);
            wg_commit();
            wg_wait<1>();
            if (lane == 0 && kb > 0) mbar_arrive(bar + 8 * (BAR_EMPTY + ((kb - 1) & 3)));
        }
        mbar_wait(bar + 8 * BAR_WPHI, 0);
        wg_wait<0>();
        fence_regs<96>(acc);
        asm volatile("setmaxnreg.inc.sync.aligned.u32 160;");
        if (lane == 0) mbar_arrive(bar + 8 * BAR_DONE);
        if (warp == 0) STAMP(1);
        uint32_t in[16], qa[16];
        mbar_wait(bar + 8 * BAR_DONE, 0);
#pragma unroll
        for (int r = 0; r < 16; r++) {
            in[r] = pack2(acc[32 + 2 * r], acc[32 + 2 * r + 1]);
            qa[r] = pack2(acc[2 * r], acc[2 * r + 1]);
        }
#pragma unroll
        for (int hh = 0; hh < 4; hh++)
            stsm4(sb + OFF_V + (hh >> 1) * 16384 + srow_a + (((2 * (hh & 1) + shi) ^ sx) << 4), pack2(acc[64 + 8 * hh], acc[65 + 8 * hh]),
                  pack2(acc[66 + 8 * hh], acc[67 + 8 * hh]), pack2(acc[68 + 8 * hh], acc[69 + 8 * hh]), pack2(acc[70 + 8 * hh], acc[71 + 8 * hh]));
        sts128(sb + OFF_V + shi * 16384 + srow_a + ((4 ^ sx) << 4), 0x3f803f80u, 0x3f803f80u, 0x3f803f80u, 0x3f803f80u);
        const uint32_t wphi_a = sb + OFF_WPHI + (lane & 15) * 32 + (lane >> 4) * 16;
        uint32_t pq[4][8];
#pragma unroll 1
        for (int it = 0; it < 2; it++) {
            hedgehog4(in, wphi_a, pq);
            if (it == 1) break;
#pragma unroll
            for (int hs = 0; hs < 8; hs++) {
                float c[4] = {0.f, 0.f, 0.f, 0.f};
                const uint32_t* o = pq[hs >> 1] + 4 * (hs & 1);
                mma16816(c, o[0], o[1], o[2], o[3], 0x3f803f80u, 0x3f803f80u);
                const float r0 = rcp(c[0]), r1 = rcp(c[2]);
                const uint32_t s0 = pack2(r0, r0), s1 = pack2(r1, r1);
                stsm4(sb + OFF_P + (hs >> 2) * 16384 + srow_a + (((2 * (hs & 3) + shi) ^ sx) << 4), hmul2(o[0], s0), hmul2(o[1], s1), hmul2(o[2], s0), hmul2(o[3], s1));
            }
            asm volatile("fence.proxy.async.shared::cta;" ::: "memory");
            bar_named(1, 256);
            if (warp == 0) STAMP(2);
            float d[32];
            const uint64_t dv = mkdesc(sb + OFF_V + wg * 16384, 16, 1024), dp = mkdesc(sb + OFF_P + wg * 16384, 16, 1024);
            wg_fence();
#pragma unroll
            for (int k = 0; k < 8; k++) wgmma64_tt(d, dv + 128 * k, dp + 128 * k, k != 0);
            wg_commit();
            mbar_wait(bar + 8 * BAR_PREP, 0);
            uint4* kvp = scr->kvp + bi * 544 + wg * 272 + (w4 < 2 ? w4 * 136 : 128) + lane;
            wg_wait<0>();
            fence_regs<32>(d);
            if (w4 < 2 || (w4 == 2 && lane < 4)) {
#pragma unroll
                for (int f = 0; f < 4; f++) {
                    const int i0 = 8 * (f >> 1) + 2 * (f & 1), i2 = 16 * (f >> 1) + 8 * (f & 1);
                    const float e0 = w4 == 0 ? d[i0] : (w4 == 1 ? d[16 + i0] : d[i2]), e1 = w4 == 0 ? d[i0 + 1] : (w4 == 1 ? d[17 + i0] : d[i2 + 1]);
                    const float e2 = w4 == 0 ? d[i0 + 4] : (w4 == 1 ? d[20 + i0] : d[i2 + 4]), e3 = w4 == 0 ? d[i0 + 5] : (w4 == 1 ? d[21 + i0] : d[i2 + 5]);
                    st_rlx128(kvp + (w4 < 2 ? f * 32 : (f >> 1) * 136 + (f & 1) * 4), tag4(__float_as_uint(e0), __float_as_uint(e1), __float_as_uint(e2), __float_as_uint(e3), tag));
                }
            }
            __syncwarp();
            if (lane == 0) mbar_arrive(bar + 8 * BAR_PUB);
            if (warp == 0) STAMP(3);
#pragma unroll
            for (int r = 0; r < 16; r++) in[r] = qa[r];
        }
        if (warp == 0) STAMP(4);
        {
            mbar_wait(bar + 8 * BAR_KVF, 0);
            uint4 kf[4][3];
#pragma unroll
            for (int hh = 0; hh < 4; hh++) {
                const uint32_t a = sb + OFF_KVF + hh * 1088;
                kf[hh][0] = lds128(a + lane * 32); kf[hh][1] = lds128(a + lane * 32 + 16); kf[hh][2] = lds128(a + 1024 + q * 16);
            }
            if (warp == 0) STAMP(5);
            uint4* og = scr->o + ((bi_i * 8 + warp) * 32 + bi_j * 4) * 32 + lane;
#pragma unroll
            for (int hh = 0; hh < 4; hh++) {
                float c[6][4];
#pragma unroll
                for (int t = 0; t < 6; t++) { c[t][0] = c[t][1] = c[t][2] = c[t][3] = 0.f; }
                const uint32_t* a = pq[hh];
                const bool od = g & 1;
                mma16816(c[0], a[0], a[1], a[2], a[3], od ? 0x3f803f80u : kf[hh][2].x, od ? 0x3f803f80u : kf[hh][2].y);
                mma16816(c[1], a[4], a[5], a[6], a[7], od ? 0x3f803f80u : kf[hh][2].z, od ? 0x3f803f80u : kf[hh][2].w);
                mma16816(c[2], a[0], a[1], a[2], a[3], kf[hh][0].x, kf[hh][0].y);
                mma16816(c[3], a[0], a[1], a[2], a[3], kf[hh][0].z, kf[hh][0].w);
                mma16816(c[4], a[4], a[5], a[6], a[7], kf[hh][1].x, kf[hh][1].y);
                mma16816(c[5], a[4], a[5], a[6], a[7], kf[hh][1].z, kf[hh][1].w);
                uint32_t w[4];
#pragma unroll
                for (int k = 0; k < 2; k++) {
                    const float rho = c[0][2 * k + 1] * rcp(c[1][2 * k + 1]);
                    const float r = rcp(fmaf(c[0][2 * k + 1], 1e-6f, fmaf(rho, c[1][2 * k], c[0][2 * k]))), rr = r * rho;
                    w[k] = pack2(fmaf(c[4][2 * k], rr, c[2][2 * k] * r), fmaf(c[4][2 * k + 1], rr, c[2][2 * k + 1] * r));
                    w[2 + k] = pack2(fmaf(c[5][2 * k], rr, c[3][2 * k] * r), fmaf(c[5][2 * k + 1], rr, c[3][2 * k + 1] * r));
                }
                st_rlx128(og + hh * 32, tag4(w[0], w[1], w[2], w[3], tag));
            }
        }
        if (warp == 0) STAMP(6);
        float oc[64];
        const int slab = bi_i * 8 + (bi_j >> 2) * 4 + w4;
        const uint8_t* ysrc = (const uint8_t*)scr->y + (size_t)((bi_j & 3) * 32 + wg * 16 + (q >> 1)) * 16384 + slab * 128 + g * 16 + (q & 1) * 8;
        const unsigned* gp = scr->g + (slab * 8 + (g >> 1)) * 8 + (g & 1) * 4;
        uint2 yv[8]; unsigned g0, g1;
        {
            const uint4* osrc = scr->o + (slab * 32 + wg * 16) * 32 + lane;
            uint4 fr[16];
            const unsigned* probe = (const unsigned*)(osrc - lane + ((lane & 3) * 4 + 3) * 32 + 31) + 2;
            {
                unsigned miss = ~0u;
                int n = 0;
#pragma unroll
                for (int s = 0; s < 4; s++) {
#pragma unroll 1
                    while ((miss >> s) & 1) { miss = __ballot_sync(~0u, (ld_rlx(probe) ^ tag) & 1); if (++n > SPIN_LIMIT) break; }
#pragma unroll
                    for (int k = 4 * s; k < 4 * s + 4; k++) fr[k] = ld_rlx128(osrc + k * 32);
                }
            }
            if (warp == 0) STAMP(14);
            mbar_wait(bar + 8 * (wg ? BAR_WO2 : BAR_WO), 0);
            const uint64_t dw = mkdesc(sb + wg * 2 * SLOT, wg ? 32768 : SLOT, 1024);
#pragma unroll
            for (int s = 0; s < 4; s++) {
                int n = 0;
#pragma unroll 1
                while (__builtin_expect(__any_sync(~0u, (bad4(fr[4 * s], tag) | bad4(fr[4 * s + 1], tag) | bad4(fr[4 * s + 2], tag) | bad4(fr[4 * s + 3], tag)) & 1), 0)) {
#pragma unroll
                    for (int k = 4 * s; k < 4 * s + 4; k++) fr[k] = ld_rlx128(osrc + k * 32);
                    if (++n > SPIN_LIMIT) break;
                }
                wg_fence();
#pragma unroll
                for (int hh = 0; hh < 4; hh++) wgmma128_rs(oc, fr[4 * s + hh], dw + 128 * (4 * s + hh), (s | hh) != 0);
                wg_commit();
                if (s == 1) {
                    wg_wait<1>();
#pragma unroll
                    for (int nt = 0; nt < 8; nt++) yv[nt] = ld_rlx64(ysrc + nt * 32768);
                    g0 = ld_rlx(gp); g1 = ld_rlx(gp + 32);
                }
            }
            if (warp == 0) STAMP(7);
            {
                const unsigned* yprobe = scr->yflag + ((bi_j & 3) * 32 + wg * 16 + (lane & 15)) * 8;
                int n = 0;
#pragma unroll 1
                while (true) {
                    uint32_t bad = (g0 ^ tag) | (g1 ^ tag);
#pragma unroll
                    for (int nt = 0; nt < 8; nt++) bad |= yv[nt].x ^ tag;
                    if (!__any_sync(~0u, bad & 1)) break;
#pragma unroll 1
                    while (__any_sync(~0u, (ld_rlx(yprobe) ^ tag) & 1)) { if (++n > SPIN_LIMIT) break; }
#pragma unroll
                    for (int nt = 0; nt < 8; nt++) yv[nt] = ld_rlx64(ysrc + nt * 32768);
                    g0 = ld_rlx(gp); g1 = ld_rlx(gp + 32);
                    if (++n > SPIN_LIMIT) break;
                }
            }
            if (warp == 0) STAMP(28);
        }
        {
            const float ga = bf_hi(g0), gb = bf_hi(g1);
            const float ha = bf_round(1.0f - ga), hb = bf_round(1.0f - gb);
            float yb[32];
#pragma unroll
            for (int nt = 0; nt < 8; nt++) {
                yb[4 * nt] = ha * bf_lo(yv[nt].x); yb[4 * nt + 1] = ha * bf_hi(yv[nt].x);
                yb[4 * nt + 2] = hb * bf_lo(yv[nt].y); yb[4 * nt + 3] = hb * bf_hi(yv[nt].y);
            }
            fence_regs<32>(yb);
            const uint32_t xw = sb + wg * 2 * SLOT + (tid & 127) * 16, xr = sb + (wg ^ 1) * 2 * SLOT + (tid & 127) * 16;
            wg_wait<0>();
            fence_regs<64>(oc);
            bar_named(3 + wg, 128);
#pragma unroll
            for (int r = 0; r < 8; r++)
                sts128(xw + r * 2048, __float_as_uint(oc[32 + 4 * r]), __float_as_uint(oc[33 + 4 * r]), __float_as_uint(oc[34 + 4 * r]), __float_as_uint(oc[35 + 4 * r]));
#pragma unroll
            for (int r = 0; r < 32; r++) yb[r] = fmaf((r & 2) ? gb : ga, oc[r], yb[r]);
            bar_named(1, 256);
            if (warp == 0) STAMP(8);
            uint32_t w[8][2];
#pragma unroll
            for (int nt = 0; nt < 8; nt++) {
                const uint4 p = lds128(xr + nt * 2048);
                w[nt][0] = pack2(fmaf(ga, __uint_as_float(p.x), yb[4 * nt]), fmaf(ga, __uint_as_float(p.y), yb[4 * nt + 1]));
                w[nt][1] = pack2(fmaf(gb, __uint_as_float(p.z), yb[4 * nt + 2]), fmaf(gb, __uint_as_float(p.w), yb[4 * nt + 3]));
            }
            const uint32_t ob = sb + wg * 2 * SLOT + 16384 + w4 * 2048;
#pragma unroll
            for (int nt = 0; nt < 8; nt += 2)
                stsm4(ob + (lane & 15) * 128 + (((nt + shi) ^ (lane & 7)) << 4), w[nt][0], w[nt][1], w[nt + 1][0], w[nt + 1][1]);
            __syncwarp();
            bf16* op = out + (size_t)(slab * 16) * 512 + (bi_j & 3) * 128 + wg * 64 + (lane & 7) * 8;
#pragma unroll
            for (int it = 0; it < 4; it++) {
                const int r = it * 4 + (lane >> 3);
                uint4 v = lds128(ob + r * 128 + (((lane & 7) ^ (r & 7)) << 4));
                *(uint4*)(op + r * 512) = v;
            }
        }
        if (warp == 0) STAMP(10);
    } else if (warp < 12) {
        if (warp == 8) {
            mbar_wait(bar + 8 * BAR_KGA, 0);
            if (lane == 0) load_stage(2);
            STAMP(22);
            mbar_wait(bar + 8 * BAR_KG, 0);
            if (lane == 0) load_stage(3);
            __syncwarp();
            STAMP(17);
        }
        if (warp == 8) {
#pragma unroll 1
            for (int kb = 0; kb < 6; kb++) {
                const int s = kb & 3;
                mbar_wait(bar + 8 * (BAR_EMPTY + s), kb >> 2);
                if (kb == xkb) mbar_wait(bar + 8 * BAR_XT, 0);
                if (lane == 0) {
                    STAMP(48 + kb);
                    if (kb < 4) load_stage(kb + 4);
                    else {
                        mbar_expect(bar + 8 * BAR_WO, 32768);
                        tma2d(sb + s * SLOT, &mwo, (bi_j & 3) * 128 + s * 64, 0, bar + 8 * BAR_WO);
                        if (kb == 5) mbar_arrive(bar + 8 * BAR_SP2);
                    }
                }
                __syncwarp();
            }
        } else if (warp == 9) {
            const int row = bi_j * 16 + (lane >> 1), half = lane & 1;
            unsigned* gp = scr->g + (bi_i * 64 + bi_j * 8) * 8 + lane * 2;
            st_rlx64(gp, tag ^ 1u, tag ^ 1u);
            if (lane < 8) st_rlx32(scr->yflag + bi * 8 + lane, tag ^ 1u);
            float gs0 = 0.f, gs1 = 0.f;
            mbar_wait(bar + 8 * BAR_WPHI, 0);
#pragma unroll 1
            for (int kb = 0; kb < 8; kb++) {
                const int s = kb & 3;
                mbar_wait(bar + 8 * (BAR_FULL + s), kb >> 2);
#pragma unroll
                for (int c = 0; c < 4; c++) {
                    const uint4 xv = lds128(sb + s * SLOT + row * 128 + (((half * 4 + c) ^ (row & 7)) << 4));
                    const uint4 gw = lds128(sb + OFF_GW + ((kb + rot) & 7) * 128 + half * 64 + c * 16);
                    const uint32_t p0 = hmul2(xv.x, gw.x), p1 = hmul2(xv.y, gw.y), p2 = hmul2(xv.z, gw.z), p3 = hmul2(xv.w, gw.w);
                    gs0 += (bf_lo(p0) + bf_lo(p1)) + (bf_lo(p2) + bf_lo(p3));
                    gs1 += (bf_hi(p0) + bf_hi(p1)) + (bf_hi(p2) + bf_hi(p3));
                }
                const uint32_t cnt = 1u + (__float_as_uint(gs0 + gs1) == 0xffc12345u);
                if (lane == 0) asm volatile("mbarrier.arrive.shared::cta.b64 _,[%0],%1;" ::"r"(bar + 8 * (kb < 7 ? BAR_EMPTY + s : BAR_DONE)), "r"(cnt) : "memory");
                __syncwarp();
            }
            float gs = gs0 + gs1;
            gs += __shfl_xor_sync(~0u, gs, 1);
            const uint32_t gv = __float_as_uint(bf_round(rcp(1.0f + ex2(-1.4426950408889634f * bf_round(gs))))) | tag;
            st_rlx64(gp, gv, gv);
        }
        mbar_wait(bar + 8 * (BAR_KP + w4), 0);
#pragma unroll
        for (int t = 0; t < 15; t++) {
            const uint4 v = lds128(buf + (t * 32 + lane) * 16);
            kc[4 * (t % 5)] += __uint_as_float(v.x); kc[4 * (t % 5) + 1] += __uint_as_float(v.y); kc[4 * (t % 5) + 2] += __uint_as_float(v.z); kc[4 * (t % 5) + 3] += __uint_as_float(v.w);
        }
        {
            const uint4 v = lds128(buf + 7680);
            kc[20] += __uint_as_float(v.x) + __uint_as_float(v.y) + __uint_as_float(v.z);
            const uint32_t cnt = 1u + (__float_as_uint(kc[20] + kc[19] + kc[0]) == 0xffc12345u);
            if (lane == 0) asm volatile("mbarrier.arrive.shared::cta.b64 _,[%0],%1;" ::"r"(bar + 8 * (BAR_KD + w4)), "r"(cnt) : "memory");
            __syncwarp();
        }
        if (lane == 0) kc[4 * 0 + 0] += ((ch & 1) ? bf_hi(pds) : bf_lo(pds));
        const uint32_t k1024 = __shfl_sync(~0u, pack2(kc[4 * 4 + 0], 0.f), 0);
#pragma unroll
        for (int i = 0; i < 2; i++) {
            const int be = g + 8 * i;
#pragma unroll
            for (int t = 0; t < 2; t++) {
                const uint32_t a = kb_ + (KW_D + 128 * t + 8 * be + 2 * q) * 4;
                const uint32_t w = pack2(kc[4 * t + 2 * i + 1], kc[4 * t + 2 * i]);
                sts32(a + 4, w); sts16(a, w >> 16); sts16(a + 10, w);
            }
            {
                const int p = 256 + 128 * (q >> 1) + 8 * be + 4 * (q & 1);
                const uint32_t a = kb_ + (KW_D + p) * 4;
                const uint32_t w = pack2(kc[4 * 2 + 2 * i + 1], kc[4 * 2 + 2 * i]);
                const uint32_t aa = (w >> 16) | (w & 0xffff0000u);
                if (p != 256) { sts16(a - 4, aa); sts32(a, aa); } else sts16(a, aa);
                sts32(a + 4, aa); sts32(a + 8, w); sts16(a + 14, w);
            }
            {
                const int k = 64 + 16 * q + be;
                const uint32_t w = pack2(kc[4 * 3 + 2 * i], kc[4 * 3 + 2 * i + 1]);
                if (k != 64) sts16(kb_ + (KW_2 + ((k - 1) >> 1) - 24) * 4 + (k & 1) * 2, w);
                else {
                    const uint32_t a = kb_ + (KW_D + 511) * 4, aa = (w << 16) | (w & 0xffffu);
                    sts16(a, w); sts32(a + 4, aa); sts32(a + 8, aa); sts32(a + 12, aa); sts16(a + 18, w);
                }
                sts16(kb_ + (KW_2 + 48 + (k >> 1) - 24) * 4 + ((k & 1) ^ 1) * 2, w >> 16);
            }
#pragma unroll
            for (int b = 0; b < 2; b++) {
                const int k = 64 + 8 * (2 * q + b) + (be >> 1);
                const uint32_t w = pack2(kc[4 * 4 + 2 * i + b], 0.f);
                if (!(be & 1) && k == 64) sts16(kb_ + (KW_2 + 63 - 24) * 4, w);
                else {
                    const uint32_t a = kb_ + (KW_3 + ((be & 1) ? 80 + k : k - 1) - 48) * 4;
                    sts16(a, w);
                    if (!((be & 1) && k == 127)) sts16(a + 6, w);
                }
            }
        }
        if (lane == 0) sts16(kb_ + (KW_3 + 127 - 48) * 4, pack2(kc[4 * 5 + 0], 0.f));
        __syncwarp();
        asm volatile("setmaxnreg.inc.sync.aligned.u32 136;");
        mbar_wait(bar + 8 * BAR_UR, 0);
        mbar_wait(bar + 8 * BAR_DONE, 0);
        if (warp == 8) STAMP(23);
        float y[16][4];
#pragma unroll
        for (int nt = 0; nt < 16; nt++) { y[nt][0] = y[nt][1] = y[nt][2] = y[nt][3] = 0.f; }
        {
            uint32_t Bp[32], A[4][3], An[4][3];
            auto uaddr = [&](int rho) { const int R0 = (lane >> 4) * 64 + (lane & 7) - rho; return ub + (((2 * R0 + ((lane >> 3) & 1)) ^ ((R0 >> 2) & 1)) << 4); };
            const uint32_t kd = kb_ + (KW_D + g - 2 * q) * 4;
#pragma unroll 1
            for (int rho = 1; rho >= 0; rho--) {
                const uint32_t a = uaddr(rho), k = kd + 2048 + rho * 64;
#pragma unroll
                for (int i = 0; i < 8; i++) ldsm4(Bp + 4 * i, a + i * 256);
                const uint32_t a0 = lds32(k), a1 = lds32(k + 32), a2 = lds32(k - 32);
#pragma unroll
                for (int i = 0; i < 12; i++) mma16816(y[i + 4], a0, a1, a2, a0, Bp[4 * (i & 7) + 2 * (i >> 3)], Bp[4 * (i & 7) + 2 * (i >> 3) + 1]);
            }
#pragma unroll
            for (int ga = 0; ga < 4; ga++) { An[ga][0] = lds32(kd + ga * 512); An[ga][1] = lds32(kd + ga * 512 + 32); An[ga][2] = lds32(kd + ga * 512 - 32); }
#pragma unroll 1
            for (int rho = 0; rho < 8; rho++) {
#pragma unroll
                for (int ga = 0; ga < 4; ga++) {
                    const uint32_t a = kd + (rho + 1) * 64 + ga * 512;
                    A[ga][0] = An[ga][0]; A[ga][1] = An[ga][1]; A[ga][2] = An[ga][2];
                    An[ga][0] = lds32(a); An[ga][1] = lds32(a + 32); An[ga][2] = lds32(a - 32);
                }
                const uint32_t an = uaddr(rho + 1);
#pragma unroll
                for (int i = 0; i < 8; i++) {
#pragma unroll
                    for (int ga = 0; ga < 4; ga++) {
                        mma16816(y[i + ga], A[ga][0], A[ga][1], A[ga][2], A[ga][0], Bp[4 * i], Bp[4 * i + 1]);
                        if (i + 8 + ga < 16) mma16816(y[i + 8 + ga], A[ga][0], A[ga][1], A[ga][2], A[ga][0], Bp[4 * i + 2], Bp[4 * i + 3]);
                    }
                    ldsm4(Bp + 4 * i, an + i * 256);
                    __syncwarp();
                }
            }
        }
        if (warp == 8) STAMP(18);
        mbar_wait(bar + 8 * BAR_WR, 0);
#pragma unroll 1
        for (int ph = 0; ph < 2; ph++) {
            uint32_t B[5][2];
            const uint32_t ka = kb_ + (KW_2 + ph * 48 + 8 + g - q) * 4;
#pragma unroll
            for (int dd = 0; dd < 5; dd++) { B[dd][0] = lds32(ka + dd * 32); B[dd][1] = lds32(ka + dd * 32 - 16); }
            const uint32_t wa = buf + ph * W3_OFF + ((lane & 7) + ((lane >> 3) & 1) + (lane >> 4) * 8) * 16;
#pragma unroll
            for (int s = 0; s < 12; s++) {
                uint32_t A[4];
                ldsm4t(A, wa + s * 256);
#pragma unroll
                for (int dd = 0; dd < 5; dd++)
                    if (s + 4 + dd < 16) mma16816(y[s + 4 + dd], A[0], A[1], A[2], A[3], B[dd][0], B[dd][1]);
            }
        }
        {
            const int ap = (lane & 7) + (lane >> 4) * 8;
            const uint32_t loff = ((2 * ap + ((lane >> 3) & 1)) ^ ((ap >> 2) & 1)) << 4;
#pragma unroll 1
            for (int ph = 0; ph < 2; ph++) {
                uint32_t B[8][2];
                const uint32_t wb = (ph ? spare : buf + W9_OFF) + loff;
                const uint32_t ka = kb_ + (KW_3 + ph * 80 + 16 + g - 2 * q) * 4;
#pragma unroll
                for (int dd = 0; dd < 8; dd++) { B[dd][0] = lds32(ka + dd * 32); B[dd][1] = lds32(ka + dd * 32 - 32); }
#pragma unroll
                for (int s = 0; s < 4; s++) {
                    uint32_t A[4];
                    ldsm4t(A, wb + s * 512);
#pragma unroll
                    for (int dd = 0; dd < 8; dd++)
                        if (8 + 2 * s + dd < 16) mma16816(y[8 + 2 * s + dd], A[0], A[1], A[2], A[3], B[dd][0], B[dd][1]);
                }
            }
            const uint32_t idw = (g == 2 * q) ? k1024 : ((g == 2 * q + 1) ? (k1024 << 16) : 0u);
#pragma unroll
            for (int s = 0; s < 4; s++) {
                uint32_t A[4];
                ldsm4t(A, spare + 2048 + loff + s * 512);
                mma16816(y[8 + 2 * s], A[0], A[1], A[2], A[3], idw, 0u);
                mma16816(y[9 + 2 * s], A[0], A[1], A[2], A[3], 0u, idw);
            }
        }
        __syncwarp();
        if (warp == 8) STAMP(19);
#pragma unroll
        for (int nt = 0; nt < 16; nt++)
#pragma unroll
            for (int b = 0; b < 2; b++) sts32(buf + ((8 * nt + 2 * q + b) * 8 + g) * 4, pack2(y[nt][b], y[nt][2 + b]));
        bar_named(2, 128);
        uint4* yp = scr->y + bi * 1024 + st;
#pragma unroll
        for (int v = 0; v < 8; v++) {
            const uint32_t a = sb + OFF_BUF + (st + 128 * v) * 4;
            const uint32_t w0 = lds32(a), w1 = lds32(a + BUF_STRIDE), w2 = lds32(a + 2 * BUF_STRIDE), w3 = lds32(a + 3 * BUF_STRIDE);
            st_rlx128(yp + v * 128, tag4(__byte_perm(w0, w1, 0x5410), __byte_perm(w0, w1, 0x7632), __byte_perm(w2, w3, 0x5410), __byte_perm(w2, w3, 0x7632), tag));
        }
        if (st < 8) st_rlx32(scr->yflag + bi * 8 + st, tag);
        if (warp == 8) STAMP(20);
    } else {
        const int qq = (bi_i & 2) + ((lane >> 1) & 1);
        uint2* kvf_h = (uint2*)(scr->kvf + (bi_j * 4 + (bi_i >> 2)) * 68);
        auto windows = [&](int rhi, int rlo) {
#pragma unroll 1
            for (int rho = rhi; rho >= rlo; rho--) {
                const int ci = lane + 32 * rho;
                uint4 e4[4];
#pragma unroll
                for (int v = 0; v < 4; v++) { const int cc = ci - 3 + v; e4[v] = lds128(ub + ((cc ^ ((cc >> 3) & 1)) << 4)); }
                float S[29];
                const uint32_t* ew = (const uint32_t*)e4;
                S[3] = 0.f;
#pragma unroll
                for (int k = 4; k <= 28; k++) S[k] = S[k - 1] + ((k & 1) ? bf_hi(ew[k >> 1]) : bf_lo(ew[k >> 1]));
                auto win = [&](int lo, int hi, uint32_t a) {
                    sts128(a, pack2(S[hi] - S[lo - 1], S[hi + 1] - S[lo]), pack2(S[hi + 2] - S[lo + 1], S[hi + 3] - S[lo + 2]),
                           pack2(S[hi + 4] - S[lo + 3], S[hi + 5] - S[lo + 4]), pack2(S[hi + 6] - S[lo + 5], S[hi + 7] - S[lo + 6]));
                };
                win(14, 18, buf + W5_OFF + 16 + ci * 16); win(19, 21, buf + W3_OFF + 16 + ci * 16);
                if (rho < 4) {
                    const uint32_t sw = (ci ^ ((ci >> 3) & 1)) << 4;
                    win(4, 12, buf + W9_OFF + sw); win(13, 19, spare + sw); win(20, 21, spare + 2048 + sw);
                }
            }
        };
        {
            mbar_wait(bar + 8 * (BAR_FULL + xkb), 0);
#pragma unroll 1
            for (int hf = 0; hf < 2; hf++) {
                const int r = w4 * 32 + hf * 16 + (lane & 15);
                uint32_t* xt = (uint32_t*)scr->xt + ((xkb + rot) * 16 + (g >> 2)) * 4096 + (bi_i * 16 + w4 * 4 + hf * 2) * 16 + (g & 3) * 4 + q;
#pragma unroll
                for (int cb = 0; cb < 8; cb += 2) {
                    uint32_t v[4];
                    ldsm4t(v, sb + xkb * SLOT + r * 128 + (((cb + (lane >> 4)) ^ (r & 7)) << 4));
                    xt[cb * 8192] = v[0]; xt[cb * 8192 + 16] = v[1]; xt[cb * 8192 + 8192] = v[2]; xt[cb * 8192 + 8192 + 16] = v[3];
                }
            }
            __syncwarp();
            if (lane == 0) mbar_arrive(bar + 8 * BAR_XT);
            if (warp == 12) STAMP(26);
            handoff(2);
            asm volatile("setmaxnreg.dec.sync.aligned.u32 56;");
            if (lane == 0) asm volatile("red.release.gpu.global.add.u32 [%0],2;" ::"l"(scr->xcnt + (xkb + rot) * 32) : "memory");
            __syncwarp();
            if (warp == 12) STAMP(27);
            {
                const uint32_t old = tag ^ 1u;
                const uint4 z4 = make_uint4(old, 0, old, 0);
#pragma unroll
                for (int v = 0; v < 5; v++) if (v < 4 || st < 32) st_rlx128(scr->kvp + bi * 544 + v * 128 + st, z4);
                if (st < 16) st_rlx128(scr->o + ((bi_i * 8 + (st >> 1)) * 32 + bi_j * 4 + 3) * 32 + 30 + (st & 1), z4);
                if (lane < 8) st_rlx64(kvf_h + ((bi_i & 3) * 8 + w4 * 2 + (lane & 1)) * 4 + (lane >> 1), old, 0);
                if (st < 4 && !(bi_i & 1)) st_rlx64(kvf_h + (64 + qq) * 2 + (lane & 1), old, 0);
                __syncwarp();
                if (lane == 0) mbar_arrive(bar + 8 * BAR_PREP);
            }
            int n = 0;
#pragma unroll 1
            while (__any_sync(~0u, (int)(ld_acq(scr->xcnt + bi_j * 32) - (epoch1 << 7)) < 0)) { if (++n > SPIN_LIMIT) break; }
            if (warp == 12) STAMP(15);
            uint4 ur[8];
#pragma unroll
            for (int v = 0; v < 8; v++) ur[v] = __ldcg(scr->xt + bi * 1024 + st + 128 * v);
            mbar_wait(bar + 8 * BAR_KG, 0);
            if (lane < 16) sts128(ub - 256 + lane * 16, 0, 0, 0, 0);
#pragma unroll
            for (int v = 0; v < 8; v++) {
                const int ci = (st >> 2) + 32 * v;
                sts128(sb + OFF_U + (st & 3) * U_STRIDE + 256 + ((ci ^ ((ci >> 3) & 1)) << 4), ur[v].x, ur[v].y, ur[v].z, ur[v].w);
            }
            __syncwarp();
            if (lane == 0) mbar_arrive(bar + 8 * BAR_UR);
            mbar_wait(bar + 8 * BAR_UR, 0);
            if (warp == 12) STAMP(16);
            mbar_wait(bar + 8 * (BAR_KD + w4), 0);
            if (lane < 2) sts128(buf + lane * W3_OFF, 0, 0, 0, 0);
            windows(5, 4);
        }
        mbar_wait(bar + 8 * BAR_SP2, 0);
        windows(3, 0);
        __syncwarp();
        if (lane == 0) mbar_arrive(bar + 8 * BAR_WR);
        if (warp == 12) STAMP(24);
        {
            const bool zw = st < 32 && !(bi_i & 1);
            const uint4* src = scr->kvp + bi_j * (16 * 544) + (bi_i >> 2) * 136;
            const uint4* zsrc = src + (lane >> 2) * (2 * 544) + 128 + (lane & 1) * 4 + qq;
            src += (lane >> 3) * (4 * 544) + ((lane >> 1) & 3) * 32 + (bi_i & 3) * 8 + w4 * 2 + (lane & 1);
            mbar_wait(bar + 8 * BAR_PUB, 0);
            if (warp == 12) STAMP(12);
            uint4 v[6];
#pragma unroll
            for (int k = 0; k < 6; k++) v[k] = make_uint4(tag ^ 1u, 0, 0, 0);
            int n = 0;
#pragma unroll 1
            while (true) {
#pragma unroll
                for (int k = 0; k < 6; k++) if ((bad4(v[k], tag) & 1) && (k < 4 || zw)) v[k] = ld_rlx128(k < 4 ? src + k * 544 : zsrc + (k - 4) * 544);
                if (!__any_sync(~0u, (bad4(v[0], tag) | bad4(v[1], tag) | bad4(v[2], tag) | bad4(v[3], tag) | (zw ? bad4(v[4], tag) | bad4(v[5], tag) : 0u)) & 1)) break;
                if (++n > SPIN_LIMIT) break;
            }
            if (warp == 12) STAMP(30);
            float f[8];
            const float* vf = (const float*)v;
#pragma unroll
            for (int r = 0; r < 4; r++) {
                f[r] = (vf[r] + vf[4 + r]) + (vf[8 + r] + vf[12 + r]);
                f[4 + r] = vf[16 + r] + vf[20 + r];
                f[4 + r] += __shfl_xor_sync(~0u, f[4 + r], 4);
            }
#pragma unroll
            for (int o = 8; o <= 16; o <<= 1)
#pragma unroll
                for (int r = 0; r < 8; r++) f[r] += __shfl_xor_sync(~0u, f[r], o);
            if (lane < 8) st_rlx64(kvf_h + ((bi_i & 3) * 8 + w4 * 2 + (lane & 1)) * 4 + (lane >> 1), tagw(pack2(f[0], f[1]), tag), pack2(f[2], f[3]));
            if (zw && lane < 4) st_rlx64(kvf_h + (64 + qq) * 2 + (lane & 1), tagw(pack2(f[4], f[5]), tag), pack2(f[6], f[7]));
        }
        if (warp == 12) STAMP(13);
        {
            const uint4* kp = scr->kvf + bi_j * 272 + st;
            uint4 v0 = make_uint4(tag ^ 1u, 0, 0, 0), v1 = v0, v2 = make_uint4(st < 16 ? tag ^ 1u : tag, 0, tag, 0);
            int n = 0;
#pragma unroll 1
            while (true) {
                if (bad4(v0, tag) & 1) v0 = ld_rlx128(kp);
                if (bad4(v1, tag) & 1) v1 = ld_rlx128(kp + 128);
                if (bad4(v2, tag) & 1) v2 = ld_rlx128(kp + 256);
                if (!__any_sync(~0u, (bad4(v0, tag) | bad4(v1, tag) | bad4(v2, tag)) & 1)) break;
                if (++n > SPIN_LIMIT) break;
            }
            sts128(sb + OFF_KVF + st * 16, v0.x, v0.y, v0.z, v0.w);
            sts128(sb + OFF_KVF + 2048 + st * 16, v1.x, v1.y, v1.z, v1.w);
            if (st < 16) sts128(sb + OFF_KVF + 4096 + st * 16, v2.x, v2.y, v2.z, v2.w);
            __syncwarp();
            if (lane == 0) mbar_arrive(bar + 8 * BAR_KVF);
        }
        if (warp == 13) {
            mbar_wait(bar + 8 * BAR_KVF, 0);
            if (lane == 0) {
                mbar_expect(bar + 8 * BAR_WO2, 65536);
                tma2d(sb + OFF_P, &mwo, (bi_j & 3) * 128 + 64, 256, bar + 8 * BAR_WO2);
                tma2d(sb + OFF_V, &mwo, (bi_j & 3) * 128, 256, bar + 8 * BAR_WO2);
            }
        }
        if (warp == 12) STAMP(25);
    }
    __syncwarp();
    if (lane == 0) {
        unsigned old;
        asm volatile("atom.acq_rel.cta.shared.add.u32 %0,[%1],1;" : "=r"(old) : "r"(bar + OFF_CNT) : "memory");
        if (old == 15) {
            atomicAdd(scr->done, 1u);
        }
    }
}

typedef CUresult (*EncFn)(CUtensorMap*, CUtensorMapDataType, cuuint32_t, void*, const cuuint64_t*, const cuuint64_t*, const cuuint32_t*,
                          const cuuint32_t*, CUtensorMapInterleave, CUtensorMapSwizzle, CUtensorMapL2promotion, CUtensorMapFloatOOBfill);

extern "C" void kernel_launch(void* const* d_in, const int* in_sizes, int n_in, void* d_out, int out_size) {
    static EncFn enc = nullptr;
    static Scratch* scr = nullptr;
    if (!enc) {
        cudaGetSymbolAddress((void**)&scr, g_scr);
        cudaDriverEntryPointQueryResult qr;
        cudaGetDriverEntryPoint("cuTensorMapEncodeTiled", (void**)&enc, cudaEnableDefault, &qr);
        cudaFuncSetAttribute(fused_kernel, cudaFuncAttributeMaxDynamicSharedMemorySize, SMEM_BYTES);
    }
    CUtensorMap mx, mw, mwo;
    const cuuint32_t es[3] = {1, 1, 1};
    {
        cuuint64_t d[2] = {512, 2048}, s[1] = {1024}; cuuint32_t b[2] = {64, 128};
        enc(&mx, CU_TENSOR_MAP_DATA_TYPE_BFLOAT16, 2, d_in[0], d, s, b, es, CU_TENSOR_MAP_INTERLEAVE_NONE, CU_TENSOR_MAP_SWIZZLE_128B,
            CU_TENSOR_MAP_L2_PROMOTION_L2_128B, CU_TENSOR_MAP_FLOAT_OOB_FILL_NONE);
    }
    {
        cuuint64_t d[3] = {512, 512, 3}, s[2] = {3072, 1024}; cuuint32_t b[3] = {64, 64, 3};
        enc(&mw, CU_TENSOR_MAP_DATA_TYPE_BFLOAT16, 3, d_in[1], d, s, b, es, CU_TENSOR_MAP_INTERLEAVE_NONE, CU_TENSOR_MAP_SWIZZLE_128B,
            CU_TENSOR_MAP_L2_PROMOTION_L2_128B, CU_TENSOR_MAP_FLOAT_OOB_FILL_NONE);
    }
    {
        cuuint64_t d[2] = {512, 512}, s[1] = {1024}; cuuint32_t b[2] = {64, 256};
        enc(&mwo, CU_TENSOR_MAP_DATA_TYPE_BFLOAT16, 2, d_in[3], d, s, b, es, CU_TENSOR_MAP_INTERLEAVE_NONE, CU_TENSOR_MAP_SWIZZLE_128B,
            CU_TENSOR_MAP_L2_PROMOTION_L2_128B, CU_TENSOR_MAP_FLOAT_OOB_FILL_NONE);
    }
    fused_kernel<<<128, 512, SMEM_BYTES, cudaStreamPerThread>>>(
        scr, (const bf16*)d_in[5], (const bf16*)d_in[6], (const bf16*)d_in[7], (const bf16*)d_in[8], (const bf16*)d_in[9],
        (const bf16*)d_in[10], (const bf16*)d_in[2], (const bf16*)d_in[11], (bf16*)d_out, mx, mw, mwo);
}
```

```cpp
#include <cuda_runtime.h>
#include <cuda.h>
#include <cuda_bf16.h>
#include <stdint.h>

typedef __nv_bfloat16 bf16;

struct Scratch {
    uint4 xt[128 * 1024];
    uint4 o[16 * 8 * 32 * 32];
    uint4 y[128 * 1024];
    uint4 kvp[8 * 16 * 544];
    uint4 kvf[8 * 4 * 68];
    unsigned g[1024 * 8];
    unsigned yflag[128 * 8];
    unsigned xcnt[8 * 32];
    unsigned done[32];
};
__device__ Scratch g_scr;
#define STAMP(n)

constexpr int SLOT = 40960;
constexpr int OFF_SP0 = 32768, OFF_SP1 = SLOT + 32768;
constexpr int OFF_P = 2 * SLOT, OFF_V = OFF_P + 32768;
constexpr int OFF_KVF = OFF_V + 32768;
constexpr int KT_BYTES = 3264, KW_D = 16, KW_2 = 560, KW_3 = 656;
constexpr int OFF_U = 4 * SLOT, U_STRIDE = 4096 + 256 + 32;
constexpr int OFF_BUF = OFF_U + 4 * U_STRIDE, BUF_STRIDE = 8320;
constexpr int OFF_K = OFF_BUF + 4 * BUF_STRIDE;
constexpr int OFF_WPHI = OFF_K + 4 * KT_BYTES;
constexpr int OFF_GW = OFF_WPHI + 2048;
constexpr int OFF_BAR = OFF_GW + 1024;
constexpr int SMEM_BYTES = OFF_BAR + 320 + 256;
static_assert(SMEM_BYTES <= 232448 && OFF_BUF % 128 == 0, "smem");
constexpr int W5_OFF = 0, W3_OFF = 3088, W9_OFF = 6176;
constexpr int BAR_FULL = 0, BAR_EMPTY = 4, BAR_WPHI = 8, BAR_WO = 9, BAR_WO2 = 10, BAR_XT = 11, BAR_DONE = 12, BAR_KG = 13, BAR_SP = 14,
              BAR_PUB = 15, BAR_KVF = 16, BAR_UR = 17, BAR_WR = 18, BAR_PREP = 19, BAR_KGA = 20, BAR_SP2 = 21, BAR_KS = 22, BAR_KP = 26, BAR_KD = 30, OFF_CNT = 272;
constexpr int SPIN_LIMIT = 1 << 17;

__device__ __forceinline__ uint32_t s2u(const void* p) { return (uint32_t)__cvta_generic_to_shared(p); }
__device__ __forceinline__ void mbar_init(uint32_t b, int c) { asm volatile("mbarrier.init.shared::cta.b64 [%0],%1;" ::"r"(b), "r"(c) : "memory"); }
__device__ __forceinline__ void mbar_expect(uint32_t b, int bytes) { asm volatile("mbarrier.arrive.expect_tx.shared::cta.b64 _,[%0],%1;" ::"r"(b), "r"(bytes) : "memory"); }
__device__ __forceinline__ void mbar_arrive(uint32_t b) { asm volatile("mbarrier.arrive.shared::cta.b64 _,[%0];" ::"r"(b) : "memory"); }
__device__ __forceinline__ void mbar_wait(uint32_t b, int ph) {
    asm volatile("{\n.reg .pred p;\n.reg .u32 n;\nmov.u32 n,0;\nLW_%=:\nmbarrier.try_wait.parity.shared::cta.b64 p,[%0],%1;\n@p bra LD_%=;\n"
                 "add.u32 n,n,1;\nsetp.lt.u32 p,n,16384;\n@p bra LW_%=;\nLD_%=:\n}" ::"r"(b), "r"(ph) : "memory");
}
__device__ __forceinline__ void tma2d(uint32_t dst, const CUtensorMap* m, int c0, int c1, uint32_t bar) {
    asm volatile("cp.async.bulk.tensor.2d.shared::cluster.global.mbarrier::complete_tx::bytes [%0],[%1,{%3,%4}],[%2];" ::"r"(dst), "l"(m), "r"(bar), "r"(c0), "r"(c1) : "memory");
}
__device__ __forceinline__ void tma3d(uint32_t dst, const CUtensorMap* m, int c0, int c1, int c2, uint32_t bar) {
    asm volatile("cp.async.bulk.tensor.3d.shared::cluster.global.mbarrier::complete_tx::bytes [%0],[%1,{%3,%4,%5}],[%2];" ::"r"(dst), "l"(m), "r"(bar), "r"(c0), "r"(c1), "r"(c2) : "memory");
}
__device__ __forceinline__ void bulk_g2s(uint32_t dst, const void* src, int bytes, uint32_t bar) {
    asm volatile("cp.async.bulk.shared::cluster.global.mbarrier::complete_tx::bytes [%0],[%1],%2,[%3];" ::"r"(dst), "l"(src), "r"(bytes), "r"(bar) : "memory");
}
__device__ __forceinline__ uint64_t mkdesc(uint32_t addr, uint32_t lbo, uint32_t sbo) {
    return (uint64_t)((addr & 0x3FFFF) >> 4) | ((uint64_t)(lbo >> 4) << 16) | ((uint64_t)(sbo >> 4) << 32) | ((uint64_t)1 << 62);
}
__device__ __forceinline__ void wg_fence() { asm volatile("wgmma.fence.sync.aligned;" ::: "memory"); }
__device__ __forceinline__ void wg_commit() { asm volatile("wgmma.commit_group.sync.aligned;" ::: "memory"); }
template <int N> __device__ __forceinline__ void wg_wait() { asm volatile("wgmma.wait_group.sync.aligned %0;" ::"n"(N) : "memory"); }
template <int N> __device__ __forceinline__ void fence_regs(float* d) {
#pragma unroll
    for (int i = 0; i < N; i++) asm volatile("" : "+f"(d[i])::"memory");
}
#define R8(d, o) "+f"(d[o]), "+f"(d[o + 1]), "+f"(d[o + 2]), "+f"(d[o + 3]), "+f"(d[o + 4]), "+f"(d[o + 5]), "+f"(d[o + 6]), "+f"(d[o + 7])
__device__ __forceinline__ void wgmma192(float* d, uint64_t da, uint64_t db, int sc) {
    asm volatile("{.reg .pred p; setp.ne.b32 p,%98,0; wgmma.mma_async.sync.aligned.m64n192k16.f32.bf16.bf16 {"
                 "%0,%1,%2,%3,%4,%5,%6,%7,%8,%9,%10,%11,%12,%13,%14,%15,%16,%17,%18,%19,%20,%21,%22,%23,%24,%25,%26,%27,%28,%29,%30,%31,"
                 "%32,%33,%34,%35,%36,%37,%38,%39,%40,%41,%42,%43,%44,%45,%46,%47,%48,%49,%50,%51,%52,%53,%54,%55,%56,%57,%58,%59,%60,%61,%62,%63,"
                 "%64,%65,%66,%67,%68,%69,%70,%71,%72,%73,%74,%75,%76,%77,%78,%79,%80,%81,%82,%83,%84,%85,%86,%87,%88,%89,%90,%91,%92,%93,%94,%95},"
                 "%96,%97,p,1,1,0,1;}"
                 : R8(d, 0), R8(d, 8), R8(d, 16), R8(d, 24), R8(d, 32), R8(d, 40), R8(d, 48), R8(d, 56), R8(d, 64), R8(d, 72), R8(d, 80), R8(d, 88)
                 : "l"(da), "l"(db), "r"(sc));
}
__device__ __forceinline__ void wgmma64_tt(float* d, uint64_t da, uint64_t db, int sc) {
    asm volatile("{.reg .pred p; setp.ne.b32 p,%34,0; wgmma.mma_async.sync.aligned.m64n64k16.f32.bf16.bf16 {"
                 "%0,%1,%2,%3,%4,%5,%6,%7,%8,%9,%10,%11,%12,%13,%14,%15,%16,%17,%18,%19,%20,%21,%22,%23,%24,%25,%26,%27,%28,%29,%30,%31},"
                 "%32,%33,p,1,1,1,1;}"
                 : R8(d, 0), R8(d, 8), R8(d, 16), R8(d, 24)
                 : "l"(da), "l"(db), "r"(sc));
}
__device__ __forceinline__ void wgmma128_rs(float* d, const uint4& a, uint64_t db, int sc) {
    asm volatile("{.reg .pred p; setp.ne.b32 p,%69,0; wgmma.mma_async.sync.aligned.m64n128k16.f32.bf16.bf16 {"
                 "%0,%1,%2,%3,%4,%5,%6,%7,%8,%9,%10,%11,%12,%13,%14,%15,%16,%17,%18,%19,%20,%21,%22,%23,%24,%25,%26,%27,%28,%29,%30,%31,"
                 "%32,%33,%34,%35,%36,%37,%38,%39,%40,%41,%42,%43,%44,%45,%46,%47,%48,%49,%50,%51,%52,%53,%54,%55,%56,%57,%58,%59,%60,%61,%62,%63},"
                 "{%64,%65,%66,%67},%68,p,1,1,1;}"
                 : R8(d, 0), R8(d, 8), R8(d, 16), R8(d, 24), R8(d, 32), R8(d, 40), R8(d, 48), R8(d, 56)
                 : "r"(a.x), "r"(a.y), "r"(a.z), "r"(a.w), "l"(db), "r"(sc));
}
__device__ __forceinline__ void mma16816(float* c, uint32_t a0, uint32_t a1, uint32_t a2, uint32_t a3, uint32_t b0, uint32_t b1) {
    asm("mma.sync.aligned.m16n8k16.row.col.f32.bf16.bf16.f32 {%0,%1,%2,%3},{%4,%5,%6,%7},{%8,%9},{%0,%1,%2,%3};"
        : "+f"(c[0]), "+f"(c[1]), "+f"(c[2]), "+f"(c[3]) : "r"(a0), "r"(a1), "r"(a2), "r"(a3), "r"(b0), "r"(b1));
}
__device__ __forceinline__ void ldsm4(uint32_t* r, uint32_t a) {
    asm volatile("ldmatrix.sync.aligned.m8n8.x4.shared.b16 {%0,%1,%2,%3},[%4];" : "=r"(r[0]), "=r"(r[1]), "=r"(r[2]), "=r"(r[3]) : "r"(a) : "memory");
}
__device__ __forceinline__ void ldsm4t(uint32_t* r, uint32_t a) {
    asm volatile("ldmatrix.sync.aligned.m8n8.x4.trans.shared.b16 {%0,%1,%2,%3},[%4];" : "=r"(r[0]), "=r"(r[1]), "=r"(r[2]), "=r"(r[3]) : "r"(a) : "memory");
}
__device__ __forceinline__ void stsm4(uint32_t a, uint32_t r0, uint32_t r1, uint32_t r2, uint32_t r3) {
    asm volatile("stmatrix.sync.aligned.m8n8.x4.shared.b16 [%0],{%1,%2,%3,%4};" ::"r"(a), "r"(r0), "r"(r1), "r"(r2), "r"(r3) : "memory");
}
__device__ __forceinline__ uint32_t lds32(uint32_t a) { uint32_t v; asm volatile("ld.shared.b32 %0,[%1];" : "=r"(v) : "r"(a) : "memory"); return v; }
__device__ __forceinline__ uint4 lds128(uint32_t a) { uint4 v; asm volatile("ld.shared.v4.b32 {%0,%1,%2,%3},[%4];" : "=r"(v.x), "=r"(v.y), "=r"(v.z), "=r"(v.w) : "r"(a) : "memory"); return v; }
__device__ __forceinline__ void sts16(uint32_t a, uint32_t v) { asm volatile("st.shared.b16 [%0],%1;" ::"r"(a), "h"((unsigned short)v) : "memory"); }
__device__ __forceinline__ void sts32(uint32_t a, uint32_t v) { asm volatile("st.shared.b32 [%0],%1;" ::"r"(a), "r"(v) : "memory"); }
__device__ __forceinline__ void sts64(uint32_t a, uint32_t x, uint32_t y) { asm volatile("st.shared.v2.b32 [%0],{%1,%2};" ::"r"(a), "r"(x), "r"(y) : "memory"); }
__device__ __forceinline__ void sts128(uint32_t a, uint32_t x, uint32_t y, uint32_t z, uint32_t w) { asm volatile("st.shared.v4.b32 [%0],{%1,%2,%3,%4};" ::"r"(a), "r"(x), "r"(y), "r"(z), "r"(w) : "memory"); }
__device__ __forceinline__ uint32_t pack2(float lo, float hi) { uint32_t d; asm("cvt.rn.bf16x2.f32 %0,%1,%2;" : "=r"(d) : "f"(hi), "f"(lo)); return d; }
__device__ __forceinline__ float bf_lo(uint32_t v) { return __uint_as_float(v << 16); }
__device__ __forceinline__ float bf_hi(uint32_t v) { return __uint_as_float(v & 0xffff0000u); }
__device__ __forceinline__ float bf_round(float v) { return bf_lo(pack2(v, 0.f)); }
__device__ __forceinline__ uint32_t hmax2(uint32_t a, uint32_t b) { uint32_t d; asm("max.bf16x2 %0,%1,%2;" : "=r"(d) : "r"(a), "r"(b)); return d; }
__device__ __forceinline__ uint32_t hmin2(uint32_t a, uint32_t b) { uint32_t d; asm("min.bf16x2 %0,%1,%2;" : "=r"(d) : "r"(a), "r"(b)); return d; }
__device__ __forceinline__ uint32_t hmul2(uint32_t a, uint32_t b) { uint32_t d; asm("mul.rn.bf16x2 %0,%1,%2;" : "=r"(d) : "r"(a), "r"(b)); return d; }
__device__ __forceinline__ float ex2(float x) { float y; asm("ex2.approx.ftz.f32 %0,%1;" : "=f"(y) : "f"(x)); return y; }
__device__ __forceinline__ float rcp(float x) { float y; asm("rcp.approx.ftz.f32 %0,%1;" : "=f"(y) : "f"(x)); return y; }
__device__ __forceinline__ uint32_t ld_nc(const uint32_t* p) { uint32_t v; asm volatile("ld.global.nc.b32 %0,[%1];" : "=r"(v) : "l"(p)); return v; }
__device__ __forceinline__ uint2 ld_nc64(const uint2* p) { uint2 v; asm volatile("ld.global.nc.v2.b32 {%0,%1},[%2];" : "=r"(v.x), "=r"(v.y) : "l"(p)); return v; }
__device__ __forceinline__ unsigned ld_acq(const unsigned* p) { unsigned v; asm volatile("ld.acquire.gpu.global.u32 %0,[%1];" : "=r"(v) : "l"(p) : "memory"); return v; }
__device__ __forceinline__ unsigned ld_rlx(const unsigned* p) { unsigned v; asm volatile("ld.relaxed.gpu.global.u32 %0,[%1];" : "=r"(v) : "l"(p) : "memory"); return v; }
__device__ __forceinline__ uint2 ld_rlx64(const void* p) { uint2 v; asm volatile("{.reg .b64 t; ld.relaxed.gpu.global.b64 t,[%2]; mov.b64 {%0,%1},t;}" : "=r"(v.x), "=r"(v.y) : "l"(p) : "memory"); return v; }
__device__ __forceinline__ uint4 ld_rlx128(const void* p) {
    uint4 v;
    asm volatile("{.reg .b64 t,u; ld.relaxed.gpu.global.v2.b64 {t,u},[%4]; mov.b64 {%0,%1},t; mov.b64 {%2,%3},u;}" : "=r"(v.x), "=r"(v.y), "=r"(v.z), "=r"(v.w) : "l"(p) : "memory");
    return v;
}
__device__ __forceinline__ void st_rlx32(void* p, uint32_t x) { asm volatile("st.relaxed.gpu.global.u32 [%0],%1;" ::"l"(p), "r"(x) : "memory"); }
__device__ __forceinline__ void st_rlx64(void* p, uint32_t x, uint32_t y) { asm volatile("{.reg .b64 t; mov.b64 t,{%1,%2}; st.relaxed.gpu.global.b64 [%0],t;}" ::"l"(p), "r"(x), "r"(y) : "memory"); }
__device__ __forceinline__ void st_rlx128(void* p, uint4 v) {
    asm volatile("{.reg .b64 t,u; mov.b64 t,{%1,%2}; mov.b64 u,{%3,%4}; st.relaxed.gpu.global.v2.b64 [%0],{t,u};}" ::"l"(p), "r"(v.x), "r"(v.y), "r"(v.z), "r"(v.w) : "memory");
}
__device__ __forceinline__ uint32_t tagw(uint32_t w, uint32_t tag) { return (w & ~1u) | tag; }
__device__ __forceinline__ uint4 tag4(uint32_t x, uint32_t y, uint32_t z, uint32_t w, uint32_t tag) { return make_uint4(tagw(x, tag), y, tagw(z, tag), w); }
__device__ __forceinline__ uint32_t bad4(const uint4& v, uint32_t tag) { return (v.x ^ tag) | (v.z ^ tag); }
__device__ __forceinline__ void bar_named(int id, int n) { asm volatile("bar.sync %0,%1;" ::"r"(id), "r"(n) : "memory"); }

struct cf { float re, im; };
__device__ __forceinline__ cf cmul(cf a, cf b) { cf r; r.re = a.re * b.re - a.im * b.im; r.im = a.re * b.im + a.im * b.re; return r; }
__device__ __forceinline__ cf cexp_p(float arl, float ait, float p) {
    float mag = ex2(arl * p);
    float t = ait * p;
    const float big = 12582912.f;
    t = (t - ((t + big) - big)) * 6.283185307179586f;
    cf r; r.re = mag * __cosf(t); r.im = mag * __sinf(t);
    return r;
}

__device__ __forceinline__ void hedgehog4(const uint32_t* a, uint32_t wphi_addr, uint32_t (*out)[8]) {
    float p[4][2][4], mx[4][2];
#pragma unroll
    for (int h = 0; h < 4; h++) {
        uint32_t b[4];
        ldsm4t(b, wphi_addr + h * 512);
        float c0[4] = {0.f, 0.f, 0.f, 0.f}, c1[4] = {0.f, 0.f, 0.f, 0.f};
        mma16816(c0, a[4 * h], a[4 * h + 1], a[4 * h + 2], a[4 * h + 3], b[0], b[1]);
        mma16816(c1, a[4 * h], a[4 * h + 1], a[4 * h + 2], a[4 * h + 3], b[2], b[3]);
#pragma unroll
        for (int k = 0; k < 2; k++) {
            p[h][k][0] = c0[2 * k]; p[h][k][1] = c0[2 * k + 1]; p[h][k][2] = c1[2 * k]; p[h][k][3] = c1[2 * k + 1];
            mx[h][k] = fmaxf(fmaxf(p[h][k][0], p[h][k][1]), fmaxf(p[h][k][2], p[h][k][3]));
        }
    }
#pragma unroll
    for (int o = 1; o <= 2; o <<= 1)
#pragma unroll
        for (int h = 0; h < 4; h++)
#pragma unroll
            for (int k = 0; k < 2; k++) mx[h][k] = fmaxf(mx[h][k], __shfl_xor_sync(~0u, mx[h][k], o));
    const float L = 1.4426950408889634f;
    float pmin = 1.f;
#pragma unroll
    for (int h = 0; h < 4; h++)
#pragma unroll
        for (int k = 0; k < 2; k++) {
            const float m = -mx[h][k] * L;
            const float e0 = ex2(fmaf(p[h][k][0], L, m)), e1 = ex2(fmaf(p[h][k][1], L, m)), e2 = ex2(fmaf(p[h][k][2], L, m)), e3 = ex2(fmaf(p[h][k][3], L, m));
            const float p01 = e0 * e1, p23 = e2 * e3, pp = p01 * p23, r = rcp(pp), r01 = r * p23, r23 = r * p01;
            pmin = fminf(pmin, pp);
            out[h][k] = pack2(e0, e1); out[h][k + 2] = pack2(e2, e3);
            out[h][4 + k] = pack2(r01 * e1, r01 * e0); out[h][4 + k + 2] = pack2(r23 * e3, r23 * e2);
        }
    if (__builtin_expect(__any_sync(~0u, !(pmin > 1e-18f)), 0)) {
#pragma unroll
        for (int h = 0; h < 4; h++)
#pragma unroll
            for (int k = 0; k < 2; k++) {
                float m = fminf(fminf(p[h][k][0], p[h][k][1]), fminf(p[h][k][2], p[h][k][3]));
                m = fminf(m, __shfl_xor_sync(~0u, m, 1));
                m = fminf(m, __shfl_xor_sync(~0u, m, 2)) * L;
                out[h][4 + k] = pack2(ex2(fmaf(p[h][k][0], -L, m)), ex2(fmaf(p[h][k][1], -L, m)));
                out[h][4 + k + 2] = pack2(ex2(fmaf(p[h][k][2], -L, m)), ex2(fmaf(p[h][k][3], -L, m)));
            }
    }
}

__global__ void __launch_bounds__(512, 1)
fused_kernel(Scratch* __restrict__ scr, const bf16* __restrict__ logA, const bf16* __restrict__ Aim, const bf16* __restrict__ Cre,
             const bf16* __restrict__ Cim, const bf16* __restrict__ logdt, const bf16* __restrict__ Dskip, const bf16* __restrict__ wphi,
             const bf16* __restrict__ gatew, bf16* __restrict__ out, const bf16* __restrict__ x,
             const __grid_constant__ CUtensorMap mx, const __grid_constant__ CUtensorMap mw, const __grid_constant__ CUtensorMap mwo) {
    extern __shared__ __align__(1024) uint8_t smem[];
    constexpr uint32_t sb = 1024;
    const int tid = threadIdx.x, warp = __shfl_sync(~0u, tid >> 5, 0), lane = tid & 31;
    const int g = lane >> 2, q = lane & 3, w4 = warp & 3;
    const int bi = blockIdx.x, bi_i = bi & 15, bi_j = bi >> 4;
    const uint32_t bar = sb + OFF_BAR;
    const int rot = (bi_j & 3) * 2, xkb = bi_j >> 2;
    auto load_stage = [&](int kb) {
        const uint32_t b = bar + 8 * (BAR_FULL + (kb & 3)), d = sb + (kb & 3) * SLOT;
        const int kc = ((kb + rot) & 7) * 64;
        mbar_expect(b, SLOT);
        tma2d(d, &mx, kc, bi_i * 128, b);
        tma3d(d + 16384, &mw, bi_j * 64, kc, 0, b);
    };

    const int ch = bi * 4 + w4;
    const int pidx = ch * 64 + lane * 2 + (warp >> 3);
    const uint32_t pla = ld_nc((const uint32_t*)logA + pidx), pai = ld_nc((const uint32_t*)Aim + pidx);
    const uint32_t pcr = ld_nc((const uint32_t*)Cre + pidx), pci = ld_nc((const uint32_t*)Cim + pidx);
    uint32_t pdt = ld_nc((const uint32_t*)logdt + (ch >> 1));
    const uint32_t pds = ld_nc((const uint32_t*)Dskip + (ch >> 1));
    unsigned done0 = ld_rlx(scr->done);
    if (tid == 0) {
        for (int s = 0; s < 4; s++) mbar_init(bar + 8 * (BAR_FULL + s), 1);
        asm volatile("fence.mbarrier_init.release.cluster;" ::: "memory");
        asm volatile("prefetch.tensormap [%0];" ::"l"(&mx) : "memory");
        load_stage(0); load_stage(1);
        STAMP(11);
    } else if (tid == 32) {
        if (s2u(smem) != sb) __trap();
        sts32(bar + OFF_CNT, 0);
        for (int s = 0; s < 4; s++) { mbar_init(bar + 8 * (BAR_EMPTY + s), 8); mbar_init(bar + 8 * (BAR_KS + s), 1); mbar_init(bar + 8 * (BAR_KP + s), 3); mbar_init(bar + 8 * (BAR_KD + s), 1); }
        mbar_init(bar + 8 * BAR_WPHI, 1); mbar_init(bar + 8 * BAR_WO, 2); mbar_init(bar + 8 * BAR_WO2, 1); mbar_init(bar + 8 * BAR_XT, 4);
        mbar_init(bar + 8 * BAR_DONE, 8); mbar_init(bar + 8 * BAR_KG, 8); mbar_init(bar + 8 * BAR_PUB, 8);
        mbar_init(bar + 8 * BAR_KVF, 4); mbar_init(bar + 8 * BAR_UR, 4); mbar_init(bar + 8 * BAR_WR, 4); mbar_init(bar + 8 * BAR_PREP, 4); mbar_init(bar + 8 * BAR_KGA, 4); mbar_init(bar + 8 * BAR_SP2, 1);
        asm volatile("fence.mbarrier_init.release.cluster;" ::: "memory");
        mbar_expect(bar + 8 * BAR_WPHI, 3072);
        bulk_g2s(sb + OFF_GW, gatew, 1024, bar + 8 * BAR_WPHI);
        bulk_g2s(sb + OFF_WPHI, wphi + bi_j * 1024, 2048, bar + 8 * BAR_WPHI);
    } else if (tid == 64) {
        asm volatile("prefetch.tensormap [%0];" ::"l"(&mw) : "memory");
    }
    const uint32_t buf = sb + OFF_BUF + w4 * BUF_STRIDE, kb_ = sb + OFF_K + w4 * KT_BYTES;
    if ((warp >> 2) == 2) {
#pragma unroll
        for (int v = 0; v < 7; v++) if (v * 32 + lane < KT_BYTES / 16) sts128(kb_ + (v * 32 + lane) * 16, 0, 0, 0, 0);
    }
    __syncthreads();
    asm volatile("" : "+r"(pdt), "+r"(done0)::"memory");
    const unsigned epoch1 = (done0 >> 7) + 1u;
    const uint32_t tag = epoch1 & 1u;

    const int st = tid & 127;
    const uint32_t ub = sb + OFF_U + w4 * U_STRIDE + 256, spare = sb + (w4 < 2 ? OFF_SP0 : OFF_SP1) + (w4 & 1) * 4096;

    auto stg_of = [&](int w) { return w < 8 ? sb + 3 * SLOT + w * 7296 : sb + 2 * SLOT + (w & 3) * 7296; };
    float kc[24];
#pragma unroll
    for (int t = 0; t < 24; t++) kc[t] = 0.f;
    auto handoff = [&](int src) {
        mbar_wait(bar + 8 * (BAR_KS + w4), 0);
#pragma unroll
        for (int t = 0; t < 5; t++)
            sts128(buf + src * 2560 + (t * 32 + lane) * 16, __float_as_uint(kc[4 * t]), __float_as_uint(kc[4 * t + 1]), __float_as_uint(kc[4 * t + 2]), __float_as_uint(kc[4 * t + 3]));
        if (lane == 0) sts32(buf + 7680 + src * 4, __float_as_uint(kc[20]));
        __syncwarp();
        if (lane == 0) mbar_arrive(bar + 8 * (BAR_KP + w4));
    };
    {
        const float dt = bf_round(expf((ch & 1) ? bf_hi(pdt) : bf_lo(pdt)));
        const uint32_t stg = (warp >> 2) == 2 ? buf : stg_of(warp);
        const int sh = ((warp >> 2) & 1) * 16;
        auto pick = [&](uint32_t v) { return __uint_as_float((v >> sh) << 16); };
        const float ea = bf_round(ex2(pick(pla) * 1.4426950408889634f));
        const float arl = (-ea * dt) * 1.4426950408889634f, ait = (pick(pai) * dt) * 0.15915494309189535f;
        cf C2; C2.re = 2.0f * (pick(pcr) * dt); C2.im = 2.0f * (pick(pci) * dt);
        const cf z1 = cexp_p(arl, ait, 1.0f), z128 = cexp_p(arl, ait, 128.0f);
        const cf z2 = cmul(z1, z1), z4 = cmul(z2, z2);
        cf z8 = cmul(z4, z4); z8.im = -z8.im;
        const uint32_t sa0 = stg + (lane >> 3) * 128 + (((lane & 7) ^ (lane >> 3)) << 4), sa1 = (sa0 ^ 64) + 512;
        uint32_t w[60];
        auto put = [&](int row, const cf& v) {
            w[row] = pack2(v.re, v.im);
            if ((row & 3) == 3) stsm4(((row & 4) ? sa1 : sa0) + (row >> 3) * 1024, w[row - 3], w[row - 2], w[row - 1], w[row]);
        };
        {
            const cf z16 = cmul(z8, z8);
            cf e; e.re = 1.f; e.im = 0.f;
            cf o = z8;
            put(0, e); put(1, o);
            e = z16; put(2, e);
#pragma unroll
            for (int b = 3; b < 16; b += 2) {
                o = cmul(o, z16); put(b, o);
                if (b + 1 < 16) { e = cmul(e, z16); put(b + 1, e); }
            }
        }
        cf h[8];
        h[0] = C2; h[1] = cmul(h[0], z1);
#pragma unroll
        for (int r = 2; r < 8; r++) h[r] = cmul(h[r - 2], z2);
#pragma unroll
        for (int r = 0; r < 8; r++) put(16 + r, h[r]);
#pragma unroll
        for (int r = 0; r < 8; r++) { h[r] = cmul(h[r], z128); put(24 + r, h[r]); }
#pragma unroll
        for (int al = 0; al < 2; al++)
#pragma unroll
            for (int r = 0; r < 4; r++) { h[2 * r] = cmul(h[2 * r], z128); put(32 + al * 4 + r, h[2 * r]); }
#pragma unroll
        for (int al = 0; al < 4; al++)
#pragma unroll
            for (int r = 0; r < 2; r++) { h[4 * r] = cmul(h[4 * r], z128); put(40 + al * 2 + r, h[4 * r]); }
#pragma unroll
        for (int al = 0; al < 8; al++) { h[0] = cmul(h[0], z128); put(48 + al, h[0]); }
        h[0] = cmul(h[0], z128);
        sts32(stg + 56 * 128 + lane * 4, pack2(h[0].re, h[0].im));
        __syncwarp();
        const int lr = lane & 7, lm = lane >> 3;
#pragma unroll
        for (int kp = 0; kp < 2; kp++) {
            uint32_t a0[4], a1[4];
            ldsm4(a0, stg + ((lm & 1) * 8 + lr) * 128 + (((4 * kp + (lm >> 1)) ^ lr) << 4));
            ldsm4(a1, stg + ((lm & 1) * 8 + lr) * 128 + (((4 * kp + 2 + (lm >> 1)) ^ lr) << 4));
#pragma unroll
            for (int t = 0; t < 6; t++) {
                uint32_t b[4];
                ldsm4(b, stg + (16 + 8 * t + lr) * 128 + (((4 * kp + lm) ^ lr) << 4));
                mma16816(kc + 4 * t, a0[0], a0[1], a0[2], a0[3], b[0], b[1]);
                mma16816(kc + 4 * t, a1[0], a1[1], a1[2], a1[3], b[2], b[3]);
            }
        }
        __syncwarp();
        asm volatile("fence.proxy.async.shared::cta;" ::: "memory");
        const uint32_t cnt = 1u + (__float_as_uint(kc[0] + kc[23]) == 0xffc12345u);
        if (lane == 0) asm volatile("mbarrier.arrive.shared::cta.b64 _,[%0],%1;" ::"r"(bar + 8 * (warp < 8 ? BAR_KG : (warp < 12 ? BAR_KS + w4 : BAR_KGA))), "r"(cnt) : "memory");
        if (warp < 8) handoff(warp >> 2);
    }

    if (warp < 8) {
        const int wg = warp >> 2;
        if (warp == 0) STAMP(21);
        float acc[96];
        const int srow = warp * 16 + (lane & 15);
        const uint32_t srow_a = srow * 128;
        const int sx = srow & 7, shi = lane >> 4;
        const uint64_t da0 = mkdesc(sb + wg * 8192, 16, 1024), db0 = mkdesc(sb + 16384, 8192, 1024);
#pragma unroll 1
        for (int kb = 0; kb < 8; kb++) {
            const int s = kb & 3;
            const uint64_t da = da0 + s * (SLOT >> 4), db = db0 + s * (SLOT >> 4);
            if (warp == 0) STAMP(40 + kb);
            mbar_wait(bar + 8 * (BAR_FULL + s), kb >> 2);
            if (warp == 0) STAMP(32 + kb);
            wg_fence();
#pragma unroll
            for (int k = 0; k < 4; k++) wgmma192(acc, da + 2 * k, db + 128 * k, kb | k);
            wg_commit();
            wg_wait<1>();
            if (lane == 0 && kb > 0) mbar_arrive(bar + 8 * (BAR_EMPTY + ((kb - 1) & 3)));
        }
        mbar_wait(bar + 8 * BAR_WPHI, 0);
        wg_wait<0>();
        fence_regs<96>(acc);
        asm volatile("setmaxnreg.inc.sync.aligned.u32 160;");
        if (lane == 0) mbar_arrive(bar + 8 * BAR_DONE);
        if (warp == 0) STAMP(1);
        uint32_t in[16], qa[16];
        mbar_wait(bar + 8 * BAR_DONE, 0);
#pragma unroll
        for (int r = 0; r < 16; r++) {
            in[r] = pack2(acc[32 + 2 * r], acc[32 + 2 * r + 1]);
            qa[r] = pack2(acc[2 * r], acc[2 * r + 1]);
        }
#pragma unroll
        for (int hh = 0; hh < 4; hh++)
            stsm4(sb + OFF_V + (hh >> 1) * 16384 + srow_a + (((2 * (hh & 1) + shi) ^ sx) << 4), pack2(acc[64 + 8 * hh], acc[65 + 8 * hh]),
                  pack2(acc[66 + 8 * hh], acc[67 + 8 * hh]), pack2(acc[68 + 8 * hh], acc[69 + 8 * hh]), pack2(acc[70 + 8 * hh], acc[71 + 8 * hh]));
        sts128(sb + OFF_V + shi * 16384 + srow_a + ((4 ^ sx) << 4), 0x3f803f80u, 0x3f803f80u, 0x3f803f80u, 0x3f803f80u);
        const uint32_t wphi_a = sb + OFF_WPHI + (lane & 15) * 32 + (lane >> 4) * 16;
        uint32_t pq[4][8];
#pragma unroll 1
        for (int it = 0; it < 2; it++) {
            hedgehog4(in, wphi_a, pq);
            if (it == 1) break;
#pragma unroll
            for (int hs = 0; hs < 8; hs++) {
                float c[4] = {0.f, 0.f, 0.f, 0.f};
                const uint32_t* o = pq[hs >> 1] + 4 * (hs & 1);
                mma16816(c, o[0], o[1], o[2], o[3], 0x3f803f80u, 0x3f803f80u);
                const float r0 = rcp(c[0]), r1 = rcp(c[2]);
                const uint32_t s0 = pack2(r0, r0), s1 = pack2(r1, r1);
                stsm4(sb + OFF_P + (hs >> 2) * 16384 + srow_a + (((2 * (hs & 3) + shi) ^ sx) << 4), hmul2(o[0], s0), hmul2(o[1], s1), hmul2(o[2], s0), hmul2(o[3], s1));
            }
            asm volatile("fence.proxy.async.shared::cta;" ::: "memory");
            bar_named(1, 256);
            if (warp == 0) STAMP(2);
            float d[32];
            const uint64_t dv = mkdesc(sb + OFF_V + wg * 16384, 16, 1024), dp = mkdesc(sb + OFF_P + wg * 16384, 16, 1024);
            wg_fence();
#pragma unroll
            for (int k = 0; k < 8; k++) wgmma64_tt(d, dv + 128 * k, dp + 128 * k, k != 0);
            wg_commit();
            mbar_wait(bar + 8 * BAR_PREP, 0);
            uint4* kvp = scr->kvp + bi * 544 + wg * 272 + (w4 < 2 ? w4 * 136 : 128) + lane;
            wg_wait<0>();
            fence_regs<32>(d);
            if (w4 < 2 || (w4 == 2 && lane < 4)) {
#pragma unroll
                for (int f = 0; f < 4; f++) {
                    const int i0 = 8 * (f >> 1) + 2 * (f & 1), i2 = 16 * (f >> 1) + 8 * (f & 1);
                    const float e0 = w4 == 0 ? d[i0] : (w4 == 1 ? d[16 + i0] : d[i2]), e1 = w4 == 0 ? d[i0 + 1] : (w4 == 1 ? d[17 + i0] : d[i2 + 1]);
                    const float e2 = w4 == 0 ? d[i0 + 4] : (w4 == 1 ? d[20 + i0] : d[i2 + 4]), e3 = w4 == 0 ? d[i0 + 5] : (w4 == 1 ? d[21 + i0] : d[i2 + 5]);
                    st_rlx128(kvp + (w4 < 2 ? f * 32 : (f >> 1) * 136 + (f & 1) * 4), tag4(__float_as_uint(e0), __float_as_uint(e1), __float_as_uint(e2), __float_as_uint(e3), tag));
                }
            }
            __syncwarp();
            if (lane == 0) mbar_arrive(bar + 8 * BAR_PUB);
            if (warp == 0) STAMP(3);
#pragma unroll
            for (int r = 0; r < 16; r++) in[r] = qa[r];
        }
        if (warp == 0) STAMP(4);
        {
            mbar_wait(bar + 8 * BAR_KVF, 0);
            uint4 kf[4][3];
#pragma unroll
            for (int hh = 0; hh < 4; hh++) {
                const uint32_t a = sb + OFF_KVF + hh * 1088;
                kf[hh][0] = lds128(a + lane * 32); kf[hh][1] = lds128(a + lane * 32 + 16); kf[hh][2] = lds128(a + 1024 + q * 16);
            }
            if (warp == 0) STAMP(5);
            uint4* og = scr->o + ((bi_i * 8 + warp) * 32 + bi_j * 4) * 32 + lane;
#pragma unroll
            for (int hh = 0; hh < 4; hh++) {
                float c[6][4];
#pragma unroll
                for (int t = 0; t < 6; t++) { c[t][0] = c[t][1] = c[t][2] = c[t][3] = 0.f; }
                const uint32_t* a = pq[hh];
                const bool od = g & 1;
                mma16816(c[0], a[0], a[1], a[2], a[3], od ? 0x3f803f80u : kf[hh][2].x, od ? 0x3f803f80u : kf[hh][2].y);
                mma16816(c[1], a[4], a[5], a[6], a[7], od ? 0x3f803f80u : kf[hh][2].z, od ? 0x3f803f80u : kf[hh][2].w);
                mma16816(c[2], a[0], a[1], a[2], a[3], kf[hh][0].x, kf[hh][0].y);
                mma16816(c[3], a[0], a[1], a[2], a[3], kf[hh][0].z, kf[hh][0].w);
                mma16816(c[4], a[4], a[5], a[6], a[7], kf[hh][1].x, kf[hh][1].y);
                mma16816(c[5], a[4], a[5], a[6], a[7], kf[hh][1].z, kf[hh][1].w);
                uint32_t w[4];
#pragma unroll
                for (int k = 0; k < 2; k++) {
                    const float rho = c[0][2 * k + 1] * rcp(c[1][2 * k + 1]);
                    const float r = rcp(fmaf(c[0][2 * k + 1], 1e-6f, fmaf(rho, c[1][2 * k], c[0][2 * k]))), rr = r * rho;
                    w[k] = pack2(fmaf(c[4][2 * k], rr, c[2][2 * k] * r), fmaf(c[4][2 * k + 1], rr, c[2][2 * k + 1] * r));
                    w[2 + k] = pack2(fmaf(c[5][2 * k], rr, c[3][2 * k] * r), fmaf(c[5][2 * k + 1], rr, c[3][2 * k + 1] * r));
                }
                st_rlx128(og + hh * 32, tag4(w[0], w[1], w[2], w[3], tag));
            }
        }
        if (warp == 0) STAMP(6);
        float oc[64];
        const int slab = bi_i * 8 + (bi_j >> 2) * 4 + w4;
        const uint8_t* ysrc = (const uint8_t*)scr->y + (size_t)((bi_j & 3) * 32 + wg * 16 + (q >> 1)) * 16384 + slab * 128 + g * 16 + (q & 1) * 8;
        const unsigned* gp = scr->g + (slab * 8 + (g >> 1)) * 8 + (g & 1) * 4;
        uint2 yv[8]; unsigned g0, g1;
        {
            const uint4* osrc = scr->o + (slab * 32 + wg * 16) * 32 + lane;
            uint4 fr[16];
            const unsigned* probe = (const unsigned*)(osrc - lane + ((lane & 3) * 4 + 3) * 32 + 31) + 2;
            {
                unsigned miss = ~0u;
                int n = 0;
#pragma unroll
                for (int s = 0; s < 4; s++) {
#pragma unroll 1
                    while ((miss >> s) & 1) { miss = __ballot_sync(~0u, (ld_rlx(probe) ^ tag) & 1); if (++n > SPIN_LIMIT) break; }
#pragma unroll
                    for (int k = 4 * s; k < 4 * s + 4; k++) fr[k] = ld_rlx128(osrc + k * 32);
                }
            }
            if (warp == 0) STAMP(14);
            mbar_wait(bar + 8 * (wg ? BAR_WO2 : BAR_WO), 0);
            const uint64_t dw = mkdesc(sb + wg * 2 * SLOT, wg ? 32768 : SLOT, 1024);
#pragma unroll
            for (int s = 0; s < 4; s++) {
                int n = 0;
#pragma unroll 1
                while (__builtin_expect(__any_sync(~0u, (bad4(fr[4 * s], tag) | bad4(fr[4 * s + 1], tag) | bad4(fr[4 * s + 2], tag) | bad4(fr[4 * s + 3], tag)) & 1), 0)) {
#pragma unroll
                    for (int k = 4 * s; k < 4 * s + 4; k++) fr[k] = ld_rlx128(osrc + k * 32);
                    if (++n > SPIN_LIMIT) break;
                }
                wg_fence();
#pragma unroll
                for (int hh = 0; hh < 4; hh++) wgmma128_rs(oc, fr[4 * s + hh], dw + 128 * (4 * s + hh), (s | hh) != 0);
                wg_commit();
                if (s == 1) {
                    wg_wait<1>();
#pragma unroll
                    for (int nt = 0; nt < 8; nt++) yv[nt] = ld_rlx64(ysrc + nt * 32768);
                    g0 = ld_rlx(gp); g1 = ld_rlx(gp + 32);
                }
            }
            if (warp == 0) STAMP(7);
            {
                const unsigned* yprobe = scr->yflag + ((bi_j & 3) * 32 + wg * 16 + (lane & 15)) * 8;
                int n = 0;
#pragma unroll 1
                while (true) {
                    uint32_t bad = (g0 ^ tag) | (g1 ^ tag);
#pragma unroll
                    for (int nt = 0; nt < 8; nt++) bad |= yv[nt].x ^ tag;
                    if (!__any_sync(~0u, bad & 1)) break;
#pragma unroll 1
                    while (__any_sync(~0u, (ld_rlx(yprobe) ^ tag) & 1)) { if (++n > SPIN_LIMIT) break; }
#pragma unroll
                    for (int nt = 0; nt < 8; nt++) yv[nt] = ld_rlx64(ysrc + nt * 32768);
                    g0 = ld_rlx(gp); g1 = ld_rlx(gp + 32);
                    if (++n > SPIN_LIMIT) break;
                }
            }
            if (warp == 0) STAMP(28);
        }
        {
            const float ga = bf_hi(g0), gb = bf_hi(g1);
            const float ha = bf_round(1.0f - ga), hb = bf_round(1.0f - gb);
            float yb[32];
#pragma unroll
            for (int nt = 0; nt < 8; nt++) {
                yb[4 * nt] = ha * bf_lo(yv[nt].x); yb[4 * nt + 1] = ha * bf_hi(yv[nt].x);
                yb[4 * nt + 2] = hb * bf_lo(yv[nt].y); yb[4 * nt + 3] = hb * bf_hi(yv[nt].y);
            }
            fence_regs<32>(yb);
            const uint32_t xw = sb + wg * 2 * SLOT + (tid & 127) * 16, xr = sb + (wg ^ 1) * 2 * SLOT + (tid & 127) * 16;
            wg_wait<0>();
            fence_regs<64>(oc);
            bar_named(3 + wg, 128);
#pragma unroll
            for (int r = 0; r < 8; r++)
                sts128(xw + r * 2048, __float_as_uint(oc[32 + 4 * r]), __float_as_uint(oc[33 + 4 * r]), __float_as_uint(oc[34 + 4 * r]), __float_as_uint(oc[35 + 4 * r]));
#pragma unroll
            for (int r = 0; r < 32; r++) yb[r] = fmaf((r & 2) ? gb : ga, oc[r], yb[r]);
            bar_named(1, 256);
            if (warp == 0) STAMP(8);
            uint32_t w[8][2];
#pragma unroll
            for (int nt = 0; nt < 8; nt++) {
                const uint4 p = lds128(xr + nt * 2048);
                w[nt][0] = pack2(fmaf(ga, __uint_as_float(p.x), yb[4 * nt]), fmaf(ga, __uint_as_float(p.y), yb[4 * nt + 1]));
                w[nt][1] = pack2(fmaf(gb, __uint_as_float(p.z), yb[4 * nt + 2]), fmaf(gb, __uint_as_float(p.w), yb[4 * nt + 3]));
            }
            const uint32_t ob = sb + wg * 2 * SLOT + 16384 + w4 * 2048;
#pragma unroll
            for (int nt = 0; nt < 8; nt += 2)
                stsm4(ob + (lane & 15) * 128 + (((nt + shi) ^ (lane & 7)) << 4), w[nt][0], w[nt][1], w[nt + 1][0], w[nt + 1][1]);
            __syncwarp();
            bf16* op = out + (size_t)(slab * 16) * 512 + (bi_j & 3) * 128 + wg * 64 + (lane & 7) * 8;
#pragma unroll
            for (int it = 0; it < 4; it++) {
                const int r = it * 4 + (lane >> 3);
                uint4 v = lds128(ob + r * 128 + (((lane & 7) ^ (r & 7)) << 4));
                *(uint4*)(op + r * 512) = v;
            }
        }
        if (warp == 0) STAMP(10);
    } else if (warp < 12) {
        if (warp == 8) {
            mbar_wait(bar + 8 * BAR_KGA, 0);
            if (lane == 0) load_stage(2);
            STAMP(22);
            mbar_wait(bar + 8 * BAR_KG, 0);
            if (lane == 0) load_stage(3);
            __syncwarp();
            STAMP(17);
        }
        if (warp == 8) {
#pragma unroll 1
            for (int kb = 0; kb < 6; kb++) {
                const int s = kb & 3;
                mbar_wait(bar + 8 * (BAR_EMPTY + s), kb >> 2);
                if (kb == xkb) mbar_wait(bar + 8 * BAR_XT, 0);
                if (lane == 0) {
                    STAMP(48 + kb);
                    if (kb < 4) load_stage(kb + 4);
                    else {
                        mbar_expect(bar + 8 * BAR_WO, 32768);
                        tma2d(sb + s * SLOT, &mwo, (bi_j & 3) * 128 + s * 64, 0, bar + 8 * BAR_WO);
                        if (kb == 5) mbar_arrive(bar + 8 * BAR_SP2);
                    }
                }
                __syncwarp();
            }
        }
        if (st < 8) st_rlx32(scr->yflag + bi * 8 + st, tag ^ 1u);
        mbar_wait(bar + 8 * (BAR_KP + w4), 0);
#pragma unroll
        for (int t = 0; t < 15; t++) {
            const uint4 v = lds128(buf + (t * 32 + lane) * 16);
            kc[4 * (t % 5)] += __uint_as_float(v.x); kc[4 * (t % 5) + 1] += __uint_as_float(v.y); kc[4 * (t % 5) + 2] += __uint_as_float(v.z); kc[4 * (t % 5) + 3] += __uint_as_float(v.w);
        }
        {
            const uint4 v = lds128(buf + 7680);
            kc[20] += __uint_as_float(v.x) + __uint_as_float(v.y) + __uint_as_float(v.z);
            const uint32_t cnt = 1u + (__float_as_uint(kc[20] + kc[19] + kc[0]) == 0xffc12345u);
            if (lane == 0) asm volatile("mbarrier.arrive.shared::cta.b64 _,[%0],%1;" ::"r"(bar + 8 * (BAR_KD + w4)), "r"(cnt) : "memory");
            __syncwarp();
        }
        if (lane == 0) kc[4 * 0 + 0] += ((ch & 1) ? bf_hi(pds) : bf_lo(pds));
        const uint32_t k1024 = __shfl_sync(~0u, pack2(kc[4 * 4 + 0], 0.f), 0);
#pragma unroll
        for (int i = 0; i < 2; i++) {
            const int be = g + 8 * i;
#pragma unroll
            for (int t = 0; t < 2; t++) {
                const uint32_t a = kb_ + (KW_D + 128 * t + 8 * be + 2 * q) * 4;
                const uint32_t w = pack2(kc[4 * t + 2 * i + 1], kc[4 * t + 2 * i]);
                sts32(a + 4, w); sts16(a, w >> 16); sts16(a + 10, w);
            }
            {
                const int p = 256 + 128 * (q >> 1) + 8 * be + 4 * (q & 1);
                const uint32_t a = kb_ + (KW_D + p) * 4;
                const uint32_t w = pack2(kc[4 * 2 + 2 * i + 1], kc[4 * 2 + 2 * i]);
                const uint32_t aa = (w >> 16) | (w & 0xffff0000u);
                if (p != 256) { sts16(a - 4, aa); sts32(a, aa); } else sts16(a, aa);
                sts32(a + 4, aa); sts32(a + 8, w); sts16(a + 14, w);
            }
            {
                const int k = 64 + 16 * q + be;
                const uint32_t w = pack2(kc[4 * 3 + 2 * i], kc[4 * 3 + 2 * i + 1]);
                if (k != 64) sts16(kb_ + (KW_2 + ((k - 1) >> 1) - 24) * 4 + (k & 1) * 2, w);
                else {
                    const uint32_t a = kb_ + (KW_D + 511) * 4, aa = (w << 16) | (w & 0xffffu);
                    sts16(a, w); sts32(a + 4, aa); sts32(a + 8, aa); sts32(a + 12, aa); sts16(a + 18, w);
                }
                sts16(kb_ + (KW_2 + 48 + (k >> 1) - 24) * 4 + ((k & 1) ^ 1) * 2, w >> 16);
            }
#pragma unroll
            for (int b = 0; b < 2; b++) {
                const int k = 64 + 8 * (2 * q + b) + (be >> 1);
                const uint32_t w = pack2(kc[4 * 4 + 2 * i + b], 0.f);
                if (!(be & 1) && k == 64) sts16(kb_ + (KW_2 + 63 - 24) * 4, w);
                else {
                    const uint32_t a = kb_ + (KW_3 + ((be & 1) ? 80 + k : k - 1) - 48) * 4;
                    sts16(a, w);
                    if (!((be & 1) && k == 127)) sts16(a + 6, w);
                }
            }
        }
        if (lane == 0) sts16(kb_ + (KW_3 + 127 - 48) * 4, pack2(kc[4 * 5 + 0], 0.f));
        __syncwarp();
        asm volatile("setmaxnreg.inc.sync.aligned.u32 136;");
        mbar_wait(bar + 8 * BAR_UR, 0);
        mbar_wait(bar + 8 * BAR_DONE, 0);
        if (warp == 8) STAMP(23);
        float y[16][4];
#pragma unroll
        for (int nt = 0; nt < 16; nt++) { y[nt][0] = y[nt][1] = y[nt][2] = y[nt][3] = 0.f; }
        {
            uint32_t Bp[32], A[4][3], An[4][3];
            auto uaddr = [&](int rho) { const int R0 = (lane >> 4) * 64 + (lane & 7) - rho; return ub + (((2 * R0 + ((lane >> 3) & 1)) ^ ((R0 >> 2) & 1)) << 4); };
            const uint32_t kd = kb_ + (KW_D + g - 2 * q) * 4;
#pragma unroll 1
            for (int rho = 1; rho >= 0; rho--) {
                const uint32_t a = uaddr(rho), k = kd + 2048 + rho * 64;
#pragma unroll
                for (int i = 0; i < 8; i++) ldsm4(Bp + 4 * i, a + i * 256);
                const uint32_t a0 = lds32(k), a1 = lds32(k + 32), a2 = lds32(k - 32);
#pragma unroll
                for (int i = 0; i < 12; i++) mma16816(y[i + 4], a0, a1, a2, a0, Bp[4 * (i & 7) + 2 * (i >> 3)], Bp[4 * (i & 7) + 2 * (i >> 3) + 1]);
            }
#pragma unroll
            for (int ga = 0; ga < 4; ga++) { An[ga][0] = lds32(kd + ga * 512); An[ga][1] = lds32(kd + ga * 512 + 32); An[ga][2] = lds32(kd + ga * 512 - 32); }
#pragma unroll 1
            for (int rho = 0; rho < 8; rho++) {
#pragma unroll
                for (int ga = 0; ga < 4; ga++) {
                    const uint32_t a = kd + (rho + 1) * 64 + ga * 512;
                    A[ga][0] = An[ga][0]; A[ga][1] = An[ga][1]; A[ga][2] = An[ga][2];
                    An[ga][0] = lds32(a); An[ga][1] = lds32(a + 32); An[ga][2] = lds32(a - 32);
                }
                const uint32_t an = uaddr(rho + 1);
#pragma unroll
                for (int i = 0; i < 8; i++) {
#pragma unroll
                    for (int ga = 0; ga < 4; ga++) {
                        mma16816(y[i + ga], A[ga][0], A[ga][1], A[ga][2], A[ga][0], Bp[4 * i], Bp[4 * i + 1]);
                        if (i + 8 + ga < 16) mma16816(y[i + 8 + ga], A[ga][0], A[ga][1], A[ga][2], A[ga][0], Bp[4 * i + 2], Bp[4 * i + 3]);
                    }
                    ldsm4(Bp + 4 * i, an + i * 256);
                    __syncwarp();
                }
            }
        }
        if (warp == 8) STAMP(18);
        mbar_wait(bar + 8 * BAR_WR, 0);
#pragma unroll 1
        for (int ph = 0; ph < 2; ph++) {
            uint32_t B[5][2];
            const uint32_t ka = kb_ + (KW_2 + ph * 48 + 8 + g - q) * 4;
#pragma unroll
            for (int dd = 0; dd < 5; dd++) { B[dd][0] = lds32(ka + dd * 32); B[dd][1] = lds32(ka + dd * 32 - 16); }
            const uint32_t wa = buf + ph * W3_OFF + ((lane & 7) + ((lane >> 3) & 1) + (lane >> 4) * 8) * 16;
#pragma unroll
            for (int s = 0; s < 12; s++) {
                uint32_t A[4];
                ldsm4t(A, wa + s * 256);
#pragma unroll
                for (int dd = 0; dd < 5; dd++)
                    if (s + 4 + dd < 16) mma16816(y[s + 4 + dd], A[0], A[1], A[2], A[3], B[dd][0], B[dd][1]);
            }
        }
        {
            const int ap = (lane & 7) + (lane >> 4) * 8;
            const uint32_t loff = ((2 * ap + ((lane >> 3) & 1)) ^ ((ap >> 2) & 1)) << 4;
#pragma unroll 1
            for (int ph = 0; ph < 2; ph++) {
                uint32_t B[8][2];
                const uint32_t wb = (ph ? spare : buf + W9_OFF) + loff;
                const uint32_t ka = kb_ + (KW_3 + ph * 80 + 16 + g - 2 * q) * 4;
#pragma unroll
                for (int dd = 0; dd < 8; dd++) { B[dd][0] = lds32(ka + dd * 32); B[dd][1] = lds32(ka + dd * 32 - 32); }
#pragma unroll
                for (int s = 0; s < 4; s++) {
                    uint32_t A[4];
                    ldsm4t(A, wb + s * 512);
#pragma unroll
                    for (int dd = 0; dd < 8; dd++)
                        if (8 + 2 * s + dd < 16) mma16816(y[8 + 2 * s + dd], A[0], A[1], A[2], A[3], B[dd][0], B[dd][1]);
                }
            }
            const uint32_t idw = (g == 2 * q) ? k1024 : ((g == 2 * q + 1) ? (k1024 << 16) : 0u);
#pragma unroll
            for (int s = 0; s < 4; s++) {
                uint32_t A[4];
                ldsm4t(A, spare + 2048 + loff + s * 512);
                mma16816(y[8 + 2 * s], A[0], A[1], A[2], A[3], idw, 0u);
                mma16816(y[9 + 2 * s], A[0], A[1], A[2], A[3], 0u, idw);
            }
        }
        __syncwarp();
        if (warp == 8) STAMP(19);
#pragma unroll
        for (int nt = 0; nt < 16; nt++)
#pragma unroll
            for (int b = 0; b < 2; b++) sts32(buf + ((8 * nt + 2 * q + b) * 8 + g) * 4, pack2(y[nt][b], y[nt][2 + b]));
        bar_named(2, 128);
        uint4* yp = scr->y + bi * 1024 + st;
#pragma unroll
        for (int v = 0; v < 8; v++) {
            const uint32_t a = sb + OFF_BUF + (st + 128 * v) * 4;
            const uint32_t w0 = lds32(a), w1 = lds32(a + BUF_STRIDE), w2 = lds32(a + 2 * BUF_STRIDE), w3 = lds32(a + 3 * BUF_STRIDE);
            st_rlx128(yp + v * 128, tag4(__byte_perm(w0, w1, 0x5410), __byte_perm(w0, w1, 0x7632), __byte_perm(w2, w3, 0x5410), __byte_perm(w2, w3, 0x7632), tag));
        }
        if (st < 8) st_rlx32(scr->yflag + bi * 8 + st, tag);
        if (warp == 8) STAMP(20);
    } else {
        const int qq = (bi_i & 2) + ((lane >> 1) & 1);
        uint2* kvf_h = (uint2*)(scr->kvf + (bi_j * 4 + (bi_i >> 2)) * 68);
        auto windows = [&](int rhi, int rlo) {
#pragma unroll 1
            for (int rho = rhi; rho >= rlo; rho--) {
                const int ci = lane + 32 * rho;
                uint4 e4[4];
#pragma unroll
                for (int v = 0; v < 4; v++) { const int cc = ci - 3 + v; e4[v] = lds128(ub + ((cc ^ ((cc >> 3) & 1)) << 4)); }
                float S[29];
                const uint32_t* ew = (const uint32_t*)e4;
                S[3] = 0.f;
#pragma unroll
                for (int k = 4; k <= 28; k++) S[k] = S[k - 1] + ((k & 1) ? bf_hi(ew[k >> 1]) : bf_lo(ew[k >> 1]));
                auto win = [&](int lo, int hi, uint32_t a) {
                    sts128(a, pack2(S[hi] - S[lo - 1], S[hi + 1] - S[lo]), pack2(S[hi + 2] - S[lo + 1], S[hi + 3] - S[lo + 2]),
                           pack2(S[hi + 4] - S[lo + 3], S[hi + 5] - S[lo + 4]), pack2(S[hi + 6] - S[lo + 5], S[hi + 7] - S[lo + 6]));
                };
                win(14, 18, buf + W5_OFF + 16 + ci * 16); win(19, 21, buf + W3_OFF + 16 + ci * 16);
                if (rho < 4) {
                    const uint32_t sw = (ci ^ ((ci >> 3) & 1)) << 4;
                    win(4, 12, buf + W9_OFF + sw); win(13, 19, spare + sw); win(20, 21, spare + 2048 + sw);
                }
            }
        };
        {
            mbar_wait(bar + 8 * (BAR_FULL + xkb), 0);
#pragma unroll 1
            for (int hf = 0; hf < 2; hf++) {
                const int r = w4 * 32 + hf * 16 + (lane & 15);
                uint32_t* xt = (uint32_t*)scr->xt + ((xkb + rot) * 16 + (g >> 2)) * 4096 + (bi_i * 16 + w4 * 4 + hf * 2) * 16 + (g & 3) * 4 + q;
#pragma unroll
                for (int cb = 0; cb < 8; cb += 2) {
                    uint32_t v[4];
                    ldsm4t(v, sb + xkb * SLOT + r * 128 + (((cb + (lane >> 4)) ^ (r & 7)) << 4));
                    xt[cb * 8192] = v[0]; xt[cb * 8192 + 16] = v[1]; xt[cb * 8192 + 8192] = v[2]; xt[cb * 8192 + 8192 + 16] = v[3];
                }
            }
            __syncwarp();
            if (lane == 0) mbar_arrive(bar + 8 * BAR_XT);
            if (warp == 12) STAMP(26);
            handoff(2);
            asm volatile("setmaxnreg.dec.sync.aligned.u32 56;");
            if (lane == 0) asm volatile("red.release.gpu.global.add.u32 [%0],2;" ::"l"(scr->xcnt + (xkb + rot) * 32) : "memory");
            __syncwarp();
            if (warp == 12) STAMP(27);
            {
                const uint32_t old = tag ^ 1u;
                const uint4 z4 = make_uint4(old, 0, old, 0);
#pragma unroll
                for (int v = 0; v < 5; v++) if (v < 4 || st < 32) st_rlx128(scr->kvp + bi * 544 + v * 128 + st, z4);
                if (st < 16) st_rlx128(scr->o + ((bi_i * 8 + (st >> 1)) * 32 + bi_j * 4 + 3) * 32 + 30 + (st & 1), z4);
                if (lane < 8) st_rlx64(kvf_h + ((bi_i & 3) * 8 + w4 * 2 + (lane & 1)) * 4 + (lane >> 1), old, 0);
                if (st < 4 && !(bi_i & 1)) st_rlx64(kvf_h + (64 + qq) * 2 + (lane & 1), old, 0);
                if ((lane & 7) < 2) st_rlx64(scr->g + (bi_i * 64 + bi_j * 8 + w4 * 2) * 8 + (lane >> 3) * 4 + (lane & 1) * 2, old, old);
                __syncwarp();
                if (lane == 0) mbar_arrive(bar + 8 * BAR_PREP);
            }
            int n = 0;
#pragma unroll 1
            while (__any_sync(~0u, (int)(ld_acq(scr->xcnt + bi_j * 32) - (epoch1 << 7)) < 0)) { if (++n > SPIN_LIMIT) break; }
            if (warp == 12) STAMP(15);
            uint4 ur[8];
#pragma unroll
            for (int v = 0; v < 8; v++) ur[v] = __ldcg(scr->xt + bi * 1024 + st + 128 * v);
            mbar_wait(bar + 8 * BAR_KG, 0);
            if (lane < 16) sts128(ub - 256 + lane * 16, 0, 0, 0, 0);
#pragma unroll
            for (int v = 0; v < 8; v++) {
                const int ci = (st >> 2) + 32 * v;
                sts128(sb + OFF_U + (st & 3) * U_STRIDE + 256 + ((ci ^ ((ci >> 3) & 1)) << 4), ur[v].x, ur[v].y, ur[v].z, ur[v].w);
            }
            __syncwarp();
            if (lane == 0) mbar_arrive(bar + 8 * BAR_UR);
            mbar_wait(bar + 8 * BAR_UR, 0);
            if (warp == 12) STAMP(16);
            mbar_wait(bar + 8 * (BAR_KD + w4), 0);
            if (lane < 2) sts128(buf + lane * W3_OFF, 0, 0, 0, 0);
            windows(5, 4);
        }
        mbar_wait(bar + 8 * BAR_SP2, 0);
        windows(3, 0);
        __syncwarp();
        if (lane == 0) mbar_arrive(bar + 8 * BAR_WR);
        if (warp == 12) STAMP(24);
        {
            const bool zw = st < 32 && !(bi_i & 1);
            const uint4* src = scr->kvp + bi_j * (16 * 544) + (bi_i >> 2) * 136;
            const uint4* zsrc = src + (lane >> 2) * (2 * 544) + 128 + (lane & 1) * 4 + qq;
            src += (lane >> 3) * (4 * 544) + ((lane >> 1) & 3) * 32 + (bi_i & 3) * 8 + w4 * 2 + (lane & 1);
            mbar_wait(bar + 8 * BAR_PUB, 0);
            if (warp == 12) STAMP(12);
            uint4 v[6];
#pragma unroll
            for (int k = 0; k < 6; k++) v[k] = make_uint4(tag ^ 1u, 0, 0, 0);
            int n = 0;
#pragma unroll 1
            while (true) {
#pragma unroll
                for (int k = 0; k < 6; k++) if ((bad4(v[k], tag) & 1) && (k < 4 || zw)) v[k] = ld_rlx128(k < 4 ? src + k * 544 : zsrc + (k - 4) * 544);
                if (!__any_sync(~0u, (bad4(v[0], tag) | bad4(v[1], tag) | bad4(v[2], tag) | bad4(v[3], tag) | (zw ? bad4(v[4], tag) | bad4(v[5], tag) : 0u)) & 1)) break;
                if (++n > SPIN_LIMIT) break;
            }
            if (warp == 12) STAMP(30);
            float f[8];
            const float* vf = (const float*)v;
#pragma unroll
            for (int r = 0; r < 4; r++) {
                f[r] = (vf[r] + vf[4 + r]) + (vf[8 + r] + vf[12 + r]);
                f[4 + r] = vf[16 + r] + vf[20 + r];
                f[4 + r] += __shfl_xor_sync(~0u, f[4 + r], 4);
            }
#pragma unroll
            for (int o = 8; o <= 16; o <<= 1)
#pragma unroll
                for (int r = 0; r < 8; r++) f[r] += __shfl_xor_sync(~0u, f[r], o);
            if (lane < 8) st_rlx64(kvf_h + ((bi_i & 3) * 8 + w4 * 2 + (lane & 1)) * 4 + (lane >> 1), tagw(pack2(f[0], f[1]), tag), pack2(f[2], f[3]));
            if (zw && lane < 4) st_rlx64(kvf_h + (64 + qq) * 2 + (lane & 1), tagw(pack2(f[4], f[5]), tag), pack2(f[6], f[7]));
        }
        if (warp == 12) STAMP(13);
        {
            const uint4* kp = scr->kvf + bi_j * 272 + st;
            uint4 v0 = make_uint4(tag ^ 1u, 0, 0, 0), v1 = v0, v2 = make_uint4(st < 16 ? tag ^ 1u : tag, 0, tag, 0);
            int n = 0;
#pragma unroll 1
            while (true) {
                if (bad4(v0, tag) & 1) v0 = ld_rlx128(kp);
                if (bad4(v1, tag) & 1) v1 = ld_rlx128(kp + 128);
                if (bad4(v2, tag) & 1) v2 = ld_rlx128(kp + 256);
                if (!__any_sync(~0u, (bad4(v0, tag) | bad4(v1, tag) | bad4(v2, tag)) & 1)) break;
                if (++n > SPIN_LIMIT) break;
            }
            sts128(sb + OFF_KVF + st * 16, v0.x, v0.y, v0.z, v0.w);
            sts128(sb + OFF_KVF + 2048 + st * 16, v1.x, v1.y, v1.z, v1.w);
            if (st < 16) sts128(sb + OFF_KVF + 4096 + st * 16, v2.x, v2.y, v2.z, v2.w);
            __syncwarp();
            if (lane == 0) mbar_arrive(bar + 8 * BAR_KVF);
        }
        if (warp == 13) {
            mbar_wait(bar + 8 * BAR_KVF, 0);
            if (lane == 0) {
                mbar_expect(bar + 8 * BAR_WO2, 65536);
                tma2d(sb + OFF_P, &mwo, (bi_j & 3) * 128 + 64, 256, bar + 8 * BAR_WO2);
                tma2d(sb + OFF_V, &mwo, (bi_j & 3) * 128, 256, bar + 8 * BAR_WO2);
            }
        }
        if (warp == 12) STAMP(25);
        {
            const uint4* xr = (const uint4*)(x + (size_t)(bi_i * 128 + bi_j * 16 + w4 * 4 + (lane >> 3)) * 512) + (lane & 7);
            uint4 xv[8];
#pragma unroll
            for (int c = 0; c < 8; c++) xv[c] = __ldg(xr + c * 8);
            float gs0 = 0.f, gs1 = 0.f;
            mbar_wait(bar + 8 * BAR_WPHI, 0);
#pragma unroll
            for (int c = 0; c < 8; c++) {
                const uint4 gw = lds128(sb + OFF_GW + c * 128 + (lane & 7) * 16);
                const uint32_t p0 = hmul2(xv[c].x, gw.x), p1 = hmul2(xv[c].y, gw.y), p2 = hmul2(xv[c].z, gw.z), p3 = hmul2(xv[c].w, gw.w);
                gs0 += (bf_lo(p0) + bf_lo(p1)) + (bf_lo(p2) + bf_lo(p3));
                gs1 += (bf_hi(p0) + bf_hi(p1)) + (bf_hi(p2) + bf_hi(p3));
            }
            float gs = gs0 + gs1;
#pragma unroll
            for (int o = 1; o < 8; o <<= 1) gs += __shfl_xor_sync(~0u, gs, o);
            const uint32_t gv = __float_as_uint(bf_round(rcp(1.0f + ex2(-1.4426950408889634f * bf_round(gs))))) | tag;
            if ((lane & 7) < 2) st_rlx64(scr->g + (bi_i * 64 + bi_j * 8 + w4 * 2) * 8 + (lane >> 3) * 4 + (lane & 1) * 2, gv, gv);
        }
    }
    __syncwarp();
    if (lane == 0) {
        unsigned old;
        asm volatile("atom.acq_rel.cta.shared.add.u32 %0,[%1],1;" : "=r"(old) : "r"(bar + OFF_CNT) : "memory");
        if (old == 15) {
            atomicAdd(scr->done, 1u);
        }
    }
}

typedef CUresult (*EncFn)(CUtensorMap*, CUtensorMapDataType, cuuint32_t, void*, const cuuint64_t*, const cuuint64_t*, const cuuint32_t*,
                          const cuuint32_t*, CUtensorMapInterleave, CUtensorMapSwizzle, CUtensorMapL2promotion, CUtensorMapFloatOOBfill);

extern "C" void kernel_launch(void* const* d_in, const int* in_sizes, int n_in, void* d_out, int out_size) {
    static EncFn enc = nullptr;
    static Scratch* scr = nullptr;
    if (!enc) {
        cudaGetSymbolAddress((void**)&scr, g_scr);
        cudaDriverEntryPointQueryResult qr;
        cudaGetDriverEntryPoint("cuTensorMapEncodeTiled", (void**)&enc, cudaEnableDefault, &qr);
        cudaFuncSetAttribute(fused_kernel, cudaFuncAttributeMaxDynamicSharedMemorySize, SMEM_BYTES);
    }
    CUtensorMap mx, mw, mwo;
    const cuuint32_t es[3] = {1, 1, 1};
    {
        cuuint64_t d[2] = {512, 2048}, s[1] = {1024}; cuuint32_t b[2] = {64, 128};
        enc(&mx, CU_TENSOR_MAP_DATA_TYPE_BFLOAT16, 2, d_in[0], d, s, b, es, CU_TENSOR_MAP_INTERLEAVE_NONE, CU_TENSOR_MAP_SWIZZLE_128B,
            CU_TENSOR_MAP_L2_PROMOTION_L2_128B, CU_TENSOR_MAP_FLOAT_OOB_FILL_NONE);
    }
    {
        cuuint64_t d[3] = {512, 512, 3}, s[2] = {3072, 1024}; cuuint32_t b[3] = {64, 64, 3};
        enc(&mw, CU_TENSOR_MAP_DATA_TYPE_BFLOAT16, 3, d_in[1], d, s, b, es, CU_TENSOR_MAP_INTERLEAVE_NONE, CU_TENSOR_MAP_SWIZZLE_128B,
            CU_TENSOR_MAP_L2_PROMOTION_L2_128B, CU_TENSOR_MAP_FLOAT_OOB_FILL_NONE);
    }
    {
        cuuint64_t d[2] = {512, 512}, s[1] = {1024}; cuuint32_t b[2] = {64, 256};
        enc(&mwo, CU_TENSOR_MAP_DATA_TYPE_BFLOAT16, 2, d_in[3], d, s, b, es, CU_TENSOR_MAP_INTERLEAVE_NONE, CU_TENSOR_MAP_SWIZZLE_128B,
            CU_TENSOR_MAP_L2_PROMOTION_L2_128B, CU_TENSOR_MAP_FLOAT_OOB_FILL_NONE);
    }
    fused_kernel<<<128, 512, SMEM_BYTES, cudaStreamPerThread>>>(
        scr, (const bf16*)d_in[5], (const bf16*)d_in[6], (const bf16*)d_in[7], (const bf16*)d_in[8], (const bf16*)d_in[9],
        (const bf16*)d_in[10], (const bf16*)d_in[2], (const bf16*)d_in[11], (bf16*)d_out, (const bf16*)d_in[0], mx, mw, mwo);
}
```

```cpp
#include <cuda_runtime.h>
#include <cuda.h>
#include <cuda_bf16.h>
#include <stdint.h>

typedef __nv_bfloat16 bf16;

struct Scratch {
    uint4 xt[128 * 1024];
    uint4 o[16 * 8 * 32 * 32];
    uint4 y[128 * 1024];
    uint4 kvp[8 * 16 * 544];
    uint4 kvf[8 * 4 * 68];
    unsigned g[1024 * 8];
    unsigned xcnt[8 * 32];
    unsigned done[32];
};
__device__ Scratch g_scr;
#define STAMP(n)

constexpr int SLOT = 40960;
constexpr int OFF_SP0 = 32768, OFF_SP1 = SLOT + 32768;
constexpr int OFF_P = 2 * SLOT, OFF_V = OFF_P + 32768;
constexpr int OFF_KVF = OFF_V + 32768;
constexpr int KT_BYTES = 3264, KW_D = 16, KW_2 = 560, KW_3 = 656;
constexpr int OFF_U = 4 * SLOT, U_STRIDE = 4096 + 256 + 32;
constexpr int OFF_BUF = OFF_U + 4 * U_STRIDE, BUF_STRIDE = 8320;
constexpr int OFF_K = OFF_BUF + 4 * BUF_STRIDE;
constexpr int OFF_WPHI = OFF_K + 4 * KT_BYTES;
constexpr int OFF_GW = OFF_WPHI + 2048;
constexpr int OFF_BAR = OFF_GW + 1024;
constexpr int SMEM_BYTES = OFF_BAR + 320 + 256;
static_assert(SMEM_BYTES <= 232448 && OFF_BUF % 128 == 0, "smem");
constexpr int W5_OFF = 0, W3_OFF = 3088, W9_OFF = 6176;
constexpr int BAR_FULL = 0, BAR_EMPTY = 4, BAR_WPHI = 8, BAR_WO = 9, BAR_WO2 = 10, BAR_XT = 11, BAR_DONE = 12, BAR_KG = 13, BAR_SP = 14,
              BAR_PUB = 15, BAR_KVF = 16, BAR_UR = 17, BAR_WR = 18, BAR_PREP = 19, BAR_KGA = 20, BAR_SP2 = 21, BAR_KS = 22, BAR_KP = 26, BAR_KD = 30, OFF_CNT = 272;
constexpr int SPIN_LIMIT = 1 << 17;

__device__ __forceinline__ uint32_t s2u(const void* p) { return (uint32_t)__cvta_generic_to_shared(p); }
__device__ __forceinline__ void mbar_init(uint32_t b, int c) { asm volatile("mbarrier.init.shared::cta.b64 [%0],%1;" ::"r"(b), "r"(c) : "memory"); }
__device__ __forceinline__ void mbar_expect(uint32_t b, int bytes) { asm volatile("mbarrier.arrive.expect_tx.shared::cta.b64 _,[%0],%1;" ::"r"(b), "r"(bytes) : "memory"); }
__device__ __forceinline__ void mbar_arrive(uint32_t b) { asm volatile("mbarrier.arrive.shared::cta.b64 _,[%0];" ::"r"(b) : "memory"); }
__device__ __forceinline__ void mbar_wait(uint32_t b, int ph) {
    asm volatile("{\n.reg .pred p;\n.reg .u32 n;\nmov.u32 n,0;\nLW_%=:\nmbarrier.try_wait.parity.shared::cta.b64 p,[%0],%1;\n@p bra LD_%=;\n"
                 "add.u32 n,n,1;\nsetp.lt.u32 p,n,16384;\n@p bra LW_%=;\nLD_%=:\n}" ::"r"(b), "r"(ph) : "memory");
}
__device__ __forceinline__ void tma2d(uint32_t dst, const CUtensorMap* m, int c0, int c1, uint32_t bar) {
    asm volatile("cp.async.bulk.tensor.2d.shared::cluster.global.mbarrier::complete_tx::bytes [%0],[%1,{%3,%4}],[%2];" ::"r"(dst), "l"(m), "r"(bar), "r"(c0), "r"(c1) : "memory");
}
__device__ __forceinline__ void tma3d(uint32_t dst, const CUtensorMap* m, int c0, int c1, int c2, uint32_t bar) {
    asm volatile("cp.async.bulk.tensor.3d.shared::cluster.global.mbarrier::complete_tx::bytes [%0],[%1,{%3,%4,%5}],[%2];" ::"r"(dst), "l"(m), "r"(bar), "r"(c0), "r"(c1), "r"(c2) : "memory");
}
__device__ __forceinline__ void bulk_g2s(uint32_t dst, const void* src, int bytes, uint32_t bar) {
    asm volatile("cp.async.bulk.shared::cluster.global.mbarrier::complete_tx::bytes [%0],[%1],%2,[%3];" ::"r"(dst), "l"(src), "r"(bytes), "r"(bar) : "memory");
}
__device__ __forceinline__ uint64_t mkdesc(uint32_t addr, uint32_t lbo, uint32_t sbo) {
    return (uint64_t)((addr & 0x3FFFF) >> 4) | ((uint64_t)(lbo >> 4) << 16) | ((uint64_t)(sbo >> 4) << 32) | ((uint64_t)1 << 62);
}
__device__ __forceinline__ void wg_fence() { asm volatile("wgmma.fence.sync.aligned;" ::: "memory"); }
__device__ __forceinline__ void wg_commit() { asm volatile("wgmma.commit_group.sync.aligned;" ::: "memory"); }
template <int N> __device__ __forceinline__ void wg_wait() { asm volatile("wgmma.wait_group.sync.aligned %0;" ::"n"(N) : "memory"); }
template <int N> __device__ __forceinline__ void fence_regs(float* d) {
#pragma unroll
    for (int i = 0; i < N; i++) asm volatile("" : "+f"(d[i])::"memory");
}
#define R8(d, o) "+f"(d[o]), "+f"(d[o + 1]), "+f"(d[o + 2]), "+f"(d[o + 3]), "+f"(d[o + 4]), "+f"(d[o + 5]), "+f"(d[o + 6]), "+f"(d[o + 7])
__device__ __forceinline__ void wgmma192(float* d, uint64_t da, uint64_t db, int sc) {
    asm volatile("{.reg .pred p; setp.ne.b32 p,%98,0; wgmma.mma_async.sync.aligned.m64n192k16.f32.bf16.bf16 {"
                 "%0,%1,%2,%3,%4,%5,%6,%7,%8,%9,%10,%11,%12,%13,%14,%15,%16,%17,%18,%19,%20,%21,%22,%23,%24,%25,%26,%27,%28,%29,%30,%31,"
                 "%32,%33,%34,%35,%36,%37,%38,%39,%40,%41,%42,%43,%44,%45,%46,%47,%48,%49,%50,%51,%52,%53,%54,%55,%56,%57,%58,%59,%60,%61,%62,%63,"
                 "%64,%65,%66,%67,%68,%69,%70,%71,%72,%73,%74,%75,%76,%77,%78,%79,%80,%81,%82,%83,%84,%85,%86,%87,%88,%89,%90,%91,%92,%93,%94,%95},"
                 "%96,%97,p,1,1,0,1;}"
                 : R8(d, 0), R8(d, 8), R8(d, 16), R8(d, 24), R8(d, 32), R8(d, 40), R8(d, 48), R8(d, 56), R8(d, 64), R8(d, 72), R8(d, 80), R8(d, 88)
                 : "l"(da), "l"(db), "r"(sc));
}
__device__ __forceinline__ void wgmma64_tt(float* d, uint64_t da, uint64_t db, int sc) {
    asm volatile("{.reg .pred p; setp.ne.b32 p,%34,0; wgmma.mma_async.sync.aligned.m64n64k16.f32.bf16.bf16 {"
                 "%0,%1,%2,%3,%4,%5,%6,%7,%8,%9,%10,%11,%12,%13,%14,%15,%16,%17,%18,%19,%20,%21,%22,%23,%24,%25,%26,%27,%28,%29,%30,%31},"
                 "%32,%33,p,1,1,1,1;}"
                 : R8(d, 0), R8(d, 8), R8(d, 16), R8(d, 24)
                 : "l"(da), "l"(db), "r"(sc));
}
__device__ __forceinline__ void wgmma128_rs(float* d, const uint4& a, uint64_t db, int sc) {
    asm volatile("{.reg .pred p; setp.ne.b32 p,%69,0; wgmma.mma_async.sync.aligned.m64n128k16.f32.bf16.bf16 {"
                 "%0,%1,%2,%3,%4,%5,%6,%7,%8,%9,%10,%11,%12,%13,%14,%15,%16,%17,%18,%19,%20,%21,%22,%23,%24,%25,%26,%27,%28,%29,%30,%31,"
                 "%32,%33,%34,%35,%36,%37,%38,%39,%40,%41,%42,%43,%44,%45,%46,%47,%48,%49,%50,%51,%52,%53,%54,%55,%56,%57,%58,%59,%60,%61,%62,%63},"
                 "{%64,%65,%66,%67},%68,p,1,1,1;}"
                 : R8(d, 0), R8(d, 8), R8(d, 16), R8(d, 24), R8(d, 32), R8(d, 40), R8(d, 48), R8(d, 56)
                 : "r"(a.x), "r"(a.y), "r"(a.z), "r"(a.w), "l"(db), "r"(sc));
}
__device__ __forceinline__ void mma16816(float* c, uint32_t a0, uint32_t a1, uint32_t a2, uint32_t a3, uint32_t b0, uint32_t b1) {
    asm("mma.sync.aligned.m16n8k16.row.col.f32.bf16.bf16.f32 {%0,%1,%2,%3},{%4,%5,%6,%7},{%8,%9},{%0,%1,%2,%3};"
        : "+f"(c[0]), "+f"(c[1]), "+f"(c[2]), "+f"(c[3]) : "r"(a0), "r"(a1), "r"(a2), "r"(a3), "r"(b0), "r"(b1));
}
__device__ __forceinline__ void ldsm4(uint32_t* r, uint32_t a) {
    asm volatile("ldmatrix.sync.aligned.m8n8.x4.shared.b16 {%0,%1,%2,%3},[%4];" : "=r"(r[0]), "=r"(r[1]), "=r"(r[2]), "=r"(r[3]) : "r"(a) : "memory");
}
__device__ __forceinline__ void ldsm4t(uint32_t* r, uint32_t a) {
    asm volatile("ldmatrix.sync.aligned.m8n8.x4.trans.shared.b16 {%0,%1,%2,%3},[%4];" : "=r"(r[0]), "=r"(r[1]), "=r"(r[2]), "=r"(r[3]) : "r"(a) : "memory");
}
__device__ __forceinline__ void stsm4(uint32_t a, uint32_t r0, uint32_t r1, uint32_t r2, uint32_t r3) {
    asm volatile("stmatrix.sync.aligned.m8n8.x4.shared.b16 [%0],{%1,%2,%3,%4};" ::"r"(a), "r"(r0), "r"(r1), "r"(r2), "r"(r3) : "memory");
}
__device__ __forceinline__ uint32_t lds32(uint32_t a) { uint32_t v; asm volatile("ld.shared.b32 %0,[%1];" : "=r"(v) : "r"(a) : "memory"); return v; }
__device__ __forceinline__ uint4 lds128(uint32_t a) { uint4 v; asm volatile("ld.shared.v4.b32 {%0,%1,%2,%3},[%4];" : "=r"(v.x), "=r"(v.y), "=r"(v.z), "=r"(v.w) : "r"(a) : "memory"); return v; }
__device__ __forceinline__ void sts16(uint32_t a, uint32_t v) { asm volatile("st.shared.b16 [%0],%1;" ::"r"(a), "h"((unsigned short)v) : "memory"); }
__device__ __forceinline__ void sts32(uint32_t a, uint32_t v) { asm volatile("st.shared.b32 [%0],%1;" ::"r"(a), "r"(v) : "memory"); }
__device__ __forceinline__ void sts64(uint32_t a, uint32_t x, uint32_t y) { asm volatile("st.shared.v2.b32 [%0],{%1,%2};" ::"r"(a), "r"(x), "r"(y) : "memory"); }
__device__ __forceinline__ void sts128(uint32_t a, uint32_t x, uint32_t y, uint32_t z, uint32_t w) { asm volatile("st.shared.v4.b32 [%0],{%1,%2,%3,%4};" ::"r"(a), "r"(x), "r"(y), "r"(z), "r"(w) : "memory"); }
__device__ __forceinline__ uint32_t pack2(float lo, float hi) { uint32_t d; asm("cvt.rn.bf16x2.f32 %0,%1,%2;" : "=r"(d) : "f"(hi), "f"(lo)); return d; }
__device__ __forceinline__ float bf_lo(uint32_t v) { return __uint_as_float(v << 16); }
__device__ __forceinline__ float bf_hi(uint32_t v) { return __uint_as_float(v & 0xffff0000u); }
__device__ __forceinline__ float bf_round(float v) { return bf_lo(pack2(v, 0.f)); }
__device__ __forceinline__ uint32_t hmax2(uint32_t a, uint32_t b) { uint32_t d; asm("max.bf16x2 %0,%1,%2;" : "=r"(d) : "r"(a), "r"(b)); return d; }
__device__ __forceinline__ uint32_t hmin2(uint32_t a, uint32_t b) { uint32_t d; asm("min.bf16x2 %0,%1,%2;" : "=r"(d) : "r"(a), "r"(b)); return d; }
__device__ __forceinline__ uint32_t hmul2(uint32_t a, uint32_t b) { uint32_t d; asm("mul.rn.bf16x2 %0,%1,%2;" : "=r"(d) : "r"(a), "r"(b)); return d; }
__device__ __forceinline__ float ex2(float x) { float y; asm("ex2.approx.ftz.f32 %0,%1;" : "=f"(y) : "f"(x)); return y; }
__device__ __forceinline__ float rcp(float x) { float y; asm("rcp.approx.ftz.f32 %0,%1;" : "=f"(y) : "f"(x)); return y; }
__device__ __forceinline__ uint32_t ld_nc(const uint32_t* p) { uint32_t v; asm volatile("ld.global.nc.b32 %0,[%1];" : "=r"(v) : "l"(p)); return v; }
__device__ __forceinline__ uint2 ld_nc64(const uint2* p) { uint2 v; asm volatile("ld.global.nc.v2.b32 {%0,%1},[%2];" : "=r"(v.x), "=r"(v.y) : "l"(p)); return v; }
__device__ __forceinline__ unsigned ld_acq(const unsigned* p) { unsigned v; asm volatile("ld.acquire.gpu.global.u32 %0,[%1];" : "=r"(v) : "l"(p) : "memory"); return v; }
__device__ __forceinline__ unsigned ld_rlx(const unsigned* p) { unsigned v; asm volatile("ld.relaxed.gpu.global.u32 %0,[%1];" : "=r"(v) : "l"(p) : "memory"); return v; }
__device__ __forceinline__ uint2 ld_rlx64(const void* p) { uint2 v; asm volatile("{.reg .b64 t; ld.relaxed.gpu.global.b64 t,[%2]; mov.b64 {%0,%1},t;}" : "=r"(v.x), "=r"(v.y) : "l"(p) : "memory"); return v; }
__device__ __forceinline__ uint4 ld_rlx128(const void* p) {
    uint4 v;
    asm volatile("{.reg .b64 t,u; ld.relaxed.gpu.global.v2.b64 {t,u},[%4]; mov.b64 {%0,%1},t; mov.b64 {%2,%3},u;}" : "=r"(v.x), "=r"(v.y), "=r"(v.z), "=r"(v.w) : "l"(p) : "memory");
    return v;
}
__device__ __forceinline__ void st_rlx32(void* p, uint32_t x) { asm volatile("st.relaxed.gpu.global.u32 [%0],%1;" ::"l"(p), "r"(x) : "memory"); }
__device__ __forceinline__ void st_rlx64(void* p, uint32_t x, uint32_t y) { asm volatile("{.reg .b64 t; mov.b64 t,{%1,%2}; st.relaxed.gpu.global.b64 [%0],t;}" ::"l"(p), "r"(x), "r"(y) : "memory"); }
__device__ __forceinline__ void st_rlx128(void* p, uint4 v) {
    asm volatile("{.reg .b64 t,u; mov.b64 t,{%1,%2}; mov.b64 u,{%3,%4}; st.relaxed.gpu.global.v2.b64 [%0],{t,u};}" ::"l"(p), "r"(v.x), "r"(v.y), "r"(v.z), "r"(v.w) : "memory");
}
__device__ __forceinline__ uint32_t tagw(uint32_t w, uint32_t tag) { return (w & ~1u) | tag; }
__device__ __forceinline__ uint4 tag4(uint32_t x, uint32_t y, uint32_t z, uint32_t w, uint32_t tag) { return make_uint4(tagw(x, tag), y, tagw(z, tag), w); }
__device__ __forceinline__ uint32_t bad4(const uint4& v, uint32_t tag) { return (v.x ^ tag) | (v.z ^ tag); }
__device__ __forceinline__ void bar_named(int id, int n) { asm volatile("bar.sync %0,%1;" ::"r"(id), "r"(n) : "memory"); }

struct cf { float re, im; };
__device__ __forceinline__ cf cmul(cf a, cf b) { cf r; r.re = a.re * b.re - a.im * b.im; r.im = a.re * b.im + a.im * b.re; return r; }
__device__ __forceinline__ cf cexp_p(float arl, float ait, float p) {
    float mag = ex2(arl * p);
    float t = ait * p;
    const float big = 12582912.f;
    t = (t - ((t + big) - big)) * 6.283185307179586f;
    cf r; r.re = mag * __cosf(t); r.im = mag * __sinf(t);
    return r;
}

__device__ __forceinline__ void hedgehog4(const uint32_t* a, uint32_t wphi_addr, uint32_t (*out)[8]) {
    float p[4][2][4], mx[4][2];
#pragma unroll
    for (int h = 0; h < 4; h++) {
        uint32_t b[4];
        ldsm4t(b, wphi_addr + h * 512);
        float c0[4] = {0.f, 0.f, 0.f, 0.f}, c1[4] = {0.f, 0.f, 0.f, 0.f};
        mma16816(c0, a[4 * h], a[4 * h + 1], a[4 * h + 2], a[4 * h + 3], b[0], b[1]);
        mma16816(c1, a[4 * h], a[4 * h + 1], a[4 * h + 2], a[4 * h + 3], b[2], b[3]);
#pragma unroll
        for (int k = 0; k < 2; k++) {
            p[h][k][0] = c0[2 * k]; p[h][k][1] = c0[2 * k + 1]; p[h][k][2] = c1[2 * k]; p[h][k][3] = c1[2 * k + 1];
            mx[h][k] = fmaxf(fmaxf(p[h][k][0], p[h][k][1]), fmaxf(p[h][k][2], p[h][k][3]));
        }
    }
#pragma unroll
    for (int o = 1; o <= 2; o <<= 1)
#pragma unroll
        for (int h = 0; h < 4; h++)
#pragma unroll
            for (int k = 0; k < 2; k++) mx[h][k] = fmaxf(mx[h][k], __shfl_xor_sync(~0u, mx[h][k], o));
    const float L = 1.4426950408889634f;
    float pmin = 1.f;
#pragma unroll
    for (int h = 0; h < 4; h++)
#pragma unroll
        for (int k = 0; k < 2; k++) {
            const float m = -mx[h][k] * L;
            const float e0 = ex2(fmaf(p[h][k][0], L, m)), e1 = ex2(fmaf(p[h][k][1], L, m)), e2 = ex2(fmaf(p[h][k][2], L, m)), e3 = ex2(fmaf(p[h][k][3], L, m));
            const float p01 = e0 * e1, p23 = e2 * e3, pp = p01 * p23, r = rcp(pp), r01 = r * p23, r23 = r * p01;
            pmin = fminf(pmin, pp);
            out[h][k] = pack2(e0, e1); out[h][k + 2] = pack2(e2, e3);
            out[h][4 + k] = pack2(r01 * e1, r01 * e0); out[h][4 + k + 2] = pack2(r23 * e3, r23 * e2);
        }
    if (__builtin_expect(__any_sync(~0u, !(pmin > 1e-18f)), 0)) {
#pragma unroll
        for (int h = 0; h < 4; h++)
#pragma unroll
            for (int k = 0; k < 2; k++) {
                float m = fminf(fminf(p[h][k][0], p[h][k][1]), fminf(p[h][k][2], p[h][k][3]));
                m = fminf(m, __shfl_xor_sync(~0u, m, 1));
                m = fminf(m, __shfl_xor_sync(~0u, m, 2)) * L;
                out[h][4 + k] = pack2(ex2(fmaf(p[h][k][0], -L, m)), ex2(fmaf(p[h][k][1], -L, m)));
                out[h][4 + k + 2] = pack2(ex2(fmaf(p[h][k][2], -L, m)), ex2(fmaf(p[h][k][3], -L, m)));
            }
    }
}

__global__ void __launch_bounds__(512, 1)
fused_kernel(Scratch* __restrict__ scr, const bf16* __restrict__ logA, const bf16* __restrict__ Aim, const bf16* __restrict__ Cre,
             const bf16* __restrict__ Cim, const bf16* __restrict__ logdt, const bf16* __restrict__ Dskip, const bf16* __restrict__ wphi,
             const bf16* __restrict__ gatew, bf16* __restrict__ out,
             const __grid_constant__ CUtensorMap mx, const __grid_constant__ CUtensorMap mw, const __grid_constant__ CUtensorMap mwo) {
    extern __shared__ __align__(1024) uint8_t smem[];
    constexpr uint32_t sb = 1024;
    const int tid = threadIdx.x, warp = __shfl_sync(~0u, tid >> 5, 0), lane = tid & 31;
    const int g = lane >> 2, q = lane & 3, w4 = warp & 3;
    const int bi = blockIdx.x, bi_i = bi & 15, bi_j = bi >> 4;
    const uint32_t bar = sb + OFF_BAR;
    const int rot = (bi_j & 3) * 2, xkb = bi_j >> 2;
    auto load_stage = [&](int kb) {
        const uint32_t b = bar + 8 * (BAR_FULL + (kb & 3)), d = sb + (kb & 3) * SLOT;
        const int kc = ((kb + rot) & 7) * 64;
        mbar_expect(b, SLOT);
        tma2d(d, &mx, kc, bi_i * 128, b);
        tma3d(d + 16384, &mw, bi_j * 64, kc, 0, b);
    };

    const int ch = bi * 4 + w4;
    const int pidx = ch * 64 + lane * 2 + (warp >> 3);
    const uint32_t pla = ld_nc((const uint32_t*)logA + pidx), pai = ld_nc((const uint32_t*)Aim + pidx);
    const uint32_t pcr = ld_nc((const uint32_t*)Cre + pidx), pci = ld_nc((const uint32_t*)Cim + pidx);
    uint32_t pdt = ld_nc((const uint32_t*)logdt + (ch >> 1));
    const uint32_t pds = ld_nc((const uint32_t*)Dskip + (ch >> 1));
    unsigned done0 = ld_rlx(scr->done);
    if (tid == 0) {
        for (int s = 0; s < 4; s++) mbar_init(bar + 8 * (BAR_FULL + s), 1);
        asm volatile("fence.mbarrier_init.release.cluster;" ::: "memory");
        asm volatile("prefetch.tensormap [%0];" ::"l"(&mx) : "memory");
        load_stage(0); load_stage(1);
        STAMP(11);
    } else if (tid == 32) {
        if (s2u(smem) != sb) __trap();
        sts32(bar + OFF_CNT, 0);
        for (int s = 0; s < 4; s++) { mbar_init(bar + 8 * (BAR_EMPTY + s), 9); mbar_init(bar + 8 * (BAR_KS + s), 1); mbar_init(bar + 8 * (BAR_KP + s), 3); mbar_init(bar + 8 * (BAR_KD + s), 1); }
        mbar_init(bar + 8 * BAR_WPHI, 1); mbar_init(bar + 8 * BAR_WO, 2); mbar_init(bar + 8 * BAR_WO2, 1); mbar_init(bar + 8 * BAR_XT, 4);
        mbar_init(bar + 8 * BAR_DONE, 9); mbar_init(bar + 8 * BAR_KG, 8); mbar_init(bar + 8 * BAR_PUB, 8);
        mbar_init(bar + 8 * BAR_KVF, 4); mbar_init(bar + 8 * BAR_UR, 4); mbar_init(bar + 8 * BAR_WR, 4); mbar_init(bar + 8 * BAR_PREP, 4); mbar_init(bar + 8 * BAR_KGA, 4); mbar_init(bar + 8 * BAR_SP2, 1);
        asm volatile("fence.mbarrier_init.release.cluster;" ::: "memory");
        mbar_expect(bar + 8 * BAR_WPHI, 3072);
        bulk_g2s(sb + OFF_GW, gatew, 1024, bar + 8 * BAR_WPHI);
        bulk_g2s(sb + OFF_WPHI, wphi + bi_j * 1024, 2048, bar + 8 * BAR_WPHI);
    } else if (tid == 64) {
        asm volatile("prefetch.tensormap [%0];" ::"l"(&mw) : "memory");
    }
    const uint32_t buf = sb + OFF_BUF + w4 * BUF_STRIDE, kb_ = sb + OFF_K + w4 * KT_BYTES;
    if ((warp >> 2) == 2) {
#pragma unroll
        for (int v = 0; v < 7; v++) if (v * 32 + lane < KT_BYTES / 16) sts128(kb_ + (v * 32 + lane) * 16, 0, 0, 0, 0);
    }
    __syncthreads();
    asm volatile("" : "+r"(pdt), "+r"(done0)::"memory");
    const unsigned epoch1 = (done0 >> 7) + 1u;
    const uint32_t tag = epoch1 & 1u;

    const int st = tid & 127;
    const uint32_t ub = sb + OFF_U + w4 * U_STRIDE + 256, spare = sb + (w4 < 2 ? OFF_SP0 : OFF_SP1) + (w4 & 1) * 4096;

    auto stg_of = [&](int w) { return w < 8 ? sb + 3 * SLOT + w * 7296 : sb + 2 * SLOT + (w & 3) * 7296; };
    float kc[24];
#pragma unroll
    for (int t = 0; t < 24; t++) kc[t] = 0.f;
    auto handoff = [&](int src) {
        mbar_wait(bar + 8 * (BAR_KS + w4), 0);
#pragma unroll
        for (int t = 0; t < 5; t++)
            sts128(buf + src * 2560 + (t * 32 + lane) * 16, __float_as_uint(kc[4 * t]), __float_as_uint(kc[4 * t + 1]), __float_as_uint(kc[4 * t + 2]), __float_as_uint(kc[4 * t + 3]));
        if (lane == 0) sts32(buf + 7680 + src * 4, __float_as_uint(kc[20]));
        __syncwarp();
        if (lane == 0) mbar_arrive(bar + 8 * (BAR_KP + w4));
    };
    {
        const float dt = bf_round(expf((ch & 1) ? bf_hi(pdt) : bf_lo(pdt)));
        const uint32_t stg = (warp >> 2) == 2 ? buf : stg_of(warp);
        const int sh = ((warp >> 2) & 1) * 16;
        auto pick = [&](uint32_t v) { return __uint_as_float((v >> sh) << 16); };
        const float ea = bf_round(ex2(pick(pla) * 1.4426950408889634f));
        const float arl = (-ea * dt) * 1.4426950408889634f, ait = (pick(pai) * dt) * 0.15915494309189535f;
        cf C2; C2.re = 2.0f * (pick(pcr) * dt); C2.im = 2.0f * (pick(pci) * dt);
        const cf z1 = cexp_p(arl, ait, 1.0f), z128 = cexp_p(arl, ait, 128.0f);
        const cf z2 = cmul(z1, z1), z4 = cmul(z2, z2);
        cf z8 = cmul(z4, z4); z8.im = -z8.im;
        const uint32_t sa0 = stg + (lane >> 3) * 128 + (((lane & 7) ^ (lane >> 3)) << 4), sa1 = (sa0 ^ 64) + 512;
        uint32_t w[60];
        auto put = [&](int row, const cf& v) {
            w[row] = pack2(v.re, v.im);
            if ((row & 3) == 3) stsm4(((row & 4) ? sa1 : sa0) + (row >> 3) * 1024, w[row - 3], w[row - 2], w[row - 1], w[row]);
        };
        {
            const cf z16 = cmul(z8, z8);
            cf e; e.re = 1.f; e.im = 0.f;
            cf o = z8;
            put(0, e); put(1, o);
            e = z16; put(2, e);
#pragma unroll
            for (int b = 3; b < 16; b += 2) {
                o = cmul(o, z16); put(b, o);
                if (b + 1 < 16) { e = cmul(e, z16); put(b + 1, e); }
            }
        }
        cf h[8];
        h[0] = C2; h[1] = cmul(h[0], z1);
#pragma unroll
        for (int r = 2; r < 8; r++) h[r] = cmul(h[r - 2], z2);
#pragma unroll
        for (int r = 0; r < 8; r++) put(16 + r, h[r]);
#pragma unroll
        for (int r = 0; r < 8; r++) { h[r] = cmul(h[r], z128); put(24 + r, h[r]); }
#pragma unroll
        for (int al = 0; al < 2; al++)
#pragma unroll
            for (int r = 0; r < 4; r++) { h[2 * r] = cmul(h[2 * r], z128); put(32 + al * 4 + r, h[2 * r]); }
#pragma unroll
        for (int al = 0; al < 4; al++)
#pragma unroll
            for (int r = 0; r < 2; r++) { h[4 * r] = cmul(h[4 * r], z128); put(40 + al * 2 + r, h[4 * r]); }
#pragma unroll
        for (int al = 0; al < 8; al++) { h[0] = cmul(h[0], z128); put(48 + al, h[0]); }
        h[0] = cmul(h[0], z128);
        sts32(stg + 56 * 128 + lane * 4, pack2(h[0].re, h[0].im));
        __syncwarp();
        const int lr = lane & 7, lm = lane >> 3;
#pragma unroll
        for (int kp = 0; kp < 2; kp++) {
            uint32_t a0[4], a1[4];
            ldsm4(a0, stg + ((lm & 1) * 8 + lr) * 128 + (((4 * kp + (lm >> 1)) ^ lr) << 4));
            ldsm4(a1, stg + ((lm & 1) * 8 + lr) * 128 + (((4 * kp + 2 + (lm >> 1)) ^ lr) << 4));
#pragma unroll
            for (int t = 0; t < 6; t++) {
                uint32_t b[4];
                ldsm4(b, stg + (16 + 8 * t + lr) * 128 + (((4 * kp + lm) ^ lr) << 4));
                mma16816(kc + 4 * t, a0[0], a0[1], a0[2], a0[3], b[0], b[1]);
                mma16816(kc + 4 * t, a1[0], a1[1], a1[2], a1[3], b[2], b[3]);
            }
        }
        __syncwarp();
        asm volatile("fence.proxy.async.shared::cta;" ::: "memory");
        const uint32_t cnt = 1u + (__float_as_uint(kc[0] + kc[23]) == 0xffc12345u);
        if (lane == 0) asm volatile("mbarrier.arrive.shared::cta.b64 _,[%0],%1;" ::"r"(bar + 8 * (warp < 8 ? BAR_KG : (warp < 12 ? BAR_KS + w4 : BAR_KGA))), "r"(cnt) : "memory");
        if (warp < 8) handoff(warp >> 2);
    }

    if (warp < 8) {
        const int wg = warp >> 2;
        if (warp == 0) STAMP(21);
        float acc[96];
        const int srow = warp * 16 + (lane & 15);
        const uint32_t srow_a = srow * 128;
        const int sx = srow & 7, shi = lane >> 4;
        const uint64_t da0 = mkdesc(sb + wg * 8192, 16, 1024), db0 = mkdesc(sb + 16384, 8192, 1024);
#pragma unroll 1
        for (int kb = 0; kb < 8; kb++) {
            const int s = kb & 3;
            const uint64_t da = da0 + s * (SLOT >> 4), db = db0 + s * (SLOT >> 4);
            if (warp == 0) STAMP(40 + kb);
            mbar_wait(bar + 8 * (BAR_FULL + s), kb >> 2);
            if (warp == 0) STAMP(32 + kb);
            wg_fence();
#pragma unroll
            for (int k = 0; k < 4; k++) wgmma192(acc, da + 2 * k, db + 128 * k, kb | k);
            wg_commit();
            wg_wait<1>();
            if (lane == 0 && kb > 0) mbar_arrive(bar + 8 * (BAR_EMPTY + ((kb - 1) & 3)));
        }
        mbar_wait(bar + 8 * BAR_WPHI, 0);
        wg_wait<0>();
        fence_regs<96>(acc);
        asm volatile("setmaxnreg.inc.sync.aligned.u32 160;");
        if (lane == 0) mbar_arrive(bar + 8 * BAR_DONE);
        if (warp == 0) STAMP(1);
        uint32_t in[16], qa[16];
        mbar_wait(bar + 8 * BAR_DONE, 0);
#pragma unroll
        for (int r = 0; r < 16; r++) {
            in[r] = pack2(acc[32 + 2 * r], acc[32 + 2 * r + 1]);
            qa[r] = pack2(acc[2 * r], acc[2 * r + 1]);
        }
#pragma unroll
        for (int hh = 0; hh < 4; hh++)
            stsm4(sb + OFF_V + (hh >> 1) * 16384 + srow_a + (((2 * (hh & 1) + shi) ^ sx) << 4), pack2(acc[64 + 8 * hh], acc[65 + 8 * hh]),
                  pack2(acc[66 + 8 * hh], acc[67 + 8 * hh]), pack2(acc[68 + 8 * hh], acc[69 + 8 * hh]), pack2(acc[70 + 8 * hh], acc[71 + 8 * hh]));
        sts128(sb + OFF_V + shi * 16384 + srow_a + ((4 ^ sx) << 4), 0x3f803f80u, 0x3f803f80u, 0x3f803f80u, 0x3f803f80u);
        const uint32_t wphi_a = sb + OFF_WPHI + (lane & 15) * 32 + (lane >> 4) * 16;
        uint32_t pq[4][8];
#pragma unroll 1
        for (int it = 0; it < 2; it++) {
            hedgehog4(in, wphi_a, pq);
            if (it == 1) break;
#pragma unroll
            for (int hs = 0; hs < 8; hs++) {
                float c[4] = {0.f, 0.f, 0.f, 0.f};
                const uint32_t* o = pq[hs >> 1] + 4 * (hs & 1);
                mma16816(c, o[0], o[1], o[2], o[3], 0x3f803f80u, 0x3f803f80u);
                const float r0 = rcp(c[0]), r1 = rcp(c[2]);
                const uint32_t s0 = pack2(r0, r0), s1 = pack2(r1, r1);
                stsm4(sb + OFF_P + (hs >> 2) * 16384 + srow_a + (((2 * (hs & 3) + shi) ^ sx) << 4), hmul2(o[0], s0), hmul2(o[1], s1), hmul2(o[2], s0), hmul2(o[3], s1));
            }
            asm volatile("fence.proxy.async.shared::cta;" ::: "memory");
            bar_named(1, 256);
            if (warp == 0) STAMP(2);
            float d[32];
            const uint64_t dv = mkdesc(sb + OFF_V + wg * 16384, 16, 1024), dp = mkdesc(sb + OFF_P + wg * 16384, 16, 1024);
            wg_fence();
#pragma unroll
            for (int k = 0; k < 8; k++) wgmma64_tt(d, dv + 128 * k, dp + 128 * k, k != 0);
            wg_commit();
            mbar_wait(bar + 8 * BAR_PREP, 0);
            uint4* kvp = scr->kvp + bi * 544 + wg * 272 + (w4 < 2 ? w4 * 136 : 128) + lane;
            wg_wait<0>();
            fence_regs<32>(d);
            if (w4 < 2 || (w4 == 2 && lane < 4)) {
#pragma unroll
                for (int f = 0; f < 4; f++) {
                    const int i0 = 8 * (f >> 1) + 2 * (f & 1), i2 = 16 * (f >> 1) + 8 * (f & 1);
                    const float e0 = w4 == 0 ? d[i0] : (w4 == 1 ? d[16 + i0] : d[i2]), e1 = w4 == 0 ? d[i0 + 1] : (w4 == 1 ? d[17 + i0] : d[i2 + 1]);
                    const float e2 = w4 == 0 ? d[i0 + 4] : (w4 == 1 ? d[20 + i0] : d[i2 + 4]), e3 = w4 == 0 ? d[i0 + 5] : (w4 == 1 ? d[21 + i0] : d[i2 + 5]);
                    st_rlx128(kvp + (w4 < 2 ? f * 32 : (f >> 1) * 136 + (f & 1) * 4), tag4(__float_as_uint(e0), __float_as_uint(e1), __float_as_uint(e2), __float_as_uint(e3), tag));
                }
            }
            __syncwarp();
            if (lane == 0) mbar_arrive(bar + 8 * BAR_PUB);
            if (warp == 0) STAMP(3);
#pragma unroll
            for (int r = 0; r < 16; r++) in[r] = qa[r];
        }
        if (warp == 0) STAMP(4);
        {
            mbar_wait(bar + 8 * BAR_KVF, 0);
            uint4 kf[4][3];
#pragma unroll
            for (int hh = 0; hh < 4; hh++) {
                const uint32_t a = sb + OFF_KVF + hh * 1088;
                kf[hh][0] = lds128(a + lane * 32); kf[hh][1] = lds128(a + lane * 32 + 16); kf[hh][2] = lds128(a + 1024 + q * 16);
            }
            if (warp == 0) STAMP(5);
            uint4* og = scr->o + ((bi_i * 8 + warp) * 32 + bi_j * 4) * 32 + lane;
#pragma unroll
            for (int hh = 0; hh < 4; hh++) {
                float c[6][4];
#pragma unroll
                for (int t = 0; t < 6; t++) { c[t][0] = c[t][1] = c[t][2] = c[t][3] = 0.f; }
                const uint32_t* a = pq[hh];
                const bool od = g & 1;
                mma16816(c[0], a[0], a[1], a[2], a[3], od ? 0x3f803f80u : kf[hh][2].x, od ? 0x3f803f80u : kf[hh][2].y);
                mma16816(c[1], a[4], a[5], a[6], a[7], od ? 0x3f803f80u : kf[hh][2].z, od ? 0x3f803f80u : kf[hh][2].w);
                mma16816(c[2], a[0], a[1], a[2], a[3], kf[hh][0].x, kf[hh][0].y);
                mma16816(c[3], a[0], a[1], a[2], a[3], kf[hh][0].z, kf[hh][0].w);
                mma16816(c[4], a[4], a[5], a[6], a[7], kf[hh][1].x, kf[hh][1].y);
                mma16816(c[5], a[4], a[5], a[6], a[7], kf[hh][1].z, kf[hh][1].w);
                uint32_t w[4];
#pragma unroll
                for (int k = 0; k < 2; k++) {
                    const float rho = c[0][2 * k + 1] * rcp(c[1][2 * k + 1]);
                    const float r = rcp(fmaf(c[0][2 * k + 1], 1e-6f, fmaf(rho, c[1][2 * k], c[0][2 * k]))), rr = r * rho;
                    w[k] = pack2(fmaf(c[4][2 * k], rr, c[2][2 * k] * r), fmaf(c[4][2 * k + 1], rr, c[2][2 * k + 1] * r));
                    w[2 + k] = pack2(fmaf(c[5][2 * k], rr, c[3][2 * k] * r), fmaf(c[5][2 * k + 1], rr, c[3][2 * k + 1] * r));
                }
                st_rlx128(og + hh * 32, tag4(w[0], w[1], w[2], w[3], tag));
            }
        }
        if (warp == 0) STAMP(6);
        float oc[64];
        const int slab = bi_i * 8 + (bi_j >> 2) * 4 + w4;
        const unsigned* ysrc = (const unsigned*)scr->y + ((bi_j & 3) * 128 + wg * 64 + 2 * q) * 1024 + (slab >> 1) * 16 + g * 2 + (slab & 1);
        const unsigned* gp = scr->g + (slab * 8 + (g >> 1)) * 8 + (g & 1) * 4;
        uint2 yv[8]; unsigned g0, g1;
        {
            const uint4* osrc = scr->o + (slab * 32 + wg * 16) * 32 + lane;
            uint4 fr[16];
            const unsigned* probe = (const unsigned*)(osrc - lane + ((lane & 3) * 4 + 3) * 32 + 31) + 2;
            {
                unsigned miss = ~0u;
                int n = 0;
#pragma unroll
                for (int s = 0; s < 4; s++) {
#pragma unroll 1
                    while ((miss >> s) & 1) { miss = __ballot_sync(~0u, (ld_rlx(probe) ^ tag) & 1); if (++n > SPIN_LIMIT) break; }
#pragma unroll
                    for (int k = 4 * s; k < 4 * s + 4; k++) fr[k] = ld_rlx128(osrc + k * 32);
                }
            }
            if (warp == 0) STAMP(14);
            mbar_wait(bar + 8 * (wg ? BAR_WO2 : BAR_WO), 0);
            const uint64_t dw = mkdesc(sb + wg * 2 * SLOT, wg ? 32768 : SLOT, 1024);
#pragma unroll
            for (int s = 0; s < 4; s++) {
                int n = 0;
#pragma unroll 1
                while (__builtin_expect(__any_sync(~0u, (bad4(fr[4 * s], tag) | bad4(fr[4 * s + 1], tag) | bad4(fr[4 * s + 2], tag) | bad4(fr[4 * s + 3], tag)) & 1), 0)) {
#pragma unroll
                    for (int k = 4 * s; k < 4 * s + 4; k++) fr[k] = ld_rlx128(osrc + k * 32);
                    if (++n > SPIN_LIMIT) break;
                }
                wg_fence();
#pragma unroll
                for (int hh = 0; hh < 4; hh++) wgmma128_rs(oc, fr[4 * s + hh], dw + 128 * (4 * s + hh), (s | hh) != 0);
                wg_commit();
                if (s == 1) {
                    wg_wait<1>();
#pragma unroll
                    for (int nt = 0; nt < 8; nt++) { yv[nt].x = ld_rlx(ysrc + nt * 8192); yv[nt].y = ld_rlx(ysrc + nt * 8192 + 1024); }
                    g0 = ld_rlx(gp); g1 = ld_rlx(gp + 32);
                }
            }
            if (warp == 0) STAMP(7);
            {
                int n = 0;
#pragma unroll 1
                while (true) {
                    uint32_t bad = (g0 ^ tag) | (g1 ^ tag);
#pragma unroll
                    for (int nt = 0; nt < 8; nt++) bad |= (yv[nt].x ^ tag) | (yv[nt].y ^ tag);
                    if (!__any_sync(~0u, bad & 1)) break;
#pragma unroll
                    for (int nt = 0; nt < 8; nt++) {
                        if ((yv[nt].x ^ tag) & 1) yv[nt].x = ld_rlx(ysrc + nt * 8192);
                        if ((yv[nt].y ^ tag) & 1) yv[nt].y = ld_rlx(ysrc + nt * 8192 + 1024);
                    }
                    g0 = ld_rlx(gp); g1 = ld_rlx(gp + 32);
                    if (++n > SPIN_LIMIT) break;
                }
            }
            if (warp == 0) STAMP(28);
        }
        {
            const float ga = bf_hi(g0), gb = bf_hi(g1);
            const float ha = bf_round(1.0f - ga), hb = bf_round(1.0f - gb);
            float yb[32];
#pragma unroll
            for (int nt = 0; nt < 8; nt++) {
                yb[4 * nt] = ha * bf_lo(yv[nt].x); yb[4 * nt + 1] = ha * bf_lo(yv[nt].y);
                yb[4 * nt + 2] = hb * bf_hi(yv[nt].x); yb[4 * nt + 3] = hb * bf_hi(yv[nt].y);
            }
            fence_regs<32>(yb);
            const uint32_t xw = sb + wg * 2 * SLOT + (tid & 127) * 16, xr = sb + (wg ^ 1) * 2 * SLOT + (tid & 127) * 16;
            wg_wait<0>();
            fence_regs<64>(oc);
            bar_named(3 + wg, 128);
#pragma unroll
            for (int r = 0; r < 8; r++)
                sts128(xw + r * 2048, __float_as_uint(oc[32 + 4 * r]), __float_as_uint(oc[33 + 4 * r]), __float_as_uint(oc[34 + 4 * r]), __float_as_uint(oc[35 + 4 * r]));
#pragma unroll
            for (int r = 0; r < 32; r++) yb[r] = fmaf((r & 2) ? gb : ga, oc[r], yb[r]);
            bar_named(1, 256);
            if (warp == 0) STAMP(8);
            uint32_t w[8][2];
#pragma unroll
            for (int nt = 0; nt < 8; nt++) {
                const uint4 p = lds128(xr + nt * 2048);
                w[nt][0] = pack2(fmaf(ga, __uint_as_float(p.x), yb[4 * nt]), fmaf(ga, __uint_as_float(p.y), yb[4 * nt + 1]));
                w[nt][1] = pack2(fmaf(gb, __uint_as_float(p.z), yb[4 * nt + 2]), fmaf(gb, __uint_as_float(p.w), yb[4 * nt + 3]));
            }
            const uint32_t ob = sb + wg * 2 * SLOT + 16384 + w4 * 2048;
#pragma unroll
            for (int nt = 0; nt < 8; nt += 2)
                stsm4(ob + (lane & 15) * 128 + (((nt + shi) ^ (lane & 7)) << 4), w[nt][0], w[nt][1], w[nt + 1][0], w[nt + 1][1]);
            __syncwarp();
            bf16* op = out + (size_t)(slab * 16) * 512 + (bi_j & 3) * 128 + wg * 64 + (lane & 7) * 8;
#pragma unroll
            for (int it = 0; it < 4; it++) {
                const int r = it * 4 + (lane >> 3);
                uint4 v = lds128(ob + r * 128 + (((lane & 7) ^ (r & 7)) << 4));
                *(uint4*)(op + r * 512) = v;
            }
        }
        if (warp == 0) STAMP(10);
    } else if (warp < 12) {
        if (warp == 8) {
            mbar_wait(bar + 8 * BAR_KGA, 0);
            if (lane == 0) load_stage(2);
            STAMP(22);
            mbar_wait(bar + 8 * BAR_KG, 0);
            if (lane == 0) load_stage(3);
            __syncwarp();
            STAMP(17);
        }
        if (warp == 8) {
#pragma unroll 1
            for (int kb = 0; kb < 6; kb++) {
                const int s = kb & 3;
                mbar_wait(bar + 8 * (BAR_EMPTY + s), kb >> 2);
                if (kb == xkb) mbar_wait(bar + 8 * BAR_XT, 0);
                if (lane == 0) {
                    STAMP(48 + kb);
                    if (kb < 4) load_stage(kb + 4);
                    else {
                        mbar_expect(bar + 8 * BAR_WO, 32768);
                        tma2d(sb + s * SLOT, &mwo, (bi_j & 3) * 128 + s * 64, 0, bar + 8 * BAR_WO);
                        if (kb == 5) mbar_arrive(bar + 8 * BAR_SP2);
                    }
                }
                __syncwarp();
            }
        } else if (warp == 9) {
            const int row = bi_j * 16 + (lane >> 1), half = lane & 1;
            unsigned* gp = scr->g + (bi_i * 64 + bi_j * 8) * 8 + lane * 2;
            st_rlx64(gp, tag ^ 1u, tag ^ 1u);
            float gs0 = 0.f, gs1 = 0.f;
            mbar_wait(bar + 8 * BAR_WPHI, 0);
#pragma unroll 1
            for (int kb = 0; kb < 8; kb++) {
                const int s = kb & 3;
                mbar_wait(bar + 8 * (BAR_FULL + s), kb >> 2);
#pragma unroll
                for (int c = 0; c < 4; c++) {
                    const uint4 xv = lds128(sb + s * SLOT + row * 128 + (((half * 4 + c) ^ (row & 7)) << 4));
                    const uint4 gw = lds128(sb + OFF_GW + ((kb + rot) & 7) * 128 + half * 64 + c * 16);
                    const uint32_t p0 = hmul2(xv.x, gw.x), p1 = hmul2(xv.y, gw.y), p2 = hmul2(xv.z, gw.z), p3 = hmul2(xv.w, gw.w);
                    gs0 += (bf_lo(p0) + bf_lo(p1)) + (bf_lo(p2) + bf_lo(p3));
                    gs1 += (bf_hi(p0) + bf_hi(p1)) + (bf_hi(p2) + bf_hi(p3));
                }
                const uint32_t cnt = 1u + (__float_as_uint(gs0 + gs1) == 0xffc12345u);
                if (lane == 0) asm volatile("mbarrier.arrive.shared::cta.b64 _,[%0],%1;" ::"r"(bar + 8 * (kb < 7 ? BAR_EMPTY + s : BAR_DONE)), "r"(cnt) : "memory");
                __syncwarp();
            }
            float gs = gs0 + gs1;
            gs += __shfl_xor_sync(~0u, gs, 1);
            const uint32_t gv = __float_as_uint(bf_round(rcp(1.0f + ex2(-1.4426950408889634f * bf_round(gs))))) | tag;
            st_rlx64(gp, gv, gv);
        }
        mbar_wait(bar + 8 * (BAR_KP + w4), 0);
#pragma unroll
        for (int t = 0; t < 15; t++) {
            const uint4 v = lds128(buf + (t * 32 + lane) * 16);
            kc[4 * (t % 5)] += __uint_as_float(v.x); kc[4 * (t % 5) + 1] += __uint_as_float(v.y); kc[4 * (t % 5) + 2] += __uint_as_float(v.z); kc[4 * (t % 5) + 3] += __uint_as_float(v.w);
        }
        {
            const uint4 v = lds128(buf + 7680);
            kc[20] += __uint_as_float(v.x) + __uint_as_float(v.y) + __uint_as_float(v.z);
            const uint32_t cnt = 1u + (__float_as_uint(kc[20] + kc[19] + kc[0]) == 0xffc12345u);
            if (lane == 0) asm volatile("mbarrier.arrive.shared::cta.b64 _,[%0],%1;" ::"r"(bar + 8 * (BAR_KD + w4)), "r"(cnt) : "memory");
            __syncwarp();
        }
        if (lane == 0) kc[4 * 0 + 0] += ((ch & 1) ? bf_hi(pds) : bf_lo(pds));
        const uint32_t k1024 = __shfl_sync(~0u, pack2(kc[4 * 4 + 0], 0.f), 0);
#pragma unroll
        for (int i = 0; i < 2; i++) {
            const int be = g + 8 * i;
#pragma unroll
            for (int t = 0; t < 2; t++) {
                const uint32_t a = kb_ + (KW_D + 128 * t + 8 * be + 2 * q) * 4;
                const uint32_t w = pack2(kc[4 * t + 2 * i + 1], kc[4 * t + 2 * i]);
                sts32(a + 4, w); sts16(a, w >> 16); sts16(a + 10, w);
            }
            {
                const int p = 256 + 128 * (q >> 1) + 8 * be + 4 * (q & 1);
                const uint32_t a = kb_ + (KW_D + p) * 4;
                const uint32_t w = pack2(kc[4 * 2 + 2 * i + 1], kc[4 * 2 + 2 * i]);
                const uint32_t aa = (w >> 16) | (w & 0xffff0000u);
                if (p != 256) { sts16(a - 4, aa); sts32(a, aa); } else sts16(a, aa);
                sts32(a + 4, aa); sts32(a + 8, w); sts16(a + 14, w);
            }
            {
                const int k = 64 + 16 * q + be;
                const uint32_t w = pack2(kc[4 * 3 + 2 * i], kc[4 * 3 + 2 * i + 1]);
                if (k != 64) sts16(kb_ + (KW_2 + ((k - 1) >> 1) - 24) * 4 + (k & 1) * 2, w);
                else {
                    const uint32_t a = kb_ + (KW_D + 511) * 4, aa = (w << 16) | (w & 0xffffu);
                    sts16(a, w); sts32(a + 4, aa); sts32(a + 8, aa); sts32(a + 12, aa); sts16(a + 18, w);
                }
                sts16(kb_ + (KW_2 + 48 + (k >> 1) - 24) * 4 + ((k & 1) ^ 1) * 2, w >> 16);
            }
#pragma unroll
            for (int b = 0; b < 2; b++) {
                const int k = 64 + 8 * (2 * q + b) + (be >> 1);
                const uint32_t w = pack2(kc[4 * 4 + 2 * i + b], 0.f);
                if (!(be & 1) && k == 64) sts16(kb_ + (KW_2 + 63 - 24) * 4, w);
                else {
                    const uint32_t a = kb_ + (KW_3 + ((be & 1) ? 80 + k : k - 1) - 48) * 4;
                    sts16(a, w);
                    if (!((be & 1) && k == 127)) sts16(a + 6, w);
                }
            }
        }
        if (lane == 0) sts16(kb_ + (KW_3 + 127 - 48) * 4, pack2(kc[4 * 5 + 0], 0.f));
        __syncwarp();
        asm volatile("setmaxnreg.inc.sync.aligned.u32 136;");
        mbar_wait(bar + 8 * BAR_UR, 0);
        mbar_wait(bar + 8 * BAR_DONE, 0);
        if (warp == 8) STAMP(23);
        float y[16][4];
#pragma unroll
        for (int nt = 0; nt < 16; nt++) { y[nt][0] = y[nt][1] = y[nt][2] = y[nt][3] = 0.f; }
        {
            uint32_t Bp[32], A[4][3], An[4][3];
            auto uaddr = [&](int rho) { const int R0 = (lane >> 4) * 64 + (lane & 7) - rho; return ub + (((2 * R0 + ((lane >> 3) & 1)) ^ ((R0 >> 2) & 1)) << 4); };
            const uint32_t kd = kb_ + (KW_D + g - 2 * q) * 4;
#pragma unroll 1
            for (int rho = 1; rho >= 0; rho--) {
                const uint32_t a = uaddr(rho), k = kd + 2048 + rho * 64;
#pragma unroll
                for (int i = 0; i < 8; i++) ldsm4(Bp + 4 * i, a + i * 256);
                const uint32_t a0 = lds32(k), a1 = lds32(k + 32), a2 = lds32(k - 32);
#pragma unroll
                for (int i = 0; i < 12; i++) mma16816(y[i + 4], a0, a1, a2, a0, Bp[4 * (i & 7) + 2 * (i >> 3)], Bp[4 * (i & 7) + 2 * (i >> 3) + 1]);
            }
#pragma unroll
            for (int ga = 0; ga < 4; ga++) { An[ga][0] = lds32(kd + ga * 512); An[ga][1] = lds32(kd + ga * 512 + 32); An[ga][2] = lds32(kd + ga * 512 - 32); }
#pragma unroll 1
            for (int rho = 0; rho < 8; rho++) {
#pragma unroll
                for (int ga = 0; ga < 4; ga++) {
                    const uint32_t a = kd + (rho + 1) * 64 + ga * 512;
                    A[ga][0] = An[ga][0]; A[ga][1] = An[ga][1]; A[ga][2] = An[ga][2];
                    An[ga][0] = lds32(a); An[ga][1] = lds32(a + 32); An[ga][2] = lds32(a - 32);
                }
                const uint32_t an = uaddr(rho + 1);
#pragma unroll
                for (int i = 0; i < 8; i++) {
#pragma unroll
                    for (int ga = 0; ga < 4; ga++) {
                        mma16816(y[i + ga], A[ga][0], A[ga][1], A[ga][2], A[ga][0], Bp[4 * i], Bp[4 * i + 1]);
                        if (i + 8 + ga < 16) mma16816(y[i + 8 + ga], A[ga][0], A[ga][1], A[ga][2], A[ga][0], Bp[4 * i + 2], Bp[4 * i + 3]);
                    }
                    ldsm4(Bp + 4 * i, an + i * 256);
                    __syncwarp();
                }
            }
        }
        if (warp == 8) STAMP(18);
        mbar_wait(bar + 8 * BAR_WR, 0);
#pragma unroll 1
        for (int ph = 0; ph < 2; ph++) {
            uint32_t B[5][2];
            const uint32_t ka = kb_ + (KW_2 + ph * 48 + 8 + g - q) * 4;
#pragma unroll
            for (int dd = 0; dd < 5; dd++) { B[dd][0] = lds32(ka + dd * 32); B[dd][1] = lds32(ka + dd * 32 - 16); }
            const uint32_t wa = buf + ph * W3_OFF + ((lane & 7) + ((lane >> 3) & 1) + (lane >> 4) * 8) * 16;
#pragma unroll
            for (int s = 0; s < 12; s++) {
                uint32_t A[4];
                ldsm4t(A, wa + s * 256);
#pragma unroll
                for (int dd = 0; dd < 5; dd++)
                    if (s + 4 + dd < 16) mma16816(y[s + 4 + dd], A[0], A[1], A[2], A[3], B[dd][0], B[dd][1]);
            }
        }
        {
            const int ap = (lane & 7) + (lane >> 4) * 8;
            const uint32_t loff = ((2 * ap + ((lane >> 3) & 1)) ^ ((ap >> 2) & 1)) << 4;
#pragma unroll 1
            for (int ph = 0; ph < 2; ph++) {
                uint32_t B[8][2];
                const uint32_t wb = (ph ? spare : buf + W9_OFF) + loff;
                const uint32_t ka = kb_ + (KW_3 + ph * 80 + 16 + g - 2 * q) * 4;
#pragma unroll
                for (int dd = 0; dd < 8; dd++) { B[dd][0] = lds32(ka + dd * 32); B[dd][1] = lds32(ka + dd * 32 - 32); }
#pragma unroll
                for (int s = 0; s < 4; s++) {
                    uint32_t A[4];
                    ldsm4t(A, wb + s * 512);
#pragma unroll
                    for (int dd = 0; dd < 8; dd++)
                        if (8 + 2 * s + dd < 16) mma16816(y[8 + 2 * s + dd], A[0], A[1], A[2], A[3], B[dd][0], B[dd][1]);
                }
            }
            const uint32_t idw = (g == 2 * q) ? k1024 : ((g == 2 * q + 1) ? (k1024 << 16) : 0u);
#pragma unroll
            for (int s = 0; s < 4; s++) {
                uint32_t A[4];
                ldsm4t(A, spare + 2048 + loff + s * 512);
                mma16816(y[8 + 2 * s], A[0], A[1], A[2], A[3], idw, 0u);
                mma16816(y[9 + 2 * s], A[0], A[1], A[2], A[3], 0u, idw);
            }
        }
        __syncwarp();
        if (warp == 8) STAMP(19);
        uint2* yp = (uint2*)scr->y + ch * 512 + q * 8 + g;
#pragma unroll
        for (int nt = 0; nt < 16; nt++) st_rlx64(yp + nt * 32, tagw(pack2(y[nt][0], y[nt][2]), tag), tagw(pack2(y[nt][1], y[nt][3]), tag));
        if (warp == 8) STAMP(20);
    } else {
        const int qq = (bi_i & 2) + ((lane >> 1) & 1);
        uint2* kvf_h = (uint2*)(scr->kvf + (bi_j * 4 + (bi_i >> 2)) * 68);
        auto windows = [&](int rhi, int rlo) {
#pragma unroll 1
            for (int rho = rhi; rho >= rlo; rho--) {
                const int ci = lane + 32 * rho;
                uint4 e4[4];
#pragma unroll
                for (int v = 0; v < 4; v++) { const int cc = ci - 3 + v; e4[v] = lds128(ub + ((cc ^ ((cc >> 3) & 1)) << 4)); }
                float S[29];
                const uint32_t* ew = (const uint32_t*)e4;
                S[3] = 0.f;
#pragma unroll
                for (int k = 4; k <= 28; k++) S[k] = S[k - 1] + ((k & 1) ? bf_hi(ew[k >> 1]) : bf_lo(ew[k >> 1]));
                auto win = [&](int lo, int hi, uint32_t a) {
                    sts128(a, pack2(S[hi] - S[lo - 1], S[hi + 1] - S[lo]), pack2(S[hi + 2] - S[lo + 1], S[hi + 3] - S[lo + 2]),
                           pack2(S[hi + 4] - S[lo + 3], S[hi + 5] - S[lo + 4]), pack2(S[hi + 6] - S[lo + 5], S[hi + 7] - S[lo + 6]));
                };
                win(14, 18, buf + W5_OFF + 16 + ci * 16); win(19, 21, buf + W3_OFF + 16 + ci * 16);
                if (rho < 4) {
                    const uint32_t sw = (ci ^ ((ci >> 3) & 1)) << 4;
                    win(4, 12, buf + W9_OFF + sw); win(13, 19, spare + sw); win(20, 21, spare + 2048 + sw);
                }
            }
        };
        {
            mbar_wait(bar + 8 * (BAR_FULL + xkb), 0);
#pragma unroll 1
            for (int hf = 0; hf < 2; hf++) {
                const int r = w4 * 32 + hf * 16 + (lane & 15);
                uint32_t* xt = (uint32_t*)scr->xt + ((xkb + rot) * 16 + (g >> 2)) * 4096 + (bi_i * 16 + w4 * 4 + hf * 2) * 16 + (g & 3) * 4 + q;
#pragma unroll
                for (int cb = 0; cb < 8; cb += 2) {
                    uint32_t v[4];
                    ldsm4t(v, sb + xkb * SLOT + r * 128 + (((cb + (lane >> 4)) ^ (r & 7)) << 4));
                    xt[cb * 8192] = v[0]; xt[cb * 8192 + 16] = v[1]; xt[cb * 8192 + 8192] = v[2]; xt[cb * 8192 + 8192 + 16] = v[3];
                }
            }
            __syncwarp();
            if (lane == 0) mbar_arrive(bar + 8 * BAR_XT);
            if (warp == 12) STAMP(26);
            handoff(2);
            asm volatile("setmaxnreg.dec.sync.aligned.u32 56;");
            if (lane == 0) asm volatile("red.release.gpu.global.add.u32 [%0],2;" ::"l"(scr->xcnt + (xkb + rot) * 32) : "memory");
            __syncwarp();
            if (warp == 12) STAMP(27);
            {
                const uint32_t old = tag ^ 1u;
                const uint4 z4 = make_uint4(old, 0, old, 0);
#pragma unroll
                for (int v = 0; v < 5; v++) if (v < 4 || st < 32) st_rlx128(scr->kvp + bi * 544 + v * 128 + st, z4);
                if (st < 16) st_rlx128(scr->o + ((bi_i * 8 + (st >> 1)) * 32 + bi_j * 4 + 3) * 32 + 30 + (st & 1), z4);
                if (lane < 8) st_rlx64(kvf_h + ((bi_i & 3) * 8 + w4 * 2 + (lane & 1)) * 4 + (lane >> 1), old, 0);
                if (st < 4 && !(bi_i & 1)) st_rlx64(kvf_h + (64 + qq) * 2 + (lane & 1), old, 0);
                __syncwarp();
                if (lane == 0) mbar_arrive(bar + 8 * BAR_PREP);
            }
            int n = 0;
#pragma unroll 1
            while (__any_sync(~0u, (int)(ld_acq(scr->xcnt + bi_j * 32) - (epoch1 << 7)) < 0)) { if (++n > SPIN_LIMIT) break; }
            if (warp == 12) STAMP(15);
            uint4 ur[8];
#pragma unroll
            for (int v = 0; v < 8; v++) ur[v] = __ldcg(scr->xt + bi * 1024 + st + 128 * v);
            mbar_wait(bar + 8 * BAR_KG, 0);
            if (lane < 16) sts128(ub - 256 + lane * 16, 0, 0, 0, 0);
#pragma unroll
            for (int v = 0; v < 8; v++) {
                const int ci = (st >> 2) + 32 * v;
                sts128(sb + OFF_U + (st & 3) * U_STRIDE + 256 + ((ci ^ ((ci >> 3) & 1)) << 4), ur[v].x, ur[v].y, ur[v].z, ur[v].w);
            }
            __syncwarp();
            if (lane == 0) mbar_arrive(bar + 8 * BAR_UR);
            mbar_wait(bar + 8 * BAR_UR, 0);
            if (warp == 12) STAMP(16);
            mbar_wait(bar + 8 * (BAR_KD + w4), 0);
            if (lane < 2) sts128(buf + lane * W3_OFF, 0, 0, 0, 0);
            windows(5, 4);
        }
        mbar_wait(bar + 8 * BAR_SP2, 0);
        windows(3, 0);
        __syncwarp();
        if (lane == 0) mbar_arrive(bar + 8 * BAR_WR);
        if (warp == 12) STAMP(24);
        {
            const bool zw = st < 32 && !(bi_i & 1);
            const uint4* src = scr->kvp + bi_j * (16 * 544) + (bi_i >> 2) * 136;
            const uint4* zsrc = src + (lane >> 2) * (2 * 544) + 128 + (lane & 1) * 4 + qq;
            src += (lane >> 3) * (4 * 544) + ((lane >> 1) & 3) * 32 + (bi_i & 3) * 8 + w4 * 2 + (lane & 1);
            mbar_wait(bar + 8 * BAR_PUB, 0);
            if (warp == 12) STAMP(12);
            uint4 v[6];
#pragma unroll
            for (int k = 0; k < 6; k++) v[k] = make_uint4(tag ^ 1u, 0, 0, 0);
            int n = 0;
#pragma unroll 1
            while (true) {
#pragma unroll
                for (int k = 0; k < 6; k++) if ((bad4(v[k], tag) & 1) && (k < 4 || zw)) v[k] = ld_rlx128(k < 4 ? src + k * 544 : zsrc + (k - 4) * 544);
                if (!__any_sync(~0u, (bad4(v[0], tag) | bad4(v[1], tag) | bad4(v[2], tag) | bad4(v[3], tag) | (zw ? bad4(v[4], tag) | bad4(v[5], tag) : 0u)) & 1)) break;
                if (++n > SPIN_LIMIT) break;
            }
            if (warp == 12) STAMP(30);
            float f[8];
            const float* vf = (const float*)v;
#pragma unroll
            for (int r = 0; r < 4; r++) {
                f[r] = (vf[r] + vf[4 + r]) + (vf[8 + r] + vf[12 + r]);
                f[4 + r] = vf[16 + r] + vf[20 + r];
                f[4 + r] += __shfl_xor_sync(~0u, f[4 + r], 4);
            }
#pragma unroll
            for (int o = 8; o <= 16; o <<= 1)
#pragma unroll
                for (int r = 0; r < 8; r++) f[r] += __shfl_xor_sync(~0u, f[r], o);
            if (lane < 8) st_rlx64(kvf_h + ((bi_i & 3) * 8 + w4 * 2 + (lane & 1)) * 4 + (lane >> 1), tagw(pack2(f[0], f[1]), tag), pack2(f[2], f[3]));
            if (zw && lane < 4) st_rlx64(kvf_h + (64 + qq) * 2 + (lane & 1), tagw(pack2(f[4], f[5]), tag), pack2(f[6], f[7]));
        }
        if (warp == 12) STAMP(13);
        {
            const uint4* kp = scr->kvf + bi_j * 272 + st;
            uint4 v0 = make_uint4(tag ^ 1u, 0, 0, 0), v1 = v0, v2 = make_uint4(st < 16 ? tag ^ 1u : tag, 0, tag, 0);
            int n = 0;
#pragma unroll 1
            while (true) {
                if (bad4(v0, tag) & 1) v0 = ld_rlx128(kp);
                if (bad4(v1, tag) & 1) v1 = ld_rlx128(kp + 128);
                if (bad4(v2, tag) & 1) v2 = ld_rlx128(kp + 256);
                if (!__any_sync(~0u, (bad4(v0, tag) | bad4(v1, tag) | bad4(v2, tag)) & 1)) break;
                if (++n > SPIN_LIMIT) break;
            }
            sts128(sb + OFF_KVF + st * 16, v0.x, v0.y, v0.z, v0.w);
            sts128(sb + OFF_KVF + 2048 + st * 16, v1.x, v1.y, v1.z, v1.w);
            if (st < 16) sts128(sb + OFF_KVF + 4096 + st * 16, v2.x, v2.y, v2.z, v2.w);
            __syncwarp();
            if (lane == 0) mbar_arrive(bar + 8 * BAR_KVF);
        }
        if (warp == 13) {
            mbar_wait(bar + 8 * BAR_KVF, 0);
            if (lane == 0) {
                mbar_expect(bar + 8 * BAR_WO2, 65536);
                tma2d(sb + OFF_P, &mwo, (bi_j & 3) * 128 + 64, 256, bar + 8 * BAR_WO2);
                tma2d(sb + OFF_V, &mwo, (bi_j & 3) * 128, 256, bar + 8 * BAR_WO2);
            }
        }
        if (warp == 12) STAMP(25);
    }
    __syncwarp();
    if (lane == 0) {
        unsigned old;
        asm volatile("atom.acq_rel.cta.shared.add.u32 %0,[%1],1;" : "=r"(old) : "r"(bar + OFF_CNT) : "memory");
        if (old == 15) {
            atomicAdd(scr->done, 1u);
        }
    }
}

typedef CUresult (*EncFn)(CUtensorMap*, CUtensorMapDataType, cuuint32_t, void*, const cuuint64_t*, const cuuint64_t*, const cuuint32_t*,
                          const cuuint32_t*, CUtensorMapInterleave, CUtensorMapSwizzle, CUtensorMapL2promotion, CUtensorMapFloatOOBfill);

extern "C" void kernel_launch(void* const* d_in, const int* in_sizes, int n_in, void* d_out, int out_size) {
    static EncFn enc = nullptr;
    static Scratch* scr = nullptr;
    if (!enc) {
        cudaGetSymbolAddress((void**)&scr, g_scr);
        cudaDriverEntryPointQueryResult qr;
        cudaGetDriverEntryPoint("cuTensorMapEncodeTiled", (void**)&enc, cudaEnableDefault, &qr);
        cudaFuncSetAttribute(fused_kernel, cudaFuncAttributeMaxDynamicSharedMemorySize, SMEM_BYTES);
    }
    CUtensorMap mx, mw, mwo;
    const cuuint32_t es[3] = {1, 1, 1};
    {
        cuuint64_t d[2] = {512, 2048}, s[1] = {1024}; cuuint32_t b[2] = {64, 128};
        enc(&mx, CU_TENSOR_MAP_DATA_TYPE_BFLOAT16, 2, d_in[0], d, s, b, es, CU_TENSOR_MAP_INTERLEAVE_NONE, CU_TENSOR_MAP_SWIZZLE_128B,
            CU_TENSOR_MAP_L2_PROMOTION_L2_128B, CU_TENSOR_MAP_FLOAT_OOB_FILL_NONE);
    }
    {
        cuuint64_t d[3] = {512, 512, 3}, s[2] = {3072, 1024}; cuuint32_t b[3] = {64, 64, 3};
        enc(&mw, CU_TENSOR_MAP_DATA_TYPE_BFLOAT16, 3, d_in[1], d, s, b, es, CU_TENSOR_MAP_INTERLEAVE_NONE, CU_TENSOR_MAP_SWIZZLE_128B,
            CU_TENSOR_MAP_L2_PROMOTION_L2_128B, CU_TENSOR_MAP_FLOAT_OOB_FILL_NONE);
    }
    {
        cuuint64_t d[2] = {512, 512}, s[1] = {1024}; cuuint32_t b[2] = {64, 256};
        enc(&mwo, CU_TENSOR_MAP_DATA_TYPE_BFLOAT16, 2, d_in[3], d, s, b, es, CU_TENSOR_MAP_INTERLEAVE_NONE, CU_TENSOR_MAP_SWIZZLE_128B,
            CU_TENSOR_MAP_L2_PROMOTION_L2_128B, CU_TENSOR_MAP_FLOAT_OOB_FILL_NONE);
    }
    fused_kernel<<<128, 512, SMEM_BYTES, cudaStreamPerThread>>>(
        scr, (const bf16*)d_in[5], (const bf16*)d_in[6], (const bf16*)d_in[7], (const bf16*)d_in[8], (const bf16*)d_in[9],
        (const bf16*)d_in[10], (const bf16*)d_in[2], (const bf16*)d_in[11], (bf16*)d_out, mx, mw, mwo);
}
```

```cpp
#include <cuda_runtime.h>
#include <cuda.h>
#include <cuda_bf16.h>
#include <stdint.h>

typedef __nv_bfloat16 bf16;

struct Scratch {
    uint4 xt[128 * 1024];
    uint4 o[16 * 8 * 32 * 32];
    uint4 y[128 * 1024];
    uint4 kvp[8 * 16 * 544];
    uint4 kvf[8 * 4 * 68];
    unsigned g[1024 * 8];
    unsigned xcnt[8 * 32];
    unsigned done[32];
};
__device__ Scratch g_scr;

constexpr int SLOT = 40960;
constexpr int OFF_SP0 = 32768, OFF_SP1 = SLOT + 32768;
constexpr int OFF_P = 2 * SLOT, OFF_V = OFF_P + 32768;
constexpr int OFF_KVF = OFF_V + 32768;
constexpr int KT_BYTES = 3264, KW_D = 16, KW_2 = 560, KW_3 = 656;
constexpr int OFF_U = 4 * SLOT, U_STRIDE = 4096 + 256 + 32;
constexpr int OFF_BUF = OFF_U + 4 * U_STRIDE, BUF_STRIDE = 8320;
constexpr int OFF_K = OFF_BUF + 4 * BUF_STRIDE;
constexpr int OFF_WPHI = OFF_K + 4 * KT_BYTES;
constexpr int OFF_GW = OFF_WPHI + 2048;
constexpr int OFF_BAR = OFF_GW + 1024;
constexpr int SMEM_BYTES = OFF_BAR + 320;
static_assert(SMEM_BYTES <= 232448 && OFF_BUF % 128 == 0, "smem");
constexpr int W5_OFF = 0, W3_OFF = 3088, W9_OFF = 6176;
constexpr int BAR_FULL = 0, BAR_EMPTY = 4, BAR_WPHI = 8, BAR_WO = 9, BAR_WO2 = 10, BAR_XT = 11, BAR_DONE = 12, BAR_KG = 13, BAR_SP = 14,
              BAR_PUB = 15, BAR_KVF = 16, BAR_UR = 17, BAR_WR = 18, BAR_PREP = 19, BAR_KGA = 20, BAR_SP2 = 21, BAR_KS = 22, BAR_KP = 26, BAR_KD = 30, OFF_CNT = 272;
constexpr int SPIN_LIMIT = 1 << 17;

__device__ __forceinline__ uint32_t s2u(const void* p) { return (uint32_t)__cvta_generic_to_shared(p); }
__device__ __forceinline__ void mbar_init(uint32_t b, int c) { asm volatile("mbarrier.init.shared::cta.b64 [%0],%1;" ::"r"(b), "r"(c) : "memory"); }
__device__ __forceinline__ void mbar_expect(uint32_t b, int bytes) { asm volatile("mbarrier.arrive.expect_tx.shared::cta.b64 _,[%0],%1;" ::"r"(b), "r"(bytes) : "memory"); }
__device__ __forceinline__ void mbar_arrive(uint32_t b) { asm volatile("mbarrier.arrive.shared::cta.b64 _,[%0];" ::"r"(b) : "memory"); }
__device__ __forceinline__ void mbar_wait(uint32_t b, int ph) {
    asm volatile("{\n.reg .pred p;\n.reg .u32 n;\nmov.u32 n,0;\nLW_%=:\nmbarrier.try_wait.parity.shared::cta.b64 p,[%0],%1;\n@p bra LD_%=;\n"
                 "add.u32 n,n,1;\nsetp.lt.u32 p,n,16384;\n@p bra LW_%=;\nLD_%=:\n}" ::"r"(b), "r"(ph) : "memory");
}
__device__ __forceinline__ void tma2d(uint32_t dst, const CUtensorMap* m, int c0, int c1, uint32_t bar) {
    asm volatile("cp.async.bulk.tensor.2d.shared::cluster.global.mbarrier::complete_tx::bytes [%0],[%1,{%3,%4}],[%2];" ::"r"(dst), "l"(m), "r"(bar), "r"(c0), "r"(c1) : "memory");
}
__device__ __forceinline__ void tma3d(uint32_t dst, const CUtensorMap* m, int c0, int c1, int c2, uint32_t bar) {
    asm volatile("cp.async.bulk.tensor.3d.shared::cluster.global.mbarrier::complete_tx::bytes [%0],[%1,{%3,%4,%5}],[%2];" ::"r"(dst), "l"(m), "r"(bar), "r"(c0), "r"(c1), "r"(c2) : "memory");
}
__device__ __forceinline__ void bulk_g2s(uint32_t dst, const void* src, int bytes, uint32_t bar) {
    asm volatile("cp.async.bulk.shared::cluster.global.mbarrier::complete_tx::bytes [%0],[%1],%2,[%3];" ::"r"(dst), "l"(src), "r"(bytes), "r"(bar) : "memory");
}
__device__ __forceinline__ uint64_t mkdesc(uint32_t addr, uint32_t lbo, uint32_t sbo) {
    return (uint64_t)((addr & 0x3FFFF) >> 4) | ((uint64_t)(lbo >> 4) << 16) | ((uint64_t)(sbo >> 4) << 32) | ((uint64_t)1 << 62);
}
__device__ __forceinline__ void wg_fence() { asm volatile("wgmma.fence.sync.aligned;" ::: "memory"); }
__device__ __forceinline__ void wg_commit() { asm volatile("wgmma.commit_group.sync.aligned;" ::: "memory"); }
template <int N> __device__ __forceinline__ void wg_wait() { asm volatile("wgmma.wait_group.sync.aligned %0;" ::"n"(N) : "memory"); }
template <int N> __device__ __forceinline__ void fence_regs(float* d) {
#pragma unroll
    for (int i = 0; i < N; i++) asm volatile("" : "+f"(d[i])::"memory");
}
#define R8(d, o) "+f"(d[o]), "+f"(d[o + 1]), "+f"(d[o + 2]), "+f"(d[o + 3]), "+f"(d[o + 4]), "+f"(d[o + 5]), "+f"(d[o + 6]), "+f"(d[o + 7])
__device__ __forceinline__ void wgmma192(float* d, uint64_t da, uint64_t db, int sc) {
    asm volatile("{.reg .pred p; setp.ne.b32 p,%98,0; wgmma.mma_async.sync.aligned.m64n192k16.f32.bf16.bf16 {"
                 "%0,%1,%2,%3,%4,%5,%6,%7,%8,%9,%10,%11,%12,%13,%14,%15,%16,%17,%18,%19,%20,%21,%22,%23,%24,%25,%26,%27,%28,%29,%30,%31,"
                 "%32,%33,%34,%35,%36,%37,%38,%39,%40,%41,%42,%43,%44,%45,%46,%47,%48,%49,%50,%51,%52,%53,%54,%55,%56,%57,%58,%59,%60,%61,%62,%63,"
                 "%64,%65,%66,%67,%68,%69,%70,%71,%72,%73,%74,%75,%76,%77,%78,%79,%80,%81,%82,%83,%84,%85,%86,%87,%88,%89,%90,%91,%92,%93,%94,%95},"
                 "%96,%97,p,1,1,0,1;}"
                 : R8(d, 0), R8(d, 8), R8(d, 16), R8(d, 24), R8(d, 32), R8(d, 40), R8(d, 48), R8(d, 56), R8(d, 64), R8(d, 72), R8(d, 80), R8(d, 88)
                 : "l"(da), "l"(db), "r"(sc));
}
__device__ __forceinline__ void wgmma64_tt(float* d, uint64_t da, uint64_t db, int sc) {
    asm volatile("{.reg .pred p; setp.ne.b32 p,%34,0; wgmma.mma_async.sync.aligned.m64n64k16.f32.bf16.bf16 {"
                 "%0,%1,%2,%3,%4,%5,%6,%7,%8,%9,%10,%11,%12,%13,%14,%15,%16,%17,%18,%19,%20,%21,%22,%23,%24,%25,%26,%27,%28,%29,%30,%31},"
                 "%32,%33,p,1,1,1,1;}"
                 : R8(d, 0), R8(d, 8), R8(d, 16), R8(d, 24)
                 : "l"(da), "l"(db), "r"(sc));
}
__device__ __forceinline__ void wgmma128_rs(float* d, const uint4& a, uint64_t db, int sc) {
    asm volatile("{.reg .pred p; setp.ne.b32 p,%69,0; wgmma.mma_async.sync.aligned.m64n128k16.f32.bf16.bf16 {"
                 "%0,%1,%2,%3,%4,%5,%6,%7,%8,%9,%10,%11,%12,%13,%14,%15,%16,%17,%18,%19,%20,%21,%22,%23,%24,%25,%26,%27,%28,%29,%30,%31,"
                 "%32,%33,%34,%35,%36,%37,%38,%39,%40,%41,%42,%43,%44,%45,%46,%47,%48,%49,%50,%51,%52,%53,%54,%55,%56,%57,%58,%59,%60,%61,%62,%63},"
                 "{%64,%65,%66,%67},%68,p,1,1,1;}"
                 : R8(d, 0), R8(d, 8), R8(d, 16), R8(d, 24), R8(d, 32), R8(d, 40), R8(d, 48), R8(d, 56)
                 : "r"(a.x), "r"(a.y), "r"(a.z), "r"(a.w), "l"(db), "r"(sc));
}
__device__ __forceinline__ void mma16816(float* c, uint32_t a0, uint32_t a1, uint32_t a2, uint32_t a3, uint32_t b0, uint32_t b1) {
    asm("mma.sync.aligned.m16n8k16.row.col.f32.bf16.bf16.f32 {%0,%1,%2,%3},{%4,%5,%6,%7},{%8,%9},{%0,%1,%2,%3};"
        : "+f"(c[0]), "+f"(c[1]), "+f"(c[2]), "+f"(c[3]) : "r"(a0), "r"(a1), "r"(a2), "r"(a3), "r"(b0), "r"(b1));
}
__device__ __forceinline__ void ldsm4(uint32_t* r, uint32_t a) {
    asm volatile("ldmatrix.sync.aligned.m8n8.x4.shared.b16 {%0,%1,%2,%3},[%4];" : "=r"(r[0]), "=r"(r[1]), "=r"(r[2]), "=r"(r[3]) : "r"(a) : "memory");
}
__device__ __forceinline__ void ldsm4t(uint32_t* r, uint32_t a) {
    asm volatile("ldmatrix.sync.aligned.m8n8.x4.trans.shared.b16 {%0,%1,%2,%3},[%4];" : "=r"(r[0]), "=r"(r[1]), "=r"(r[2]), "=r"(r[3]) : "r"(a) : "memory");
}
__device__ __forceinline__ void stsm4(uint32_t a, uint32_t r0, uint32_t r1, uint32_t r2, uint32_t r3) {
    asm volatile("stmatrix.sync.aligned.m8n8.x4.shared.b16 [%0],{%1,%2,%3,%4};" ::"r"(a), "r"(r0), "r"(r1), "r"(r2), "r"(r3) : "memory");
}
__device__ __forceinline__ uint32_t lds32(uint32_t a) { uint32_t v; asm volatile("ld.shared.b32 %0,[%1];" : "=r"(v) : "r"(a) : "memory"); return v; }
__device__ __forceinline__ uint4 lds128(uint32_t a) { uint4 v; asm volatile("ld.shared.v4.b32 {%0,%1,%2,%3},[%4];" : "=r"(v.x), "=r"(v.y), "=r"(v.z), "=r"(v.w) : "r"(a) : "memory"); return v; }
__device__ __forceinline__ void sts16(uint32_t a, uint32_t v) { asm volatile("st.shared.b16 [%0],%1;" ::"r"(a), "h"((unsigned short)v) : "memory"); }
__device__ __forceinline__ void sts32(uint32_t a, uint32_t v) { asm volatile("st.shared.b32 [%0],%1;" ::"r"(a), "r"(v) : "memory"); }
__device__ __forceinline__ void sts64(uint32_t a, uint32_t x, uint32_t y) { asm volatile("st.shared.v2.b32 [%0],{%1,%2};" ::"r"(a), "r"(x), "r"(y) : "memory"); }
__device__ __forceinline__ void sts128(uint32_t a, uint32_t x, uint32_t y, uint32_t z, uint32_t w) { asm volatile("st.shared.v4.b32 [%0],{%1,%2,%3,%4};" ::"r"(a), "r"(x), "r"(y), "r"(z), "r"(w) : "memory"); }
__device__ __forceinline__ uint32_t pack2(float lo, float hi) { uint32_t d; asm("cvt.rn.bf16x2.f32 %0,%1,%2;" : "=r"(d) : "f"(hi), "f"(lo)); return d; }
__device__ __forceinline__ float bf_lo(uint32_t v) { return __uint_as_float(v << 16); }
__device__ __forceinline__ float bf_hi(uint32_t v) { return __uint_as_float(v & 0xffff0000u); }
__device__ __forceinline__ float bf_round(float v) { return bf_lo(pack2(v, 0.f)); }
__device__ __forceinline__ uint32_t hmul2(uint32_t a, uint32_t b) { uint32_t d; asm("mul.rn.bf16x2 %0,%1,%2;" : "=r"(d) : "r"(a), "r"(b)); return d; }
__device__ __forceinline__ float ex2(float x) { float y; asm("ex2.approx.ftz.f32 %0,%1;" : "=f"(y) : "f"(x)); return y; }
__device__ __forceinline__ float rcp(float x) { float y; asm("rcp.approx.ftz.f32 %0,%1;" : "=f"(y) : "f"(x)); return y; }
__device__ __forceinline__ uint32_t ld_nc(const uint32_t* p) { uint32_t v; asm volatile("ld.global.nc.b32 %0,[%1];" : "=r"(v) : "l"(p)); return v; }
__device__ __forceinline__ unsigned ld_acq(const unsigned* p) { unsigned v; asm volatile("ld.acquire.gpu.global.u32 %0,[%1];" : "=r"(v) : "l"(p) : "memory"); return v; }
__device__ __forceinline__ unsigned ld_rlx(const unsigned* p) { unsigned v; asm volatile("ld.relaxed.gpu.global.u32 %0,[%1];" : "=r"(v) : "l"(p) : "memory"); return v; }
__device__ __forceinline__ uint2 ld_rlx64(const void* p) { uint2 v; asm volatile("{.reg .b64 t; ld.relaxed.gpu.global.b64 t,[%2]; mov.b64 {%0,%1},t;}" : "=r"(v.x), "=r"(v.y) : "l"(p) : "memory"); return v; }
__device__ __forceinline__ uint4 ld_rlx128(const void* p) {
    uint4 v;
    asm volatile("{.reg .b64 t,u; ld.relaxed.gpu.global.v2.b64 {t,u},[%4]; mov.b64 {%0,%1},t; mov.b64 {%2,%3},u;}" : "=r"(v.x), "=r"(v.y), "=r"(v.z), "=r"(v.w) : "l"(p) : "memory");
    return v;
}
__device__ __forceinline__ void st_rlx32(void* p, uint32_t x) { asm volatile("st.relaxed.gpu.global.u32 [%0],%1;" ::"l"(p), "r"(x) : "memory"); }
__device__ __forceinline__ void st_rlx64(void* p, uint32_t x, uint32_t y) { asm volatile("{.reg .b64 t; mov.b64 t,{%1,%2}; st.relaxed.gpu.global.b64 [%0],t;}" ::"l"(p), "r"(x), "r"(y) : "memory"); }
__device__ __forceinline__ void st_rlx128(void* p, uint4 v) {
    asm volatile("{.reg .b64 t,u; mov.b64 t,{%1,%2}; mov.b64 u,{%3,%4}; st.relaxed.gpu.global.v2.b64 [%0],{t,u};}" ::"l"(p), "r"(v.x), "r"(v.y), "r"(v.z), "r"(v.w) : "memory");
}
__device__ __forceinline__ uint32_t tagw(uint32_t w, uint32_t tag) { return (w & ~1u) | tag; }
__device__ __forceinline__ uint4 tag4(uint32_t x, uint32_t y, uint32_t z, uint32_t w, uint32_t tag) { return make_uint4(tagw(x, tag), y, tagw(z, tag), w); }
__device__ __forceinline__ uint32_t bad4(const uint4& v, uint32_t tag) { return (v.x ^ tag) | (v.z ^ tag); }
__device__ __forceinline__ void bar_named(int id, int n) { asm volatile("bar.sync %0,%1;" ::"r"(id), "r"(n) : "memory"); }

struct cf { float re, im; };
__device__ __forceinline__ cf cmul(cf a, cf b) { cf r; r.re = a.re * b.re - a.im * b.im; r.im = a.re * b.im + a.im * b.re; return r; }
__device__ __forceinline__ cf cexp_p(float arl, float ait, float p) {
    float mag = ex2(arl * p);
    float t = ait * p;
    const float big = 12582912.f;
    t = (t - ((t + big) - big)) * 6.283185307179586f;
    cf r; r.re = mag * __cosf(t); r.im = mag * __sinf(t);
    return r;
}

__device__ __forceinline__ void hedgehog4(const uint32_t* a, uint32_t wphi_addr, uint32_t (*out)[8]) {
    float p[4][2][4], mx[4][2];
#pragma unroll
    for (int h = 0; h < 4; h++) {
        uint32_t b[4];
        ldsm4t(b, wphi_addr + h * 512);
        float c0[4] = {0.f, 0.f, 0.f, 0.f}, c1[4] = {0.f, 0.f, 0.f, 0.f};
        mma16816(c0, a[4 * h], a[4 * h + 1], a[4 * h + 2], a[4 * h + 3], b[0], b[1]);
        mma16816(c1, a[4 * h], a[4 * h + 1], a[4 * h + 2], a[4 * h + 3], b[2], b[3]);
#pragma unroll
        for (int k = 0; k < 2; k++) {
            p[h][k][0] = c0[2 * k]; p[h][k][1] = c0[2 * k + 1]; p[h][k][2] = c1[2 * k]; p[h][k][3] = c1[2 * k + 1];
            mx[h][k] = fmaxf(fmaxf(p[h][k][0], p[h][k][1]), fmaxf(p[h][k][2], p[h][k][3]));
        }
    }
#pragma unroll
    for (int o = 1; o <= 2; o <<= 1)
#pragma unroll
        for (int h = 0; h < 4; h++)
#pragma unroll
            for (int k = 0; k < 2; k++) mx[h][k] = fmaxf(mx[h][k], __shfl_xor_sync(~0u, mx[h][k], o));
    const float L = 1.4426950408889634f;
    float pmin = 1.f;
#pragma unroll
    for (int h = 0; h < 4; h++)
#pragma unroll
        for (int k = 0; k < 2; k++) {
            const float m = -mx[h][k] * L;
            const float e0 = ex2(fmaf(p[h][k][0], L, m)), e1 = ex2(fmaf(p[h][k][1], L, m)), e2 = ex2(fmaf(p[h][k][2], L, m)), e3 = ex2(fmaf(p[h][k][3], L, m));
            const float p01 = e0 * e1, p23 = e2 * e3, pp = p01 * p23, r = rcp(pp), r01 = r * p23, r23 = r * p01;
            pmin = fminf(pmin, pp);
            out[h][k] = pack2(e0, e1); out[h][k + 2] = pack2(e2, e3);
            out[h][4 + k] = pack2(r01 * e1, r01 * e0); out[h][4 + k + 2] = pack2(r23 * e3, r23 * e2);
        }
    if (__builtin_expect(__any_sync(~0u, !(pmin > 1e-18f)), 0)) {
#pragma unroll
        for (int h = 0; h < 4; h++)
#pragma unroll
            for (int k = 0; k < 2; k++) {
                float m = fminf(fminf(p[h][k][0], p[h][k][1]), fminf(p[h][k][2], p[h][k][3]));
                m = fminf(m, __shfl_xor_sync(~0u, m, 1));
                m = fminf(m, __shfl_xor_sync(~0u, m, 2)) * L;
                out[h][4 + k] = pack2(ex2(fmaf(p[h][k][0], -L, m)), ex2(fmaf(p[h][k][1], -L, m)));
                out[h][4 + k + 2] = pack2(ex2(fmaf(p[h][k][2], -L, m)), ex2(fmaf(p[h][k][3], -L, m)));
            }
    }
}

__global__ void __launch_bounds__(512, 1)
fused_kernel(Scratch* __restrict__ scr, const bf16* __restrict__ logA, const bf16* __restrict__ Aim, const bf16* __restrict__ Cre,
             const bf16* __restrict__ Cim, const bf16* __restrict__ logdt, const bf16* __restrict__ Dskip, const bf16* __restrict__ wphi,
             const bf16* __restrict__ gatew, bf16* __restrict__ out,
             const __grid_constant__ CUtensorMap mx, const __grid_constant__ CUtensorMap mw, const __grid_constant__ CUtensorMap mwo) {
    extern __shared__ __align__(1024) uint8_t smem[];
    constexpr uint32_t sb = 1024;
    const int tid = threadIdx.x, warp = __shfl_sync(~0u, tid >> 5, 0), lane = tid & 31;
    const int g = lane >> 2, q = lane & 3, w4 = warp & 3;
    const int bi = blockIdx.x, bi_i = bi & 15, bi_j = bi >> 4;
    const uint32_t bar = sb + OFF_BAR;
    const int rot = (bi_j & 3) * 2, xkb = bi_j >> 2;
    auto load_stage = [&](int kb) {
        const uint32_t b = bar + 8 * (BAR_FULL + (kb & 3)), d = sb + (kb & 3) * SLOT;
        const int kc = ((kb + rot) & 7) * 64;
        mbar_expect(b, SLOT);
        tma2d(d, &mx, kc, bi_i * 128, b);
        tma3d(d + 16384, &mw, bi_j * 64, kc, 0, b);
    };

    const int ch = bi * 4 + w4;
    const int pidx = ch * 64 + lane * 2 + (warp >> 3);
    const uint32_t pla = ld_nc((const uint32_t*)logA + pidx), pai = ld_nc((const uint32_t*)Aim + pidx);
    const uint32_t pcr = ld_nc((const uint32_t*)Cre + pidx), pci = ld_nc((const uint32_t*)Cim + pidx);
    uint32_t pdt = ld_nc((const uint32_t*)logdt + (ch >> 1));
    const uint32_t pds = ld_nc((const uint32_t*)Dskip + (ch >> 1));
    unsigned done0 = ld_rlx(scr->done);
    if (tid == 0) {
        for (int s = 0; s < 4; s++) mbar_init(bar + 8 * (BAR_FULL + s), 1);
        asm volatile("fence.mbarrier_init.release.cluster;" ::: "memory");
        asm volatile("prefetch.tensormap [%0];" ::"l"(&mx) : "memory");
        load_stage(0); load_stage(1);
    } else if (tid == 32) {
        if (s2u(smem) != sb) __trap();
        sts32(bar + OFF_CNT, 0);
        for (int s = 0; s < 4; s++) { mbar_init(bar + 8 * (BAR_EMPTY + s), 9); mbar_init(bar + 8 * (BAR_KS + s), 1); mbar_init(bar + 8 * (BAR_KP + s), 3); mbar_init(bar + 8 * (BAR_KD + s), 1); }
        mbar_init(bar + 8 * BAR_WPHI, 1); mbar_init(bar + 8 * BAR_WO, 2); mbar_init(bar + 8 * BAR_WO2, 1); mbar_init(bar + 8 * BAR_XT, 4);
        mbar_init(bar + 8 * BAR_DONE, 9); mbar_init(bar + 8 * BAR_KG, 8); mbar_init(bar + 8 * BAR_PUB, 8);
        mbar_init(bar + 8 * BAR_KVF, 4); mbar_init(bar + 8 * BAR_UR, 4); mbar_init(bar + 8 * BAR_WR, 4); mbar_init(bar + 8 * BAR_PREP, 4); mbar_init(bar + 8 * BAR_KGA, 4); mbar_init(bar + 8 * BAR_SP2, 1);
        asm volatile("fence.mbarrier_init.release.cluster;" ::: "memory");
        mbar_expect(bar + 8 * BAR_WPHI, 3072);
        bulk_g2s(sb + OFF_GW, gatew, 1024, bar + 8 * BAR_WPHI);
        bulk_g2s(sb + OFF_WPHI, wphi + bi_j * 1024, 2048, bar + 8 * BAR_WPHI);
    } else if (tid == 64) {
        asm volatile("prefetch.tensormap [%0];" ::"l"(&mw) : "memory");
    }
    const uint32_t buf = sb + OFF_BUF + w4 * BUF_STRIDE, kb_ = sb + OFF_K + w4 * KT_BYTES;
    if ((warp >> 2) == 2) {
#pragma unroll
        for (int v = 0; v < 7; v++) if (v * 32 + lane < KT_BYTES / 16) sts128(kb_ + (v * 32 + lane) * 16, 0, 0, 0, 0);
    }
    __syncthreads();
    asm volatile("" : "+r"(pdt), "+r"(done0)::"memory");
    const unsigned epoch1 = (done0 >> 7) + 1u;
    const uint32_t tag = epoch1 & 1u;

    const int st = tid & 127;
    const uint32_t ub = sb + OFF_U + w4 * U_STRIDE + 256, spare = sb + (w4 < 2 ? OFF_SP0 : OFF_SP1) + (w4 & 1) * 4096;

    auto stg_of = [&](int w) { return w < 8 ? sb + 3 * SLOT + w * 7296 : sb + 2 * SLOT + (w & 3) * 7296; };
    float kc[24];
#pragma unroll
    for (int t = 0; t < 24; t++) kc[t] = 0.f;
    auto handoff = [&](int src) {
        mbar_wait(bar + 8 * (BAR_KS + w4), 0);
#pragma unroll
        for (int t = 0; t < 5; t++)
            sts128(buf + src * 2560 + (t * 32 + lane) * 16, __float_as_uint(kc[4 * t]), __float_as_uint(kc[4 * t + 1]), __float_as_uint(kc[4 * t + 2]), __float_as_uint(kc[4 * t + 3]));
        if (lane == 0) sts32(buf + 7680 + src * 4, __float_as_uint(kc[20]));
        __syncwarp();
        if (lane == 0) mbar_arrive(bar + 8 * (BAR_KP + w4));
    };
    {
        const float dt = bf_round(expf((ch & 1) ? bf_hi(pdt) : bf_lo(pdt)));
        const uint32_t stg = (warp >> 2) == 2 ? buf : stg_of(warp);
        const int sh = ((warp >> 2) & 1) * 16;
        auto pick = [&](uint32_t v) { return __uint_as_float((v >> sh) << 16); };
        const float ea = bf_round(ex2(pick(pla) * 1.4426950408889634f));
        const float arl = (-ea * dt) * 1.4426950408889634f, ait = (pick(pai) * dt) * 0.15915494309189535f;
        cf C2; C2.re = 2.0f * (pick(pcr) * dt); C2.im = 2.0f * (pick(pci) * dt);
        const cf z1 = cexp_p(arl, ait, 1.0f), z128 = cexp_p(arl, ait, 128.0f);
        const cf z2 = cmul(z1, z1), z4 = cmul(z2, z2);
        cf z8 = cmul(z4, z4); z8.im = -z8.im;
        const uint32_t sa0 = stg + (lane >> 3) * 128 + (((lane & 7) ^ (lane >> 3)) << 4), sa1 = (sa0 ^ 64) + 512;
        uint32_t w[60];
        auto put = [&](int row, const cf& v) {
            w[row] = pack2(v.re, v.im);
            if ((row & 3) == 3) stsm4(((row & 4) ? sa1 : sa0) + (row >> 3) * 1024, w[row - 3], w[row - 2], w[row - 1], w[row]);
        };
        {
            const cf z16 = cmul(z8, z8);
            cf e; e.re = 1.f; e.im = 0.f;
            cf o = z8;
            put(0, e); put(1, o);
            e = z16; put(2, e);
#pragma unroll
            for (int b = 3; b < 16; b += 2) {
                o = cmul(o, z16); put(b, o);
                if (b + 1 < 16) { e = cmul(e, z16); put(b + 1, e); }
            }
        }
        cf h[8];
        h[0] = C2; h[1] = cmul(h[0], z1);
#pragma unroll
        for (int r = 2; r < 8; r++) h[r] = cmul(h[r - 2], z2);
#pragma unroll
        for (int r = 0; r < 8; r++) put(16 + r, h[r]);
#pragma unroll
        for (int r = 0; r < 8; r++) { h[r] = cmul(h[r], z128); put(24 + r, h[r]); }
#pragma unroll
        for (int al = 0; al < 2; al++)
#pragma unroll
            for (int r = 0; r < 4; r++) { h[2 * r] = cmul(h[2 * r], z128); put(32 + al * 4 + r, h[2 * r]); }
#pragma unroll
        for (int al = 0; al < 4; al++)
#pragma unroll
            for (int r = 0; r < 2; r++) { h[4 * r] = cmul(h[4 * r], z128); put(40 + al * 2 + r, h[4 * r]); }
#pragma unroll
        for (int al = 0; al < 8; al++) { h[0] = cmul(h[0], z128); put(48 + al, h[0]); }
        h[0] = cmul(h[0], z128);
        sts32(stg + 56 * 128 + lane * 4, pack2(h[0].re, h[0].im));
        __syncwarp();
        const int lr = lane & 7, lm = lane >> 3;
#pragma unroll
        for (int kp = 0; kp < 2; kp++) {
            uint32_t a0[4], a1[4];
            ldsm4(a0, stg + ((lm & 1) * 8 + lr) * 128 + (((4 * kp + (lm >> 1)) ^ lr) << 4));
            ldsm4(a1, stg + ((lm & 1) * 8 + lr) * 128 + (((4 * kp + 2 + (lm >> 1)) ^ lr) << 4));
#pragma unroll
            for (int t = 0; t < 6; t++) {
                uint32_t b[4];
                ldsm4(b, stg + (16 + 8 * t + lr) * 128 + (((4 * kp + lm) ^ lr) << 4));
                mma16816(kc + 4 * t, a0[0], a0[1], a0[2], a0[3], b[0], b[1]);
                mma16816(kc + 4 * t, a1[0], a1[1], a1[2], a1[3], b[2], b[3]);
            }
        }
        __syncwarp();
        asm volatile("fence.proxy.async.shared::cta;" ::: "memory");
        const uint32_t cnt = 1u + (__float_as_uint(kc[0] + kc[23]) == 0xffc12345u);
        if (lane == 0) asm volatile("mbarrier.arrive.shared::cta.b64 _,[%0],%1;" ::"r"(bar + 8 * (warp < 8 ? BAR_KG : (warp < 12 ? BAR_KS + w4 : BAR_KGA))), "r"(cnt) : "memory");
        if (warp < 8) handoff(warp >> 2);
    }

    if (warp < 8) {
        const int wg = warp >> 2;
        float acc[96];
        const int srow = warp * 16 + (lane & 15);
        const uint32_t srow_a = srow * 128;
        const int sx = srow & 7, shi = lane >> 4;
        const uint64_t da0 = mkdesc(sb + wg * 8192, 16, 1024), db0 = mkdesc(sb + 16384, 8192, 1024);
#pragma unroll 1
        for (int kb = 0; kb < 8; kb++) {
            const int s = kb & 3;
            const uint64_t da = da0 + s * (SLOT >> 4), db = db0 + s * (SLOT >> 4);
            mbar_wait(bar + 8 * (BAR_FULL + s), kb >> 2);
            wg_fence();
#pragma unroll
            for (int k = 0; k < 4; k++) wgmma192(acc, da + 2 * k, db + 128 * k, kb | k);
            wg_commit();
            wg_wait<1>();
            if (lane == 0 && kb > 0) mbar_arrive(bar + 8 * (BAR_EMPTY + ((kb - 1) & 3)));
        }
        mbar_wait(bar + 8 * BAR_WPHI, 0);
        wg_wait<0>();
        fence_regs<96>(acc);
        asm volatile("setmaxnreg.inc.sync.aligned.u32 160;");
        if (lane == 0) mbar_arrive(bar + 8 * BAR_DONE);
        uint32_t in[16], qa[16];
        mbar_wait(bar + 8 * BAR_DONE, 0);
#pragma unroll
        for (int r = 0; r < 16; r++) {
            in[r] = pack2(acc[32 + 2 * r], acc[32 + 2 * r + 1]);
            qa[r] = pack2(acc[2 * r], acc[2 * r + 1]);
        }
#pragma unroll
        for (int hh = 0; hh < 4; hh++)
            stsm4(sb + OFF_V + (hh >> 1) * 16384 + srow_a + (((2 * (hh & 1) + shi) ^ sx) << 4), pack2(acc[64 + 8 * hh], acc[65 + 8 * hh]),
                  pack2(acc[66 + 8 * hh], acc[67 + 8 * hh]), pack2(acc[68 + 8 * hh], acc[69 + 8 * hh]), pack2(acc[70 + 8 * hh], acc[71 + 8 * hh]));
        sts128(sb + OFF_V + shi * 16384 + srow_a + ((4 ^ sx) << 4), 0x3f803f80u, 0x3f803f80u, 0x3f803f80u, 0x3f803f80u);
        const uint32_t wphi_a = sb + OFF_WPHI + (lane & 15) * 32 + (lane >> 4) * 16;
        uint32_t pq[4][8];
#pragma unroll 1
        for (int it = 0; it < 2; it++) {
            hedgehog4(in, wphi_a, pq);
            if (it == 1) break;
#pragma unroll
            for (int hs = 0; hs < 8; hs++) {
                float c[4] = {0.f, 0.f, 0.f, 0.f};
                const uint32_t* o = pq[hs >> 1] + 4 * (hs & 1);
                mma16816(c, o[0], o[1], o[2], o[3], 0x3f803f80u, 0x3f803f80u);
                const float r0 = rcp(c[0]), r1 = rcp(c[2]);
                const uint32_t s0 = pack2(r0, r0), s1 = pack2(r1, r1);
                stsm4(sb + OFF_P + (hs >> 2) * 16384 + srow_a + (((2 * (hs & 3) + shi) ^ sx) << 4), hmul2(o[0], s0), hmul2(o[1], s1), hmul2(o[2], s0), hmul2(o[3], s1));
            }
            asm volatile("fence.proxy.async.shared::cta;" ::: "memory");
            bar_named(1, 256);
            float d[32];
            const uint64_t dv = mkdesc(sb + OFF_V + wg * 16384, 16, 1024), dp = mkdesc(sb + OFF_P + wg * 16384, 16, 1024);
            wg_fence();
#pragma unroll
            for (int k = 0; k < 8; k++) wgmma64_tt(d, dv + 128 * k, dp + 128 * k, k != 0);
            wg_commit();
            mbar_wait(bar + 8 * BAR_PREP, 0);
            uint4* kvp = scr->kvp + bi * 544 + wg * 272 + (w4 < 2 ? w4 * 136 : 128) + lane;
            wg_wait<0>();
            fence_regs<32>(d);
            if (w4 < 2 || (w4 == 2 && lane < 4)) {
#pragma unroll
                for (int f = 0; f < 4; f++) {
                    const int i0 = 8 * (f >> 1) + 2 * (f & 1), i2 = 16 * (f >> 1) + 8 * (f & 1);
                    const float e0 = w4 == 0 ? d[i0] : (w4 == 1 ? d[16 + i0] : d[i2]), e1 = w4 == 0 ? d[i0 + 1] : (w4 == 1 ? d[17 + i0] : d[i2 + 1]);
                    const float e2 = w4 == 0 ? d[i0 + 4] : (w4 == 1 ? d[20 + i0] : d[i2 + 4]), e3 = w4 == 0 ? d[i0 + 5] : (w4 == 1 ? d[21 + i0] : d[i2 + 5]);
                    st_rlx128(kvp + (w4 < 2 ? f * 32 : (f >> 1) * 136 + (f & 1) * 4), tag4(__float_as_uint(e0), __float_as_uint(e1), __float_as_uint(e2), __float_as_uint(e3), tag));
                }
            }
            __syncwarp();
            if (lane == 0) mbar_arrive(bar + 8 * BAR_PUB);
#pragma unroll
            for (int r = 0; r < 16; r++) in[r] = qa[r];
        }
        {
            mbar_wait(bar + 8 * BAR_KVF, 0);
            uint4 kf[4][3];
#pragma unroll
            for (int hh = 0; hh < 4; hh++) {
                const uint32_t a = sb + OFF_KVF + hh * 1088;
                kf[hh][0] = lds128(a + lane * 32); kf[hh][1] = lds128(a + lane * 32 + 16); kf[hh][2] = lds128(a + 1024 + q * 16);
            }
            uint4* og = scr->o + ((bi_i * 8 + warp) * 32 + bi_j * 4) * 32 + lane;
#pragma unroll
            for (int hh = 0; hh < 4; hh++) {
                float c[6][4];
#pragma unroll
                for (int t = 0; t < 6; t++) { c[t][0] = c[t][1] = c[t][2] = c[t][3] = 0.f; }
                const uint32_t* a = pq[hh];
                const bool od = g & 1;
                mma16816(c[0], a[0], a[1], a[2], a[3], od ? 0x3f803f80u : kf[hh][2].x, od ? 0x3f803f80u : kf[hh][2].y);
                mma16816(c[1], a[4], a[5], a[6], a[7], od ? 0x3f803f80u : kf[hh][2].z, od ? 0x3f803f80u : kf[hh][2].w);
                mma16816(c[2], a[0], a[1], a[2], a[3], kf[hh][0].x, kf[hh][0].y);
                mma16816(c[3], a[0], a[1], a[2], a[3], kf[hh][0].z, kf[hh][0].w);
                mma16816(c[4], a[4], a[5], a[6], a[7], kf[hh][1].x, kf[hh][1].y);
                mma16816(c[5], a[4], a[5], a[6], a[7], kf[hh][1].z, kf[hh][1].w);
                uint32_t w[4];
#pragma unroll
                for (int k = 0; k < 2; k++) {
                    const float rho = c[0][2 * k + 1] * rcp(c[1][2 * k + 1]);
                    const float r = rcp(fmaf(c[0][2 * k + 1], 1e-6f, fmaf(rho, c[1][2 * k], c[0][2 * k]))), rr = r * rho;
                    w[k] = pack2(fmaf(c[4][2 * k], rr, c[2][2 * k] * r), fmaf(c[4][2 * k + 1], rr, c[2][2 * k + 1] * r));
                    w[2 + k] = pack2(fmaf(c[5][2 * k], rr, c[3][2 * k] * r), fmaf(c[5][2 * k + 1], rr, c[3][2 * k + 1] * r));
                }
                st_rlx128(og + hh * 32, tag4(w[0], w[1], w[2], w[3], tag));
            }
        }
        float oc[64];
        const int slab = bi_i * 8 + (bi_j >> 2) * 4 + w4;
        const uint8_t* ysrc = (const uint8_t*)scr->y + (size_t)((bi_j & 3) * 32 + wg * 16 + (q >> 1)) * 16384 + slab * 128 + g * 16 + (q & 1) * 8;
        const unsigned* gp = scr->g + (slab * 8 + (g >> 1)) * 8 + (g & 1) * 4;
        uint2 yv[8]; unsigned g0, g1;
        {
            const uint4* osrc = scr->o + (slab * 32 + wg * 16) * 32 + lane;
            uint4 fr[16];
            const unsigned* probe = (const unsigned*)(osrc - lane + ((lane & 3) * 4 + 3) * 32 + 31) + 2;
            {
                unsigned miss = ~0u;
                int n = 0;
#pragma unroll
                for (int s = 0; s < 4; s++) {
#pragma unroll 1
                    while ((miss >> s) & 1) { miss = __ballot_sync(~0u, (ld_rlx(probe) ^ tag) & 1); if (++n > SPIN_LIMIT) break; }
#pragma unroll
                    for (int k = 4 * s; k < 4 * s + 4; k++) fr[k] = ld_rlx128(osrc + k * 32);
                }
            }
            mbar_wait(bar + 8 * (wg ? BAR_WO2 : BAR_WO), 0);
            const uint64_t dw = mkdesc(sb + wg * 2 * SLOT, wg ? 32768 : SLOT, 1024);
#pragma unroll
            for (int s = 0; s < 4; s++) {
                int n = 0;
#pragma unroll 1
                while (__builtin_expect(__any_sync(~0u, (bad4(fr[4 * s], tag) | bad4(fr[4 * s + 1], tag) | bad4(fr[4 * s + 2], tag) | bad4(fr[4 * s + 3], tag)) & 1), 0)) {
#pragma unroll
                    for (int k = 4 * s; k < 4 * s + 4; k++) fr[k] = ld_rlx128(osrc + k * 32);
                    if (++n > SPIN_LIMIT) break;
                }
                wg_fence();
#pragma unroll
                for (int hh = 0; hh < 4; hh++) wgmma128_rs(oc, fr[4 * s + hh], dw + 128 * (4 * s + hh), (s | hh) != 0);
                wg_commit();
                if (s == 1) {
                    wg_wait<1>();
#pragma unroll
                    for (int nt = 0; nt < 8; nt++) yv[nt] = ld_rlx64(ysrc + nt * 32768);
                    g0 = ld_rlx(gp); g1 = ld_rlx(gp + 32);
                }
            }
            {
                int n = 0;
#pragma unroll 1
                while (true) {
                    uint32_t bad = (g0 ^ tag) | (g1 ^ tag);
#pragma unroll
                    for (int nt = 0; nt < 8; nt++) bad |= yv[nt].x ^ tag;
                    if (!__any_sync(~0u, bad & 1)) break;
#pragma unroll
                    for (int nt = 0; nt < 8; nt++) if ((yv[nt].x ^ tag) & 1) yv[nt] = ld_rlx64(ysrc + nt * 32768);
                    g0 = ld_rlx(gp); g1 = ld_rlx(gp + 32);
                    if (++n > SPIN_LIMIT) break;
                }
            }
        }
        {
            const float ga = bf_hi(g0), gb = bf_hi(g1);
            const float ha = bf_round(1.0f - ga), hb = bf_round(1.0f - gb);
            float yb[32];
#pragma unroll
            for (int nt = 0; nt < 8; nt++) {
                yb[4 * nt] = ha * bf_lo(yv[nt].x); yb[4 * nt + 1] = ha * bf_hi(yv[nt].x);
                yb[4 * nt + 2] = hb * bf_lo(yv[nt].y); yb[4 * nt + 3] = hb * bf_hi(yv[nt].y);
            }
            fence_regs<32>(yb);
            const uint32_t xw = sb + wg * 2 * SLOT + (tid & 127) * 16, xr = sb + (wg ^ 1) * 2 * SLOT + (tid & 127) * 16;
            wg_wait<0>();
            fence_regs<64>(oc);
            bar_named(3 + wg, 128);
#pragma unroll
            for (int r = 0; r < 8; r++)
                sts128(xw + r * 2048, __float_as_uint(oc[32 + 4 * r]), __float_as_uint(oc[33 + 4 * r]), __float_as_uint(oc[34 + 4 * r]), __float_as_uint(oc[35 + 4 * r]));
#pragma unroll
            for (int r = 0; r < 32; r++) yb[r] = fmaf((r & 2) ? gb : ga, oc[r], yb[r]);
            bar_named(1, 256);
            uint32_t w[8][2];
#pragma unroll
            for (int nt = 0; nt < 8; nt++) {
                const uint4 p = lds128(xr + nt * 2048);
                w[nt][0] = pack2(fmaf(ga, __uint_as_float(p.x), yb[4 * nt]), fmaf(ga, __uint_as_float(p.y), yb[4 * nt + 1]));
                w[nt][1] = pack2(fmaf(gb, __uint_as_float(p.z), yb[4 * nt + 2]), fmaf(gb, __uint_as_float(p.w), yb[4 * nt + 3]));
            }
            const uint32_t ob = sb + wg * 2 * SLOT + 16384 + w4 * 2048;
#pragma unroll
            for (int nt = 0; nt < 8; nt += 2)
                stsm4(ob + (lane & 15) * 128 + (((nt + shi) ^ (lane & 7)) << 4), w[nt][0], w[nt][1], w[nt + 1][0], w[nt + 1][1]);
            __syncwarp();
            bf16* op = out + (size_t)(slab * 16) * 512 + (bi_j & 3) * 128 + wg * 64 + (lane & 7) * 8;
#pragma unroll
            for (int it = 0; it < 4; it++) {
                const int r = it * 4 + (lane >> 3);
                uint4 v = lds128(ob + r * 128 + (((lane & 7) ^ (r & 7)) << 4));
                *(uint4*)(op + r * 512) = v;
            }
        }
    } else if (warp < 12) {
        if (warp == 8) {
            mbar_wait(bar + 8 * BAR_KGA, 0);
            if (lane == 0) load_stage(2);
            mbar_wait(bar + 8 * BAR_KG, 0);
            if (lane == 0) load_stage(3);
            __syncwarp();
        }
        if (warp == 8) {
#pragma unroll 1
            for (int kb = 0; kb < 6; kb++) {
                const int s = kb & 3;
                mbar_wait(bar + 8 * (BAR_EMPTY + s), kb >> 2);
                if (kb == xkb) mbar_wait(bar + 8 * BAR_XT, 0);
                if (lane == 0) {
                    if (kb < 4) load_stage(kb + 4);
                    else {
                        mbar_expect(bar + 8 * BAR_WO, 32768);
                        tma2d(sb + s * SLOT, &mwo, (bi_j & 3) * 128 + s * 64, 0, bar + 8 * BAR_WO);
                        if (kb == 5) mbar_arrive(bar + 8 * BAR_SP2);
                    }
                }
                __syncwarp();
            }
        } else if (warp == 9) {
            const int row = bi_j * 16 + (lane >> 1), half = lane & 1;
            unsigned* gp = scr->g + (bi_i * 64 + bi_j * 8) * 8 + lane * 2;
            st_rlx64(gp, tag ^ 1u, tag ^ 1u);
            float gs0 = 0.f, gs1 = 0.f;
            mbar_wait(bar + 8 * BAR_WPHI, 0);
#pragma unroll 1
            for (int kb = 0; kb < 8; kb++) {
                const int s = kb & 3;
                mbar_wait(bar + 8 * (BAR_FULL + s), kb >> 2);
#pragma unroll
                for (int c = 0; c < 4; c++) {
                    const uint4 xv = lds128(sb + s * SLOT + row * 128 + (((half * 4 + c) ^ (row & 7)) << 4));
                    const uint4 gw = lds128(sb + OFF_GW + ((kb + rot) & 7) * 128 + half * 64 + c * 16);
                    const uint32_t p0 = hmul2(xv.x, gw.x), p1 = hmul2(xv.y, gw.y), p2 = hmul2(xv.z, gw.z), p3 = hmul2(xv.w, gw.w);
                    gs0 += (bf_lo(p0) + bf_lo(p1)) + (bf_lo(p2) + bf_lo(p3));
                    gs1 += (bf_hi(p0) + bf_hi(p1)) + (bf_hi(p2) + bf_hi(p3));
                }
                const uint32_t cnt = 1u + (__float_as_uint(gs0 + gs1) == 0xffc12345u);
                if (lane == 0) asm volatile("mbarrier.arrive.shared::cta.b64 _,[%0],%1;" ::"r"(bar + 8 * (kb < 7 ? BAR_EMPTY + s : BAR_DONE)), "r"(cnt) : "memory");
                __syncwarp();
            }
            float gs = gs0 + gs1;
            gs += __shfl_xor_sync(~0u, gs, 1);
            const uint32_t gv = __float_as_uint(bf_round(rcp(1.0f + ex2(-1.4426950408889634f * bf_round(gs))))) | tag;
            st_rlx64(gp, gv, gv);
        }
        mbar_wait(bar + 8 * (BAR_KP + w4), 0);
#pragma unroll
        for (int t = 0; t < 15; t++) {
            const uint4 v = lds128(buf + (t * 32 + lane) * 16);
            kc[4 * (t % 5)] += __uint_as_float(v.x); kc[4 * (t % 5) + 1] += __uint_as_float(v.y); kc[4 * (t % 5) + 2] += __uint_as_float(v.z); kc[4 * (t % 5) + 3] += __uint_as_float(v.w);
        }
        {
            const uint4 v = lds128(buf + 7680);
            kc[20] += __uint_as_float(v.x) + __uint_as_float(v.y) + __uint_as_float(v.z);
            const uint32_t cnt = 1u + (__float_as_uint(kc[20] + kc[19] + kc[0]) == 0xffc12345u);
            if (lane == 0) asm volatile("mbarrier.arrive.shared::cta.b64 _,[%0],%1;" ::"r"(bar + 8 * (BAR_KD + w4)), "r"(cnt) : "memory");
            __syncwarp();
        }
        if (lane == 0) kc[4 * 0 + 0] += ((ch & 1) ? bf_hi(pds) : bf_lo(pds));
        const uint32_t k1024 = __shfl_sync(~0u, pack2(kc[4 * 4 + 0], 0.f), 0);
#pragma unroll
        for (int i = 0; i < 2; i++) {
            const int be = g + 8 * i;
#pragma unroll
            for (int t = 0; t < 2; t++) {
                const uint32_t a = kb_ + (KW_D + 128 * t + 8 * be + 2 * q) * 4;
                const uint32_t w = pack2(kc[4 * t + 2 * i + 1], kc[4 * t + 2 * i]);
                sts32(a + 4, w); sts16(a, w >> 16); sts16(a + 10, w);
            }
            {
                const int p = 256 + 128 * (q >> 1) + 8 * be + 4 * (q & 1);
                const uint32_t a = kb_ + (KW_D + p) * 4;
                const uint32_t w = pack2(kc[4 * 2 + 2 * i + 1], kc[4 * 2 + 2 * i]);
                const uint32_t aa = (w >> 16) | (w & 0xffff0000u);
                if (p != 256) { sts16(a - 4, aa); sts32(a, aa); } else sts16(a, aa);
                sts32(a + 4, aa); sts32(a + 8, w); sts16(a + 14, w);
            }
            {
                const int k = 64 + 16 * q + be;
                const uint32_t w = pack2(kc[4 * 3 + 2 * i], kc[4 * 3 + 2 * i + 1]);
                if (k != 64) sts16(kb_ + (KW_2 + ((k - 1) >> 1) - 24) * 4 + (k & 1) * 2, w);
                else {
                    const uint32_t a = kb_ + (KW_D + 511) * 4, aa = (w << 16) | (w & 0xffffu);
                    sts16(a, w); sts32(a + 4, aa); sts32(a + 8, aa); sts32(a + 12, aa); sts16(a + 18, w);
                }
                sts16(kb_ + (KW_2 + 48 + (k >> 1) - 24) * 4 + ((k & 1) ^ 1) * 2, w >> 16);
            }
#pragma unroll
            for (int b = 0; b < 2; b++) {
                const int k = 64 + 8 * (2 * q + b) + (be >> 1);
                const uint32_t w = pack2(kc[4 * 4 + 2 * i + b], 0.f);
                if (!(be & 1) && k == 64) sts16(kb_ + (KW_2 + 63 - 24) * 4, w);
                else {
                    const uint32_t a = kb_ + (KW_3 + ((be & 1) ? 80 + k : k - 1) - 48) * 4;
                    sts16(a, w);
                    if (!((be & 1) && k == 127)) sts16(a + 6, w);
                }
            }
        }
        if (lane == 0) sts16(kb_ + (KW_3 + 127 - 48) * 4, pack2(kc[4 * 5 + 0], 0.f));
        __syncwarp();
        asm volatile("setmaxnreg.inc.sync.aligned.u32 136;");
        mbar_wait(bar + 8 * BAR_UR, 0);
        mbar_wait(bar + 8 * BAR_DONE, 0);
        float y[16][4];
#pragma unroll
        for (int nt = 0; nt < 16; nt++) { y[nt][0] = y[nt][1] = y[nt][2] = y[nt][3] = 0.f; }
        {
            uint32_t Bp[32], A[4][3], An[4][3];
            auto uaddr = [&](int rho) { const int R0 = (lane >> 4) * 64 + (lane & 7) - rho; return ub + (((2 * R0 + ((lane >> 3) & 1)) ^ ((R0 >> 2) & 1)) << 4); };
            const uint32_t kd = kb_ + (KW_D + g - 2 * q) * 4;
#pragma unroll 1
            for (int rho = 1; rho >= 0; rho--) {
                const uint32_t a = uaddr(rho), k = kd + 2048 + rho * 64;
#pragma unroll
                for (int i = 0; i < 8; i++) ldsm4(Bp + 4 * i, a + i * 256);
                const uint32_t a0 = lds32(k), a1 = lds32(k + 32), a2 = lds32(k - 32);
#pragma unroll
                for (int i = 0; i < 12; i++) mma16816(y[i + 4], a0, a1, a2, a0, Bp[4 * (i & 7) + 2 * (i >> 3)], Bp[4 * (i & 7) + 2 * (i >> 3) + 1]);
            }
#pragma unroll
            for (int ga = 0; ga < 4; ga++) { An[ga][0] = lds32(kd + ga * 512); An[ga][1] = lds32(kd + ga * 512 + 32); An[ga][2] = lds32(kd + ga * 512 - 32); }
#pragma unroll 1
            for (int rho = 0; rho < 8; rho++) {
#pragma unroll
                for (int ga = 0; ga < 4; ga++) {
                    const uint32_t a = kd + (rho + 1) * 64 + ga * 512;
                    A[ga][0] = An[ga][0]; A[ga][1] = An[ga][1]; A[ga][2] = An[ga][2];
                    An[ga][0] = lds32(a); An[ga][1] = lds32(a + 32); An[ga][2] = lds32(a - 32);
                }
                const uint32_t an = uaddr(rho + 1);
#pragma unroll
                for (int i = 0; i < 8; i++) {
#pragma unroll
                    for (int ga = 0; ga < 4; ga++) {
                        mma16816(y[i + ga], A[ga][0], A[ga][1], A[ga][2], A[ga][0], Bp[4 * i], Bp[4 * i + 1]);
                        if (i + 8 + ga < 16) mma16816(y[i + 8 + ga], A[ga][0], A[ga][1], A[ga][2], A[ga][0], Bp[4 * i + 2], Bp[4 * i + 3]);
                    }
                    ldsm4(Bp + 4 * i, an + i * 256);
                    __syncwarp();
                }
            }
        }
        mbar_wait(bar + 8 * BAR_WR, 0);
#pragma unroll 1
        for (int ph = 0; ph < 2; ph++) {
            uint32_t B[5][2];
            const uint32_t ka = kb_ + (KW_2 + ph * 48 + 8 + g - q) * 4;
#pragma unroll
            for (int dd = 0; dd < 5; dd++) { B[dd][0] = lds32(ka + dd * 32); B[dd][1] = lds32(ka + dd * 32 - 16); }
            const uint32_t wa = buf + ph * W3_OFF + ((lane & 7) + ((lane >> 3) & 1) + (lane >> 4) * 8) * 16;
#pragma unroll
            for (int s = 0; s < 12; s++) {
                uint32_t A[4];
                ldsm4t(A, wa + s * 256);
#pragma unroll
                for (int dd = 0; dd < 5; dd++)
                    if (s + 4 + dd < 16) mma16816(y[s + 4 + dd], A[0], A[1], A[2], A[3], B[dd][0], B[dd][1]);
            }
        }
        {
            const int ap = (lane & 7) + (lane >> 4) * 8;
            const uint32_t loff = ((2 * ap + ((lane >> 3) & 1)) ^ ((ap >> 2) & 1)) << 4;
#pragma unroll 1
            for (int ph = 0; ph < 2; ph++) {
                uint32_t B[8][2];
                const uint32_t wb = (ph ? spare : buf + W9_OFF) + loff;
                const uint32_t ka = kb_ + (KW_3 + ph * 80 + 16 + g - 2 * q) * 4;
#pragma unroll
                for (int dd = 0; dd < 8; dd++) { B[dd][0] = lds32(ka + dd * 32); B[dd][1] = lds32(ka + dd * 32 - 32); }
#pragma unroll
                for (int s = 0; s < 4; s++) {
                    uint32_t A[4];
                    ldsm4t(A, wb + s * 512);
#pragma unroll
                    for (int dd = 0; dd < 8; dd++)
                        if (8 + 2 * s + dd < 16) mma16816(y[8 + 2 * s + dd], A[0], A[1], A[2], A[3], B[dd][0], B[dd][1]);
                }
            }
            const uint32_t idw = (g == 2 * q) ? k1024 : ((g == 2 * q + 1) ? (k1024 << 16) : 0u);
#pragma unroll
            for (int s = 0; s < 4; s++) {
                uint32_t A[4];
                ldsm4t(A, spare + 2048 + loff + s * 512);
                mma16816(y[8 + 2 * s], A[0], A[1], A[2], A[3], idw, 0u);
                mma16816(y[9 + 2 * s], A[0], A[1], A[2], A[3], 0u, idw);
            }
        }
        __syncwarp();
#pragma unroll
        for (int nt = 0; nt < 16; nt++)
#pragma unroll
            for (int b = 0; b < 2; b++) sts32(buf + ((8 * nt + 2 * q + b) * 8 + g) * 4, pack2(y[nt][b], y[nt][2 + b]));
        bar_named(2, 128);
        uint4* yp = scr->y + bi * 1024 + st;
#pragma unroll
        for (int v = 0; v < 8; v++) {
            const uint32_t a = sb + OFF_BUF + (st + 128 * v) * 4;
            const uint32_t w0 = lds32(a), w1 = lds32(a + BUF_STRIDE), w2 = lds32(a + 2 * BUF_STRIDE), w3 = lds32(a + 3 * BUF_STRIDE);
            st_rlx128(yp + v * 128, tag4(__byte_perm(w0, w1, 0x5410), __byte_perm(w0, w1, 0x7632), __byte_perm(w2, w3, 0x5410), __byte_perm(w2, w3, 0x7632), tag));
        }
    } else {
        const int qq = (bi_i & 2) + ((lane >> 1) & 1);
        uint2* kvf_h = (uint2*)(scr->kvf + (bi_j * 4 + (bi_i >> 2)) * 68);
        auto windows = [&](int rhi, int rlo) {
#pragma unroll 1
            for (int rho = rhi; rho >= rlo; rho--) {
                const int ci = lane + 32 * rho;
                uint4 e4[4];
#pragma unroll
                for (int v = 0; v < 4; v++) { const int cc = ci - 3 + v; e4[v] = lds128(ub + ((cc ^ ((cc >> 3) & 1)) << 4)); }
                float S[29];
                const uint32_t* ew = (const uint32_t*)e4;
                S[3] = 0.f;
#pragma unroll
                for (int k = 4; k <= 28; k++) S[k] = S[k - 1] + ((k & 1) ? bf_hi(ew[k >> 1]) : bf_lo(ew[k >> 1]));
                auto win = [&](int lo, int hi, uint32_t a) {
                    sts128(a, pack2(S[hi] - S[lo - 1], S[hi + 1] - S[lo]), pack2(S[hi + 2] - S[lo + 1], S[hi + 3] - S[lo + 2]),
                           pack2(S[hi + 4] - S[lo + 3], S[hi + 5] - S[lo + 4]), pack2(S[hi + 6] - S[lo + 5], S[hi + 7] - S[lo + 6]));
                };
                win(14, 18, buf + W5_OFF + 16 + ci * 16); win(19, 21, buf + W3_OFF + 16 + ci * 16);
                if (rho < 4) {
                    const uint32_t sw = (ci ^ ((ci >> 3) & 1)) << 4;
                    win(4, 12, buf + W9_OFF + sw); win(13, 19, spare + sw); win(20, 21, spare + 2048 + sw);
                }
            }
        };
        {
            mbar_wait(bar + 8 * (BAR_FULL + xkb), 0);
#pragma unroll 1
            for (int hf = 0; hf < 2; hf++) {
                const int r = w4 * 32 + hf * 16 + (lane & 15);
                uint32_t* xt = (uint32_t*)scr->xt + ((xkb + rot) * 16 + (g >> 2)) * 4096 + (bi_i * 16 + w4 * 4 + hf * 2) * 16 + (g & 3) * 4 + q;
#pragma unroll
                for (int cb = 0; cb < 8; cb += 2) {
                    uint32_t v[4];
                    ldsm4t(v, sb + xkb * SLOT + r * 128 + (((cb + (lane >> 4)) ^ (r & 7)) << 4));
                    xt[cb * 8192] = v[0]; xt[cb * 8192 + 16] = v[1]; xt[cb * 8192 + 8192] = v[2]; xt[cb * 8192 + 8192 + 16] = v[3];
                }
            }
            __syncwarp();
            if (lane == 0) mbar_arrive(bar + 8 * BAR_XT);
            handoff(2);
            asm volatile("setmaxnreg.dec.sync.aligned.u32 56;");
            if (lane == 0) asm volatile("red.release.gpu.global.add.u32 [%0],2;" ::"l"(scr->xcnt + (xkb + rot) * 32) : "memory");
            __syncwarp();
            {
                const uint32_t old = tag ^ 1u;
                const uint4 z4 = make_uint4(old, 0, old, 0);
#pragma unroll
                for (int v = 0; v < 5; v++) if (v < 4 || st < 32) st_rlx128(scr->kvp + bi * 544 + v * 128 + st, z4);
                if (st < 16) st_rlx128(scr->o + ((bi_i * 8 + (st >> 1)) * 32 + bi_j * 4 + 3) * 32 + 30 + (st & 1), z4);
                if (lane < 8) st_rlx64(kvf_h + ((bi_i & 3) * 8 + w4 * 2 + (lane & 1)) * 4 + (lane >> 1), old, 0);
                if (st < 4 && !(bi_i & 1)) st_rlx64(kvf_h + (64 + qq) * 2 + (lane & 1), old, 0);
                __syncwarp();
                if (lane == 0) mbar_arrive(bar + 8 * BAR_PREP);
            }
            int n = 0;
#pragma unroll 1
            while (__any_sync(~0u, (int)(ld_acq(scr->xcnt + bi_j * 32) - (epoch1 << 7)) < 0)) { if (++n > SPIN_LIMIT) break; }
            uint4 ur[8];
#pragma unroll
            for (int v = 0; v < 8; v++) ur[v] = __ldcg(scr->xt + bi * 1024 + st + 128 * v);
            mbar_wait(bar + 8 * BAR_KG, 0);
            if (lane < 16) sts128(ub - 256 + lane * 16, 0, 0, 0, 0);
#pragma unroll
            for (int v = 0; v < 8; v++) {
                const int ci = (st >> 2) + 32 * v;
                sts128(sb + OFF_U + (st & 3) * U_STRIDE + 256 + ((ci ^ ((ci >> 3) & 1)) << 4), ur[v].x, ur[v].y, ur[v].z, ur[v].w);
            }
            __syncwarp();
            if (lane == 0) mbar_arrive(bar + 8 * BAR_UR);
            mbar_wait(bar + 8 * BAR_UR, 0);
            mbar_wait(bar + 8 * (BAR_KD + w4), 0);
            if (lane < 2) sts128(buf + lane * W3_OFF, 0, 0, 0, 0);
            windows(5, 4);
        }
        mbar_wait(bar + 8 * BAR_SP2, 0);
        windows(3, 0);
        __syncwarp();
        if (lane == 0) mbar_arrive(bar + 8 * BAR_WR);
        {
            const bool zw = st < 32 && !(bi_i & 1);
            const uint4* src = scr->kvp + bi_j * (16 * 544) + (bi_i >> 2) * 136;
            const uint4* zsrc = src + (lane >> 2) * (2 * 544) + 128 + (lane & 1) * 4 + qq;
            src += (lane >> 3) * (4 * 544) + ((lane >> 1) & 3) * 32 + (bi_i & 3) * 8 + w4 * 2 + (lane & 1);
            mbar_wait(bar + 8 * BAR_PUB, 0);
            uint4 v[6];
#pragma unroll
            for (int k = 0; k < 6; k++) v[k] = make_uint4(tag ^ 1u, 0, 0, 0);
            int n = 0;
#pragma unroll 1
            while (true) {
#pragma unroll
                for (int k = 0; k < 6; k++) if ((bad4(v[k], tag) & 1) && (k < 4 || zw)) v[k] = ld_rlx128(k < 4 ? src + k * 544 : zsrc + (k - 4) * 544);
                if (!__any_sync(~0u, (bad4(v[0], tag) | bad4(v[1], tag) | bad4(v[2], tag) | bad4(v[3], tag) | (zw ? bad4(v[4], tag) | bad4(v[5], tag) : 0u)) & 1)) break;
                if (++n > SPIN_LIMIT) break;
            }
            float f[8];
            const float* vf = (const float*)v;
#pragma unroll
            for (int r = 0; r < 4; r++) {
                f[r] = (vf[r] + vf[4 + r]) + (vf[8 + r] + vf[12 + r]);
                f[4 + r] = vf[16 + r] + vf[20 + r];
                f[4 + r] += __shfl_xor_sync(~0u, f[4 + r], 4);
            }
#pragma unroll
            for (int o = 8; o <= 16; o <<= 1)
#pragma unroll
                for (int r = 0; r < 8; r++) f[r] += __shfl_xor_sync(~0u, f[r], o);
            if (lane < 8) st_rlx64(kvf_h + ((bi_i & 3) * 8 + w4 * 2 + (lane & 1)) * 4 + (lane >> 1), tagw(pack2(f[0], f[1]), tag), pack2(f[2], f[3]));
            if (zw && lane < 4) st_rlx64(kvf_h + (64 + qq) * 2 + (lane & 1), tagw(pack2(f[4], f[5]), tag), pack2(f[6], f[7]));
        }
        {
            const uint4* kp = scr->kvf + bi_j * 272 + st;
            uint4 v0 = make_uint4(tag ^ 1u, 0, 0, 0), v1 = v0, v2 = make_uint4(st < 16 ? tag ^ 1u : tag, 0, tag, 0);
            int n = 0;
#pragma unroll 1
            while (true) {
                if (bad4(v0, tag) & 1) v0 = ld_rlx128(kp);
                if (bad4(v1, tag) & 1) v1 = ld_rlx128(kp + 128);
                if (bad4(v2, tag) & 1) v2 = ld_rlx128(kp + 256);
                if (!__any_sync(~0u, (bad4(v0, tag) | bad4(v1, tag) | bad4(v2, tag)) & 1)) break;
                if (++n > SPIN_LIMIT) break;
            }
            sts128(sb + OFF_KVF + st * 16, v0.x, v0.y, v0.z, v0.w);
            sts128(sb + OFF_KVF + 2048 + st * 16, v1.x, v1.y, v1.z, v1.w);
            if (st < 16) sts128(sb + OFF_KVF + 4096 + st * 16, v2.x, v2.y, v2.z, v2.w);
            __syncwarp();
            if (lane == 0) mbar_arrive(bar + 8 * BAR_KVF);
        }
        if (warp == 13) {
            mbar_wait(bar + 8 * BAR_KVF, 0);
            if (lane == 0) {
                mbar_expect(bar + 8 * BAR_WO2, 65536);
                tma2d(sb + OFF_P, &mwo, (bi_j & 3) * 128 + 64, 256, bar + 8 * BAR_WO2);
                tma2d(sb + OFF_V, &mwo, (bi_j & 3) * 128, 256, bar + 8 * BAR_WO2);
            }
        }
    }
    __syncwarp();
    if (lane == 0) {
        unsigned old;
        asm volatile("atom.acq_rel.cta.shared.add.u32 %0,[%1],1;" : "=r"(old) : "r"(bar + OFF_CNT) : "memory");
        if (old == 15) {
            atomicAdd(scr->done, 1u);
        }
    }
}

typedef CUresult (*EncFn)(CUtensorMap*, CUtensorMapDataType, cuuint32_t, void*, const cuuint64_t*, const cuuint64_t*, const cuuint32_t*,
                          const cuuint32_t*, CUtensorMapInterleave, CUtensorMapSwizzle, CUtensorMapL2promotion, CUtensorMapFloatOOBfill);

extern "C" void kernel_launch(void* const* d_in, const int* in_sizes, int n_in, void* d_out, int out_size) {
    static EncFn enc = nullptr;
    static Scratch* scr = nullptr;
    if (!enc) {
        cudaGetSymbolAddress((void**)&scr, g_scr);
        cudaDriverEntryPointQueryResult qr;
        cudaGetDriverEntryPoint("cuTensorMapEncodeTiled", (void**)&enc, cudaEnableDefault, &qr);
        cudaFuncSetAttribute(fused_kernel, cudaFuncAttributeMaxDynamicSharedMemorySize, SMEM_BYTES);
    }
    CUtensorMap mx, mw, mwo;
    const cuuint32_t es[3] = {1, 1, 1};
    {
        cuuint64_t d[2] = {512, 2048}, s[1] = {1024}; cuuint32_t b[2] = {64, 128};
        enc(&mx, CU_TENSOR_MAP_DATA_TYPE_BFLOAT16, 2, d_in[0], d, s, b, es, CU_TENSOR_MAP_INTERLEAVE_NONE, CU_TENSOR_MAP_SWIZZLE_128B,
            CU_TENSOR_MAP_L2_PROMOTION_L2_128B, CU_TENSOR_MAP_FLOAT_OOB_FILL_NONE);
    }
    {
        cuuint64_t d[3] = {512, 512, 3}, s[2] = {3072, 1024}; cuuint32_t b[3] = {64, 64, 3};
        enc(&mw, CU_TENSOR_MAP_DATA_TYPE_BFLOAT16, 3, d_in[1], d, s, b, es, CU_TENSOR_MAP_INTERLEAVE_NONE, CU_TENSOR_MAP_SWIZZLE_128B,
            CU_TENSOR_MAP_L2_PROMOTION_L2_128B, CU_TENSOR_MAP_FLOAT_OOB_FILL_NONE);
    }
    {
        cuuint64_t d[2] = {512, 512}, s[1] = {1024}; cuuint32_t b[2] = {64, 256};
        enc(&mwo, CU_TENSOR_MAP_DATA_TYPE_BFLOAT16, 2, d_in[3], d, s, b, es, CU_TENSOR_MAP_INTERLEAVE_NONE, CU_TENSOR_MAP_SWIZZLE_128B,
            CU_TENSOR_MAP_L2_PROMOTION_L2_128B, CU_TENSOR_MAP_FLOAT_OOB_FILL_NONE);
    }
    fused_kernel<<<128, 512, SMEM_BYTES, cudaStreamPerThread>>>(
        scr, (const bf16*)d_in[5], (const bf16*)d_in[6], (const bf16*)d_in[7], (const bf16*)d_in[8], (const bf16*)d_in[9],
        (const bf16*)d_in[10], (const bf16*)d_in[2], (const bf16*)d_in[11], (bf16*)d_out, mx, mw, mwo);
}
```

```cpp
#include <cuda_runtime.h>
#include <cuda.h>
#include <cuda_bf16.h>
#include <stdint.h>

typedef __nv_bfloat16 bf16;

struct Scratch {
    uint4 xt[128 * 1024];
    uint4 o[16 * 8 * 32 * 32];
    uint4 y[128 * 1024];
    uint4 kvp[8 * 16 * 544];
    uint4 kvf[8 * 4 * 68];
    unsigned g[1024 * 8];
    unsigned xcnt[8 * 32];
    unsigned done[32];
};
__device__ Scratch g_scr;
#define STAMP(n)

constexpr int SLOT = 40960;
constexpr int OFF_SP0 = 32768, OFF_SP1 = SLOT + 32768;
constexpr int OFF_P = 2 * SLOT, OFF_V = OFF_P + 32768;
constexpr int OFF_KVF = OFF_V + 32768;
constexpr int KT_BYTES = 3264, KW_D = 16, KW_2 = 560, KW_3 = 656;
constexpr int OFF_U = 4 * SLOT, U_STRIDE = 4096 + 256 + 32;
constexpr int OFF_BUF = OFF_U + 4 * U_STRIDE, BUF_STRIDE = 8320;
constexpr int OFF_K = OFF_BUF + 4 * BUF_STRIDE;
constexpr int OFF_WPHI = OFF_K + 4 * KT_BYTES;
constexpr int OFF_GW = OFF_WPHI + 2048;
constexpr int OFF_BAR = OFF_GW + 1024;
constexpr int SMEM_BYTES = OFF_BAR + 320 + 256;
static_assert(SMEM_BYTES <= 232448 && OFF_BUF % 128 == 0, "smem");
constexpr int W5_OFF = 0, W3_OFF = 3088, W9_OFF = 6176;
constexpr int BAR_FULL = 0, BAR_EMPTY = 4, BAR_WPHI = 8, BAR_WO = 9, BAR_WO2 = 10, BAR_XT = 11, BAR_DONE = 12, BAR_KG = 13, BAR_SP = 14,
              BAR_PUB = 15, BAR_KVF = 16, BAR_UR = 17, BAR_WR = 18, BAR_PREP = 19, BAR_KGA = 20, BAR_SP2 = 21, BAR_KS = 22, BAR_KP = 26, BAR_KD = 30, OFF_CNT = 272;
constexpr int SPIN_LIMIT = 1 << 17;

__device__ __forceinline__ uint32_t s2u(const void* p) { return (uint32_t)__cvta_generic_to_shared(p); }
__device__ __forceinline__ void mbar_init(uint32_t b, int c) { asm volatile("mbarrier.init.shared::cta.b64 [%0],%1;" ::"r"(b), "r"(c) : "memory"); }
__device__ __forceinline__ void mbar_expect(uint32_t b, int bytes) { asm volatile("mbarrier.arrive.expect_tx.shared::cta.b64 _,[%0],%1;" ::"r"(b), "r"(bytes) : "memory"); }
__device__ __forceinline__ void mbar_arrive(uint32_t b) { asm volatile("mbarrier.arrive.shared::cta.b64 _,[%0];" ::"r"(b) : "memory"); }
__device__ __forceinline__ void mbar_wait(uint32_t b, int ph) {
    asm volatile("{\n.reg .pred p;\n.reg .u32 n;\nmov.u32 n,0;\nLW_%=:\nmbarrier.try_wait.parity.shared::cta.b64 p,[%0],%1;\n@p bra LD_%=;\n"
                 "add.u32 n,n,1;\nsetp.lt.u32 p,n,16384;\n@p bra LW_%=;\nLD_%=:\n}" ::"r"(b), "r"(ph) : "memory");
}
__device__ __forceinline__ void tma2d(uint32_t dst, const CUtensorMap* m, int c0, int c1, uint32_t bar) {
    asm volatile("cp.async.bulk.tensor.2d.shared::cluster.global.mbarrier::complete_tx::bytes [%0],[%1,{%3,%4}],[%2];" ::"r"(dst), "l"(m), "r"(bar), "r"(c0), "r"(c1) : "memory");
}
__device__ __forceinline__ void tma3d(uint32_t dst, const CUtensorMap* m, int c0, int c1, int c2, uint32_t bar) {
    asm volatile("cp.async.bulk.tensor.3d.shared::cluster.global.mbarrier::complete_tx::bytes [%0],[%1,{%3,%4,%5}],[%2];" ::"r"(dst), "l"(m), "r"(bar), "r"(c0), "r"(c1), "r"(c2) : "memory");
}
__device__ __forceinline__ void bulk_g2s(uint32_t dst, const void* src, int bytes, uint32_t bar) {
    asm volatile("cp.async.bulk.shared::cluster.global.mbarrier::complete_tx::bytes [%0],[%1],%2,[%3];" ::"r"(dst), "l"(src), "r"(bytes), "r"(bar) : "memory");
}
__device__ __forceinline__ uint64_t mkdesc(uint32_t addr, uint32_t lbo, uint32_t sbo) {
    return (uint64_t)((addr & 0x3FFFF) >> 4) | ((uint64_t)(lbo >> 4) << 16) | ((uint64_t)(sbo >> 4) << 32) | ((uint64_t)1 << 62);
}
__device__ __forceinline__ void wg_fence() { asm volatile("wgmma.fence.sync.aligned;" ::: "memory"); }
__device__ __forceinline__ void wg_commit() { asm volatile("wgmma.commit_group.sync.aligned;" ::: "memory"); }
template <int N> __device__ __forceinline__ void wg_wait() { asm volatile("wgmma.wait_group.sync.aligned %0;" ::"n"(N) : "memory"); }
template <int N> __device__ __forceinline__ void fence_regs(float* d) {
#pragma unroll
    for (int i = 0; i < N; i++) asm volatile("" : "+f"(d[i])::"memory");
}
#define R8(d, o) "+f"(d[o]), "+f"(d[o + 1]), "+f"(d[o + 2]), "+f"(d[o + 3]), "+f"(d[o + 4]), "+f"(d[o + 5]), "+f"(d[o + 6]), "+f"(d[o + 7])
__device__ __forceinline__ void wgmma192(float* d, uint64_t da, uint64_t db, int sc) {
    asm volatile("{.reg .pred p; setp.ne.b32 p,%98,0; wgmma.mma_async.sync.aligned.m64n192k16.f32.bf16.bf16 {"
                 "%0,%1,%2,%3,%4,%5,%6,%7,%8,%9,%10,%11,%12,%13,%14,%15,%16,%17,%18,%19,%20,%21,%22,%23,%24,%25,%26,%27,%28,%29,%30,%31,"
                 "%32,%33,%34,%35,%36,%37,%38,%39,%40,%41,%42,%43,%44,%45,%46,%47,%48,%49,%50,%51,%52,%53,%54,%55,%56,%57,%58,%59,%60,%61,%62,%63,"
                 "%64,%65,%66,%67,%68,%69,%70,%71,%72,%73,%74,%75,%76,%77,%78,%79,%80,%81,%82,%83,%84,%85,%86,%87,%88,%89,%90,%91,%92,%93,%94,%95},"
                 "%96,%97,p,1,1,0,1;}"
                 : R8(d, 0), R8(d, 8), R8(d, 16), R8(d, 24), R8(d, 32), R8(d, 40), R8(d, 48), R8(d, 56), R8(d, 64), R8(d, 72), R8(d, 80), R8(d, 88)
                 : "l"(da), "l"(db), "r"(sc));
}
__device__ __forceinline__ void wgmma64_tt(float* d, uint64_t da, uint64_t db, int sc) {
    asm volatile("{.reg .pred p; setp.ne.b32 p,%34,0; wgmma.mma_async.sync.aligned.m64n64k16.f32.bf16.bf16 {"
                 "%0,%1,%2,%3,%4,%5,%6,%7,%8,%9,%10,%11,%12,%13,%14,%15,%16,%17,%18,%19,%20,%21,%22,%23,%24,%25,%26,%27,%28,%29,%30,%31},"
                 "%32,%33,p,1,1,1,1;}"
                 : R8(d, 0), R8(d, 8), R8(d, 16), R8(d, 24)
                 : "l"(da), "l"(db), "r"(sc));
}
__device__ __forceinline__ void wgmma128_rs(float* d, const uint4& a, uint64_t db, int sc) {
    asm volatile("{.reg .pred p; setp.ne.b32 p,%69,0; wgmma.mma_async.sync.aligned.m64n128k16.f32.bf16.bf16 {"
                 "%0,%1,%2,%3,%4,%5,%6,%7,%8,%9,%10,%11,%12,%13,%14,%15,%16,%17,%18,%19,%20,%21,%22,%23,%24,%25,%26,%27,%28,%29,%30,%31,"
                 "%32,%33,%34,%35,%36,%37,%38,%39,%40,%41,%42,%43,%44,%45,%46,%47,%48,%49,%50,%51,%52,%53,%54,%55,%56,%57,%58,%59,%60,%61,%62,%63},"
                 "{%64,%65,%66,%67},%68,p,1,1,1;}"
                 : R8(d, 0), R8(d, 8), R8(d, 16), R8(d, 24), R8(d, 32), R8(d, 40), R8(d, 48), R8(d, 56)
                 : "r"(a.x), "r"(a.y), "r"(a.z), "r"(a.w), "l"(db), "r"(sc));
}
__device__ __forceinline__ void mma16816(float* c, uint32_t a0, uint32_t a1, uint32_t a2, uint32_t a3, uint32_t b0, uint32_t b1) {
    asm("mma.sync.aligned.m16n8k16.row.col.f32.bf16.bf16.f32 {%0,%1,%2,%3},{%4,%5,%6,%7},{%8,%9},{%0,%1,%2,%3};"
        : "+f"(c[0]), "+f"(c[1]), "+f"(c[2]), "+f"(c[3]) : "r"(a0), "r"(a1), "r"(a2), "r"(a3), "r"(b0), "r"(b1));
}
__device__ __forceinline__ void ldsm4(uint32_t* r, uint32_t a) {
    asm volatile("ldmatrix.sync.aligned.m8n8.x4.shared.b16 {%0,%1,%2,%3},[%4];" : "=r"(r[0]), "=r"(r[1]), "=r"(r[2]), "=r"(r[3]) : "r"(a) : "memory");
}
__device__ __forceinline__ void ldsm4t(uint32_t* r, uint32_t a) {
    asm volatile("ldmatrix.sync.aligned.m8n8.x4.trans.shared.b16 {%0,%1,%2,%3},[%4];" : "=r"(r[0]), "=r"(r[1]), "=r"(r[2]), "=r"(r[3]) : "r"(a) : "memory");
}
__device__ __forceinline__ void stsm4(uint32_t a, uint32_t r0, uint32_t r1, uint32_t r2, uint32_t r3) {
    asm volatile("stmatrix.sync.aligned.m8n8.x4.shared.b16 [%0],{%1,%2,%3,%4};" ::"r"(a), "r"(r0), "r"(r1), "r"(r2), "r"(r3) : "memory");
}
__device__ __forceinline__ uint32_t lds32(uint32_t a) { uint32_t v; asm volatile("ld.shared.b32 %0,[%1];" : "=r"(v) : "r"(a) : "memory"); return v; }
__device__ __forceinline__ uint4 lds128(uint32_t a) { uint4 v; asm volatile("ld.shared.v4.b32 {%0,%1,%2,%3},[%4];" : "=r"(v.x), "=r"(v.y), "=r"(v.z), "=r"(v.w) : "r"(a) : "memory"); return v; }
__device__ __forceinline__ void sts16(uint32_t a, uint32_t v) { asm volatile("st.shared.b16 [%0],%1;" ::"r"(a), "h"((unsigned short)v) : "memory"); }
__device__ __forceinline__ void sts32(uint32_t a, uint32_t v) { asm volatile("st.shared.b32 [%0],%1;" ::"r"(a), "r"(v) : "memory"); }
__device__ __forceinline__ void sts64(uint32_t a, uint32_t x, uint32_t y) { asm volatile("st.shared.v2.b32 [%0],{%1,%2};" ::"r"(a), "r"(x), "r"(y) : "memory"); }
__device__ __forceinline__ void sts128(uint32_t a, uint32_t x, uint32_t y, uint32_t z, uint32_t w) { asm volatile("st.shared.v4.b32 [%0],{%1,%2,%3,%4};" ::"r"(a), "r"(x), "r"(y), "r"(z), "r"(w) : "memory"); }
__device__ __forceinline__ uint32_t pack2(float lo, float hi) { uint32_t d; asm("cvt.rn.bf16x2.f32 %0,%1,%2;" : "=r"(d) : "f"(hi), "f"(lo)); return d; }
__device__ __forceinline__ float bf_lo(uint32_t v) { return __uint_as_float(v << 16); }
__device__ __forceinline__ float bf_hi(uint32_t v) { return __uint_as_float(v & 0xffff0000u); }
__device__ __forceinline__ float bf_round(float v) { return bf_lo(pack2(v, 0.f)); }
__device__ __forceinline__ uint32_t hmax2(uint32_t a, uint32_t b) { uint32_t d; asm("max.bf16x2 %0,%1,%2;" : "=r"(d) : "r"(a), "r"(b)); return d; }
__device__ __forceinline__ uint32_t hmin2(uint32_t a, uint32_t b) { uint32_t d; asm("min.bf16x2 %0,%1,%2;" : "=r"(d) : "r"(a), "r"(b)); return d; }
__device__ __forceinline__ uint32_t hmul2(uint32_t a, uint32_t b) { uint32_t d; asm("mul.rn.bf16x2 %0,%1,%2;" : "=r"(d) : "r"(a), "r"(b)); return d; }
__device__ __forceinline__ float ex2(float x) { float y; asm("ex2.approx.ftz.f32 %0,%1;" : "=f"(y) : "f"(x)); return y; }
__device__ __forceinline__ float rcp(float x) { float y; asm("rcp.approx.ftz.f32 %0,%1;" : "=f"(y) : "f"(x)); return y; }
__device__ __forceinline__ uint32_t ld_nc(const uint32_t* p) { uint32_t v; asm volatile("ld.global.nc.b32 %0,[%1];" : "=r"(v) : "l"(p)); return v; }
__device__ __forceinline__ uint2 ld_nc64(const uint2* p) { uint2 v; asm volatile("ld.global.nc.v2.b32 {%0,%1},[%2];" : "=r"(v.x), "=r"(v.y) : "l"(p)); return v; }
__device__ __forceinline__ unsigned ld_acq(const unsigned* p) { unsigned v; asm volatile("ld.acquire.gpu.global.u32 %0,[%1];" : "=r"(v) : "l"(p) : "memory"); return v; }
__device__ __forceinline__ unsigned ld_rlx(const unsigned* p) { unsigned v; asm volatile("ld.relaxed.gpu.global.u32 %0,[%1];" : "=r"(v) : "l"(p) : "memory"); return v; }
__device__ __forceinline__ uint2 ld_rlx64(const void* p) { uint2 v; asm volatile("{.reg .b64 t; ld.relaxed.gpu.global.b64 t,[%2]; mov.b64 {%0,%1},t;}" : "=r"(v.x), "=r"(v.y) : "l"(p) : "memory"); return v; }
__device__ __forceinline__ uint4 ld_rlx128(const void* p) {
    uint4 v;
    asm volatile("{.reg .b64 t,u; ld.relaxed.gpu.global.v2.b64 {t,u},[%4]; mov.b64 {%0,%1},t; mov.b64 {%2,%3},u;}" : "=r"(v.x), "=r"(v.y), "=r"(v.z), "=r"(v.w) : "l"(p) : "memory");
    return v;
}
__device__ __forceinline__ void st_rlx32(void* p, uint32_t x) { asm volatile("st.relaxed.gpu.global.u32 [%0],%1;" ::"l"(p), "r"(x) : "memory"); }
__device__ __forceinline__ void st_rlx64(void* p, uint32_t x, uint32_t y) { asm volatile("{.reg .b64 t; mov.b64 t,{%1,%2}; st.relaxed.gpu.global.b64 [%0],t;}" ::"l"(p), "r"(x), "r"(y) : "memory"); }
__device__ __forceinline__ void st_rlx128(void* p, uint4 v) {
    asm volatile("{.reg .b64 t,u; mov.b64 t,{%1,%2}; mov.b64 u,{%3,%4}; st.relaxed.gpu.global.v2.b64 [%0],{t,u};}" ::"l"(p), "r"(v.x), "r"(v.y), "r"(v.z), "r"(v.w) : "memory");
}
__device__ __forceinline__ uint32_t tagw(uint32_t w, uint32_t tag) { return (w & ~1u) | tag; }
__device__ __forceinline__ uint4 tag4(uint32_t x, uint32_t y, uint32_t z, uint32_t w, uint32_t tag) { return make_uint4(tagw(x, tag), y, tagw(z, tag), w); }
__device__ __forceinline__ uint32_t bad4(const uint4& v, uint32_t tag) { return (v.x ^ tag) | (v.z ^ tag); }
__device__ __forceinline__ void bar_named(int id, int n) { asm volatile("bar.sync %0,%1;" ::"r"(id), "r"(n) : "memory"); }

struct cf { float re, im; };
__device__ __forceinline__ cf cmul(cf a, cf b) { cf r; r.re = a.re * b.re - a.im * b.im; r.im = a.re * b.im + a.im * b.re; return r; }
__device__ __forceinline__ cf cexp_p(float arl, float ait, float p) {
    float mag = ex2(arl * p);
    float t = ait * p;
    const float big = 12582912.f;
    t = (t - ((t + big) - big)) * 6.283185307179586f;
    cf r; r.re = mag * __cosf(t); r.im = mag * __sinf(t);
    return r;
}

__device__ __forceinline__ void hedgehog4(const uint32_t* a, uint32_t wphi_addr, uint32_t (*out)[8]) {
    float p[4][2][4], mx[4][2];
#pragma unroll
    for (int h = 0; h < 4; h++) {
        uint32_t b[4];
        ldsm4t(b, wphi_addr + h * 512);
        float c0[4] = {0.f, 0.f, 0.f, 0.f}, c1[4] = {0.f, 0.f, 0.f, 0.f};
        mma16816(c0, a[4 * h], a[4 * h + 1], a[4 * h + 2], a[4 * h + 3], b[0], b[1]);
        mma16816(c1, a[4 * h], a[4 * h + 1], a[4 * h + 2], a[4 * h + 3], b[2], b[3]);
#pragma unroll
        for (int k = 0; k < 2; k++) {
            p[h][k][0] = c0[2 * k]; p[h][k][1] = c0[2 * k + 1]; p[h][k][2] = c1[2 * k]; p[h][k][3] = c1[2 * k + 1];
            mx[h][k] = fmaxf(fmaxf(p[h][k][0], p[h][k][1]), fmaxf(p[h][k][2], p[h][k][3]));
        }
    }
#pragma unroll
    for (int o = 1; o <= 2; o <<= 1)
#pragma unroll
        for (int h = 0; h < 4; h++)
#pragma unroll
            for (int k = 0; k < 2; k++) mx[h][k] = fmaxf(mx[h][k], __shfl_xor_sync(~0u, mx[h][k], o));
    const float L = 1.4426950408889634f;
    float pmin = 1.f;
#pragma unroll
    for (int h = 0; h < 4; h++)
#pragma unroll
        for (int k = 0; k < 2; k++) {
            const float m = -mx[h][k] * L;
            const float e0 = ex2(fmaf(p[h][k][0], L, m)), e1 = ex2(fmaf(p[h][k][1], L, m)), e2 = ex2(fmaf(p[h][k][2], L, m)), e3 = ex2(fmaf(p[h][k][3], L, m));
            const float p01 = e0 * e1, p23 = e2 * e3, pp = p01 * p23, r = rcp(pp), r01 = r * p23, r23 = r * p01;
            pmin = fminf(pmin, pp);
            out[h][k] = pack2(e0, e1); out[h][k + 2] = pack2(e2, e3);
            out[h][4 + k] = pack2(r01 * e1, r01 * e0); out[h][4 + k + 2] = pack2(r23 * e3, r23 * e2);
        }
    if (__builtin_expect(__any_sync(~0u, !(pmin > 1e-18f)), 0)) {
#pragma unroll
        for (int h = 0; h < 4; h++)
#pragma unroll
            for (int k = 0; k < 2; k++) {
                float m = fminf(fminf(p[h][k][0], p[h][k][1]), fminf(p[h][k][2], p[h][k][3]));
                m = fminf(m, __shfl_xor_sync(~0u, m, 1));
                m = fminf(m, __shfl_xor_sync(~0u, m, 2)) * L;
                out[h][4 + k] = pack2(ex2(fmaf(p[h][k][0], -L, m)), ex2(fmaf(p[h][k][1], -L, m)));
                out[h][4 + k + 2] = pack2(ex2(fmaf(p[h][k][2], -L, m)), ex2(fmaf(p[h][k][3], -L, m)));
            }
    }
}

__global__ void __launch_bounds__(512, 1)
fused_kernel(Scratch* __restrict__ scr, const bf16* __restrict__ logA, const bf16* __restrict__ Aim, const bf16* __restrict__ Cre,
             const bf16* __restrict__ Cim, const bf16* __restrict__ logdt, const bf16* __restrict__ Dskip, const bf16* __restrict__ wphi,
             const bf16* __restrict__ gatew, bf16* __restrict__ out,
             const __grid_constant__ CUtensorMap mx, const __grid_constant__ CUtensorMap mw, const __grid_constant__ CUtensorMap mwo) {
    extern __shared__ __align__(1024) uint8_t smem[];
    constexpr uint32_t sb = 1024;
    const int tid = threadIdx.x, warp = __shfl_sync(~0u, tid >> 5, 0), lane = tid & 31;
    const int g = lane >> 2, q = lane & 3, w4 = warp & 3;
    const int bi = blockIdx.x, bi_i = bi & 15, bi_j = bi >> 4;
    const uint32_t bar = sb + OFF_BAR;
    const int rot = (bi_j & 3) * 2, xkb = bi_j >> 2;
    auto load_stage = [&](int kb) {
        const uint32_t b = bar + 8 * (BAR_FULL + (kb & 3)), d = sb + (kb & 3) * SLOT;
        const int kc = ((kb + rot) & 7) * 64;
        mbar_expect(b, SLOT);
        tma2d(d, &mx, kc, bi_i * 128, b);
        tma3d(d + 16384, &mw, bi_j * 64, kc, 0, b);
    };

    const int ch = bi * 4 + w4;
    const int pidx = ch * 64 + lane * 2 + (warp >> 3);
    const uint32_t pla = ld_nc((const uint32_t*)logA + pidx), pai = ld_nc((const uint32_t*)Aim + pidx);
    const uint32_t pcr = ld_nc((const uint32_t*)Cre + pidx), pci = ld_nc((const uint32_t*)Cim + pidx);
    uint32_t pdt = ld_nc((const uint32_t*)logdt + (ch >> 1));
    const uint32_t pds = ld_nc((const uint32_t*)Dskip + (ch >> 1));
    unsigned done0 = ld_rlx(scr->done);
    if (tid == 0) {
        for (int s = 0; s < 4; s++) mbar_init(bar + 8 * (BAR_FULL + s), 1);
        asm volatile("fence.mbarrier_init.release.cluster;" ::: "memory");
        asm volatile("prefetch.tensormap [%0];" ::"l"(&mx) : "memory");
        load_stage(0); load_stage(1);
        STAMP(11);
    } else if (tid == 32) {
        if (s2u(smem) != sb) __trap();
        sts32(bar + OFF_CNT, 0);
        for (int s = 0; s < 4; s++) { mbar_init(bar + 8 * (BAR_EMPTY + s), 9); mbar_init(bar + 8 * (BAR_KS + s), 1); mbar_init(bar + 8 * (BAR_KP + s), 3); mbar_init(bar + 8 * (BAR_KD + s), 1); }
        mbar_init(bar + 8 * BAR_WPHI, 1); mbar_init(bar + 8 * BAR_WO, 2); mbar_init(bar + 8 * BAR_WO2, 1); mbar_init(bar + 8 * BAR_XT, 4);
        mbar_init(bar + 8 * BAR_DONE, 9); mbar_init(bar + 8 * BAR_KG, 8); mbar_init(bar + 8 * BAR_PUB, 8);
        mbar_init(bar + 8 * BAR_KVF, 4); mbar_init(bar + 8 * BAR_UR, 4); mbar_init(bar + 8 * BAR_WR, 4); mbar_init(bar + 8 * BAR_PREP, 4); mbar_init(bar + 8 * BAR_KGA, 4); mbar_init(bar + 8 * BAR_SP2, 1);
        asm volatile("fence.mbarrier_init.release.cluster;" ::: "memory");
        mbar_expect(bar + 8 * BAR_WPHI, 3072);
        bulk_g2s(sb + OFF_GW, gatew, 1024, bar + 8 * BAR_WPHI);
        bulk_g2s(sb + OFF_WPHI, wphi + bi_j * 1024, 2048, bar + 8 * BAR_WPHI);
    } else if (tid == 64) {
        asm volatile("prefetch.tensormap [%0];" ::"l"(&mw) : "memory");
    }
    const uint32_t buf = sb + OFF_BUF + w4 * BUF_STRIDE, kb_ = sb + OFF_K + w4 * KT_BYTES;
    if ((warp >> 2) == 2) {
#pragma unroll
        for (int v = 0; v < 7; v++) if (v * 32 + lane < KT_BYTES / 16) sts128(kb_ + (v * 32 + lane) * 16, 0, 0, 0, 0);
    }
    __syncthreads();
    asm volatile("" : "+r"(pdt), "+r"(done0)::"memory");
    const unsigned epoch1 = (done0 >> 7) + 1u;
    const uint32_t tag = epoch1 & 1u;

    const int st = tid & 127;
    const uint32_t ub = sb + OFF_U + w4 * U_STRIDE + 256, spare = sb + (w4 < 2 ? OFF_SP0 : OFF_SP1) + (w4 & 1) * 4096;

    auto stg_of = [&](int w) { return w < 8 ? sb + 3 * SLOT + w * 7296 : sb + 2 * SLOT + (w & 3) * 7296; };
    float kc[24];
#pragma unroll
    for (int t = 0; t < 24; t++) kc[t] = 0.f;
    auto handoff = [&](int src) {
        mbar_wait(bar + 8 * (BAR_KS + w4), 0);
#pragma unroll
        for (int t = 0; t < 5; t++)
            sts128(buf + src * 2560 + (t * 32 + lane) * 16, __float_as_uint(kc[4 * t]), __float_as_uint(kc[4 * t + 1]), __float_as_uint(kc[4 * t + 2]), __float_as_uint(kc[4 * t + 3]));
        if (lane == 0) sts32(buf + 7680 + src * 4, __float_as_uint(kc[20]));
        __syncwarp();
        if (lane == 0) mbar_arrive(bar + 8 * (BAR_KP + w4));
    };
    {
        const float dt = bf_round(expf((ch & 1) ? bf_hi(pdt) : bf_lo(pdt)));
        const uint32_t stg = (warp >> 2) == 2 ? buf : stg_of(warp);
        const int sh = ((warp >> 2) & 1) * 16;
        auto pick = [&](uint32_t v) { return __uint_as_float((v >> sh) << 16); };
        const float ea = bf_round(ex2(pick(pla) * 1.4426950408889634f));
        const float arl = (-ea * dt) * 1.4426950408889634f, ait = (pick(pai) * dt) * 0.15915494309189535f;
        cf C2; C2.re = 2.0f * (pick(pcr) * dt); C2.im = 2.0f * (pick(pci) * dt);
        const cf z1 = cexp_p(arl, ait, 1.0f), z128 = cexp_p(arl, ait, 128.0f);
        const cf z2 = cmul(z1, z1), z4 = cmul(z2, z2);
        cf z8 = cmul(z4, z4); z8.im = -z8.im;
        const uint32_t sa0 = stg + (lane >> 3) * 128 + (((lane & 7) ^ (lane >> 3)) << 4), sa1 = (sa0 ^ 64) + 512;
        uint32_t w[60];
        auto put = [&](int row, const cf& v) {
            w[row] = pack2(v.re, v.im);
            if ((row & 3) == 3) stsm4(((row & 4) ? sa1 : sa0) + (row >> 3) * 1024, w[row - 3], w[row - 2], w[row - 1], w[row]);
        };
        {
            const cf z16 = cmul(z8, z8);
            cf e; e.re = 1.f; e.im = 0.f;
            cf o = z8;
            put(0, e); put(1, o);
            e = z16; put(2, e);
#pragma unroll
            for (int b = 3; b < 16; b += 2) {
                o = cmul(o, z16); put(b, o);
                if (b + 1 < 16) { e = cmul(e, z16); put(b + 1, e); }
            }
        }
        cf h[8];
        h[0] = C2; h[1] = cmul(h[0], z1);
#pragma unroll
        for (int r = 2; r < 8; r++) h[r] = cmul(h[r - 2], z2);
#pragma unroll
        for (int r = 0; r < 8; r++) put(16 + r, h[r]);
#pragma unroll
        for (int r = 0; r < 8; r++) { h[r] = cmul(h[r], z128); put(24 + r, h[r]); }
#pragma unroll
        for (int al = 0; al < 2; al++)
#pragma unroll
            for (int r = 0; r < 4; r++) { h[2 * r] = cmul(h[2 * r], z128); put(32 + al * 4 + r, h[2 * r]); }
#pragma unroll
        for (int al = 0; al < 4; al++)
#pragma unroll
            for (int r = 0; r < 2; r++) { h[4 * r] = cmul(h[4 * r], z128); put(40 + al * 2 + r, h[4 * r]); }
#pragma unroll
        for (int al = 0; al < 8; al++) { h[0] = cmul(h[0], z128); put(48 + al, h[0]); }
        h[0] = cmul(h[0], z128);
        sts32(stg + 56 * 128 + lane * 4, pack2(h[0].re, h[0].im));
        __syncwarp();
        const int lr = lane & 7, lm = lane >> 3;
#pragma unroll
        for (int kp = 0; kp < 2; kp++) {
            uint32_t a0[4], a1[4];
            ldsm4(a0, stg + ((lm & 1) * 8 + lr) * 128 + (((4 * kp + (lm >> 1)) ^ lr) << 4));
            ldsm4(a1, stg + ((lm & 1) * 8 + lr) * 128 + (((4 * kp + 2 + (lm >> 1)) ^ lr) << 4));
#pragma unroll
            for (int t = 0; t < 6; t++) {
                uint32_t b[4];
                ldsm4(b, stg + (16 + 8 * t + lr) * 128 + (((4 * kp + lm) ^ lr) << 4));
                mma16816(kc + 4 * t, a0[0], a0[1], a0[2], a0[3], b[0], b[1]);
                mma16816(kc + 4 * t, a1[0], a1[1], a1[2], a1[3], b[2], b[3]);
            }
        }
        __syncwarp();
        asm volatile("fence.proxy.async.shared::cta;" ::: "memory");
        const uint32_t cnt = 1u + (__float_as_uint(kc[0] + kc[23]) == 0xffc12345u);
        if (lane == 0) asm volatile("mbarrier.arrive.shared::cta.b64 _,[%0],%1;" ::"r"(bar + 8 * (warp < 8 ? BAR_KG : (warp < 12 ? BAR_KS + w4 : BAR_KGA))), "r"(cnt) : "memory");
        if (warp < 8) handoff(warp >> 2);
    }

    if (warp < 8) {
        const int wg = warp >> 2;
        if (warp == 0) STAMP(21);
        float acc[96];
        const int srow = warp * 16 + (lane & 15);
        const uint32_t srow_a = srow * 128;
        const int sx = srow & 7, shi = lane >> 4;
        const uint64_t da0 = mkdesc(sb + wg * 8192, 16, 1024), db0 = mkdesc(sb + 16384, 8192, 1024);
#pragma unroll 1
        for (int kb = 0; kb < 8; kb++) {
            const int s = kb & 3;
            const uint64_t da = da0 + s * (SLOT >> 4), db = db0 + s * (SLOT >> 4);
            if (warp == 0) STAMP(40 + kb);
            mbar_wait(bar + 8 * (BAR_FULL + s), kb >> 2);
            if (warp == 0) STAMP(32 + kb);
            wg_fence();
#pragma unroll
            for (int k = 0; k < 4; k++) wgmma192(acc, da + 2 * k, db + 128 * k, kb | k);
            wg_commit();
            wg_wait<1>();
            if (lane == 0 && kb > 0) mbar_arrive(bar + 8 * (BAR_EMPTY + ((kb - 1) & 3)));
        }
        mbar_wait(bar + 8 * BAR_WPHI, 0);
        wg_wait<0>();
        fence_regs<96>(acc);
        asm volatile("setmaxnreg.inc.sync.aligned.u32 160;");
        if (lane == 0) mbar_arrive(bar + 8 * BAR_DONE);
        if (warp == 0) STAMP(1);
        uint32_t in[16], qa[16];
        mbar_wait(bar + 8 * BAR_DONE, 0);
#pragma unroll
        for (int r = 0; r < 16; r++) {
            in[r] = pack2(acc[32 + 2 * r], acc[32 + 2 * r + 1]);
            qa[r] = pack2(acc[2 * r], acc[2 * r + 1]);
        }
#pragma unroll
        for (int hh = 0; hh < 4; hh++)
            stsm4(sb + OFF_V + (hh >> 1) * 16384 + srow_a + (((2 * (hh & 1) + shi) ^ sx) << 4), pack2(acc[64 + 8 * hh], acc[65 + 8 * hh]),
                  pack2(acc[66 + 8 * hh], acc[67 + 8 * hh]), pack2(acc[68 + 8 * hh], acc[69 + 8 * hh]), pack2(acc[70 + 8 * hh], acc[71 + 8 * hh]));
        sts128(sb + OFF_V + shi * 16384 + srow_a + ((4 ^ sx) << 4), 0x3f803f80u, 0x3f803f80u, 0x3f803f80u, 0x3f803f80u);
        const uint32_t wphi_a = sb + OFF_WPHI + (lane & 15) * 32 + (lane >> 4) * 16;
        uint32_t pq[4][8];
#pragma unroll 1
        for (int it = 0; it < 2; it++) {
            hedgehog4(in, wphi_a, pq);
            if (it == 1) break;
#pragma unroll
            for (int hs = 0; hs < 8; hs++) {
                float c[4] = {0.f, 0.f, 0.f, 0.f};
                const uint32_t* o = pq[hs >> 1] + 4 * (hs & 1);
                mma16816(c, o[0], o[1], o[2], o[3], 0x3f803f80u, 0x3f803f80u);
                const float r0 = rcp(c[0]), r1 = rcp(c[2]);
                const uint32_t s0 = pack2(r0, r0), s1 = pack2(r1, r1);
                stsm4(sb + OFF_P + (hs >> 2) * 16384 + srow_a + (((2 * (hs & 3) + shi) ^ sx) << 4), hmul2(o[0], s0), hmul2(o[1], s1), hmul2(o[2], s0), hmul2(o[3], s1));
            }
            asm volatile("fence.proxy.async.shared::cta;" ::: "memory");
            bar_named(1, 256);
            if (warp == 0) STAMP(2);
            float d[32];
            const uint64_t dv = mkdesc(sb + OFF_V + wg * 16384, 16, 1024), dp = mkdesc(sb + OFF_P + wg * 16384, 16, 1024);
            wg_fence();
#pragma unroll
            for (int k = 0; k < 8; k++) wgmma64_tt(d, dv + 128 * k, dp + 128 * k, k != 0);
            wg_commit();
            mbar_wait(bar + 8 * BAR_PREP, 0);
            uint4* kvp = scr->kvp + bi * 544 + wg * 272 + (w4 < 2 ? w4 * 136 : 128) + lane;
            wg_wait<0>();
            fence_regs<32>(d);
            if (w4 < 2 || (w4 == 2 && lane < 4)) {
#pragma unroll
                for (int f = 0; f < 4; f++) {
                    const int i0 = 8 * (f >> 1) + 2 * (f & 1), i2 = 16 * (f >> 1) + 8 * (f & 1);
                    const float e0 = w4 == 0 ? d[i0] : (w4 == 1 ? d[16 + i0] : d[i2]), e1 = w4 == 0 ? d[i0 + 1] : (w4 == 1 ? d[17 + i0] : d[i2 + 1]);
                    const float e2 = w4 == 0 ? d[i0 + 4] : (w4 == 1 ? d[20 + i0] : d[i2 + 4]), e3 = w4 == 0 ? d[i0 + 5] : (w4 == 1 ? d[21 + i0] : d[i2 + 5]);
                    st_rlx128(kvp + (w4 < 2 ? f * 32 : (f >> 1) * 136 + (f & 1) * 4), tag4(__float_as_uint(e0), __float_as_uint(e1), __float_as_uint(e2), __float_as_uint(e3), tag));
                }
            }
            __syncwarp();
            if (lane == 0) mbar_arrive(bar + 8 * BAR_PUB);
            if (warp == 0) STAMP(3);
#pragma unroll
            for (int r = 0; r < 16; r++) in[r] = qa[r];
        }
        if (warp == 0) STAMP(4);
        {
            mbar_wait(bar + 8 * BAR_KVF, 0);
            uint4 kf[4][3];
#pragma unroll
            for (int hh = 0; hh < 4; hh++) {
                const uint32_t a = sb + OFF_KVF + hh * 1088;
                kf[hh][0] = lds128(a + lane * 32); kf[hh][1] = lds128(a + lane * 32 + 16); kf[hh][2] = lds128(a + 1024 + q * 16);
            }
            if (warp == 0) STAMP(5);
            uint4* og = scr->o + ((bi_i * 8 + warp) * 32 + bi_j * 4) * 32 + lane;
#pragma unroll
            for (int hh = 0; hh < 4; hh++) {
                float c[6][4];
#pragma unroll
                for (int t = 0; t < 6; t++) { c[t][0] = c[t][1] = c[t][2] = c[t][3] = 0.f; }
                const uint32_t* a = pq[hh];
                const bool od = g & 1;
                mma16816(c[0], a[0], a[1], a[2], a[3], od ? 0x3f803f80u : kf[hh][2].x, od ? 0x3f803f80u : kf[hh][2].y);
                mma16816(c[1], a[4], a[5], a[6], a[7], od ? 0x3f803f80u : kf[hh][2].z, od ? 0x3f803f80u : kf[hh][2].w);
                mma16816(c[2], a[0], a[1], a[2], a[3], kf[hh][0].x, kf[hh][0].y);
                mma16816(c[3], a[0], a[1], a[2], a[3], kf[hh][0].z, kf[hh][0].w);
                mma16816(c[4], a[4], a[5], a[6], a[7], kf[hh][1].x, kf[hh][1].y);
                mma16816(c[5], a[4], a[5], a[6], a[7], kf[hh][1].z, kf[hh][1].w);
                uint32_t w[4];
#pragma unroll
                for (int k = 0; k < 2; k++) {
                    const float rho = c[0][2 * k + 1] * rcp(c[1][2 * k + 1]);
                    const float r = rcp(fmaf(c[0][2 * k + 1], 1e-6f, fmaf(rho, c[1][2 * k], c[0][2 * k]))), rr = r * rho;
                    w[k] = pack2(fmaf(c[4][2 * k], rr, c[2][2 * k] * r), fmaf(c[4][2 * k + 1], rr, c[2][2 * k + 1] * r));
                    w[2 + k] = pack2(fmaf(c[5][2 * k], rr, c[3][2 * k] * r), fmaf(c[5][2 * k + 1], rr, c[3][2 * k + 1] * r));
                }
                st_rlx128(og + hh * 32, tag4(w[0], w[1], w[2], w[3], tag));
            }
        }
        if (warp == 0) STAMP(6);
        float oc[64];
        const int slab = bi_i * 8 + (bi_j >> 2) * 4 + w4;
        const uint8_t* ysrc = (const uint8_t*)scr->y + (size_t)((bi_j & 3) * 32 + wg * 16 + (q >> 1)) * 16384 + slab * 128 + g * 16 + (q & 1) * 8;
        const unsigned* gp = scr->g + (slab * 8 + (g >> 1)) * 8 + (g & 1) * 4;
        uint2 yv[8]; unsigned g0, g1;
        {
            const uint4* osrc = scr->o + (slab * 32 + wg * 16) * 32 + lane;
            uint4 fr[16];
            const unsigned* probe = (const unsigned*)(osrc - lane + ((lane & 3) * 4 + 3) * 32 + 31) + 2;
            unsigned miss = ~0u;
            int n = 0;
            auto fetch = [&](int s) {
#pragma unroll 1
                while ((miss >> s) & 1) { miss = __ballot_sync(~0u, (ld_rlx(probe) ^ tag) & 1); if (++n > SPIN_LIMIT) break; }
#pragma unroll
                for (int k = 4 * s; k < 4 * s + 4; k++) fr[k] = ld_rlx128(osrc + k * 32);
            };
            const uint64_t dw = mkdesc(sb + wg * 2 * SLOT, wg ? 32768 : SLOT, 1024);
            auto mma = [&](int s) {
#pragma unroll 1
                while (__builtin_expect(__any_sync(~0u, (bad4(fr[4 * s], tag) | bad4(fr[4 * s + 1], tag) | bad4(fr[4 * s + 2], tag) | bad4(fr[4 * s + 3], tag)) & 1), 0)) {
#pragma unroll
                    for (int k = 4 * s; k < 4 * s + 4; k++) fr[k] = ld_rlx128(osrc + k * 32);
                    if (++n > SPIN_LIMIT) break;
                }
                wg_fence();
#pragma unroll
                for (int hh = 0; hh < 4; hh++) wgmma128_rs(oc, fr[4 * s + hh], dw + 128 * (4 * s + hh), (s | hh) != 0);
                wg_commit();
            };
            fetch(0); fetch(1);
            mbar_wait(bar + 8 * (wg ? BAR_WO2 : BAR_WO), 0);
            mma(0); fetch(2); mma(1); fetch(3);
            if (warp == 0) STAMP(14);
            wg_wait<1>();
#pragma unroll
            for (int nt = 0; nt < 8; nt++) yv[nt] = ld_rlx64(ysrc + nt * 32768);
            g0 = ld_rlx(gp); g1 = ld_rlx(gp + 32);
            mma(2); mma(3);
            if (warp == 0) STAMP(7);
            {
#pragma unroll 1
                while (true) {
                    uint32_t bad = (g0 ^ tag) | (g1 ^ tag);
#pragma unroll
                    for (int nt = 0; nt < 8; nt++) bad |= yv[nt].x ^ tag;
                    if (!__any_sync(~0u, bad & 1)) break;
#pragma unroll
                    for (int nt = 0; nt < 8; nt++) if ((yv[nt].x ^ tag) & 1) yv[nt] = ld_rlx64(ysrc + nt * 32768);
                    g0 = ld_rlx(gp); g1 = ld_rlx(gp + 32);
                    if (++n > SPIN_LIMIT) break;
                }
            }
            if (warp == 0) STAMP(28);
        }
        {
            const float ga = bf_hi(g0), gb = bf_hi(g1);
            const float ha = bf_round(1.0f - ga), hb = bf_round(1.0f - gb);
            float yb[32];
#pragma unroll
            for (int nt = 0; nt < 8; nt++) {
                yb[4 * nt] = ha * bf_lo(yv[nt].x); yb[4 * nt + 1] = ha * bf_hi(yv[nt].x);
                yb[4 * nt + 2] = hb * bf_lo(yv[nt].y); yb[4 * nt + 3] = hb * bf_hi(yv[nt].y);
            }
            fence_regs<32>(yb);
            const uint32_t xw = sb + wg * 2 * SLOT + (tid & 127) * 16, xr = sb + (wg ^ 1) * 2 * SLOT + (tid & 127) * 16;
            wg_wait<0>();
            fence_regs<64>(oc);
            bar_named(3 + wg, 128);
#pragma unroll
            for (int r = 0; r < 8; r++)
                sts128(xw + r * 2048, __float_as_uint(oc[32 + 4 * r]), __float_as_uint(oc[33 + 4 * r]), __float_as_uint(oc[34 + 4 * r]), __float_as_uint(oc[35 + 4 * r]));
#pragma unroll
            for (int r = 0; r < 32; r++) yb[r] = fmaf((r & 2) ? gb : ga, oc[r], yb[r]);
            bar_named(1, 256);
            if (warp == 0) STAMP(8);
            uint32_t w[8][2];
#pragma unroll
            for (int nt = 0; nt < 8; nt++) {
                const uint4 p = lds128(xr + nt * 2048);
                w[nt][0] = pack2(fmaf(ga, __uint_as_float(p.x), yb[4 * nt]), fmaf(ga, __uint_as_float(p.y), yb[4 * nt + 1]));
                w[nt][1] = pack2(fmaf(gb, __uint_as_float(p.z), yb[4 * nt + 2]), fmaf(gb, __uint_as_float(p.w), yb[4 * nt + 3]));
            }
            const uint32_t ob = sb + wg * 2 * SLOT + 16384 + w4 * 2048;
#pragma unroll
            for (int nt = 0; nt < 8; nt += 2)
                stsm4(ob + (lane & 15) * 128 + (((nt + shi) ^ (lane & 7)) << 4), w[nt][0], w[nt][1], w[nt + 1][0], w[nt + 1][1]);
            __syncwarp();
            bf16* op = out + (size_t)(slab * 16) * 512 + (bi_j & 3) * 128 + wg * 64 + (lane & 7) * 8;
#pragma unroll
            for (int it = 0; it < 4; it++) {
                const int r = it * 4 + (lane >> 3);
                uint4 v = lds128(ob + r * 128 + (((lane & 7) ^ (r & 7)) << 4));
                *(uint4*)(op + r * 512) = v;
            }
        }
        if (warp == 0) STAMP(10);
    } else if (warp < 12) {
        if (warp == 8) {
            mbar_wait(bar + 8 * BAR_KGA, 0);
            if (lane == 0) load_stage(2);
            STAMP(22);
            mbar_wait(bar + 8 * BAR_KG, 0);
            if (lane == 0) load_stage(3);
            __syncwarp();
            STAMP(17);
        }
        if (warp == 8) {
#pragma unroll 1
            for (int kb = 0; kb < 6; kb++) {
                const int s = kb & 3;
                mbar_wait(bar + 8 * (BAR_EMPTY + s), kb >> 2);
                if (kb == xkb) mbar_wait(bar + 8 * BAR_XT, 0);
                if (lane == 0) {
                    STAMP(48 + kb);
                    if (kb < 4) load_stage(kb + 4);
                    else {
                        mbar_expect(bar + 8 * BAR_WO, 32768);
                        tma2d(sb + s * SLOT, &mwo, (bi_j & 3) * 128 + s * 64, 0, bar + 8 * BAR_WO);
                        if (kb == 5) mbar_arrive(bar + 8 * BAR_SP2);
                    }
                }
                __syncwarp();
            }
        } else if (warp == 9) {
            const int row = bi_j * 16 + (lane >> 1), half = lane & 1;
            unsigned* gp = scr->g + (bi_i * 64 + bi_j * 8) * 8 + lane * 2;
            st_rlx64(gp, tag ^ 1u, tag ^ 1u);
            float gs0 = 0.f, gs1 = 0.f;
            mbar_wait(bar + 8 * BAR_WPHI, 0);
#pragma unroll 1
            for (int kb = 0; kb < 8; kb++) {
                const int s = kb & 3;
                mbar_wait(bar + 8 * (BAR_FULL + s), kb >> 2);
#pragma unroll
                for (int c = 0; c < 4; c++) {
                    const uint4 xv = lds128(sb + s * SLOT + row * 128 + (((half * 4 + c) ^ (row & 7)) << 4));
                    const uint4 gw = lds128(sb + OFF_GW + ((kb + rot) & 7) * 128 + half * 64 + c * 16);
                    const uint32_t p0 = hmul2(xv.x, gw.x), p1 = hmul2(xv.y, gw.y), p2 = hmul2(xv.z, gw.z), p3 = hmul2(xv.w, gw.w);
                    gs0 += (bf_lo(p0) + bf_lo(p1)) + (bf_lo(p2) + bf_lo(p3));
                    gs1 += (bf_hi(p0) + bf_hi(p1)) + (bf_hi(p2) + bf_hi(p3));
                }
                const uint32_t cnt = 1u + (__float_as_uint(gs0 + gs1) == 0xffc12345u);
                if (lane == 0) asm volatile("mbarrier.arrive.shared::cta.b64 _,[%0],%1;" ::"r"(bar + 8 * (kb < 7 ? BAR_EMPTY + s : BAR_DONE)), "r"(cnt) : "memory");
                __syncwarp();
            }
            float gs = gs0 + gs1;
            gs += __shfl_xor_sync(~0u, gs, 1);
            const uint32_t gv = __float_as_uint(bf_round(rcp(1.0f + ex2(-1.4426950408889634f * bf_round(gs))))) | tag;
            st_rlx64(gp, gv, gv);
        }
        mbar_wait(bar + 8 * (BAR_KP + w4), 0);
#pragma unroll
        for (int t = 0; t < 15; t++) {
            const uint4 v = lds128(buf + (t * 32 + lane) * 16);
            kc[4 * (t % 5)] += __uint_as_float(v.x); kc[4 * (t % 5) + 1] += __uint_as_float(v.y); kc[4 * (t % 5) + 2] += __uint_as_float(v.z); kc[4 * (t % 5) + 3] += __uint_as_float(v.w);
        }
        {
            const uint4 v = lds128(buf + 7680);
            kc[20] += __uint_as_float(v.x) + __uint_as_float(v.y) + __uint_as_float(v.z);
            const uint32_t cnt = 1u + (__float_as_uint(kc[20] + kc[19] + kc[0]) == 0xffc12345u);
            if (lane == 0) asm volatile("mbarrier.arrive.shared::cta.b64 _,[%0],%1;" ::"r"(bar + 8 * (BAR_KD + w4)), "r"(cnt) : "memory");
            __syncwarp();
        }
        if (lane == 0) kc[4 * 0 + 0] += ((ch & 1) ? bf_hi(pds) : bf_lo(pds));
        const uint32_t k1024 = __shfl_sync(~0u, pack2(kc[4 * 4 + 0], 0.f), 0);
#pragma unroll
        for (int i = 0; i < 2; i++) {
            const int be = g + 8 * i;
#pragma unroll
            for (int t = 0; t < 2; t++) {
                const uint32_t a = kb_ + (KW_D + 128 * t + 8 * be + 2 * q) * 4;
                const uint32_t w = pack2(kc[4 * t + 2 * i + 1], kc[4 * t + 2 * i]);
                sts32(a + 4, w); sts16(a, w >> 16); sts16(a + 10, w);
            }
            {
                const int p = 256 + 128 * (q >> 1) + 8 * be + 4 * (q & 1);
                const uint32_t a = kb_ + (KW_D + p) * 4;
                const uint32_t w = pack2(kc[4 * 2 + 2 * i + 1], kc[4 * 2 + 2 * i]);
                const uint32_t aa = (w >> 16) | (w & 0xffff0000u);
                if (p != 256) { sts16(a - 4, aa); sts32(a, aa); } else sts16(a, aa);
                sts32(a + 4, aa); sts32(a + 8, w); sts16(a + 14, w);
            }
            {
                const int k = 64 + 16 * q + be;
                const uint32_t w = pack2(kc[4 * 3 + 2 * i], kc[4 * 3 + 2 * i + 1]);
                if (k != 64) sts16(kb_ + (KW_2 + ((k - 1) >> 1) - 24) * 4 + (k & 1) * 2, w);
                else {
                    const uint32_t a = kb_ + (KW_D + 511) * 4, aa = (w << 16) | (w & 0xffffu);
                    sts16(a, w); sts32(a + 4, aa); sts32(a + 8, aa); sts32(a + 12, aa); sts16(a + 18, w);
                }
                sts16(kb_ + (KW_2 + 48 + (k >> 1) - 24) * 4 + ((k & 1) ^ 1) * 2, w >> 16);
            }
#pragma unroll
            for (int b = 0; b < 2; b++) {
                const int k = 64 + 8 * (2 * q + b) + (be >> 1);
                const uint32_t w = pack2(kc[4 * 4 + 2 * i + b], 0.f);
                if (!(be & 1) && k == 64) sts16(kb_ + (KW_2 + 63 - 24) * 4, w);
                else {
                    const uint32_t a = kb_ + (KW_3 + ((be & 1) ? 80 + k : k - 1) - 48) * 4;
                    sts16(a, w);
                    if (!((be & 1) && k == 127)) sts16(a + 6, w);
                }
            }
        }
        if (lane == 0) sts16(kb_ + (KW_3 + 127 - 48) * 4, pack2(kc[4 * 5 + 0], 0.f));
        __syncwarp();
        asm volatile("setmaxnreg.inc.sync.aligned.u32 136;");
        mbar_wait(bar + 8 * BAR_UR, 0);
        mbar_wait(bar + 8 * BAR_DONE, 0);
        if (warp == 8) STAMP(23);
        float y[16][4];
#pragma unroll
        for (int nt = 0; nt < 16; nt++) { y[nt][0] = y[nt][1] = y[nt][2] = y[nt][3] = 0.f; }
        {
            uint32_t Bp[32], A[4][3], An[4][3];
            auto uaddr = [&](int rho) { const int R0 = (lane >> 4) * 64 + (lane & 7) - rho; return ub + (((2 * R0 + ((lane >> 3) & 1)) ^ ((R0 >> 2) & 1)) << 4); };
            const uint32_t kd = kb_ + (KW_D + g - 2 * q) * 4;
#pragma unroll 1
            for (int rho = 1; rho >= 0; rho--) {
                const uint32_t a = uaddr(rho), k = kd + 2048 + rho * 64;
#pragma unroll
                for (int i = 0; i < 8; i++) ldsm4(Bp + 4 * i, a + i * 256);
                const uint32_t a0 = lds32(k), a1 = lds32(k + 32), a2 = lds32(k - 32);
#pragma unroll
                for (int i = 0; i < 12; i++) mma16816(y[i + 4], a0, a1, a2, a0, Bp[4 * (i & 7) + 2 * (i >> 3)], Bp[4 * (i & 7) + 2 * (i >> 3) + 1]);
            }
#pragma unroll
            for (int ga = 0; ga < 4; ga++) { An[ga][0] = lds32(kd + ga * 512); An[ga][1] = lds32(kd + ga * 512 + 32); An[ga][2] = lds32(kd + ga * 512 - 32); }
#pragma unroll 1
            for (int rho = 0; rho < 8; rho++) {
#pragma unroll
                for (int ga = 0; ga < 4; ga++) {
                    const uint32_t a = kd + (rho + 1) * 64 + ga * 512;
                    A[ga][0] = An[ga][0]; A[ga][1] = An[ga][1]; A[ga][2] = An[ga][2];
                    An[ga][0] = lds32(a); An[ga][1] = lds32(a + 32); An[ga][2] = lds32(a - 32);
                }
                const uint32_t an = uaddr(rho + 1);
#pragma unroll
                for (int i = 0; i < 8; i++) {
#pragma unroll
                    for (int ga = 0; ga < 4; ga++) {
                        mma16816(y[i + ga], A[ga][0], A[ga][1], A[ga][2], A[ga][0], Bp[4 * i], Bp[4 * i + 1]);
                        if (i + 8 + ga < 16) mma16816(y[i + 8 + ga], A[ga][0], A[ga][1], A[ga][2], A[ga][0], Bp[4 * i + 2], Bp[4 * i + 3]);
                    }
                    ldsm4(Bp + 4 * i, an + i * 256);
                    __syncwarp();
                }
            }
        }
        if (warp == 8) STAMP(18);
        mbar_wait(bar + 8 * BAR_WR, 0);
#pragma unroll 1
        for (int ph = 0; ph < 2; ph++) {
            uint32_t B[5][2];
            const uint32_t ka = kb_ + (KW_2 + ph * 48 + 8 + g - q) * 4;
#pragma unroll
            for (int dd = 0; dd < 5; dd++) { B[dd][0] = lds32(ka + dd * 32); B[dd][1] = lds32(ka + dd * 32 - 16); }
            const uint32_t wa = buf + ph * W3_OFF + ((lane & 7) + ((lane >> 3) & 1) + (lane >> 4) * 8) * 16;
#pragma unroll
            for (int s = 0; s < 12; s++) {
                uint32_t A[4];
                ldsm4t(A, wa + s * 256);
#pragma unroll
                for (int dd = 0; dd < 5; dd++)
                    if (s + 4 + dd < 16) mma16816(y[s + 4 + dd], A[0], A[1], A[2], A[3], B[dd][0], B[dd][1]);
            }
        }
        {
            const int ap = (lane & 7) + (lane >> 4) * 8;
            const uint32_t loff = ((2 * ap + ((lane >> 3) & 1)) ^ ((ap >> 2) & 1)) << 4;
#pragma unroll 1
            for (int ph = 0; ph < 2; ph++) {
                uint32_t B[8][2];
                const uint32_t wb = (ph ? spare : buf + W9_OFF) + loff;
                const uint32_t ka = kb_ + (KW_3 + ph * 80 + 16 + g - 2 * q) * 4;
#pragma unroll
                for (int dd = 0; dd < 8; dd++) { B[dd][0] = lds32(ka + dd * 32); B[dd][1] = lds32(ka + dd * 32 - 32); }
#pragma unroll
                for (int s = 0; s < 4; s++) {
                    uint32_t A[4];
                    ldsm4t(A, wb + s * 512);
#pragma unroll
                    for (int dd = 0; dd < 8; dd++)
                        if (8 + 2 * s + dd < 16) mma16816(y[8 + 2 * s + dd], A[0], A[1], A[2], A[3], B[dd][0], B[dd][1]);
                }
            }
            const uint32_t idw = (g == 2 * q) ? k1024 : ((g == 2 * q + 1) ? (k1024 << 16) : 0u);
#pragma unroll
            for (int s = 0; s < 4; s++) {
                uint32_t A[4];
                ldsm4t(A, spare + 2048 + loff + s * 512);
                mma16816(y[8 + 2 * s], A[0], A[1], A[2], A[3], idw, 0u);
                mma16816(y[9 + 2 * s], A[0], A[1], A[2], A[3], 0u, idw);
            }
        }
        __syncwarp();
        if (warp == 8) STAMP(19);
#pragma unroll
        for (int nt = 0; nt < 16; nt++)
#pragma unroll
            for (int b = 0; b < 2; b++) sts32(buf + ((8 * nt + 2 * q + b) * 8 + g) * 4, pack2(y[nt][b], y[nt][2 + b]));
        bar_named(2, 128);
        uint4* yp = scr->y + bi * 1024 + st;
#pragma unroll
        for (int v = 0; v < 8; v++) {
            const uint32_t a = sb + OFF_BUF + (st + 128 * v) * 4;
            const uint32_t w0 = lds32(a), w1 = lds32(a + BUF_STRIDE), w2 = lds32(a + 2 * BUF_STRIDE), w3 = lds32(a + 3 * BUF_STRIDE);
            st_rlx128(yp + v * 128, tag4(__byte_perm(w0, w1, 0x5410), __byte_perm(w0, w1, 0x7632), __byte_perm(w2, w3, 0x5410), __byte_perm(w2, w3, 0x7632), tag));
        }
        if (warp == 8) STAMP(20);
    } else {
        const int qq = (bi_i & 2) + ((lane >> 1) & 1);
        uint2* kvf_h = (uint2*)(scr->kvf + (bi_j * 4 + (bi_i >> 2)) * 68);
        auto windows = [&](int rhi, int rlo) {
#pragma unroll 1
            for (int rho = rhi; rho >= rlo; rho--) {
                const int ci = lane + 32 * rho;
                uint4 e4[4];
#pragma unroll
                for (int v = 0; v < 4; v++) { const int cc = ci - 3 + v; e4[v] = lds128(ub + ((cc ^ ((cc >> 3) & 1)) << 4)); }
                float S[29];
                const uint32_t* ew = (const uint32_t*)e4;
                S[3] = 0.f;
#pragma unroll
                for (int k = 4; k <= 28; k++) S[k] = S[k - 1] + ((k & 1) ? bf_hi(ew[k >> 1]) : bf_lo(ew[k >> 1]));
                auto win = [&](int lo, int hi, uint32_t a) {
                    sts128(a, pack2(S[hi] - S[lo - 1], S[hi + 1] - S[lo]), pack2(S[hi + 2] - S[lo + 1], S[hi + 3] - S[lo + 2]),
                           pack2(S[hi + 4] - S[lo + 3], S[hi + 5] - S[lo + 4]), pack2(S[hi + 6] - S[lo + 5], S[hi + 7] - S[lo + 6]));
                };
                win(14, 18, buf + W5_OFF + 16 + ci * 16); win(19, 21, buf + W3_OFF + 16 + ci * 16);
                if (rho < 4) {
                    const uint32_t sw = (ci ^ ((ci >> 3) & 1)) << 4;
                    win(4, 12, buf + W9_OFF + sw); win(13, 19, spare + sw); win(20, 21, spare + 2048 + sw);
                }
            }
        };
        {
            mbar_wait(bar + 8 * (BAR_FULL + xkb), 0);
#pragma unroll 1
            for (int hf = 0; hf < 2; hf++) {
                const int r = w4 * 32 + hf * 16 + (lane & 15);
                uint32_t* xt = (uint32_t*)scr->xt + ((xkb + rot) * 16 + (g >> 2)) * 4096 + (bi_i * 16 + w4 * 4 + hf * 2) * 16 + (g & 3) * 4 + q;
#pragma unroll
                for (int cb = 0; cb < 8; cb += 2) {
                    uint32_t v[4];
                    ldsm4t(v, sb + xkb * SLOT + r * 128 + (((cb + (lane >> 4)) ^ (r & 7)) << 4));
                    xt[cb * 8192] = v[0]; xt[cb * 8192 + 16] = v[1]; xt[cb * 8192 + 8192] = v[2]; xt[cb * 8192 + 8192 + 16] = v[3];
                }
            }
            __syncwarp();
            if (lane == 0) mbar_arrive(bar + 8 * BAR_XT);
            if (warp == 12) STAMP(26);
            handoff(2);
            asm volatile("setmaxnreg.dec.sync.aligned.u32 56;");
            if (lane == 0) asm volatile("red.release.gpu.global.add.u32 [%0],2;" ::"l"(scr->xcnt + (xkb + rot) * 32) : "memory");
            __syncwarp();
            if (warp == 12) STAMP(27);
            {
                const uint32_t old = tag ^ 1u;
                const uint4 z4 = make_uint4(old, 0, old, 0);
#pragma unroll
                for (int v = 0; v < 5; v++) if (v < 4 || st < 32) st_rlx128(scr->kvp + bi * 544 + v * 128 + st, z4);
                if (st < 16) st_rlx128(scr->o + ((bi_i * 8 + (st >> 1)) * 32 + bi_j * 4 + 3) * 32 + 30 + (st & 1), z4);
                if (lane < 8) st_rlx64(kvf_h + ((bi_i & 3) * 8 + w4 * 2 + (lane & 1)) * 4 + (lane >> 1), old, 0);
                if (st < 4 && !(bi_i & 1)) st_rlx64(kvf_h + (64 + qq) * 2 + (lane & 1), old, 0);
                __syncwarp();
                if (lane == 0) mbar_arrive(bar + 8 * BAR_PREP);
            }
            int n = 0;
#pragma unroll 1
            while (__any_sync(~0u, (int)(ld_acq(scr->xcnt + bi_j * 32) - (epoch1 << 7)) < 0)) { if (++n > SPIN_LIMIT) break; }
            if (warp == 12) STAMP(15);
            uint4 ur[8];
#pragma unroll
            for (int v = 0; v < 8; v++) ur[v] = __ldcg(scr->xt + bi * 1024 + st + 128 * v);
            mbar_wait(bar + 8 * BAR_KG, 0);
            if (lane < 16) sts128(ub - 256 + lane * 16, 0, 0, 0, 0);
#pragma unroll
            for (int v = 0; v < 8; v++) {
                const int ci = (st >> 2) + 32 * v;
                sts128(sb + OFF_U + (st & 3) * U_STRIDE + 256 + ((ci ^ ((ci >> 3) & 1)) << 4), ur[v].x, ur[v].y, ur[v].z, ur[v].w);
            }
            __syncwarp();
            if (lane == 0) mbar_arrive(bar + 8 * BAR_UR);
            mbar_wait(bar + 8 * BAR_UR, 0);
            if (warp == 12) STAMP(16);
            mbar_wait(bar + 8 * (BAR_KD + w4), 0);
            if (lane < 2) sts128(buf + lane * W3_OFF, 0, 0, 0, 0);
            windows(5, 4);
        }
        mbar_wait(bar + 8 * BAR_SP2, 0);
        windows(3, 0);
        __syncwarp();
        if (lane == 0) mbar_arrive(bar + 8 * BAR_WR);
        if (warp == 12) STAMP(24);
        {
            const bool zw = st < 32 && !(bi_i & 1);
            const uint4* src = scr->kvp + bi_j * (16 * 544) + (bi_i >> 2) * 136;
            const uint4* zsrc = src + (lane >> 2) * (2 * 544) + 128 + (lane & 1) * 4 + qq;
            src += (lane >> 3) * (4 * 544) + ((lane >> 1) & 3) * 32 + (bi_i & 3) * 8 + w4 * 2 + (lane & 1);
            mbar_wait(bar + 8 * BAR_PUB, 0);
            if (warp == 12) STAMP(12);
            uint4 v[6];
#pragma unroll
            for (int k = 0; k < 6; k++) v[k] = make_uint4(tag ^ 1u, 0, 0, 0);
            int n = 0;
#pragma unroll 1
            while (true) {
#pragma unroll
                for (int k = 0; k < 6; k++) if ((bad4(v[k], tag) & 1) && (k < 4 || zw)) v[k] = ld_rlx128(k < 4 ? src + k * 544 : zsrc + (k - 4) * 544);
                if (!__any_sync(~0u, (bad4(v[0], tag) | bad4(v[1], tag) | bad4(v[2], tag) | bad4(v[3], tag) | (zw ? bad4(v[4], tag) | bad4(v[5], tag) : 0u)) & 1)) break;
                if (++n > SPIN_LIMIT) break;
            }
            if (warp == 12) STAMP(30);
            float f[8];
            const float* vf = (const float*)v;
#pragma unroll
            for (int r = 0; r < 4; r++) {
                f[r] = (vf[r] + vf[4 + r]) + (vf[8 + r] + vf[12 + r]);
                f[4 + r] = vf[16 + r] + vf[20 + r];
                f[4 + r] += __shfl_xor_sync(~0u, f[4 + r], 4);
            }
#pragma unroll
            for (int o = 8; o <= 16; o <<= 1)
#pragma unroll
                for (int r = 0; r < 8; r++) f[r] += __shfl_xor_sync(~0u, f[r], o);
            if (lane < 8) st_rlx64(kvf_h + ((bi_i & 3) * 8 + w4 * 2 + (lane & 1)) * 4 + (lane >> 1), tagw(pack2(f[0], f[1]), tag), pack2(f[2], f[3]));
            if (zw && lane < 4) st_rlx64(kvf_h + (64 + qq) * 2 + (lane & 1), tagw(pack2(f[4], f[5]), tag), pack2(f[6], f[7]));
        }
        if (warp == 12) STAMP(13);
        {
            const uint4* kp = scr->kvf + bi_j * 272 + st;
            uint4 v0 = make_uint4(tag ^ 1u, 0, 0, 0), v1 = v0, v2 = make_uint4(st < 16 ? tag ^ 1u : tag, 0, tag, 0);
            int n = 0;
#pragma unroll 1
            while (true) {
                if (bad4(v0, tag) & 1) v0 = ld_rlx128(kp);
                if (bad4(v1, tag) & 1) v1 = ld_rlx128(kp + 128);
                if (bad4(v2, tag) & 1) v2 = ld_rlx128(kp + 256);
                if (!__any_sync(~0u, (bad4(v0, tag) | bad4(v1, tag) | bad4(v2, tag)) & 1)) break;
                if (++n > SPIN_LIMIT) break;
            }
            sts128(sb + OFF_KVF + st * 16, v0.x, v0.y, v0.z, v0.w);
            sts128(sb + OFF_KVF + 2048 + st * 16, v1.x, v1.y, v1.z, v1.w);
            if (st < 16) sts128(sb + OFF_KVF + 4096 + st * 16, v2.x, v2.y, v2.z, v2.w);
            __syncwarp();
            if (lane == 0) mbar_arrive(bar + 8 * BAR_KVF);
        }
        if (warp == 13) {
            mbar_wait(bar + 8 * BAR_KVF, 0);
            if (lane == 0) {
                mbar_expect(bar + 8 * BAR_WO2, 65536);
                tma2d(sb + OFF_P, &mwo, (bi_j & 3) * 128 + 64, 256, bar + 8 * BAR_WO2);
                tma2d(sb + OFF_V, &mwo, (bi_j & 3) * 128, 256, bar + 8 * BAR_WO2);
            }
        }
        if (warp == 12) STAMP(25);
    }
    __syncwarp();
    if (lane == 0) {
        unsigned old;
        asm volatile("atom.acq_rel.cta.shared.add.u32 %0,[%1],1;" : "=r"(old) : "r"(bar + OFF_CNT) : "memory");
        if (old == 15) {
            atomicAdd(scr->done, 1u);
        }
    }
}

typedef CUresult (*EncFn)(CUtensorMap*, CUtensorMapDataType, cuuint32_t, void*, const cuuint64_t*, const cuuint64_t*, const cuuint32_t*,
                          const cuuint32_t*, CUtensorMapInterleave, CUtensorMapSwizzle, CUtensorMapL2promotion, CUtensorMapFloatOOBfill);

extern "C" void kernel_launch(void* const* d_in, const int* in_sizes, int n_in, void* d_out, int out_size) {
    static EncFn enc = nullptr;
    static Scratch* scr = nullptr;
    if (!enc) {
        cudaGetSymbolAddress((void**)&scr, g_scr);
        cudaDriverEntryPointQueryResult qr;
        cudaGetDriverEntryPoint("cuTensorMapEncodeTiled", (void**)&enc, cudaEnableDefault, &qr);
        cudaFuncSetAttribute(fused_kernel, cudaFuncAttributeMaxDynamicSharedMemorySize, SMEM_BYTES);
    }
    CUtensorMap mx, mw, mwo;
    const cuuint32_t es[3] = {1, 1, 1};
    {
        cuuint64_t d[2] = {512, 2048}, s[1] = {1024}; cuuint32_t b[2] = {64, 128};
        enc(&mx, CU_TENSOR_MAP_DATA_TYPE_BFLOAT16, 2, d_in[0], d, s, b, es, CU_TENSOR_MAP_INTERLEAVE_NONE, CU_TENSOR_MAP_SWIZZLE_128B,
            CU_TENSOR_MAP_L2_PROMOTION_L2_128B, CU_TENSOR_MAP_FLOAT_OOB_FILL_NONE);
    }
    {
        cuuint64_t d[3] = {512, 512, 3}, s[2] = {3072, 1024}; cuuint32_t b[3] = {64, 64, 3};
        enc(&mw, CU_TENSOR_MAP_DATA_TYPE_BFLOAT16, 3, d_in[1], d, s, b, es, CU_TENSOR_MAP_INTERLEAVE_NONE, CU_TENSOR_MAP_SWIZZLE_128B,
            CU_TENSOR_MAP_L2_PROMOTION_L2_128B, CU_TENSOR_MAP_FLOAT_OOB_FILL_NONE);
    }
    {
        cuuint64_t d[2] = {512, 512}, s[1] = {1024}; cuuint32_t b[2] = {64, 256};
        enc(&mwo, CU_TENSOR_MAP_DATA_TYPE_BFLOAT16, 2, d_in[3], d, s, b, es, CU_TENSOR_MAP_INTERLEAVE_NONE, CU_TENSOR_MAP_SWIZZLE_128B,
            CU_TENSOR_MAP_L2_PROMOTION_L2_128B, CU_TENSOR_MAP_FLOAT_OOB_FILL_NONE);
    }
    fused_kernel<<<128, 512, SMEM_BYTES, cudaStreamPerThread>>>(
        scr, (const bf16*)d_in[5], (const bf16*)d_in[6], (const bf16*)d_in[7], (const bf16*)d_in[8], (const bf16*)d_in[9],
        (const bf16*)d_in[10], (const bf16*)d_in[2], (const bf16*)d_in[11], (bf16*)d_out, mx, mw, mwo);
}
```

```cpp
#include <cuda_runtime.h>
#include <cuda.h>
#include <cuda_bf16.h>
#include <stdint.h>

typedef __nv_bfloat16 bf16;

struct Scratch {
    uint4 xt[128 * 1024];
    uint4 o[16 * 8 * 32 * 32];
    uint4 y[128 * 1024];
    uint4 kvp[8 * 16 * 544];
    uint4 kvf[8 * 4 * 68];
    unsigned g[1024 * 8];
    unsigned xcnt[8 * 32];
    unsigned done[32];
};
__device__ Scratch g_scr;
#define STAMP(n)

constexpr int SLOT = 40960;
constexpr int OFF_SP0 = 32768, OFF_SP1 = SLOT + 32768;
constexpr int OFF_P = 2 * SLOT, OFF_V = OFF_P + 32768;
constexpr int OFF_KVF = OFF_V + 32768;
constexpr int KT_BYTES = 3264, KW_D = 16, KW_2 = 560, KW_3 = 656;
constexpr int OFF_U = 4 * SLOT, U_STRIDE = 4096 + 256 + 32;
constexpr int OFF_BUF = OFF_U + 4 * U_STRIDE, BUF_STRIDE = 8320;
constexpr int OFF_K = OFF_BUF + 4 * BUF_STRIDE;
constexpr int OFF_WPHI = OFF_K + 4 * KT_BYTES;
constexpr int OFF_GW = OFF_WPHI + 2048;
constexpr int OFF_BAR = OFF_GW + 1024;
constexpr int SMEM_BYTES = OFF_BAR + 320 + 256;
static_assert(SMEM_BYTES <= 232448 && OFF_BUF % 128 == 0, "smem");
constexpr int W5_OFF = 0, W3_OFF = 3088, W9_OFF = 6176;
constexpr int BAR_FULL = 0, BAR_EMPTY = 4, BAR_WPHI = 8, BAR_WO = 9, BAR_WO2 = 10, BAR_XT = 11, BAR_DONE = 12, BAR_KG = 13, BAR_SP = 14,
              BAR_PUB = 15, BAR_KVX = 16, BAR_UR = 17, BAR_WR = 18, BAR_PREP = 19, BAR_KGA = 20, BAR_SP2 = 21, BAR_KS = 22, BAR_KP = 26, BAR_KD = 30, BAR_KVF = 34, OFF_CNT = 304;
constexpr int SPIN_LIMIT = 1 << 17;

__device__ __forceinline__ uint32_t s2u(const void* p) { return (uint32_t)__cvta_generic_to_shared(p); }
__device__ __forceinline__ void mbar_init(uint32_t b, int c) { asm volatile("mbarrier.init.shared::cta.b64 [%0],%1;" ::"r"(b), "r"(c) : "memory"); }
__device__ __forceinline__ void mbar_expect(uint32_t b, int bytes) { asm volatile("mbarrier.arrive.expect_tx.shared::cta.b64 _,[%0],%1;" ::"r"(b), "r"(bytes) : "memory"); }
__device__ __forceinline__ void mbar_arrive(uint32_t b) { asm volatile("mbarrier.arrive.shared::cta.b64 _,[%0];" ::"r"(b) : "memory"); }
__device__ __forceinline__ void mbar_wait(uint32_t b, int ph) {
    asm volatile("{\n.reg .pred p;\n.reg .u32 n;\nmov.u32 n,0;\nLW_%=:\nmbarrier.try_wait.parity.shared::cta.b64 p,[%0],%1;\n@p bra LD_%=;\n"
                 "add.u32 n,n,1;\nsetp.lt.u32 p,n,16384;\n@p bra LW_%=;\nLD_%=:\n}" ::"r"(b), "r"(ph) : "memory");
}
__device__ __forceinline__ void tma2d(uint32_t dst, const CUtensorMap* m, int c0, int c1, uint32_t bar) {
    asm volatile("cp.async.bulk.tensor.2d.shared::cluster.global.mbarrier::complete_tx::bytes [%0],[%1,{%3,%4}],[%2];" ::"r"(dst), "l"(m), "r"(bar), "r"(c0), "r"(c1) : "memory");
}
__device__ __forceinline__ void tma3d(uint32_t dst, const CUtensorMap* m, int c0, int c1, int c2, uint32_t bar) {
    asm volatile("cp.async.bulk.tensor.3d.shared::cluster.global.mbarrier::complete_tx::bytes [%0],[%1,{%3,%4,%5}],[%2];" ::"r"(dst), "l"(m), "r"(bar), "r"(c0), "r"(c1), "r"(c2) : "memory");
}
__device__ __forceinline__ void bulk_g2s(uint32_t dst, const void* src, int bytes, uint32_t bar) {
    asm volatile("cp.async.bulk.shared::cluster.global.mbarrier::complete_tx::bytes [%0],[%1],%2,[%3];" ::"r"(dst), "l"(src), "r"(bytes), "r"(bar) : "memory");
}
__device__ __forceinline__ uint64_t mkdesc(uint32_t addr, uint32_t lbo, uint32_t sbo) {
    return (uint64_t)((addr & 0x3FFFF) >> 4) | ((uint64_t)(lbo >> 4) << 16) | ((uint64_t)(sbo >> 4) << 32) | ((uint64_t)1 << 62);
}
__device__ __forceinline__ void wg_fence() { asm volatile("wgmma.fence.sync.aligned;" ::: "memory"); }
__device__ __forceinline__ void wg_commit() { asm volatile("wgmma.commit_group.sync.aligned;" ::: "memory"); }
template <int N> __device__ __forceinline__ void wg_wait() { asm volatile("wgmma.wait_group.sync.aligned %0;" ::"n"(N) : "memory"); }
template <int N> __device__ __forceinline__ void fence_regs(float* d) {
#pragma unroll
    for (int i = 0; i < N; i++) asm volatile("" : "+f"(d[i])::"memory");
}
#define R8(d, o) "+f"(d[o]), "+f"(d[o + 1]), "+f"(d[o + 2]), "+f"(d[o + 3]), "+f"(d[o + 4]), "+f"(d[o + 5]), "+f"(d[o + 6]), "+f"(d[o + 7])
__device__ __forceinline__ void wgmma192(float* d, uint64_t da, uint64_t db, int sc) {
    asm volatile("{.reg .pred p; setp.ne.b32 p,%98,0; wgmma.mma_async.sync.aligned.m64n192k16.f32.bf16.bf16 {"
                 "%0,%1,%2,%3,%4,%5,%6,%7,%8,%9,%10,%11,%12,%13,%14,%15,%16,%17,%18,%19,%20,%21,%22,%23,%24,%25,%26,%27,%28,%29,%30,%31,"
                 "%32,%33,%34,%35,%36,%37,%38,%39,%40,%41,%42,%43,%44,%45,%46,%47,%48,%49,%50,%51,%52,%53,%54,%55,%56,%57,%58,%59,%60,%61,%62,%63,"
                 "%64,%65,%66,%67,%68,%69,%70,%71,%72,%73,%74,%75,%76,%77,%78,%79,%80,%81,%82,%83,%84,%85,%86,%87,%88,%89,%90,%91,%92,%93,%94,%95},"
                 "%96,%97,p,1,1,0,1;}"
                 : R8(d, 0), R8(d, 8), R8(d, 16), R8(d, 24), R8(d, 32), R8(d, 40), R8(d, 48), R8(d, 56), R8(d, 64), R8(d, 72), R8(d, 80), R8(d, 88)
                 : "l"(da), "l"(db), "r"(sc));
}
__device__ __forceinline__ void wgmma64_tt(float* d, uint64_t da, uint64_t db, int sc) {
    asm volatile("{.reg .pred p; setp.ne.b32 p,%34,0; wgmma.mma_async.sync.aligned.m64n64k16.f32.bf16.bf16 {"
                 "%0,%1,%2,%3,%4,%5,%6,%7,%8,%9,%10,%11,%12,%13,%14,%15,%16,%17,%18,%19,%20,%21,%22,%23,%24,%25,%26,%27,%28,%29,%30,%31},"
                 "%32,%33,p,1,1,1,1;}"
                 : R8(d, 0), R8(d, 8), R8(d, 16), R8(d, 24)
                 : "l"(da), "l"(db), "r"(sc));
}
__device__ __forceinline__ void wgmma128_rs(float* d, const uint4& a, uint64_t db, int sc) {
    asm volatile("{.reg .pred p; setp.ne.b32 p,%69,0; wgmma.mma_async.sync.aligned.m64n128k16.f32.bf16.bf16 {"
                 "%0,%1,%2,%3,%4,%5,%6,%7,%8,%9,%10,%11,%12,%13,%14,%15,%16,%17,%18,%19,%20,%21,%22,%23,%24,%25,%26,%27,%28,%29,%30,%31,"
                 "%32,%33,%34,%35,%36,%37,%38,%39,%40,%41,%42,%43,%44,%45,%46,%47,%48,%49,%50,%51,%52,%53,%54,%55,%56,%57,%58,%59,%60,%61,%62,%63},"
                 "{%64,%65,%66,%67},%68,p,1,1,1;}"
                 : R8(d, 0), R8(d, 8), R8(d, 16), R8(d, 24), R8(d, 32), R8(d, 40), R8(d, 48), R8(d, 56)
                 : "r"(a.x), "r"(a.y), "r"(a.z), "r"(a.w), "l"(db), "r"(sc));
}
__device__ __forceinline__ void mma16816(float* c, uint32_t a0, uint32_t a1, uint32_t a2, uint32_t a3, uint32_t b0, uint32_t b1) {
    asm("mma.sync.aligned.m16n8k16.row.col.f32.bf16.bf16.f32 {%0,%1,%2,%3},{%4,%5,%6,%7},{%8,%9},{%0,%1,%2,%3};"
        : "+f"(c[0]), "+f"(c[1]), "+f"(c[2]), "+f"(c[3]) : "r"(a0), "r"(a1), "r"(a2), "r"(a3), "r"(b0), "r"(b1));
}
__device__ __forceinline__ void ldsm4(uint32_t* r, uint32_t a) {
    asm volatile("ldmatrix.sync.aligned.m8n8.x4.shared.b16 {%0,%1,%2,%3},[%4];" : "=r"(r[0]), "=r"(r[1]), "=r"(r[2]), "=r"(r[3]) : "r"(a) : "memory");
}
__device__ __forceinline__ void ldsm4t(uint32_t* r, uint32_t a) {
    asm volatile("ldmatrix.sync.aligned.m8n8.x4.trans.shared.b16 {%0,%1,%2,%3},[%4];" : "=r"(r[0]), "=r"(r[1]), "=r"(r[2]), "=r"(r[3]) : "r"(a) : "memory");
}
__device__ __forceinline__ void stsm4(uint32_t a, uint32_t r0, uint32_t r1, uint32_t r2, uint32_t r3) {
    asm volatile("stmatrix.sync.aligned.m8n8.x4.shared.b16 [%0],{%1,%2,%3,%4};" ::"r"(a), "r"(r0), "r"(r1), "r"(r2), "r"(r3) : "memory");
}
__device__ __forceinline__ uint32_t lds32(uint32_t a) { uint32_t v; asm volatile("ld.shared.b32 %0,[%1];" : "=r"(v) : "r"(a) : "memory"); return v; }
__device__ __forceinline__ uint4 lds128(uint32_t a) { uint4 v; asm volatile("ld.shared.v4.b32 {%0,%1,%2,%3},[%4];" : "=r"(v.x), "=r"(v.y), "=r"(v.z), "=r"(v.w) : "r"(a) : "memory"); return v; }
__device__ __forceinline__ void sts16(uint32_t a, uint32_t v) { asm volatile("st.shared.b16 [%0],%1;" ::"r"(a), "h"((unsigned short)v) : "memory"); }
__device__ __forceinline__ void sts32(uint32_t a, uint32_t v) { asm volatile("st.shared.b32 [%0],%1;" ::"r"(a), "r"(v) : "memory"); }
__device__ __forceinline__ void sts64(uint32_t a, uint32_t x, uint32_t y) { asm volatile("st.shared.v2.b32 [%0],{%1,%2};" ::"r"(a), "r"(x), "r"(y) : "memory"); }
__device__ __forceinline__ void sts128(uint32_t a, uint32_t x, uint32_t y, uint32_t z, uint32_t w) { asm volatile("st.shared.v4.b32 [%0],{%1,%2,%3,%4};" ::"r"(a), "r"(x), "r"(y), "r"(z), "r"(w) : "memory"); }
__device__ __forceinline__ uint32_t pack2(float lo, float hi) { uint32_t d; asm("cvt.rn.bf16x2.f32 %0,%1,%2;" : "=r"(d) : "f"(hi), "f"(lo)); return d; }
__device__ __forceinline__ float bf_lo(uint32_t v) { return __uint_as_float(v << 16); }
__device__ __forceinline__ float bf_hi(uint32_t v) { return __uint_as_float(v & 0xffff0000u); }
__device__ __forceinline__ float bf_round(float v) { return bf_lo(pack2(v, 0.f)); }
__device__ __forceinline__ uint32_t hmax2(uint32_t a, uint32_t b) { uint32_t d; asm("max.bf16x2 %0,%1,%2;" : "=r"(d) : "r"(a), "r"(b)); return d; }
__device__ __forceinline__ uint32_t hmin2(uint32_t a, uint32_t b) { uint32_t d; asm("min.bf16x2 %0,%1,%2;" : "=r"(d) : "r"(a), "r"(b)); return d; }
__device__ __forceinline__ uint32_t hmul2(uint32_t a, uint32_t b) { uint32_t d; asm("mul.rn.bf16x2 %0,%1,%2;" : "=r"(d) : "r"(a), "r"(b)); return d; }
__device__ __forceinline__ float ex2(float x) { float y; asm("ex2.approx.ftz.f32 %0,%1;" : "=f"(y) : "f"(x)); return y; }
__device__ __forceinline__ float rcp(float x) { float y; asm("rcp.approx.ftz.f32 %0,%1;" : "=f"(y) : "f"(x)); return y; }
__device__ __forceinline__ uint32_t ld_nc(const uint32_t* p) { uint32_t v; asm volatile("ld.global.nc.b32 %0,[%1];" : "=r"(v) : "l"(p)); return v; }
__device__ __forceinline__ uint2 ld_nc64(const uint2* p) { uint2 v; asm volatile("ld.global.nc.v2.b32 {%0,%1},[%2];" : "=r"(v.x), "=r"(v.y) : "l"(p)); return v; }
__device__ __forceinline__ unsigned ld_acq(const unsigned* p) { unsigned v; asm volatile("ld.acquire.gpu.global.u32 %0,[%1];" : "=r"(v) : "l"(p) : "memory"); return v; }
__device__ __forceinline__ unsigned ld_rlx(const unsigned* p) { unsigned v; asm volatile("ld.relaxed.gpu.global.u32 %0,[%1];" : "=r"(v) : "l"(p) : "memory"); return v; }
__device__ __forceinline__ uint2 ld_rlx64(const void* p) { uint2 v; asm volatile("{.reg .b64 t; ld.relaxed.gpu.global.b64 t,[%2]; mov.b64 {%0,%1},t;}" : "=r"(v.x), "=r"(v.y) : "l"(p) : "memory"); return v; }
__device__ __forceinline__ uint4 ld_rlx128(const void* p) {
    uint4 v;
    asm volatile("{.reg .b64 t,u; ld.relaxed.gpu.global.v2.b64 {t,u},[%4]; mov.b64 {%0,%1},t; mov.b64 {%2,%3},u;}" : "=r"(v.x), "=r"(v.y), "=r"(v.z), "=r"(v.w) : "l"(p) : "memory");
    return v;
}
__device__ __forceinline__ void st_rlx32(void* p, uint32_t x) { asm volatile("st.relaxed.gpu.global.u32 [%0],%1;" ::"l"(p), "r"(x) : "memory"); }
__device__ __forceinline__ void st_rlx64(void* p, uint32_t x, uint32_t y) { asm volatile("{.reg .b64 t; mov.b64 t,{%1,%2}; st.relaxed.gpu.global.b64 [%0],t;}" ::"l"(p), "r"(x), "r"(y) : "memory"); }
__device__ __forceinline__ void st_rlx128(void* p, uint4 v) {
    asm volatile("{.reg .b64 t,u; mov.b64 t,{%1,%2}; mov.b64 u,{%3,%4}; st.relaxed.gpu.global.v2.b64 [%0],{t,u};}" ::"l"(p), "r"(v.x), "r"(v.y), "r"(v.z), "r"(v.w) : "memory");
}
__device__ __forceinline__ uint32_t tagw(uint32_t w, uint32_t tag) { return (w & ~1u) | tag; }
__device__ __forceinline__ uint4 tag4(uint32_t x, uint32_t y, uint32_t z, uint32_t w, uint32_t tag) { return make_uint4(tagw(x, tag), y, tagw(z, tag), w); }
__device__ __forceinline__ uint32_t bad4(const uint4& v, uint32_t tag) { return (v.x ^ tag) | (v.z ^ tag); }
__device__ __forceinline__ void bar_named(int id, int n) { asm volatile("bar.sync %0,%1;" ::"r"(id), "r"(n) : "memory"); }

struct cf { float re, im; };
__device__ __forceinline__ cf cmul(cf a, cf b) { cf r; r.re = a.re * b.re - a.im * b.im; r.im = a.re * b.im + a.im * b.re; return r; }
__device__ __forceinline__ cf cexp_p(float arl, float ait, float p) {
    float mag = ex2(arl * p);
    float t = ait * p;
    const float big = 12582912.f;
    t = (t - ((t + big) - big)) * 6.283185307179586f;
    cf r; r.re = mag * __cosf(t); r.im = mag * __sinf(t);
    return r;
}

__device__ __forceinline__ void hedgehog4(const uint32_t* a, uint32_t wphi_addr, uint32_t (*out)[8]) {
    float p[4][2][4], mx[4][2];
#pragma unroll
    for (int h = 0; h < 4; h++) {
        uint32_t b[4];
        ldsm4t(b, wphi_addr + h * 512);
        float c0[4] = {0.f, 0.f, 0.f, 0.f}, c1[4] = {0.f, 0.f, 0.f, 0.f};
        mma16816(c0, a[4 * h], a[4 * h + 1], a[4 * h + 2], a[4 * h + 3], b[0], b[1]);
        mma16816(c1, a[4 * h], a[4 * h + 1], a[4 * h + 2], a[4 * h + 3], b[2], b[3]);
#pragma unroll
        for (int k = 0; k < 2; k++) {
            p[h][k][0] = c0[2 * k]; p[h][k][1] = c0[2 * k + 1]; p[h][k][2] = c1[2 * k]; p[h][k][3] = c1[2 * k + 1];
            mx[h][k] = fmaxf(fmaxf(p[h][k][0], p[h][k][1]), fmaxf(p[h][k][2], p[h][k][3]));
        }
    }
#pragma unroll
    for (int o = 1; o <= 2; o <<= 1)
#pragma unroll
        for (int h = 0; h < 4; h++)
#pragma unroll
            for (int k = 0; k < 2; k++) mx[h][k] = fmaxf(mx[h][k], __shfl_xor_sync(~0u, mx[h][k], o));
    const float L = 1.4426950408889634f;
    float pmin = 1.f;
#pragma unroll
    for (int h = 0; h < 4; h++)
#pragma unroll
        for (int k = 0; k < 2; k++) {
            const float m = -mx[h][k] * L;
            const float e0 = ex2(fmaf(p[h][k][0], L, m)), e1 = ex2(fmaf(p[h][k][1], L, m)), e2 = ex2(fmaf(p[h][k][2], L, m)), e3 = ex2(fmaf(p[h][k][3], L, m));
            const float p01 = e0 * e1, p23 = e2 * e3, pp = p01 * p23, r = rcp(pp), r01 = r * p23, r23 = r * p01;
            pmin = fminf(pmin, pp);
            out[h][k] = pack2(e0, e1); out[h][k + 2] = pack2(e2, e3);
            out[h][4 + k] = pack2(r01 * e1, r01 * e0); out[h][4 + k + 2] = pack2(r23 * e3, r23 * e2);
        }
    if (__builtin_expect(__any_sync(~0u, !(pmin > 1e-18f)), 0)) {
#pragma unroll
        for (int h = 0; h < 4; h++)
#pragma unroll
            for (int k = 0; k < 2; k++) {
                float m = fminf(fminf(p[h][k][0], p[h][k][1]), fminf(p[h][k][2], p[h][k][3]));
                m = fminf(m, __shfl_xor_sync(~0u, m, 1));
                m = fminf(m, __shfl_xor_sync(~0u, m, 2)) * L;
                out[h][4 + k] = pack2(ex2(fmaf(p[h][k][0], -L, m)), ex2(fmaf(p[h][k][1], -L, m)));
                out[h][4 + k + 2] = pack2(ex2(fmaf(p[h][k][2], -L, m)), ex2(fmaf(p[h][k][3], -L, m)));
            }
    }
}

__global__ void __launch_bounds__(512, 1)
fused_kernel(Scratch* __restrict__ scr, const bf16* __restrict__ logA, const bf16* __restrict__ Aim, const bf16* __restrict__ Cre,
             const bf16* __restrict__ Cim, const bf16* __restrict__ logdt, const bf16* __restrict__ Dskip, const bf16* __restrict__ wphi,
             const bf16* __restrict__ gatew, bf16* __restrict__ out,
             const __grid_constant__ CUtensorMap mx, const __grid_constant__ CUtensorMap mw, const __grid_constant__ CUtensorMap mwo) {
    extern __shared__ __align__(1024) uint8_t smem[];
    constexpr uint32_t sb = 1024;
    const int tid = threadIdx.x, warp = __shfl_sync(~0u, tid >> 5, 0), lane = tid & 31;
    const int g = lane >> 2, q = lane & 3, w4 = warp & 3;
    const int bi = blockIdx.x, bi_i = bi & 15, bi_j = bi >> 4;
    const uint32_t bar = sb + OFF_BAR;
    const int rot = (bi_j & 3) * 2, xkb = bi_j >> 2;
    auto load_stage = [&](int kb) {
        const uint32_t b = bar + 8 * (BAR_FULL + (kb & 3)), d = sb + (kb & 3) * SLOT;
        const int kc = ((kb + rot) & 7) * 64;
        mbar_expect(b, SLOT);
        tma2d(d, &mx, kc, bi_i * 128, b);
        tma3d(d + 16384, &mw, bi_j * 64, kc, 0, b);
    };

    const int ch = bi * 4 + w4;
    const int pidx = ch * 64 + lane * 2 + (warp >> 3);
    const uint32_t pla = ld_nc((const uint32_t*)logA + pidx), pai = ld_nc((const uint32_t*)Aim + pidx);
    const uint32_t pcr = ld_nc((const uint32_t*)Cre + pidx), pci = ld_nc((const uint32_t*)Cim + pidx);
    uint32_t pdt = ld_nc((const uint32_t*)logdt + (ch >> 1));
    const uint32_t pds = ld_nc((const uint32_t*)Dskip + (ch >> 1));
    unsigned done0 = ld_rlx(scr->done);
    if (tid == 0) {
        for (int s = 0; s < 4; s++) mbar_init(bar + 8 * (BAR_FULL + s), 1);
        asm volatile("fence.mbarrier_init.release.cluster;" ::: "memory");
        asm volatile("prefetch.tensormap [%0];" ::"l"(&mx) : "memory");
        load_stage(0); load_stage(1);
        STAMP(11);
    } else if (tid == 32) {
        if (s2u(smem) != sb) __trap();
        sts32(bar + OFF_CNT, 0);
        for (int s = 0; s < 4; s++) { mbar_init(bar + 8 * (BAR_EMPTY + s), 9); mbar_init(bar + 8 * (BAR_KS + s), 1); mbar_init(bar + 8 * (BAR_KP + s), 3); mbar_init(bar + 8 * (BAR_KD + s), 1); mbar_init(bar + 8 * (BAR_KVF + s), 1); }
        mbar_init(bar + 8 * BAR_WPHI, 1); mbar_init(bar + 8 * BAR_WO, 2); mbar_init(bar + 8 * BAR_WO2, 1); mbar_init(bar + 8 * BAR_XT, 4);
        mbar_init(bar + 8 * BAR_DONE, 9); mbar_init(bar + 8 * BAR_KG, 8); mbar_init(bar + 8 * BAR_PUB, 8);
        mbar_init(bar + 8 * BAR_UR, 4); mbar_init(bar + 8 * BAR_WR, 4); mbar_init(bar + 8 * BAR_PREP, 4); mbar_init(bar + 8 * BAR_KGA, 4); mbar_init(bar + 8 * BAR_SP2, 1);
        asm volatile("fence.mbarrier_init.release.cluster;" ::: "memory");
        mbar_expect(bar + 8 * BAR_WPHI, 3072);
        bulk_g2s(sb + OFF_GW, gatew, 1024, bar + 8 * BAR_WPHI);
        bulk_g2s(sb + OFF_WPHI, wphi + bi_j * 1024, 2048, bar + 8 * BAR_WPHI);
    } else if (tid == 64) {
        asm volatile("prefetch.tensormap [%0];" ::"l"(&mw) : "memory");
    }
    const uint32_t buf = sb + OFF_BUF + w4 * BUF_STRIDE, kb_ = sb + OFF_K + w4 * KT_BYTES;
    if ((warp >> 2) == 2) {
#pragma unroll
        for (int v = 0; v < 7; v++) if (v * 32 + lane < KT_BYTES / 16) sts128(kb_ + (v * 32 + lane) * 16, 0, 0, 0, 0);
    }
    __syncthreads();
    asm volatile("" : "+r"(pdt), "+r"(done0)::"memory");
    const unsigned epoch1 = (done0 >> 7) + 1u;
    const uint32_t tag = epoch1 & 1u;

    const int st = tid & 127;
    const uint32_t ub = sb + OFF_U + w4 * U_STRIDE + 256, spare = sb + (w4 < 2 ? OFF_SP0 : OFF_SP1) + (w4 & 1) * 4096;

    auto stg_of = [&](int w) { return w < 8 ? sb + 3 * SLOT + w * 7296 : sb + 2 * SLOT + (w & 3) * 7296; };
    float kc[24];
#pragma unroll
    for (int t = 0; t < 24; t++) kc[t] = 0.f;
    auto handoff = [&](int src) {
        mbar_wait(bar + 8 * (BAR_KS + w4), 0);
#pragma unroll
        for (int t = 0; t < 5; t++)
            sts128(buf + src * 2560 + (t * 32 + lane) * 16, __float_as_uint(kc[4 * t]), __float_as_uint(kc[4 * t + 1]), __float_as_uint(kc[4 * t + 2]), __float_as_uint(kc[4 * t + 3]));
        if (lane == 0) sts32(buf + 7680 + src * 4, __float_as_uint(kc[20]));
        __syncwarp();
        if (lane == 0) mbar_arrive(bar + 8 * (BAR_KP + w4));
    };
    {
        const float dt = bf_round(expf((ch & 1) ? bf_hi(pdt) : bf_lo(pdt)));
        const uint32_t stg = (warp >> 2) == 2 ? buf : stg_of(warp);
        const int sh = ((warp >> 2) & 1) * 16;
        auto pick = [&](uint32_t v) { return __uint_as_float((v >> sh) << 16); };
        const float ea = bf_round(ex2(pick(pla) * 1.4426950408889634f));
        const float arl = (-ea * dt) * 1.4426950408889634f, ait = (pick(pai) * dt) * 0.15915494309189535f;
        cf C2; C2.re = 2.0f * (pick(pcr) * dt); C2.im = 2.0f * (pick(pci) * dt);
        const cf z1 = cexp_p(arl, ait, 1.0f), z128 = cexp_p(arl, ait, 128.0f);
        const cf z2 = cmul(z1, z1), z4 = cmul(z2, z2);
        cf z8 = cmul(z4, z4); z8.im = -z8.im;
        const uint32_t sa0 = stg + (lane >> 3) * 128 + (((lane & 7) ^ (lane >> 3)) << 4), sa1 = (sa0 ^ 64) + 512;
        uint32_t w[60];
        auto put = [&](int row, const cf& v) {
            w[row] = pack2(v.re, v.im);
            if ((row & 3) == 3) stsm4(((row & 4) ? sa1 : sa0) + (row >> 3) * 1024, w[row - 3], w[row - 2], w[row - 1], w[row]);
        };
        {
            const cf z16 = cmul(z8, z8);
            cf e; e.re = 1.f; e.im = 0.f;
            cf o = z8;
            put(0, e); put(1, o);
            e = z16; put(2, e);
#pragma unroll
            for (int b = 3; b < 16; b += 2) {
                o = cmul(o, z16); put(b, o);
                if (b + 1 < 16) { e = cmul(e, z16); put(b + 1, e); }
            }
        }
        cf h[8];
        h[0] = C2; h[1] = cmul(h[0], z1);
#pragma unroll
        for (int r = 2; r < 8; r++) h[r] = cmul(h[r - 2], z2);
#pragma unroll
        for (int r = 0; r < 8; r++) put(16 + r, h[r]);
#pragma unroll
        for (int r = 0; r < 8; r++) { h[r] = cmul(h[r], z128); put(24 + r, h[r]); }
#pragma unroll
        for (int al = 0; al < 2; al++)
#pragma unroll
            for (int r = 0; r < 4; r++) { h[2 * r] = cmul(h[2 * r], z128); put(32 + al * 4 + r, h[2 * r]); }
#pragma unroll
        for (int al = 0; al < 4; al++)
#pragma unroll
            for (int r = 0; r < 2; r++) { h[4 * r] = cmul(h[4 * r], z128); put(40 + al * 2 + r, h[4 * r]); }
#pragma unroll
        for (int al = 0; al < 8; al++) { h[0] = cmul(h[0], z128); put(48 + al, h[0]); }
        h[0] = cmul(h[0], z128);
        sts32(stg + 56 * 128 + lane * 4, pack2(h[0].re, h[0].im));
        __syncwarp();
        const int lr = lane & 7, lm = lane >> 3;
#pragma unroll
        for (int kp = 0; kp < 2; kp++) {
            uint32_t a0[4], a1[4];
            ldsm4(a0, stg + ((lm & 1) * 8 + lr) * 128 + (((4 * kp + (lm >> 1)) ^ lr) << 4));
            ldsm4(a1, stg + ((lm & 1) * 8 + lr) * 128 + (((4 * kp + 2 + (lm >> 1)) ^ lr) << 4));
#pragma unroll
            for (int t = 0; t < 6; t++) {
                uint32_t b[4];
                ldsm4(b, stg + (16 + 8 * t + lr) * 128 + (((4 * kp + lm) ^ lr) << 4));
                mma16816(kc + 4 * t, a0[0], a0[1], a0[2], a0[3], b[0], b[1]);
                mma16816(kc + 4 * t, a1[0], a1[1], a1[2], a1[3], b[2], b[3]);
            }
        }
        __syncwarp();
        asm volatile("fence.proxy.async.shared::cta;" ::: "memory");
        const uint32_t cnt = 1u + (__float_as_uint(kc[0] + kc[23]) == 0xffc12345u);
        if (lane == 0) asm volatile("mbarrier.arrive.shared::cta.b64 _,[%0],%1;" ::"r"(bar + 8 * (warp < 8 ? BAR_KG : (warp < 12 ? BAR_KS + w4 : BAR_KGA))), "r"(cnt) : "memory");
        if (warp < 8) handoff(warp >> 2);
    }

    if (warp < 8) {
        const int wg = warp >> 2;
        if (warp == 0) STAMP(21);
        float acc[96];
        const int srow = warp * 16 + (lane & 15);
        const uint32_t srow_a = srow * 128;
        const int sx = srow & 7, shi = lane >> 4;
        const uint64_t da0 = mkdesc(sb + wg * 8192, 16, 1024), db0 = mkdesc(sb + 16384, 8192, 1024);
#pragma unroll 1
        for (int kb = 0; kb < 8; kb++) {
            const int s = kb & 3;
            const uint64_t da = da0 + s * (SLOT >> 4), db = db0 + s * (SLOT >> 4);
            if (warp == 0) STAMP(40 + kb);
            mbar_wait(bar + 8 * (BAR_FULL + s), kb >> 2);
            if (warp == 0) STAMP(32 + kb);
            wg_fence();
#pragma unroll
            for (int k = 0; k < 4; k++) wgmma192(acc, da + 2 * k, db + 128 * k, kb | k);
            wg_commit();
            wg_wait<1>();
            if (lane == 0 && kb > 0) mbar_arrive(bar + 8 * (BAR_EMPTY + ((kb - 1) & 3)));
        }
        mbar_wait(bar + 8 * BAR_WPHI, 0);
        wg_wait<0>();
        fence_regs<96>(acc);
        asm volatile("setmaxnreg.inc.sync.aligned.u32 160;");
        if (lane == 0) mbar_arrive(bar + 8 * BAR_DONE);
        if (warp == 0) STAMP(1);
        uint32_t in[16], qa[16];
        mbar_wait(bar + 8 * BAR_DONE, 0);
#pragma unroll
        for (int r = 0; r < 16; r++) {
            in[r] = pack2(acc[32 + 2 * r], acc[32 + 2 * r + 1]);
            qa[r] = pack2(acc[2 * r], acc[2 * r + 1]);
        }
#pragma unroll
        for (int hh = 0; hh < 4; hh++)
            stsm4(sb + OFF_V + (hh >> 1) * 16384 + srow_a + (((2 * (hh & 1) + shi) ^ sx) << 4), pack2(acc[64 + 8 * hh], acc[65 + 8 * hh]),
                  pack2(acc[66 + 8 * hh], acc[67 + 8 * hh]), pack2(acc[68 + 8 * hh], acc[69 + 8 * hh]), pack2(acc[70 + 8 * hh], acc[71 + 8 * hh]));
        sts128(sb + OFF_V + shi * 16384 + srow_a + ((4 ^ sx) << 4), 0x3f803f80u, 0x3f803f80u, 0x3f803f80u, 0x3f803f80u);
        const uint32_t wphi_a = sb + OFF_WPHI + (lane & 15) * 32 + (lane >> 4) * 16;
        uint32_t pq[4][8];
#pragma unroll 1
        for (int it = 0; it < 2; it++) {
            hedgehog4(in, wphi_a, pq);
            if (it == 1) break;
#pragma unroll
            for (int hs = 0; hs < 8; hs++) {
                float c[4] = {0.f, 0.f, 0.f, 0.f};
                const uint32_t* o = pq[hs >> 1] + 4 * (hs & 1);
                mma16816(c, o[0], o[1], o[2], o[3], 0x3f803f80u, 0x3f803f80u);
                const float r0 = rcp(c[0]), r1 = rcp(c[2]);
                const uint32_t s0 = pack2(r0, r0), s1 = pack2(r1, r1);
                stsm4(sb + OFF_P + (hs >> 2) * 16384 + srow_a + (((2 * (hs & 3) + shi) ^ sx) << 4), hmul2(o[0], s0), hmul2(o[1], s1), hmul2(o[2], s0), hmul2(o[3], s1));
            }
            asm volatile("fence.proxy.async.shared::cta;" ::: "memory");
            bar_named(1, 256);
            if (warp == 0) STAMP(2);
            float d[32];
            const uint64_t dv = mkdesc(sb + OFF_V + wg * 16384, 16, 1024), dp = mkdesc(sb + OFF_P + wg * 16384, 16, 1024);
            wg_fence();
#pragma unroll
            for (int k = 0; k < 8; k++) wgmma64_tt(d, dv + 128 * k, dp + 128 * k, k != 0);
            wg_commit();
            mbar_wait(bar + 8 * BAR_PREP, 0);
            uint4* kvp = scr->kvp + bi * 544 + wg * 272 + (w4 < 2 ? w4 * 136 : 128) + lane;
            wg_wait<0>();
            fence_regs<32>(d);
            if (w4 < 2 || (w4 == 2 && lane < 4)) {
#pragma unroll
                for (int f = 0; f < 4; f++) {
                    const int i0 = 8 * (f >> 1) + 2 * (f & 1), i2 = 16 * (f >> 1) + 8 * (f & 1);
                    const float e0 = w4 == 0 ? d[i0] : (w4 == 1 ? d[16 + i0] : d[i2]), e1 = w4 == 0 ? d[i0 + 1] : (w4 == 1 ? d[17 + i0] : d[i2 + 1]);
                    const float e2 = w4 == 0 ? d[i0 + 4] : (w4 == 1 ? d[20 + i0] : d[i2 + 4]), e3 = w4 == 0 ? d[i0 + 5] : (w4 == 1 ? d[21 + i0] : d[i2 + 5]);
                    st_rlx128(kvp + (w4 < 2 ? f * 32 : (f >> 1) * 136 + (f & 1) * 4), tag4(__float_as_uint(e0), __float_as_uint(e1), __float_as_uint(e2), __float_as_uint(e3), tag));
                }
            }
            __syncwarp();
            if (lane == 0) mbar_arrive(bar + 8 * BAR_PUB);
            if (warp == 0) STAMP(3);
#pragma unroll
            for (int r = 0; r < 16; r++) in[r] = qa[r];
        }
        if (warp == 0) STAMP(4);
        {
            uint4 kf[4][3];
            uint4* og = scr->o + ((bi_i * 8 + warp) * 32 + bi_j * 4) * 32 + lane;
#pragma unroll
            for (int hh = 0; hh < 4; hh++) {
                mbar_wait(bar + 8 * (BAR_KVF + hh), 0);
                if (hh == 0 && warp == 0) STAMP(5);
                {
                    const uint32_t ka = sb + OFF_KVF + hh * 1088;
                    kf[hh][0] = lds128(ka + lane * 32); kf[hh][1] = lds128(ka + lane * 32 + 16); kf[hh][2] = lds128(ka + 1024 + q * 16);
                }
                float c[6][4];
#pragma unroll
                for (int t = 0; t < 6; t++) { c[t][0] = c[t][1] = c[t][2] = c[t][3] = 0.f; }
                const uint32_t* a = pq[hh];
                const bool od = g & 1;
                mma16816(c[0], a[0], a[1], a[2], a[3], od ? 0x3f803f80u : kf[hh][2].x, od ? 0x3f803f80u : kf[hh][2].y);
                mma16816(c[1], a[4], a[5], a[6], a[7], od ? 0x3f803f80u : kf[hh][2].z, od ? 0x3f803f80u : kf[hh][2].w);
                mma16816(c[2], a[0], a[1], a[2], a[3], kf[hh][0].x, kf[hh][0].y);
                mma16816(c[3], a[0], a[1], a[2], a[3], kf[hh][0].z, kf[hh][0].w);
                mma16816(c[4], a[4], a[5], a[6], a[7], kf[hh][1].x, kf[hh][1].y);
                mma16816(c[5], a[4], a[5], a[6], a[7], kf[hh][1].z, kf[hh][1].w);
                uint32_t w[4];
#pragma unroll
                for (int k = 0; k < 2; k++) {
                    const float rho = c[0][2 * k + 1] * rcp(c[1][2 * k + 1]);
                    const float r = rcp(fmaf(c[0][2 * k + 1], 1e-6f, fmaf(rho, c[1][2 * k], c[0][2 * k]))), rr = r * rho;
                    w[k] = pack2(fmaf(c[4][2 * k], rr, c[2][2 * k] * r), fmaf(c[4][2 * k + 1], rr, c[2][2 * k + 1] * r));
                    w[2 + k] = pack2(fmaf(c[5][2 * k], rr, c[3][2 * k] * r), fmaf(c[5][2 * k + 1], rr, c[3][2 * k + 1] * r));
                }
                st_rlx128(og + hh * 32, tag4(w[0], w[1], w[2], w[3], tag));
            }
        }
        if (warp == 0) STAMP(6);
        float oc[64];
        const int slab = bi_i * 8 + (bi_j >> 2) * 4 + w4;
        const uint8_t* ysrc = (const uint8_t*)scr->y + (size_t)((bi_j & 3) * 32 + wg * 16 + (q >> 1)) * 16384 + slab * 128 + g * 16 + (q & 1) * 8;
        const unsigned* gp = scr->g + (slab * 8 + (g >> 1)) * 8 + (g & 1) * 4;
        uint2 yv[8]; unsigned g0, g1;
        {
            const uint4* osrc = scr->o + (slab * 32 + wg * 16) * 32 + lane;
            uint4 fr[16];
            const unsigned* probe = (const unsigned*)(osrc - lane + ((lane & 3) * 4 + 3) * 32 + 31) + 2;
            unsigned miss = ~0u;
            int n = 0;
            auto fetch = [&](int s) {
#pragma unroll 1
                while ((miss >> s) & 1) { miss = __ballot_sync(~0u, (ld_rlx(probe) ^ tag) & 1); if (++n > SPIN_LIMIT) break; }
#pragma unroll
                for (int k = 4 * s; k < 4 * s + 4; k++) fr[k] = ld_rlx128(osrc + k * 32);
            };
            const uint64_t dw = mkdesc(sb + wg * 2 * SLOT, wg ? 32768 : SLOT, 1024);
            auto mma = [&](int s) {
#pragma unroll 1
                while (__builtin_expect(__any_sync(~0u, (bad4(fr[4 * s], tag) | bad4(fr[4 * s + 1], tag) | bad4(fr[4 * s + 2], tag) | bad4(fr[4 * s + 3], tag)) & 1), 0)) {
#pragma unroll
                    for (int k = 4 * s; k < 4 * s + 4; k++) fr[k] = ld_rlx128(osrc + k * 32);
                    if (++n > SPIN_LIMIT) break;
                }
                wg_fence();
#pragma unroll
                for (int hh = 0; hh < 4; hh++) wgmma128_rs(oc, fr[4 * s + hh], dw + 128 * (4 * s + hh), (s | hh) != 0);
                wg_commit();
            };
            fetch(0); fetch(1);
            mbar_wait(bar + 8 * (wg ? BAR_WO2 : BAR_WO), 0);
            mma(0); fetch(2); mma(1); fetch(3);
            if (warp == 0) STAMP(14);
            wg_wait<1>();
#pragma unroll
            for (int nt = 0; nt < 8; nt++) yv[nt] = ld_rlx64(ysrc + nt * 32768);
            g0 = ld_rlx(gp); g1 = ld_rlx(gp + 32);
            mma(2); mma(3);
            if (warp == 0) STAMP(7);
            {
#pragma unroll 1
                while (true) {
                    uint32_t bad = (g0 ^ tag) | (g1 ^ tag);
#pragma unroll
                    for (int nt = 0; nt < 8; nt++) bad |= yv[nt].x ^ tag;
                    if (!__any_sync(~0u, bad & 1)) break;
#pragma unroll
                    for (int nt = 0; nt < 8; nt++) if ((yv[nt].x ^ tag) & 1) yv[nt] = ld_rlx64(ysrc + nt * 32768);
                    g0 = ld_rlx(gp); g1 = ld_rlx(gp + 32);
                    if (++n > SPIN_LIMIT) break;
                }
            }
            if (warp == 0) STAMP(28);
        }
        {
            const float ga = bf_hi(g0), gb = bf_hi(g1);
            const float ha = bf_round(1.0f - ga), hb = bf_round(1.0f - gb);
            float yb[32];
#pragma unroll
            for (int nt = 0; nt < 8; nt++) {
                yb[4 * nt] = ha * bf_lo(yv[nt].x); yb[4 * nt + 1] = ha * bf_hi(yv[nt].x);
                yb[4 * nt + 2] = hb * bf_lo(yv[nt].y); yb[4 * nt + 3] = hb * bf_hi(yv[nt].y);
            }
            fence_regs<32>(yb);
            const uint32_t xw = sb + wg * 2 * SLOT + (tid & 127) * 16, xr = sb + (wg ^ 1) * 2 * SLOT + (tid & 127) * 16;
            wg_wait<0>();
            fence_regs<64>(oc);
            bar_named(3 + wg, 128);
#pragma unroll
            for (int r = 0; r < 8; r++)
                sts128(xw + r * 2048, __float_as_uint(oc[32 + 4 * r]), __float_as_uint(oc[33 + 4 * r]), __float_as_uint(oc[34 + 4 * r]), __float_as_uint(oc[35 + 4 * r]));
#pragma unroll
            for (int r = 0; r < 32; r++) yb[r] = fmaf((r & 2) ? gb : ga, oc[r], yb[r]);
            bar_named(1, 256);
            if (warp == 0) STAMP(8);
            uint32_t w[8][2];
#pragma unroll
            for (int nt = 0; nt < 8; nt++) {
                const uint4 p = lds128(xr + nt * 2048);
                w[nt][0] = pack2(fmaf(ga, __uint_as_float(p.x), yb[4 * nt]), fmaf(ga, __uint_as_float(p.y), yb[4 * nt + 1]));
                w[nt][1] = pack2(fmaf(gb, __uint_as_float(p.z), yb[4 * nt + 2]), fmaf(gb, __uint_as_float(p.w), yb[4 * nt + 3]));
            }
            const uint32_t ob = sb + wg * 2 * SLOT + 16384 + w4 * 2048;
#pragma unroll
            for (int nt = 0; nt < 8; nt += 2)
                stsm4(ob + (lane & 15) * 128 + (((nt + shi) ^ (lane & 7)) << 4), w[nt][0], w[nt][1], w[nt + 1][0], w[nt + 1][1]);
            __syncwarp();
            bf16* op = out + (size_t)(slab * 16) * 512 + (bi_j & 3) * 128 + wg * 64 + (lane & 7) * 8;
#pragma unroll
            for (int it = 0; it < 4; it++) {
                const int r = it * 4 + (lane >> 3);
                uint4 v = lds128(ob + r * 128 + (((lane & 7) ^ (r & 7)) << 4));
                *(uint4*)(op + r * 512) = v;
            }
        }
        if (warp == 0) STAMP(10);
    } else if (warp < 12) {
        if (warp == 8) {
            mbar_wait(bar + 8 * BAR_KGA, 0);
            if (lane == 0) load_stage(2);
            STAMP(22);
            mbar_wait(bar + 8 * BAR_KG, 0);
            if (lane == 0) load_stage(3);
            __syncwarp();
            STAMP(17);
        }
        if (warp == 8) {
#pragma unroll 1
            for (int kb = 0; kb < 6; kb++) {
                const int s = kb & 3;
                mbar_wait(bar + 8 * (BAR_EMPTY + s), kb >> 2);
                if (kb == xkb) mbar_wait(bar + 8 * BAR_XT, 0);
                if (lane == 0) {
                    STAMP(48 + kb);
                    if (kb < 4) load_stage(kb + 4);
                    else {
                        mbar_expect(bar + 8 * BAR_WO, 32768);
                        tma2d(sb + s * SLOT, &mwo, (bi_j & 3) * 128 + s * 64, 0, bar + 8 * BAR_WO);
                        if (kb == 5) mbar_arrive(bar + 8 * BAR_SP2);
                    }
                }
                __syncwarp();
            }
        } else if (warp == 9) {
            const int row = bi_j * 16 + (lane >> 1), half = lane & 1;
            unsigned* gp = scr->g + (bi_i * 64 + bi_j * 8) * 8 + lane * 2;
            st_rlx64(gp, tag ^ 1u, tag ^ 1u);
            float gs0 = 0.f, gs1 = 0.f;
            mbar_wait(bar + 8 * BAR_WPHI, 0);
#pragma unroll 1
            for (int kb = 0; kb < 8; kb++) {
                const int s = kb & 3;
                mbar_wait(bar + 8 * (BAR_FULL + s), kb >> 2);
#pragma unroll
                for (int c = 0; c < 4; c++) {
                    const uint4 xv = lds128(sb + s * SLOT + row * 128 + (((half * 4 + c) ^ (row & 7)) << 4));
                    const uint4 gw = lds128(sb + OFF_GW + ((kb + rot) & 7) * 128 + half * 64 + c * 16);
                    const uint32_t p0 = hmul2(xv.x, gw.x), p1 = hmul2(xv.y, gw.y), p2 = hmul2(xv.z, gw.z), p3 = hmul2(xv.w, gw.w);
                    gs0 += (bf_lo(p0) + bf_lo(p1)) + (bf_lo(p2) + bf_lo(p3));
                    gs1 += (bf_hi(p0) + bf_hi(p1)) + (bf_hi(p2) + bf_hi(p3));
                }
                const uint32_t cnt = 1u + (__float_as_uint(gs0 + gs1) == 0xffc12345u);
                if (lane == 0) asm volatile("mbarrier.arrive.shared::cta.b64 _,[%0],%1;" ::"r"(bar + 8 * (kb < 7 ? BAR_EMPTY + s : BAR_DONE)), "r"(cnt) : "memory");
                __syncwarp();
            }
            float gs = gs0 + gs1;
            gs += __shfl_xor_sync(~0u, gs, 1);
            const uint32_t gv = __float_as_uint(bf_round(rcp(1.0f + ex2(-1.4426950408889634f * bf_round(gs))))) | tag;
            st_rlx64(gp, gv, gv);
        }
        mbar_wait(bar + 8 * (BAR_KP + w4), 0);
#pragma unroll
        for (int t = 0; t < 15; t++) {
            const uint4 v = lds128(buf + (t * 32 + lane) * 16);
            kc[4 * (t % 5)] += __uint_as_float(v.x); kc[4 * (t % 5) + 1] += __uint_as_float(v.y); kc[4 * (t % 5) + 2] += __uint_as_float(v.z); kc[4 * (t % 5) + 3] += __uint_as_float(v.w);
        }
        {
            const uint4 v = lds128(buf + 7680);
            kc[20] += __uint_as_float(v.x) + __uint_as_float(v.y) + __uint_as_float(v.z);
            const uint32_t cnt = 1u + (__float_as_uint(kc[20] + kc[19] + kc[0]) == 0xffc12345u);
            if (lane == 0) asm volatile("mbarrier.arrive.shared::cta.b64 _,[%0],%1;" ::"r"(bar + 8 * (BAR_KD + w4)), "r"(cnt) : "memory");
            __syncwarp();
        }
        if (lane == 0) kc[4 * 0 + 0] += ((ch & 1) ? bf_hi(pds) : bf_lo(pds));
        const uint32_t k1024 = __shfl_sync(~0u, pack2(kc[4 * 4 + 0], 0.f), 0);
#pragma unroll
        for (int i = 0; i < 2; i++) {
            const int be = g + 8 * i;
#pragma unroll
            for (int t = 0; t < 2; t++) {
                const uint32_t a = kb_ + (KW_D + 128 * t + 8 * be + 2 * q) * 4;
                const uint32_t w = pack2(kc[4 * t + 2 * i + 1], kc[4 * t + 2 * i]);
                sts32(a + 4, w); sts16(a, w >> 16); sts16(a + 10, w);
            }
            {
                const int p = 256 + 128 * (q >> 1) + 8 * be + 4 * (q & 1);
                const uint32_t a = kb_ + (KW_D + p) * 4;
                const uint32_t w = pack2(kc[4 * 2 + 2 * i + 1], kc[4 * 2 + 2 * i]);
                const uint32_t aa = (w >> 16) | (w & 0xffff0000u);
                if (p != 256) { sts16(a - 4, aa); sts32(a, aa); } else sts16(a, aa);
                sts32(a + 4, aa); sts32(a + 8, w); sts16(a + 14, w);
            }
            {
                const int k = 64 + 16 * q + be;
                const uint32_t w = pack2(kc[4 * 3 + 2 * i], kc[4 * 3 + 2 * i + 1]);
                if (k != 64) sts16(kb_ + (KW_2 + ((k - 1) >> 1) - 24) * 4 + (k & 1) * 2, w);
                else {
                    const uint32_t a = kb_ + (KW_D + 511) * 4, aa = (w << 16) | (w & 0xffffu);
                    sts16(a, w); sts32(a + 4, aa); sts32(a + 8, aa); sts32(a + 12, aa); sts16(a + 18, w);
                }
                sts16(kb_ + (KW_2 + 48 + (k >> 1) - 24) * 4 + ((k & 1) ^ 1) * 2, w >> 16);
            }
#pragma unroll
            for (int b = 0; b < 2; b++) {
                const int k = 64 + 8 * (2 * q + b) + (be >> 1);
                const uint32_t w = pack2(kc[4 * 4 + 2 * i + b], 0.f);
                if (!(be & 1) && k == 64) sts16(kb_ + (KW_2 + 63 - 24) * 4, w);
                else {
                    const uint32_t a = kb_ + (KW_3 + ((be & 1) ? 80 + k : k - 1) - 48) * 4;
                    sts16(a, w);
                    if (!((be & 1) && k == 127)) sts16(a + 6, w);
                }
            }
        }
        if (lane == 0) sts16(kb_ + (KW_3 + 127 - 48) * 4, pack2(kc[4 * 5 + 0], 0.f));
        __syncwarp();
        asm volatile("setmaxnreg.inc.sync.aligned.u32 136;");
        mbar_wait(bar + 8 * BAR_UR, 0);
        mbar_wait(bar + 8 * BAR_DONE, 0);
        if (warp == 8) STAMP(23);
        float y[16][4];
#pragma unroll
        for (int nt = 0; nt < 16; nt++) { y[nt][0] = y[nt][1] = y[nt][2] = y[nt][3] = 0.f; }
        {
            uint32_t Bp[32], A[4][3], An[4][3];
            auto uaddr = [&](int rho) { const int R0 = (lane >> 4) * 64 + (lane & 7) - rho; return ub + (((2 * R0 + ((lane >> 3) & 1)) ^ ((R0 >> 2) & 1)) << 4); };
            const uint32_t kd = kb_ + (KW_D + g - 2 * q) * 4;
#pragma unroll 1
            for (int rho = 1; rho >= 0; rho--) {
                const uint32_t a = uaddr(rho), k = kd + 2048 + rho * 64;
#pragma unroll
                for (int i = 0; i < 8; i++) ldsm4(Bp + 4 * i, a + i * 256);
                const uint32_t a0 = lds32(k), a1 = lds32(k + 32), a2 = lds32(k - 32);
#pragma unroll
                for (int i = 0; i < 12; i++) mma16816(y[i + 4], a0, a1, a2, a0, Bp[4 * (i & 7) + 2 * (i >> 3)], Bp[4 * (i & 7) + 2 * (i >> 3) + 1]);
            }
#pragma unroll
            for (int ga = 0; ga < 4; ga++) { An[ga][0] = lds32(kd + ga * 512); An[ga][1] = lds32(kd + ga * 512 + 32); An[ga][2] = lds32(kd + ga * 512 - 32); }
#pragma unroll 1
            for (int rho = 0; rho < 8; rho++) {
#pragma unroll
                for (int ga = 0; ga < 4; ga++) {
                    const uint32_t a = kd + (rho + 1) * 64 + ga * 512;
                    A[ga][0] = An[ga][0]; A[ga][1] = An[ga][1]; A[ga][2] = An[ga][2];
                    An[ga][0] = lds32(a); An[ga][1] = lds32(a + 32); An[ga][2] = lds32(a - 32);
                }
                const uint32_t an = uaddr(rho + 1);
#pragma unroll
                for (int i = 0; i < 8; i++) {
#pragma unroll
                    for (int ga = 0; ga < 4; ga++) {
                        mma16816(y[i + ga], A[ga][0], A[ga][1], A[ga][2], A[ga][0], Bp[4 * i], Bp[4 * i + 1]);
                        if (i + 8 + ga < 16) mma16816(y[i + 8 + ga], A[ga][0], A[ga][1], A[ga][2], A[ga][0], Bp[4 * i + 2], Bp[4 * i + 3]);
                    }
                    ldsm4(Bp + 4 * i, an + i * 256);
                    __syncwarp();
                }
            }
        }
        if (warp == 8) STAMP(18);
        mbar_wait(bar + 8 * BAR_WR, 0);
#pragma unroll 1
        for (int ph = 0; ph < 2; ph++) {
            uint32_t B[5][2];
            const uint32_t ka = kb_ + (KW_2 + ph * 48 + 8 + g - q) * 4;
#pragma unroll
            for (int dd = 0; dd < 5; dd++) { B[dd][0] = lds32(ka + dd * 32); B[dd][1] = lds32(ka + dd * 32 - 16); }
            const uint32_t wa = buf + ph * W3_OFF + ((lane & 7) + ((lane >> 3) & 1) + (lane >> 4) * 8) * 16;
#pragma unroll
            for (int s = 0; s < 12; s++) {
                uint32_t A[4];
                ldsm4t(A, wa + s * 256);
#pragma unroll
                for (int dd = 0; dd < 5; dd++)
                    if (s + 4 + dd < 16) mma16816(y[s + 4 + dd], A[0], A[1], A[2], A[3], B[dd][0], B[dd][1]);
            }
        }
        {
            const int ap = (lane & 7) + (lane >> 4) * 8;
            const uint32_t loff = ((2 * ap + ((lane >> 3) & 1)) ^ ((ap >> 2) & 1)) << 4;
#pragma unroll 1
            for (int ph = 0; ph < 2; ph++) {
                uint32_t B[8][2];
                const uint32_t wb = (ph ? spare : buf + W9_OFF) + loff;
                const uint32_t ka = kb_ + (KW_3 + ph * 80 + 16 + g - 2 * q) * 4;
#pragma unroll
                for (int dd = 0; dd < 8; dd++) { B[dd][0] = lds32(ka + dd * 32); B[dd][1] = lds32(ka + dd * 32 - 32); }
#pragma unroll
                for (int s = 0; s < 4; s++) {
                    uint32_t A[4];
                    ldsm4t(A, wb + s * 512);
#pragma unroll
                    for (int dd = 0; dd < 8; dd++)
                        if (8 + 2 * s + dd < 16) mma16816(y[8 + 2 * s + dd], A[0], A[1], A[2], A[3], B[dd][0], B[dd][1]);
                }
            }
            const uint32_t idw = (g == 2 * q) ? k1024 : ((g == 2 * q + 1) ? (k1024 << 16) : 0u);
#pragma unroll
            for (int s = 0; s < 4; s++) {
                uint32_t A[4];
                ldsm4t(A, spare + 2048 + loff + s * 512);
                mma16816(y[8 + 2 * s], A[0], A[1], A[2], A[3], idw, 0u);
                mma16816(y[9 + 2 * s], A[0], A[1], A[2], A[3], 0u, idw);
            }
        }
        __syncwarp();
        if (warp == 8) STAMP(19);
#pragma unroll
        for (int nt = 0; nt < 16; nt++)
#pragma unroll
            for (int b = 0; b < 2; b++) sts32(buf + ((8 * nt + 2 * q + b) * 8 + g) * 4, pack2(y[nt][b], y[nt][2 + b]));
        bar_named(2, 128);
        uint4* yp = scr->y + bi * 1024 + st;
#pragma unroll
        for (int v = 0; v < 8; v++) {
            const uint32_t a = sb + OFF_BUF + (st + 128 * v) * 4;
            const uint32_t w0 = lds32(a), w1 = lds32(a + BUF_STRIDE), w2 = lds32(a + 2 * BUF_STRIDE), w3 = lds32(a + 3 * BUF_STRIDE);
            st_rlx128(yp + v * 128, tag4(__byte_perm(w0, w1, 0x5410), __byte_perm(w0, w1, 0x7632), __byte_perm(w2, w3, 0x5410), __byte_perm(w2, w3, 0x7632), tag));
        }
        if (warp == 8) STAMP(20);
    } else {
        const int qq = (bi_i & 2) + ((lane >> 1) & 1);
        uint2* kvf_h = (uint2*)(scr->kvf + (bi_j * 4 + (bi_i >> 2)) * 68);
        auto windows = [&](int rhi, int rlo) {
#pragma unroll 1
            for (int rho = rhi; rho >= rlo; rho--) {
                const int ci = lane + 32 * rho;
                uint4 e4[4];
#pragma unroll
                for (int v = 0; v < 4; v++) { const int cc = ci - 3 + v; e4[v] = lds128(ub + ((cc ^ ((cc >> 3) & 1)) << 4)); }
                float S[29];
                const uint32_t* ew = (const uint32_t*)e4;
                S[3] = 0.f;
#pragma unroll
                for (int k = 4; k <= 28; k++) S[k] = S[k - 1] + ((k & 1) ? bf_hi(ew[k >> 1]) : bf_lo(ew[k >> 1]));
                auto win = [&](int lo, int hi, uint32_t a) {
                    sts128(a, pack2(S[hi] - S[lo - 1], S[hi + 1] - S[lo]), pack2(S[hi + 2] - S[lo + 1], S[hi + 3] - S[lo + 2]),
                           pack2(S[hi + 4] - S[lo + 3], S[hi + 5] - S[lo + 4]), pack2(S[hi + 6] - S[lo + 5], S[hi + 7] - S[lo + 6]));
                };
                win(14, 18, buf + W5_OFF + 16 + ci * 16); win(19, 21, buf + W3_OFF + 16 + ci * 16);
                if (rho < 4) {
                    const uint32_t sw = (ci ^ ((ci >> 3) & 1)) << 4;
                    win(4, 12, buf + W9_OFF + sw); win(13, 19, spare + sw); win(20, 21, spare + 2048 + sw);
                }
            }
        };
        {
            mbar_wait(bar + 8 * (BAR_FULL + xkb), 0);
#pragma unroll 1
            for (int hf = 0; hf < 2; hf++) {
                const int r = w4 * 32 + hf * 16 + (lane & 15);
                uint32_t* xt = (uint32_t*)scr->xt + ((xkb + rot) * 16 + (g >> 2)) * 4096 + (bi_i * 16 + w4 * 4 + hf * 2) * 16 + (g & 3) * 4 + q;
#pragma unroll
                for (int cb = 0; cb < 8; cb += 2) {
                    uint32_t v[4];
                    ldsm4t(v, sb + xkb * SLOT + r * 128 + (((cb + (lane >> 4)) ^ (r & 7)) << 4));
                    xt[cb * 8192] = v[0]; xt[cb * 8192 + 16] = v[1]; xt[cb * 8192 + 8192] = v[2]; xt[cb * 8192 + 8192 + 16] = v[3];
                }
            }
            __syncwarp();
            if (lane == 0) mbar_arrive(bar + 8 * BAR_XT);
            if (warp == 12) STAMP(26);
            handoff(2);
            asm volatile("setmaxnreg.dec.sync.aligned.u32 56;");
            if (lane == 0) asm volatile("red.release.gpu.global.add.u32 [%0],2;" ::"l"(scr->xcnt + (xkb + rot) * 32) : "memory");
            __syncwarp();
            if (warp == 12) STAMP(27);
            {
                const uint32_t old = tag ^ 1u;
                const uint4 z4 = make_uint4(old, 0, old, 0);
#pragma unroll
                for (int v = 0; v < 5; v++) if (v < 4 || st < 32) st_rlx128(scr->kvp + bi * 544 + v * 128 + st, z4);
                if (st < 16) st_rlx128(scr->o + ((bi_i * 8 + (st >> 1)) * 32 + bi_j * 4 + 3) * 32 + 30 + (st & 1), z4);
                if (lane < 8) st_rlx64(kvf_h + ((bi_i & 3) * 8 + w4 * 2 + (lane & 1)) * 4 + (lane >> 1), old, 0);
                if (st < 4 && !(bi_i & 1)) st_rlx64(kvf_h + (64 + qq) * 2 + (lane & 1), old, 0);
                __syncwarp();
                if (lane == 0) mbar_arrive(bar + 8 * BAR_PREP);
            }
            int n = 0;
#pragma unroll 1
            while (__any_sync(~0u, (int)(ld_acq(scr->xcnt + bi_j * 32) - (epoch1 << 7)) < 0)) { if (++n > SPIN_LIMIT) break; }
            if (warp == 12) STAMP(15);
            uint4 ur[8];
#pragma unroll
            for (int v = 0; v < 8; v++) ur[v] = __ldcg(scr->xt + bi * 1024 + st + 128 * v);
            mbar_wait(bar + 8 * BAR_KG, 0);
            if (lane < 16) sts128(ub - 256 + lane * 16, 0, 0, 0, 0);
#pragma unroll
            for (int v = 0; v < 8; v++) {
                const int ci = (st >> 2) + 32 * v;
                sts128(sb + OFF_U + (st & 3) * U_STRIDE + 256 + ((ci ^ ((ci >> 3) & 1)) << 4), ur[v].x, ur[v].y, ur[v].z, ur[v].w);
            }
            __syncwarp();
            if (lane == 0) mbar_arrive(bar + 8 * BAR_UR);
            mbar_wait(bar + 8 * BAR_UR, 0);
            if (warp == 12) STAMP(16);
            mbar_wait(bar + 8 * (BAR_KD + w4), 0);
            if (lane < 2) sts128(buf + lane * W3_OFF, 0, 0, 0, 0);
            windows(5, 4);
        }
        mbar_wait(bar + 8 * BAR_SP2, 0);
        windows(3, 0);
        __syncwarp();
        if (lane == 0) mbar_arrive(bar + 8 * BAR_WR);
        if (warp == 12) STAMP(24);
        {
            const bool zw = st < 32 && !(bi_i & 1);
            const uint4* src = scr->kvp + bi_j * (16 * 544) + (bi_i >> 2) * 136;
            const uint4* zsrc = src + (lane >> 2) * (2 * 544) + 128 + (lane & 1) * 4 + qq;
            src += (lane >> 3) * (4 * 544) + ((lane >> 1) & 3) * 32 + (bi_i & 3) * 8 + w4 * 2 + (lane & 1);
            mbar_wait(bar + 8 * BAR_PUB, 0);
            if (warp == 12) STAMP(12);
            uint4 v[6];
#pragma unroll
            for (int k = 0; k < 6; k++) v[k] = make_uint4(tag ^ 1u, 0, 0, 0);
            int n = 0;
#pragma unroll 1
            while (true) {
#pragma unroll
                for (int k = 0; k < 6; k++) if ((bad4(v[k], tag) & 1) && (k < 4 || zw)) v[k] = ld_rlx128(k < 4 ? src + k * 544 : zsrc + (k - 4) * 544);
                if (!__any_sync(~0u, (bad4(v[0], tag) | bad4(v[1], tag) | bad4(v[2], tag) | bad4(v[3], tag) | (zw ? bad4(v[4], tag) | bad4(v[5], tag) : 0u)) & 1)) break;
                if (++n > SPIN_LIMIT) break;
            }
            if (warp == 12) STAMP(30);
            float f[8];
            const float* vf = (const float*)v;
#pragma unroll
            for (int r = 0; r < 4; r++) {
                f[r] = (vf[r] + vf[4 + r]) + (vf[8 + r] + vf[12 + r]);
                f[4 + r] = vf[16 + r] + vf[20 + r];
                f[4 + r] += __shfl_xor_sync(~0u, f[4 + r], 4);
            }
#pragma unroll
            for (int o = 8; o <= 16; o <<= 1)
#pragma unroll
                for (int r = 0; r < 8; r++) f[r] += __shfl_xor_sync(~0u, f[r], o);
            if (lane < 8) st_rlx64(kvf_h + ((bi_i & 3) * 8 + w4 * 2 + (lane & 1)) * 4 + (lane >> 1), tagw(pack2(f[0], f[1]), tag), pack2(f[2], f[3]));
            if (zw && lane < 4) st_rlx64(kvf_h + (64 + qq) * 2 + (lane & 1), tagw(pack2(f[4], f[5]), tag), pack2(f[6], f[7]));
        }
        if (warp == 12) STAMP(13);
        {
            const uint4* kp = scr->kvf + (bi_j * 4 + w4) * 68 + lane;
            uint4 v0 = make_uint4(tag ^ 1u, 0, 0, 0), v1 = v0, v2 = make_uint4(lane < 4 ? tag ^ 1u : tag, 0, tag, 0);
            int n = 0;
#pragma unroll 1
            while (true) {
                if (bad4(v0, tag) & 1) v0 = ld_rlx128(kp);
                if (bad4(v1, tag) & 1) v1 = ld_rlx128(kp + 32);
                if (bad4(v2, tag) & 1) v2 = ld_rlx128(kp + 64);
                if (!__any_sync(~0u, (bad4(v0, tag) | bad4(v1, tag) | bad4(v2, tag)) & 1)) break;
                if (++n > SPIN_LIMIT) break;
            }
            const uint32_t a = sb + OFF_KVF + w4 * 1088 + lane * 16;
            sts128(a, v0.x, v0.y, v0.z, v0.w);
            sts128(a + 512, v1.x, v1.y, v1.z, v1.w);
            if (lane < 4) sts128(a + 1024, v2.x, v2.y, v2.z, v2.w);
            __syncwarp();
            if (lane == 0) mbar_arrive(bar + 8 * (BAR_KVF + w4));
        }
        if (warp == 13) {
            if (lane == 0) {
                mbar_expect(bar + 8 * BAR_WO2, 65536);
                tma2d(sb + OFF_P, &mwo, (bi_j & 3) * 128 + 64, 256, bar + 8 * BAR_WO2);
                tma2d(sb + OFF_V, &mwo, (bi_j & 3) * 128, 256, bar + 8 * BAR_WO2);
            }
        }
        if (warp == 12) STAMP(25);
    }
    __syncwarp();
    if (lane == 0) {
        unsigned old;
        asm volatile("atom.acq_rel.cta.shared.add.u32 %0,[%1],1;" : "=r"(old) : "r"(bar + OFF_CNT) : "memory");
        if (old == 15) {
            atomicAdd(scr->done, 1u);
        }
    }
}

typedef CUresult (*EncFn)(CUtensorMap*, CUtensorMapDataType, cuuint32_t, void*, const cuuint64_t*, const cuuint64_t*, const cuuint32_t*,
                          const cuuint32_t*, CUtensorMapInterleave, CUtensorMapSwizzle, CUtensorMapL2promotion, CUtensorMapFloatOOBfill);

extern "C" void kernel_launch(void* const* d_in, const int* in_sizes, int n_in, void* d_out, int out_size) {
    static EncFn enc = nullptr;
    static Scratch* scr = nullptr;
    if (!enc) {
        cudaGetSymbolAddress((void**)&scr, g_scr);
        cudaDriverEntryPointQueryResult qr;
        cudaGetDriverEntryPoint("cuTensorMapEncodeTiled", (void**)&enc, cudaEnableDefault, &qr);
        cudaFuncSetAttribute(fused_kernel, cudaFuncAttributeMaxDynamicSharedMemorySize, SMEM_BYTES);
    }
    CUtensorMap mx, mw, mwo;
    const cuuint32_t es[3] = {1, 1, 1};
    {
        cuuint64_t d[2] = {512, 2048}, s[1] = {1024}; cuuint32_t b[2] = {64, 128};
        enc(&mx, CU_TENSOR_MAP_DATA_TYPE_BFLOAT16, 2, d_in[0], d, s, b, es, CU_TENSOR_MAP_INTERLEAVE_NONE, CU_TENSOR_MAP_SWIZZLE_128B,
            CU_TENSOR_MAP_L2_PROMOTION_L2_128B, CU_TENSOR_MAP_FLOAT_OOB_FILL_NONE);
    }
    {
        cuuint64_t d[3] = {512, 512, 3}, s[2] = {3072, 1024}; cuuint32_t b[3] = {64, 64, 3};
        enc(&mw, CU_TENSOR_MAP_DATA_TYPE_BFLOAT16, 3, d_in[1], d, s, b, es, CU_TENSOR_MAP_INTERLEAVE_NONE, CU_TENSOR_MAP_SWIZZLE_128B,
            CU_TENSOR_MAP_L2_PROMOTION_L2_128B, CU_TENSOR_MAP_FLOAT_OOB_FILL_NONE);
    }
    {
        cuuint64_t d[2] = {512, 512}, s[1] = {1024}; cuuint32_t b[2] = {64, 256};
        enc(&mwo, CU_TENSOR_MAP_DATA_TYPE_BFLOAT16, 2, d_in[3], d, s, b, es, CU_TENSOR_MAP_INTERLEAVE_NONE, CU_TENSOR_MAP_SWIZZLE_128B,
            CU_TENSOR_MAP_L2_PROMOTION_L2_128B, CU_TENSOR_MAP_FLOAT_OOB_FILL_NONE);
    }
    fused_kernel<<<128, 512, SMEM_BYTES, cudaStreamPerThread>>>(
        scr, (const bf16*)d_in[5], (const bf16*)d_in[6], (const bf16*)d_in[7], (const bf16*)d_in[8], (const bf16*)d_in[9],
        (const bf16*)d_in[10], (const bf16*)d_in[2], (const bf16*)d_in[11], (bf16*)d_out, mx, mw, mwo);
}
```

```cpp
#include <cuda_runtime.h>
#include <cuda.h>
#include <cuda_bf16.h>
#include <stdint.h>

typedef __nv_bfloat16 bf16;

struct Scratch {
    uint4 xt[128 * 1024];
    uint4 o[16 * 8 * 32 * 32];
    uint4 y[128 * 1024];
    uint4 kvp[8 * 16 * 544];
    uint4 kvf[8 * 4 * 68];
    unsigned g[1024 * 8];
    unsigned xcnt[8 * 32];
    unsigned done[32];
};
__device__ Scratch g_scr;

constexpr int SLOT = 40960;
constexpr int OFF_SP0 = 32768, OFF_SP1 = SLOT + 32768;
constexpr int OFF_P = 2 * SLOT, OFF_V = OFF_P + 32768;
constexpr int OFF_KVF = OFF_V + 32768;
constexpr int KT_BYTES = 3264, KW_D = 16, KW_2 = 560, KW_3 = 656;
constexpr int OFF_U = 4 * SLOT, U_STRIDE = 4096 + 256 + 32;
constexpr int OFF_BUF = OFF_U + 4 * U_STRIDE, BUF_STRIDE = 8320;
constexpr int OFF_K = OFF_BUF + 4 * BUF_STRIDE;
constexpr int OFF_WPHI = OFF_K + 4 * KT_BYTES;
constexpr int OFF_GW = OFF_WPHI + 2048;
constexpr int OFF_BAR = OFF_GW + 1024;
constexpr int SMEM_BYTES = OFF_BAR + 320;
static_assert(SMEM_BYTES <= 232448 && OFF_BUF % 128 == 0, "smem");
constexpr int W5_OFF = 0, W3_OFF = 3088, W9_OFF = 6176;
constexpr int BAR_FULL = 0, BAR_EMPTY = 4, BAR_WPHI = 8, BAR_WO = 9, BAR_WO2 = 10, BAR_XT = 11, BAR_DONE = 12, BAR_KG = 13,
              BAR_PUB = 15, BAR_UR = 17, BAR_WR = 18, BAR_PREP = 19, BAR_KGA = 20, BAR_SP2 = 21, BAR_KS = 22, BAR_KP = 26, BAR_KD = 30, BAR_KVF = 34, OFF_CNT = 304;
constexpr int SPIN_LIMIT = 1 << 17;

__device__ __forceinline__ uint32_t s2u(const void* p) { return (uint32_t)__cvta_generic_to_shared(p); }
__device__ __forceinline__ void mbar_init(uint32_t b, int c) { asm volatile("mbarrier.init.shared::cta.b64 [%0],%1;" ::"r"(b), "r"(c) : "memory"); }
__device__ __forceinline__ void mbar_expect(uint32_t b, int bytes) { asm volatile("mbarrier.arrive.expect_tx.shared::cta.b64 _,[%0],%1;" ::"r"(b), "r"(bytes) : "memory"); }
__device__ __forceinline__ void mbar_arrive(uint32_t b) { asm volatile("mbarrier.arrive.shared::cta.b64 _,[%0];" ::"r"(b) : "memory"); }
__device__ __forceinline__ void mbar_wait(uint32_t b, int ph) {
    asm volatile("{\n.reg .pred p;\n.reg .u32 n;\nmov.u32 n,0;\nLW_%=:\nmbarrier.try_wait.parity.shared::cta.b64 p,[%0],%1;\n@p bra LD_%=;\n"
                 "add.u32 n,n,1;\nsetp.lt.u32 p,n,16384;\n@p bra LW_%=;\nLD_%=:\n}" ::"r"(b), "r"(ph) : "memory");
}
__device__ __forceinline__ void tma2d(uint32_t dst, const CUtensorMap* m, int c0, int c1, uint32_t bar) {
    asm volatile("cp.async.bulk.tensor.2d.shared::cluster.global.mbarrier::complete_tx::bytes [%0],[%1,{%3,%4}],[%2];" ::"r"(dst), "l"(m), "r"(bar), "r"(c0), "r"(c1) : "memory");
}
__device__ __forceinline__ void tma3d(uint32_t dst, const CUtensorMap* m, int c0, int c1, int c2, uint32_t bar) {
    asm volatile("cp.async.bulk.tensor.3d.shared::cluster.global.mbarrier::complete_tx::bytes [%0],[%1,{%3,%4,%5}],[%2];" ::"r"(dst), "l"(m), "r"(bar), "r"(c0), "r"(c1), "r"(c2) : "memory");
}
__device__ __forceinline__ void bulk_g2s(uint32_t dst, const void* src, int bytes, uint32_t bar) {
    asm volatile("cp.async.bulk.shared::cluster.global.mbarrier::complete_tx::bytes [%0],[%1],%2,[%3];" ::"r"(dst), "l"(src), "r"(bytes), "r"(bar) : "memory");
}
__device__ __forceinline__ uint64_t mkdesc(uint32_t addr, uint32_t lbo, uint32_t sbo) {
    return (uint64_t)((addr & 0x3FFFF) >> 4) | ((uint64_t)(lbo >> 4) << 16) | ((uint64_t)(sbo >> 4) << 32) | ((uint64_t)1 << 62);
}
__device__ __forceinline__ void wg_fence() { asm volatile("wgmma.fence.sync.aligned;" ::: "memory"); }
__device__ __forceinline__ void wg_commit() { asm volatile("wgmma.commit_group.sync.aligned;" ::: "memory"); }
template <int N> __device__ __forceinline__ void wg_wait() { asm volatile("wgmma.wait_group.sync.aligned %0;" ::"n"(N) : "memory"); }
template <int N> __device__ __forceinline__ void fence_regs(float* d) {
#pragma unroll
    for (int i = 0; i < N; i++) asm volatile("" : "+f"(d[i])::"memory");
}
#define R8(d, o) "+f"(d[o]), "+f"(d[o + 1]), "+f"(d[o + 2]), "+f"(d[o + 3]), "+f"(d[o + 4]), "+f"(d[o + 5]), "+f"(d[o + 6]), "+f"(d[o + 7])
__device__ __forceinline__ void wgmma192(float* d, uint64_t da, uint64_t db, int sc) {
    asm volatile("{.reg .pred p; setp.ne.b32 p,%98,0; wgmma.mma_async.sync.aligned.m64n192k16.f32.bf16.bf16 {"
                 "%0,%1,%2,%3,%4,%5,%6,%7,%8,%9,%10,%11,%12,%13,%14,%15,%16,%17,%18,%19,%20,%21,%22,%23,%24,%25,%26,%27,%28,%29,%30,%31,"
                 "%32,%33,%34,%35,%36,%37,%38,%39,%40,%41,%42,%43,%44,%45,%46,%47,%48,%49,%50,%51,%52,%53,%54,%55,%56,%57,%58,%59,%60,%61,%62,%63,"
                 "%64,%65,%66,%67,%68,%69,%70,%71,%72,%73,%74,%75,%76,%77,%78,%79,%80,%81,%82,%83,%84,%85,%86,%87,%88,%89,%90,%91,%92,%93,%94,%95},"
                 "%96,%97,p,1,1,0,1;}"
                 : R8(d, 0), R8(d, 8), R8(d, 16), R8(d, 24), R8(d, 32), R8(d, 40), R8(d, 48), R8(d, 56), R8(d, 64), R8(d, 72), R8(d, 80), R8(d, 88)
                 : "l"(da), "l"(db), "r"(sc));
}
__device__ __forceinline__ void wgmma64_tt(float* d, uint64_t da, uint64_t db, int sc) {
    asm volatile("{.reg .pred p; setp.ne.b32 p,%34,0; wgmma.mma_async.sync.aligned.m64n64k16.f32.bf16.bf16 {"
                 "%0,%1,%2,%3,%4,%5,%6,%7,%8,%9,%10,%11,%12,%13,%14,%15,%16,%17,%18,%19,%20,%21,%22,%23,%24,%25,%26,%27,%28,%29,%30,%31},"
                 "%32,%33,p,1,1,1,1;}"
                 : R8(d, 0), R8(d, 8), R8(d, 16), R8(d, 24)
                 : "l"(da), "l"(db), "r"(sc));
}
__device__ __forceinline__ void wgmma128_rs(float* d, const uint4& a, uint64_t db, int sc) {
    asm volatile("{.reg .pred p; setp.ne.b32 p,%69,0; wgmma.mma_async.sync.aligned.m64n128k16.f32.bf16.bf16 {"
                 "%0,%1,%2,%3,%4,%5,%6,%7,%8,%9,%10,%11,%12,%13,%14,%15,%16,%17,%18,%19,%20,%21,%22,%23,%24,%25,%26,%27,%28,%29,%30,%31,"
                 "%32,%33,%34,%35,%36,%37,%38,%39,%40,%41,%42,%43,%44,%45,%46,%47,%48,%49,%50,%51,%52,%53,%54,%55,%56,%57,%58,%59,%60,%61,%62,%63},"
                 "{%64,%65,%66,%67},%68,p,1,1,1;}"
                 : R8(d, 0), R8(d, 8), R8(d, 16), R8(d, 24), R8(d, 32), R8(d, 40), R8(d, 48), R8(d, 56)
                 : "r"(a.x), "r"(a.y), "r"(a.z), "r"(a.w), "l"(db), "r"(sc));
}
__device__ __forceinline__ void mma16816(float* c, uint32_t a0, uint32_t a1, uint32_t a2, uint32_t a3, uint32_t b0, uint32_t b1) {
    asm("mma.sync.aligned.m16n8k16.row.col.f32.bf16.bf16.f32 {%0,%1,%2,%3},{%4,%5,%6,%7},{%8,%9},{%0,%1,%2,%3};"
        : "+f"(c[0]), "+f"(c[1]), "+f"(c[2]), "+f"(c[3]) : "r"(a0), "r"(a1), "r"(a2), "r"(a3), "r"(b0), "r"(b1));
}
__device__ __forceinline__ void ldsm4(uint32_t* r, uint32_t a) {
    asm volatile("ldmatrix.sync.aligned.m8n8.x4.shared.b16 {%0,%1,%2,%3},[%4];" : "=r"(r[0]), "=r"(r[1]), "=r"(r[2]), "=r"(r[3]) : "r"(a) : "memory");
}
__device__ __forceinline__ void ldsm4t(uint32_t* r, uint32_t a) {
    asm volatile("ldmatrix.sync.aligned.m8n8.x4.trans.shared.b16 {%0,%1,%2,%3},[%4];" : "=r"(r[0]), "=r"(r[1]), "=r"(r[2]), "=r"(r[3]) : "r"(a) : "memory");
}
__device__ __forceinline__ void stsm4(uint32_t a, uint32_t r0, uint32_t r1, uint32_t r2, uint32_t r3) {
    asm volatile("stmatrix.sync.aligned.m8n8.x4.shared.b16 [%0],{%1,%2,%3,%4};" ::"r"(a), "r"(r0), "r"(r1), "r"(r2), "r"(r3) : "memory");
}
__device__ __forceinline__ uint32_t lds32(uint32_t a) { uint32_t v; asm volatile("ld.shared.b32 %0,[%1];" : "=r"(v) : "r"(a) : "memory"); return v; }
__device__ __forceinline__ uint4 lds128(uint32_t a) { uint4 v; asm volatile("ld.shared.v4.b32 {%0,%1,%2,%3},[%4];" : "=r"(v.x), "=r"(v.y), "=r"(v.z), "=r"(v.w) : "r"(a) : "memory"); return v; }
__device__ __forceinline__ void sts16(uint32_t a, uint32_t v) { asm volatile("st.shared.b16 [%0],%1;" ::"r"(a), "h"((unsigned short)v) : "memory"); }
__device__ __forceinline__ void sts32(uint32_t a, uint32_t v) { asm volatile("st.shared.b32 [%0],%1;" ::"r"(a), "r"(v) : "memory"); }
__device__ __forceinline__ void sts64(uint32_t a, uint32_t x, uint32_t y) { asm volatile("st.shared.v2.b32 [%0],{%1,%2};" ::"r"(a), "r"(x), "r"(y) : "memory"); }
__device__ __forceinline__ void sts128(uint32_t a, uint32_t x, uint32_t y, uint32_t z, uint32_t w) { asm volatile("st.shared.v4.b32 [%0],{%1,%2,%3,%4};" ::"r"(a), "r"(x), "r"(y), "r"(z), "r"(w) : "memory"); }
__device__ __forceinline__ uint32_t pack2(float lo, float hi) { uint32_t d; asm("cvt.rn.bf16x2.f32 %0,%1,%2;" : "=r"(d) : "f"(hi), "f"(lo)); return d; }
__device__ __forceinline__ float bf_lo(uint32_t v) { return __uint_as_float(v << 16); }
__device__ __forceinline__ float bf_hi(uint32_t v) { return __uint_as_float(v & 0xffff0000u); }
__device__ __forceinline__ float bf_round(float v) { return bf_lo(pack2(v, 0.f)); }
__device__ __forceinline__ uint32_t hmul2(uint32_t a, uint32_t b) { uint32_t d; asm("mul.rn.bf16x2 %0,%1,%2;" : "=r"(d) : "r"(a), "r"(b)); return d; }
__device__ __forceinline__ float ex2(float x) { float y; asm("ex2.approx.ftz.f32 %0,%1;" : "=f"(y) : "f"(x)); return y; }
__device__ __forceinline__ float rcp(float x) { float y; asm("rcp.approx.ftz.f32 %0,%1;" : "=f"(y) : "f"(x)); return y; }
__device__ __forceinline__ uint32_t ld_nc(const uint32_t* p) { uint32_t v; asm volatile("ld.global.nc.b32 %0,[%1];" : "=r"(v) : "l"(p)); return v; }
__device__ __forceinline__ unsigned ld_acq(const unsigned* p) { unsigned v; asm volatile("ld.acquire.gpu.global.u32 %0,[%1];" : "=r"(v) : "l"(p) : "memory"); return v; }
__device__ __forceinline__ unsigned ld_rlx(const unsigned* p) { unsigned v; asm volatile("ld.relaxed.gpu.global.u32 %0,[%1];" : "=r"(v) : "l"(p) : "memory"); return v; }
__device__ __forceinline__ uint2 ld_rlx64(const void* p) { uint2 v; asm volatile("{.reg .b64 t; ld.relaxed.gpu.global.b64 t,[%2]; mov.b64 {%0,%1},t;}" : "=r"(v.x), "=r"(v.y) : "l"(p) : "memory"); return v; }
__device__ __forceinline__ uint4 ld_rlx128(const void* p) {
    uint4 v;
    asm volatile("{.reg .b64 t,u; ld.relaxed.gpu.global.v2.b64 {t,u},[%4]; mov.b64 {%0,%1},t; mov.b64 {%2,%3},u;}" : "=r"(v.x), "=r"(v.y), "=r"(v.z), "=r"(v.w) : "l"(p) : "memory");
    return v;
}
__device__ __forceinline__ void st_rlx32(void* p, uint32_t x) { asm volatile("st.relaxed.gpu.global.u32 [%0],%1;" ::"l"(p), "r"(x) : "memory"); }
__device__ __forceinline__ void st_rlx64(void* p, uint32_t x, uint32_t y) { asm volatile("{.reg .b64 t; mov.b64 t,{%1,%2}; st.relaxed.gpu.global.b64 [%0],t;}" ::"l"(p), "r"(x), "r"(y) : "memory"); }
__device__ __forceinline__ void st_rlx128(void* p, uint4 v) {
    asm volatile("{.reg .b64 t,u; mov.b64 t,{%1,%2}; mov.b64 u,{%3,%4}; st.relaxed.gpu.global.v2.b64 [%0],{t,u};}" ::"l"(p), "r"(v.x), "r"(v.y), "r"(v.z), "r"(v.w) : "memory");
}
__device__ __forceinline__ uint32_t tagw(uint32_t w, uint32_t tag) { return (w & ~1u) | tag; }
__device__ __forceinline__ uint4 tag4(uint32_t x, uint32_t y, uint32_t z, uint32_t w, uint32_t tag) { return make_uint4(tagw(x, tag), y, tagw(z, tag), w); }
__device__ __forceinline__ uint32_t bad4(const uint4& v, uint32_t tag) { return (v.x ^ tag) | (v.z ^ tag); }
__device__ __forceinline__ void bar_named(int id, int n) { asm volatile("bar.sync %0,%1;" ::"r"(id), "r"(n) : "memory"); }

struct cf { float re, im; };
__device__ __forceinline__ cf cmul(cf a, cf b) { cf r; r.re = a.re * b.re - a.im * b.im; r.im = a.re * b.im + a.im * b.re; return r; }
__device__ __forceinline__ cf cexp_p(float arl, float ait, float p) {
    float mag = ex2(arl * p);
    float t = ait * p;
    const float big = 12582912.f;
    t = (t - ((t + big) - big)) * 6.283185307179586f;
    cf r; r.re = mag * __cosf(t); r.im = mag * __sinf(t);
    return r;
}

__device__ __forceinline__ void hedgehog4(const uint32_t* a, uint32_t wphi_addr, uint32_t (*out)[8]) {
    float p[4][2][4], mx[4][2];
#pragma unroll
    for (int h = 0; h < 4; h++) {
        uint32_t b[4];
        ldsm4t(b, wphi_addr + h * 512);
        float c0[4] = {0.f, 0.f, 0.f, 0.f}, c1[4] = {0.f, 0.f, 0.f, 0.f};
        mma16816(c0, a[4 * h], a[4 * h + 1], a[4 * h + 2], a[4 * h + 3], b[0], b[1]);
        mma16816(c1, a[4 * h], a[4 * h + 1], a[4 * h + 2], a[4 * h + 3], b[2], b[3]);
#pragma unroll
        for (int k = 0; k < 2; k++) {
            p[h][k][0] = c0[2 * k]; p[h][k][1] = c0[2 * k + 1]; p[h][k][2] = c1[2 * k]; p[h][k][3] = c1[2 * k + 1];
            mx[h][k] = fmaxf(fmaxf(p[h][k][0], p[h][k][1]), fmaxf(p[h][k][2], p[h][k][3]));
        }
    }
#pragma unroll
    for (int o = 1; o <= 2; o <<= 1)
#pragma unroll
        for (int h = 0; h < 4; h++)
#pragma unroll
            for (int k = 0; k < 2; k++) mx[h][k] = fmaxf(mx[h][k], __shfl_xor_sync(~0u, mx[h][k], o));
    const float L = 1.4426950408889634f;
    float pmin = 1.f;
#pragma unroll
    for (int h = 0; h < 4; h++)
#pragma unroll
        for (int k = 0; k < 2; k++) {
            const float m = -mx[h][k] * L;
            const float e0 = ex2(fmaf(p[h][k][0], L, m)), e1 = ex2(fmaf(p[h][k][1], L, m)), e2 = ex2(fmaf(p[h][k][2], L, m)), e3 = ex2(fmaf(p[h][k][3], L, m));
            const float p01 = e0 * e1, p23 = e2 * e3, pp = p01 * p23, r = rcp(pp), r01 = r * p23, r23 = r * p01;
            pmin = fminf(pmin, pp);
            out[h][k] = pack2(e0, e1); out[h][k + 2] = pack2(e2, e3);
            out[h][4 + k] = pack2(r01 * e1, r01 * e0); out[h][4 + k + 2] = pack2(r23 * e3, r23 * e2);
        }
    if (__builtin_expect(__any_sync(~0u, !(pmin > 1e-18f)), 0)) {
#pragma unroll
        for (int h = 0; h < 4; h++)
#pragma unroll
            for (int k = 0; k < 2; k++) {
                float m = fminf(fminf(p[h][k][0], p[h][k][1]), fminf(p[h][k][2], p[h][k][3]));
                m = fminf(m, __shfl_xor_sync(~0u, m, 1));
                m = fminf(m, __shfl_xor_sync(~0u, m, 2)) * L;
                out[h][4 + k] = pack2(ex2(fmaf(p[h][k][0], -L, m)), ex2(fmaf(p[h][k][1], -L, m)));
                out[h][4 + k + 2] = pack2(ex2(fmaf(p[h][k][2], -L, m)), ex2(fmaf(p[h][k][3], -L, m)));
            }
    }
}

__global__ void __launch_bounds__(512, 1)
fused_kernel(Scratch* __restrict__ scr, const bf16* __restrict__ logA, const bf16* __restrict__ Aim, const bf16* __restrict__ Cre,
             const bf16* __restrict__ Cim, const bf16* __restrict__ logdt, const bf16* __restrict__ Dskip, const bf16* __restrict__ wphi,
             const bf16* __restrict__ gatew, bf16* __restrict__ out,
             const __grid_constant__ CUtensorMap mx, const __grid_constant__ CUtensorMap mw, const __grid_constant__ CUtensorMap mwo) {
    extern __shared__ __align__(1024) uint8_t smem[];
    constexpr uint32_t sb = 1024;
    const int tid = threadIdx.x, warp = __shfl_sync(~0u, tid >> 5, 0), lane = tid & 31;
    const int g = lane >> 2, q = lane & 3, w4 = warp & 3;
    const int bi = blockIdx.x, bi_i = bi & 15, bi_j = bi >> 4;
    const uint32_t bar = sb + OFF_BAR;
    const int rot = (bi_j & 3) * 2, xkb = bi_j >> 2;
    auto load_stage = [&](int kb) {
        const uint32_t b = bar + 8 * (BAR_FULL + (kb & 3)), d = sb + (kb & 3) * SLOT;
        const int kc = ((kb + rot) & 7) * 64;
        mbar_expect(b, SLOT);
        tma2d(d, &mx, kc, bi_i * 128, b);
        tma3d(d + 16384, &mw, bi_j * 64, kc, 0, b);
    };

    const int ch = bi * 4 + w4;
    const int pidx = ch * 64 + lane * 2 + (warp >> 3);
    const uint32_t pla = ld_nc((const uint32_t*)logA + pidx), pai = ld_nc((const uint32_t*)Aim + pidx);
    const uint32_t pcr = ld_nc((const uint32_t*)Cre + pidx), pci = ld_nc((const uint32_t*)Cim + pidx);
    uint32_t pdt = ld_nc((const uint32_t*)logdt + (ch >> 1));
    const uint32_t pds = ld_nc((const uint32_t*)Dskip + (ch >> 1));
    unsigned done0 = ld_rlx(scr->done);
    if (tid == 0) {
        for (int s = 0; s < 4; s++) mbar_init(bar + 8 * (BAR_FULL + s), 1);
        asm volatile("fence.mbarrier_init.release.cluster;" ::: "memory");
        asm volatile("prefetch.tensormap [%0];" ::"l"(&mx) : "memory");
        load_stage(0); load_stage(1);
    } else if (tid == 32) {
        if (s2u(smem) != sb) __trap();
        sts32(bar + OFF_CNT, 0);
        for (int s = 0; s < 4; s++) { mbar_init(bar + 8 * (BAR_EMPTY + s), 9); mbar_init(bar + 8 * (BAR_KS + s), 1); mbar_init(bar + 8 * (BAR_KP + s), 3); mbar_init(bar + 8 * (BAR_KD + s), 1); mbar_init(bar + 8 * (BAR_KVF + s), 1); }
        mbar_init(bar + 8 * BAR_WPHI, 1); mbar_init(bar + 8 * BAR_WO, 2); mbar_init(bar + 8 * BAR_WO2, 1); mbar_init(bar + 8 * BAR_XT, 4);
        mbar_init(bar + 8 * BAR_DONE, 9); mbar_init(bar + 8 * BAR_KG, 8); mbar_init(bar + 8 * BAR_PUB, 8);
        mbar_init(bar + 8 * BAR_UR, 4); mbar_init(bar + 8 * BAR_WR, 4); mbar_init(bar + 8 * BAR_PREP, 4); mbar_init(bar + 8 * BAR_KGA, 4); mbar_init(bar + 8 * BAR_SP2, 1);
        asm volatile("fence.mbarrier_init.release.cluster;" ::: "memory");
        mbar_expect(bar + 8 * BAR_WPHI, 3072);
        bulk_g2s(sb + OFF_GW, gatew, 1024, bar + 8 * BAR_WPHI);
        bulk_g2s(sb + OFF_WPHI, wphi + bi_j * 1024, 2048, bar + 8 * BAR_WPHI);
    } else if (tid == 64) {
        asm volatile("prefetch.tensormap [%0];" ::"l"(&mw) : "memory");
    }
    const uint32_t buf = sb + OFF_BUF + w4 * BUF_STRIDE, kb_ = sb + OFF_K + w4 * KT_BYTES;
    if ((warp >> 2) == 2) {
#pragma unroll
        for (int v = 0; v < 7; v++) if (v * 32 + lane < KT_BYTES / 16) sts128(kb_ + (v * 32 + lane) * 16, 0, 0, 0, 0);
    }
    __syncthreads();
    asm volatile("" : "+r"(pdt), "+r"(done0)::"memory");
    const unsigned epoch1 = (done0 >> 7) + 1u;
    const uint32_t tag = epoch1 & 1u;

    const int st = tid & 127;
    const uint32_t ub = sb + OFF_U + w4 * U_STRIDE + 256, spare = sb + (w4 < 2 ? OFF_SP0 : OFF_SP1) + (w4 & 1) * 4096;

    auto stg_of = [&](int w) { return w < 8 ? sb + 3 * SLOT + w * 7296 : sb + 2 * SLOT + (w & 3) * 7296; };
    float kc[24];
#pragma unroll
    for (int t = 0; t < 24; t++) kc[t] = 0.f;
    auto handoff = [&](int src) {
        mbar_wait(bar + 8 * (BAR_KS + w4), 0);
#pragma unroll
        for (int t = 0; t < 5; t++)
            sts128(buf + src * 2560 + (t * 32 + lane) * 16, __float_as_uint(kc[4 * t]), __float_as_uint(kc[4 * t + 1]), __float_as_uint(kc[4 * t + 2]), __float_as_uint(kc[4 * t + 3]));
        if (lane == 0) sts32(buf + 7680 + src * 4, __float_as_uint(kc[20]));
        __syncwarp();
        if (lane == 0) mbar_arrive(bar + 8 * (BAR_KP + w4));
    };
    {
        const float dt = bf_round(expf((ch & 1) ? bf_hi(pdt) : bf_lo(pdt)));
        const uint32_t stg = (warp >> 2) == 2 ? buf : stg_of(warp);
        const int sh = ((warp >> 2) & 1) * 16;
        auto pick = [&](uint32_t v) { return __uint_as_float((v >> sh) << 16); };
        const float ea = bf_round(ex2(pick(pla) * 1.4426950408889634f));
        const float arl = (-ea * dt) * 1.4426950408889634f, ait = (pick(pai) * dt) * 0.15915494309189535f;
        cf C2; C2.re = 2.0f * (pick(pcr) * dt); C2.im = 2.0f * (pick(pci) * dt);
        const cf z1 = cexp_p(arl, ait, 1.0f), z128 = cexp_p(arl, ait, 128.0f);
        const cf z2 = cmul(z1, z1), z4 = cmul(z2, z2);
        cf z8 = cmul(z4, z4); z8.im = -z8.im;
        const uint32_t sa0 = stg + (lane >> 3) * 128 + (((lane & 7) ^ (lane >> 3)) << 4), sa1 = (sa0 ^ 64) + 512;
        uint32_t w[60];
        auto put = [&](int row, const cf& v) {
            w[row] = pack2(v.re, v.im);
            if ((row & 3) == 3) stsm4(((row & 4) ? sa1 : sa0) + (row >> 3) * 1024, w[row - 3], w[row - 2], w[row - 1], w[row]);
        };
        {
            const cf z16 = cmul(z8, z8);
            cf e; e.re = 1.f; e.im = 0.f;
            cf o = z8;
            put(0, e); put(1, o);
            e = z16; put(2, e);
#pragma unroll
            for (int b = 3; b < 16; b += 2) {
                o = cmul(o, z16); put(b, o);
                if (b + 1 < 16) { e = cmul(e, z16); put(b + 1, e); }
            }
        }
        cf h[8];
        h[0] = C2; h[1] = cmul(h[0], z1);
#pragma unroll
        for (int r = 2; r < 8; r++) h[r] = cmul(h[r - 2], z2);
#pragma unroll
        for (int r = 0; r < 8; r++) put(16 + r, h[r]);
#pragma unroll
        for (int r = 0; r < 8; r++) { h[r] = cmul(h[r], z128); put(24 + r, h[r]); }
#pragma unroll
        for (int al = 0; al < 2; al++)
#pragma unroll
            for (int r = 0; r < 4; r++) { h[2 * r] = cmul(h[2 * r], z128); put(32 + al * 4 + r, h[2 * r]); }
#pragma unroll
        for (int al = 0; al < 4; al++)
#pragma unroll
            for (int r = 0; r < 2; r++) { h[4 * r] = cmul(h[4 * r], z128); put(40 + al * 2 + r, h[4 * r]); }
#pragma unroll
        for (int al = 0; al < 8; al++) { h[0] = cmul(h[0], z128); put(48 + al, h[0]); }
        h[0] = cmul(h[0], z128);
        sts32(stg + 56 * 128 + lane * 4, pack2(h[0].re, h[0].im));
        __syncwarp();
        const int lr = lane & 7, lm = lane >> 3;
#pragma unroll
        for (int kp = 0; kp < 2; kp++) {
            uint32_t a0[4], a1[4];
            ldsm4(a0, stg + ((lm & 1) * 8 + lr) * 128 + (((4 * kp + (lm >> 1)) ^ lr) << 4));
            ldsm4(a1, stg + ((lm & 1) * 8 + lr) * 128 + (((4 * kp + 2 + (lm >> 1)) ^ lr) << 4));
#pragma unroll
            for (int t = 0; t < 6; t++) {
                uint32_t b[4];
                ldsm4(b, stg + (16 + 8 * t + lr) * 128 + (((4 * kp + lm) ^ lr) << 4));
                mma16816(kc + 4 * t, a0[0], a0[1], a0[2], a0[3], b[0], b[1]);
                mma16816(kc + 4 * t, a1[0], a1[1], a1[2], a1[3], b[2], b[3]);
            }
        }
        __syncwarp();
        asm volatile("fence.proxy.async.shared::cta;" ::: "memory");
        const uint32_t cnt = 1u + (__float_as_uint(kc[0] + kc[23]) == 0xffc12345u);
        if (lane == 0) asm volatile("mbarrier.arrive.shared::cta.b64 _,[%0],%1;" ::"r"(bar + 8 * (warp < 8 ? BAR_KG : (warp < 12 ? BAR_KS + w4 : BAR_KGA))), "r"(cnt) : "memory");
        if (warp < 8) handoff(warp >> 2);
    }

    if (warp < 8) {
        const int wg = warp >> 2;
        float acc[96];
        const int srow = warp * 16 + (lane & 15);
        const uint32_t srow_a = srow * 128;
        const int sx = srow & 7, shi = lane >> 4;
        const uint64_t da0 = mkdesc(sb + wg * 8192, 16, 1024), db0 = mkdesc(sb + 16384, 8192, 1024);
#pragma unroll 1
        for (int kb = 0; kb < 8; kb++) {
            const int s = kb & 3;
            const uint64_t da = da0 + s * (SLOT >> 4), db = db0 + s * (SLOT >> 4);
            mbar_wait(bar + 8 * (BAR_FULL + s), kb >> 2);
            wg_fence();
#pragma unroll
            for (int k = 0; k < 4; k++) wgmma192(acc, da + 2 * k, db + 128 * k, kb | k);
            wg_commit();
            wg_wait<1>();
            if (lane == 0 && kb > 0) mbar_arrive(bar + 8 * (BAR_EMPTY + ((kb - 1) & 3)));
        }
        mbar_wait(bar + 8 * BAR_WPHI, 0);
        wg_wait<0>();
        fence_regs<96>(acc);
        asm volatile("setmaxnreg.inc.sync.aligned.u32 160;");
        if (lane == 0) mbar_arrive(bar + 8 * BAR_DONE);
        uint32_t in[16], qa[16];
        mbar_wait(bar + 8 * BAR_DONE, 0);
#pragma unroll
        for (int r = 0; r < 16; r++) {
            in[r] = pack2(acc[32 + 2 * r], acc[32 + 2 * r + 1]);
            qa[r] = pack2(acc[2 * r], acc[2 * r + 1]);
        }
#pragma unroll
        for (int hh = 0; hh < 4; hh++)
            stsm4(sb + OFF_V + (hh >> 1) * 16384 + srow_a + (((2 * (hh & 1) + shi) ^ sx) << 4), pack2(acc[64 + 8 * hh], acc[65 + 8 * hh]),
                  pack2(acc[66 + 8 * hh], acc[67 + 8 * hh]), pack2(acc[68 + 8 * hh], acc[69 + 8 * hh]), pack2(acc[70 + 8 * hh], acc[71 + 8 * hh]));
        sts128(sb + OFF_V + shi * 16384 + srow_a + ((4 ^ sx) << 4), 0x3f803f80u, 0x3f803f80u, 0x3f803f80u, 0x3f803f80u);
        const uint32_t wphi_a = sb + OFF_WPHI + (lane & 15) * 32 + (lane >> 4) * 16;
        uint32_t pq[4][8];
#pragma unroll 1
        for (int it = 0; it < 2; it++) {
            hedgehog4(in, wphi_a, pq);
            if (it == 1) break;
#pragma unroll
            for (int hs = 0; hs < 8; hs++) {
                float c[4] = {0.f, 0.f, 0.f, 0.f};
                const uint32_t* o = pq[hs >> 1] + 4 * (hs & 1);
                mma16816(c, o[0], o[1], o[2], o[3], 0x3f803f80u, 0x3f803f80u);
                const float r0 = rcp(c[0]), r1 = rcp(c[2]);
                const uint32_t s0 = pack2(r0, r0), s1 = pack2(r1, r1);
                stsm4(sb + OFF_P + (hs >> 2) * 16384 + srow_a + (((2 * (hs & 3) + shi) ^ sx) << 4), hmul2(o[0], s0), hmul2(o[1], s1), hmul2(o[2], s0), hmul2(o[3], s1));
            }
            asm volatile("fence.proxy.async.shared::cta;" ::: "memory");
            bar_named(1, 256);
            float d[32];
            const uint64_t dv = mkdesc(sb + OFF_V + wg * 16384, 16, 1024), dp = mkdesc(sb + OFF_P + wg * 16384, 16, 1024);
            wg_fence();
#pragma unroll
            for (int k = 0; k < 8; k++) wgmma64_tt(d, dv + 128 * k, dp + 128 * k, k != 0);
            wg_commit();
            mbar_wait(bar + 8 * BAR_PREP, 0);
            uint4* kvp = scr->kvp + bi * 544 + wg * 272 + (w4 < 2 ? w4 * 136 : 128) + lane;
            wg_wait<0>();
            fence_regs<32>(d);
            if (w4 < 2 || (w4 == 2 && lane < 4)) {
#pragma unroll
                for (int f = 0; f < 4; f++) {
                    const int i0 = 8 * (f >> 1) + 2 * (f & 1), i2 = 16 * (f >> 1) + 8 * (f & 1);
                    const float e0 = w4 == 0 ? d[i0] : (w4 == 1 ? d[16 + i0] : d[i2]), e1 = w4 == 0 ? d[i0 + 1] : (w4 == 1 ? d[17 + i0] : d[i2 + 1]);
                    const float e2 = w4 == 0 ? d[i0 + 4] : (w4 == 1 ? d[20 + i0] : d[i2 + 4]), e3 = w4 == 0 ? d[i0 + 5] : (w4 == 1 ? d[21 + i0] : d[i2 + 5]);
                    st_rlx128(kvp + (w4 < 2 ? f * 32 : (f >> 1) * 136 + (f & 1) * 4), tag4(__float_as_uint(e0), __float_as_uint(e1), __float_as_uint(e2), __float_as_uint(e3), tag));
                }
            }
            __syncwarp();
            if (lane == 0) mbar_arrive(bar + 8 * BAR_PUB);
#pragma unroll
            for (int r = 0; r < 16; r++) in[r] = qa[r];
        }
        {
            uint4 kf[4][3];
            uint4* og = scr->o + ((bi_i * 8 + warp) * 32 + bi_j * 4) * 32 + lane;
#pragma unroll
            for (int hh = 0; hh < 4; hh++) {
                mbar_wait(bar + 8 * (BAR_KVF + hh), 0);
                {
                    const uint32_t ka = sb + OFF_KVF + hh * 1088;
                    kf[hh][0] = lds128(ka + lane * 32); kf[hh][1] = lds128(ka + lane * 32 + 16); kf[hh][2] = lds128(ka + 1024 + q * 16);
                }
                float c[6][4];
#pragma unroll
                for (int t = 0; t < 6; t++) { c[t][0] = c[t][1] = c[t][2] = c[t][3] = 0.f; }
                const uint32_t* a = pq[hh];
                const bool od = g & 1;
                mma16816(c[0], a[0], a[1], a[2], a[3], od ? 0x3f803f80u : kf[hh][2].x, od ? 0x3f803f80u : kf[hh][2].y);
                mma16816(c[1], a[4], a[5], a[6], a[7], od ? 0x3f803f80u : kf[hh][2].z, od ? 0x3f803f80u : kf[hh][2].w);
                mma16816(c[2], a[0], a[1], a[2], a[3], kf[hh][0].x, kf[hh][0].y);
                mma16816(c[3], a[0], a[1], a[2], a[3], kf[hh][0].z, kf[hh][0].w);
                mma16816(c[4], a[4], a[5], a[6], a[7], kf[hh][1].x, kf[hh][1].y);
                mma16816(c[5], a[4], a[5], a[6], a[7], kf[hh][1].z, kf[hh][1].w);
                uint32_t w[4];
#pragma unroll
                for (int k = 0; k < 2; k++) {
                    const float rho = c[0][2 * k + 1] * rcp(c[1][2 * k + 1]);
                    const float r = rcp(fmaf(c[0][2 * k + 1], 1e-6f, fmaf(rho, c[1][2 * k], c[0][2 * k]))), rr = r * rho;
                    w[k] = pack2(fmaf(c[4][2 * k], rr, c[2][2 * k] * r), fmaf(c[4][2 * k + 1], rr, c[2][2 * k + 1] * r));
                    w[2 + k] = pack2(fmaf(c[5][2 * k], rr, c[3][2 * k] * r), fmaf(c[5][2 * k + 1], rr, c[3][2 * k + 1] * r));
                }
                st_rlx128(og + hh * 32, tag4(w[0], w[1], w[2], w[3], tag));
            }
        }
        float oc[64];
        const int slab = bi_i * 8 + (bi_j >> 2) * 4 + w4;
        const uint8_t* ysrc = (const uint8_t*)scr->y + (size_t)((bi_j & 3) * 32 + wg * 16 + (q >> 1)) * 16384 + slab * 128 + g * 16 + (q & 1) * 8;
        const unsigned* gp = scr->g + (slab * 8 + (g >> 1)) * 8 + (g & 1) * 4;
        uint2 yv[8]; unsigned g0, g1;
        {
            const uint4* osrc = scr->o + (slab * 32 + wg * 16) * 32 + lane;
            uint4 fr[16];
            const unsigned* probe = (const unsigned*)(osrc - lane + ((lane & 3) * 4 + 3) * 32 + 31) + 2;
            unsigned miss = ~0u;
            int n = 0;
            auto fetch = [&](int s) {
#pragma unroll 1
                while ((miss >> s) & 1) { miss = __ballot_sync(~0u, (ld_rlx(probe) ^ tag) & 1); if (++n > SPIN_LIMIT) break; }
#pragma unroll
                for (int k = 4 * s; k < 4 * s + 4; k++) fr[k] = ld_rlx128(osrc + k * 32);
            };
            const uint64_t dw = mkdesc(sb + wg * 2 * SLOT, wg ? 32768 : SLOT, 1024);
            auto mma = [&](int s) {
#pragma unroll 1
                while (__builtin_expect(__any_sync(~0u, (bad4(fr[4 * s], tag) | bad4(fr[4 * s + 1], tag) | bad4(fr[4 * s + 2], tag) | bad4(fr[4 * s + 3], tag)) & 1), 0)) {
#pragma unroll
                    for (int k = 4 * s; k < 4 * s + 4; k++) fr[k] = ld_rlx128(osrc + k * 32);
                    if (++n > SPIN_LIMIT) break;
                }
                wg_fence();
#pragma unroll
                for (int hh = 0; hh < 4; hh++) wgmma128_rs(oc, fr[4 * s + hh], dw + 128 * (4 * s + hh), (s | hh) != 0);
                wg_commit();
            };
            fetch(0); fetch(1);
            mbar_wait(bar + 8 * (wg ? BAR_WO2 : BAR_WO), 0);
            mma(0); fetch(2); mma(1); fetch(3);
            wg_wait<1>();
#pragma unroll
            for (int nt = 0; nt < 8; nt++) yv[nt] = ld_rlx64(ysrc + nt * 32768);
            g0 = ld_rlx(gp); g1 = ld_rlx(gp + 32);
            mma(2); mma(3);
            {
#pragma unroll 1
                while (true) {
                    uint32_t bad = (g0 ^ tag) | (g1 ^ tag);
#pragma unroll
                    for (int nt = 0; nt < 8; nt++) bad |= yv[nt].x ^ tag;
                    if (!__any_sync(~0u, bad & 1)) break;
#pragma unroll
                    for (int nt = 0; nt < 8; nt++) if ((yv[nt].x ^ tag) & 1) yv[nt] = ld_rlx64(ysrc + nt * 32768);
                    g0 = ld_rlx(gp); g1 = ld_rlx(gp + 32);
                    if (++n > SPIN_LIMIT) break;
                }
            }
        }
        {
            const float ga = bf_hi(g0), gb = bf_hi(g1);
            const float ha = bf_round(1.0f - ga), hb = bf_round(1.0f - gb);
            float yb[32];
#pragma unroll
            for (int nt = 0; nt < 8; nt++) {
                yb[4 * nt] = ha * bf_lo(yv[nt].x); yb[4 * nt + 1] = ha * bf_hi(yv[nt].x);
                yb[4 * nt + 2] = hb * bf_lo(yv[nt].y); yb[4 * nt + 3] = hb * bf_hi(yv[nt].y);
            }
            fence_regs<32>(yb);
            const uint32_t xw = sb + wg * 2 * SLOT + (tid & 127) * 16, xr = sb + (wg ^ 1) * 2 * SLOT + (tid & 127) * 16;
            wg_wait<0>();
            fence_regs<64>(oc);
            bar_named(3 + wg, 128);
#pragma unroll
            for (int r = 0; r < 8; r++)
                sts128(xw + r * 2048, __float_as_uint(oc[32 + 4 * r]), __float_as_uint(oc[33 + 4 * r]), __float_as_uint(oc[34 + 4 * r]), __float_as_uint(oc[35 + 4 * r]));
#pragma unroll
            for (int r = 0; r < 32; r++) yb[r] = fmaf((r & 2) ? gb : ga, oc[r], yb[r]);
            bar_named(1, 256);
            uint32_t w[8][2];
#pragma unroll
            for (int nt = 0; nt < 8; nt++) {
                const uint4 p = lds128(xr + nt * 2048);
                w[nt][0] = pack2(fmaf(ga, __uint_as_float(p.x), yb[4 * nt]), fmaf(ga, __uint_as_float(p.y), yb[4 * nt + 1]));
                w[nt][1] = pack2(fmaf(gb, __uint_as_float(p.z), yb[4 * nt + 2]), fmaf(gb, __uint_as_float(p.w), yb[4 * nt + 3]));
            }
            const uint32_t ob = sb + wg * 2 * SLOT + 16384 + w4 * 2048;
#pragma unroll
            for (int nt = 0; nt < 8; nt += 2)
                stsm4(ob + (lane & 15) * 128 + (((nt + shi) ^ (lane & 7)) << 4), w[nt][0], w[nt][1], w[nt + 1][0], w[nt + 1][1]);
            __syncwarp();
            bf16* op = out + (size_t)(slab * 16) * 512 + (bi_j & 3) * 128 + wg * 64 + (lane & 7) * 8;
#pragma unroll
            for (int it = 0; it < 4; it++) {
                const int r = it * 4 + (lane >> 3);
                uint4 v = lds128(ob + r * 128 + (((lane & 7) ^ (r & 7)) << 4));
                *(uint4*)(op + r * 512) = v;
            }
        }
    } else if (warp < 12) {
        if (warp == 8) {
            mbar_wait(bar + 8 * BAR_KGA, 0);
            if (lane == 0) load_stage(2);
            mbar_wait(bar + 8 * BAR_KG, 0);
            if (lane == 0) load_stage(3);
            __syncwarp();
        }
        if (warp == 8) {
#pragma unroll 1
            for (int kb = 0; kb < 6; kb++) {
                const int s = kb & 3;
                mbar_wait(bar + 8 * (BAR_EMPTY + s), kb >> 2);
                if (kb == xkb) mbar_wait(bar + 8 * BAR_XT, 0);
                if (lane == 0) {
                    if (kb < 4) load_stage(kb + 4);
                    else {
                        mbar_expect(bar + 8 * BAR_WO, 32768);
                        tma2d(sb + s * SLOT, &mwo, (bi_j & 3) * 128 + s * 64, 0, bar + 8 * BAR_WO);
                        if (kb == 5) mbar_arrive(bar + 8 * BAR_SP2);
                    }
                }
                __syncwarp();
            }
        } else if (warp == 9) {
            const int row = bi_j * 16 + (lane >> 1), half = lane & 1;
            unsigned* gp = scr->g + (bi_i * 64 + bi_j * 8) * 8 + lane * 2;
            st_rlx64(gp, tag ^ 1u, tag ^ 1u);
            float gs0 = 0.f, gs1 = 0.f;
            mbar_wait(bar + 8 * BAR_WPHI, 0);
#pragma unroll 1
            for (int kb = 0; kb < 8; kb++) {
                const int s = kb & 3;
                mbar_wait(bar + 8 * (BAR_FULL + s), kb >> 2);
#pragma unroll
                for (int c = 0; c < 4; c++) {
                    const uint4 xv = lds128(sb + s * SLOT + row * 128 + (((half * 4 + c) ^ (row & 7)) << 4));
                    const uint4 gw = lds128(sb + OFF_GW + ((kb + rot) & 7) * 128 + half * 64 + c * 16);
                    const uint32_t p0 = hmul2(xv.x, gw.x), p1 = hmul2(xv.y, gw.y), p2 = hmul2(xv.z, gw.z), p3 = hmul2(xv.w, gw.w);
                    gs0 += (bf_lo(p0) + bf_lo(p1)) + (bf_lo(p2) + bf_lo(p3));
                    gs1 += (bf_hi(p0) + bf_hi(p1)) + (bf_hi(p2) + bf_hi(p3));
                }
                const uint32_t cnt = 1u + (__float_as_uint(gs0 + gs1) == 0xffc12345u);
                if (lane == 0) asm volatile("mbarrier.arrive.shared::cta.b64 _,[%0],%1;" ::"r"(bar + 8 * (kb < 7 ? BAR_EMPTY + s : BAR_DONE)), "r"(cnt) : "memory");
                __syncwarp();
            }
            float gs = gs0 + gs1;
            gs += __shfl_xor_sync(~0u, gs, 1);
            const uint32_t gv = __float_as_uint(bf_round(rcp(1.0f + ex2(-1.4426950408889634f * bf_round(gs))))) | tag;
            st_rlx64(gp, gv, gv);
        }
        mbar_wait(bar + 8 * (BAR_KP + w4), 0);
#pragma unroll
        for (int t = 0; t < 15; t++) {
            const uint4 v = lds128(buf + (t * 32 + lane) * 16);
            kc[4 * (t % 5)] += __uint_as_float(v.x); kc[4 * (t % 5) + 1] += __uint_as_float(v.y); kc[4 * (t % 5) + 2] += __uint_as_float(v.z); kc[4 * (t % 5) + 3] += __uint_as_float(v.w);
        }
        {
            const uint4 v = lds128(buf + 7680);
            kc[20] += __uint_as_float(v.x) + __uint_as_float(v.y) + __uint_as_float(v.z);
            const uint32_t cnt = 1u + (__float_as_uint(kc[20] + kc[19] + kc[0]) == 0xffc12345u);
            if (lane == 0) asm volatile("mbarrier.arrive.shared::cta.b64 _,[%0],%1;" ::"r"(bar + 8 * (BAR_KD + w4)), "r"(cnt) : "memory");
            __syncwarp();
        }
        if (lane == 0) kc[4 * 0 + 0] += ((ch & 1) ? bf_hi(pds) : bf_lo(pds));
        const uint32_t k1024 = __shfl_sync(~0u, pack2(kc[4 * 4 + 0], 0.f), 0);
#pragma unroll
        for (int i = 0; i < 2; i++) {
            const int be = g + 8 * i;
#pragma unroll
            for (int t = 0; t < 2; t++) {
                const uint32_t a = kb_ + (KW_D + 128 * t + 8 * be + 2 * q) * 4;
                const uint32_t w = pack2(kc[4 * t + 2 * i + 1], kc[4 * t + 2 * i]);
                sts32(a + 4, w); sts16(a, w >> 16); sts16(a + 10, w);
            }
            {
                const int p = 256 + 128 * (q >> 1) + 8 * be + 4 * (q & 1);
                const uint32_t a = kb_ + (KW_D + p) * 4;
                const uint32_t w = pack2(kc[4 * 2 + 2 * i + 1], kc[4 * 2 + 2 * i]);
                const uint32_t aa = (w >> 16) | (w & 0xffff0000u);
                if (p != 256) { sts16(a - 4, aa); sts32(a, aa); } else sts16(a, aa);
                sts32(a + 4, aa); sts32(a + 8, w); sts16(a + 14, w);
            }
            {
                const int k = 64 + 16 * q + be;
                const uint32_t w = pack2(kc[4 * 3 + 2 * i], kc[4 * 3 + 2 * i + 1]);
                if (k != 64) sts16(kb_ + (KW_2 + ((k - 1) >> 1) - 24) * 4 + (k & 1) * 2, w);
                else {
                    const uint32_t a = kb_ + (KW_D + 511) * 4, aa = (w << 16) | (w & 0xffffu);
                    sts16(a, w); sts32(a + 4, aa); sts32(a + 8, aa); sts32(a + 12, aa); sts16(a + 18, w);
                }
                sts16(kb_ + (KW_2 + 48 + (k >> 1) - 24) * 4 + ((k & 1) ^ 1) * 2, w >> 16);
            }
#pragma unroll
            for (int b = 0; b < 2; b++) {
                const int k = 64 + 8 * (2 * q + b) + (be >> 1);
                const uint32_t w = pack2(kc[4 * 4 + 2 * i + b], 0.f);
                if (!(be & 1) && k == 64) sts16(kb_ + (KW_2 + 63 - 24) * 4, w);
                else {
                    const uint32_t a = kb_ + (KW_3 + ((be & 1) ? 80 + k : k - 1) - 48) * 4;
                    sts16(a, w);
                    if (!((be & 1) && k == 127)) sts16(a + 6, w);
                }
            }
        }
        if (lane == 0) sts16(kb_ + (KW_3 + 127 - 48) * 4, pack2(kc[4 * 5 + 0], 0.f));
        __syncwarp();
        asm volatile("setmaxnreg.inc.sync.aligned.u32 136;");
        mbar_wait(bar + 8 * BAR_UR, 0);
        mbar_wait(bar + 8 * BAR_DONE, 0);
        float y[16][4];
#pragma unroll
        for (int nt = 0; nt < 16; nt++) { y[nt][0] = y[nt][1] = y[nt][2] = y[nt][3] = 0.f; }
        {
            uint32_t Bp[32], A[4][3], An[4][3];
            auto uaddr = [&](int rho) { const int R0 = (lane >> 4) * 64 + (lane & 7) - rho; return ub + (((2 * R0 + ((lane >> 3) & 1)) ^ ((R0 >> 2) & 1)) << 4); };
            const uint32_t kd = kb_ + (KW_D + g - 2 * q) * 4;
#pragma unroll 1
            for (int rho = 1; rho >= 0; rho--) {
                const uint32_t a = uaddr(rho), k = kd + 2048 + rho * 64;
#pragma unroll
                for (int i = 0; i < 8; i++) ldsm4(Bp + 4 * i, a + i * 256);
                const uint32_t a0 = lds32(k), a1 = lds32(k + 32), a2 = lds32(k - 32);
#pragma unroll
                for (int i = 0; i < 12; i++) mma16816(y[i + 4], a0, a1, a2, a0, Bp[4 * (i & 7) + 2 * (i >> 3)], Bp[4 * (i & 7) + 2 * (i >> 3) + 1]);
            }
#pragma unroll
            for (int ga = 0; ga < 4; ga++) { An[ga][0] = lds32(kd + ga * 512); An[ga][1] = lds32(kd + ga * 512 + 32); An[ga][2] = lds32(kd + ga * 512 - 32); }
#pragma unroll 1
            for (int rho = 0; rho < 8; rho++) {
#pragma unroll
                for (int ga = 0; ga < 4; ga++) {
                    const uint32_t a = kd + (rho + 1) * 64 + ga * 512;
                    A[ga][0] = An[ga][0]; A[ga][1] = An[ga][1]; A[ga][2] = An[ga][2];
                    An[ga][0] = lds32(a); An[ga][1] = lds32(a + 32); An[ga][2] = lds32(a - 32);
                }
                const uint32_t an = uaddr(rho + 1);
#pragma unroll
                for (int i = 0; i < 8; i++) {
#pragma unroll
                    for (int ga = 0; ga < 4; ga++) {
                        mma16816(y[i + ga], A[ga][0], A[ga][1], A[ga][2], A[ga][0], Bp[4 * i], Bp[4 * i + 1]);
                        if (i + 8 + ga < 16) mma16816(y[i + 8 + ga], A[ga][0], A[ga][1], A[ga][2], A[ga][0], Bp[4 * i + 2], Bp[4 * i + 3]);
                    }
                    ldsm4(Bp + 4 * i, an + i * 256);
                    __syncwarp();
                }
            }
        }
        mbar_wait(bar + 8 * BAR_WR, 0);
#pragma unroll 1
        for (int ph = 0; ph < 2; ph++) {
            uint32_t B[5][2];
            const uint32_t ka = kb_ + (KW_2 + ph * 48 + 8 + g - q) * 4;
#pragma unroll
            for (int dd = 0; dd < 5; dd++) { B[dd][0] = lds32(ka + dd * 32); B[dd][1] = lds32(ka + dd * 32 - 16); }
            const uint32_t wa = buf + ph * W3_OFF + ((lane & 7) + ((lane >> 3) & 1) + (lane >> 4) * 8) * 16;
#pragma unroll
            for (int s = 0; s < 12; s++) {
                uint32_t A[4];
                ldsm4t(A, wa + s * 256);
#pragma unroll
                for (int dd = 0; dd < 5; dd++)
                    if (s + 4 + dd < 16) mma16816(y[s + 4 + dd], A[0], A[1], A[2], A[3], B[dd][0], B[dd][1]);
            }
        }
        {
            const int ap = (lane & 7) + (lane >> 4) * 8;
            const uint32_t loff = ((2 * ap + ((lane >> 3) & 1)) ^ ((ap >> 2) & 1)) << 4;
#pragma unroll 1
            for (int ph = 0; ph < 2; ph++) {
                uint32_t B[8][2];
                const uint32_t wb = (ph ? spare : buf + W9_OFF) + loff;
                const uint32_t ka = kb_ + (KW_3 + ph * 80 + 16 + g - 2 * q) * 4;
#pragma unroll
                for (int dd = 0; dd < 8; dd++) { B[dd][0] = lds32(ka + dd * 32); B[dd][1] = lds32(ka + dd * 32 - 32); }
#pragma unroll
                for (int s = 0; s < 4; s++) {
                    uint32_t A[4];
                    ldsm4t(A, wb + s * 512);
#pragma unroll
                    for (int dd = 0; dd < 8; dd++)
                        if (8 + 2 * s + dd < 16) mma16816(y[8 + 2 * s + dd], A[0], A[1], A[2], A[3], B[dd][0], B[dd][1]);
                }
            }
            const uint32_t idw = (g == 2 * q) ? k1024 : ((g == 2 * q + 1) ? (k1024 << 16) : 0u);
#pragma unroll
            for (int s = 0; s < 4; s++) {
                uint32_t A[4];
                ldsm4t(A, spare + 2048 + loff + s * 512);
                mma16816(y[8 + 2 * s], A[0], A[1], A[2], A[3], idw, 0u);
                mma16816(y[9 + 2 * s], A[0], A[1], A[2], A[3], 0u, idw);
            }
        }
        __syncwarp();
#pragma unroll
        for (int nt = 0; nt < 16; nt++)
#pragma unroll
            for (int b = 0; b < 2; b++) sts32(buf + ((8 * nt + 2 * q + b) * 8 + g) * 4, pack2(y[nt][b], y[nt][2 + b]));
        bar_named(2, 128);
        uint4* yp = scr->y + bi * 1024 + st;
#pragma unroll
        for (int v = 0; v < 8; v++) {
            const uint32_t a = sb + OFF_BUF + (st + 128 * v) * 4;
            const uint32_t w0 = lds32(a), w1 = lds32(a + BUF_STRIDE), w2 = lds32(a + 2 * BUF_STRIDE), w3 = lds32(a + 3 * BUF_STRIDE);
            st_rlx128(yp + v * 128, tag4(__byte_perm(w0, w1, 0x5410), __byte_perm(w0, w1, 0x7632), __byte_perm(w2, w3, 0x5410), __byte_perm(w2, w3, 0x7632), tag));
        }
    } else {
        const int qq = (bi_i & 2) + ((lane >> 1) & 1);
        uint2* kvf_h = (uint2*)(scr->kvf + (bi_j * 4 + (bi_i >> 2)) * 68);
        auto windows = [&](int rhi, int rlo) {
#pragma unroll 1
            for (int rho = rhi; rho >= rlo; rho--) {
                const int ci = lane + 32 * rho;
                uint4 e4[4];
#pragma unroll
                for (int v = 0; v < 4; v++) { const int cc = ci - 3 + v; e4[v] = lds128(ub + ((cc ^ ((cc >> 3) & 1)) << 4)); }
                float S[29];
                const uint32_t* ew = (const uint32_t*)e4;
                S[3] = 0.f;
#pragma unroll
                for (int k = 4; k <= 28; k++) S[k] = S[k - 1] + ((k & 1) ? bf_hi(ew[k >> 1]) : bf_lo(ew[k >> 1]));
                auto win = [&](int lo, int hi, uint32_t a) {
                    sts128(a, pack2(S[hi] - S[lo - 1], S[hi + 1] - S[lo]), pack2(S[hi + 2] - S[lo + 1], S[hi + 3] - S[lo + 2]),
                           pack2(S[hi + 4] - S[lo + 3], S[hi + 5] - S[lo + 4]), pack2(S[hi + 6] - S[lo + 5], S[hi + 7] - S[lo + 6]));
                };
                win(14, 18, buf + W5_OFF + 16 + ci * 16); win(19, 21, buf + W3_OFF + 16 + ci * 16);
                if (rho < 4) {
                    const uint32_t sw = (ci ^ ((ci >> 3) & 1)) << 4;
                    win(4, 12, buf + W9_OFF + sw); win(13, 19, spare + sw); win(20, 21, spare + 2048 + sw);
                }
            }
        };
        {
            mbar_wait(bar + 8 * (BAR_FULL + xkb), 0);
#pragma unroll 1
            for (int hf = 0; hf < 2; hf++) {
                const int r = w4 * 32 + hf * 16 + (lane & 15);
                uint32_t* xt = (uint32_t*)scr->xt + ((xkb + rot) * 16 + (g >> 2)) * 4096 + (bi_i * 16 + w4 * 4 + hf * 2) * 16 + (g & 3) * 4 + q;
#pragma unroll
                for (int cb = 0; cb < 8; cb += 2) {
                    uint32_t v[4];
                    ldsm4t(v, sb + xkb * SLOT + r * 128 + (((cb + (lane >> 4)) ^ (r & 7)) << 4));
                    xt[cb * 8192] = v[0]; xt[cb * 8192 + 16] = v[1]; xt[cb * 8192 + 8192] = v[2]; xt[cb * 8192 + 8192 + 16] = v[3];
                }
            }
            __syncwarp();
            if (lane == 0) mbar_arrive(bar + 8 * BAR_XT);
            handoff(2);
            asm volatile("setmaxnreg.dec.sync.aligned.u32 56;");
            if (lane == 0) asm volatile("red.release.gpu.global.add.u32 [%0],2;" ::"l"(scr->xcnt + (xkb + rot) * 32) : "memory");
            __syncwarp();
            {
                const uint32_t old = tag ^ 1u;
                const uint4 z4 = make_uint4(old, 0, old, 0);
#pragma unroll
                for (int v = 0; v < 5; v++) if (v < 4 || st < 32) st_rlx128(scr->kvp + bi * 544 + v * 128 + st, z4);
                if (st < 16) st_rlx128(scr->o + ((bi_i * 8 + (st >> 1)) * 32 + bi_j * 4 + 3) * 32 + 30 + (st & 1), z4);
                if (lane < 8) st_rlx64(kvf_h + ((bi_i & 3) * 8 + w4 * 2 + (lane & 1)) * 4 + (lane >> 1), old, 0);
                if (st < 4 && !(bi_i & 1)) st_rlx64(kvf_h + (64 + qq) * 2 + (lane & 1), old, 0);
                __syncwarp();
                if (lane == 0) mbar_arrive(bar + 8 * BAR_PREP);
            }
            int n = 0;
#pragma unroll 1
            while (__any_sync(~0u, (int)(ld_acq(scr->xcnt + bi_j * 32) - (epoch1 << 7)) < 0)) { if (++n > SPIN_LIMIT) break; }
            uint4 ur[8];
#pragma unroll
            for (int v = 0; v < 8; v++) ur[v] = __ldcg(scr->xt + bi * 1024 + st + 128 * v);
            mbar_wait(bar + 8 * BAR_KG, 0);
            if (lane < 16) sts128(ub - 256 + lane * 16, 0, 0, 0, 0);
#pragma unroll
            for (int v = 0; v < 8; v++) {
                const int ci = (st >> 2) + 32 * v;
                sts128(sb + OFF_U + (st & 3) * U_STRIDE + 256 + ((ci ^ ((ci >> 3) & 1)) << 4), ur[v].x, ur[v].y, ur[v].z, ur[v].w);
            }
            __syncwarp();
            if (lane == 0) mbar_arrive(bar + 8 * BAR_UR);
            mbar_wait(bar + 8 * BAR_UR, 0);
            mbar_wait(bar + 8 * (BAR_KD + w4), 0);
            if (lane < 2) sts128(buf + lane * W3_OFF, 0, 0, 0, 0);
            windows(5, 4);
        }
        mbar_wait(bar + 8 * BAR_SP2, 0);
        windows(3, 0);
        __syncwarp();
        if (lane == 0) mbar_arrive(bar + 8 * BAR_WR);
        {
            const bool zw = st < 32 && !(bi_i & 1);
            const uint4* src = scr->kvp + bi_j * (16 * 544) + (bi_i >> 2) * 136;
            const uint4* zsrc = src + (lane >> 2) * (2 * 544) + 128 + (lane & 1) * 4 + qq;
            src += (lane >> 3) * (4 * 544) + ((lane >> 1) & 3) * 32 + (bi_i & 3) * 8 + w4 * 2 + (lane & 1);
            mbar_wait(bar + 8 * BAR_PUB, 0);
            uint4 v[6];
#pragma unroll
            for (int k = 0; k < 6; k++) v[k] = make_uint4(tag ^ 1u, 0, 0, 0);
            int n = 0;
#pragma unroll 1
            while (true) {
#pragma unroll
                for (int k = 0; k < 6; k++) if ((bad4(v[k], tag) & 1) && (k < 4 || zw)) v[k] = ld_rlx128(k < 4 ? src + k * 544 : zsrc + (k - 4) * 544);
                if (!__any_sync(~0u, (bad4(v[0], tag) | bad4(v[1], tag) | bad4(v[2], tag) | bad4(v[3], tag) | (zw ? bad4(v[4], tag) | bad4(v[5], tag) : 0u)) & 1)) break;
                if (++n > SPIN_LIMIT) break;
            }
            float f[8];
            const float* vf = (const float*)v;
#pragma unroll
            for (int r = 0; r < 4; r++) {
                f[r] = (vf[r] + vf[4 + r]) + (vf[8 + r] + vf[12 + r]);
                f[4 + r] = vf[16 + r] + vf[20 + r];
                f[4 + r] += __shfl_xor_sync(~0u, f[4 + r], 4);
            }
#pragma unroll
            for (int o = 8; o <= 16; o <<= 1)
#pragma unroll
                for (int r = 0; r < 8; r++) f[r] += __shfl_xor_sync(~0u, f[r], o);
            if (lane < 8) st_rlx64(kvf_h + ((bi_i & 3) * 8 + w4 * 2 + (lane & 1)) * 4 + (lane >> 1), tagw(pack2(f[0], f[1]), tag), pack2(f[2], f[3]));
            if (zw && lane < 4) st_rlx64(kvf_h + (64 + qq) * 2 + (lane & 1), tagw(pack2(f[4], f[5]), tag), pack2(f[6], f[7]));
        }
        {
            const uint4* kp = scr->kvf + (bi_j * 4 + w4) * 68 + lane;
            uint4 v0 = make_uint4(tag ^ 1u, 0, 0, 0), v1 = v0, v2 = make_uint4(lane < 4 ? tag ^ 1u : tag, 0, tag, 0);
            int n = 0;
#pragma unroll 1
            while (true) {
                if (bad4(v0, tag) & 1) v0 = ld_rlx128(kp);
                if (bad4(v1, tag) & 1) v1 = ld_rlx128(kp + 32);
                if (bad4(v2, tag) & 1) v2 = ld_rlx128(kp + 64);
                if (!__any_sync(~0u, (bad4(v0, tag) | bad4(v1, tag) | bad4(v2, tag)) & 1)) break;
                if (++n > SPIN_LIMIT) break;
            }
            const uint32_t a = sb + OFF_KVF + w4 * 1088 + lane * 16;
            sts128(a, v0.x, v0.y, v0.z, v0.w);
            sts128(a + 512, v1.x, v1.y, v1.z, v1.w);
            if (lane < 4) sts128(a + 1024, v2.x, v2.y, v2.z, v2.w);
            __syncwarp();
            if (lane == 0) mbar_arrive(bar + 8 * (BAR_KVF + w4));
        }
        if (warp == 13) {
            if (lane == 0) {
                mbar_expect(bar + 8 * BAR_WO2, 65536);
                tma2d(sb + OFF_P, &mwo, (bi_j & 3) * 128 + 64, 256, bar + 8 * BAR_WO2);
                tma2d(sb + OFF_V, &mwo, (bi_j & 3) * 128, 256, bar + 8 * BAR_WO2);
            }
        }
    }
    __syncwarp();
    if (lane == 0) {
        unsigned old;
        asm volatile("atom.acq_rel.cta.shared.add.u32 %0,[%1],1;" : "=r"(old) : "r"(bar + OFF_CNT) : "memory");
        if (old == 15) {
            atomicAdd(scr->done, 1u);
        }
    }
}

typedef CUresult (*EncFn)(CUtensorMap*, CUtensorMapDataType, cuuint32_t, void*, const cuuint64_t*, const cuuint64_t*, const cuuint32_t*,
                          const cuuint32_t*, CUtensorMapInterleave, CUtensorMapSwizzle, CUtensorMapL2promotion, CUtensorMapFloatOOBfill);

extern "C" void kernel_launch(void* const* d_in, const int* in_sizes, int n_in, void* d_out, int out_size) {
    static EncFn enc = nullptr;
    static Scratch* scr = nullptr;
    if (!enc) {
        cudaGetSymbolAddress((void**)&scr, g_scr);
        cudaDriverEntryPointQueryResult qr;
        cudaGetDriverEntryPoint("cuTensorMapEncodeTiled", (void**)&enc, cudaEnableDefault, &qr);
        cudaFuncSetAttribute(fused_kernel, cudaFuncAttributeMaxDynamicSharedMemorySize, SMEM_BYTES);
    }
    CUtensorMap mx, mw, mwo;
    const cuuint32_t es[3] = {1, 1, 1};
    {
        cuuint64_t d[2] = {512, 2048}, s[1] = {1024}; cuuint32_t b[2] = {64, 128};
        enc(&mx, CU_TENSOR_MAP_DATA_TYPE_BFLOAT16, 2, d_in[0], d, s, b, es, CU_TENSOR_MAP_INTERLEAVE_NONE, CU_TENSOR_MAP_SWIZZLE_128B,
            CU_TENSOR_MAP_L2_PROMOTION_L2_128B, CU_TENSOR_MAP_FLOAT_OOB_FILL_NONE);
    }
    {
        cuuint64_t d[3] = {512, 512, 3}, s[2] = {3072, 1024}; cuuint32_t b[3] = {64, 64, 3};
        enc(&mw, CU_TENSOR_MAP_DATA_TYPE_BFLOAT16, 3, d_in[1], d, s, b, es, CU_TENSOR_MAP_INTERLEAVE_NONE, CU_TENSOR_MAP_SWIZZLE_128B,
            CU_TENSOR_MAP_L2_PROMOTION_L2_128B, CU_TENSOR_MAP_FLOAT_OOB_FILL_NONE);
    }
    {
        cuuint64_t d[2] = {512, 512}, s[1] = {1024}; cuuint32_t b[2] = {64, 256};
        enc(&mwo, CU_TENSOR_MAP_DATA_TYPE_BFLOAT16, 2, d_in[3], d, s, b, es, CU_TENSOR_MAP_INTERLEAVE_NONE, CU_TENSOR_MAP_SWIZZLE_128B,
            CU_TENSOR_MAP_L2_PROMOTION_L2_128B, CU_TENSOR_MAP_FLOAT_OOB_FILL_NONE);
    }
    fused_kernel<<<128, 512, SMEM_BYTES, cudaStreamPerThread>>>(
        scr, (const bf16*)d_in[5], (const bf16*)d_in[6], (const bf16*)d_in[7], (const bf16*)d_in[8], (const bf16*)d_in[9],
        (const bf16*)d_in[10], (const bf16*)d_in[2], (const bf16*)d_in[11], (bf16*)d_out, mx, mw, mwo);
}
```
